```python
import torch

def _softmax(x, axis=-1):
    return torch.softmax(x, dim=axis)
def _gelu(x):
    return torch.nn.functional.gelu(x, approximate="tanh")
def _silu(x):
    return torch.nn.functional.silu(x)
def _sigmoid(x):
    return torch.sigmoid(x)
def _layernorm(x, axis=-1, eps=1e-5):
    m = x.mean(dim=axis, keepdim=True)
    v = x.var(dim=axis, keepdim=True, unbiased=False)
    return (x - m) / torch.sqrt(v + eps)
def _scatter_add(tgt, idx, src, axis=0):
    return tgt.clone().index_add_(axis, idx, src)
def _segment_sum(src, seg, n):
    out = torch.zeros((n,) + src.shape[1:], dtype=src.dtype)
    return out.index_add_(0, seg, src)
def _pad(x, pw):
    flat = tuple(v for pair in reversed(pw) for v in pair)
    return torch.nn.functional.pad(x, flat)

kernel_name = 'interleave_layers__linear_kernel_hedgehog__sliding_local_dilated__prompt'

def setup_inputs():

    _w = (lambda a: (lambda t: t.to(torch.bfloat16) if t.is_floating_point() else t)(torch.as_tensor(a)))
    def _A_setup():
        B, S, D, H = 1, 2048, 1024, 32
        Dh = D // H
        return {
            "x": _w((lambda *s: torch.randn(*s, dtype=torch.bfloat16) * 0.05)(B, S, D)),
            "wqkv": _w((lambda *s: torch.randn(*s, dtype=torch.bfloat16) * 0.2)(D, 3 * D)),
            "w_phi": _w((lambda *s: torch.randn(*s, dtype=torch.bfloat16) * 0.2)(H, Dh, Dh) * (Dh ** -0.5)),
            "wo": _w((lambda *s: torch.randn(*s, dtype=torch.bfloat16) * 0.05)(D, D)),
        }
    _A_in = _A_setup()

    def _B_setup():
        B, S, D = 1, 2048, 1024
        return {
            "x": _w((lambda *s: torch.randn(*s, dtype=torch.bfloat16) * 0.05)(B, S, D)),
            "wqkv": _w((lambda *s: torch.randn(*s, dtype=torch.bfloat16) * 0.1)(D, 3 * D)),
            "wo": _w((lambda *s: torch.randn(*s, dtype=torch.bfloat16) * 0.05)(D, D)),
        }
    _B_in = _B_setup()

    return {
        "A_x": _A_in["x"],
        "A_wqkv": _A_in["wqkv"],
        "A_w_phi": _A_in["w_phi"],
        "A_wo": _A_in["wo"],
        "B_x": _B_in["x"],
        "B_wqkv": _B_in["wqkv"],
        "B_wo": _B_in["wo"],
    }

def reference(A_x, A_wqkv, A_w_phi, A_wo, B_x, B_wqkv, B_wo):
    def _A_ref(x, wqkv, w_phi, wo):
        B, S, D = x.shape
        H = 32; Dh = D // H
        qkv = (lambda x, *d: x.permute(*d))((x @ wqkv).reshape(B, S, 3, H, Dh), 2, 0, 3, 1, 4)
        q, k, v = qkv[0], qkv[1], qkv[2]
        pq = torch.einsum("bhsd,hdf->bhsf", q, w_phi)
        pk = torch.einsum("bhsd,hdf->bhsf", k, w_phi)
        phi_q = torch.concatenate([_softmax(pq, axis=-1), _softmax(-pq, axis=-1)], axis=-1)
        phi_k = torch.concatenate([_softmax(pk, axis=-1), _softmax(-pk, axis=-1)], axis=-1)
        kv = torch.einsum("bhsf,bhsd->bhfd", phi_k, v)
        z  = torch.einsum("bhsf->bhf", phi_k)
        num = torch.einsum("bhqf,bhfd->bhqd", phi_q, kv)
        den = torch.einsum("bhqf,bhf->bhq", phi_q, z)[..., None] + 1e-6
        o = num / den
        return (lambda x, *d: x.permute(*d))(o, 0, 2, 1, 3).reshape(B, S, D) @ wo

    def _B_ref(x, wqkv, wo):
        B, S, D = x.shape
        H = 32; Dh = D // H
        W, dil = 8, 2
        qkv = (lambda x, *d: x.permute(*d))((x @ wqkv).reshape(B, S, 3, H, Dh), 2, 0, 3, 1, 4)
        q, k, v = qkv[0], qkv[1], qkv[2]
        scale = Dh ** -0.5
        pos = torch.arange(S)
        off = torch.arange(W) * dil
        idx = pos[:, None] - off[None, :]
        mask = idx >= 0
        idx_c = torch.where(mask, idx, 0).reshape(-1)
        kg = k[:, :, idx_c, :].reshape(B, H, S, W, Dh)
        vg = v[:, :, idx_c, :].reshape(B, H, S, W, Dh)
        logits = torch.einsum("bhsd,bhswd->bhsw", q, kg) * scale
        logits = torch.where(mask[None, None, :, :], logits, -1e9)
        attn = _softmax(logits, axis=-1)
        o = torch.einsum("bhsw,bhswd->bhsd", attn, vg)
        return (lambda x, *d: x.permute(*d))(o, 0, 2, 1, 3).reshape(B, S, D) @ wo

    x = A_x
    x = x + _A_ref(_layernorm(x, axis=-1), A_wqkv, A_w_phi, A_wo)
    x = x + _B_ref(_layernorm(x, axis=-1), B_wqkv, B_wo)
    x = x + _A_ref(_layernorm(x, axis=-1), A_wqkv, A_w_phi, A_wo)
    x = x + _B_ref(_layernorm(x, axis=-1), B_wqkv, B_wo)
    return x
```

```cpp
#include <cuda_runtime.h>
#include <cuda_bf16.h>
#include <cuda.h>
#include <stdint.h>

typedef __nv_bfloat16 bf16;

constexpr int S_ = 2048, D_ = 1024;

struct __align__(128) Flag { unsigned int v; unsigned int pad[31]; };
__device__ __align__(1024) bf16 g_x[S_ * D_];
__device__ __align__(1024) bf16 g_o[S_ * D_];
__device__ __align__(1024) uint4 g_halo[2 * 2 * 128 * 512];
__device__ __align__(1024) float g_kv[2 * 2 * 8 * 8448];
__device__ __align__(1024) float2 g_stats[2 * 8 * S_];
__device__ __align__(1024) float g_cs[2 * 2 * 3072];
__device__ Flag g_kvflag[16], g_csflag[16];
__device__ __align__(128) unsigned int g_xf[16 * 32], g_of[16 * 32];
__device__ unsigned int g_epoch, g_err;
#define PROFT(cond, idx) asm volatile("" ::: "memory")

__device__ __forceinline__ uint32_t smem_u32(const void* p) { return (uint32_t)__cvta_generic_to_shared(p); }
__device__ __forceinline__ void mbar_init(uint32_t bar, uint32_t count) {
  asm volatile("mbarrier.init.shared::cta.b64 [%0], %1;" ::"r"(bar), "r"(count) : "memory");
}
__device__ __forceinline__ void mbar_expect_tx(uint32_t bar, uint32_t bytes) {
  asm volatile("mbarrier.arrive.expect_tx.shared::cta.b64 _, [%0], %1;" ::"r"(bar), "r"(bytes) : "memory");
}
__device__ __forceinline__ void mbar_arrive(uint32_t bar) {
  asm volatile("mbarrier.arrive.shared::cta.b64 _, [%0];" ::"r"(bar) : "memory");
}
__device__ __forceinline__ bool mbar_try_wait(uint32_t bar, uint32_t parity) {
  uint32_t ok;
  asm volatile("{\n.reg .pred p;\nmbarrier.try_wait.parity.shared::cta.b64 p, [%1], %2;\nselp.b32 %0, 1, 0, p;\n}\n"
               : "=r"(ok) : "r"(bar), "r"(parity) : "memory");
  return ok != 0;
}
__device__ __forceinline__ bool mbar_test_wait(uint32_t bar, uint32_t parity) {
  uint32_t ok;
  asm volatile("{\n.reg .pred p;\nmbarrier.test_wait.parity.shared::cta.b64 p, [%1], %2;\nselp.b32 %0, 1, 0, p;\n}\n"
               : "=r"(ok) : "r"(bar), "r"(parity) : "memory");
  return ok != 0;
}
__device__ __forceinline__ uint64_t gtimer() {
  uint64_t t; asm volatile("mov.u64 %0, %globaltimer;" : "=l"(t)); return t;
}
__device__ __forceinline__ void mbar_wait(uint32_t bar, uint32_t parity) {
  uint32_t n = 0;
#pragma unroll 1
  while (!mbar_try_wait(bar, parity)) {
    if (++n > (1u << 22)) { g_err = 1u; break; }
  }
}
__device__ __forceinline__ unsigned int ld_acquire(const unsigned int* p) {
  unsigned int v; asm volatile("ld.acquire.gpu.global.u32 %0, [%1];" : "=r"(v) : "l"(p) : "memory"); return v;
}
__device__ __forceinline__ void flag_add(unsigned int* p) {
  asm volatile("red.release.gpu.global.add.u32 [%0], 1;" ::"l"(p) : "memory");
}
__device__ __forceinline__ void flag_set(unsigned int* p, unsigned int v) {
  asm volatile("st.release.gpu.global.u32 [%0], %1;" ::"l"(p), "r"(v) : "memory");
}
template <int SLEEP>
__device__ __forceinline__ void src_wait(const unsigned int* f, unsigned int target, uint32_t need, uint32_t& ready, int lane) {
  uint32_t n = 0;
#pragma unroll 1
  while ((ready & need) != need) {
    const unsigned int v = ld_acquire(f + (lane & 15));
    ready = __ballot_sync(0xffffffffu, (int)(v - target) >= 0);
    if (SLEEP) { if ((ready & need) != need) __nanosleep(SLEEP); }
    if (++n > (1u << 20)) { g_err = 3u; break; }
  }
  __syncwarp();
}
__device__ __forceinline__ unsigned int ld_relaxed(const unsigned int* p) {
  unsigned int v; asm volatile("ld.relaxed.gpu.global.u32 %0, [%1];" : "=r"(v) : "l"(p) : "memory"); return v;
}
__device__ __forceinline__ uint4 ld_relaxed4(const uint4* p) {
  uint4 v; asm volatile("ld.relaxed.gpu.global.v4.u32 {%0,%1,%2,%3}, [%4];" : "=r"(v.x), "=r"(v.y), "=r"(v.z), "=r"(v.w) : "l"(p) : "memory"); return v;
}
__device__ __forceinline__ void st_relaxed4(uint4* p, uint32_t a, uint32_t b, uint32_t c, uint32_t d) {
  asm volatile("st.relaxed.gpu.global.v4.u32 [%0], {%1,%2,%3,%4};" ::"l"(p), "r"(a), "r"(b), "r"(c), "r"(d) : "memory");
}
template <int SLEEP>
__device__ __forceinline__ void flag_wait_t(const unsigned int* p, unsigned int target) {
  uint32_t n = 0;
#pragma unroll 1
  while ((int)(ld_acquire(p) - target) < 0) {
    if (SLEEP) __nanosleep(SLEEP);
    if (++n > (1u << 20)) { g_err = 2u; break; }
  }
}
__device__ __forceinline__ void flag_wait(const unsigned int* p, unsigned int target) { flag_wait_t<0>(p, target); }
__device__ __forceinline__ void flag_wait_slow(const unsigned int* p, unsigned int target) { flag_wait_t<256>(p, target); }
__device__ __forceinline__ void tma_load_2d(uint32_t dst, const CUtensorMap* tm, int c0, int c1, uint32_t bar) {
  asm volatile("cp.async.bulk.tensor.2d.shared::cluster.global.mbarrier::complete_tx::bytes [%0], [%1, {%2, %3}], [%4];"
               ::"r"(dst), "l"(tm), "r"(c0), "r"(c1), "r"(bar) : "memory");
}
__device__ __forceinline__ void tma_load_2d_mc(uint32_t dst, const CUtensorMap* tm, int c0, int c1, uint32_t bar, uint16_t mask) {
  asm volatile("cp.async.bulk.tensor.2d.shared::cluster.global.mbarrier::complete_tx::bytes.multicast::cluster [%0], [%1, {%2, %3}], [%4], %5;"
               ::"r"(dst), "l"(tm), "r"(c0), "r"(c1), "r"(bar), "h"(mask) : "memory");
}
__device__ __forceinline__ void mbar_wait_u(uint32_t bar, uint32_t parity) {
  uint32_t n = 0;
#pragma unroll 1
  while (!__all_sync(0xffffffffu, mbar_try_wait(bar, parity))) {
    if (++n > (1u << 22)) { g_err = 1u; break; }
  }
}
__device__ __forceinline__ void expect_tx_e(uint32_t bar, uint32_t bytes) {
  asm volatile("{\n.reg .pred p;\nelect.sync _|p, 0xffffffff;\n@p mbarrier.arrive.expect_tx.shared::cta.b64 _, [%0], %1;\n}\n" ::"r"(bar), "r"(bytes) : "memory");
}
__device__ __forceinline__ void tma_2d_e(uint32_t dst, const CUtensorMap* tm, int c0, int c1, uint32_t bar) {
  asm volatile("{\n.reg .pred p;\nelect.sync _|p, 0xffffffff;\n"
               "@p cp.async.bulk.tensor.2d.shared::cluster.global.mbarrier::complete_tx::bytes [%0], [%1, {%2, %3}], [%4];\n}\n"
               ::"r"(dst), "l"(tm), "r"(c0), "r"(c1), "r"(bar) : "memory");
}
__device__ __forceinline__ void tma_2d_mc_e(uint32_t dst, const CUtensorMap* tm, int c0, int c1, uint32_t bar) {
  asm volatile("{\n.reg .pred p;\nelect.sync _|p, 0xffffffff;\n"
               "@p cp.async.bulk.tensor.2d.shared::cluster.global.mbarrier::complete_tx::bytes.multicast::cluster [%0], [%1, {%2, %3}], [%4], %5;\n}\n"
               ::"r"(dst), "l"(tm), "r"(c0), "r"(c1), "r"(bar), "h"((uint16_t)3) : "memory");
}
__device__ __forceinline__ void tma_pf_e(const CUtensorMap* tm, int c0, int c1) {
  asm volatile("{\n.reg .pred p;\nelect.sync _|p, 0xffffffff;\n"
               "@p cp.async.bulk.prefetch.tensor.2d.L2.global.tile [%0, {%1, %2}];\n}\n" ::"l"(tm), "r"(c0), "r"(c1) : "memory");
}
__device__ __forceinline__ void tma_2d_to_e(uint32_t dst, const CUtensorMap* tm, int c0, int c1, uint32_t bar, uint32_t mask) {
  asm volatile("{\n.reg .pred p;\nelect.sync _|p, 0xffffffff;\n"
               "@p cp.async.bulk.tensor.2d.shared::cluster.global.mbarrier::complete_tx::bytes.multicast::cluster [%0], [%1, {%2, %3}], [%4], %5;\n}\n"
               ::"r"(dst), "l"(tm), "r"(c0), "r"(c1), "r"(bar), "h"((uint16_t)mask) : "memory");
}
__device__ __forceinline__ void tma_3d_mc_e(uint32_t dst, const CUtensorMap* tm, int c1, int c2, uint32_t bar) {
  asm volatile("{\n.reg .pred p;\nelect.sync _|p, 0xffffffff;\n"
               "@p cp.async.bulk.tensor.3d.shared::cluster.global.mbarrier::complete_tx::bytes.multicast::cluster [%0], [%1, {%6, %2, %3}], [%4], %5;\n}\n"
               ::"r"(dst), "l"(tm), "r"(c1), "r"(c2), "r"(bar), "h"((uint16_t)3), "r"(0) : "memory");
}
__device__ __forceinline__ uint32_t poll_flags(const unsigned int* f, unsigned int target, int lane) {
  const unsigned int v = ld_acquire(f + (lane & 15));
  const uint32_t r = __ballot_sync(0xffffffffu, (int)(v - target) >= 0);
  __syncwarp();
  return r;
}
__device__ __forceinline__ void mbar_arrive_cluster(uint32_t local_bar, uint32_t rank) {
  asm volatile("{\n.reg .b32 ra;\nmapa.shared::cluster.u32 ra, %0, %1;\nmbarrier.arrive.shared::cluster.b64 _, [ra];\n}\n"
               ::"r"(local_bar), "r"(rank) : "memory");
}
__device__ __forceinline__ void release2(uint32_t bar) { mbar_arrive_cluster(bar, 0); mbar_arrive_cluster(bar, 1); }
__device__ __forceinline__ void tma_store_2d(const CUtensorMap* tm, uint32_t src, int c0, int c1) {
  asm volatile("cp.async.bulk.tensor.2d.global.shared::cta.bulk_group [%0, {%2, %3}], [%1];"
               ::"l"(tm), "r"(src), "r"(c0), "r"(c1) : "memory");
}
__device__ __forceinline__ void bulk_store(void* dst, uint32_t src, uint32_t bytes) {
  asm volatile("cp.async.bulk.global.shared::cta.bulk_group [%0], [%1], %2;" ::"l"(dst), "r"(src), "r"(bytes) : "memory");
}
__device__ __forceinline__ void bulk_load(uint32_t dst, const void* src, uint32_t bytes, uint32_t bar) {
  asm volatile("cp.async.bulk.shared::cluster.global.mbarrier::complete_tx::bytes [%0], [%1], %2, [%3];" ::"r"(dst), "l"(src), "r"(bytes), "r"(bar) : "memory");
}
__device__ __forceinline__ void bulk_red_add(void* dst, uint32_t src, uint32_t bytes) {
  asm volatile("cp.reduce.async.bulk.global.shared::cta.bulk_group.add.f32 [%0], [%1], %2;" ::"l"(dst), "r"(src), "r"(bytes) : "memory");
}
__device__ __forceinline__ void bulk_commit() { asm volatile("cp.async.bulk.commit_group;" ::: "memory"); }
__device__ __forceinline__ void bulk_wait0() { asm volatile("cp.async.bulk.wait_group 0;" ::: "memory"); }
__device__ __forceinline__ void fence_async_smem() { asm volatile("fence.proxy.async.shared::cta;" ::: "memory"); }
__device__ __forceinline__ void fence_async_all() { asm volatile("fence.proxy.async.global;" ::: "memory"); }
__device__ __forceinline__ void wgmma_fence() { asm volatile("wgmma.fence.sync.aligned;" ::: "memory"); }
__device__ __forceinline__ void wgmma_commit() { asm volatile("wgmma.commit_group.sync.aligned;" ::: "memory"); }
template <int N> __device__ __forceinline__ void wgmma_wait() { asm volatile("wgmma.wait_group.sync.aligned %0;" ::"n"(N) : "memory"); }
__device__ __forceinline__ void cluster_arrive() { asm volatile("barrier.cluster.arrive.release.aligned;" ::: "memory"); }
__device__ __forceinline__ void cluster_wait() { asm volatile("barrier.cluster.wait.acquire.aligned;" ::: "memory"); }
template <int ID, int N> __device__ __forceinline__ void nbar() { asm volatile("bar.sync %0, %1;" ::"n"(ID), "n"(N) : "memory"); }
__device__ __forceinline__ uint64_t make_desc(uint32_t addr, uint32_t lbo_bytes, uint32_t sbo_bytes) {
  uint64_t d = 0;
  d |= (uint64_t)((addr & 0x3FFFF) >> 4);
  d |= (uint64_t)((lbo_bytes >> 4) & 0x3FFF) << 16;
  d |= (uint64_t)((sbo_bytes >> 4) & 0x3FFF) << 32;
  d |= (uint64_t)1 << 62;
  return d;
}
__device__ __forceinline__ uint64_t desc64(uint32_t lo, uint32_t hi) { return (uint64_t)lo | ((uint64_t)hi << 32); }
__device__ __forceinline__ uint32_t pack_bf16(float lo, float hi) {
  uint32_t r; asm("cvt.rn.bf16x2.f32 %0, %1, %2;" : "=r"(r) : "f"(hi), "f"(lo)); return r;
}
__device__ __forceinline__ uint32_t mul_bf16x2(uint32_t a, uint32_t s, bool hi) {
  __nv_bfloat162 x = *reinterpret_cast<__nv_bfloat162*>(&a), y = *reinterpret_cast<__nv_bfloat162*>(&s);
  x = __hmul2(x, hi ? __high2bfloat162(y) : __low2bfloat162(y));
  return *reinterpret_cast<uint32_t*>(&x);
}
__device__ __forceinline__ float bf16r(float x) { return __bfloat162float(__float2bfloat16_rn(x)); }
__device__ __forceinline__ float bf_lo(uint32_t u) { return __uint_as_float(u << 16); }
__device__ __forceinline__ float bf_hi(uint32_t u) { return __uint_as_float(u & 0xFFFF0000u); }
__device__ __forceinline__ float ex2(float x) { float r; asm("ex2.approx.ftz.f32 %0, %1;" : "=f"(r) : "f"(x)); return r; }
__device__ __forceinline__ float rcp(float x) { float r; asm("rcp.approx.ftz.f32 %0, %1;" : "=f"(r) : "f"(x)); return r; }
__device__ __forceinline__ void mma_bf16(float (&d)[4], uint32_t a0, uint32_t a1, uint32_t a2, uint32_t a3, uint32_t b0, uint32_t b1) {
  asm("mma.sync.aligned.m16n8k16.row.col.f32.bf16.bf16.f32 {%0,%1,%2,%3}, {%4,%5,%6,%7}, {%8,%9}, {%0,%1,%2,%3};"
               : "+f"(d[0]), "+f"(d[1]), "+f"(d[2]), "+f"(d[3]) : "r"(a0), "r"(a1), "r"(a2), "r"(a3), "r"(b0), "r"(b1));
}
__device__ __forceinline__ void ldsm_x4(uint32_t& r0, uint32_t& r1, uint32_t& r2, uint32_t& r3, uint32_t addr) {
  asm volatile("ldmatrix.sync.aligned.m8n8.x4.shared.b16 {%0,%1,%2,%3}, [%4];"
               : "=r"(r0), "=r"(r1), "=r"(r2), "=r"(r3) : "r"(addr) : "memory");
}
__device__ __forceinline__ void ldsm_x4_t(uint32_t& r0, uint32_t& r1, uint32_t& r2, uint32_t& r3, uint32_t addr) {
  asm volatile("ldmatrix.sync.aligned.m8n8.x4.trans.shared.b16 {%0,%1,%2,%3}, [%4];"
               : "=r"(r0), "=r"(r1), "=r"(r2), "=r"(r3) : "r"(addr) : "memory");
}
__device__ __forceinline__ void ldsm_x2_t(uint32_t& r0, uint32_t& r1, uint32_t addr) {
  asm volatile("ldmatrix.sync.aligned.m8n8.x2.trans.shared.b16 {%0,%1}, [%2];"
               : "=r"(r0), "=r"(r1) : "r"(addr) : "memory");
}
__device__ __forceinline__ void stsm_x4(uint32_t addr, uint32_t r0, uint32_t r1, uint32_t r2, uint32_t r3) {
  asm volatile("stmatrix.sync.aligned.m8n8.x4.shared.b16 [%0], {%1,%2,%3,%4};"
               ::"r"(addr), "r"(r0), "r"(r1), "r"(r2), "r"(r3) : "memory");
}
__device__ __forceinline__ void stsm_x4_p(bool on, uint32_t addr, uint32_t r0, uint32_t r1, uint32_t r2, uint32_t r3) {
  asm volatile("{\n.reg .pred p;\nsetp.ne.b32 p, %5, 0;\n@p stmatrix.sync.aligned.m8n8.x4.shared.b16 [%0], {%1,%2,%3,%4};\n}\n"
               ::"r"(addr), "r"(r0), "r"(r1), "r"(r2), "r"(r3), "r"((int)on) : "memory");
}
__device__ __forceinline__ float2 lds_f2(uint32_t addr) {
  float2 v; asm volatile("ld.shared.v2.f32 {%0,%1}, [%2];" : "=f"(v.x), "=f"(v.y) : "r"(addr) : "memory"); return v;
}
__device__ __forceinline__ uint4 lds128(uint32_t addr) {
  uint4 v; asm volatile("ld.shared.v4.b32 {%0,%1,%2,%3}, [%4];" : "=r"(v.x), "=r"(v.y), "=r"(v.z), "=r"(v.w) : "r"(addr) : "memory"); return v;
}
__device__ __forceinline__ void sts128(uint32_t addr, uint4 v) {
  asm volatile("st.shared.v4.b32 [%0], {%1,%2,%3,%4};" ::"r"(addr), "r"(v.x), "r"(v.y), "r"(v.z), "r"(v.w) : "memory");
}
__device__ __forceinline__ float lds_f(uint32_t addr) {
  float v; asm volatile("ld.shared.f32 %0, [%1];" : "=f"(v) : "r"(addr) : "memory"); return v;
}
__device__ __forceinline__ void sts16(uint32_t addr, uint32_t v) {
  asm volatile("st.shared.u16 [%0], %1;" ::"r"(addr), "h"((unsigned short)v) : "memory");
}
__device__ __forceinline__ void nbar_dyn(int id, int n) { asm volatile("bar.sync %0, %1;" ::"r"(id), "r"(n) : "memory"); }
__device__ __forceinline__ uint64_t make_desc_ns(uint32_t addr, uint32_t lbo_bytes, uint32_t sbo_bytes) {
  return (uint64_t)((addr & 0x3FFFF) >> 4) | ((uint64_t)(lbo_bytes >> 4) << 16) | ((uint64_t)(sbo_bytes >> 4) << 32);
}
__device__ __forceinline__ void sts_f(uint32_t addr, float v) { asm volatile("st.shared.f32 [%0], %1;" ::"r"(addr), "f"(v) : "memory"); }
__device__ __forceinline__ void sts64(uint32_t addr, uint32_t a, uint32_t b) {
  asm volatile("st.shared.v2.b32 [%0], {%1,%2};" ::"r"(addr), "r"(a), "r"(b) : "memory");
}
__device__ __forceinline__ void sts_f2(uint32_t addr, float a, float b) {
  asm volatile("st.shared.v2.f32 [%0], {%1,%2};" ::"r"(addr), "f"(a), "f"(b) : "memory");
}
__device__ __forceinline__ void red_add2(float* p, float a, float b) {
  asm volatile("red.global.add.v2.f32 [%0], {%1,%2};" ::"l"(p), "f"(a), "f"(b) : "memory");
}
__device__ __forceinline__ void red_add4(float* p, float a, float b, float c, float d) {
  asm volatile("red.global.add.v4.f32 [%0], {%1,%2,%3,%4};" ::"l"(p), "f"(a), "f"(b), "f"(c), "f"(d) : "memory");
}
__device__ __forceinline__ void red_add1(float* p, float a) {
  asm volatile("red.global.add.f32 [%0], %1;" ::"l"(p), "f"(a) : "memory");
}
__device__ __forceinline__ void l2_prefetch(const void* p, uint32_t bytes) {
  asm volatile("cp.async.bulk.prefetch.L2.global [%0], %1;" ::"l"(p), "r"(bytes) : "memory");
}

__device__ __forceinline__ void wgmma_n256(float (&d)[192], uint64_t da, uint64_t db, int scale_d) {
  asm volatile("{\n.reg .pred p;\nsetp.ne.b32 p, %130, 0;\n"
    "wgmma.mma_async.sync.aligned.m64n256k16.f32.bf16.bf16 {%0, %1, %2, %3, %4, %5, %6, %7, %8, %9, %10, %11, %12, %13, %14, %15, %16, %17, %18, %19, %20, %21, %22, %23, %24, %25, %26, %27, %28, %29, %30, %31, %32, %33, %34, %35, %36, %37, %38, %39, %40, %41, %42, %43, %44, %45, %46, %47, %48, %49, %50, %51, %52, %53, %54, %55, %56, %57, %58, %59, %60, %61, %62, %63, %64, %65, %66, %67, %68, %69, %70, %71, %72, %73, %74, %75, %76, %77, %78, %79, %80, %81, %82, %83, %84, %85, %86, %87, %88, %89, %90, %91, %92, %93, %94, %95, %96, %97, %98, %99, %100, %101, %102, %103, %104, %105, %106, %107, %108, %109, %110, %111, %112, %113, %114, %115, %116, %117, %118, %119, %120, %121, %122, %123, %124, %125, %126, %127}, %128, %129, p, 1, 1, 0, 1;\n}\n"
    : "+f"(d[0]), "+f"(d[1]), "+f"(d[2]), "+f"(d[3]), "+f"(d[4]), "+f"(d[5]), "+f"(d[6]), "+f"(d[7]), "+f"(d[8]), "+f"(d[9]), "+f"(d[10]), "+f"(d[11]), "+f"(d[12]), "+f"(d[13]), "+f"(d[14]), "+f"(d[15]), "+f"(d[16]), "+f"(d[17]), "+f"(d[18]), "+f"(d[19]), "+f"(d[20]), "+f"(d[21]), "+f"(d[22]), "+f"(d[23]), "+f"(d[24]), "+f"(d[25]), "+f"(d[26]), "+f"(d[27]), "+f"(d[28]), "+f"(d[29]), "+f"(d[30]), "+f"(d[31]), "+f"(d[32]), "+f"(d[33]), "+f"(d[34]), "+f"(d[35]), "+f"(d[36]), "+f"(d[37]), "+f"(d[38]), "+f"(d[39]), "+f"(d[40]), "+f"(d[41]), "+f"(d[42]), "+f"(d[43]), "+f"(d[44]), "+f"(d[45]), "+f"(d[46]), "+f"(d[47]), "+f"(d[48]), "+f"(d[49]), "+f"(d[50]), "+f"(d[51]), "+f"(d[52]), "+f"(d[53]), "+f"(d[54]), "+f"(d[55]), "+f"(d[56]), "+f"(d[57]), "+f"(d[58]), "+f"(d[59]), "+f"(d[60]), "+f"(d[61]), "+f"(d[62]), "+f"(d[63]), "+f"(d[64]), "+f"(d[65]), "+f"(d[66]), "+f"(d[67]), "+f"(d[68]), "+f"(d[69]), "+f"(d[70]), "+f"(d[71]), "+f"(d[72]), "+f"(d[73]), "+f"(d[74]), "+f"(d[75]), "+f"(d[76]), "+f"(d[77]), "+f"(d[78]), "+f"(d[79]), "+f"(d[80]), "+f"(d[81]), "+f"(d[82]), "+f"(d[83]), "+f"(d[84]), "+f"(d[85]), "+f"(d[86]), "+f"(d[87]), "+f"(d[88]), "+f"(d[89]), "+f"(d[90]), "+f"(d[91]), "+f"(d[92]), "+f"(d[93]), "+f"(d[94]), "+f"(d[95]), "+f"(d[96]), "+f"(d[97]), "+f"(d[98]), "+f"(d[99]), "+f"(d[100]), "+f"(d[101]), "+f"(d[102]), "+f"(d[103]), "+f"(d[104]), "+f"(d[105]), "+f"(d[106]), "+f"(d[107]), "+f"(d[108]), "+f"(d[109]), "+f"(d[110]), "+f"(d[111]), "+f"(d[112]), "+f"(d[113]), "+f"(d[114]), "+f"(d[115]), "+f"(d[116]), "+f"(d[117]), "+f"(d[118]), "+f"(d[119]), "+f"(d[120]), "+f"(d[121]), "+f"(d[122]), "+f"(d[123]), "+f"(d[124]), "+f"(d[125]), "+f"(d[126]), "+f"(d[127])
    : "l"(da), "l"(db), "r"(scale_d));
}
__device__ __forceinline__ void wgmma_n128(float (&d)[192], uint64_t da, uint64_t db, int scale_d) {
  asm volatile("{\n.reg .pred p;\nsetp.ne.b32 p, %66, 0;\n"
    "wgmma.mma_async.sync.aligned.m64n128k16.f32.bf16.bf16 {%0, %1, %2, %3, %4, %5, %6, %7, %8, %9, %10, %11, %12, %13, %14, %15, %16, %17, %18, %19, %20, %21, %22, %23, %24, %25, %26, %27, %28, %29, %30, %31, %32, %33, %34, %35, %36, %37, %38, %39, %40, %41, %42, %43, %44, %45, %46, %47, %48, %49, %50, %51, %52, %53, %54, %55, %56, %57, %58, %59, %60, %61, %62, %63}, %64, %65, p, 1, 1, 0, 1;\n}\n"
    : "+f"(d[128]), "+f"(d[129]), "+f"(d[130]), "+f"(d[131]), "+f"(d[132]), "+f"(d[133]), "+f"(d[134]), "+f"(d[135]), "+f"(d[136]), "+f"(d[137]), "+f"(d[138]), "+f"(d[139]), "+f"(d[140]), "+f"(d[141]), "+f"(d[142]), "+f"(d[143]), "+f"(d[144]), "+f"(d[145]), "+f"(d[146]), "+f"(d[147]), "+f"(d[148]), "+f"(d[149]), "+f"(d[150]), "+f"(d[151]), "+f"(d[152]), "+f"(d[153]), "+f"(d[154]), "+f"(d[155]), "+f"(d[156]), "+f"(d[157]), "+f"(d[158]), "+f"(d[159]), "+f"(d[160]), "+f"(d[161]), "+f"(d[162]), "+f"(d[163]), "+f"(d[164]), "+f"(d[165]), "+f"(d[166]), "+f"(d[167]), "+f"(d[168]), "+f"(d[169]), "+f"(d[170]), "+f"(d[171]), "+f"(d[172]), "+f"(d[173]), "+f"(d[174]), "+f"(d[175]), "+f"(d[176]), "+f"(d[177]), "+f"(d[178]), "+f"(d[179]), "+f"(d[180]), "+f"(d[181]), "+f"(d[182]), "+f"(d[183]), "+f"(d[184]), "+f"(d[185]), "+f"(d[186]), "+f"(d[187]), "+f"(d[188]), "+f"(d[189]), "+f"(d[190]), "+f"(d[191])
    : "l"(da), "l"(db), "r"(scale_d));
}
__device__ __forceinline__ void wgmma_n256_k(float (&d)[192], uint64_t da, uint64_t db, int scale_d) {
  asm volatile("{\n.reg .pred p;\nsetp.ne.b32 p, %130, 0;\n"
    "wgmma.mma_async.sync.aligned.m64n256k16.f32.bf16.bf16 {%0, %1, %2, %3, %4, %5, %6, %7, %8, %9, %10, %11, %12, %13, %14, %15, %16, %17, %18, %19, %20, %21, %22, %23, %24, %25, %26, %27, %28, %29, %30, %31, %32, %33, %34, %35, %36, %37, %38, %39, %40, %41, %42, %43, %44, %45, %46, %47, %48, %49, %50, %51, %52, %53, %54, %55, %56, %57, %58, %59, %60, %61, %62, %63, %64, %65, %66, %67, %68, %69, %70, %71, %72, %73, %74, %75, %76, %77, %78, %79, %80, %81, %82, %83, %84, %85, %86, %87, %88, %89, %90, %91, %92, %93, %94, %95, %96, %97, %98, %99, %100, %101, %102, %103, %104, %105, %106, %107, %108, %109, %110, %111, %112, %113, %114, %115, %116, %117, %118, %119, %120, %121, %122, %123, %124, %125, %126, %127}, %128, %129, p, 1, 1, 0, 0;\n}\n"
    : "+f"(d[0]), "+f"(d[1]), "+f"(d[2]), "+f"(d[3]), "+f"(d[4]), "+f"(d[5]), "+f"(d[6]), "+f"(d[7]), "+f"(d[8]), "+f"(d[9]), "+f"(d[10]), "+f"(d[11]), "+f"(d[12]), "+f"(d[13]), "+f"(d[14]), "+f"(d[15]), "+f"(d[16]), "+f"(d[17]), "+f"(d[18]), "+f"(d[19]), "+f"(d[20]), "+f"(d[21]), "+f"(d[22]), "+f"(d[23]), "+f"(d[24]), "+f"(d[25]), "+f"(d[26]), "+f"(d[27]), "+f"(d[28]), "+f"(d[29]), "+f"(d[30]), "+f"(d[31]), "+f"(d[32]), "+f"(d[33]), "+f"(d[34]), "+f"(d[35]), "+f"(d[36]), "+f"(d[37]), "+f"(d[38]), "+f"(d[39]), "+f"(d[40]), "+f"(d[41]), "+f"(d[42]), "+f"(d[43]), "+f"(d[44]), "+f"(d[45]), "+f"(d[46]), "+f"(d[47]), "+f"(d[48]), "+f"(d[49]), "+f"(d[50]), "+f"(d[51]), "+f"(d[52]), "+f"(d[53]), "+f"(d[54]), "+f"(d[55]), "+f"(d[56]), "+f"(d[57]), "+f"(d[58]), "+f"(d[59]), "+f"(d[60]), "+f"(d[61]), "+f"(d[62]), "+f"(d[63]), "+f"(d[64]), "+f"(d[65]), "+f"(d[66]), "+f"(d[67]), "+f"(d[68]), "+f"(d[69]), "+f"(d[70]), "+f"(d[71]), "+f"(d[72]), "+f"(d[73]), "+f"(d[74]), "+f"(d[75]), "+f"(d[76]), "+f"(d[77]), "+f"(d[78]), "+f"(d[79]), "+f"(d[80]), "+f"(d[81]), "+f"(d[82]), "+f"(d[83]), "+f"(d[84]), "+f"(d[85]), "+f"(d[86]), "+f"(d[87]), "+f"(d[88]), "+f"(d[89]), "+f"(d[90]), "+f"(d[91]), "+f"(d[92]), "+f"(d[93]), "+f"(d[94]), "+f"(d[95]), "+f"(d[96]), "+f"(d[97]), "+f"(d[98]), "+f"(d[99]), "+f"(d[100]), "+f"(d[101]), "+f"(d[102]), "+f"(d[103]), "+f"(d[104]), "+f"(d[105]), "+f"(d[106]), "+f"(d[107]), "+f"(d[108]), "+f"(d[109]), "+f"(d[110]), "+f"(d[111]), "+f"(d[112]), "+f"(d[113]), "+f"(d[114]), "+f"(d[115]), "+f"(d[116]), "+f"(d[117]), "+f"(d[118]), "+f"(d[119]), "+f"(d[120]), "+f"(d[121]), "+f"(d[122]), "+f"(d[123]), "+f"(d[124]), "+f"(d[125]), "+f"(d[126]), "+f"(d[127])
    : "l"(da), "l"(db), "r"(scale_d));
}
__device__ __forceinline__ void wgmma_n128_k(float (&d)[192], uint64_t da, uint64_t db, int scale_d) {
  asm volatile("{\n.reg .pred p;\nsetp.ne.b32 p, %66, 0;\n"
    "wgmma.mma_async.sync.aligned.m64n128k16.f32.bf16.bf16 {%0, %1, %2, %3, %4, %5, %6, %7, %8, %9, %10, %11, %12, %13, %14, %15, %16, %17, %18, %19, %20, %21, %22, %23, %24, %25, %26, %27, %28, %29, %30, %31, %32, %33, %34, %35, %36, %37, %38, %39, %40, %41, %42, %43, %44, %45, %46, %47, %48, %49, %50, %51, %52, %53, %54, %55, %56, %57, %58, %59, %60, %61, %62, %63}, %64, %65, p, 1, 1, 0, 0;\n}\n"
    : "+f"(d[128]), "+f"(d[129]), "+f"(d[130]), "+f"(d[131]), "+f"(d[132]), "+f"(d[133]), "+f"(d[134]), "+f"(d[135]), "+f"(d[136]), "+f"(d[137]), "+f"(d[138]), "+f"(d[139]), "+f"(d[140]), "+f"(d[141]), "+f"(d[142]), "+f"(d[143]), "+f"(d[144]), "+f"(d[145]), "+f"(d[146]), "+f"(d[147]), "+f"(d[148]), "+f"(d[149]), "+f"(d[150]), "+f"(d[151]), "+f"(d[152]), "+f"(d[153]), "+f"(d[154]), "+f"(d[155]), "+f"(d[156]), "+f"(d[157]), "+f"(d[158]), "+f"(d[159]), "+f"(d[160]), "+f"(d[161]), "+f"(d[162]), "+f"(d[163]), "+f"(d[164]), "+f"(d[165]), "+f"(d[166]), "+f"(d[167]), "+f"(d[168]), "+f"(d[169]), "+f"(d[170]), "+f"(d[171]), "+f"(d[172]), "+f"(d[173]), "+f"(d[174]), "+f"(d[175]), "+f"(d[176]), "+f"(d[177]), "+f"(d[178]), "+f"(d[179]), "+f"(d[180]), "+f"(d[181]), "+f"(d[182]), "+f"(d[183]), "+f"(d[184]), "+f"(d[185]), "+f"(d[186]), "+f"(d[187]), "+f"(d[188]), "+f"(d[189]), "+f"(d[190]), "+f"(d[191])
    : "l"(da), "l"(db), "r"(scale_d));
}
__device__ __forceinline__ void wgmma_n40_tt(float (&d)[20], uint64_t da, uint64_t db, int scale_d) {
  asm volatile("{\n.reg .pred p;\nsetp.ne.b32 p, %22, 0;\n"
    "wgmma.mma_async.sync.aligned.m64n40k16.f32.bf16.bf16 {%0, %1, %2, %3, %4, %5, %6, %7, %8, %9, %10, %11, %12, %13, %14, %15, %16, %17, %18, %19}, %20, %21, p, 1, 1, 1, 1;\n}\n"
    : "+f"(d[0]), "+f"(d[1]), "+f"(d[2]), "+f"(d[3]), "+f"(d[4]), "+f"(d[5]), "+f"(d[6]), "+f"(d[7]), "+f"(d[8]), "+f"(d[9]), "+f"(d[10]), "+f"(d[11]), "+f"(d[12]), "+f"(d[13]), "+f"(d[14]), "+f"(d[15]), "+f"(d[16]), "+f"(d[17]), "+f"(d[18]), "+f"(d[19])
    : "l"(da), "l"(db), "r"(scale_d));
}
__device__ __forceinline__ void wgmma_n40_rs(float (&d)[20], const uint32_t (&a)[4], uint64_t db, int scale_d) {
  asm volatile("{\n.reg .pred p;\nsetp.ne.b32 p, %25, 0;\n"
    "wgmma.mma_async.sync.aligned.m64n40k16.f32.bf16.bf16 {%0, %1, %2, %3, %4, %5, %6, %7, %8, %9, %10, %11, %12, %13, %14, %15, %16, %17, %18, %19}, {%20, %21, %22, %23}, %24, p, 1, 1, 1;\n}\n"
    : "+f"(d[0]), "+f"(d[1]), "+f"(d[2]), "+f"(d[3]), "+f"(d[4]), "+f"(d[5]), "+f"(d[6]), "+f"(d[7]), "+f"(d[8]), "+f"(d[9]), "+f"(d[10]), "+f"(d[11]), "+f"(d[12]), "+f"(d[13]), "+f"(d[14]), "+f"(d[15]), "+f"(d[16]), "+f"(d[17]), "+f"(d[18]), "+f"(d[19])
    : "r"(a[0]), "r"(a[1]), "r"(a[2]), "r"(a[3]), "l"(db), "r"(scale_d));
}
__device__ __forceinline__ void wgmma_n256_0(float (&d)[192], uint64_t da, uint64_t db) {
  asm volatile("{\n.reg .pred p;\nsetp.ne.b32 p, 0, 0;\n"
    "wgmma.mma_async.sync.aligned.m64n256k16.f32.bf16.bf16 {%0, %1, %2, %3, %4, %5, %6, %7, %8, %9, %10, %11, %12, %13, %14, %15, %16, %17, %18, %19, %20, %21, %22, %23, %24, %25, %26, %27, %28, %29, %30, %31, %32, %33, %34, %35, %36, %37, %38, %39, %40, %41, %42, %43, %44, %45, %46, %47, %48, %49, %50, %51, %52, %53, %54, %55, %56, %57, %58, %59, %60, %61, %62, %63, %64, %65, %66, %67, %68, %69, %70, %71, %72, %73, %74, %75, %76, %77, %78, %79, %80, %81, %82, %83, %84, %85, %86, %87, %88, %89, %90, %91, %92, %93, %94, %95, %96, %97, %98, %99, %100, %101, %102, %103, %104, %105, %106, %107, %108, %109, %110, %111, %112, %113, %114, %115, %116, %117, %118, %119, %120, %121, %122, %123, %124, %125, %126, %127}, %128, %129, p, 1, 1, 0, 1;\n}\n"
    : "=f"(d[0]), "=f"(d[1]), "=f"(d[2]), "=f"(d[3]), "=f"(d[4]), "=f"(d[5]), "=f"(d[6]), "=f"(d[7]), "=f"(d[8]), "=f"(d[9]), "=f"(d[10]), "=f"(d[11]), "=f"(d[12]), "=f"(d[13]), "=f"(d[14]), "=f"(d[15]), "=f"(d[16]), "=f"(d[17]), "=f"(d[18]), "=f"(d[19]), "=f"(d[20]), "=f"(d[21]), "=f"(d[22]), "=f"(d[23]), "=f"(d[24]), "=f"(d[25]), "=f"(d[26]), "=f"(d[27]), "=f"(d[28]), "=f"(d[29]), "=f"(d[30]), "=f"(d[31]), "=f"(d[32]), "=f"(d[33]), "=f"(d[34]), "=f"(d[35]), "=f"(d[36]), "=f"(d[37]), "=f"(d[38]), "=f"(d[39]), "=f"(d[40]), "=f"(d[41]), "=f"(d[42]), "=f"(d[43]), "=f"(d[44]), "=f"(d[45]), "=f"(d[46]), "=f"(d[47]), "=f"(d[48]), "=f"(d[49]), "=f"(d[50]), "=f"(d[51]), "=f"(d[52]), "=f"(d[53]), "=f"(d[54]), "=f"(d[55]), "=f"(d[56]), "=f"(d[57]), "=f"(d[58]), "=f"(d[59]), "=f"(d[60]), "=f"(d[61]), "=f"(d[62]), "=f"(d[63]), "=f"(d[64]), "=f"(d[65]), "=f"(d[66]), "=f"(d[67]), "=f"(d[68]), "=f"(d[69]), "=f"(d[70]), "=f"(d[71]), "=f"(d[72]), "=f"(d[73]), "=f"(d[74]), "=f"(d[75]), "=f"(d[76]), "=f"(d[77]), "=f"(d[78]), "=f"(d[79]), "=f"(d[80]), "=f"(d[81]), "=f"(d[82]), "=f"(d[83]), "=f"(d[84]), "=f"(d[85]), "=f"(d[86]), "=f"(d[87]), "=f"(d[88]), "=f"(d[89]), "=f"(d[90]), "=f"(d[91]), "=f"(d[92]), "=f"(d[93]), "=f"(d[94]), "=f"(d[95]), "=f"(d[96]), "=f"(d[97]), "=f"(d[98]), "=f"(d[99]), "=f"(d[100]), "=f"(d[101]), "=f"(d[102]), "=f"(d[103]), "=f"(d[104]), "=f"(d[105]), "=f"(d[106]), "=f"(d[107]), "=f"(d[108]), "=f"(d[109]), "=f"(d[110]), "=f"(d[111]), "=f"(d[112]), "=f"(d[113]), "=f"(d[114]), "=f"(d[115]), "=f"(d[116]), "=f"(d[117]), "=f"(d[118]), "=f"(d[119]), "=f"(d[120]), "=f"(d[121]), "=f"(d[122]), "=f"(d[123]), "=f"(d[124]), "=f"(d[125]), "=f"(d[126]), "=f"(d[127])
    : "l"(da), "l"(db));
}
__device__ __forceinline__ void wgmma_n128_0(float (&d)[192], uint64_t da, uint64_t db) {
  asm volatile("{\n.reg .pred p;\nsetp.ne.b32 p, 0, 0;\n"
    "wgmma.mma_async.sync.aligned.m64n128k16.f32.bf16.bf16 {%0, %1, %2, %3, %4, %5, %6, %7, %8, %9, %10, %11, %12, %13, %14, %15, %16, %17, %18, %19, %20, %21, %22, %23, %24, %25, %26, %27, %28, %29, %30, %31, %32, %33, %34, %35, %36, %37, %38, %39, %40, %41, %42, %43, %44, %45, %46, %47, %48, %49, %50, %51, %52, %53, %54, %55, %56, %57, %58, %59, %60, %61, %62, %63}, %64, %65, p, 1, 1, 0, 1;\n}\n"
    : "=f"(d[128]), "=f"(d[129]), "=f"(d[130]), "=f"(d[131]), "=f"(d[132]), "=f"(d[133]), "=f"(d[134]), "=f"(d[135]), "=f"(d[136]), "=f"(d[137]), "=f"(d[138]), "=f"(d[139]), "=f"(d[140]), "=f"(d[141]), "=f"(d[142]), "=f"(d[143]), "=f"(d[144]), "=f"(d[145]), "=f"(d[146]), "=f"(d[147]), "=f"(d[148]), "=f"(d[149]), "=f"(d[150]), "=f"(d[151]), "=f"(d[152]), "=f"(d[153]), "=f"(d[154]), "=f"(d[155]), "=f"(d[156]), "=f"(d[157]), "=f"(d[158]), "=f"(d[159]), "=f"(d[160]), "=f"(d[161]), "=f"(d[162]), "=f"(d[163]), "=f"(d[164]), "=f"(d[165]), "=f"(d[166]), "=f"(d[167]), "=f"(d[168]), "=f"(d[169]), "=f"(d[170]), "=f"(d[171]), "=f"(d[172]), "=f"(d[173]), "=f"(d[174]), "=f"(d[175]), "=f"(d[176]), "=f"(d[177]), "=f"(d[178]), "=f"(d[179]), "=f"(d[180]), "=f"(d[181]), "=f"(d[182]), "=f"(d[183]), "=f"(d[184]), "=f"(d[185]), "=f"(d[186]), "=f"(d[187]), "=f"(d[188]), "=f"(d[189]), "=f"(d[190]), "=f"(d[191])
    : "l"(da), "l"(db));
}

constexpr int SLOT = 16384;
constexpr int KVT = 10240;
constexpr uint32_t QA = 0x0BAu, QK = 0x462u, QQ = 0x981u;
constexpr int SM_SD = 12 * SLOT;
constexpr int SM_BAR = SM_SD + 8192;
constexpr int SM_RS = SM_BAR + 512;
constexpr int SM_AP = SM_RS + 768;
constexpr int SM_BP = SM_AP + 2048;
constexpr int SM_WPHI = SM_BP + 12288;
constexpr int SM_EPOCH = SM_WPHI + 10240;
constexpr int SM_TOTAL = SM_EPOCH + 16 + 1024;
constexpr int B_FULLS = 0, B_XOLD = 24, B_STAT = 32, B_EMPTYS = 40, B_FULLT = 256  , B_CONS = 384  , B_E0 = 480, B_E1 = 488, B_E2 = 496, B_EPI = 504, B_KVRDY = 152  , B_CS = 160,
              B_KVDONE = 168  , B_ODONE = 176, B_XDONE = 184, B_OH1 = 192, B_CSL = 200, B_CS2 = 208, B_CSFREE = 216  , B_XH0 = 232, B_X1 = 240;
constexpr uint64_t BAR_CNT = 0xc07fc0eac00a800ull;
constexpr uint64_t WO_A0 = 0xab813a8643b57643ull, WO_B0 = 0x9460579210a89210ull, WO_A1 = 0x9b13a954ba654baull, WO_B1 = 0x5487602138790213ull;
__constant__ uint32_t c_ops[2][32] = {{0xc000, 0xc110, 0xc220, 0xc930, 0xd621, 0xd731, 0xe840, 0xe541, 0xea50, 0xeb51, 0x60, 0x361, 0x1170, 0x1473, 0x2280, 0x2681, 0x3990, 0x37a0, 0x4891, 0x45b0, 0x5aa1, 0x60c0, 0x63b1, 0x71c1, 0x86d0, 0x74e0, 0x98d1, 0x5be1, 0x99f0, 0xaaf1},
                                      {0xc300, 0xc110, 0xc220, 0xc030, 0xc940, 0xd750, 0xd860, 0xf421, 0xf531, 0xf641, 0xa51, 0x370, 0x1b63, 0x1180, 0x2471, 0x2290, 0x3581, 0x30a0, 0x4991, 0x46b0, 0x5aa1, 0x57c0, 0x68d0, 0x73b1, 0x74e0, 0x81c1, 0x6bd1, 0x85f0, 0x99e1, 0xa0f1}};
constexpr uint64_t WO_DA0 = 0xa597654210eedd00ull, WO_DB0 = 0x9786433210eeccccull, WO_DA1 = 0xa9687543210fff00ull, WO_DB1 = 0x876543210ddcccccull;
constexpr int XS = 10;

#define HPI 2
#define XOLD_AT 0
#define PL 2
#define PROFX(i) PROFT(tid_ == 128 && layer == PL, 200 + (i))
#define LATE_AT 0
#define RV1
#define H1_AT 1
#define QP 0
#define WSPLIT 0
#define H1B 1
#define PPOLL 99
#define RLATE 0
#define CSW3 1
#define OPOLL 0
#define STL 0
#define OUNR 2
#define H1A 1
#define D1 0
#define FE 1
#define SKEW 1
#define NLAYERS 4
constexpr float L2E = 1.4426950408889634f;
#define PHI_MAX 2147483648.f

#define D128(lo) desc64(lo, 0x40000040u)
struct Ctx { uint32_t sb; int g, rb, isum, cu; bf16* out; };

__device__ __forceinline__ void colsum_load(const bf16* __restrict__ w, int rb, int g, int wi, int lane, uint32_t stg, float (&s)[8]) {
  const int ch = wi * 8 + (lane & 7), sec = ch >> 4;
  const bf16* src = w + (size_t)(rb * 64 + (lane >> 3) * 16) * 3072 + (sec == 2 ? 0 : 1024 + sec * 1024) + g * 128 + (ch & 15) * 8;
  stg += lane * 16;
#pragma unroll
  for (int i = 0; i < 8; ++i) s[i] = 0.f;
#pragma unroll
  for (int r = 0; r < 12; ++r)
    asm volatile("cp.async.cg.shared.global [%0], [%1], 16;" ::"r"(stg + r * 512), "l"(src + (size_t)(4 + r) * 3072) : "memory");
  uint4 v[4];
#pragma unroll
  for (int r = 0; r < 4; ++r) v[r] = __ldg(reinterpret_cast<const uint4*>(src + (size_t)r * 3072));
#pragma unroll 1
  for (int r0 = 0;; ++r0) {
#pragma unroll
    for (int r = 0; r < 4; ++r) {
      s[0] += bf_lo(v[r].x); s[1] += bf_hi(v[r].x); s[2] += bf_lo(v[r].y); s[3] += bf_hi(v[r].y);
      s[4] += bf_lo(v[r].z); s[5] += bf_hi(v[r].z); s[6] += bf_lo(v[r].w); s[7] += bf_hi(v[r].w);
    }
    if (r0 == 3) break;
    asm volatile("cp.async.wait_all;" ::: "memory");
#pragma unroll
    for (int r = 0; r < 4; ++r) v[r] = lds128(stg + (r0 * 4 + r) * 512);
  }
#pragma unroll
  for (int i = 0; i < 8; ++i) { s[i] += __shfl_xor_sync(0xffffffffu, s[i], 8); s[i] += __shfl_xor_sync(0xffffffffu, s[i], 16); }
}
__device__ __forceinline__ void colsum_red(float* cs, int g, int wi, int lane, const float (&s)[8]) {
  if (lane < 8) {
    red_add4(cs + g * 384 + (wi * 8 + lane) * 8, s[0], s[1], s[2], s[3]);
    red_add4(cs + g * 384 + (wi * 8 + lane) * 8 + 4, s[4], s[5], s[6], s[7]);
  }
}
#define PHASE_CTX() \
  uint32_t sb = c.sb; asm volatile("" : "+r"(sb)); \
  int tid_ = threadIdx.x; asm volatile("" : "+r"(tid_)); \
  const uint32_t bar = sb + SM_BAR; \
  const int lane = tid_ & 31, cw = (tid_ >> 5) - 4, wg = cw >> 2, wq = cw & 3, gq = lane >> 2, t = lane & 3, wrow0 = cw * 16; \
  const int lrow = (lane & 7) + ((lane >> 3) & 1) * 8, lchk = lane >> 4; \
  const bool elected = (tid_ & 127) == 0; \
  const uint32_t rowo = (wrow0 + lrow) * 128, X = (lchk ^ (lane & 7)) << 4; \
  (void)bar; (void)wq; (void)gq; (void)lrow; (void)lchk; (void)elected; (void)wrow0; (void)wg; (void)rowo; (void)X; (void)t;

template <int PITCH = D_>
__device__ __forceinline__ void slab_out_half(uint32_t slot, bf16* dst, int wrow0, int lane) {
  const int r0 = lane >> 3, ch = lane & 7;
  const uint32_t src = slot + (wrow0 + r0) * 128;
  uint4 v[4];
#pragma unroll
  for (int i = 0; i < 4; ++i) v[i] = lds128(src + i * 512 + (((ch ^ (4 * i + r0)) & 7) << 4));
  dst += (size_t)(wrow0 + r0) * PITCH + ch * 8;
#pragma unroll
  for (int i = 0; i < 4; ++i) *reinterpret_cast<uint4*>(dst + (size_t)i * 4 * PITCH) = v[i];
}

__device__ __forceinline__ void consumer(const Ctx& c) {
  const int g = c.g, m0 = c.rb * 128;
  float acc[192];
  mbar_wait(c.sb + SM_BAR + B_XOLD, 0);
#pragma unroll 1
  for (int layer = 0;; ++layer) {
    {
      PHASE_CTX();
      const uint32_t wu = __shfl_sync(0xffffffffu, wg, 0);
      const uint32_t dA0 = (((sb + wu * 8192) & 0x3FFFF) >> 4) | (1u << 16), dB0 = ((sb & 0x3FFFF) >> 4) | (512u << 16);
      {
        float s0 = 0.f, s1 = 0.f, q0 = 0.f, q1 = 0.f;
        mbar_wait(bar + B_FULLS, 0);
        if (elected && c.isum == 0 && layer == 0) mbar_arrive(bar + B_CSL);
        wgmma_fence();
        wgmma_n256_0(acc, D128(dA0 + XS * 1024), D128(dB0 + 2048));
        wgmma_n128_0(acc, D128(dA0 + XS * 1024), D128(dB0 + 1024));
        if (layer > 0) slab_out_half(sb + (XS + 1) * SLOT, g_x + (size_t)m0 * D_ + g * 128 + 64, wrow0, lane);
        else mbar_wait(bar + B_X1, 0);
        wgmma_fence();
#pragma unroll
        for (int k = 1; k < 4; ++k) {
          wgmma_n256(acc, D128(dA0 + XS * 1024 + k * 2), D128(dB0 + 2048 + k * 128), 1);
          wgmma_n128(acc, D128(dA0 + XS * 1024 + k * 2), D128(dB0 + 1024 + k * 128), 1);
          if (k == 3) wgmma_commit();
#pragma unroll
          for (int jp = (k - 1) * 3; jp < k * 3 && jp < 8; ++jp) {
            uint32_t x0, x1, x2, x3;
            ldsm_x4(x0, x1, x2, x3, sb + (XS + (jp >> 2)) * SLOT + rowo + (X ^ ((jp & 3) << 5)));
            s0 += (bf_lo(x0) + bf_hi(x0)) + (bf_lo(x2) + bf_hi(x2));
            s1 += (bf_lo(x1) + bf_hi(x1)) + (bf_lo(x3) + bf_hi(x3));
            q0 = fmaf(bf_lo(x0), bf_lo(x0), fmaf(bf_hi(x0), bf_hi(x0), fmaf(bf_lo(x2), bf_lo(x2), fmaf(bf_hi(x2), bf_hi(x2), q0))));
            q1 = fmaf(bf_lo(x1), bf_lo(x1), fmaf(bf_hi(x1), bf_hi(x1), fmaf(bf_lo(x3), bf_lo(x3), fmaf(bf_hi(x3), bf_hi(x3), q1))));
          }
        }
        const bool od = t & 1;
        float sa = od ? s1 : s0, qa = od ? q1 : q0;
        sa += __shfl_xor_sync(0xffffffffu, od ? s0 : s1, 1);
        qa += __shfl_xor_sync(0xffffffffu, od ? q0 : q1, 1);
        sa += __shfl_xor_sync(0xffffffffu, sa, 2);
        qa += __shfl_xor_sync(0xffffffffu, qa, 2);
        if (t < 2) g_stats[((layer & 1) * 8 + g) * S_ + m0 + wrow0 + gq + t * 8] = make_float2(sa, qa);
        __syncwarp();
        if (lane == 0) mbar_arrive(bar + B_XDONE);
      }
      uint32_t s = 1, u = 0, sp = 0;
#pragma unroll 1
      for (int i = 1; i < 14; ++i) {
        mbar_wait(bar + B_FULLS + s * 8, (u + (s ? layer : 0)) & 1);
        if (elected && i == c.isum && layer == 0) mbar_arrive(bar + B_CSL);
        const uint32_t da = dA0 + ((QA >> (4 * s)) & 15) * 1024, dk = dB0 + ((QK >> (4 * s)) & 15) * 1024,
                       dq = dB0 + ((QQ >> (4 * s)) & 15) * 1024;
        wgmma_fence();
#pragma unroll
        for (int k = 0; k < 4; ++k) {
          wgmma_n256(acc, D128(da + k * 2), D128(dk + k * 128), 1);
          wgmma_n128(acc, D128(da + k * 2), D128(dq + k * 128), 1);
        }
        wgmma_commit();
        wgmma_wait<1>();
        if (i == 1) nbar_dyn(3 + wu, 128);
        if (elected) release2(bar + B_EMPTYS + sp * 8);
        sp = s;
        if (++s == 3) { s = 0; ++u; }
      }
      {
        const uint64_t dap = make_desc_ns(sb + SM_AP + wu * 1024, 0, 128), dbp = make_desc_ns(sb + SM_BP + (layer & 1) * 6144, 0, 128);
        if (SKEW && wu == 0) {
          wgmma_wait<0>();
          nbar<6, 256>();
        }
        if (layer < 2) mbar_wait(bar + (layer ? B_CS2 : B_CS), 0);
        mbar_wait(bar + B_STAT, layer & 1);
        mbar_wait(bar + B_FULLS + 16, layer & 1);
        wgmma_fence();
        wgmma_n256_k(acc, dap, dbp, 1);
#pragma unroll
        for (int k = 0; k < 4; ++k) wgmma_n256(acc, D128(dA0 + (QA >> 8) * 1024 + k * 2), D128(dB0 + (QK >> 8) * 1024 + k * 128), 1);
        mbar_wait(bar + B_FULLS, 1);
        PROFT(tid_ == 128, layer * 16 + 9);
        wgmma_fence();
#pragma unroll
        for (int k = 0; k < 4; ++k) wgmma_n256(acc, D128(dA0 + (QA & 15) * 1024 + k * 2), D128(dB0 + (QK & 15) * 1024 + k * 128), 1);
        wgmma_commit();
        if ((SKEW & 1) && wu) nbar<6, 256>();
#define Q_TAIL() \
        wgmma_n128_k(acc, dap, dbp + 256, 1); \
        _Pragma("unroll") for (int k = 0; k < 4; ++k) wgmma_n128(acc, D128(dA0 + (QA >> 8) * 1024 + k * 2), D128(dB0 + (QQ >> 8) * 1024 + k * 128), 1); \
        _Pragma("unroll") for (int k = 0; k < 4; ++k) wgmma_n128(acc, D128(dA0 + (QA & 15) * 1024 + k * 2), D128(dB0 + (QQ & 15) * 1024 + k * 128), 1);
        if (SKEW != 3 || wu == 0) { Q_TAIL(); }
        wgmma_commit();
        if (SKEW == 2 && wu) nbar<6, 256>();
        wgmma_wait<1>();
#pragma unroll
        for (int i = 0; i < 128; ++i) asm volatile("" : "+f"(acc[i]) :: "memory");
      }
    }
    uint32_t xo[32];
    {
      PHASE_CTX();
      PROFT(tid_ == 128, layer * 16 + 1);
      const bool isB = layer & 1;
      const int cu = c.cu;
      if (cu >= 4) asm volatile("bar.arrive 7, 256;" ::: "memory");
      else if (isB && cu == 0) asm volatile("bar.arrive 10, 64;" ::: "memory");
      if (elected && isB && cu == 0) release2(bar + B_E1);
      uint32_t kq[64];
#pragma unroll
      for (int i = 0; i < 32; ++i) kq[i] = pack_bf16(acc[2 * i], acc[2 * i + 1]);
      const unsigned int epoch = __float_as_uint(lds_f(sb + SM_EPOCH));
      uint4* const hbuf = g_halo + (size_t)((((epoch & 1) * 2 + (layer >> 1)) * 16 + c.rb) * 8 + g) * 512 + lane;
      if (isB && cu == 7) {
#pragma unroll
        for (int jp = 0; jp < 8; ++jp) st_relaxed4(hbuf + jp * 32, ~kq[4 * jp], ~kq[4 * jp + 1], ~kq[4 * jp + 2], ~kq[4 * jp + 3]);
#pragma unroll
        for (int jp = 8; jp < 16; ++jp)
          st_relaxed4(hbuf + jp * 32, ~pack_bf16(acc[8 * jp], acc[8 * jp + 1]), ~pack_bf16(acc[8 * jp + 2], acc[8 * jp + 3]),
                      ~pack_bf16(acc[8 * jp + 4], acc[8 * jp + 5]), ~pack_bf16(acc[8 * jp + 6], acc[8 * jp + 7]));
      }
      const uint32_t rowq = rowo & 8191;
      const uint32_t rB = sb + 4 * SLOT + wg * 4 * KVT + rowq, pA = sb + (3 + 3 * wg) * SLOT + rowq;
      PROFX(13);
      if (cu < 4) nbar<7, 256>();
      PROFX(14);
      {
        const uint32_t vb = isB ? rB + KVT + 2048 : pA + 2 * SLOT - (rowq >> 1), vst = isB ? 2 * KVT : 8192;
        const uint32_t X0 = isB ? X : (lchk ^ ((lane & 7) >> 1)) << 4, X1 = isB ? X ^ 64 : X0 + 4096;
        const bool dup = isB && cu == 3;
        if (isB) {
#pragma unroll
          for (int jp = 0; jp < 8; ++jp) {
            stsm_x4(rB + 2048 + (jp >> 2) * 2 * KVT + (X ^ ((jp & 3) << 5)), kq[4 * jp], kq[4 * jp + 1], kq[4 * jp + 2], kq[4 * jp + 3]);
            stsm_x4_p(dup, rB + 2048 + 32768 + (jp >> 2) * 2 * KVT + (X ^ ((jp & 3) << 5)), kq[4 * jp], kq[4 * jp + 1], kq[4 * jp + 2], kq[4 * jp + 3]);
          }
        }
#pragma unroll
        for (int jp = 8; jp < 16; ++jp) {
          const uint32_t v0 = pack_bf16(acc[8 * jp], acc[8 * jp + 1]), v1 = pack_bf16(acc[8 * jp + 2], acc[8 * jp + 3]),
                         v2 = pack_bf16(acc[8 * jp + 4], acc[8 * jp + 5]), v3 = pack_bf16(acc[8 * jp + 6], acc[8 * jp + 7]);
          const uint32_t ad = vb + ((jp >> 2) & 1) * vst + (((jp & 2) ? X1 : X0) ^ ((jp & 1) << 5));
          stsm_x4(ad, v0, v1, v2, v3);
          stsm_x4_p(dup, ad + 32768, v0, v1, v2, v3);
        }
        if (dup) asm volatile("bar.arrive 9, 64;" ::: "memory");
      }
      const float rs0 = lds_f(sb + SM_RS + (16 + wrow0 + gq) * 4), rs1 = lds_f(sb + SM_RS + (24 + wrow0 + gq) * 4);
      PROFT(tid_ == 128, layer * 16 + 2);
#define Q_DONE() \
      wgmma_wait<0>(); \
      if (lane == 0) release2(bar + B_E0); \
      _Pragma("unroll") for (int i = 128; i < 192; ++i) asm volatile("" : "+f"(acc[i]) :: "memory"); \
      _Pragma("unroll") for (int i = 0; i < 32; ++i) kq[32 + i] = pack_bf16(acc[128 + 2 * i], acc[129 + 2 * i]);
      Q_DONE();
      if (isB) {
        const int e = gq & 1;
        const uint32_t KX = ((lane >> 3) ^ (lane & 7)) << 4;
        float f0[4], f1[4], rj[4];
        uint32_t msk = 0;
#pragma unroll
        for (int nt = 0; nt < 4; ++nt) {
          const int kk = nt * 8 + 2 * t + e;
          const bool okk = (m0 + wrow0 + kk) >= 16;
          const int d0 = kk - gq, d1 = d0 - 8;
          rj[nt] = lds_f(sb + SM_RS + (wrow0 + kk) * 4);
          f0[nt] = rj[nt] * rs0 * (0.17677669529663687f * L2E);
          f1[nt] = rj[nt] * rs1 * (0.17677669529663687f * L2E);
          msk |= (okk && d0 >= 2 && d0 <= 16) ? (1u << nt) : 0u;
          msk |= (okk && d1 >= 2 && d1 <= 16) ? (16u << nt) : 0u;
        }
        if ((cu & 3) == 0) asm volatile("bar.arrive %0, 128;" :: "r"(3 + (cu >> 2)) : "memory");
        if (cu == 0) {
          nbar<11, 64>();
        } else if (cu == 4) {
          uint4 hv[16];
          if (c.rb > 0) {
            uint32_t n = 0;
#pragma unroll 1
            while (true) {
              uint32_t mn = 0xFFFFFFFFu;
#pragma unroll
              for (int i = 0; i < 16; ++i) hv[i] = ld_relaxed4(hbuf - 8 * 512 + i * 32);
#pragma unroll
              for (int i = 0; i < 16; ++i) mn = __vimin3_u32(__vimin3_u32(mn, hv[i].x, hv[i].y), hv[i].z, hv[i].w);
              if (__all_sync(0xffffffffu, mn != 0u)) break;
              if (++n > (1u << 20)) { g_err = 4u; break; }
            }
          } else {
#pragma unroll
            for (int i = 0; i < 16; ++i) hv[i] = make_uint4(~0u, ~0u, ~0u, ~0u);
          }
          nbar<10, 64>();
#pragma unroll
          for (int i = 0; i < 16; ++i)
            stsm_x4(rB - 4 * KVT + (((i >> 2) & 1) * 2 + (i >> 3)) * KVT + (X ^ ((i & 3) << 5)), ~hv[i].x, ~hv[i].y, ~hv[i].z, ~hv[i].w);
          asm volatile("bar.arrive 11, 64;" ::: "memory");
          nbar<9, 64>();
        } else {
          nbar_dyn(3 + (cu >> 2), 128);
        }
        PROFT(tid_ == 128, layer * 16 + 5);
#pragma unroll
        for (int i = 16; i < 32; ++i) xo[i] = 0u;
#pragma unroll 1
        for (int hp = 0; hp < 2; ++hp) {
          const uint32_t qad = sb + (XS + hp) * SLOT + rowo, kt = rB + 2 * hp * KVT - (lane & 8) * 128, vt = rB + (2 * hp + 1) * KVT;
          uint32_t qa[2][8];
#pragma unroll
          for (int i = 0; i < 16; ++i) { qa[i >> 3][i & 7] = kq[32 + i]; kq[32 + i] = kq[48 + i]; }
          float l0[2][4], l1[2][4];
#pragma unroll
          for (int nt = 0; nt < 4; ++nt)
#pragma unroll
            for (int h = 0; h < 2; ++h) {
              float sc[4] = {0.f, 0.f, 0.f, 0.f};
              uint32_t b0, b1, b2, b3;
              ldsm_x4(b0, b1, b2, b3, kt + nt * 1024 + (KX ^ (h << 6)));
              mma_bf16(sc, qa[h][0], qa[h][1], qa[h][2], qa[h][3], b0, b1);
              mma_bf16(sc, qa[h][4], qa[h][5], qa[h][6], qa[h][7], b2, b3);
              l0[h][nt] = (msk >> nt) & 1 ? (e ? sc[1] : sc[0]) * f0[nt] : -1e30f;
              l1[h][nt] = (msk >> (4 + nt)) & 1 ? (e ? sc[3] : sc[2]) * f1[nt] : -1e30f;
            }
          float mx0[2], mx1[2], s0[2], s1[2];
#pragma unroll
          for (int h = 0; h < 2; ++h) {
            mx0[h] = fmaxf(fmaxf(l0[h][0], l0[h][1]), fmaxf(l0[h][2], l0[h][3]));
            mx1[h] = fmaxf(fmaxf(l1[h][0], l1[h][1]), fmaxf(l1[h][2], l1[h][3]));
          }
#pragma unroll
          for (int o = 1; o <= 2; o <<= 1)
#pragma unroll
            for (int h = 0; h < 2; ++h) {
              mx0[h] = fmaxf(mx0[h], __shfl_xor_sync(0xffffffffu, mx0[h], o));
              mx1[h] = fmaxf(mx1[h], __shfl_xor_sync(0xffffffffu, mx1[h], o));
            }
#pragma unroll
          for (int h = 0; h < 2; ++h) {
#pragma unroll
            for (int nt = 0; nt < 4; ++nt) { l0[h][nt] = ex2(l0[h][nt] - mx0[h]); l1[h][nt] = ex2(l1[h][nt] - mx1[h]); }
            s0[h] = (l0[h][0] + l0[h][1]) + (l0[h][2] + l0[h][3]);
            s1[h] = (l1[h][0] + l1[h][1]) + (l1[h][2] + l1[h][3]);
          }
#pragma unroll
          for (int o = 1; o <= 2; o <<= 1)
#pragma unroll
            for (int h = 0; h < 2; ++h) {
              s0[h] += __shfl_xor_sync(0xffffffffu, s0[h], o);
              s1[h] += __shfl_xor_sync(0xffffffffu, s1[h], o);
            }
          uint32_t pl[2][4], phh[2][4];
#pragma unroll
          for (int h = 0; h < 2; ++h) {
            const float i0 = rcp(s0[h]), i1 = rcp(s1[h]);
#pragma unroll
            for (int nt = 0; nt < 4; ++nt) {
              const uint32_t pk = pack_bf16(l0[h][nt] * i0 * rj[nt], l1[h][nt] * i1 * rj[nt]);
              pl[h][nt] = e ? pk << 16 : pk & 0xFFFFu;
              phh[h][nt] = e ? pk & 0xFFFF0000u : pk >> 16;
            }
          }
          float oa[2][4][4];
#pragma unroll
          for (int h = 0; h < 2; ++h)
#pragma unroll
            for (int i = 0; i < 4; ++i) { oa[h][i][0] = oa[h][i][1] = oa[h][i][2] = oa[h][i][3] = 0.f; }
#pragma unroll
          for (int ks = 0; ks < 2; ++ks)
#pragma unroll
            for (int np = 0; np < 2; ++np)
#pragma unroll
              for (int h = 0; h < 2; ++h) {
                uint32_t b0, b1, b2, b3;
                ldsm_x4_t(b0, b1, b2, b3, vt + ks * 2048 + (X ^ (h << 6) ^ (np << 5)));
                mma_bf16(oa[h][2 * np], pl[h][2 * ks], phh[h][2 * ks], pl[h][2 * ks + 1], phh[h][2 * ks + 1], b0, b1);
                mma_bf16(oa[h][2 * np + 1], pl[h][2 * ks], phh[h][2 * ks], pl[h][2 * ks + 1], phh[h][2 * ks + 1], b2, b3);
              }
          mbar_wait(bar + B_XOLD, 0);
#pragma unroll
          for (int i = 0; i < 16; ++i) xo[i] = xo[16 + i];
#pragma unroll
          for (int jp = 0; jp < 4; ++jp) ldsm_x4(xo[16 + 4 * jp], xo[17 + 4 * jp], xo[18 + 4 * jp], xo[19 + 4 * jp], qad + (X ^ (jp << 5)));
#pragma unroll
          for (int h = 0; h < 2; ++h)
#pragma unroll
            for (int np = 0; np < 2; ++np)
              stsm_x4(qad + (X ^ (h << 6) ^ (np << 5)),
                      pack_bf16(oa[h][2 * np][0], oa[h][2 * np][1]), pack_bf16(oa[h][2 * np][2], oa[h][2 * np][3]),
                      pack_bf16(oa[h][2 * np + 1][0], oa[h][2 * np + 1][1]), pack_bf16(oa[h][2 * np + 1][2], oa[h][2 * np + 1][3]));
          if (FE) fence_async_smem();
          if (hp == 0 || H1B) {
            __syncwarp();
            slab_out_half(sb + (XS + hp) * SLOT, g_o + (size_t)m0 * D_ + g * 128 + hp * 64, wrow0, lane);
            __syncwarp();
            if (lane == 0) mbar_arrive(bar + (hp ? B_ODONE : B_OH1));
          }
        }
      } else {
        PHASE_CTX();
        const uint32_t pA = sb + (3 + 3 * wg) * SLOT + (rowo & 8191);
        const float sc0 = rs0 * L2E, sc1 = rs1 * L2E;
        const uint32_t wa0 = sb + SM_WPHI + lrow * 80 + lchk * 16;
        __syncwarp();
        float p[HPI][4][4];
        auto proj = [&](int hp) {
#pragma unroll
            for (int h = 0; h < HPI; ++h)
#pragma unroll
              for (int i = 0; i < 4; ++i) { p[h][i][0] = p[h][i][1] = p[h][i][2] = p[h][i][3] = 0.f; }
            const uint32_t wa = wa0 + hp * 5120;
#pragma unroll
            for (int ks = 0; ks < 2; ++ks)
#pragma unroll
              for (int np = 0; np < 2; ++np)
#pragma unroll
                for (int h = 0; h < HPI; ++h) {
                  uint32_t b0, b1, b2, b3;
                  ldsm_x4_t(b0, b1, b2, b3, wa + h * 2560 + ks * 1280 + np * 32);
                  mma_bf16(p[h][2 * np], kq[8 * h + 4 * ks], kq[8 * h + 4 * ks + 1], kq[8 * h + 4 * ks + 2], kq[8 * h + 4 * ks + 3], b0, b1);
                  mma_bf16(p[h][2 * np + 1], kq[8 * h + 4 * ks], kq[8 * h + 4 * ks + 1], kq[8 * h + 4 * ks + 2], kq[8 * h + 4 * ks + 3], b2, b3);
                }
        };
#pragma unroll 1
        for (int it = 0;; ++it) {
          const bool isq = it >= 2;
          const int hp = it & 1;
          const float mul0 = isq ? 1.f : rs0, mul1 = isq ? 1.f : rs1;
          uint32_t ph[2][4][4];
          proj(hp);
          bool bad = false;
          {
            float ss[HPI][2][4];
#pragma unroll
            for (int h = 0; h < HPI; ++h) {
#pragma unroll
              for (int i = 0; i < 4; ++i) {
                const float e0 = ex2(p[h][i][0] * sc0), e1 = ex2(p[h][i][1] * sc0), e2 = ex2(p[h][i][2] * sc1), e3 = ex2(p[h][i][3] * sc1);
                const float m0 = e0 * e1, m1 = e2 * e3, rr = rcp(m0 * m1), r0 = rr * m1, r1 = rr * m0;
                ph[h][i >> 1][(i & 1) * 2] = pack_bf16(e0, e1);
                ph[h][i >> 1][(i & 1) * 2 + 1] = pack_bf16(e2, e3);
                ph[h][2 + (i >> 1)][(i & 1) * 2] = pack_bf16(e1 * r0, e0 * r0);
                ph[h][2 + (i >> 1)][(i & 1) * 2 + 1] = pack_bf16(e3 * r1, e2 * r1);
              }
#pragma unroll
              for (int sg = 0; sg < 2; ++sg) {
                ss[h][sg][0] = ss[h][sg][1] = ss[h][sg][2] = ss[h][sg][3] = 0.f;
#pragma unroll
                for (int ks = 0; ks < 2; ++ks)
                  mma_bf16(ss[h][sg], ph[h][2 * sg + ks][0], ph[h][2 * sg + ks][1], ph[h][2 * sg + ks][2], ph[h][2 * sg + ks][3], 0x3F803F80u, 0x3F803F80u);
              }
            }
#pragma unroll
            for (int h = 0; h < HPI; ++h)
#pragma unroll
              for (int sg = 0; sg < 2; ++sg) {
                bad = bad || !(ss[h][sg][0] < PHI_MAX) || !(ss[h][sg][2] < PHI_MAX);
                const uint32_t iv = pack_bf16(rcp(ss[h][sg][0]) * mul0, rcp(ss[h][sg][2]) * mul1);
#pragma unroll
                for (int ks = 0; ks < 2; ++ks)
#pragma unroll
                  for (int j = 0; j < 4; ++j) ph[h][2 * sg + ks][j] = mul_bf16x2(ph[h][2 * sg + ks][j], iv, j & 1);
              }
          }
          if (__builtin_expect(__any_sync(0xffffffffu, bad), 0)) {
            proj(hp);
            float mx[HPI][2], mn[HPI][2];
#pragma unroll
            for (int h = 0; h < HPI; ++h)
#pragma unroll
              for (int r = 0; r < 2; ++r) {
                mx[h][r] = fmaxf(fmaxf(fmaxf(p[h][0][2 * r], p[h][0][2 * r + 1]), fmaxf(p[h][1][2 * r], p[h][1][2 * r + 1])),
                                 fmaxf(fmaxf(p[h][2][2 * r], p[h][2][2 * r + 1]), fmaxf(p[h][3][2 * r], p[h][3][2 * r + 1])));
                mn[h][r] = fminf(fminf(fminf(p[h][0][2 * r], p[h][0][2 * r + 1]), fminf(p[h][1][2 * r], p[h][1][2 * r + 1])),
                                 fminf(fminf(p[h][2][2 * r], p[h][2][2 * r + 1]), fminf(p[h][3][2 * r], p[h][3][2 * r + 1])));
              }
#pragma unroll
            for (int o = 1; o <= 2; o <<= 1)
#pragma unroll
              for (int h = 0; h < HPI; ++h)
#pragma unroll
                for (int r = 0; r < 2; ++r) {
                  mx[h][r] = fmaxf(mx[h][r], __shfl_xor_sync(0xffffffffu, mx[h][r], o));
                  mn[h][r] = fminf(mn[h][r], __shfl_xor_sync(0xffffffffu, mn[h][r], o));
                }
            float en[HPI][4][4], sp[HPI][2], sn[HPI][2];
#pragma unroll
            for (int h = 0; h < HPI; ++h) {
              mx[h][0] *= -sc0; mx[h][1] *= -sc1; mn[h][0] *= sc0; mn[h][1] *= sc1;
              sp[h][0] = sp[h][1] = sn[h][0] = sn[h][1] = 0.f;
            }
#pragma unroll
            for (int i = 0; i < 4; ++i)
#pragma unroll
              for (int e = 0; e < 4; ++e)
#pragma unroll
                for (int h = 0; h < HPI; ++h) {
                  en[h][i][e] = ex2(fmaf(p[h][i][e], (e >> 1) ? -sc1 : -sc0, mn[h][e >> 1]));
                  p[h][i][e] = ex2(fmaf(p[h][i][e], (e >> 1) ? sc1 : sc0, mx[h][e >> 1]));
                  sp[h][e >> 1] += p[h][i][e]; sn[h][e >> 1] += en[h][i][e];
                }
#pragma unroll
            for (int o = 1; o <= 2; o <<= 1)
#pragma unroll
              for (int h = 0; h < HPI; ++h)
#pragma unroll
                for (int r = 0; r < 2; ++r) {
                  sp[h][r] += __shfl_xor_sync(0xffffffffu, sp[h][r], o);
                  sn[h][r] += __shfl_xor_sync(0xffffffffu, sn[h][r], o);
                }
#pragma unroll
            for (int h = 0; h < HPI; ++h) {
              const float ip0 = rcp(sp[h][0]) * mul0, ip1 = rcp(sp[h][1]) * mul1, in0 = rcp(sn[h][0]) * mul0, in1 = rcp(sn[h][1]) * mul1;
#pragma unroll
              for (int cp = 0; cp < 2; ++cp) {
                ph[h][cp][0] = pack_bf16(p[h][2 * cp][0] * ip0, p[h][2 * cp][1] * ip0);
                ph[h][cp][1] = pack_bf16(p[h][2 * cp][2] * ip1, p[h][2 * cp][3] * ip1);
                ph[h][cp][2] = pack_bf16(p[h][2 * cp + 1][0] * ip0, p[h][2 * cp + 1][1] * ip0);
                ph[h][cp][3] = pack_bf16(p[h][2 * cp + 1][2] * ip1, p[h][2 * cp + 1][3] * ip1);
                ph[h][2 + cp][0] = pack_bf16(en[h][2 * cp][0] * in0, en[h][2 * cp][1] * in0);
                ph[h][2 + cp][1] = pack_bf16(en[h][2 * cp][2] * in1, en[h][2 * cp][3] * in1);
                ph[h][2 + cp][2] = pack_bf16(en[h][2 * cp + 1][0] * in0, en[h][2 * cp + 1][1] * in0);
                ph[h][2 + cp][3] = pack_bf16(en[h][2 * cp + 1][2] * in1, en[h][2 * cp + 1][3] * in1);
              }
            }
          }
#pragma unroll
          for (int i = 0; i < 48; ++i) kq[i] = kq[16 + i];
          if (!isq) {
#pragma unroll
            for (int h = 0; h < HPI; ++h)
#pragma unroll
              for (int cp = 0; cp < 4; ++cp)
                stsm_x4(pA + hp * 16384 + h * 8192 + (X ^ (cp << 5)), ph[h][cp][0], ph[h][cp][1], ph[h][cp][2], ph[h][cp][3]);
            PROFT(tid_ == 128, layer * 16 + 11);
            fence_async_smem();
            nbar<1, 256>();
            uint32_t hu = 2 * hp + wg;
            asm volatile("" : "+r"(hu));
            hu = __shfl_sync(0xffffffffu, hu, 0);
            const uint32_t dP = (((sb + 3 * SLOT + hu * 8192) & 0x3FFFF) >> 4) | (512u << 16);
            const uint32_t dV = (((sb + 5 * SLOT + hu * 4096) & 0x3FFFF) >> 4) | (((SM_SD - 5 * SLOT - hu * 4096) >> 4) << 16);
            float kva[20];
            wgmma_fence();
#pragma unroll
            for (int ks = 0; ks < 8; ++ks)
              wgmma_n40_tt(kva, desc64(dP + (ks >> 2) * 3072 + (ks & 3) * 128, 0x40000040u),
                           desc64(dV + (ks >> 2) * (3072u - (2816u << 16)) + (ks & 3) * 64, 0x80000020u), ks != 0);
            wgmma_commit();
            wgmma_wait<0>();
            nbar_dyn(3 + wg, 128);
            PROFT(tid_ == 128, layer * 16 + 12);
#pragma unroll
            for (int i = 0; i < 4; ++i)
              sts128(sb + (3 + hp) * SLOT + (cw * 128 + i * 32 + lane) * 16,
                     make_uint4(__float_as_uint(kva[4 * i]), __float_as_uint(kva[4 * i + 1]), __float_as_uint(kva[4 * i + 2]), __float_as_uint(kva[4 * i + 3])));
            if (t == 0) {
              sts_f(sb + SM_AP + hp * 512 + (cw * 8 + gq) * 8, kva[16]);
              sts_f(sb + SM_AP + hp * 512 + (cw * 8 + gq) * 8 + 4, kva[18]);
            }
            fence_async_smem();
            __syncwarp();
            if (lane == 0) mbar_arrive(bar + B_KVDONE - hp * 32);
            if (elected && hp) release2(bar + B_E1);
            PROFT(tid_ == 128, layer * 16 + 3);
            continue;
          }
          PROFT(tid_ == 128 && hp == 0, layer * 16 + 10);
          mbar_wait(bar + B_KVDONE - 32, (layer >> 1) & 1);
          mbar_wait(bar + B_KVRDY - hp * 8, (layer >> 1) & 1);
          PROFT(tid_ == 128 && hp == 0, layer * 16 + 5);
          {
            uint4 u[4];
#pragma unroll
            for (int i = 0; i < 4; ++i) u[i] = lds128(sb + (3 + hp) * SLOT + (cw * 128 + i * 32 + lane) * 16);
            const float zz = lds_f(sb + SM_AP + hp * 512 + ((cw * 8 + (lane & 7)) * 2 + ((lane >> 3) & 1)) * 4);
#pragma unroll
            for (int i = 0; i < 4; i += 2)
              stsm_x4(sb + (5 + 3 * hp) * SLOT + rowo + (X ^ ((i & 2) << 4)),
                      pack_bf16(__uint_as_float(u[i].x), __uint_as_float(u[i].y)), pack_bf16(__uint_as_float(u[i].z), __uint_as_float(u[i].w)),
                      pack_bf16(__uint_as_float(u[i + 1].x), __uint_as_float(u[i + 1].y)), pack_bf16(__uint_as_float(u[i + 1].z), __uint_as_float(u[i + 1].w)));
            if (lane < 16) sts128(sb + (5 + 3 * hp) * SLOT + rowo + ((4 ^ (lane & 7)) << 4), make_uint4(pack_bf16(zz, 0.f), 0u, 0u, 0u));
          }
          fence_async_smem();
          nbar<1, 256>();
          PROFT(tid_ == 128 && hp == 1, layer * 16 + 4);
          float oa[2][20];
          const uint32_t dK = __shfl_sync(0xffffffffu, (((sb + (5 + 3 * hp) * SLOT) & 0x3FFFF) >> 4) | (512u << 16), 0);
          wgmma_fence();
#pragma unroll
          for (int ks = 0; ks < 4; ++ks) {
#pragma unroll
            for (int hh = 0; hh < 2; ++hh) wgmma_n40_rs(oa[hh], ph[hh][ks], D128(dK + hh * 512 + ks * 128), ks != 0);
          }
          wgmma_commit();
          mbar_wait(bar + B_XOLD, 1);
#pragma unroll
          for (int jp = 0; jp < 8; ++jp)
            ldsm_x4(xo[4 * jp], xo[4 * jp + 1], xo[4 * jp + 2], xo[4 * jp + 3], sb + (XS + (jp >> 2)) * SLOT + rowo + (X ^ ((jp & 3) << 5)));
          wgmma_wait<0>();
#pragma unroll
          for (int hh = 0; hh < 2; ++hh) {
            const float dn0 = __shfl_sync(0xffffffffu, oa[hh][16], lane & ~3), dn1 = __shfl_sync(0xffffffffu, oa[hh][18], lane & ~3);
            const float i0 = __fdividef(1.f, dn0 + 1e-6f), i1 = __fdividef(1.f, dn1 + 1e-6f);
            const uint32_t qad = sb + (3 + hp) * SLOT + rowo, hx = hh << 6;
#pragma unroll
            for (int np = 0; np < 2; ++np)
              stsm_x4(qad + (X ^ hx ^ (np << 5)),
                      pack_bf16(oa[hh][8 * np] * i0, oa[hh][8 * np + 1] * i0), pack_bf16(oa[hh][8 * np + 2] * i1, oa[hh][8 * np + 3] * i1),
                      pack_bf16(oa[hh][8 * np + 4] * i0, oa[hh][8 * np + 5] * i0), pack_bf16(oa[hh][8 * np + 6] * i1, oa[hh][8 * np + 7] * i1));
          }
          if (FE) fence_async_smem();
          if (hp == 0 || H1A) {
            __syncwarp();
            slab_out_half(sb + (3 + hp) * SLOT, g_o + (size_t)m0 * D_ + g * 128 + hp * 64, wrow0, lane);
            __syncwarp();
            if (lane == 0) mbar_arrive(bar + (hp ? B_ODONE : B_OH1));
          }
          if (hp) break;
        }
      }
      if (!FE) fence_async_smem();
      __syncwarp();
      PROFT(lane == 0 && layer == PL, 216 + cw);
      if (lane == 0) mbar_arrive(bar + B_EPI);
      PROFT(tid_ == 128, layer * 16 + 6);
    }
    {
      PHASE_CTX();
      const uint32_t wu = __shfl_sync(0xffffffffu, wg, 0);
      const uint32_t dA0 = (((sb + wu * 8192) & 0x3FFFF) >> 4) | (1u << 16), dB0 = ((sb & 0x3FFFF) >> 4) | (512u << 16);
#pragma unroll
      for (int i = 0; i < 32; ++i) { acc[128 + 2 * i] = bf_lo(xo[i]); acc[129 + 2 * i] = bf_hi(xo[i]); }
      nbar_dyn(3 + wg, 128);
      uint64_t ta = (layer & 1) ? WO_A1 : WO_A0, tw = (layer & 1) ? WO_B1 : WO_B0;
#pragma unroll 1
      for (int i = 0; i < 16; ++i) {
        mbar_wait(bar + B_FULLT + i * 8, layer & 1);
        PROFT(tid_ == 128 && layer == PL, 160 + i);
        const uint32_t da = dA0 + ((uint32_t)ta & 15) * 1024, db = dB0 + ((uint32_t)tw & 15) * 1024;
        ta >>= 4; tw >>= 4;
        wgmma_fence();
#pragma unroll
        for (int k = 0; k < 4; ++k) wgmma_n128(acc, D128(da + k * 2), D128(db + k * 128), 1);
        wgmma_commit();
        if (i == 0) {
          if (elected) {
            if ((layer & 1) && wu) release2(bar + B_E1);
            release2(bar + B_E2);
          }
        } else {
          wgmma_wait<1>();
          if (elected && (i != 2 || !D1) && i < 13) release2(bar + B_CONS + (i - 1) * 8);
          if (elected && (unsigned)(i - 13) < 2u && layer + 1 < NLAYERS) release2(bar + B_EMPTYS + (i - 13) * 8);
        }
        if (i == H1_AT && !((layer & 1) ? H1B : H1A)) {
          slab_out_half(sb + ((layer & 1) ? XS + 1 : 4) * SLOT, g_o + (size_t)m0 * D_ + g * 128 + 64, wrow0, lane);
          __syncwarp();
          if (lane == 0) mbar_arrive(bar + B_ODONE);
        }
        if (i == 1 && D1) {
          wgmma_wait<0>();
          if (elected) release2(bar + B_CONS + 8);
        }
      }
      wgmma_wait<0>();
#pragma unroll
      for (int i = 128; i < 192; ++i) asm volatile("" : "+f"(acc[i]) :: "memory");
      if (elected && layer + 1 < NLAYERS) release2(bar + B_EMPTYS + 16);
      PROFT(tid_ == 128, layer * 16 + 7);
    }
    {
      PHASE_CTX();
#pragma unroll
      for (int jp = 0; jp < 8; ++jp)
        stsm_x4(sb + (XS + (jp >> 2)) * SLOT + rowo + (X ^ ((jp & 3) << 5)),
                pack_bf16(acc[128 + 8 * jp], acc[129 + 8 * jp]), pack_bf16(acc[130 + 8 * jp], acc[131 + 8 * jp]),
                pack_bf16(acc[132 + 8 * jp], acc[133 + 8 * jp]), pack_bf16(acc[134 + 8 * jp], acc[135 + 8 * jp]));
      fence_async_smem();
      __syncwarp();
      const bool last = layer == NLAYERS - 1;
      slab_out_half(sb + XS * SLOT, (last ? c.out : g_x) + (size_t)m0 * D_ + g * 128, wrow0, lane);
      if (last) slab_out_half(sb + (XS + 1) * SLOT, c.out + (size_t)m0 * D_ + g * 128 + 64, wrow0, lane);
      __syncwarp();
      if (lane == 0) mbar_arrive(bar + (last ? B_XDONE : B_XH0));
      PROFT(tid_ == 128, layer * 16 + 24);
      if (last) break;
      nbar_dyn(3 + wg, 128);
    }
  }
}

#define JP 2
__device__ __forceinline__ int kblock(int i, int g, int d) {
  const int j = i >> 1;
  return ((g + (d <= JP || j < JP ? j : j == JP ? d : j - 1 + (j - 1 >= d ? 1 : 0))) & 7) * 2 + (i & 1);
}

#define WOORD 0xFDB9753ECA864210ull
__device__ __forceinline__ int wo_kblock(int m, int g) { return (2 * g + (int)((WOORD >> (4 * m)) & 15)) & 15; }

__global__ void __cluster_dims__(2, 1, 1) __launch_bounds__(384, 1)
mega_kernel(const __grid_constant__ CUtensorMap tm_x0, const __grid_constant__ CUtensorMap tm_x,
            const __grid_constant__ CUtensorMap tm_o,
            const __grid_constant__ CUtensorMap tm_wA, const __grid_constant__ CUtensorMap tm_wB,
            const __grid_constant__ CUtensorMap tm_woA, const __grid_constant__ CUtensorMap tm_woB,
            const bf16* __restrict__ wA, const bf16* __restrict__ wB,
            const bf16* __restrict__ woA, const bf16* __restrict__ woB, const bf16* __restrict__ wphi, bf16* __restrict__ out) {
  extern __shared__ uint8_t smem_raw[];
  const uint32_t sb = (smem_u32(smem_raw) + 1023u) & ~1023u;
  const uint32_t bar = sb + SM_BAR;
  const int warp = __shfl_sync(0xffffffffu, threadIdx.x >> 5, 0), lane = threadIdx.x & 31;
  const int cr = blockIdx.x & 1;
  const int g = (blockIdx.x >> 1) & 7;
  const int rb = (blockIdx.x >> 4) * 2 + cr;
  const int m0 = rb * 128, cl = ((rb >> 1) - g) & 7;
  const int isum0 = 2 * min(cl, JP);

  if (lane < 2 || (lane == 2 && warp >= 1 && warp < 7) || threadIdx.x == 67 || (warp >= 4 && (lane & 28) == 4)) {
    const int i = lane < 2 ? 3 + warp * 2 + lane : lane == 3 ? 30 : lane > 3 ? 12 + warp * 4 + lane : warp < 4 ? warp - 1 : warp + 23;
    mbar_init(bar + i * 8, i < 32 ? 1u << ((BAR_CNT >> (2 * i)) & 3) : i < 48 ? 1u : i == 60 ? 16u : i < 63 ? 4u : 8u);
    asm volatile("fence.mbarrier_init.release.cluster;" ::: "memory");
  }
  __syncwarp();
  asm volatile("barrier.cluster.arrive.relaxed.aligned;" ::: "memory");
  if (warp < 3 && lane == 0) {
    if (warp != 1) {
      const uint32_t xb = bar + (warp ? B_X1 : B_XOLD);
      mbar_expect_tx(xb, 16384);
      tma_load_2d(sb + (XS + (warp >> 1)) * SLOT, &tm_x0, g * 128 + warp * 32, m0, xb);
    } else {
      mbar_expect_tx(bar + B_FULLS, 49152);
#pragma unroll 1
      for (int j = 0; j < 6; ++j)
        tma_load_2d(sb + (j < 4 ? j + 4 : j - 2) * 8192, &tm_wA, (j < 4 ? 1024 + (j >> 1) * 1024 : 0) + g * 128 + (j & 1) * 64, g * 128, bar + B_FULLS);
    }
  }
  __syncwarp();
  cluster_wait();
  PROFT(threadIdx.x == 0, 125);

  if (warp < 4) {
    asm volatile("setmaxnreg.dec.sync.aligned.u32 40;");
    const unsigned int epoch = ld_relaxed(&g_epoch);
    const unsigned int xbase = epoch * NLAYERS, cbase = epoch * 16u;
    auto wo_loads_l = [&](int layer, int mode) {
      const CUtensorMap* tx = layer == 0 ? &tm_x0 : &tm_x;
      const CUtensorMap* two = (layer & 1) ? &tm_woB : &tm_woA;
      uint32_t ready = 0u;
#pragma unroll 1
      for (int n = mode == 2 ? 10 : 0; n < 30; ++n) {
        const uint32_t op = c_ops[layer & 1][n];
        const int m = (op >> 4) & 15, kb = wo_kblock(m, g);
        uint32_t dst = sb + ((op >> 8) & 15) * SLOT, fb = bar + B_FULLT + m * 8, eb = bar + B_CONS + (op >> 12) * 8;
        int kc = kb * 64;
        if (op & 1) {
          if (!(mode & 2)) continue;
          if (!((ready >> kb) & 1)) {
            PROFT(m == 2 && lane == 0, 64 + layer * 16 + 2);
            src_wait<0>(g_of + rb * 32, xbase + layer + 1, 1u << kb, ready, lane);
            fence_async_all();
          }
          if (op & 2) mbar_wait_u(bar + B_ODONE, layer & 1);
          asm volatile("" : "+r"(dst), "+r"(fb), "+r"(eb), "+r"(kc));
          mbar_wait_u(eb, layer & 1);
          tma_2d_e(dst, &tm_o, kc, m0, fb);
          PROFT(lane == 0 && layer == PL, 176 + m);
          PROFT(m == 3 && lane == 0, 64 + layer * 16 + 3);
        } else {
          if (!(mode & 1)) continue;
          dst += cr * 8192;
          asm volatile("" : "+r"(dst), "+r"(fb), "+r"(eb), "+r"(kc));
          mbar_wait_u(eb, layer & 1);
          tma_2d_mc_e(dst, two, g * 128 + cr * 64, kc, fb);
          expect_tx_e(fb, m < 2 ? 16384 : 32768);
          PROFT(lane == 0 && layer == PL, 144 + m);
          if (n == 2) {
            fence_async_all();
            expect_tx_e(bar + B_XOLD, 32768);
            tma_2d_e(sb + XS * SLOT, tx, g * 128, m0, bar + B_XOLD);
            tma_2d_e(sb + (XS + 1) * SLOT, tx, g * 128 + 64, m0, bar + B_XOLD);
          }
        }
      }
    };
#define wo_loads(mode) wo_loads_l(layer, mode)
    auto wo_a = [&](int layer) {
      uint64_t ts = ((layer & 1) ? WO_A1 : WO_A0) >> 8, td = ((layer & 1) ? WO_DA1 : WO_DA0) >> 8, tk = WOORD >> 8;
      uint32_t ready = 0u;
#pragma unroll 1
      for (int m = 2; m < 16; ++m) {
        const int kb = (2 * g + (uint32_t)tk) & 15;
        uint32_t dst = sb + ((uint32_t)ts & 15) * SLOT, fb = bar + B_FULLT + m * 8, eb = bar + B_CONS + ((uint32_t)td & 15) * 8;
        int kc = kb * 64;
        ts >>= 4; td >>= 4; tk >>= 4;
        if (!((ready >> kb) & 1)) {
          PROFT(m == 2 && lane == 0, 64 + layer * 16 + 2);
          src_wait<0>(g_of + rb * 32, xbase + layer + 1, 1u << kb, ready, lane);
          fence_async_all();
        }
        if (m == 7 - (layer & 1)) mbar_wait_u(bar + B_ODONE, layer & 1);
        asm volatile("" : "+r"(dst), "+r"(fb), "+r"(eb), "+r"(kc));
        mbar_wait_u(eb, layer & 1);
        tma_2d_e(dst, &tm_o, kc, m0, fb);
        PROFT(lane == 0 && layer == PL, 176 + m);
        if (m == PPOLL && (layer & 1)) { ready = poll_flags(g_of + rb * 32, xbase + layer + 1, lane); fence_async_all(); }
      }
    };
    auto wo_w = [&](int layer) {
      const CUtensorMap* tx = layer == 0 ? &tm_x0 : &tm_x;
      const CUtensorMap* two = (layer & 1) ? &tm_woB : &tm_woA;
      uint64_t ts = (layer & 1) ? WO_B1 : WO_B0, td = (layer & 1) ? WO_DB1 : WO_DB0, tk = WOORD;
#pragma unroll 1
      for (int m = 0; m < 16; ++m) {
        uint32_t dst = sb + ((uint32_t)ts & 15) * SLOT + cr * 8192, fb = bar + B_FULLT + m * 8, eb = bar + B_CONS + ((uint32_t)td & 15) * 8;
        int kc = ((2 * g + (uint32_t)tk) & 15) * 64;
        ts >>= 4; td >>= 4; tk >>= 4;
        asm volatile("" : "+r"(dst), "+r"(fb), "+r"(eb), "+r"(kc));
        mbar_wait_u(eb, layer & 1);
        tma_2d_mc_e(dst, two, g * 128 + cr * 64, kc, fb);
        expect_tx_e(fb, m < 2 ? 16384 : 32768);
        PROFT(lane == 0 && layer == PL, 144 + m);
        if (m == XOLD_AT) {
          fence_async_all();
          expect_tx_e(bar + B_XOLD, 32768);
          tma_2d_e(sb + XS * SLOT, tx, g * 128, m0, bar + B_XOLD);
          tma_2d_e(sb + (XS + 1) * SLOT, tx, g * 128 + 64, m0, bar + B_XOLD);
        }
      }
    };
    auto kv_fetch = [&](int layer, int hp) {
      const float* kvl = g_kv + ((size_t)((epoch & 1) * 2 + (layer >> 1)) * 8 + g) * 8448;
      flag_wait(&g_kvflag[hp * 8 + g].v, epoch * (16u * ((NLAYERS + 1) / 2)) + 16u * ((layer >> 1) + 1));
      fence_async_all();
      mbar_expect_tx(bar + B_KVRDY - hp * 8, 16896);
      bulk_load(sb + (3 + hp) * SLOT, kvl + hp * 4096, 16384, bar + B_KVRDY - hp * 8);
      bulk_load(sb + SM_AP + hp * 512, kvl + 8192 + hp * 128, 512, bar + B_KVRDY - hp * 8);
    };
    if (warp == 0) {
#pragma unroll 1
      for (int layer = 0; layer < NLAYERS; ++layer) {
        const CUtensorMap* tx = layer == 0 ? &tm_x0 : &tm_x;
        const CUtensorMap* tw = (layer & 1) ? &tm_wB : &tm_wA;
        uint32_t s = layer == 0 ? 1 : 0, u = 0, ready = layer == 0 ? 0xFFFFu : 0u;
#pragma unroll 1
        for (int i = s; i < 16; ++i) {
          const int kb = layer == 0 ? kblock(i, g, cl) : wo_kblock(i, g), kc = kb * 64;
          const uint32_t fb = bar + B_FULLS + s * 8;
          const uint32_t kd = sb + (((QK >> (4 * s)) & 15) + cr) * SLOT, qd = sb + ((QQ >> (4 * s)) & 15) * SLOT + cr * 8192;
          const uint32_t need = 1u << kb;
          const bool early = i >= 2 && (ready & need) == need;
          mbar_wait_u(bar + B_EMPTYS + s * 8, (u + (s ? layer : 0) + 1) & 1);
          if (layer == 0 && (unsigned)(i - isum0 - 3) < 2u) mbar_wait_u(bar + B_CSFREE + (i - isum0 - 3) * 8, 0);
          if (early) tma_2d_e(sb + ((QA >> (4 * s)) & 15) * SLOT, tx, kc, m0, fb);
          tma_2d_mc_e(kd, tw, 1024 + cr * 1024 + g * 128, kc, fb);
          tma_2d_mc_e(kd + 8192, tw, 1024 + cr * 1024 + g * 128 + 64, kc, fb);
          tma_2d_mc_e(qd, tw, g * 128 + cr * 64, kc, fb);
          expect_tx_e(fb, i < 2 ? 49152 : 65536);
#define PFD 4
#define PFM 3
#define PFS 2
          if (layer == 0 && rb >= PFM && i == max(PFS, rb - PFD)) {
#pragma unroll 1
            for (int j = 0; j < 6; ++j) tma_pf_e(tw, (j >> 1) * 1024 + g * 128 + (j & 1) * 64, ((2 * g + rb) & 15) * 64);
          }
          if (i >= 2 && !early) {
            PROFT(i == 2 && lane == 0, 64 + layer * 16 + 0);
            src_wait<0>(g_xf + rb * 32, xbase + layer + 1, need, ready, lane);
            PROFT(i == 2 && lane == 0, 64 + layer * 16 + 1);
            fence_async_all();
            tma_2d_e(sb + ((QA >> (4 * s)) & 15) * SLOT, tx, kc, m0, fb);
          }
          if (++s == 3) { s = 0; ++u; }
        }
        if (layer < WSPLIT) wo_loads(3); else wo_a(layer);
      }
    } else {
      if (warp >= 2) {
        const int h2 = threadIdx.x - 64;
#pragma unroll 1
        for (int i = h2; i < 512; i += 64)
          asm volatile("cp.async.cg.shared.global [%0], [%1], 16;" ::"r"(sb + SM_WPHI + (i >> 2) * 80 + (i & 3) * 16), "l"(wphi + (size_t)g * 4096 + i * 8) : "memory");
        sts128(sb + SM_SD + h2 * 128 + (h2 & 3) * 16, make_uint4(0u, 0u, 0u, 0u));
        sts128(sb + SM_SD + h2 * 128 + 64 + (h2 & 3) * 16, make_uint4(0u, 0u, 0u, 0u));
        if (h2 < 16) sts_f(sb + SM_RS + h2 * 4, 0.f);
        if (h2 == 1) sts_f(sb + SM_EPOCH + 4, 0.f);
        if (h2 == 0) sts_f(sb + SM_EPOCH, __uint_as_float(epoch));
        float4* kz = reinterpret_cast<float4*>(g_kv + (size_t)((epoch & 1) ^ 1) * (2 * 8 * 8448)) + blockIdx.x * 264;
#pragma unroll 1
        for (int i = h2; i < 264; i += 64) kz[i] = make_float4(0.f, 0.f, 0.f, 0.f);
        uint4* hz = g_halo + (size_t)((epoch & 1) ^ 1) * (2 * 128 * 512) + blockIdx.x * 1024;
#pragma unroll 1
        for (int i = h2; i < 1024; i += 64) hz[i] = make_uint4(0u, 0u, 0u, 0u);
        if (h2 < 12) reinterpret_cast<float4*>(g_cs + ((epoch & 1) ^ 1) * 6144 + blockIdx.x * 48)[h2] = make_float4(0.f, 0.f, 0.f, 0.f);
      }
      {
        const int ht = threadIdx.x - 32, bc = ht % 48, hf = ht / 48;
        const int st = (isum0 + cr) % 3;
        const uint32_t src = sb + (bc < 32 ? ((QK >> (4 * st)) & 15) * SLOT + (bc >> 3) * 8192 : ((QQ >> (4 * st)) & 15) * SLOT + ((bc >> 3) - 4) * 8192) + hf * 4096;
        float s[8] = {0.f, 0.f, 0.f, 0.f, 0.f, 0.f, 0.f, 0.f};
        mbar_wait(bar + B_CSL, 0);
        if (ht < 6) asm volatile("cp.async.bulk.prefetch.tensor.2d.L2.global.tile [%0, {%1, %2}];" ::"l"(&tm_wB), "r"((ht >> 1) * 1024 + g * 128 + (ht & 1) * 64), "r"(rb * 64) : "memory");
#pragma unroll 4
        for (int r = 0; r < 32; ++r) {
          const uint4 v = lds128(src + r * 128 + (((bc ^ r) & 7) << 4));
          s[0] += bf_lo(v.x); s[1] += bf_hi(v.x); s[2] += bf_lo(v.y); s[3] += bf_hi(v.y);
          s[4] += bf_lo(v.z); s[5] += bf_hi(v.z); s[6] += bf_lo(v.w); s[7] += bf_hi(v.w);
        }
        float* cd = g_cs + (epoch & 1) * 6144 + g * 384 + bc * 8;
        red_add4(cd, s[0], s[1], s[2], s[3]);
        red_add4(cd + 4, s[4], s[5], s[6], s[7]);
        nbar<2, 96>();
        if (ht == 32) { release2(bar + B_CSFREE + cr * 8); flag_add(&g_csflag[g].v); }
      }
      if (warp == 1) {
        if (lane >= 27) {
          const CUtensorMap* tm = lane == 27 ? &tm_o : lane == 28 ? &tm_wB : lane == 29 ? &tm_woA : lane == 30 ? &tm_woB : &tm_x;
          asm volatile("prefetch.tensormap [%0];" ::"l"(tm) : "memory");
        }
        if (lane == 0) {
#pragma unroll 1
          for (int e = 0;; ++e) {
            if (e > 0 && e < NLAYERS) {
              mbar_wait(bar + B_XH0, (e - 1) & 1);
              flag_set(g_xf + rb * 32 + 2 * g, xbase + e + 1);
            }
            mbar_wait(bar + B_XDONE, e & 1);
            PROFT(e < 4, 64 + e * 16 + 4);
            if (e == NLAYERS) {
              if (blockIdx.x == 0) g_epoch = epoch + 1;
              break;
            }
            PROFT(e < 4, 64 + e * 16 + 5);
            flag_set(g_xf + rb * 32 + 2 * g + 1, xbase + e + 1);
            PROFT(e < 4, 64 + e * 16 + 7);
            if ((e & 1) == 0) {
              float* kvl = g_kv + ((size_t)((epoch & 1) * 2 + (e >> 1)) * 8 + g) * 8448;
#pragma unroll 1
              for (int hp = 0; hp < 2; ++hp) {
                mbar_wait(bar + B_KVDONE - hp * 32, (e >> 1) & 1);
                bulk_red_add(kvl + hp * 4096, sb + (3 + hp) * SLOT, 16384);
                bulk_red_add(kvl + 8192 + hp * 128, sb + SM_AP + hp * 512, 512);
                bulk_commit();
                PROFT(e < 4, 64 + e * 16 + 6);
                bulk_wait0();
                PROFT(e < 4, 64 + e * 16 + 10);
                fence_async_all();
                flag_add(&g_kvflag[hp * 8 + g].v);
              }
            }
            mbar_wait(bar + B_OH1, e & 1);
            flag_set(g_of + rb * 32 + 2 * g, xbase + e + 1);
            PROFT(e < 4, 64 + e * 16 + 9);
            mbar_wait(bar + B_ODONE, e & 1);
            PROFT(e < 4, 64 + e * 16 + 8);
            flag_set(g_of + rb * 32 + 2 * g + 1, xbase + e + 1);
            PROFT(e < 4, 64 + e * 16 + 11);
          }
        }
      } else {
        const int h2 = threadIdx.x - 64;
        if (h2 == 0) l2_prefetch(woA + (size_t)blockIdx.x * 8192, 16384);
        if (h2 == 32) l2_prefetch(woB + (size_t)blockIdx.x * 8192, 16384);
        const float* cs = g_cs + (epoch & 1) * 6144;
#pragma unroll 1
        for (int layer = 0; layer < NLAYERS; ++layer) {
          if (layer < 2) {
            if (lane == 0) flag_wait_slow(&g_csflag[layer * 8 + g].v, cbase + 16u);
            __syncwarp();
#pragma unroll 1
            for (int c4 = h2; c4 < 96; c4 += 64) {
              const float4 a = __ldcg(reinterpret_cast<const float4*>(cs + layer * 3072 + g * 384 + c4 * 4));
              const float av[4] = {a.x, a.y, a.z, a.w};
#pragma unroll
              for (int j = 0; j < 4; ++j) {
                const float c1 = bf16r(av[j]), c2 = bf16r(av[j] - c1), c3 = (av[j] - c1) - c2;
                sts128(sb + SM_BP + layer * 6144 + (c4 * 4 + j) * 16, make_uint4(pack_bf16(c1, c2), pack_bf16(c3, 0.f), 0u, 0u));
              }
            }
            asm volatile("cp.async.wait_all;" ::: "memory");
            fence_async_smem();
            nbar<5, 64>();
            if (h2 == 0) mbar_arrive(bar + (layer ? B_CS2 : B_CS));
            PROFT(h2 == 0, 64 + layer * 16 + 12);
          }
          const bool hal = (layer & 1) && rb > 0;
          {
            uint32_t rdy = 0u;
            src_wait<256>(g_xf + rb * 32, xbase + layer + 1, 0xAAAAu, rdy, lane);
            rdy = 0u;
            if (hal) src_wait<256>(g_xf + (rb - 1) * 32, xbase + layer + 1, 0xAAAAu, rdy, lane);
          }
#pragma unroll 1
          for (int r = h2 + (hal ? 0 : 16); r < 144; r += 64) {
            const float2* sp = g_stats + (layer & 1) * 8 * S_ + (m0 - 16 + r);
            float2 u[8];
#pragma unroll
            for (int i = 0; i < 8; ++i) u[i] = __ldcg(sp + i * S_);
            const float sum = ((u[0].x + u[1].x) + (u[2].x + u[3].x)) + ((u[4].x + u[5].x) + (u[6].x + u[7].x));
            const float sq = ((u[0].y + u[1].y) + (u[2].y + u[3].y)) + ((u[4].y + u[5].y) + (u[6].y + u[7].y));
            const float mean = sum * (1.f / D_);
            const float var = fmaxf(fmaf(-sum, mean, sq) * (1.f / D_), 0.f);
            const float sd = bf16r(sqrtf(bf16r(bf16r(var) + 1e-5f)));
            sts_f(sb + SM_RS + r * 4, 1.f / sd);
            if (r >= 16) {
              const float hm = -0.5f * bf16r(mean);
              sts16(sb + SM_SD + (r - 16) * 64 + ((r >> 1) & 3) * 16, __float_as_uint(sd) >> 16);
              sts128(sb + SM_AP + (r - 16) * 16, make_uint4(pack_bf16(hm, hm), pack_bf16(hm, 0.f), 0u, 0u));
            }
          }
          fence_async_smem();
          nbar<5, 64>();
          if (h2 == 0) {
            mbar_arrive(bar + B_STAT);
            PROFT(true, 64 + layer * 16 + 14);
          }
          __syncwarp();
          if (warp == 3) {
            wo_w(__shfl_sync(0xffffffffu, layer, 0));
          } else if (!(layer & 1)) {
            if (lane == 0) {
#pragma unroll 1
              for (int hp = 0; hp < 2; ++hp) {
                mbar_wait(bar + B_KVDONE - hp * 32, (layer >> 1) & 1);
                kv_fetch(layer, hp);
                PROFT(hp == 0, 64 + layer * 16 + 15);
              }
            }
            __syncwarp();
          }
          if (layer == 0 && warp == 2) {
#pragma unroll 1
            for (int wi = 0; wi < 6; ++wi) {
              float sB[8];
              colsum_load(wB, rb, g, wi, lane, sb + SM_BP + 6144, sB);
              colsum_red(g_cs + (epoch & 1) * 6144 + 3072, g, wi, lane, sB);
            }
            __syncwarp();
            if (lane == 0) flag_add(&g_csflag[8 + g].v);
            PROFT(h2 == 0, 64 + 13);
          }
        }
      }
    }
    __syncwarp();
    asm volatile("barrier.cluster.arrive.relaxed.aligned;\nbarrier.cluster.wait.aligned;\n" ::: "memory");
  } else {
    asm volatile("setmaxnreg.inc.sync.aligned.u32 232;");
    PROFT(threadIdx.x == 128, 0);
    Ctx c; c.sb = sb; c.g = g; c.rb = rb; c.isum = isum0 + cr; c.cu = warp - 4; c.out = out;
    consumer(c);
    asm volatile("bar.warp.sync 0xffffffff;\nbarrier.cluster.arrive.relaxed.aligned;\nbarrier.cluster.wait.aligned;\n" ::: "memory");
  }
}

typedef CUresult (*PFN_encodeTiled)(CUtensorMap*, CUtensorMapDataType, cuuint32_t, void*, const cuuint64_t*, const cuuint64_t*,
                                    const cuuint32_t*, const cuuint32_t*, CUtensorMapInterleave, CUtensorMapSwizzle,
                                    CUtensorMapL2promotion, CUtensorMapFloatOOBfill);

static CUtensorMap make_map(PFN_encodeTiled enc, const void* ptr, uint64_t cols, uint64_t rows, uint32_t box_c, uint32_t box_r, uint32_t nb = 1) {
  CUtensorMap m;
  cuuint64_t dims[3] = {nb > 1 ? box_c : cols, rows, cols / box_c};
  cuuint64_t strides[2] = {cols * 2, box_c * 2};
  cuuint32_t box[3] = {box_c, box_r, nb};
  cuuint32_t es[3] = {1, 1, 1};
  CUresult r = enc(&m, CU_TENSOR_MAP_DATA_TYPE_BFLOAT16, nb > 1 ? 3 : 2, const_cast<void*>(ptr), dims, strides, box, es, CU_TENSOR_MAP_INTERLEAVE_NONE,
      CU_TENSOR_MAP_SWIZZLE_128B, CU_TENSOR_MAP_L2_PROMOTION_L2_256B, CU_TENSOR_MAP_FLOAT_OOB_FILL_NONE);
  (void)r;
  return m;
}

extern "C" void kernel_launch(void* const* d_in, const int* in_sizes, int n_in, void* d_out, int out_size) {
  const bf16* A_x = (const bf16*)d_in[0];
  const bf16* A_wqkv = (const bf16*)d_in[1];
  const bf16* A_wphi = (const bf16*)d_in[2];
  const bf16* A_wo = (const bf16*)d_in[3];
  const bf16* B_wqkv = (const bf16*)d_in[5];
  const bf16* B_wo = (const bf16*)d_in[6];
  bf16* out = (bf16*)d_out;

  static PFN_encodeTiled enc = nullptr;
  static bf16 *p_x, *p_o;
  if (!enc) {
    void* fn = nullptr; cudaDriverEntryPointQueryResult qr;
    cudaGetDriverEntryPoint("cuTensorMapEncodeTiled", &fn, cudaEnableDefault, &qr);
    enc = (PFN_encodeTiled)fn;
    cudaGetSymbolAddress((void**)&p_x, g_x);
    cudaGetSymbolAddress((void**)&p_o, g_o);
    cudaFuncSetAttribute(mega_kernel, cudaFuncAttributeMaxDynamicSharedMemorySize, SM_TOTAL);
  }
  CUtensorMap tm_x0 = make_map(enc, A_x, 1024, 2048, 64, 128);
  CUtensorMap tm_x = make_map(enc, p_x, 1024, 2048, 64, 128);
  CUtensorMap tm_o = make_map(enc, p_o, 1024, 2048, 64, 128);
  CUtensorMap tm_wA = make_map(enc, A_wqkv, 3072, 1024, 64, 64);
  CUtensorMap tm_wB = make_map(enc, B_wqkv, 3072, 1024, 64, 64);
  CUtensorMap tm_woA = make_map(enc, A_wo, 1024, 1024, 64, 64);
  CUtensorMap tm_woB = make_map(enc, B_wo, 1024, 1024, 64, 64);
  mega_kernel<<<128, 384, SM_TOTAL, cudaStreamPerThread>>>(tm_x0, tm_x, tm_o, tm_wA, tm_wB, tm_woA, tm_woB,
                                                           A_wqkv, B_wqkv, A_wo, B_wo, A_wphi, out);
}
```

```cpp
#include <cuda_runtime.h>
#include <cuda_bf16.h>
#include <cuda.h>
#include <stdint.h>

typedef __nv_bfloat16 bf16;

constexpr int S_ = 2048, D_ = 1024;

struct __align__(128) Flag { unsigned int v; unsigned int pad[31]; };
__device__ __align__(1024) bf16 g_x[S_ * D_];
__device__ __align__(1024) bf16 g_o[S_ * D_];
__device__ __align__(1024) uint4 g_halo[2 * 2 * 128 * 512];
__device__ __align__(1024) float g_kv[2 * 2 * 8 * 8448];
__device__ __align__(1024) float2 g_stats[2 * 8 * S_];
__device__ __align__(1024) float g_cs[2 * 2 * 3072];
__device__ Flag g_kvflag[16], g_csflag[16];
__device__ __align__(128) unsigned int g_xf[16 * 32], g_of[16 * 32];
__device__ unsigned int g_epoch, g_err;
#define PROFT(cond, idx) asm volatile("" ::: "memory")

__device__ __forceinline__ uint32_t smem_u32(const void* p) { return (uint32_t)__cvta_generic_to_shared(p); }
__device__ __forceinline__ void mbar_init(uint32_t bar, uint32_t count) {
  asm volatile("mbarrier.init.shared::cta.b64 [%0], %1;" ::"r"(bar), "r"(count) : "memory");
}
__device__ __forceinline__ void mbar_expect_tx(uint32_t bar, uint32_t bytes) {
  asm volatile("mbarrier.arrive.expect_tx.shared::cta.b64 _, [%0], %1;" ::"r"(bar), "r"(bytes) : "memory");
}
__device__ __forceinline__ void mbar_arrive(uint32_t bar) {
  asm volatile("mbarrier.arrive.shared::cta.b64 _, [%0];" ::"r"(bar) : "memory");
}
__device__ __forceinline__ bool mbar_try_wait(uint32_t bar, uint32_t parity) {
  uint32_t ok;
  asm volatile("{\n.reg .pred p;\nmbarrier.try_wait.parity.shared::cta.b64 p, [%1], %2;\nselp.b32 %0, 1, 0, p;\n}\n"
               : "=r"(ok) : "r"(bar), "r"(parity) : "memory");
  return ok != 0;
}
__device__ __forceinline__ bool mbar_test_wait(uint32_t bar, uint32_t parity) {
  uint32_t ok;
  asm volatile("{\n.reg .pred p;\nmbarrier.test_wait.parity.shared::cta.b64 p, [%1], %2;\nselp.b32 %0, 1, 0, p;\n}\n"
               : "=r"(ok) : "r"(bar), "r"(parity) : "memory");
  return ok != 0;
}
__device__ __forceinline__ uint64_t gtimer() {
  uint64_t t; asm volatile("mov.u64 %0, %globaltimer;" : "=l"(t)); return t;
}
__device__ __forceinline__ void mbar_wait(uint32_t bar, uint32_t parity) {
  uint32_t n = 0;
#pragma unroll 1
  while (!mbar_try_wait(bar, parity)) {
    if (++n > (1u << 22)) { g_err = 1u; break; }
  }
}
__device__ __forceinline__ unsigned int ld_acquire(const unsigned int* p) {
  unsigned int v; asm volatile("ld.acquire.gpu.global.u32 %0, [%1];" : "=r"(v) : "l"(p) : "memory"); return v;
}
__device__ __forceinline__ void flag_add(unsigned int* p) {
  asm volatile("red.release.gpu.global.add.u32 [%0], 1;" ::"l"(p) : "memory");
}
__device__ __forceinline__ void flag_set(unsigned int* p, unsigned int v) {
  asm volatile("st.release.gpu.global.u32 [%0], %1;" ::"l"(p), "r"(v) : "memory");
}
template <int SLEEP>
__device__ __forceinline__ void src_wait(const unsigned int* f, unsigned int target, uint32_t need, uint32_t& ready, int lane) {
  uint32_t n = 0;
#pragma unroll 1
  while ((ready & need) != need) {
    const unsigned int v = ld_acquire(f + (lane & 15));
    ready = __ballot_sync(0xffffffffu, (int)(v - target) >= 0);
    if (SLEEP) { if ((ready & need) != need) __nanosleep(SLEEP); }
    if (++n > (1u << 20)) { g_err = 3u; break; }
  }
  __syncwarp();
}
__device__ __forceinline__ unsigned int ld_relaxed(const unsigned int* p) {
  unsigned int v; asm volatile("ld.relaxed.gpu.global.u32 %0, [%1];" : "=r"(v) : "l"(p) : "memory"); return v;
}
__device__ __forceinline__ uint4 ld_relaxed4(const uint4* p) {
  uint4 v; asm volatile("ld.relaxed.gpu.global.v4.u32 {%0,%1,%2,%3}, [%4];" : "=r"(v.x), "=r"(v.y), "=r"(v.z), "=r"(v.w) : "l"(p) : "memory"); return v;
}
__device__ __forceinline__ void st_relaxed4(uint4* p, uint32_t a, uint32_t b, uint32_t c, uint32_t d) {
  asm volatile("st.relaxed.gpu.global.v4.u32 [%0], {%1,%2,%3,%4};" ::"l"(p), "r"(a), "r"(b), "r"(c), "r"(d) : "memory");
}
template <int SLEEP>
__device__ __forceinline__ void flag_wait_t(const unsigned int* p, unsigned int target) {
  uint32_t n = 0;
#pragma unroll 1
  while ((int)(ld_acquire(p) - target) < 0) {
    if (SLEEP) __nanosleep(SLEEP);
    if (++n > (1u << 20)) { g_err = 2u; break; }
  }
}
__device__ __forceinline__ void flag_wait(const unsigned int* p, unsigned int target) { flag_wait_t<0>(p, target); }
__device__ __forceinline__ void flag_wait_slow(const unsigned int* p, unsigned int target) { flag_wait_t<256>(p, target); }
__device__ __forceinline__ void tma_load_2d(uint32_t dst, const CUtensorMap* tm, int c0, int c1, uint32_t bar) {
  asm volatile("cp.async.bulk.tensor.2d.shared::cluster.global.mbarrier::complete_tx::bytes [%0], [%1, {%2, %3}], [%4];"
               ::"r"(dst), "l"(tm), "r"(c0), "r"(c1), "r"(bar) : "memory");
}
__device__ __forceinline__ void tma_load_2d_mc(uint32_t dst, const CUtensorMap* tm, int c0, int c1, uint32_t bar, uint16_t mask) {
  asm volatile("cp.async.bulk.tensor.2d.shared::cluster.global.mbarrier::complete_tx::bytes.multicast::cluster [%0], [%1, {%2, %3}], [%4], %5;"
               ::"r"(dst), "l"(tm), "r"(c0), "r"(c1), "r"(bar), "h"(mask) : "memory");
}
__device__ __forceinline__ void mbar_wait_u(uint32_t bar, uint32_t parity) {
  uint32_t n = 0;
#pragma unroll 1
  while (!__all_sync(0xffffffffu, mbar_try_wait(bar, parity))) {
    if (++n > (1u << 22)) { g_err = 1u; break; }
  }
}
__device__ __forceinline__ void expect_tx_e(uint32_t bar, uint32_t bytes) {
  asm volatile("{\n.reg .pred p;\nelect.sync _|p, 0xffffffff;\n@p mbarrier.arrive.expect_tx.shared::cta.b64 _, [%0], %1;\n}\n" ::"r"(bar), "r"(bytes) : "memory");
}
__device__ __forceinline__ void tma_2d_e(uint32_t dst, const CUtensorMap* tm, int c0, int c1, uint32_t bar) {
  asm volatile("{\n.reg .pred p;\nelect.sync _|p, 0xffffffff;\n"
               "@p cp.async.bulk.tensor.2d.shared::cluster.global.mbarrier::complete_tx::bytes [%0], [%1, {%2, %3}], [%4];\n}\n"
               ::"r"(dst), "l"(tm), "r"(c0), "r"(c1), "r"(bar) : "memory");
}
__device__ __forceinline__ void tma_2d_mc_e(uint32_t dst, const CUtensorMap* tm, int c0, int c1, uint32_t bar) {
  asm volatile("{\n.reg .pred p;\nelect.sync _|p, 0xffffffff;\n"
               "@p cp.async.bulk.tensor.2d.shared::cluster.global.mbarrier::complete_tx::bytes.multicast::cluster [%0], [%1, {%2, %3}], [%4], %5;\n}\n"
               ::"r"(dst), "l"(tm), "r"(c0), "r"(c1), "r"(bar), "h"((uint16_t)3) : "memory");
}
__device__ __forceinline__ void tma_pf_e(const CUtensorMap* tm, int c0, int c1) {
  asm volatile("{\n.reg .pred p;\nelect.sync _|p, 0xffffffff;\n"
               "@p cp.async.bulk.prefetch.tensor.2d.L2.global.tile [%0, {%1, %2}];\n}\n" ::"l"(tm), "r"(c0), "r"(c1) : "memory");
}
__device__ __forceinline__ void tma_2d_to_e(uint32_t dst, const CUtensorMap* tm, int c0, int c1, uint32_t bar, uint32_t mask) {
  asm volatile("{\n.reg .pred p;\nelect.sync _|p, 0xffffffff;\n"
               "@p cp.async.bulk.tensor.2d.shared::cluster.global.mbarrier::complete_tx::bytes.multicast::cluster [%0], [%1, {%2, %3}], [%4], %5;\n}\n"
               ::"r"(dst), "l"(tm), "r"(c0), "r"(c1), "r"(bar), "h"((uint16_t)mask) : "memory");
}
__device__ __forceinline__ void tma_3d_mc_e(uint32_t dst, const CUtensorMap* tm, int c1, int c2, uint32_t bar) {
  asm volatile("{\n.reg .pred p;\nelect.sync _|p, 0xffffffff;\n"
               "@p cp.async.bulk.tensor.3d.shared::cluster.global.mbarrier::complete_tx::bytes.multicast::cluster [%0], [%1, {%6, %2, %3}], [%4], %5;\n}\n"
               ::"r"(dst), "l"(tm), "r"(c1), "r"(c2), "r"(bar), "h"((uint16_t)3), "r"(0) : "memory");
}
__device__ __forceinline__ uint32_t poll_flags(const unsigned int* f, unsigned int target, int lane) {
  const unsigned int v = ld_acquire(f + (lane & 15));
  const uint32_t r = __ballot_sync(0xffffffffu, (int)(v - target) >= 0);
  __syncwarp();
  return r;
}
__device__ __forceinline__ void mbar_arrive_cluster(uint32_t local_bar, uint32_t rank) {
  asm volatile("{\n.reg .b32 ra;\nmapa.shared::cluster.u32 ra, %0, %1;\nmbarrier.arrive.shared::cluster.b64 _, [ra];\n}\n"
               ::"r"(local_bar), "r"(rank) : "memory");
}
__device__ __forceinline__ void release2(uint32_t bar) { mbar_arrive_cluster(bar, 0); mbar_arrive_cluster(bar, 1); }
__device__ __forceinline__ void tma_store_2d(const CUtensorMap* tm, uint32_t src, int c0, int c1) {
  asm volatile("cp.async.bulk.tensor.2d.global.shared::cta.bulk_group [%0, {%2, %3}], [%1];"
               ::"l"(tm), "r"(src), "r"(c0), "r"(c1) : "memory");
}
__device__ __forceinline__ void bulk_store(void* dst, uint32_t src, uint32_t bytes) {
  asm volatile("cp.async.bulk.global.shared::cta.bulk_group [%0], [%1], %2;" ::"l"(dst), "r"(src), "r"(bytes) : "memory");
}
__device__ __forceinline__ void bulk_load(uint32_t dst, const void* src, uint32_t bytes, uint32_t bar) {
  asm volatile("cp.async.bulk.shared::cluster.global.mbarrier::complete_tx::bytes [%0], [%1], %2, [%3];" ::"r"(dst), "l"(src), "r"(bytes), "r"(bar) : "memory");
}
__device__ __forceinline__ void bulk_red_add(void* dst, uint32_t src, uint32_t bytes) {
  asm volatile("cp.reduce.async.bulk.global.shared::cta.bulk_group.add.f32 [%0], [%1], %2;" ::"l"(dst), "r"(src), "r"(bytes) : "memory");
}
__device__ __forceinline__ void bulk_commit() { asm volatile("cp.async.bulk.commit_group;" ::: "memory"); }
__device__ __forceinline__ void bulk_wait0() { asm volatile("cp.async.bulk.wait_group 0;" ::: "memory"); }
__device__ __forceinline__ void fence_async_smem() { asm volatile("fence.proxy.async.shared::cta;" ::: "memory"); }
__device__ __forceinline__ void fence_async_all() { asm volatile("fence.proxy.async.global;" ::: "memory"); }
__device__ __forceinline__ void wgmma_fence() { asm volatile("wgmma.fence.sync.aligned;" ::: "memory"); }
__device__ __forceinline__ void wgmma_commit() { asm volatile("wgmma.commit_group.sync.aligned;" ::: "memory"); }
template <int N> __device__ __forceinline__ void wgmma_wait() { asm volatile("wgmma.wait_group.sync.aligned %0;" ::"n"(N) : "memory"); }
__device__ __forceinline__ void cluster_arrive() { asm volatile("barrier.cluster.arrive.release.aligned;" ::: "memory"); }
__device__ __forceinline__ void cluster_wait() { asm volatile("barrier.cluster.wait.acquire.aligned;" ::: "memory"); }
template <int ID, int N> __device__ __forceinline__ void nbar() { asm volatile("bar.sync %0, %1;" ::"n"(ID), "n"(N) : "memory"); }
__device__ __forceinline__ uint64_t make_desc(uint32_t addr, uint32_t lbo_bytes, uint32_t sbo_bytes) {
  uint64_t d = 0;
  d |= (uint64_t)((addr & 0x3FFFF) >> 4);
  d |= (uint64_t)((lbo_bytes >> 4) & 0x3FFF) << 16;
  d |= (uint64_t)((sbo_bytes >> 4) & 0x3FFF) << 32;
  d |= (uint64_t)1 << 62;
  return d;
}
__device__ __forceinline__ uint64_t desc64(uint32_t lo, uint32_t hi) { return (uint64_t)lo | ((uint64_t)hi << 32); }
__device__ __forceinline__ uint32_t pack_bf16(float lo, float hi) {
  uint32_t r; asm("cvt.rn.bf16x2.f32 %0, %1, %2;" : "=r"(r) : "f"(hi), "f"(lo)); return r;
}
__device__ __forceinline__ uint32_t mul_bf16x2(uint32_t a, uint32_t s, bool hi) {
  __nv_bfloat162 x = *reinterpret_cast<__nv_bfloat162*>(&a), y = *reinterpret_cast<__nv_bfloat162*>(&s);
  x = __hmul2(x, hi ? __high2bfloat162(y) : __low2bfloat162(y));
  return *reinterpret_cast<uint32_t*>(&x);
}
__device__ __forceinline__ float bf16r(float x) { return __bfloat162float(__float2bfloat16_rn(x)); }
__device__ __forceinline__ float bf_lo(uint32_t u) { return __uint_as_float(u << 16); }
__device__ __forceinline__ float bf_hi(uint32_t u) { return __uint_as_float(u & 0xFFFF0000u); }
__device__ __forceinline__ float ex2(float x) { float r; asm("ex2.approx.ftz.f32 %0, %1;" : "=f"(r) : "f"(x)); return r; }
__device__ __forceinline__ float rcp(float x) { float r; asm("rcp.approx.ftz.f32 %0, %1;" : "=f"(r) : "f"(x)); return r; }
__device__ __forceinline__ void mma_bf16(float (&d)[4], uint32_t a0, uint32_t a1, uint32_t a2, uint32_t a3, uint32_t b0, uint32_t b1) {
  asm("mma.sync.aligned.m16n8k16.row.col.f32.bf16.bf16.f32 {%0,%1,%2,%3}, {%4,%5,%6,%7}, {%8,%9}, {%0,%1,%2,%3};"
               : "+f"(d[0]), "+f"(d[1]), "+f"(d[2]), "+f"(d[3]) : "r"(a0), "r"(a1), "r"(a2), "r"(a3), "r"(b0), "r"(b1));
}
__device__ __forceinline__ void ldsm_x4(uint32_t& r0, uint32_t& r1, uint32_t& r2, uint32_t& r3, uint32_t addr) {
  asm volatile("ldmatrix.sync.aligned.m8n8.x4.shared.b16 {%0,%1,%2,%3}, [%4];"
               : "=r"(r0), "=r"(r1), "=r"(r2), "=r"(r3) : "r"(addr) : "memory");
}
__device__ __forceinline__ void ldsm_x4_t(uint32_t& r0, uint32_t& r1, uint32_t& r2, uint32_t& r3, uint32_t addr) {
  asm volatile("ldmatrix.sync.aligned.m8n8.x4.trans.shared.b16 {%0,%1,%2,%3}, [%4];"
               : "=r"(r0), "=r"(r1), "=r"(r2), "=r"(r3) : "r"(addr) : "memory");
}
__device__ __forceinline__ void ldsm_x2_t(uint32_t& r0, uint32_t& r1, uint32_t addr) {
  asm volatile("ldmatrix.sync.aligned.m8n8.x2.trans.shared.b16 {%0,%1}, [%2];"
               : "=r"(r0), "=r"(r1) : "r"(addr) : "memory");
}
__device__ __forceinline__ void stsm_x4(uint32_t addr, uint32_t r0, uint32_t r1, uint32_t r2, uint32_t r3) {
  asm volatile("stmatrix.sync.aligned.m8n8.x4.shared.b16 [%0], {%1,%2,%3,%4};"
               ::"r"(addr), "r"(r0), "r"(r1), "r"(r2), "r"(r3) : "memory");
}
__device__ __forceinline__ void stsm_x4_p(bool on, uint32_t addr, uint32_t r0, uint32_t r1, uint32_t r2, uint32_t r3) {
  asm volatile("{\n.reg .pred p;\nsetp.ne.b32 p, %5, 0;\n@p stmatrix.sync.aligned.m8n8.x4.shared.b16 [%0], {%1,%2,%3,%4};\n}\n"
               ::"r"(addr), "r"(r0), "r"(r1), "r"(r2), "r"(r3), "r"((int)on) : "memory");
}
__device__ __forceinline__ float2 lds_f2(uint32_t addr) {
  float2 v; asm volatile("ld.shared.v2.f32 {%0,%1}, [%2];" : "=f"(v.x), "=f"(v.y) : "r"(addr) : "memory"); return v;
}
__device__ __forceinline__ uint4 lds128(uint32_t addr) {
  uint4 v; asm volatile("ld.shared.v4.b32 {%0,%1,%2,%3}, [%4];" : "=r"(v.x), "=r"(v.y), "=r"(v.z), "=r"(v.w) : "r"(addr) : "memory"); return v;
}
__device__ __forceinline__ void sts128(uint32_t addr, uint4 v) {
  asm volatile("st.shared.v4.b32 [%0], {%1,%2,%3,%4};" ::"r"(addr), "r"(v.x), "r"(v.y), "r"(v.z), "r"(v.w) : "memory");
}
__device__ __forceinline__ float lds_f(uint32_t addr) {
  float v; asm volatile("ld.shared.f32 %0, [%1];" : "=f"(v) : "r"(addr) : "memory"); return v;
}
__device__ __forceinline__ uint32_t lds_vol(uint32_t addr) {
  uint32_t v; asm volatile("ld.volatile.shared.u32 %0, [%1];" : "=r"(v) : "r"(addr) : "memory"); return v;
}
__device__ __forceinline__ void sts16(uint32_t addr, uint32_t v) {
  asm volatile("st.shared.u16 [%0], %1;" ::"r"(addr), "h"((unsigned short)v) : "memory");
}
__device__ __forceinline__ void nbar_dyn(int id, int n) { asm volatile("bar.sync %0, %1;" ::"r"(id), "r"(n) : "memory"); }
__device__ __forceinline__ uint64_t make_desc_ns(uint32_t addr, uint32_t lbo_bytes, uint32_t sbo_bytes) {
  return (uint64_t)((addr & 0x3FFFF) >> 4) | ((uint64_t)(lbo_bytes >> 4) << 16) | ((uint64_t)(sbo_bytes >> 4) << 32);
}
__device__ __forceinline__ void sts_f(uint32_t addr, float v) { asm volatile("st.shared.f32 [%0], %1;" ::"r"(addr), "f"(v) : "memory"); }
__device__ __forceinline__ void sts64(uint32_t addr, uint32_t a, uint32_t b) {
  asm volatile("st.shared.v2.b32 [%0], {%1,%2};" ::"r"(addr), "r"(a), "r"(b) : "memory");
}
__device__ __forceinline__ void sts_f2(uint32_t addr, float a, float b) {
  asm volatile("st.shared.v2.f32 [%0], {%1,%2};" ::"r"(addr), "f"(a), "f"(b) : "memory");
}
__device__ __forceinline__ void red_add2(float* p, float a, float b) {
  asm volatile("red.global.add.v2.f32 [%0], {%1,%2};" ::"l"(p), "f"(a), "f"(b) : "memory");
}
__device__ __forceinline__ void red_add4(float* p, float a, float b, float c, float d) {
  asm volatile("red.global.add.v4.f32 [%0], {%1,%2,%3,%4};" ::"l"(p), "f"(a), "f"(b), "f"(c), "f"(d) : "memory");
}
__device__ __forceinline__ void red_add1(float* p, float a) {
  asm volatile("red.global.add.f32 [%0], %1;" ::"l"(p), "f"(a) : "memory");
}
__device__ __forceinline__ void l2_prefetch(const void* p, uint32_t bytes) {
  asm volatile("cp.async.bulk.prefetch.L2.global [%0], %1;" ::"l"(p), "r"(bytes) : "memory");
}

__device__ __forceinline__ void wgmma_n256(float (&d)[192], uint64_t da, uint64_t db, int scale_d) {
  asm volatile("{\n.reg .pred p;\nsetp.ne.b32 p, %130, 0;\n"
    "wgmma.mma_async.sync.aligned.m64n256k16.f32.bf16.bf16 {%0, %1, %2, %3, %4, %5, %6, %7, %8, %9, %10, %11, %12, %13, %14, %15, %16, %17, %18, %19, %20, %21, %22, %23, %24, %25, %26, %27, %28, %29, %30, %31, %32, %33, %34, %35, %36, %37, %38, %39, %40, %41, %42, %43, %44, %45, %46, %47, %48, %49, %50, %51, %52, %53, %54, %55, %56, %57, %58, %59, %60, %61, %62, %63, %64, %65, %66, %67, %68, %69, %70, %71, %72, %73, %74, %75, %76, %77, %78, %79, %80, %81, %82, %83, %84, %85, %86, %87, %88, %89, %90, %91, %92, %93, %94, %95, %96, %97, %98, %99, %100, %101, %102, %103, %104, %105, %106, %107, %108, %109, %110, %111, %112, %113, %114, %115, %116, %117, %118, %119, %120, %121, %122, %123, %124, %125, %126, %127}, %128, %129, p, 1, 1, 0, 1;\n}\n"
    : "+f"(d[0]), "+f"(d[1]), "+f"(d[2]), "+f"(d[3]), "+f"(d[4]), "+f"(d[5]), "+f"(d[6]), "+f"(d[7]), "+f"(d[8]), "+f"(d[9]), "+f"(d[10]), "+f"(d[11]), "+f"(d[12]), "+f"(d[13]), "+f"(d[14]), "+f"(d[15]), "+f"(d[16]), "+f"(d[17]), "+f"(d[18]), "+f"(d[19]), "+f"(d[20]), "+f"(d[21]), "+f"(d[22]), "+f"(d[23]), "+f"(d[24]), "+f"(d[25]), "+f"(d[26]), "+f"(d[27]), "+f"(d[28]), "+f"(d[29]), "+f"(d[30]), "+f"(d[31]), "+f"(d[32]), "+f"(d[33]), "+f"(d[34]), "+f"(d[35]), "+f"(d[36]), "+f"(d[37]), "+f"(d[38]), "+f"(d[39]), "+f"(d[40]), "+f"(d[41]), "+f"(d[42]), "+f"(d[43]), "+f"(d[44]), "+f"(d[45]), "+f"(d[46]), "+f"(d[47]), "+f"(d[48]), "+f"(d[49]), "+f"(d[50]), "+f"(d[51]), "+f"(d[52]), "+f"(d[53]), "+f"(d[54]), "+f"(d[55]), "+f"(d[56]), "+f"(d[57]), "+f"(d[58]), "+f"(d[59]), "+f"(d[60]), "+f"(d[61]), "+f"(d[62]), "+f"(d[63]), "+f"(d[64]), "+f"(d[65]), "+f"(d[66]), "+f"(d[67]), "+f"(d[68]), "+f"(d[69]), "+f"(d[70]), "+f"(d[71]), "+f"(d[72]), "+f"(d[73]), "+f"(d[74]), "+f"(d[75]), "+f"(d[76]), "+f"(d[77]), "+f"(d[78]), "+f"(d[79]), "+f"(d[80]), "+f"(d[81]), "+f"(d[82]), "+f"(d[83]), "+f"(d[84]), "+f"(d[85]), "+f"(d[86]), "+f"(d[87]), "+f"(d[88]), "+f"(d[89]), "+f"(d[90]), "+f"(d[91]), "+f"(d[92]), "+f"(d[93]), "+f"(d[94]), "+f"(d[95]), "+f"(d[96]), "+f"(d[97]), "+f"(d[98]), "+f"(d[99]), "+f"(d[100]), "+f"(d[101]), "+f"(d[102]), "+f"(d[103]), "+f"(d[104]), "+f"(d[105]), "+f"(d[106]), "+f"(d[107]), "+f"(d[108]), "+f"(d[109]), "+f"(d[110]), "+f"(d[111]), "+f"(d[112]), "+f"(d[113]), "+f"(d[114]), "+f"(d[115]), "+f"(d[116]), "+f"(d[117]), "+f"(d[118]), "+f"(d[119]), "+f"(d[120]), "+f"(d[121]), "+f"(d[122]), "+f"(d[123]), "+f"(d[124]), "+f"(d[125]), "+f"(d[126]), "+f"(d[127])
    : "l"(da), "l"(db), "r"(scale_d));
}
__device__ __forceinline__ void wgmma_n128(float (&d)[192], uint64_t da, uint64_t db, int scale_d) {
  asm volatile("{\n.reg .pred p;\nsetp.ne.b32 p, %66, 0;\n"
    "wgmma.mma_async.sync.aligned.m64n128k16.f32.bf16.bf16 {%0, %1, %2, %3, %4, %5, %6, %7, %8, %9, %10, %11, %12, %13, %14, %15, %16, %17, %18, %19, %20, %21, %22, %23, %24, %25, %26, %27, %28, %29, %30, %31, %32, %33, %34, %35, %36, %37, %38, %39, %40, %41, %42, %43, %44, %45, %46, %47, %48, %49, %50, %51, %52, %53, %54, %55, %56, %57, %58, %59, %60, %61, %62, %63}, %64, %65, p, 1, 1, 0, 1;\n}\n"
    : "+f"(d[128]), "+f"(d[129]), "+f"(d[130]), "+f"(d[131]), "+f"(d[132]), "+f"(d[133]), "+f"(d[134]), "+f"(d[135]), "+f"(d[136]), "+f"(d[137]), "+f"(d[138]), "+f"(d[139]), "+f"(d[140]), "+f"(d[141]), "+f"(d[142]), "+f"(d[143]), "+f"(d[144]), "+f"(d[145]), "+f"(d[146]), "+f"(d[147]), "+f"(d[148]), "+f"(d[149]), "+f"(d[150]), "+f"(d[151]), "+f"(d[152]), "+f"(d[153]), "+f"(d[154]), "+f"(d[155]), "+f"(d[156]), "+f"(d[157]), "+f"(d[158]), "+f"(d[159]), "+f"(d[160]), "+f"(d[161]), "+f"(d[162]), "+f"(d[163]), "+f"(d[164]), "+f"(d[165]), "+f"(d[166]), "+f"(d[167]), "+f"(d[168]), "+f"(d[169]), "+f"(d[170]), "+f"(d[171]), "+f"(d[172]), "+f"(d[173]), "+f"(d[174]), "+f"(d[175]), "+f"(d[176]), "+f"(d[177]), "+f"(d[178]), "+f"(d[179]), "+f"(d[180]), "+f"(d[181]), "+f"(d[182]), "+f"(d[183]), "+f"(d[184]), "+f"(d[185]), "+f"(d[186]), "+f"(d[187]), "+f"(d[188]), "+f"(d[189]), "+f"(d[190]), "+f"(d[191])
    : "l"(da), "l"(db), "r"(scale_d));
}
__device__ __forceinline__ void wgmma_n256_k(float (&d)[192], uint64_t da, uint64_t db, int scale_d) {
  asm volatile("{\n.reg .pred p;\nsetp.ne.b32 p, %130, 0;\n"
    "wgmma.mma_async.sync.aligned.m64n256k16.f32.bf16.bf16 {%0, %1, %2, %3, %4, %5, %6, %7, %8, %9, %10, %11, %12, %13, %14, %15, %16, %17, %18, %19, %20, %21, %22, %23, %24, %25, %26, %27, %28, %29, %30, %31, %32, %33, %34, %35, %36, %37, %38, %39, %40, %41, %42, %43, %44, %45, %46, %47, %48, %49, %50, %51, %52, %53, %54, %55, %56, %57, %58, %59, %60, %61, %62, %63, %64, %65, %66, %67, %68, %69, %70, %71, %72, %73, %74, %75, %76, %77, %78, %79, %80, %81, %82, %83, %84, %85, %86, %87, %88, %89, %90, %91, %92, %93, %94, %95, %96, %97, %98, %99, %100, %101, %102, %103, %104, %105, %106, %107, %108, %109, %110, %111, %112, %113, %114, %115, %116, %117, %118, %119, %120, %121, %122, %123, %124, %125, %126, %127}, %128, %129, p, 1, 1, 0, 0;\n}\n"
    : "+f"(d[0]), "+f"(d[1]), "+f"(d[2]), "+f"(d[3]), "+f"(d[4]), "+f"(d[5]), "+f"(d[6]), "+f"(d[7]), "+f"(d[8]), "+f"(d[9]), "+f"(d[10]), "+f"(d[11]), "+f"(d[12]), "+f"(d[13]), "+f"(d[14]), "+f"(d[15]), "+f"(d[16]), "+f"(d[17]), "+f"(d[18]), "+f"(d[19]), "+f"(d[20]), "+f"(d[21]), "+f"(d[22]), "+f"(d[23]), "+f"(d[24]), "+f"(d[25]), "+f"(d[26]), "+f"(d[27]), "+f"(d[28]), "+f"(d[29]), "+f"(d[30]), "+f"(d[31]), "+f"(d[32]), "+f"(d[33]), "+f"(d[34]), "+f"(d[35]), "+f"(d[36]), "+f"(d[37]), "+f"(d[38]), "+f"(d[39]), "+f"(d[40]), "+f"(d[41]), "+f"(d[42]), "+f"(d[43]), "+f"(d[44]), "+f"(d[45]), "+f"(d[46]), "+f"(d[47]), "+f"(d[48]), "+f"(d[49]), "+f"(d[50]), "+f"(d[51]), "+f"(d[52]), "+f"(d[53]), "+f"(d[54]), "+f"(d[55]), "+f"(d[56]), "+f"(d[57]), "+f"(d[58]), "+f"(d[59]), "+f"(d[60]), "+f"(d[61]), "+f"(d[62]), "+f"(d[63]), "+f"(d[64]), "+f"(d[65]), "+f"(d[66]), "+f"(d[67]), "+f"(d[68]), "+f"(d[69]), "+f"(d[70]), "+f"(d[71]), "+f"(d[72]), "+f"(d[73]), "+f"(d[74]), "+f"(d[75]), "+f"(d[76]), "+f"(d[77]), "+f"(d[78]), "+f"(d[79]), "+f"(d[80]), "+f"(d[81]), "+f"(d[82]), "+f"(d[83]), "+f"(d[84]), "+f"(d[85]), "+f"(d[86]), "+f"(d[87]), "+f"(d[88]), "+f"(d[89]), "+f"(d[90]), "+f"(d[91]), "+f"(d[92]), "+f"(d[93]), "+f"(d[94]), "+f"(d[95]), "+f"(d[96]), "+f"(d[97]), "+f"(d[98]), "+f"(d[99]), "+f"(d[100]), "+f"(d[101]), "+f"(d[102]), "+f"(d[103]), "+f"(d[104]), "+f"(d[105]), "+f"(d[106]), "+f"(d[107]), "+f"(d[108]), "+f"(d[109]), "+f"(d[110]), "+f"(d[111]), "+f"(d[112]), "+f"(d[113]), "+f"(d[114]), "+f"(d[115]), "+f"(d[116]), "+f"(d[117]), "+f"(d[118]), "+f"(d[119]), "+f"(d[120]), "+f"(d[121]), "+f"(d[122]), "+f"(d[123]), "+f"(d[124]), "+f"(d[125]), "+f"(d[126]), "+f"(d[127])
    : "l"(da), "l"(db), "r"(scale_d));
}
__device__ __forceinline__ void wgmma_n128_k(float (&d)[192], uint64_t da, uint64_t db, int scale_d) {
  asm volatile("{\n.reg .pred p;\nsetp.ne.b32 p, %66, 0;\n"
    "wgmma.mma_async.sync.aligned.m64n128k16.f32.bf16.bf16 {%0, %1, %2, %3, %4, %5, %6, %7, %8, %9, %10, %11, %12, %13, %14, %15, %16, %17, %18, %19, %20, %21, %22, %23, %24, %25, %26, %27, %28, %29, %30, %31, %32, %33, %34, %35, %36, %37, %38, %39, %40, %41, %42, %43, %44, %45, %46, %47, %48, %49, %50, %51, %52, %53, %54, %55, %56, %57, %58, %59, %60, %61, %62, %63}, %64, %65, p, 1, 1, 0, 0;\n}\n"
    : "+f"(d[128]), "+f"(d[129]), "+f"(d[130]), "+f"(d[131]), "+f"(d[132]), "+f"(d[133]), "+f"(d[134]), "+f"(d[135]), "+f"(d[136]), "+f"(d[137]), "+f"(d[138]), "+f"(d[139]), "+f"(d[140]), "+f"(d[141]), "+f"(d[142]), "+f"(d[143]), "+f"(d[144]), "+f"(d[145]), "+f"(d[146]), "+f"(d[147]), "+f"(d[148]), "+f"(d[149]), "+f"(d[150]), "+f"(d[151]), "+f"(d[152]), "+f"(d[153]), "+f"(d[154]), "+f"(d[155]), "+f"(d[156]), "+f"(d[157]), "+f"(d[158]), "+f"(d[159]), "+f"(d[160]), "+f"(d[161]), "+f"(d[162]), "+f"(d[163]), "+f"(d[164]), "+f"(d[165]), "+f"(d[166]), "+f"(d[167]), "+f"(d[168]), "+f"(d[169]), "+f"(d[170]), "+f"(d[171]), "+f"(d[172]), "+f"(d[173]), "+f"(d[174]), "+f"(d[175]), "+f"(d[176]), "+f"(d[177]), "+f"(d[178]), "+f"(d[179]), "+f"(d[180]), "+f"(d[181]), "+f"(d[182]), "+f"(d[183]), "+f"(d[184]), "+f"(d[185]), "+f"(d[186]), "+f"(d[187]), "+f"(d[188]), "+f"(d[189]), "+f"(d[190]), "+f"(d[191])
    : "l"(da), "l"(db), "r"(scale_d));
}
__device__ __forceinline__ void wgmma_n40_tt(float (&d)[20], uint64_t da, uint64_t db, int scale_d) {
  asm volatile("{\n.reg .pred p;\nsetp.ne.b32 p, %22, 0;\n"
    "wgmma.mma_async.sync.aligned.m64n40k16.f32.bf16.bf16 {%0, %1, %2, %3, %4, %5, %6, %7, %8, %9, %10, %11, %12, %13, %14, %15, %16, %17, %18, %19}, %20, %21, p, 1, 1, 1, 1;\n}\n"
    : "+f"(d[0]), "+f"(d[1]), "+f"(d[2]), "+f"(d[3]), "+f"(d[4]), "+f"(d[5]), "+f"(d[6]), "+f"(d[7]), "+f"(d[8]), "+f"(d[9]), "+f"(d[10]), "+f"(d[11]), "+f"(d[12]), "+f"(d[13]), "+f"(d[14]), "+f"(d[15]), "+f"(d[16]), "+f"(d[17]), "+f"(d[18]), "+f"(d[19])
    : "l"(da), "l"(db), "r"(scale_d));
}
__device__ __forceinline__ void wgmma_n40_rs(float (&d)[20], const uint32_t (&a)[4], uint64_t db, int scale_d) {
  asm volatile("{\n.reg .pred p;\nsetp.ne.b32 p, %25, 0;\n"
    "wgmma.mma_async.sync.aligned.m64n40k16.f32.bf16.bf16 {%0, %1, %2, %3, %4, %5, %6, %7, %8, %9, %10, %11, %12, %13, %14, %15, %16, %17, %18, %19}, {%20, %21, %22, %23}, %24, p, 1, 1, 1;\n}\n"
    : "+f"(d[0]), "+f"(d[1]), "+f"(d[2]), "+f"(d[3]), "+f"(d[4]), "+f"(d[5]), "+f"(d[6]), "+f"(d[7]), "+f"(d[8]), "+f"(d[9]), "+f"(d[10]), "+f"(d[11]), "+f"(d[12]), "+f"(d[13]), "+f"(d[14]), "+f"(d[15]), "+f"(d[16]), "+f"(d[17]), "+f"(d[18]), "+f"(d[19])
    : "r"(a[0]), "r"(a[1]), "r"(a[2]), "r"(a[3]), "l"(db), "r"(scale_d));
}
__device__ __forceinline__ void wgmma_n256_0(float (&d)[192], uint64_t da, uint64_t db) {
  asm volatile("{\n.reg .pred p;\nsetp.ne.b32 p, 0, 0;\n"
    "wgmma.mma_async.sync.aligned.m64n256k16.f32.bf16.bf16 {%0, %1, %2, %3, %4, %5, %6, %7, %8, %9, %10, %11, %12, %13, %14, %15, %16, %17, %18, %19, %20, %21, %22, %23, %24, %25, %26, %27, %28, %29, %30, %31, %32, %33, %34, %35, %36, %37, %38, %39, %40, %41, %42, %43, %44, %45, %46, %47, %48, %49, %50, %51, %52, %53, %54, %55, %56, %57, %58, %59, %60, %61, %62, %63, %64, %65, %66, %67, %68, %69, %70, %71, %72, %73, %74, %75, %76, %77, %78, %79, %80, %81, %82, %83, %84, %85, %86, %87, %88, %89, %90, %91, %92, %93, %94, %95, %96, %97, %98, %99, %100, %101, %102, %103, %104, %105, %106, %107, %108, %109, %110, %111, %112, %113, %114, %115, %116, %117, %118, %119, %120, %121, %122, %123, %124, %125, %126, %127}, %128, %129, p, 1, 1, 0, 1;\n}\n"
    : "=f"(d[0]), "=f"(d[1]), "=f"(d[2]), "=f"(d[3]), "=f"(d[4]), "=f"(d[5]), "=f"(d[6]), "=f"(d[7]), "=f"(d[8]), "=f"(d[9]), "=f"(d[10]), "=f"(d[11]), "=f"(d[12]), "=f"(d[13]), "=f"(d[14]), "=f"(d[15]), "=f"(d[16]), "=f"(d[17]), "=f"(d[18]), "=f"(d[19]), "=f"(d[20]), "=f"(d[21]), "=f"(d[22]), "=f"(d[23]), "=f"(d[24]), "=f"(d[25]), "=f"(d[26]), "=f"(d[27]), "=f"(d[28]), "=f"(d[29]), "=f"(d[30]), "=f"(d[31]), "=f"(d[32]), "=f"(d[33]), "=f"(d[34]), "=f"(d[35]), "=f"(d[36]), "=f"(d[37]), "=f"(d[38]), "=f"(d[39]), "=f"(d[40]), "=f"(d[41]), "=f"(d[42]), "=f"(d[43]), "=f"(d[44]), "=f"(d[45]), "=f"(d[46]), "=f"(d[47]), "=f"(d[48]), "=f"(d[49]), "=f"(d[50]), "=f"(d[51]), "=f"(d[52]), "=f"(d[53]), "=f"(d[54]), "=f"(d[55]), "=f"(d[56]), "=f"(d[57]), "=f"(d[58]), "=f"(d[59]), "=f"(d[60]), "=f"(d[61]), "=f"(d[62]), "=f"(d[63]), "=f"(d[64]), "=f"(d[65]), "=f"(d[66]), "=f"(d[67]), "=f"(d[68]), "=f"(d[69]), "=f"(d[70]), "=f"(d[71]), "=f"(d[72]), "=f"(d[73]), "=f"(d[74]), "=f"(d[75]), "=f"(d[76]), "=f"(d[77]), "=f"(d[78]), "=f"(d[79]), "=f"(d[80]), "=f"(d[81]), "=f"(d[82]), "=f"(d[83]), "=f"(d[84]), "=f"(d[85]), "=f"(d[86]), "=f"(d[87]), "=f"(d[88]), "=f"(d[89]), "=f"(d[90]), "=f"(d[91]), "=f"(d[92]), "=f"(d[93]), "=f"(d[94]), "=f"(d[95]), "=f"(d[96]), "=f"(d[97]), "=f"(d[98]), "=f"(d[99]), "=f"(d[100]), "=f"(d[101]), "=f"(d[102]), "=f"(d[103]), "=f"(d[104]), "=f"(d[105]), "=f"(d[106]), "=f"(d[107]), "=f"(d[108]), "=f"(d[109]), "=f"(d[110]), "=f"(d[111]), "=f"(d[112]), "=f"(d[113]), "=f"(d[114]), "=f"(d[115]), "=f"(d[116]), "=f"(d[117]), "=f"(d[118]), "=f"(d[119]), "=f"(d[120]), "=f"(d[121]), "=f"(d[122]), "=f"(d[123]), "=f"(d[124]), "=f"(d[125]), "=f"(d[126]), "=f"(d[127])
    : "l"(da), "l"(db));
}
__device__ __forceinline__ void wgmma_n128_0(float (&d)[192], uint64_t da, uint64_t db) {
  asm volatile("{\n.reg .pred p;\nsetp.ne.b32 p, 0, 0;\n"
    "wgmma.mma_async.sync.aligned.m64n128k16.f32.bf16.bf16 {%0, %1, %2, %3, %4, %5, %6, %7, %8, %9, %10, %11, %12, %13, %14, %15, %16, %17, %18, %19, %20, %21, %22, %23, %24, %25, %26, %27, %28, %29, %30, %31, %32, %33, %34, %35, %36, %37, %38, %39, %40, %41, %42, %43, %44, %45, %46, %47, %48, %49, %50, %51, %52, %53, %54, %55, %56, %57, %58, %59, %60, %61, %62, %63}, %64, %65, p, 1, 1, 0, 1;\n}\n"
    : "=f"(d[128]), "=f"(d[129]), "=f"(d[130]), "=f"(d[131]), "=f"(d[132]), "=f"(d[133]), "=f"(d[134]), "=f"(d[135]), "=f"(d[136]), "=f"(d[137]), "=f"(d[138]), "=f"(d[139]), "=f"(d[140]), "=f"(d[141]), "=f"(d[142]), "=f"(d[143]), "=f"(d[144]), "=f"(d[145]), "=f"(d[146]), "=f"(d[147]), "=f"(d[148]), "=f"(d[149]), "=f"(d[150]), "=f"(d[151]), "=f"(d[152]), "=f"(d[153]), "=f"(d[154]), "=f"(d[155]), "=f"(d[156]), "=f"(d[157]), "=f"(d[158]), "=f"(d[159]), "=f"(d[160]), "=f"(d[161]), "=f"(d[162]), "=f"(d[163]), "=f"(d[164]), "=f"(d[165]), "=f"(d[166]), "=f"(d[167]), "=f"(d[168]), "=f"(d[169]), "=f"(d[170]), "=f"(d[171]), "=f"(d[172]), "=f"(d[173]), "=f"(d[174]), "=f"(d[175]), "=f"(d[176]), "=f"(d[177]), "=f"(d[178]), "=f"(d[179]), "=f"(d[180]), "=f"(d[181]), "=f"(d[182]), "=f"(d[183]), "=f"(d[184]), "=f"(d[185]), "=f"(d[186]), "=f"(d[187]), "=f"(d[188]), "=f"(d[189]), "=f"(d[190]), "=f"(d[191])
    : "l"(da), "l"(db));
}
__device__ __forceinline__ void wgmma_n64a(float (&d)[192], uint64_t da, uint64_t db, int scale_d) {
  asm volatile("{\n.reg .pred p;\nsetp.ne.b32 p, %34, 0;\n"
    "wgmma.mma_async.sync.aligned.m64n64k16.f32.bf16.bf16 {%0, %1, %2, %3, %4, %5, %6, %7, %8, %9, %10, %11, %12, %13, %14, %15, %16, %17, %18, %19, %20, %21, %22, %23, %24, %25, %26, %27, %28, %29, %30, %31}, %32, %33, p, 1, 1, 0, 1;\n}\n"
    : "+f"(d[128]), "+f"(d[129]), "+f"(d[130]), "+f"(d[131]), "+f"(d[132]), "+f"(d[133]), "+f"(d[134]), "+f"(d[135]), "+f"(d[136]), "+f"(d[137]), "+f"(d[138]), "+f"(d[139]), "+f"(d[140]), "+f"(d[141]), "+f"(d[142]), "+f"(d[143]), "+f"(d[144]), "+f"(d[145]), "+f"(d[146]), "+f"(d[147]), "+f"(d[148]), "+f"(d[149]), "+f"(d[150]), "+f"(d[151]), "+f"(d[152]), "+f"(d[153]), "+f"(d[154]), "+f"(d[155]), "+f"(d[156]), "+f"(d[157]), "+f"(d[158]), "+f"(d[159])
    : "l"(da), "l"(db), "r"(scale_d));
}
__device__ __forceinline__ void wgmma_n64b(float (&d)[192], uint64_t da, uint64_t db, int scale_d) {
  asm volatile("{\n.reg .pred p;\nsetp.ne.b32 p, %34, 0;\n"
    "wgmma.mma_async.sync.aligned.m64n64k16.f32.bf16.bf16 {%0, %1, %2, %3, %4, %5, %6, %7, %8, %9, %10, %11, %12, %13, %14, %15, %16, %17, %18, %19, %20, %21, %22, %23, %24, %25, %26, %27, %28, %29, %30, %31}, %32, %33, p, 1, 1, 0, 1;\n}\n"
    : "+f"(d[160]), "+f"(d[161]), "+f"(d[162]), "+f"(d[163]), "+f"(d[164]), "+f"(d[165]), "+f"(d[166]), "+f"(d[167]), "+f"(d[168]), "+f"(d[169]), "+f"(d[170]), "+f"(d[171]), "+f"(d[172]), "+f"(d[173]), "+f"(d[174]), "+f"(d[175]), "+f"(d[176]), "+f"(d[177]), "+f"(d[178]), "+f"(d[179]), "+f"(d[180]), "+f"(d[181]), "+f"(d[182]), "+f"(d[183]), "+f"(d[184]), "+f"(d[185]), "+f"(d[186]), "+f"(d[187]), "+f"(d[188]), "+f"(d[189]), "+f"(d[190]), "+f"(d[191])
    : "l"(da), "l"(db), "r"(scale_d));
}

constexpr int SLOT = 16384;
constexpr int KVT = 10240;
constexpr uint32_t QA = 0x0BAu, QK = 0x462u, QQ = 0x981u;
constexpr int SM_SD = 12 * SLOT;
constexpr int SM_BAR = SM_SD + 8192;
constexpr int SM_RS = SM_BAR + 512;
constexpr int SM_AP = SM_RS + 768;
constexpr int SM_BP = SM_AP + 2048;
constexpr int SM_WPHI = SM_BP + 12288;
constexpr int SM_EPOCH = SM_WPHI + 10240;
constexpr int SM_TOTAL = SM_EPOCH + 16 + 1024;
constexpr int B_FULLS = 0, B_XOLD = 24, B_STAT = 32, B_EMPTYS = 40, B_FULLT = 256  , B_CONS = 384  , B_E3 = 472, B_E0 = 480, B_E1 = 488, B_E2 = 496, B_EPI = 504, B_KVRDY = 152  , B_CS = 160,
              B_KVDONE = 168  , B_ODONE = 176, B_XDONE = 184, B_OH1 = 192, B_CSL = 200, B_CS2 = 208, B_CSFREE = 216  , B_XH0 = 232, B_OF = 240, B_FLG = 64  ;
constexpr uint64_t BAR_CNT = 0x1c07fc0eac00a800ull;
constexpr uint64_t WO_A0 = 0xab76218762187643ull, WO_B0 = 0x95403a5904359021ull, WO_A1 = 0xa9b21a9052a765baull, WO_B1 = 0x548763b14890321ull;
constexpr uint64_t WO_DA0 = 0xa9876543210edd00ull, WO_DB0 = 0xa9876543210eccccull, WO_DA1 = 0xa9887543210fff00ull, WO_DB1 = 0x876543210bbcccccull;
constexpr int XS = 10;

#define HPI 2
#define PL 2
#define PROFX(i) PROFT(tid_ == 128 && layer == PL, 200 + (i))
#define GAA 99
#define GAB 99
#define GWA 99
#define GWB 99
#define PSL 20
#define EP 0
#define DRY 0
#define NLAYERS 4
constexpr float L2E = 1.4426950408889634f;
#define PHI_MAX 2147483648.f

#define D128(lo) desc64(lo, 0x40000040u)
struct Ctx { uint32_t sb; int g, rb, isum, cu; bf16* out; };

__device__ __forceinline__ void colsum_load(const bf16* __restrict__ w, int rb, int g, int wi, int lane, uint32_t stg, float (&s)[8]) {
  const int ch = wi * 8 + (lane & 7), sec = ch >> 4;
  const bf16* src = w + (size_t)(rb * 64 + (lane >> 3) * 16) * 3072 + (sec == 2 ? 0 : 1024 + sec * 1024) + g * 128 + (ch & 15) * 8;
  stg += lane * 16;
#pragma unroll
  for (int i = 0; i < 8; ++i) s[i] = 0.f;
#pragma unroll
  for (int r = 0; r < 12; ++r)
    asm volatile("cp.async.cg.shared.global [%0], [%1], 16;" ::"r"(stg + r * 512), "l"(src + (size_t)(4 + r) * 3072) : "memory");
  uint4 v[4];
#pragma unroll
  for (int r = 0; r < 4; ++r) v[r] = __ldg(reinterpret_cast<const uint4*>(src + (size_t)r * 3072));
#pragma unroll 1
  for (int r0 = 0;; ++r0) {
#pragma unroll
    for (int r = 0; r < 4; ++r) {
      s[0] += bf_lo(v[r].x); s[1] += bf_hi(v[r].x); s[2] += bf_lo(v[r].y); s[3] += bf_hi(v[r].y);
      s[4] += bf_lo(v[r].z); s[5] += bf_hi(v[r].z); s[6] += bf_lo(v[r].w); s[7] += bf_hi(v[r].w);
    }
    if (r0 == 3) break;
    asm volatile("cp.async.wait_all;" ::: "memory");
#pragma unroll
    for (int r = 0; r < 4; ++r) v[r] = lds128(stg + (r0 * 4 + r) * 512);
  }
#pragma unroll
  for (int i = 0; i < 8; ++i) { s[i] += __shfl_xor_sync(0xffffffffu, s[i], 8); s[i] += __shfl_xor_sync(0xffffffffu, s[i], 16); }
}
__device__ __forceinline__ void colsum_red(float* cs, int g, int wi, int lane, const float (&s)[8]) {
  if (lane < 8) {
    red_add4(cs + g * 384 + (wi * 8 + lane) * 8, s[0], s[1], s[2], s[3]);
    red_add4(cs + g * 384 + (wi * 8 + lane) * 8 + 4, s[4], s[5], s[6], s[7]);
  }
}
#define PHASE_CTX() \
  uint32_t sb = c.sb; asm volatile("" : "+r"(sb)); \
  int tid_ = threadIdx.x; asm volatile("" : "+r"(tid_)); \
  const uint32_t bar = sb + SM_BAR; \
  const int lane = tid_ & 31, cw = (tid_ >> 5) - 4, wg = cw >> 2, wq = cw & 3, gq = lane >> 2, t = lane & 3, wrow0 = cw * 16; \
  const int lrow = (lane & 7) + ((lane >> 3) & 1) * 8, lchk = lane >> 4; \
  const bool elected = (tid_ & 127) == 0; \
  const uint32_t rowo = (wrow0 + lrow) * 128, X = (lchk ^ (lane & 7)) << 4; \
  (void)bar; (void)wq; (void)gq; (void)lrow; (void)lchk; (void)elected; (void)wrow0; (void)wg; (void)rowo; (void)X; (void)t;

template <int PITCH = D_>
__device__ __forceinline__ void slab_out_half(uint32_t slot, bf16* dst, int wrow0, int lane) {
  const int r0 = lane >> 3, ch = lane & 7;
  const uint32_t src = slot + (wrow0 + r0) * 128;
  uint4 v[4];
#pragma unroll
  for (int i = 0; i < 4; ++i) v[i] = lds128(src + i * 512 + (((ch ^ (4 * i + r0)) & 7) << 4));
  dst += (size_t)(wrow0 + r0) * PITCH + ch * 8;
#pragma unroll
  for (int i = 0; i < 4; ++i) *reinterpret_cast<uint4*>(dst + (size_t)i * 4 * PITCH) = v[i];
}

__device__ __forceinline__ void stats_out(float s0, float s1, float q0, float q1, float2* dst, int t) {
  const bool od = t & 1;
  float sa = od ? s1 : s0, qa = od ? q1 : q0;
  sa += __shfl_xor_sync(0xffffffffu, od ? s0 : s1, 1);
  qa += __shfl_xor_sync(0xffffffffu, od ? q0 : q1, 1);
  sa += __shfl_xor_sync(0xffffffffu, sa, 2);
  qa += __shfl_xor_sync(0xffffffffu, qa, 2);
  if (t < 2) dst[t * 8] = make_float2(sa, qa);
}

__device__ __forceinline__ void consumer(const Ctx& c) {
  const int g = c.g, m0 = c.rb * 128;
  float acc[192];
#define X_H1() \
      _Pragma("unroll") for (int jp = 4; jp < 8; ++jp) \
        stsm_x4(sb + (XS + 1) * SLOT + rowo + (X ^ ((jp & 3) << 5)), \
                pack_bf16(acc[128 + 8 * jp], acc[129 + 8 * jp]), pack_bf16(acc[130 + 8 * jp], acc[131 + 8 * jp]), \
                pack_bf16(acc[132 + 8 * jp], acc[133 + 8 * jp]), pack_bf16(acc[134 + 8 * jp], acc[135 + 8 * jp]));
#pragma unroll
  for (int i = 128; i < 192; ++i) acc[i] = 0.f;
#pragma unroll 1
  for (int layer = 0;; ++layer) {
    {
      PHASE_CTX();
      const uint32_t wu = __shfl_sync(0xffffffffu, wg, 0);
      const uint32_t dA0 = (((sb + wu * 8192) & 0x3FFFF) >> 4) | (1u << 16), dB0 = ((sb & 0x3FFFF) >> 4) | (512u << 16);
      {
        PROFX(0);
        mbar_wait(bar + B_FULLS, 0);
        PROFX(1);
        if (elected && c.isum == 0 && layer == 0) mbar_arrive(bar + B_CSL);
        wgmma_fence();
        wgmma_n256_0(acc, D128(dA0 + XS * 1024), D128(dB0 + 2048));
#pragma unroll
        for (int k = 1; k < 4; ++k) wgmma_n256(acc, D128(dA0 + XS * 1024 + k * 2), D128(dB0 + 2048 + k * 128), 1);
        wgmma_commit();
        wgmma_wait<1>();
        float s0 = 0.f, s1 = 0.f, q0 = 0.f, q1 = 0.f;
        if (layer) {
          X_H1();
#pragma unroll
          for (int i = 128; i < 192; i += 4) {
            s0 += acc[i] + acc[i + 1]; s1 += acc[i + 2] + acc[i + 3];
            q0 = fmaf(acc[i], acc[i], fmaf(acc[i + 1], acc[i + 1], q0)); q1 = fmaf(acc[i + 2], acc[i + 2], fmaf(acc[i + 3], acc[i + 3], q1));
          }
        }
        asm volatile("" : "+f"(s0), "+f"(s1), "+f"(q0), "+f"(q1) :: "memory");
        wgmma_fence();
        wgmma_n128_0(acc, D128(dA0 + XS * 1024), D128(dB0 + 1024));
#pragma unroll
        for (int k = 1; k < 4; ++k) wgmma_n128(acc, D128(dA0 + XS * 1024 + k * 2), D128(dB0 + 1024 + k * 128), 1);
        wgmma_commit();
        if (layer) {
          PHASE_CTX();
          fence_async_smem();
          nbar_dyn(3 + wu, 128);
          stats_out(s0, s1, q0, q1, g_stats + ((layer & 1) * 8 + g) * S_ + m0 + wrow0 + gq, t);
          PROFT(tid_ == 128, layer * 16 + 8);
        }
      }
      uint32_t s = 1, u = 0, sp = 0;
      const int ix = layer ? 1 : g ? 3 : 1;
#pragma unroll 1
      for (int i = 1; i < 14; ++i) {
        mbar_wait(bar + B_FULLS + s * 8, (u + (s ? layer : 0)) & 1);
        if (elected && i == c.isum && layer == 0) mbar_arrive(bar + B_CSL);
        const uint32_t da = dA0 + ((QA >> (4 * s)) & 15) * 1024, dk = dB0 + ((QK >> (4 * s)) & 15) * 1024,
                       dq = dB0 + ((QQ >> (4 * s)) & 15) * 1024;
        wgmma_fence();
#pragma unroll
        for (int k = 0; k < 4; ++k) {
          wgmma_n256(acc, D128(da + k * 2), D128(dk + k * 128), 1);
          wgmma_n128(acc, D128(da + k * 2), D128(dq + k * 128), 1);
        }
        wgmma_commit();
        if (i == ix) {
          PHASE_CTX();
          if (layer) {
            slab_out_half(sb + (XS + 1) * SLOT, g_x + (size_t)m0 * D_ + g * 128 + 64, wrow0, lane);
          } else {
            float s0 = 0.f, s1 = 0.f, q0 = 0.f, q1 = 0.f;
#pragma unroll 1
            for (int hf = 0; hf < 4; ++hf) {
              const uint32_t xa = sb + ((QA >> (4 * ((hf & 2) ? s : sp))) & 15) * SLOT + rowo;
#pragma unroll
              for (int jp = 0; jp < 2; ++jp) {
                uint32_t x0, x1, x2, x3;
                ldsm_x4(x0, x1, x2, x3, xa + (X ^ (jp << 5) ^ ((hf & 1) << 6)));
                s0 += (bf_lo(x0) + bf_hi(x0)) + (bf_lo(x2) + bf_hi(x2));
                s1 += (bf_lo(x1) + bf_hi(x1)) + (bf_lo(x3) + bf_hi(x3));
                q0 = fmaf(bf_lo(x0), bf_lo(x0), fmaf(bf_hi(x0), bf_hi(x0), fmaf(bf_lo(x2), bf_lo(x2), fmaf(bf_hi(x2), bf_hi(x2), q0))));
                q1 = fmaf(bf_lo(x1), bf_lo(x1), fmaf(bf_hi(x1), bf_hi(x1), fmaf(bf_lo(x3), bf_lo(x3), fmaf(bf_hi(x3), bf_hi(x3), q1))));
              }
            }
            stats_out(s0, s1, q0, q1, g_stats + g * S_ + m0 + wrow0 + gq, t);
          }
          __syncwarp();
          if (lane == 0) mbar_arrive(bar + B_XDONE);
          nbar_dyn(3 + wu, 128);
        }
        wgmma_wait<1>();
        if (elected) release2(bar + B_EMPTYS + sp * 8);
        sp = s;
        if (++s == 3) { s = 0; ++u; }
      }
      {
        const uint64_t dap = make_desc_ns(sb + SM_AP + wu * 1024, 0, 128), dbp = make_desc_ns(sb + SM_BP + (layer & 1) * 6144, 0, 128);
        if (wu == 0) {
          wgmma_wait<0>();
          nbar<6, 256>();
        }
        if (layer < 2) mbar_wait(bar + (layer ? B_CS2 : B_CS), 0);
        mbar_wait(bar + B_STAT, layer & 1);
        mbar_wait(bar + B_FULLS + 16, layer & 1);
        wgmma_fence();
        wgmma_n256_k(acc, dap, dbp, 1);
#pragma unroll
        for (int k = 0; k < 4; ++k) wgmma_n256(acc, D128(dA0 + (QA >> 8) * 1024 + k * 2), D128(dB0 + (QK >> 8) * 1024 + k * 128), 1);
        mbar_wait(bar + B_FULLS, 1);
        PROFT(tid_ == 128, layer * 16 + 9);
        wgmma_fence();
#pragma unroll
        for (int k = 0; k < 4; ++k) wgmma_n256(acc, D128(dA0 + (QA & 15) * 1024 + k * 2), D128(dB0 + (QK & 15) * 1024 + k * 128), 1);
        wgmma_commit();
        if (wu) nbar<6, 256>();
#define Q_TAIL() \
        wgmma_n128_k(acc, dap, dbp + 256, 1); \
        _Pragma("unroll") for (int k = 0; k < 4; ++k) wgmma_n128(acc, D128(dA0 + (QA >> 8) * 1024 + k * 2), D128(dB0 + (QQ >> 8) * 1024 + k * 128), 1); \
        _Pragma("unroll") for (int k = 0; k < 4; ++k) wgmma_n128(acc, D128(dA0 + (QA & 15) * 1024 + k * 2), D128(dB0 + (QQ & 15) * 1024 + k * 128), 1);
        Q_TAIL();
        wgmma_commit();
        wgmma_wait<1>();
#pragma unroll
        for (int i = 0; i < 128; ++i) asm volatile("" : "+f"(acc[i]) :: "memory");
      }
    }
    uint32_t xo[32];
    {
      PHASE_CTX();
      PROFT(tid_ == 128, layer * 16 + 1);
      const bool isB = layer & 1;
      const int cu = c.cu;
      if (cu >= 4) asm volatile("bar.arrive 7, 256;" ::: "memory");
      else if (isB && cu == 0) asm volatile("bar.arrive 10, 64;" ::: "memory");
      if (elected && isB && cu == 0) release2(bar + B_E1);
      uint32_t kq[64];
#pragma unroll
      for (int i = 0; i < 32; ++i) kq[i] = pack_bf16(acc[2 * i], acc[2 * i + 1]);
      const unsigned int epoch = __float_as_uint(lds_f(sb + SM_EPOCH));
      uint4* const hbuf = g_halo + (size_t)((((epoch & 1) * 2 + (layer >> 1)) * 16 + c.rb) * 8 + g) * 512 + lane;
      if (isB && cu == 7) {
#pragma unroll
        for (int jp = 0; jp < 8; ++jp) st_relaxed4(hbuf + jp * 32, ~kq[4 * jp], ~kq[4 * jp + 1], ~kq[4 * jp + 2], ~kq[4 * jp + 3]);
#pragma unroll
        for (int jp = 8; jp < 16; ++jp)
          st_relaxed4(hbuf + jp * 32, ~pack_bf16(acc[8 * jp], acc[8 * jp + 1]), ~pack_bf16(acc[8 * jp + 2], acc[8 * jp + 3]),
                      ~pack_bf16(acc[8 * jp + 4], acc[8 * jp + 5]), ~pack_bf16(acc[8 * jp + 6], acc[8 * jp + 7]));
      }
      const uint32_t rowq = rowo & 8191;
      const uint32_t rB = sb + 4 * SLOT + wg * 4 * KVT + rowq, pA = sb + (3 + 3 * wg) * SLOT + rowq;
      PROFX(13);
      if (cu < 4) nbar<7, 256>();
      PROFX(14);
      {
        const uint32_t vb = isB ? rB + KVT + 2048 + wg * 2 * KVT : pA + 2 * SLOT - (rowq >> 1), vst = isB ? (1 - 2 * wg) * 2 * KVT : 8192;
        const uint32_t X0 = isB ? X : (lchk ^ ((lane & 7) >> 1)) << 4, X1 = isB ? X ^ 64 : X0 + 4096;
        const bool dup = isB && cu == 3;
        if (isB) {
#pragma unroll
          for (int jp = 0; jp < 8; ++jp) {
            stsm_x4(vb - KVT + (jp >> 2) * vst + (X ^ ((jp & 3) << 5)), kq[4 * jp], kq[4 * jp + 1], kq[4 * jp + 2], kq[4 * jp + 3]);
            stsm_x4_p(dup, rB + 2048 + 32768 + (1 - (jp >> 2)) * 2 * KVT + (X ^ ((jp & 3) << 5)), kq[4 * jp], kq[4 * jp + 1], kq[4 * jp + 2], kq[4 * jp + 3]);
          }
        }
#pragma unroll
        for (int jp = 8; jp < 16; ++jp) {
          const uint32_t v0 = pack_bf16(acc[8 * jp], acc[8 * jp + 1]), v1 = pack_bf16(acc[8 * jp + 2], acc[8 * jp + 3]),
                         v2 = pack_bf16(acc[8 * jp + 4], acc[8 * jp + 5]), v3 = pack_bf16(acc[8 * jp + 6], acc[8 * jp + 7]);
          const uint32_t ad = vb + ((jp >> 2) & 1) * vst + (((jp & 2) ? X1 : X0) ^ ((jp & 1) << 5));
          stsm_x4(ad, v0, v1, v2, v3);
          stsm_x4_p(dup, ad + 32768 + ((jp & 4) ? -2 * KVT : 2 * KVT), v0, v1, v2, v3);
        }
        if (dup) asm volatile("bar.arrive 9, 64;" ::: "memory");
      }
      const float rs0 = lds_f(sb + SM_RS + (16 + wrow0 + gq) * 4), rs1 = lds_f(sb + SM_RS + (24 + wrow0 + gq) * 4);
      PROFT(tid_ == 128, layer * 16 + 2);
#define Q_DONE() \
      wgmma_wait<0>(); \
      if (lane == 0) release2(bar + B_E0); \
      _Pragma("unroll") for (int i = 128; i < 192; ++i) asm volatile("" : "+f"(acc[i]) :: "memory"); \
      _Pragma("unroll") for (int i = 0; i < 32; ++i) kq[32 + i] = pack_bf16(acc[128 + 2 * i], acc[129 + 2 * i]);
      Q_DONE();
      if (isB) {
        const int e = gq & 1;
        const uint32_t KX = ((lane >> 3) ^ (lane & 7)) << 4;
        float f0[4], f1[4], rj[4];
        uint32_t msk = 0;
#pragma unroll
        for (int nt = 0; nt < 4; ++nt) {
          const int kk = nt * 8 + 2 * t + e;
          const bool okk = (m0 + wrow0 + kk) >= 16;
          const int d0 = kk - gq, d1 = d0 - 8;
          rj[nt] = lds_f(sb + SM_RS + (wrow0 + kk) * 4);
          f0[nt] = rj[nt] * rs0 * (0.17677669529663687f * L2E);
          f1[nt] = rj[nt] * rs1 * (0.17677669529663687f * L2E);
          msk |= (okk && d0 >= 2 && d0 <= 16) ? (1u << nt) : 0u;
          msk |= (okk && d1 >= 2 && d1 <= 16) ? (16u << nt) : 0u;
        }
        if ((cu & 3) == 0) asm volatile("bar.arrive %0, 128;" :: "r"(3 + (cu >> 2)) : "memory");
        if (cu == 0) {
          nbar<11, 64>();
        } else if (cu == 4) {
          uint4 hv[16];
          if (c.rb > 0) {
            uint32_t n = 0;
#pragma unroll 1
            while (true) {
              uint32_t mn = 0xFFFFFFFFu;
#pragma unroll
              for (int i = 0; i < 16; ++i) hv[i] = ld_relaxed4(hbuf - 8 * 512 + i * 32);
#pragma unroll
              for (int i = 0; i < 16; ++i) mn = __vimin3_u32(__vimin3_u32(mn, hv[i].x, hv[i].y), hv[i].z, hv[i].w);
              if (__all_sync(0xffffffffu, mn != 0u)) break;
              if (++n > (1u << 20)) { g_err = 4u; break; }
            }
          } else {
#pragma unroll
            for (int i = 0; i < 16; ++i) hv[i] = make_uint4(~0u, ~0u, ~0u, ~0u);
          }
          nbar<10, 64>();
#pragma unroll
          for (int i = 0; i < 16; ++i)
            stsm_x4(rB - 4 * KVT + (((i >> 2) & 1) * 2 + (i >> 3)) * KVT + (X ^ ((i & 3) << 5)), ~hv[i].x, ~hv[i].y, ~hv[i].z, ~hv[i].w);
          asm volatile("bar.arrive 11, 64;" ::: "memory");
          nbar<9, 64>();
        } else {
          nbar_dyn(3 + (cu >> 2), 128);
        }
        PROFT(tid_ == 128, layer * 16 + 5);
#pragma unroll
        for (int i = 16; i < 32; ++i) xo[i] = 0u;
#pragma unroll 1
        for (int hp = 0; hp < 2; ++hp) {
          const uint32_t qad = sb + (XS + hp) * SLOT + rowo, kt = rB + 2 * (hp ^ wg) * KVT - (lane & 8) * 128, vt = rB + (2 * (hp ^ wg) + 1) * KVT;
          uint32_t qa[2][8];
#pragma unroll
          for (int i = 0; i < 16; ++i) { qa[i >> 3][i & 7] = kq[32 + i]; kq[32 + i] = kq[48 + i]; }
          float l0[2][4], l1[2][4];
#pragma unroll
          for (int nt = 0; nt < 4; ++nt)
#pragma unroll
            for (int h = 0; h < 2; ++h) {
              float sc[4] = {0.f, 0.f, 0.f, 0.f};
              uint32_t b0, b1, b2, b3;
              ldsm_x4(b0, b1, b2, b3, kt + nt * 1024 + (KX ^ (h << 6)));
              mma_bf16(sc, qa[h][0], qa[h][1], qa[h][2], qa[h][3], b0, b1);
              mma_bf16(sc, qa[h][4], qa[h][5], qa[h][6], qa[h][7], b2, b3);
              l0[h][nt] = (msk >> nt) & 1 ? (e ? sc[1] : sc[0]) * f0[nt] : -1e30f;
              l1[h][nt] = (msk >> (4 + nt)) & 1 ? (e ? sc[3] : sc[2]) * f1[nt] : -1e30f;
            }
          float mx0[2], mx1[2], s0[2], s1[2];
#pragma unroll
          for (int h = 0; h < 2; ++h) {
            mx0[h] = fmaxf(fmaxf(l0[h][0], l0[h][1]), fmaxf(l0[h][2], l0[h][3]));
            mx1[h] = fmaxf(fmaxf(l1[h][0], l1[h][1]), fmaxf(l1[h][2], l1[h][3]));
          }
#pragma unroll
          for (int o = 1; o <= 2; o <<= 1)
#pragma unroll
            for (int h = 0; h < 2; ++h) {
              mx0[h] = fmaxf(mx0[h], __shfl_xor_sync(0xffffffffu, mx0[h], o));
              mx1[h] = fmaxf(mx1[h], __shfl_xor_sync(0xffffffffu, mx1[h], o));
            }
#pragma unroll
          for (int h = 0; h < 2; ++h) {
#pragma unroll
            for (int nt = 0; nt < 4; ++nt) { l0[h][nt] = ex2(l0[h][nt] - mx0[h]); l1[h][nt] = ex2(l1[h][nt] - mx1[h]); }
            s0[h] = (l0[h][0] + l0[h][1]) + (l0[h][2] + l0[h][3]);
            s1[h] = (l1[h][0] + l1[h][1]) + (l1[h][2] + l1[h][3]);
          }
#pragma unroll
          for (int o = 1; o <= 2; o <<= 1)
#pragma unroll
            for (int h = 0; h < 2; ++h) {
              s0[h] += __shfl_xor_sync(0xffffffffu, s0[h], o);
              s1[h] += __shfl_xor_sync(0xffffffffu, s1[h], o);
            }
          uint32_t pl[2][4], phh[2][4];
#pragma unroll
          for (int h = 0; h < 2; ++h) {
            const float i0 = rcp(s0[h]), i1 = rcp(s1[h]);
#pragma unroll
            for (int nt = 0; nt < 4; ++nt) {
              const uint32_t pk = pack_bf16(l0[h][nt] * i0 * rj[nt], l1[h][nt] * i1 * rj[nt]);
              pl[h][nt] = e ? pk << 16 : pk & 0xFFFFu;
              phh[h][nt] = e ? pk & 0xFFFF0000u : pk >> 16;
            }
          }
          float oa[2][4][4];
#pragma unroll
          for (int h = 0; h < 2; ++h)
#pragma unroll
            for (int i = 0; i < 4; ++i) { oa[h][i][0] = oa[h][i][1] = oa[h][i][2] = oa[h][i][3] = 0.f; }
#pragma unroll
          for (int ks = 0; ks < 2; ++ks)
#pragma unroll
            for (int np = 0; np < 2; ++np)
#pragma unroll
              for (int h = 0; h < 2; ++h) {
                uint32_t b0, b1, b2, b3;
                ldsm_x4_t(b0, b1, b2, b3, vt + ks * 2048 + (X ^ (h << 6) ^ (np << 5)));
                mma_bf16(oa[h][2 * np], pl[h][2 * ks], phh[h][2 * ks], pl[h][2 * ks + 1], phh[h][2 * ks + 1], b0, b1);
                mma_bf16(oa[h][2 * np + 1], pl[h][2 * ks], phh[h][2 * ks], pl[h][2 * ks + 1], phh[h][2 * ks + 1], b2, b3);
              }
          if (hp == 0 && lane == 0) release2(bar + B_E3);
          mbar_wait(bar + B_XOLD, 1);
#pragma unroll
          for (int i = 0; i < 16; ++i) xo[i] = xo[16 + i];
#pragma unroll
          for (int jp = 0; jp < 4; ++jp) ldsm_x4(xo[16 + 4 * jp], xo[17 + 4 * jp], xo[18 + 4 * jp], xo[19 + 4 * jp], qad + (X ^ (jp << 5)));
#pragma unroll
          for (int h = 0; h < 2; ++h)
#pragma unroll
            for (int np = 0; np < 2; ++np)
              stsm_x4(qad + (X ^ (h << 6) ^ (np << 5)),
                      pack_bf16(oa[h][2 * np][0], oa[h][2 * np][1]), pack_bf16(oa[h][2 * np][2], oa[h][2 * np][3]),
                      pack_bf16(oa[h][2 * np + 1][0], oa[h][2 * np + 1][1]), pack_bf16(oa[h][2 * np + 1][2], oa[h][2 * np + 1][3]));
          fence_async_smem();
          {
            __syncwarp();
            slab_out_half(sb + (XS + hp) * SLOT, g_o + (size_t)m0 * D_ + g * 128 + hp * 64, wrow0, lane);
            __syncwarp();
            if (lane == 0) mbar_arrive(bar + (hp ? B_ODONE : B_OH1));
          }
        }
      } else {
        PHASE_CTX();
        const uint32_t pA = sb + (3 + 3 * wg) * SLOT + (rowo & 8191);
        const float sc0 = rs0 * L2E, sc1 = rs1 * L2E;
        const uint32_t wa0 = sb + SM_WPHI + lrow * 80 + lchk * 16;
        __syncwarp();
#pragma unroll
        for (int i = 0; i < 32; ++i) xo[i] = 0u;
        float p[HPI][4][4];
        auto proj = [&](int hp) {
#pragma unroll
            for (int h = 0; h < HPI; ++h)
#pragma unroll
              for (int i = 0; i < 4; ++i) { p[h][i][0] = p[h][i][1] = p[h][i][2] = p[h][i][3] = 0.f; }
            const uint32_t wa = wa0 + hp * 5120;
#pragma unroll
            for (int ks = 0; ks < 2; ++ks)
#pragma unroll
              for (int np = 0; np < 2; ++np)
#pragma unroll
                for (int h = 0; h < HPI; ++h) {
                  uint32_t b0, b1, b2, b3;
                  ldsm_x4_t(b0, b1, b2, b3, wa + h * 2560 + ks * 1280 + np * 32);
                  mma_bf16(p[h][2 * np], kq[8 * h + 4 * ks], kq[8 * h + 4 * ks + 1], kq[8 * h + 4 * ks + 2], kq[8 * h + 4 * ks + 3], b0, b1);
                  mma_bf16(p[h][2 * np + 1], kq[8 * h + 4 * ks], kq[8 * h + 4 * ks + 1], kq[8 * h + 4 * ks + 2], kq[8 * h + 4 * ks + 3], b2, b3);
                }
        };
#pragma unroll 1
        for (int it = 0;; ++it) {
          const bool isq = it >= 2;
          const int hp = it & 1;
          const float mul0 = isq ? 1.f : rs0, mul1 = isq ? 1.f : rs1;
          uint32_t ph[2][4][4];
          proj(hp);
          bool bad = false;
          {
            float ss[HPI][2][4];
#pragma unroll
            for (int h = 0; h < HPI; ++h) {
#pragma unroll
              for (int i = 0; i < 4; ++i) {
                const float e0 = ex2(p[h][i][0] * sc0), e1 = ex2(p[h][i][1] * sc0), e2 = ex2(p[h][i][2] * sc1), e3 = ex2(p[h][i][3] * sc1);
                const float m0 = e0 * e1, m1 = e2 * e3, rr = rcp(m0 * m1), r0 = rr * m1, r1 = rr * m0;
                ph[h][i >> 1][(i & 1) * 2] = pack_bf16(e0, e1);
                ph[h][i >> 1][(i & 1) * 2 + 1] = pack_bf16(e2, e3);
                ph[h][2 + (i >> 1)][(i & 1) * 2] = pack_bf16(e1 * r0, e0 * r0);
                ph[h][2 + (i >> 1)][(i & 1) * 2 + 1] = pack_bf16(e3 * r1, e2 * r1);
              }
#pragma unroll
              for (int sg = 0; sg < 2; ++sg) {
                ss[h][sg][0] = ss[h][sg][1] = ss[h][sg][2] = ss[h][sg][3] = 0.f;
#pragma unroll
                for (int ks = 0; ks < 2; ++ks)
                  mma_bf16(ss[h][sg], ph[h][2 * sg + ks][0], ph[h][2 * sg + ks][1], ph[h][2 * sg + ks][2], ph[h][2 * sg + ks][3], 0x3F803F80u, 0x3F803F80u);
              }
            }
#pragma unroll
            for (int h = 0; h < HPI; ++h)
#pragma unroll
              for (int sg = 0; sg < 2; ++sg) {
                bad = bad || !(ss[h][sg][0] < PHI_MAX) || !(ss[h][sg][2] < PHI_MAX);
                const uint32_t iv = pack_bf16(rcp(ss[h][sg][0]) * mul0, rcp(ss[h][sg][2]) * mul1);
#pragma unroll
                for (int ks = 0; ks < 2; ++ks)
#pragma unroll
                  for (int j = 0; j < 4; ++j) ph[h][2 * sg + ks][j] = mul_bf16x2(ph[h][2 * sg + ks][j], iv, j & 1);
              }
          }
          if (__builtin_expect(__any_sync(0xffffffffu, bad), 0)) {
            proj(hp);
            float mx[HPI][2], mn[HPI][2];
#pragma unroll
            for (int h = 0; h < HPI; ++h)
#pragma unroll
              for (int r = 0; r < 2; ++r) {
                mx[h][r] = fmaxf(fmaxf(fmaxf(p[h][0][2 * r], p[h][0][2 * r + 1]), fmaxf(p[h][1][2 * r], p[h][1][2 * r + 1])),
                                 fmaxf(fmaxf(p[h][2][2 * r], p[h][2][2 * r + 1]), fmaxf(p[h][3][2 * r], p[h][3][2 * r + 1])));
                mn[h][r] = fminf(fminf(fminf(p[h][0][2 * r], p[h][0][2 * r + 1]), fminf(p[h][1][2 * r], p[h][1][2 * r + 1])),
                                 fminf(fminf(p[h][2][2 * r], p[h][2][2 * r + 1]), fminf(p[h][3][2 * r], p[h][3][2 * r + 1])));
              }
#pragma unroll
            for (int o = 1; o <= 2; o <<= 1)
#pragma unroll
              for (int h = 0; h < HPI; ++h)
#pragma unroll
                for (int r = 0; r < 2; ++r) {
                  mx[h][r] = fmaxf(mx[h][r], __shfl_xor_sync(0xffffffffu, mx[h][r], o));
                  mn[h][r] = fminf(mn[h][r], __shfl_xor_sync(0xffffffffu, mn[h][r], o));
                }
            float en[HPI][4][4], sp[HPI][2], sn[HPI][2];
#pragma unroll
            for (int h = 0; h < HPI; ++h) {
              mx[h][0] *= -sc0; mx[h][1] *= -sc1; mn[h][0] *= sc0; mn[h][1] *= sc1;
              sp[h][0] = sp[h][1] = sn[h][0] = sn[h][1] = 0.f;
            }
#pragma unroll
            for (int i = 0; i < 4; ++i)
#pragma unroll
              for (int e = 0; e < 4; ++e)
#pragma unroll
                for (int h = 0; h < HPI; ++h) {
                  en[h][i][e] = ex2(fmaf(p[h][i][e], (e >> 1) ? -sc1 : -sc0, mn[h][e >> 1]));
                  p[h][i][e] = ex2(fmaf(p[h][i][e], (e >> 1) ? sc1 : sc0, mx[h][e >> 1]));
                  sp[h][e >> 1] += p[h][i][e]; sn[h][e >> 1] += en[h][i][e];
                }
#pragma unroll
            for (int o = 1; o <= 2; o <<= 1)
#pragma unroll
              for (int h = 0; h < HPI; ++h)
#pragma unroll
                for (int r = 0; r < 2; ++r) {
                  sp[h][r] += __shfl_xor_sync(0xffffffffu, sp[h][r], o);
                  sn[h][r] += __shfl_xor_sync(0xffffffffu, sn[h][r], o);
                }
#pragma unroll
            for (int h = 0; h < HPI; ++h) {
              const float ip0 = rcp(sp[h][0]) * mul0, ip1 = rcp(sp[h][1]) * mul1, in0 = rcp(sn[h][0]) * mul0, in1 = rcp(sn[h][1]) * mul1;
#pragma unroll
              for (int cp = 0; cp < 2; ++cp) {
                ph[h][cp][0] = pack_bf16(p[h][2 * cp][0] * ip0, p[h][2 * cp][1] * ip0);
                ph[h][cp][1] = pack_bf16(p[h][2 * cp][2] * ip1, p[h][2 * cp][3] * ip1);
                ph[h][cp][2] = pack_bf16(p[h][2 * cp + 1][0] * ip0, p[h][2 * cp + 1][1] * ip0);
                ph[h][cp][3] = pack_bf16(p[h][2 * cp + 1][2] * ip1, p[h][2 * cp + 1][3] * ip1);
                ph[h][2 + cp][0] = pack_bf16(en[h][2 * cp][0] * in0, en[h][2 * cp][1] * in0);
                ph[h][2 + cp][1] = pack_bf16(en[h][2 * cp][2] * in1, en[h][2 * cp][3] * in1);
                ph[h][2 + cp][2] = pack_bf16(en[h][2 * cp + 1][0] * in0, en[h][2 * cp + 1][1] * in0);
                ph[h][2 + cp][3] = pack_bf16(en[h][2 * cp + 1][2] * in1, en[h][2 * cp + 1][3] * in1);
              }
            }
          }
#pragma unroll
          for (int i = 0; i < 48; ++i) kq[i] = kq[16 + i];
          if (!isq) {
#pragma unroll
            for (int h = 0; h < HPI; ++h)
#pragma unroll
              for (int cp = 0; cp < 4; ++cp)
                stsm_x4(pA + hp * 16384 + h * 8192 + (X ^ (cp << 5)), ph[h][cp][0], ph[h][cp][1], ph[h][cp][2], ph[h][cp][3]);
            PROFT(tid_ == 128, layer * 16 + 11);
            fence_async_smem();
            nbar<1, 256>();
            uint32_t hu = 2 * hp + wg;
            asm volatile("" : "+r"(hu));
            hu = __shfl_sync(0xffffffffu, hu, 0);
            const uint32_t dP = (((sb + 3 * SLOT + hu * 8192) & 0x3FFFF) >> 4) | (512u << 16);
            const uint32_t dV = (((sb + 5 * SLOT + hu * 4096) & 0x3FFFF) >> 4) | (((SM_SD - 5 * SLOT - hu * 4096) >> 4) << 16);
            float kva[20];
            wgmma_fence();
#pragma unroll
            for (int ks = 0; ks < 8; ++ks)
              wgmma_n40_tt(kva, desc64(dP + (ks >> 2) * 3072 + (ks & 3) * 128, 0x40000040u),
                           desc64(dV + (ks >> 2) * (3072u - (2816u << 16)) + (ks & 3) * 64, 0x80000020u), ks != 0);
            wgmma_commit();
            wgmma_wait<0>();
            nbar_dyn(3 + wg, 128);
            PROFT(tid_ == 128, layer * 16 + 12);
#pragma unroll
            for (int i = 0; i < 4; ++i)
              sts128(sb + (3 + hp) * SLOT + (cw * 128 + i * 32 + lane) * 16,
                     make_uint4(__float_as_uint(kva[4 * i]), __float_as_uint(kva[4 * i + 1]), __float_as_uint(kva[4 * i + 2]), __float_as_uint(kva[4 * i + 3])));
            if (t == 0) {
              sts_f(sb + SM_AP + hp * 512 + (cw * 8 + gq) * 8, kva[16]);
              sts_f(sb + SM_AP + hp * 512 + (cw * 8 + gq) * 8 + 4, kva[18]);
            }
            fence_async_smem();
            __syncwarp();
            if (lane == 0) mbar_arrive(bar + B_KVDONE - hp * 32);
            if (elected && hp) release2(bar + B_E1);
            PROFT(tid_ == 128, layer * 16 + 3);
            continue;
          }
          PROFT(tid_ == 128 && hp == 0, layer * 16 + 10);
          mbar_wait(bar + B_KVDONE - 32, (layer >> 1) & 1);
          mbar_wait(bar + B_KVRDY - hp * 8, (layer >> 1) & 1);
          PROFT(tid_ == 128 && hp == 0, layer * 16 + 5);
          {
            uint4 u[4];
#pragma unroll
            for (int i = 0; i < 4; ++i) u[i] = lds128(sb + (3 + hp) * SLOT + (cw * 128 + i * 32 + lane) * 16);
            const float zz = lds_f(sb + SM_AP + hp * 512 + ((cw * 8 + (lane & 7)) * 2 + ((lane >> 3) & 1)) * 4);
#pragma unroll
            for (int i = 0; i < 4; i += 2)
              stsm_x4(sb + (5 + 3 * hp) * SLOT + rowo + (X ^ ((i & 2) << 4)),
                      pack_bf16(__uint_as_float(u[i].x), __uint_as_float(u[i].y)), pack_bf16(__uint_as_float(u[i].z), __uint_as_float(u[i].w)),
                      pack_bf16(__uint_as_float(u[i + 1].x), __uint_as_float(u[i + 1].y)), pack_bf16(__uint_as_float(u[i + 1].z), __uint_as_float(u[i + 1].w)));
            if (lane < 16) sts128(sb + (5 + 3 * hp) * SLOT + rowo + ((4 ^ (lane & 7)) << 4), make_uint4(pack_bf16(zz, 0.f), 0u, 0u, 0u));
          }
          fence_async_smem();
          nbar<1, 256>();
          PROFT(tid_ == 128 && hp == 1, layer * 16 + 4);
          float oa[2][20];
          const uint32_t dK = __shfl_sync(0xffffffffu, (((sb + (5 + 3 * hp) * SLOT) & 0x3FFFF) >> 4) | (512u << 16), 0);
          wgmma_fence();
#pragma unroll
          for (int ks = 0; ks < 4; ++ks) {
#pragma unroll
            for (int hh = 0; hh < 2; ++hh) wgmma_n40_rs(oa[hh], ph[hh][ks], D128(dK + hh * 512 + ks * 128), ks != 0);
          }
          wgmma_commit();
          if (hp == 0) {
            mbar_wait(bar + B_XOLD, 0);
#pragma unroll
            for (int jp = 0; jp < 8; ++jp)
              ldsm_x4(xo[4 * jp], xo[4 * jp + 1], xo[4 * jp + 2], xo[4 * jp + 3], sb + (XS + (jp >> 2)) * SLOT + rowo + (X ^ ((jp & 3) << 5)));
          }
          wgmma_wait<0>();
#pragma unroll
          for (int hh = 0; hh < 2; ++hh) {
            const float dn0 = __shfl_sync(0xffffffffu, oa[hh][16], lane & ~3), dn1 = __shfl_sync(0xffffffffu, oa[hh][18], lane & ~3);
            const float i0 = __fdividef(1.f, dn0 + 1e-6f), i1 = __fdividef(1.f, dn1 + 1e-6f);
            const uint32_t qad = sb + (3 + hp) * SLOT + rowo, hx = hh << 6;
#pragma unroll
            for (int np = 0; np < 2; ++np)
              stsm_x4(qad + (X ^ hx ^ (np << 5)),
                      pack_bf16(oa[hh][8 * np] * i0, oa[hh][8 * np + 1] * i0), pack_bf16(oa[hh][8 * np + 2] * i1, oa[hh][8 * np + 3] * i1),
                      pack_bf16(oa[hh][8 * np + 4] * i0, oa[hh][8 * np + 5] * i0), pack_bf16(oa[hh][8 * np + 6] * i1, oa[hh][8 * np + 7] * i1));
          }
          fence_async_smem();
          {
            __syncwarp();
            if (hp == 0 && lane == 0) release2(bar + B_E3);
            slab_out_half(sb + (3 + hp) * SLOT, g_o + (size_t)m0 * D_ + g * 128 + hp * 64, wrow0, lane);
            __syncwarp();
            if (lane == 0) mbar_arrive(bar + (hp ? B_ODONE : B_OH1));
          }
          if (hp) break;
        }
      }
      __syncwarp();
      PROFT(lane == 0 && layer == PL, 216 + cw);
      if (lane == 0) mbar_arrive(bar + B_EPI);
      PROFT(tid_ == 128, layer * 16 + 6);
    }
    {
      PHASE_CTX();
      const uint32_t wu = __shfl_sync(0xffffffffu, wg, 0);
      const uint32_t dA0 = (((sb + wu * 8192) & 0x3FFFF) >> 4) | (1u << 16), dB0 = ((sb & 0x3FFFF) >> 4) | (512u << 16);
#pragma unroll
      for (int i = 0; i < 32; ++i) { acc[128 + 2 * i] = bf_lo(xo[i]); acc[129 + 2 * i] = bf_hi(xo[i]); }
      nbar_dyn(3 + wg, 128);
      uint64_t ta = (layer & 1) ? WO_A1 : WO_A0, tw = (layer & 1) ? WO_B1 : WO_B0;
#pragma unroll 1
      for (int i = 0; i < 16; ++i) {
        bool rel = i > 0 && i < 12;
        if (DRY && rel && !__all_sync(0xffffffffu, mbar_test_wait(bar + B_FULLT + i * 8, layer & 1))) {
          wgmma_wait<0>();
          if (elected) release2(bar + B_CONS + (i - 1) * 8);
          rel = false;
        }
        mbar_wait(bar + B_FULLT + i * 8, layer & 1);
        PROFT(tid_ == 128 && layer == PL, 160 + i);
        const uint32_t da = dA0 + ((uint32_t)ta & 15) * 1024, db = dB0 + ((uint32_t)tw & 15) * 1024;
        ta >>= 4; tw >>= 4;
        wgmma_fence();
#pragma unroll
        for (int k = 0; k < 4; ++k) wgmma_n128(acc, D128(da + k * 2), D128(db + k * 128), 1);
        wgmma_commit();
        if (i == 0) {
          if (elected) {
            if ((layer & 1) && wu) release2(bar + B_E1);
            release2(bar + B_E2);
          }
        } else {
          wgmma_wait<1>();
          if (elected && rel) release2(bar + B_CONS + (i - 1) * 8);
          if (elected && (unsigned)(i - 13) < 2u && layer + 1 < NLAYERS) release2(bar + B_EMPTYS + (i - 13) * 8);
        }
      }
      const bool last = layer == NLAYERS - 1;
      wgmma_wait<0>();
#pragma unroll
      for (int i = 128; i < 192; ++i) asm volatile("" : "+f"(acc[i]) :: "memory");
      if (elected && !last) release2(bar + B_EMPTYS + 16);
      PROFT(tid_ == 128, layer * 16 + 7);
#pragma unroll
      for (int jp = 0; jp < 4; ++jp)
        stsm_x4(sb + XS * SLOT + rowo + (X ^ (jp << 5)),
                pack_bf16(acc[128 + 8 * jp], acc[129 + 8 * jp]), pack_bf16(acc[130 + 8 * jp], acc[131 + 8 * jp]),
                pack_bf16(acc[132 + 8 * jp], acc[133 + 8 * jp]), pack_bf16(acc[134 + 8 * jp], acc[135 + 8 * jp]));
      if (last) {
        __syncwarp();
        slab_out_half(sb + XS * SLOT, c.out + (size_t)m0 * D_ + g * 128, wrow0, lane);
        X_H1();
        __syncwarp();
        slab_out_half(sb + (XS + 1) * SLOT, c.out + (size_t)m0 * D_ + g * 128 + 64, wrow0, lane);
        __syncwarp();
        if (lane == 0) mbar_arrive(bar + B_XDONE);
        PROFT(tid_ == 128, layer * 16 + 24);
        break;
      }
      fence_async_smem();
      __syncwarp();
      slab_out_half(sb + XS * SLOT, g_x + (size_t)m0 * D_ + g * 128, wrow0, lane);
      __syncwarp();
      if (lane == 0) mbar_arrive(bar + B_XH0);
      nbar_dyn(3 + wu, 128);
    }
  }
}

__device__ __forceinline__ void flag_fetch(uint32_t bar, const unsigned int* f) {
  asm volatile("{\n.reg .pred p;\nelect.sync _|p, 0xffffffff;\n@p mbarrier.expect_tx.relaxed.cta.shared::cta.b64 [%2], 64;\n"
               "@p cp.async.bulk.shared::cluster.global.mbarrier::complete_tx::bytes [%0], [%1], 64, [%2];\n}\n"
               ::"r"(bar + B_FLG), "l"(f), "r"(bar + 128) : "memory");
}
__device__ __forceinline__ uint32_t korder0(int g, int sp) {
  uint32_t ord = 0, used = 1, n = 4;
#pragma unroll 1
  for (int j = -1; j < 8; ++j) {
    const uint32_t p = (j < 0 ? g : j == 0 ? sp : g + j) & 7;
    if (!((used >> p) & 1)) { ord |= p << n; n += 4; used |= 1u << p; }
  }
  return ord;
}

#define WOORD 0xFDB9753ECA864210ull
__device__ __forceinline__ int wo_kblock(int m, int g) { return (2 * g + (int)((WOORD >> (4 * m)) & 15)) & 15; }

__global__ void __cluster_dims__(2, 1, 1) __launch_bounds__(384, 1)
mega_kernel(const __grid_constant__ CUtensorMap tm_x0, const __grid_constant__ CUtensorMap tm_x,
            const __grid_constant__ CUtensorMap tm_o,
            const __grid_constant__ CUtensorMap tm_wA, const __grid_constant__ CUtensorMap tm_wB,
            const __grid_constant__ CUtensorMap tm_woA, const __grid_constant__ CUtensorMap tm_woB,
            const bf16* __restrict__ wA, const bf16* __restrict__ wB,
            const bf16* __restrict__ woA, const bf16* __restrict__ woB, const bf16* __restrict__ wphi, bf16* __restrict__ out) {
  extern __shared__ uint8_t smem_raw[];
  const uint32_t sb = (smem_u32(smem_raw) + 1023u) & ~1023u;
  const uint32_t bar = sb + SM_BAR;
  const int warp = __shfl_sync(0xffffffffu, threadIdx.x >> 5, 0), lane = threadIdx.x & 31;
  const int cr = blockIdx.x & 1;
  const int g = (blockIdx.x >> 1) & 7;
  const int rb = (blockIdx.x >> 4) * 2 + cr;
  const int m0 = rb * 128, sp0 = rb >> 1;
  const int isum0 = sp0 == 0 ? 0 : (sp0 == g || g == 0) ? 2 : 4;

  if (warp < 4) {
    asm volatile("setmaxnreg.dec.sync.aligned.u32 40;");
    if (warp > 0) {
      const uint32_t st = warp - 1, fb = bar + B_FULLS + st * 8;
      const int kc = (st < 2 ? st : 2 * (g ? g : sp0 ? sp0 : 1)) * 64;
      if (lane == 0) {
        mbar_init(fb, 1);
        asm volatile("fence.mbarrier_init.release.cluster;" ::: "memory");
      }
      __syncwarp();
      asm volatile("barrier.cluster.arrive.relaxed.aligned;" ::: "memory");
      expect_tx_e(fb, 65536);
      tma_2d_e(sb + ((QA >> (4 * st)) & 15) * SLOT, &tm_x0, kc, m0, fb);
#pragma unroll 1
      for (int j = 0; j < 6; ++j)
        tma_2d_e(sb + (j < 4 ? ((QK >> (4 * st)) & 15) * SLOT + j * 8192 : ((QQ >> (4 * st)) & 15) * SLOT + (j - 4) * 8192), &tm_wA,
                 (j < 4 ? 1024 + (j >> 1) * 1024 : 0) + g * 128 + (j & 1) * 64, kc, fb);
    } else {
      asm volatile("barrier.cluster.arrive.relaxed.aligned;" ::: "memory");
    }
    const unsigned int epoch = ld_relaxed(&g_epoch);
    cluster_wait();
    PROFT(threadIdx.x == 0, 125);
    const unsigned int xbase = epoch * NLAYERS, cbase = epoch * 16u;
    auto wo_a = [&](int layer) {
      uint64_t ts = ((layer & 1) ? WO_A1 : WO_A0) >> 8, td = ((layer & 1) ? WO_DA1 : WO_DA0) >> 8, tk = WOORD >> 8;
      uint32_t ready = 0u;
#pragma unroll 1
      for (int m = 2; m < 16; ++m) {
        const int kb = (2 * g + (uint32_t)tk) & 15;
        uint32_t dst = sb + ((uint32_t)ts & 15) * SLOT, fb = bar + B_FULLT + m * 8, eb = bar + B_CONS + ((uint32_t)td & 15) * 8;
        int kc = kb * 64;
        ts >>= 4; td >>= 4; tk >>= 4;
        if (!((ready >> kb) & 1)) {
          PROFT(m == 2 && lane == 0, 64 + layer * 16 + 2);
          if (EP && m > EP) {
            uint32_t n = 0;
#pragma unroll 1
            while (true) {
              ready |= __ballot_sync(0xffffffffu, (int)(lds_vol(bar + B_FLG + (lane & 15) * 4) - (xbase + layer + 1)) >= 0);
              if (((ready >> kb) & 1) || ++n > (1u << 20)) break;
              if ((n & 3) == 0) flag_fetch(bar, g_of + rb * 32);
              __nanosleep(PSL);
            }
          }
          src_wait<0>(g_of + rb * 32, xbase + layer + 1, 1u << kb, ready, lane);
          fence_async_all();
        }
        if (m == ((layer & 1) ? GAB : GAA)) mbar_wait_u(bar + B_OF, layer & 1);
        asm volatile("" : "+r"(dst), "+r"(fb), "+r"(eb), "+r"(kc));
        mbar_wait_u(eb, layer & 1);
        tma_2d_e(dst, &tm_o, kc, m0, fb);
        if (EP && m >= EP && (ready & 0xFFFFu) != 0xFFFFu) flag_fetch(bar, g_of + rb * 32);
        PROFT(lane == 0 && layer == PL, 176 + m);
      }
    };
    auto wo_w = [&](int layer) {
      const CUtensorMap* tx = layer == 0 ? &tm_x0 : &tm_x;
      const CUtensorMap* two = (layer & 1) ? &tm_woB : &tm_woA;
      uint64_t ts = (layer & 1) ? WO_B1 : WO_B0, td = (layer & 1) ? WO_DB1 : WO_DB0, tk = WOORD;
#pragma unroll 1
      for (int m = 0; m < 16; ++m) {
        uint32_t dst = sb + ((uint32_t)ts & 15) * SLOT + cr * 8192, fb = bar + B_FULLT + m * 8, eb = bar + B_CONS + ((uint32_t)td & 15) * 8;
        int kc = ((2 * g + (uint32_t)tk) & 15) * 64;
        ts >>= 4; td >>= 4; tk >>= 4;
        if (m == ((layer & 1) ? GWB : GWA)) mbar_wait_u(bar + B_OF, layer & 1);
        asm volatile("" : "+r"(dst), "+r"(fb), "+r"(eb), "+r"(kc));
        mbar_wait_u(eb, layer & 1);
        tma_2d_mc_e(dst, two, g * 128 + cr * 64, kc, fb);
        expect_tx_e(fb, m < 2 ? 16384 : 32768);
        PROFT(lane == 0 && layer == PL, 144 + m);
        if (m == 0) {
          fence_async_all();
          expect_tx_e(bar + B_XOLD, 32768);
          tma_2d_e(sb + XS * SLOT, tx, g * 128, m0, bar + B_XOLD);
          tma_2d_e(sb + (XS + 1) * SLOT, tx, g * 128 + 64, m0, bar + B_XOLD);
        }
      }
    };
    auto kv_fetch = [&](int layer, int hp) {
      const float* kvl = g_kv + ((size_t)((epoch & 1) * 2 + (layer >> 1)) * 8 + g) * 8448;
      flag_wait(&g_kvflag[hp * 8 + g].v, epoch * (16u * ((NLAYERS + 1) / 2)) + 16u * ((layer >> 1) + 1));
      fence_async_all();
      mbar_expect_tx(bar + B_KVRDY - hp * 8, 16896);
      bulk_load(sb + (3 + hp) * SLOT, kvl + hp * 4096, 16384, bar + B_KVRDY - hp * 8);
      bulk_load(sb + SM_AP + hp * 512, kvl + 8192 + hp * 128, 512, bar + B_KVRDY - hp * 8);
    };
    if (warp == 0) {
      const uint32_t ord0 = korder0(g, sp0);
#define PFW 0
      mbar_wait_u(bar + B_FULLS + PFW * 8, 0);
      tma_pf_e(&tm_x0, g * 128 + 64, m0);
#pragma unroll 1
      for (int j = 0; j < 6; ++j) tma_pf_e(&tm_wA, (j >> 1) * 1024 + g * 128 + (j & 1) * 64, rb * 64);
#pragma unroll 1
      for (int layer = 0; layer < NLAYERS; ++layer) {
        const CUtensorMap* tx = layer == 0 ? &tm_x0 : &tm_x;
        const CUtensorMap* tw = (layer & 1) ? &tm_wB : &tm_wA;
        uint32_t s = 0, u = layer == 0, ready = layer == 0 ? 0xFFFFu : 0u;
#pragma unroll 1
        for (int i = layer == 0 ? 3 : 0; i < 16; ++i) {
          const int kb = layer == 0 ? ((ord0 >> (4 * (i >> 1))) & 7) * 2 + (i & 1) : wo_kblock(i, g), kc = kb * 64;
          const uint32_t fb = bar + B_FULLS + s * 8;
          const uint32_t kd = sb + (((QK >> (4 * s)) & 15) + cr) * SLOT, qd = sb + ((QQ >> (4 * s)) & 15) * SLOT + cr * 8192;
          const uint32_t need = 1u << kb;
          const bool early = i >= 2 && (ready & need) == need;
          mbar_wait_u(bar + B_EMPTYS + s * 8, (u + (s ? layer : 0) + 1) & 1);
          if (layer == 0 && (unsigned)(i - isum0 - 3) < 2u) mbar_wait_u(bar + B_CSFREE + (i - isum0 - 3) * 8, 0);
          if (early) tma_2d_e(sb + ((QA >> (4 * s)) & 15) * SLOT, tx, kc, m0, fb);
          tma_2d_mc_e(kd, tw, 1024 + cr * 1024 + g * 128, kc, fb);
          tma_2d_mc_e(kd + 8192, tw, 1024 + cr * 1024 + g * 128 + 64, kc, fb);
          tma_2d_mc_e(qd, tw, g * 128 + cr * 64, kc, fb);
          expect_tx_e(fb, i < 2 ? 49152 : 65536);
          if (i >= 2 && !early) {
            PROFT(i == 2 && lane == 0, 64 + layer * 16 + 0);
            src_wait<0>(g_xf + rb * 32, xbase + layer + 1, need, ready, lane);
            PROFT(i == 2 && lane == 0, 64 + layer * 16 + 1);
            fence_async_all();
            tma_2d_e(sb + ((QA >> (4 * s)) & 15) * SLOT, tx, kc, m0, fb);
          }
          if (++s == 3) { s = 0; ++u; }
        }
        wo_a(layer);
      }
    } else {
      if (warp >= 2) {
        const int h2 = threadIdx.x - 64;
#pragma unroll 1
        for (int i = h2; i < 512; i += 64)
          asm volatile("cp.async.cg.shared.global [%0], [%1], 16;" ::"r"(sb + SM_WPHI + (i >> 2) * 80 + (i & 3) * 16), "l"(wphi + (size_t)g * 4096 + i * 8) : "memory");
        sts128(sb + SM_SD + h2 * 128 + (h2 & 3) * 16, make_uint4(0u, 0u, 0u, 0u));
        sts128(sb + SM_SD + h2 * 128 + 64 + (h2 & 3) * 16, make_uint4(0u, 0u, 0u, 0u));
        if (h2 < 16) sts_f(sb + SM_RS + h2 * 4, 0.f);
        if (h2 < 16) sts_f(bar + B_FLG + h2 * 4, __uint_as_float(xbase));
        if (h2 == 0) sts_f(sb + SM_EPOCH, __uint_as_float(epoch));
        float4* kz = reinterpret_cast<float4*>(g_kv + (size_t)((epoch & 1) ^ 1) * (2 * 8 * 8448)) + blockIdx.x * 264;
#pragma unroll 1
        for (int i = h2; i < 264; i += 64) kz[i] = make_float4(0.f, 0.f, 0.f, 0.f);
        uint4* hz = g_halo + (size_t)((epoch & 1) ^ 1) * (2 * 128 * 512) + blockIdx.x * 1024;
#pragma unroll 1
        for (int i = h2; i < 1024; i += 64) hz[i] = make_uint4(0u, 0u, 0u, 0u);
        if (h2 < 12) reinterpret_cast<float4*>(g_cs + ((epoch & 1) ^ 1) * 6144 + blockIdx.x * 48)[h2] = make_float4(0.f, 0.f, 0.f, 0.f);
      }
      {
        const int ht = threadIdx.x - 32, bc = ht % 48, hf = ht / 48;
        const int st = (isum0 + cr) % 3;
        const uint32_t src = sb + (bc < 32 ? ((QK >> (4 * st)) & 15) * SLOT + (bc >> 3) * 8192 : ((QQ >> (4 * st)) & 15) * SLOT + ((bc >> 3) - 4) * 8192) + hf * 4096;
        float s[8] = {0.f, 0.f, 0.f, 0.f, 0.f, 0.f, 0.f, 0.f};
        mbar_wait(bar + B_CSL, 0);
        if (ht < 6) asm volatile("cp.async.bulk.prefetch.tensor.2d.L2.global.tile [%0, {%1, %2}];" ::"l"(&tm_wB), "r"((ht >> 1) * 1024 + g * 128 + (ht & 1) * 64), "r"(rb * 64) : "memory");
#pragma unroll 4
        for (int r = 0; r < 32; ++r) {
          const uint4 v = lds128(src + r * 128 + (((bc ^ r) & 7) << 4));
          s[0] += bf_lo(v.x); s[1] += bf_hi(v.x); s[2] += bf_lo(v.y); s[3] += bf_hi(v.y);
          s[4] += bf_lo(v.z); s[5] += bf_hi(v.z); s[6] += bf_lo(v.w); s[7] += bf_hi(v.w);
        }
        float* cd = g_cs + (epoch & 1) * 6144 + g * 384 + bc * 8;
        red_add4(cd, s[0], s[1], s[2], s[3]);
        red_add4(cd + 4, s[4], s[5], s[6], s[7]);
        nbar<2, 96>();
        if (ht == 32) { release2(bar + B_CSFREE + cr * 8); flag_add(&g_csflag[g].v); }
      }
      if (warp == 1) {
        if (lane >= 27) {
          const CUtensorMap* tm = lane == 27 ? &tm_o : lane == 28 ? &tm_wB : lane == 29 ? &tm_woA : lane == 30 ? &tm_woB : &tm_x;
          asm volatile("prefetch.tensormap [%0];" ::"l"(tm) : "memory");
        }
        if (lane == 0) {
#pragma unroll 1
          for (int e = 0;; ++e) {
            if (e > 0 && e < NLAYERS) {
              mbar_wait(bar + B_XH0, (e - 1) & 1);
              flag_set(g_xf + rb * 32 + 2 * g, xbase + e + 1);
            }
            mbar_wait(bar + B_XDONE, e & 1);
            PROFT(e < 4, 64 + e * 16 + 4);
            if (e == NLAYERS) {
              if (blockIdx.x == 0) g_epoch = epoch + 1;
              break;
            }
            PROFT(e < 4, 64 + e * 16 + 5);
            flag_set(g_xf + rb * 32 + 2 * g + 1, xbase + e + 1);
            PROFT(e < 4, 64 + e * 16 + 7);
            if ((e & 1) == 0) {
              float* kvl = g_kv + ((size_t)((epoch & 1) * 2 + (e >> 1)) * 8 + g) * 8448;
#pragma unroll 1
              for (int hp = 0; hp < 2; ++hp) {
                mbar_wait(bar + B_KVDONE - hp * 32, (e >> 1) & 1);
                bulk_red_add(kvl + hp * 4096, sb + (3 + hp) * SLOT, 16384);
                bulk_red_add(kvl + 8192 + hp * 128, sb + SM_AP + hp * 512, 512);
                bulk_commit();
                PROFT(e < 4, 64 + e * 16 + 6);
                bulk_wait0();
                PROFT(e < 4, 64 + e * 16 + 10);
                fence_async_all();
                flag_add(&g_kvflag[hp * 8 + g].v);
              }
            }
            mbar_wait(bar + B_OH1, e & 1);
            flag_set(g_of + rb * 32 + 2 * g, xbase + e + 1);
            PROFT(e < 4, 64 + e * 16 + 9);
            mbar_wait(bar + B_ODONE, e & 1);
            PROFT(e < 4, 64 + e * 16 + 8);
            flag_set(g_of + rb * 32 + 2 * g + 1, xbase + e + 1);
            release2(bar + B_OF);
            PROFT(e < 4, 64 + e * 16 + 11);
          }
        }
      } else {
        const int h2 = threadIdx.x - 64;
        if (h2 == 0) l2_prefetch(woA + (size_t)blockIdx.x * 8192, 16384);
        if (h2 == 32) l2_prefetch(woB + (size_t)blockIdx.x * 8192, 16384);
        const float* cs = g_cs + (epoch & 1) * 6144;
#pragma unroll 1
        for (int layer = 0; layer < NLAYERS; ++layer) {
          if (layer < 2) {
            if (lane == 0) flag_wait_slow(&g_csflag[layer * 8 + g].v, cbase + 16u);
            __syncwarp();
#pragma unroll 1
            for (int c4 = h2; c4 < 96; c4 += 64) {
              const float4 a = __ldcg(reinterpret_cast<const float4*>(cs + layer * 3072 + g * 384 + c4 * 4));
              const float av[4] = {a.x, a.y, a.z, a.w};
#pragma unroll
              for (int j = 0; j < 4; ++j) {
                const float c1 = bf16r(av[j]), c2 = bf16r(av[j] - c1), c3 = (av[j] - c1) - c2;
                sts128(sb + SM_BP + layer * 6144 + (c4 * 4 + j) * 16, make_uint4(pack_bf16(c1, c2), pack_bf16(c3, 0.f), 0u, 0u));
              }
            }
            asm volatile("cp.async.wait_all;" ::: "memory");
            fence_async_smem();
            nbar<5, 64>();
            if (h2 == 0) mbar_arrive(bar + (layer ? B_CS2 : B_CS));
            PROFT(h2 == 0, 64 + layer * 16 + 12);
          }
          const bool hal = (layer & 1) && rb > 0;
          {
            uint32_t rdy = 0u;
            src_wait<256>(g_xf + rb * 32, xbase + layer + 1, 0xAAAAu, rdy, lane);
            rdy = 0u;
            if (hal) src_wait<256>(g_xf + (rb - 1) * 32, xbase + layer + 1, 0xAAAAu, rdy, lane);
          }
#pragma unroll 1
          for (int r = h2 + (hal ? 0 : 16); r < 144; r += 64) {
            const float2* sp = g_stats + (layer & 1) * 8 * S_ + (m0 - 16 + r);
            float2 u[8];
#pragma unroll
            for (int i = 0; i < 8; ++i) u[i] = __ldcg(sp + i * S_);
            const float sum = ((u[0].x + u[1].x) + (u[2].x + u[3].x)) + ((u[4].x + u[5].x) + (u[6].x + u[7].x));
            const float sq = ((u[0].y + u[1].y) + (u[2].y + u[3].y)) + ((u[4].y + u[5].y) + (u[6].y + u[7].y));
            const float mean = sum * (1.f / D_);
            const float var = fmaxf(fmaf(-sum, mean, sq) * (1.f / D_), 0.f);
            const float sd = bf16r(sqrtf(bf16r(bf16r(var) + 1e-5f)));
            sts_f(sb + SM_RS + r * 4, 1.f / sd);
            if (r >= 16) {
              const float hm = -0.5f * bf16r(mean);
              sts16(sb + SM_SD + (r - 16) * 64 + ((r >> 1) & 3) * 16, __float_as_uint(sd) >> 16);
              sts128(sb + SM_AP + (r - 16) * 16, make_uint4(pack_bf16(hm, hm), pack_bf16(hm, 0.f), 0u, 0u));
            }
          }
          fence_async_smem();
          nbar<5, 64>();
          if (h2 == 0) {
            mbar_arrive(bar + B_STAT);
            PROFT(true, 64 + layer * 16 + 14);
          }
          __syncwarp();
          if (warp == 3) {
            wo_w(__shfl_sync(0xffffffffu, layer, 0));
          } else if (!(layer & 1)) {
            if (lane == 0) {
#pragma unroll 1
              for (int hp = 0; hp < 2; ++hp) {
                mbar_wait(bar + B_KVDONE - hp * 32, (layer >> 1) & 1);
                kv_fetch(layer, hp);
                PROFT(hp == 0, 64 + layer * 16 + 15);
              }
            }
            __syncwarp();
          }
          if (layer == 0 && warp == 2) {
#pragma unroll 1
            for (int wi = 0; wi < 6; ++wi) {
              float sB[8];
              colsum_load(wB, rb, g, wi, lane, sb + SM_BP + 6144, sB);
              colsum_red(g_cs + (epoch & 1) * 6144 + 3072, g, wi, lane, sB);
            }
            __syncwarp();
            if (lane == 0) flag_add(&g_csflag[8 + g].v);
            PROFT(h2 == 0, 64 + 13);
          }
        }
      }
    }
    __syncwarp();
    asm volatile("barrier.cluster.arrive.relaxed.aligned;\nbarrier.cluster.wait.aligned;\n" ::: "memory");
  } else {
    if (lane < 8 && threadIdx.x >= 131 && warp != 5) {
      const int i = (warp - 4) * 8 + lane;
      mbar_init(bar + i * 8, i < 32 ? 1u << ((BAR_CNT >> (2 * i)) & 3) : i < 48 ? 1u : (i == 59 || i == 60) ? 16u : i < 63 ? 4u : 8u);
      asm volatile("fence.mbarrier_init.release.cluster;" ::: "memory");
    }
    __syncwarp();
    asm volatile("barrier.cluster.arrive.relaxed.aligned;" ::: "memory");
    asm volatile("setmaxnreg.inc.sync.aligned.u32 232;");
    cluster_wait();
    PROFT(threadIdx.x == 128, 0);
    Ctx c; c.sb = sb; c.g = g; c.rb = rb; c.isum = isum0 + cr; c.cu = warp - 4; c.out = out;
    consumer(c);
    asm volatile("bar.warp.sync 0xffffffff;\nbarrier.cluster.arrive.relaxed.aligned;\nbarrier.cluster.wait.aligned;\n" ::: "memory");
  }
}

typedef CUresult (*PFN_encodeTiled)(CUtensorMap*, CUtensorMapDataType, cuuint32_t, void*, const cuuint64_t*, const cuuint64_t*,
                                    const cuuint32_t*, const cuuint32_t*, CUtensorMapInterleave, CUtensorMapSwizzle,
                                    CUtensorMapL2promotion, CUtensorMapFloatOOBfill);

static CUtensorMap make_map(PFN_encodeTiled enc, const void* ptr, uint64_t cols, uint64_t rows, uint32_t box_c, uint32_t box_r, uint32_t nb = 1) {
  CUtensorMap m;
  cuuint64_t dims[3] = {nb > 1 ? box_c : cols, rows, cols / box_c};
  cuuint64_t strides[2] = {cols * 2, box_c * 2};
  cuuint32_t box[3] = {box_c, box_r, nb};
  cuuint32_t es[3] = {1, 1, 1};
  CUresult r = enc(&m, CU_TENSOR_MAP_DATA_TYPE_BFLOAT16, nb > 1 ? 3 : 2, const_cast<void*>(ptr), dims, strides, box, es, CU_TENSOR_MAP_INTERLEAVE_NONE,
      CU_TENSOR_MAP_SWIZZLE_128B, CU_TENSOR_MAP_L2_PROMOTION_L2_256B, CU_TENSOR_MAP_FLOAT_OOB_FILL_NONE);
  (void)r;
  return m;
}

extern "C" void kernel_launch(void* const* d_in, const int* in_sizes, int n_in, void* d_out, int out_size) {
  const bf16* A_x = (const bf16*)d_in[0];
  const bf16* A_wqkv = (const bf16*)d_in[1];
  const bf16* A_wphi = (const bf16*)d_in[2];
  const bf16* A_wo = (const bf16*)d_in[3];
  const bf16* B_wqkv = (const bf16*)d_in[5];
  const bf16* B_wo = (const bf16*)d_in[6];
  bf16* out = (bf16*)d_out;

  static PFN_encodeTiled enc = nullptr;
  static bf16 *p_x, *p_o;
  if (!enc) {
    void* fn = nullptr; cudaDriverEntryPointQueryResult qr;
    cudaGetDriverEntryPoint("cuTensorMapEncodeTiled", &fn, cudaEnableDefault, &qr);
    enc = (PFN_encodeTiled)fn;
    cudaGetSymbolAddress((void**)&p_x, g_x);
    cudaGetSymbolAddress((void**)&p_o, g_o);
    cudaFuncSetAttribute(mega_kernel, cudaFuncAttributeMaxDynamicSharedMemorySize, SM_TOTAL);
  }
  CUtensorMap tm_x0 = make_map(enc, A_x, 1024, 2048, 64, 128);
  CUtensorMap tm_x = make_map(enc, p_x, 1024, 2048, 64, 128);
  CUtensorMap tm_o = make_map(enc, p_o, 1024, 2048, 64, 128);
  CUtensorMap tm_wA = make_map(enc, A_wqkv, 3072, 1024, 64, 64);
  CUtensorMap tm_wB = make_map(enc, B_wqkv, 3072, 1024, 64, 64);
  CUtensorMap tm_woA = make_map(enc, A_wo, 1024, 1024, 64, 64);
  CUtensorMap tm_woB = make_map(enc, B_wo, 1024, 1024, 64, 64);
  mega_kernel<<<128, 384, SM_TOTAL, cudaStreamPerThread>>>(tm_x0, tm_x, tm_o, tm_wA, tm_wB, tm_woA, tm_woB,
                                                           A_wqkv, B_wqkv, A_wo, B_wo, A_wphi, out);
}
```

```cpp
#include <cuda_runtime.h>
#include <cuda_bf16.h>
#include <cuda.h>
#include <stdint.h>

typedef __nv_bfloat16 bf16;

constexpr int S_ = 2048, D_ = 1024;

struct __align__(128) Flag { unsigned int v; unsigned int pad[31]; };
__device__ __align__(1024) bf16 g_x[S_ * D_];
__device__ __align__(1024) bf16 g_o[S_ * D_];
__device__ __align__(1024) uint4 g_halo[2 * 2 * 128 * 512];
__device__ __align__(1024) float g_kv[8 * 2 * 8448];
__device__ __align__(1024) float2 g_stats[4 * S_];
__device__ __align__(1024) float g_cs[2 * 2 * 3072];
__device__ Flag g_kvflag[16], g_csflag[16];
__device__ __align__(128) unsigned int g_xf[16 * 32], g_of[16 * 32];
__device__ unsigned int g_epoch, g_err;
#define PROFT(cond, idx) asm volatile("" ::: "memory")

__device__ __forceinline__ uint32_t smem_u32(const void* p) { return (uint32_t)__cvta_generic_to_shared(p); }
__device__ __forceinline__ void mbar_init(uint32_t bar, uint32_t count) {
  asm volatile("mbarrier.init.shared::cta.b64 [%0], %1;" ::"r"(bar), "r"(count) : "memory");
}
__device__ __forceinline__ void mbar_expect_tx(uint32_t bar, uint32_t bytes) {
  asm volatile("mbarrier.arrive.expect_tx.shared::cta.b64 _, [%0], %1;" ::"r"(bar), "r"(bytes) : "memory");
}
__device__ __forceinline__ void mbar_arrive(uint32_t bar) {
  asm volatile("mbarrier.arrive.shared::cta.b64 _, [%0];" ::"r"(bar) : "memory");
}
__device__ __forceinline__ bool mbar_try_wait(uint32_t bar, uint32_t parity) {
  uint32_t ok;
  asm volatile("{\n.reg .pred p;\nmbarrier.try_wait.parity.shared::cta.b64 p, [%1], %2;\nselp.b32 %0, 1, 0, p;\n}\n"
               : "=r"(ok) : "r"(bar), "r"(parity) : "memory");
  return ok != 0;
}
__device__ __forceinline__ bool mbar_test_wait(uint32_t bar, uint32_t parity) {
  uint32_t ok;
  asm volatile("{\n.reg .pred p;\nmbarrier.test_wait.parity.shared::cta.b64 p, [%1], %2;\nselp.b32 %0, 1, 0, p;\n}\n"
               : "=r"(ok) : "r"(bar), "r"(parity) : "memory");
  return ok != 0;
}
__device__ __forceinline__ uint64_t gtimer() {
  uint64_t t; asm volatile("mov.u64 %0, %globaltimer;" : "=l"(t)); return t;
}
__device__ __forceinline__ void mbar_wait(uint32_t bar, uint32_t parity) {
  uint32_t n = 0;
#pragma unroll 1
  while (!mbar_try_wait(bar, parity)) {
    if (++n > (1u << 22)) { g_err = 1u; break; }
  }
}
__device__ __forceinline__ unsigned int ld_acquire(const unsigned int* p) {
  unsigned int v; asm volatile("ld.acquire.gpu.global.u32 %0, [%1];" : "=r"(v) : "l"(p) : "memory"); return v;
}
__device__ __forceinline__ void flag_add(unsigned int* p) {
  asm volatile("red.release.gpu.global.add.u32 [%0], 1;" ::"l"(p) : "memory");
}
__device__ __forceinline__ void flag_set(unsigned int* p, unsigned int v) {
  asm volatile("st.release.gpu.global.u32 [%0], %1;" ::"l"(p), "r"(v) : "memory");
}
template <int SLEEP>
__device__ __forceinline__ void src_wait(const unsigned int* f, unsigned int target, uint32_t need, uint32_t& ready, int lane) {
  uint32_t n = 0;
#pragma unroll 1
  while ((ready & need) != need) {
    const unsigned int v = ld_acquire(f + (lane & 15));
    ready = __ballot_sync(0xffffffffu, (int)(v - target) >= 0);
    if (SLEEP) { if ((ready & need) != need) __nanosleep(SLEEP); }
    if (++n > (1u << 20)) { g_err = 3u; break; }
  }
  __syncwarp();
}
__device__ __forceinline__ unsigned int ld_relaxed(const unsigned int* p) {
  unsigned int v; asm volatile("ld.relaxed.gpu.global.u32 %0, [%1];" : "=r"(v) : "l"(p) : "memory"); return v;
}
__device__ __forceinline__ uint4 ld_relaxed4(const uint4* p) {
  uint4 v; asm volatile("ld.relaxed.gpu.global.v4.u32 {%0,%1,%2,%3}, [%4];" : "=r"(v.x), "=r"(v.y), "=r"(v.z), "=r"(v.w) : "l"(p) : "memory"); return v;
}
__device__ __forceinline__ void st_relaxed4(uint4* p, uint32_t a, uint32_t b, uint32_t c, uint32_t d) {
  asm volatile("st.relaxed.gpu.global.v4.u32 [%0], {%1,%2,%3,%4};" ::"l"(p), "r"(a), "r"(b), "r"(c), "r"(d) : "memory");
}
template <int SLEEP>
__device__ __forceinline__ void flag_wait_t(const unsigned int* p, unsigned int target) {
  uint32_t n = 0;
#pragma unroll 1
  while ((int)(ld_acquire(p) - target) < 0) {
    if (SLEEP) __nanosleep(SLEEP);
    if (++n > (1u << 20)) { g_err = 2u; break; }
  }
}
__device__ __forceinline__ void flag_wait(const unsigned int* p, unsigned int target) { flag_wait_t<0>(p, target); }
__device__ __forceinline__ void flag_wait_slow(const unsigned int* p, unsigned int target) { flag_wait_t<256>(p, target); }
__device__ __forceinline__ void tma_load_2d(uint32_t dst, const CUtensorMap* tm, int c0, int c1, uint32_t bar) {
  asm volatile("cp.async.bulk.tensor.2d.shared::cluster.global.mbarrier::complete_tx::bytes [%0], [%1, {%2, %3}], [%4];"
               ::"r"(dst), "l"(tm), "r"(c0), "r"(c1), "r"(bar) : "memory");
}
__device__ __forceinline__ void tma_load_2d_mc(uint32_t dst, const CUtensorMap* tm, int c0, int c1, uint32_t bar, uint16_t mask) {
  asm volatile("cp.async.bulk.tensor.2d.shared::cluster.global.mbarrier::complete_tx::bytes.multicast::cluster [%0], [%1, {%2, %3}], [%4], %5;"
               ::"r"(dst), "l"(tm), "r"(c0), "r"(c1), "r"(bar), "h"(mask) : "memory");
}
__device__ __forceinline__ void mbar_wait_u(uint32_t bar, uint32_t parity) {
  uint32_t n = 0;
#pragma unroll 1
  while (!__all_sync(0xffffffffu, mbar_try_wait(bar, parity))) {
    if (++n > (1u << 22)) { g_err = 1u; break; }
  }
}
__device__ __forceinline__ void expect_tx_e(uint32_t bar, uint32_t bytes) {
  asm volatile("{\n.reg .pred p;\nelect.sync _|p, 0xffffffff;\n@p mbarrier.arrive.expect_tx.shared::cta.b64 _, [%0], %1;\n}\n" ::"r"(bar), "r"(bytes) : "memory");
}
__device__ __forceinline__ void tma_2d_e(uint32_t dst, const CUtensorMap* tm, int c0, int c1, uint32_t bar) {
  asm volatile("{\n.reg .pred p;\nelect.sync _|p, 0xffffffff;\n"
               "@p cp.async.bulk.tensor.2d.shared::cluster.global.mbarrier::complete_tx::bytes [%0], [%1, {%2, %3}], [%4];\n}\n"
               ::"r"(dst), "l"(tm), "r"(c0), "r"(c1), "r"(bar) : "memory");
}
__device__ __forceinline__ void tma_2d_mc_e(uint32_t dst, const CUtensorMap* tm, int c0, int c1, uint32_t bar) {
  asm volatile("{\n.reg .pred p;\nelect.sync _|p, 0xffffffff;\n"
               "@p cp.async.bulk.tensor.2d.shared::cluster.global.mbarrier::complete_tx::bytes.multicast::cluster [%0], [%1, {%2, %3}], [%4], %5;\n}\n"
               ::"r"(dst), "l"(tm), "r"(c0), "r"(c1), "r"(bar), "h"((uint16_t)3) : "memory");
}
__device__ __forceinline__ void tma_pf_e(const CUtensorMap* tm, int c0, int c1) {
  asm volatile("{\n.reg .pred p;\nelect.sync _|p, 0xffffffff;\n"
               "@p cp.async.bulk.prefetch.tensor.2d.L2.global.tile [%0, {%1, %2}];\n}\n" ::"l"(tm), "r"(c0), "r"(c1) : "memory");
}
__device__ __forceinline__ void tma_2d_to_e(uint32_t dst, const CUtensorMap* tm, int c0, int c1, uint32_t bar, uint32_t mask) {
  asm volatile("{\n.reg .pred p;\nelect.sync _|p, 0xffffffff;\n"
               "@p cp.async.bulk.tensor.2d.shared::cluster.global.mbarrier::complete_tx::bytes.multicast::cluster [%0], [%1, {%2, %3}], [%4], %5;\n}\n"
               ::"r"(dst), "l"(tm), "r"(c0), "r"(c1), "r"(bar), "h"((uint16_t)mask) : "memory");
}
__device__ __forceinline__ void tma_3d_mc_e(uint32_t dst, const CUtensorMap* tm, int c1, int c2, uint32_t bar) {
  asm volatile("{\n.reg .pred p;\nelect.sync _|p, 0xffffffff;\n"
               "@p cp.async.bulk.tensor.3d.shared::cluster.global.mbarrier::complete_tx::bytes.multicast::cluster [%0], [%1, {%6, %2, %3}], [%4], %5;\n}\n"
               ::"r"(dst), "l"(tm), "r"(c1), "r"(c2), "r"(bar), "h"((uint16_t)3), "r"(0) : "memory");
}
__device__ __forceinline__ uint32_t poll_flags(const unsigned int* f, unsigned int target, int lane) {
  const unsigned int v = ld_acquire(f + (lane & 15));
  const uint32_t r = __ballot_sync(0xffffffffu, (int)(v - target) >= 0);
  __syncwarp();
  return r;
}
__device__ __forceinline__ void mbar_arrive_cluster(uint32_t local_bar, uint32_t rank) {
  asm volatile("{\n.reg .b32 ra;\nmapa.shared::cluster.u32 ra, %0, %1;\nmbarrier.arrive.shared::cluster.b64 _, [ra];\n}\n"
               ::"r"(local_bar), "r"(rank) : "memory");
}
__device__ __forceinline__ void release2(uint32_t bar) { mbar_arrive_cluster(bar, 0); mbar_arrive_cluster(bar, 1); }
__device__ __forceinline__ void tma_store_2d(const CUtensorMap* tm, uint32_t src, int c0, int c1) {
  asm volatile("cp.async.bulk.tensor.2d.global.shared::cta.bulk_group [%0, {%2, %3}], [%1];"
               ::"l"(tm), "r"(src), "r"(c0), "r"(c1) : "memory");
}
__device__ __forceinline__ void bulk_store(void* dst, uint32_t src, uint32_t bytes) {
  asm volatile("cp.async.bulk.global.shared::cta.bulk_group [%0], [%1], %2;" ::"l"(dst), "r"(src), "r"(bytes) : "memory");
}
__device__ __forceinline__ void bulk_load(uint32_t dst, const void* src, uint32_t bytes, uint32_t bar) {
  asm volatile("cp.async.bulk.shared::cluster.global.mbarrier::complete_tx::bytes [%0], [%1], %2, [%3];" ::"r"(dst), "l"(src), "r"(bytes), "r"(bar) : "memory");
}
__device__ __forceinline__ void bulk_red_add(void* dst, uint32_t src, uint32_t bytes) {
  asm volatile("cp.reduce.async.bulk.global.shared::cta.bulk_group.add.f32 [%0], [%1], %2;" ::"l"(dst), "r"(src), "r"(bytes) : "memory");
}
__device__ __forceinline__ void bulk_commit() { asm volatile("cp.async.bulk.commit_group;" ::: "memory"); }
__device__ __forceinline__ void bulk_wait0() { asm volatile("cp.async.bulk.wait_group 0;" ::: "memory"); }
__device__ __forceinline__ void fence_async_smem() { asm volatile("fence.proxy.async.shared::cta;" ::: "memory"); }
__device__ __forceinline__ void fence_async_all() { asm volatile("fence.proxy.async.global;" ::: "memory"); }
__device__ __forceinline__ void wgmma_fence() { asm volatile("wgmma.fence.sync.aligned;" ::: "memory"); }
__device__ __forceinline__ void wgmma_commit() { asm volatile("wgmma.commit_group.sync.aligned;" ::: "memory"); }
template <int N> __device__ __forceinline__ void wgmma_wait() { asm volatile("wgmma.wait_group.sync.aligned %0;" ::"n"(N) : "memory"); }
__device__ __forceinline__ void cluster_arrive() { asm volatile("barrier.cluster.arrive.release.aligned;" ::: "memory"); }
__device__ __forceinline__ void cluster_wait() { asm volatile("barrier.cluster.wait.acquire.aligned;" ::: "memory"); }
template <int ID, int N> __device__ __forceinline__ void nbar() { asm volatile("bar.sync %0, %1;" ::"n"(ID), "n"(N) : "memory"); }
__device__ __forceinline__ uint64_t make_desc(uint32_t addr, uint32_t lbo_bytes, uint32_t sbo_bytes) {
  uint64_t d = 0;
  d |= (uint64_t)((addr & 0x3FFFF) >> 4);
  d |= (uint64_t)((lbo_bytes >> 4) & 0x3FFF) << 16;
  d |= (uint64_t)((sbo_bytes >> 4) & 0x3FFF) << 32;
  d |= (uint64_t)1 << 62;
  return d;
}
__device__ __forceinline__ uint64_t desc64(uint32_t lo, uint32_t hi) { return (uint64_t)lo | ((uint64_t)hi << 32); }
__device__ __forceinline__ uint32_t pack_bf16(float lo, float hi) {
  uint32_t r; asm("cvt.rn.bf16x2.f32 %0, %1, %2;" : "=r"(r) : "f"(hi), "f"(lo)); return r;
}
__device__ __forceinline__ uint32_t mul_bf16x2(uint32_t a, uint32_t s, bool hi) {
  __nv_bfloat162 x = *reinterpret_cast<__nv_bfloat162*>(&a), y = *reinterpret_cast<__nv_bfloat162*>(&s);
  x = __hmul2(x, hi ? __high2bfloat162(y) : __low2bfloat162(y));
  return *reinterpret_cast<uint32_t*>(&x);
}
__device__ __forceinline__ float bf16r(float x) { return __bfloat162float(__float2bfloat16_rn(x)); }
__device__ __forceinline__ float bf_lo(uint32_t u) { return __uint_as_float(u << 16); }
__device__ __forceinline__ float bf_hi(uint32_t u) { return __uint_as_float(u & 0xFFFF0000u); }
__device__ __forceinline__ float ex2(float x) { float r; asm("ex2.approx.ftz.f32 %0, %1;" : "=f"(r) : "f"(x)); return r; }
__device__ __forceinline__ float rcp(float x) { float r; asm("rcp.approx.ftz.f32 %0, %1;" : "=f"(r) : "f"(x)); return r; }
__device__ __forceinline__ void mma_bf16(float (&d)[4], uint32_t a0, uint32_t a1, uint32_t a2, uint32_t a3, uint32_t b0, uint32_t b1) {
  asm("mma.sync.aligned.m16n8k16.row.col.f32.bf16.bf16.f32 {%0,%1,%2,%3}, {%4,%5,%6,%7}, {%8,%9}, {%0,%1,%2,%3};"
               : "+f"(d[0]), "+f"(d[1]), "+f"(d[2]), "+f"(d[3]) : "r"(a0), "r"(a1), "r"(a2), "r"(a3), "r"(b0), "r"(b1));
}
__device__ __forceinline__ void ldsm_x4(uint32_t& r0, uint32_t& r1, uint32_t& r2, uint32_t& r3, uint32_t addr) {
  asm volatile("ldmatrix.sync.aligned.m8n8.x4.shared.b16 {%0,%1,%2,%3}, [%4];"
               : "=r"(r0), "=r"(r1), "=r"(r2), "=r"(r3) : "r"(addr) : "memory");
}
__device__ __forceinline__ void ldsm_x4_t(uint32_t& r0, uint32_t& r1, uint32_t& r2, uint32_t& r3, uint32_t addr) {
  asm volatile("ldmatrix.sync.aligned.m8n8.x4.trans.shared.b16 {%0,%1,%2,%3}, [%4];"
               : "=r"(r0), "=r"(r1), "=r"(r2), "=r"(r3) : "r"(addr) : "memory");
}
__device__ __forceinline__ void ldsm_x2_t(uint32_t& r0, uint32_t& r1, uint32_t addr) {
  asm volatile("ldmatrix.sync.aligned.m8n8.x2.trans.shared.b16 {%0,%1}, [%2];"
               : "=r"(r0), "=r"(r1) : "r"(addr) : "memory");
}
__device__ __forceinline__ void stsm_x4(uint32_t addr, uint32_t r0, uint32_t r1, uint32_t r2, uint32_t r3) {
  asm volatile("stmatrix.sync.aligned.m8n8.x4.shared.b16 [%0], {%1,%2,%3,%4};"
               ::"r"(addr), "r"(r0), "r"(r1), "r"(r2), "r"(r3) : "memory");
}
__device__ __forceinline__ void stsm_x4_p(bool on, uint32_t addr, uint32_t r0, uint32_t r1, uint32_t r2, uint32_t r3) {
  asm volatile("{\n.reg .pred p;\nsetp.ne.b32 p, %5, 0;\n@p stmatrix.sync.aligned.m8n8.x4.shared.b16 [%0], {%1,%2,%3,%4};\n}\n"
               ::"r"(addr), "r"(r0), "r"(r1), "r"(r2), "r"(r3), "r"((int)on) : "memory");
}
__device__ __forceinline__ float2 lds_f2(uint32_t addr) {
  float2 v; asm volatile("ld.shared.v2.f32 {%0,%1}, [%2];" : "=f"(v.x), "=f"(v.y) : "r"(addr) : "memory"); return v;
}
__device__ __forceinline__ uint4 lds128(uint32_t addr) {
  uint4 v; asm volatile("ld.shared.v4.b32 {%0,%1,%2,%3}, [%4];" : "=r"(v.x), "=r"(v.y), "=r"(v.z), "=r"(v.w) : "r"(addr) : "memory"); return v;
}
__device__ __forceinline__ void sts128(uint32_t addr, uint4 v) {
  asm volatile("st.shared.v4.b32 [%0], {%1,%2,%3,%4};" ::"r"(addr), "r"(v.x), "r"(v.y), "r"(v.z), "r"(v.w) : "memory");
}
__device__ __forceinline__ float lds_f(uint32_t addr) {
  float v; asm volatile("ld.shared.f32 %0, [%1];" : "=f"(v) : "r"(addr) : "memory"); return v;
}
__device__ __forceinline__ uint32_t lds_vol(uint32_t addr) {
  uint32_t v; asm volatile("ld.volatile.shared.u32 %0, [%1];" : "=r"(v) : "r"(addr) : "memory"); return v;
}
__device__ __forceinline__ void sts16(uint32_t addr, uint32_t v) {
  asm volatile("st.shared.u16 [%0], %1;" ::"r"(addr), "h"((unsigned short)v) : "memory");
}
__device__ __forceinline__ void nbar_dyn(int id, int n) { asm volatile("bar.sync %0, %1;" ::"r"(id), "r"(n) : "memory"); }
__device__ __forceinline__ uint64_t make_desc_ns(uint32_t addr, uint32_t lbo_bytes, uint32_t sbo_bytes) {
  return (uint64_t)((addr & 0x3FFFF) >> 4) | ((uint64_t)(lbo_bytes >> 4) << 16) | ((uint64_t)(sbo_bytes >> 4) << 32);
}
__device__ __forceinline__ void sts_f(uint32_t addr, float v) { asm volatile("st.shared.f32 [%0], %1;" ::"r"(addr), "f"(v) : "memory"); }
__device__ __forceinline__ void sts64(uint32_t addr, uint32_t a, uint32_t b) {
  asm volatile("st.shared.v2.b32 [%0], {%1,%2};" ::"r"(addr), "r"(a), "r"(b) : "memory");
}
__device__ __forceinline__ void sts_f2(uint32_t addr, float a, float b) {
  asm volatile("st.shared.v2.f32 [%0], {%1,%2};" ::"r"(addr), "f"(a), "f"(b) : "memory");
}
__device__ __forceinline__ void red_add2(float* p, float a, float b) {
  asm volatile("red.global.add.v2.f32 [%0], {%1,%2};" ::"l"(p), "f"(a), "f"(b) : "memory");
}
__device__ __forceinline__ void red_add4(float* p, float a, float b, float c, float d) {
  asm volatile("red.global.add.v4.f32 [%0], {%1,%2,%3,%4};" ::"l"(p), "f"(a), "f"(b), "f"(c), "f"(d) : "memory");
}
__device__ __forceinline__ void red_add1(float* p, float a) {
  asm volatile("red.global.add.f32 [%0], %1;" ::"l"(p), "f"(a) : "memory");
}
__device__ __forceinline__ void l2_prefetch(const void* p, uint32_t bytes) {
  asm volatile("cp.async.bulk.prefetch.L2.global [%0], %1;" ::"l"(p), "r"(bytes) : "memory");
}

__device__ __forceinline__ void wgmma_n256(float (&d)[192], uint64_t da, uint64_t db, int scale_d) {
  asm volatile("{\n.reg .pred p;\nsetp.ne.b32 p, %130, 0;\n"
    "wgmma.mma_async.sync.aligned.m64n256k16.f32.bf16.bf16 {%0, %1, %2, %3, %4, %5, %6, %7, %8, %9, %10, %11, %12, %13, %14, %15, %16, %17, %18, %19, %20, %21, %22, %23, %24, %25, %26, %27, %28, %29, %30, %31, %32, %33, %34, %35, %36, %37, %38, %39, %40, %41, %42, %43, %44, %45, %46, %47, %48, %49, %50, %51, %52, %53, %54, %55, %56, %57, %58, %59, %60, %61, %62, %63, %64, %65, %66, %67, %68, %69, %70, %71, %72, %73, %74, %75, %76, %77, %78, %79, %80, %81, %82, %83, %84, %85, %86, %87, %88, %89, %90, %91, %92, %93, %94, %95, %96, %97, %98, %99, %100, %101, %102, %103, %104, %105, %106, %107, %108, %109, %110, %111, %112, %113, %114, %115, %116, %117, %118, %119, %120, %121, %122, %123, %124, %125, %126, %127}, %128, %129, p, 1, 1, 0, 1;\n}\n"
    : "+f"(d[0]), "+f"(d[1]), "+f"(d[2]), "+f"(d[3]), "+f"(d[4]), "+f"(d[5]), "+f"(d[6]), "+f"(d[7]), "+f"(d[8]), "+f"(d[9]), "+f"(d[10]), "+f"(d[11]), "+f"(d[12]), "+f"(d[13]), "+f"(d[14]), "+f"(d[15]), "+f"(d[16]), "+f"(d[17]), "+f"(d[18]), "+f"(d[19]), "+f"(d[20]), "+f"(d[21]), "+f"(d[22]), "+f"(d[23]), "+f"(d[24]), "+f"(d[25]), "+f"(d[26]), "+f"(d[27]), "+f"(d[28]), "+f"(d[29]), "+f"(d[30]), "+f"(d[31]), "+f"(d[32]), "+f"(d[33]), "+f"(d[34]), "+f"(d[35]), "+f"(d[36]), "+f"(d[37]), "+f"(d[38]), "+f"(d[39]), "+f"(d[40]), "+f"(d[41]), "+f"(d[42]), "+f"(d[43]), "+f"(d[44]), "+f"(d[45]), "+f"(d[46]), "+f"(d[47]), "+f"(d[48]), "+f"(d[49]), "+f"(d[50]), "+f"(d[51]), "+f"(d[52]), "+f"(d[53]), "+f"(d[54]), "+f"(d[55]), "+f"(d[56]), "+f"(d[57]), "+f"(d[58]), "+f"(d[59]), "+f"(d[60]), "+f"(d[61]), "+f"(d[62]), "+f"(d[63]), "+f"(d[64]), "+f"(d[65]), "+f"(d[66]), "+f"(d[67]), "+f"(d[68]), "+f"(d[69]), "+f"(d[70]), "+f"(d[71]), "+f"(d[72]), "+f"(d[73]), "+f"(d[74]), "+f"(d[75]), "+f"(d[76]), "+f"(d[77]), "+f"(d[78]), "+f"(d[79]), "+f"(d[80]), "+f"(d[81]), "+f"(d[82]), "+f"(d[83]), "+f"(d[84]), "+f"(d[85]), "+f"(d[86]), "+f"(d[87]), "+f"(d[88]), "+f"(d[89]), "+f"(d[90]), "+f"(d[91]), "+f"(d[92]), "+f"(d[93]), "+f"(d[94]), "+f"(d[95]), "+f"(d[96]), "+f"(d[97]), "+f"(d[98]), "+f"(d[99]), "+f"(d[100]), "+f"(d[101]), "+f"(d[102]), "+f"(d[103]), "+f"(d[104]), "+f"(d[105]), "+f"(d[106]), "+f"(d[107]), "+f"(d[108]), "+f"(d[109]), "+f"(d[110]), "+f"(d[111]), "+f"(d[112]), "+f"(d[113]), "+f"(d[114]), "+f"(d[115]), "+f"(d[116]), "+f"(d[117]), "+f"(d[118]), "+f"(d[119]), "+f"(d[120]), "+f"(d[121]), "+f"(d[122]), "+f"(d[123]), "+f"(d[124]), "+f"(d[125]), "+f"(d[126]), "+f"(d[127])
    : "l"(da), "l"(db), "r"(scale_d));
}
__device__ __forceinline__ void wgmma_n128(float (&d)[192], uint64_t da, uint64_t db, int scale_d) {
  asm volatile("{\n.reg .pred p;\nsetp.ne.b32 p, %66, 0;\n"
    "wgmma.mma_async.sync.aligned.m64n128k16.f32.bf16.bf16 {%0, %1, %2, %3, %4, %5, %6, %7, %8, %9, %10, %11, %12, %13, %14, %15, %16, %17, %18, %19, %20, %21, %22, %23, %24, %25, %26, %27, %28, %29, %30, %31, %32, %33, %34, %35, %36, %37, %38, %39, %40, %41, %42, %43, %44, %45, %46, %47, %48, %49, %50, %51, %52, %53, %54, %55, %56, %57, %58, %59, %60, %61, %62, %63}, %64, %65, p, 1, 1, 0, 1;\n}\n"
    : "+f"(d[128]), "+f"(d[129]), "+f"(d[130]), "+f"(d[131]), "+f"(d[132]), "+f"(d[133]), "+f"(d[134]), "+f"(d[135]), "+f"(d[136]), "+f"(d[137]), "+f"(d[138]), "+f"(d[139]), "+f"(d[140]), "+f"(d[141]), "+f"(d[142]), "+f"(d[143]), "+f"(d[144]), "+f"(d[145]), "+f"(d[146]), "+f"(d[147]), "+f"(d[148]), "+f"(d[149]), "+f"(d[150]), "+f"(d[151]), "+f"(d[152]), "+f"(d[153]), "+f"(d[154]), "+f"(d[155]), "+f"(d[156]), "+f"(d[157]), "+f"(d[158]), "+f"(d[159]), "+f"(d[160]), "+f"(d[161]), "+f"(d[162]), "+f"(d[163]), "+f"(d[164]), "+f"(d[165]), "+f"(d[166]), "+f"(d[167]), "+f"(d[168]), "+f"(d[169]), "+f"(d[170]), "+f"(d[171]), "+f"(d[172]), "+f"(d[173]), "+f"(d[174]), "+f"(d[175]), "+f"(d[176]), "+f"(d[177]), "+f"(d[178]), "+f"(d[179]), "+f"(d[180]), "+f"(d[181]), "+f"(d[182]), "+f"(d[183]), "+f"(d[184]), "+f"(d[185]), "+f"(d[186]), "+f"(d[187]), "+f"(d[188]), "+f"(d[189]), "+f"(d[190]), "+f"(d[191])
    : "l"(da), "l"(db), "r"(scale_d));
}
__device__ __forceinline__ void wgmma_n256_k(float (&d)[192], uint64_t da, uint64_t db, int scale_d) {
  asm volatile("{\n.reg .pred p;\nsetp.ne.b32 p, %130, 0;\n"
    "wgmma.mma_async.sync.aligned.m64n256k16.f32.bf16.bf16 {%0, %1, %2, %3, %4, %5, %6, %7, %8, %9, %10, %11, %12, %13, %14, %15, %16, %17, %18, %19, %20, %21, %22, %23, %24, %25, %26, %27, %28, %29, %30, %31, %32, %33, %34, %35, %36, %37, %38, %39, %40, %41, %42, %43, %44, %45, %46, %47, %48, %49, %50, %51, %52, %53, %54, %55, %56, %57, %58, %59, %60, %61, %62, %63, %64, %65, %66, %67, %68, %69, %70, %71, %72, %73, %74, %75, %76, %77, %78, %79, %80, %81, %82, %83, %84, %85, %86, %87, %88, %89, %90, %91, %92, %93, %94, %95, %96, %97, %98, %99, %100, %101, %102, %103, %104, %105, %106, %107, %108, %109, %110, %111, %112, %113, %114, %115, %116, %117, %118, %119, %120, %121, %122, %123, %124, %125, %126, %127}, %128, %129, p, 1, 1, 0, 0;\n}\n"
    : "+f"(d[0]), "+f"(d[1]), "+f"(d[2]), "+f"(d[3]), "+f"(d[4]), "+f"(d[5]), "+f"(d[6]), "+f"(d[7]), "+f"(d[8]), "+f"(d[9]), "+f"(d[10]), "+f"(d[11]), "+f"(d[12]), "+f"(d[13]), "+f"(d[14]), "+f"(d[15]), "+f"(d[16]), "+f"(d[17]), "+f"(d[18]), "+f"(d[19]), "+f"(d[20]), "+f"(d[21]), "+f"(d[22]), "+f"(d[23]), "+f"(d[24]), "+f"(d[25]), "+f"(d[26]), "+f"(d[27]), "+f"(d[28]), "+f"(d[29]), "+f"(d[30]), "+f"(d[31]), "+f"(d[32]), "+f"(d[33]), "+f"(d[34]), "+f"(d[35]), "+f"(d[36]), "+f"(d[37]), "+f"(d[38]), "+f"(d[39]), "+f"(d[40]), "+f"(d[41]), "+f"(d[42]), "+f"(d[43]), "+f"(d[44]), "+f"(d[45]), "+f"(d[46]), "+f"(d[47]), "+f"(d[48]), "+f"(d[49]), "+f"(d[50]), "+f"(d[51]), "+f"(d[52]), "+f"(d[53]), "+f"(d[54]), "+f"(d[55]), "+f"(d[56]), "+f"(d[57]), "+f"(d[58]), "+f"(d[59]), "+f"(d[60]), "+f"(d[61]), "+f"(d[62]), "+f"(d[63]), "+f"(d[64]), "+f"(d[65]), "+f"(d[66]), "+f"(d[67]), "+f"(d[68]), "+f"(d[69]), "+f"(d[70]), "+f"(d[71]), "+f"(d[72]), "+f"(d[73]), "+f"(d[74]), "+f"(d[75]), "+f"(d[76]), "+f"(d[77]), "+f"(d[78]), "+f"(d[79]), "+f"(d[80]), "+f"(d[81]), "+f"(d[82]), "+f"(d[83]), "+f"(d[84]), "+f"(d[85]), "+f"(d[86]), "+f"(d[87]), "+f"(d[88]), "+f"(d[89]), "+f"(d[90]), "+f"(d[91]), "+f"(d[92]), "+f"(d[93]), "+f"(d[94]), "+f"(d[95]), "+f"(d[96]), "+f"(d[97]), "+f"(d[98]), "+f"(d[99]), "+f"(d[100]), "+f"(d[101]), "+f"(d[102]), "+f"(d[103]), "+f"(d[104]), "+f"(d[105]), "+f"(d[106]), "+f"(d[107]), "+f"(d[108]), "+f"(d[109]), "+f"(d[110]), "+f"(d[111]), "+f"(d[112]), "+f"(d[113]), "+f"(d[114]), "+f"(d[115]), "+f"(d[116]), "+f"(d[117]), "+f"(d[118]), "+f"(d[119]), "+f"(d[120]), "+f"(d[121]), "+f"(d[122]), "+f"(d[123]), "+f"(d[124]), "+f"(d[125]), "+f"(d[126]), "+f"(d[127])
    : "l"(da), "l"(db), "r"(scale_d));
}
__device__ __forceinline__ void wgmma_n128_k(float (&d)[192], uint64_t da, uint64_t db, int scale_d) {
  asm volatile("{\n.reg .pred p;\nsetp.ne.b32 p, %66, 0;\n"
    "wgmma.mma_async.sync.aligned.m64n128k16.f32.bf16.bf16 {%0, %1, %2, %3, %4, %5, %6, %7, %8, %9, %10, %11, %12, %13, %14, %15, %16, %17, %18, %19, %20, %21, %22, %23, %24, %25, %26, %27, %28, %29, %30, %31, %32, %33, %34, %35, %36, %37, %38, %39, %40, %41, %42, %43, %44, %45, %46, %47, %48, %49, %50, %51, %52, %53, %54, %55, %56, %57, %58, %59, %60, %61, %62, %63}, %64, %65, p, 1, 1, 0, 0;\n}\n"
    : "+f"(d[128]), "+f"(d[129]), "+f"(d[130]), "+f"(d[131]), "+f"(d[132]), "+f"(d[133]), "+f"(d[134]), "+f"(d[135]), "+f"(d[136]), "+f"(d[137]), "+f"(d[138]), "+f"(d[139]), "+f"(d[140]), "+f"(d[141]), "+f"(d[142]), "+f"(d[143]), "+f"(d[144]), "+f"(d[145]), "+f"(d[146]), "+f"(d[147]), "+f"(d[148]), "+f"(d[149]), "+f"(d[150]), "+f"(d[151]), "+f"(d[152]), "+f"(d[153]), "+f"(d[154]), "+f"(d[155]), "+f"(d[156]), "+f"(d[157]), "+f"(d[158]), "+f"(d[159]), "+f"(d[160]), "+f"(d[161]), "+f"(d[162]), "+f"(d[163]), "+f"(d[164]), "+f"(d[165]), "+f"(d[166]), "+f"(d[167]), "+f"(d[168]), "+f"(d[169]), "+f"(d[170]), "+f"(d[171]), "+f"(d[172]), "+f"(d[173]), "+f"(d[174]), "+f"(d[175]), "+f"(d[176]), "+f"(d[177]), "+f"(d[178]), "+f"(d[179]), "+f"(d[180]), "+f"(d[181]), "+f"(d[182]), "+f"(d[183]), "+f"(d[184]), "+f"(d[185]), "+f"(d[186]), "+f"(d[187]), "+f"(d[188]), "+f"(d[189]), "+f"(d[190]), "+f"(d[191])
    : "l"(da), "l"(db), "r"(scale_d));
}
__device__ __forceinline__ void wgmma_n40_tt(float (&d)[20], uint64_t da, uint64_t db, int scale_d) {
  asm volatile("{\n.reg .pred p;\nsetp.ne.b32 p, %22, 0;\n"
    "wgmma.mma_async.sync.aligned.m64n40k16.f32.bf16.bf16 {%0, %1, %2, %3, %4, %5, %6, %7, %8, %9, %10, %11, %12, %13, %14, %15, %16, %17, %18, %19}, %20, %21, p, 1, 1, 1, 1;\n}\n"
    : "+f"(d[0]), "+f"(d[1]), "+f"(d[2]), "+f"(d[3]), "+f"(d[4]), "+f"(d[5]), "+f"(d[6]), "+f"(d[7]), "+f"(d[8]), "+f"(d[9]), "+f"(d[10]), "+f"(d[11]), "+f"(d[12]), "+f"(d[13]), "+f"(d[14]), "+f"(d[15]), "+f"(d[16]), "+f"(d[17]), "+f"(d[18]), "+f"(d[19])
    : "l"(da), "l"(db), "r"(scale_d));
}
__device__ __forceinline__ void wgmma_n40_rs(float (&d)[20], const uint32_t (&a)[4], uint64_t db, int scale_d) {
  asm volatile("{\n.reg .pred p;\nsetp.ne.b32 p, %25, 0;\n"
    "wgmma.mma_async.sync.aligned.m64n40k16.f32.bf16.bf16 {%0, %1, %2, %3, %4, %5, %6, %7, %8, %9, %10, %11, %12, %13, %14, %15, %16, %17, %18, %19}, {%20, %21, %22, %23}, %24, p, 1, 1, 1;\n}\n"
    : "+f"(d[0]), "+f"(d[1]), "+f"(d[2]), "+f"(d[3]), "+f"(d[4]), "+f"(d[5]), "+f"(d[6]), "+f"(d[7]), "+f"(d[8]), "+f"(d[9]), "+f"(d[10]), "+f"(d[11]), "+f"(d[12]), "+f"(d[13]), "+f"(d[14]), "+f"(d[15]), "+f"(d[16]), "+f"(d[17]), "+f"(d[18]), "+f"(d[19])
    : "r"(a[0]), "r"(a[1]), "r"(a[2]), "r"(a[3]), "l"(db), "r"(scale_d));
}
__device__ __forceinline__ void wgmma_n256_0(float (&d)[192], uint64_t da, uint64_t db) {
  asm volatile("{\n.reg .pred p;\nsetp.ne.b32 p, 0, 0;\n"
    "wgmma.mma_async.sync.aligned.m64n256k16.f32.bf16.bf16 {%0, %1, %2, %3, %4, %5, %6, %7, %8, %9, %10, %11, %12, %13, %14, %15, %16, %17, %18, %19, %20, %21, %22, %23, %24, %25, %26, %27, %28, %29, %30, %31, %32, %33, %34, %35, %36, %37, %38, %39, %40, %41, %42, %43, %44, %45, %46, %47, %48, %49, %50, %51, %52, %53, %54, %55, %56, %57, %58, %59, %60, %61, %62, %63, %64, %65, %66, %67, %68, %69, %70, %71, %72, %73, %74, %75, %76, %77, %78, %79, %80, %81, %82, %83, %84, %85, %86, %87, %88, %89, %90, %91, %92, %93, %94, %95, %96, %97, %98, %99, %100, %101, %102, %103, %104, %105, %106, %107, %108, %109, %110, %111, %112, %113, %114, %115, %116, %117, %118, %119, %120, %121, %122, %123, %124, %125, %126, %127}, %128, %129, p, 1, 1, 0, 1;\n}\n"
    : "=f"(d[0]), "=f"(d[1]), "=f"(d[2]), "=f"(d[3]), "=f"(d[4]), "=f"(d[5]), "=f"(d[6]), "=f"(d[7]), "=f"(d[8]), "=f"(d[9]), "=f"(d[10]), "=f"(d[11]), "=f"(d[12]), "=f"(d[13]), "=f"(d[14]), "=f"(d[15]), "=f"(d[16]), "=f"(d[17]), "=f"(d[18]), "=f"(d[19]), "=f"(d[20]), "=f"(d[21]), "=f"(d[22]), "=f"(d[23]), "=f"(d[24]), "=f"(d[25]), "=f"(d[26]), "=f"(d[27]), "=f"(d[28]), "=f"(d[29]), "=f"(d[30]), "=f"(d[31]), "=f"(d[32]), "=f"(d[33]), "=f"(d[34]), "=f"(d[35]), "=f"(d[36]), "=f"(d[37]), "=f"(d[38]), "=f"(d[39]), "=f"(d[40]), "=f"(d[41]), "=f"(d[42]), "=f"(d[43]), "=f"(d[44]), "=f"(d[45]), "=f"(d[46]), "=f"(d[47]), "=f"(d[48]), "=f"(d[49]), "=f"(d[50]), "=f"(d[51]), "=f"(d[52]), "=f"(d[53]), "=f"(d[54]), "=f"(d[55]), "=f"(d[56]), "=f"(d[57]), "=f"(d[58]), "=f"(d[59]), "=f"(d[60]), "=f"(d[61]), "=f"(d[62]), "=f"(d[63]), "=f"(d[64]), "=f"(d[65]), "=f"(d[66]), "=f"(d[67]), "=f"(d[68]), "=f"(d[69]), "=f"(d[70]), "=f"(d[71]), "=f"(d[72]), "=f"(d[73]), "=f"(d[74]), "=f"(d[75]), "=f"(d[76]), "=f"(d[77]), "=f"(d[78]), "=f"(d[79]), "=f"(d[80]), "=f"(d[81]), "=f"(d[82]), "=f"(d[83]), "=f"(d[84]), "=f"(d[85]), "=f"(d[86]), "=f"(d[87]), "=f"(d[88]), "=f"(d[89]), "=f"(d[90]), "=f"(d[91]), "=f"(d[92]), "=f"(d[93]), "=f"(d[94]), "=f"(d[95]), "=f"(d[96]), "=f"(d[97]), "=f"(d[98]), "=f"(d[99]), "=f"(d[100]), "=f"(d[101]), "=f"(d[102]), "=f"(d[103]), "=f"(d[104]), "=f"(d[105]), "=f"(d[106]), "=f"(d[107]), "=f"(d[108]), "=f"(d[109]), "=f"(d[110]), "=f"(d[111]), "=f"(d[112]), "=f"(d[113]), "=f"(d[114]), "=f"(d[115]), "=f"(d[116]), "=f"(d[117]), "=f"(d[118]), "=f"(d[119]), "=f"(d[120]), "=f"(d[121]), "=f"(d[122]), "=f"(d[123]), "=f"(d[124]), "=f"(d[125]), "=f"(d[126]), "=f"(d[127])
    : "l"(da), "l"(db));
}
__device__ __forceinline__ void wgmma_n128_0(float (&d)[192], uint64_t da, uint64_t db) {
  asm volatile("{\n.reg .pred p;\nsetp.ne.b32 p, 0, 0;\n"
    "wgmma.mma_async.sync.aligned.m64n128k16.f32.bf16.bf16 {%0, %1, %2, %3, %4, %5, %6, %7, %8, %9, %10, %11, %12, %13, %14, %15, %16, %17, %18, %19, %20, %21, %22, %23, %24, %25, %26, %27, %28, %29, %30, %31, %32, %33, %34, %35, %36, %37, %38, %39, %40, %41, %42, %43, %44, %45, %46, %47, %48, %49, %50, %51, %52, %53, %54, %55, %56, %57, %58, %59, %60, %61, %62, %63}, %64, %65, p, 1, 1, 0, 1;\n}\n"
    : "=f"(d[128]), "=f"(d[129]), "=f"(d[130]), "=f"(d[131]), "=f"(d[132]), "=f"(d[133]), "=f"(d[134]), "=f"(d[135]), "=f"(d[136]), "=f"(d[137]), "=f"(d[138]), "=f"(d[139]), "=f"(d[140]), "=f"(d[141]), "=f"(d[142]), "=f"(d[143]), "=f"(d[144]), "=f"(d[145]), "=f"(d[146]), "=f"(d[147]), "=f"(d[148]), "=f"(d[149]), "=f"(d[150]), "=f"(d[151]), "=f"(d[152]), "=f"(d[153]), "=f"(d[154]), "=f"(d[155]), "=f"(d[156]), "=f"(d[157]), "=f"(d[158]), "=f"(d[159]), "=f"(d[160]), "=f"(d[161]), "=f"(d[162]), "=f"(d[163]), "=f"(d[164]), "=f"(d[165]), "=f"(d[166]), "=f"(d[167]), "=f"(d[168]), "=f"(d[169]), "=f"(d[170]), "=f"(d[171]), "=f"(d[172]), "=f"(d[173]), "=f"(d[174]), "=f"(d[175]), "=f"(d[176]), "=f"(d[177]), "=f"(d[178]), "=f"(d[179]), "=f"(d[180]), "=f"(d[181]), "=f"(d[182]), "=f"(d[183]), "=f"(d[184]), "=f"(d[185]), "=f"(d[186]), "=f"(d[187]), "=f"(d[188]), "=f"(d[189]), "=f"(d[190]), "=f"(d[191])
    : "l"(da), "l"(db));
}
__device__ __forceinline__ void wgmma_n64a(float (&d)[192], uint64_t da, uint64_t db, int scale_d) {
  asm volatile("{\n.reg .pred p;\nsetp.ne.b32 p, %34, 0;\n"
    "wgmma.mma_async.sync.aligned.m64n64k16.f32.bf16.bf16 {%0, %1, %2, %3, %4, %5, %6, %7, %8, %9, %10, %11, %12, %13, %14, %15, %16, %17, %18, %19, %20, %21, %22, %23, %24, %25, %26, %27, %28, %29, %30, %31}, %32, %33, p, 1, 1, 0, 1;\n}\n"
    : "+f"(d[128]), "+f"(d[129]), "+f"(d[130]), "+f"(d[131]), "+f"(d[132]), "+f"(d[133]), "+f"(d[134]), "+f"(d[135]), "+f"(d[136]), "+f"(d[137]), "+f"(d[138]), "+f"(d[139]), "+f"(d[140]), "+f"(d[141]), "+f"(d[142]), "+f"(d[143]), "+f"(d[144]), "+f"(d[145]), "+f"(d[146]), "+f"(d[147]), "+f"(d[148]), "+f"(d[149]), "+f"(d[150]), "+f"(d[151]), "+f"(d[152]), "+f"(d[153]), "+f"(d[154]), "+f"(d[155]), "+f"(d[156]), "+f"(d[157]), "+f"(d[158]), "+f"(d[159])
    : "l"(da), "l"(db), "r"(scale_d));
}
__device__ __forceinline__ void wgmma_n64b(float (&d)[192], uint64_t da, uint64_t db, int scale_d) {
  asm volatile("{\n.reg .pred p;\nsetp.ne.b32 p, %34, 0;\n"
    "wgmma.mma_async.sync.aligned.m64n64k16.f32.bf16.bf16 {%0, %1, %2, %3, %4, %5, %6, %7, %8, %9, %10, %11, %12, %13, %14, %15, %16, %17, %18, %19, %20, %21, %22, %23, %24, %25, %26, %27, %28, %29, %30, %31}, %32, %33, p, 1, 1, 0, 1;\n}\n"
    : "+f"(d[160]), "+f"(d[161]), "+f"(d[162]), "+f"(d[163]), "+f"(d[164]), "+f"(d[165]), "+f"(d[166]), "+f"(d[167]), "+f"(d[168]), "+f"(d[169]), "+f"(d[170]), "+f"(d[171]), "+f"(d[172]), "+f"(d[173]), "+f"(d[174]), "+f"(d[175]), "+f"(d[176]), "+f"(d[177]), "+f"(d[178]), "+f"(d[179]), "+f"(d[180]), "+f"(d[181]), "+f"(d[182]), "+f"(d[183]), "+f"(d[184]), "+f"(d[185]), "+f"(d[186]), "+f"(d[187]), "+f"(d[188]), "+f"(d[189]), "+f"(d[190]), "+f"(d[191])
    : "l"(da), "l"(db), "r"(scale_d));
}

constexpr int SLOT = 16384;
constexpr int KVT = 10240;
constexpr uint32_t QA = 0x0BAu, QK = 0x462u, QQ = 0x981u;
constexpr int SM_SD = 12 * SLOT;
constexpr int SM_BAR = SM_SD + 8192;
constexpr int SM_RS = SM_BAR + 512;
constexpr int SM_AP = SM_RS + 768;
constexpr int SM_BP = SM_AP + 2048;
constexpr int SM_WPHI = SM_BP + 12288;
constexpr int SM_EPOCH = SM_WPHI + 10240;
constexpr int SM_TOTAL = SM_EPOCH + 16 + 1024;
constexpr int B_FULLS = 0, B_XOLD = 24, B_STAT = 32, B_EMPTYS = 40, B_FULLT = 256  , B_CONS = 384  , B_E3 = 472, B_E0 = 480, B_E1 = 488, B_E2 = 496, B_EPI = 504, B_KVRDY = 152  , B_CS = 160,
              B_KVDONE = 168  , B_ODONE = 176, B_XDONE = 184, B_OH1 = 192, B_CS2 = 208, B_XH0 = 232, B_OF = 240, B_FLG = 64  ;
constexpr uint64_t BAR_CNT = 0x1c07fc0eac00a800ull;
constexpr uint64_t WO_A0 = 0xba73218732187643ull, WO_B0 = 0x540695406ba59021ull, WO_A1 = 0xba732157321576baull, WO_B1 = 0x9506489064890321ull;
constexpr uint64_t WO_DA0 = 0xa9876543210edd00ull, WO_DB0 = 0xa98765432bbbccccull, WO_DA1 = 0xa9876543210fff00ull, WO_DB1 = 0xa98765432bbcccccull;
constexpr int XS = 10;

#define HPI 2
#define PL 2
#define PROFX(i) PROFT(tid_ == 128 && layer == PL, 200 + (i))
#define GAA 99
#define GAB 99
#define GWA 99
#define GWB 99
#define PSL 20
#define EP 5
#define DRY 0
#define NCOM 3
#define CG0 0
#define CG1 99
#define CPF 0
#define CSLP 128
#define PFS 8
#define NLAYERS 4
constexpr float L2E = 1.4426950408889634f;
#define PHI_MAX 2147483648.f

#define D128(lo) desc64(lo, 0x40000040u)
struct Ctx { uint32_t sb; int g, rb, cu; bf16* out; };

__device__ __forceinline__ void colsum_load(const bf16* __restrict__ w, int rb, int g, int wi, int lane, uint32_t stg, float (&s)[8]) {
  const int ch = wi * 8 + (lane & 7), sec = ch >> 4;
  const bf16* src = w + (size_t)(rb * 64 + (lane >> 3) * 16) * 3072 + (sec == 2 ? 0 : 1024 + sec * 1024) + g * 128 + (ch & 15) * 8;
  stg += lane * 16;
#pragma unroll
  for (int i = 0; i < 8; ++i) s[i] = 0.f;
#pragma unroll
  for (int r = 0; r < 12; ++r)
    asm volatile("cp.async.cg.shared.global [%0], [%1], 16;" ::"r"(stg + r * 512), "l"(src + (size_t)(4 + r) * 3072) : "memory");
  uint4 v[4];
#pragma unroll
  for (int r = 0; r < 4; ++r) v[r] = __ldg(reinterpret_cast<const uint4*>(src + (size_t)r * 3072));
#pragma unroll 1
  for (int r0 = 0;; ++r0) {
#pragma unroll
    for (int r = 0; r < 4; ++r) {
      s[0] += bf_lo(v[r].x); s[1] += bf_hi(v[r].x); s[2] += bf_lo(v[r].y); s[3] += bf_hi(v[r].y);
      s[4] += bf_lo(v[r].z); s[5] += bf_hi(v[r].z); s[6] += bf_lo(v[r].w); s[7] += bf_hi(v[r].w);
    }
    if (r0 == 3) break;
    asm volatile("cp.async.wait_all;" ::: "memory");
#pragma unroll
    for (int r = 0; r < 4; ++r) v[r] = lds128(stg + (r0 * 4 + r) * 512);
  }
#pragma unroll
  for (int i = 0; i < 8; ++i) { s[i] += __shfl_xor_sync(0xffffffffu, s[i], 8); s[i] += __shfl_xor_sync(0xffffffffu, s[i], 16); }
}
__device__ __forceinline__ void colsum_red(float* cs, int g, int wi, int lane, const float (&s)[8]) {
  if (lane < 8) {
    red_add4(cs + g * 384 + (wi * 8 + lane) * 8, s[0], s[1], s[2], s[3]);
    red_add4(cs + g * 384 + (wi * 8 + lane) * 8 + 4, s[4], s[5], s[6], s[7]);
  }
}
#define PHASE_CTX() \
  uint32_t sb = c.sb; asm volatile("" : "+r"(sb)); \
  int tid_ = threadIdx.x; asm volatile("" : "+r"(tid_)); \
  const uint32_t bar = sb + SM_BAR; \
  const int lane = tid_ & 31, cw = (tid_ >> 5) - 4, wg = cw >> 2, wq = cw & 3, gq = lane >> 2, t = lane & 3, wrow0 = cw * 16; \
  const int lrow = (lane & 7) + ((lane >> 3) & 1) * 8, lchk = lane >> 4; \
  const bool elected = (tid_ & 127) == 0; \
  const uint32_t rowo = (wrow0 + lrow) * 128, X = (lchk ^ (lane & 7)) << 4; \
  (void)bar; (void)wq; (void)gq; (void)lrow; (void)lchk; (void)elected; (void)wrow0; (void)wg; (void)rowo; (void)X; (void)t;

template <int PITCH = D_>
__device__ __forceinline__ void slab_out_half(uint32_t slot, bf16* dst, int wrow0, int lane) {
  const int r0 = lane >> 3, ch = lane & 7;
  const uint32_t src = slot + (wrow0 + r0) * 128;
  uint4 v[4];
#pragma unroll
  for (int i = 0; i < 4; ++i) v[i] = lds128(src + i * 512 + (((ch ^ (4 * i + r0)) & 7) << 4));
  dst += (size_t)(wrow0 + r0) * PITCH + ch * 8;
#pragma unroll
  for (int i = 0; i < 4; ++i) *reinterpret_cast<uint4*>(dst + (size_t)i * 4 * PITCH) = v[i];
}

__device__ __forceinline__ void stats_out(float s0, float s1, float q0, float q1, float2* dst, int t) {
  const bool od = t & 1;
  float sa = od ? s1 : s0, qa = od ? q1 : q0;
  sa += __shfl_xor_sync(0xffffffffu, od ? s0 : s1, 1);
  qa += __shfl_xor_sync(0xffffffffu, od ? q0 : q1, 1);
  sa += __shfl_xor_sync(0xffffffffu, sa, 2);
  qa += __shfl_xor_sync(0xffffffffu, qa, 2);
  if (t < 2) red_add2(&dst[t * 8].x, sa, qa);
}

__device__ __forceinline__ void consumer(const Ctx& c) {
  const int g = c.g, m0 = c.rb * 128;
  float acc[192];
#define X_H1() \
      _Pragma("unroll") for (int jp = 4; jp < 8; ++jp) \
        stsm_x4(sb + (XS + 1) * SLOT + rowo + (X ^ ((jp & 3) << 5)), \
                pack_bf16(acc[128 + 8 * jp], acc[129 + 8 * jp]), pack_bf16(acc[130 + 8 * jp], acc[131 + 8 * jp]), \
                pack_bf16(acc[132 + 8 * jp], acc[133 + 8 * jp]), pack_bf16(acc[134 + 8 * jp], acc[135 + 8 * jp]));
#pragma unroll
  for (int i = 128; i < 192; ++i) acc[i] = 0.f;
#pragma unroll 1
  for (int layer = 0;; ++layer) {
    {
      PHASE_CTX();
      const uint32_t wu = __shfl_sync(0xffffffffu, wg, 0);
      const uint32_t dA0 = (((sb + wu * 8192) & 0x3FFFF) >> 4) | (1u << 16), dB0 = ((sb & 0x3FFFF) >> 4) | (512u << 16);
      {
        PROFX(0);
        mbar_wait(bar + B_FULLS, 0);
        PROFX(1);
        wgmma_fence();
        wgmma_n256_0(acc, D128(dA0 + XS * 1024), D128(dB0 + 2048));
#pragma unroll
        for (int k = 1; k < 4; ++k) wgmma_n256(acc, D128(dA0 + XS * 1024 + k * 2), D128(dB0 + 2048 + k * 128), 1);
        wgmma_commit();
        wgmma_wait<1>();
        float s0 = 0.f, s1 = 0.f, q0 = 0.f, q1 = 0.f;
        if (layer) {
          X_H1();
#pragma unroll
          for (int i = 128; i < 192; i += 4) {
            s0 += acc[i] + acc[i + 1]; s1 += acc[i + 2] + acc[i + 3];
            q0 = fmaf(acc[i], acc[i], fmaf(acc[i + 1], acc[i + 1], q0)); q1 = fmaf(acc[i + 2], acc[i + 2], fmaf(acc[i + 3], acc[i + 3], q1));
          }
        }
        asm volatile("" : "+f"(s0), "+f"(s1), "+f"(q0), "+f"(q1) :: "memory");
        wgmma_fence();
        wgmma_n128_0(acc, D128(dA0 + XS * 1024), D128(dB0 + 1024));
#pragma unroll
        for (int k = 1; k < 4; ++k) wgmma_n128(acc, D128(dA0 + XS * 1024 + k * 2), D128(dB0 + 1024 + k * 128), 1);
        wgmma_commit();
        if (layer) {
          PHASE_CTX();
          fence_async_smem();
          nbar_dyn(3 + wu, 128);
          stats_out(s0, s1, q0, q1, g_stats + layer * S_ + m0 + wrow0 + gq, t);
          PROFT(tid_ == 128, layer * 16 + 8);
        }
      }
      uint32_t s = 1, u = 0, sp = 0;
      const int ix = layer ? 1 : 2 * min(g, NCOM) + 1;
#pragma unroll 1
      for (int i = 1; i < 14; ++i) {
        mbar_wait(bar + B_FULLS + s * 8, (u + (s ? layer : 0)) & 1);
        const uint32_t da = dA0 + ((QA >> (4 * s)) & 15) * 1024, dk = dB0 + ((QK >> (4 * s)) & 15) * 1024,
                       dq = dB0 + ((QQ >> (4 * s)) & 15) * 1024;
        wgmma_fence();
#pragma unroll
        for (int k = 0; k < 4; ++k) {
          wgmma_n256(acc, D128(da + k * 2), D128(dk + k * 128), 1);
          wgmma_n128(acc, D128(da + k * 2), D128(dq + k * 128), 1);
        }
        wgmma_commit();
        if (i == ix || (i == ix + 1 && !layer)) {
          PHASE_CTX();
          if (layer) {
            slab_out_half(sb + (XS + 1) * SLOT, g_x + (size_t)m0 * D_ + g * 128 + 64, wrow0, lane);
          } else {
            float s0 = 0.f, s1 = 0.f, q0 = 0.f, q1 = 0.f;
            const uint32_t xa = sb + ((QA >> (4 * sp)) & 15) * SLOT + rowo;
#pragma unroll
            for (int jp = 0; jp < 4; ++jp) {
              uint32_t x0, x1, x2, x3;
              ldsm_x4(x0, x1, x2, x3, xa + (X ^ (jp << 5)));
              s0 += (bf_lo(x0) + bf_hi(x0)) + (bf_lo(x2) + bf_hi(x2));
              s1 += (bf_lo(x1) + bf_hi(x1)) + (bf_lo(x3) + bf_hi(x3));
              q0 = fmaf(bf_lo(x0), bf_lo(x0), fmaf(bf_hi(x0), bf_hi(x0), fmaf(bf_lo(x2), bf_lo(x2), fmaf(bf_hi(x2), bf_hi(x2), q0))));
              q1 = fmaf(bf_lo(x1), bf_lo(x1), fmaf(bf_hi(x1), bf_hi(x1), fmaf(bf_lo(x3), bf_lo(x3), fmaf(bf_hi(x3), bf_hi(x3), q1))));
            }
            stats_out(s0, s1, q0, q1, g_stats + m0 + wrow0 + gq, t);
          }
          __syncwarp();
          if (lane == 0 && (layer || i != ix)) mbar_arrive(bar + B_XDONE);
          nbar_dyn(3 + wu, 128);
        }
        wgmma_wait<1>();
        if (elected) release2(bar + B_EMPTYS + sp * 8);
        sp = s;
        if (++s == 3) { s = 0; ++u; }
      }
      {
        const uint64_t dap = make_desc_ns(sb + SM_AP + wu * 1024, 0, 128), dbp = make_desc_ns(sb + SM_BP + (layer & 1) * 6144, 0, 128);
        if (wu == 0) {
          wgmma_wait<0>();
          nbar<6, 256>();
        }
        if (layer < 2) mbar_wait(bar + (layer ? B_CS2 : B_CS), 0);
        mbar_wait(bar + B_STAT, layer & 1);
        mbar_wait(bar + B_FULLS + 16, layer & 1);
        wgmma_fence();
        wgmma_n256_k(acc, dap, dbp, 1);
#pragma unroll
        for (int k = 0; k < 4; ++k) wgmma_n256(acc, D128(dA0 + (QA >> 8) * 1024 + k * 2), D128(dB0 + (QK >> 8) * 1024 + k * 128), 1);
        mbar_wait(bar + B_FULLS, 1);
        PROFT(tid_ == 128, layer * 16 + 9);
        wgmma_fence();
#pragma unroll
        for (int k = 0; k < 4; ++k) wgmma_n256(acc, D128(dA0 + (QA & 15) * 1024 + k * 2), D128(dB0 + (QK & 15) * 1024 + k * 128), 1);
        wgmma_commit();
        if (wu) nbar<6, 256>();
#define Q_TAIL() \
        wgmma_n128_k(acc, dap, dbp + 256, 1); \
        _Pragma("unroll") for (int k = 0; k < 4; ++k) wgmma_n128(acc, D128(dA0 + (QA >> 8) * 1024 + k * 2), D128(dB0 + (QQ >> 8) * 1024 + k * 128), 1); \
        _Pragma("unroll") for (int k = 0; k < 4; ++k) wgmma_n128(acc, D128(dA0 + (QA & 15) * 1024 + k * 2), D128(dB0 + (QQ & 15) * 1024 + k * 128), 1);
        Q_TAIL();
        wgmma_commit();
        wgmma_wait<1>();
#pragma unroll
        for (int i = 0; i < 128; ++i) asm volatile("" : "+f"(acc[i]) :: "memory");
      }
    }
    uint32_t xo[32];
    {
      PHASE_CTX();
      PROFT(tid_ == 128, layer * 16 + 1);
      const bool isB = layer & 1;
      const int cu = c.cu;
      if (cu >= 4) asm volatile("bar.arrive 7, 256;" ::: "memory");
      else if (isB && cu == 0) asm volatile("bar.arrive 10, 64;" ::: "memory");
      if (elected && isB && cu == 0) release2(bar + B_E1);
      uint32_t kq[64];
#pragma unroll
      for (int i = 0; i < 32; ++i) kq[i] = pack_bf16(acc[2 * i], acc[2 * i + 1]);
      const unsigned int epoch = __float_as_uint(lds_f(sb + SM_EPOCH));
      uint4* const hbuf = g_halo + (size_t)((((epoch & 1) * 2 + (layer >> 1)) * 16 + c.rb) * 8 + g) * 512 + lane;
      if (isB && cu == 7) {
#pragma unroll
        for (int jp = 0; jp < 8; ++jp) st_relaxed4(hbuf + jp * 32, ~kq[4 * jp], ~kq[4 * jp + 1], ~kq[4 * jp + 2], ~kq[4 * jp + 3]);
#pragma unroll
        for (int jp = 8; jp < 16; ++jp)
          st_relaxed4(hbuf + jp * 32, ~pack_bf16(acc[8 * jp], acc[8 * jp + 1]), ~pack_bf16(acc[8 * jp + 2], acc[8 * jp + 3]),
                      ~pack_bf16(acc[8 * jp + 4], acc[8 * jp + 5]), ~pack_bf16(acc[8 * jp + 6], acc[8 * jp + 7]));
      }
      const uint32_t rowq = rowo & 8191;
      const uint32_t rB = sb + 4 * SLOT + wg * 4 * KVT + rowq, pA = sb + (3 + 3 * wg) * SLOT + rowq;
      PROFX(13);
      if (cu < 4) nbar<7, 256>();
      PROFX(14);
      {
        const uint32_t vb = isB ? rB + KVT + 2048 + wg * 2 * KVT : pA + 2 * SLOT - (rowq >> 1), vst = isB ? (1 - 2 * wg) * 2 * KVT : 8192;
        const uint32_t X0 = isB ? X : (lchk ^ ((lane & 7) >> 1)) << 4, X1 = isB ? X ^ 64 : X0 + 4096;
        const bool dup = isB && cu == 3;
        if (isB) {
#pragma unroll
          for (int jp = 0; jp < 8; ++jp) {
            stsm_x4(vb - KVT + (jp >> 2) * vst + (X ^ ((jp & 3) << 5)), kq[4 * jp], kq[4 * jp + 1], kq[4 * jp + 2], kq[4 * jp + 3]);
            stsm_x4_p(dup, rB + 2048 + 32768 + (1 - (jp >> 2)) * 2 * KVT + (X ^ ((jp & 3) << 5)), kq[4 * jp], kq[4 * jp + 1], kq[4 * jp + 2], kq[4 * jp + 3]);
          }
        }
#pragma unroll
        for (int jp = 8; jp < 16; ++jp) {
          const uint32_t v0 = pack_bf16(acc[8 * jp], acc[8 * jp + 1]), v1 = pack_bf16(acc[8 * jp + 2], acc[8 * jp + 3]),
                         v2 = pack_bf16(acc[8 * jp + 4], acc[8 * jp + 5]), v3 = pack_bf16(acc[8 * jp + 6], acc[8 * jp + 7]);
          const uint32_t ad = vb + ((jp >> 2) & 1) * vst + (((jp & 2) ? X1 : X0) ^ ((jp & 1) << 5));
          stsm_x4(ad, v0, v1, v2, v3);
          stsm_x4_p(dup, ad + 32768 + ((jp & 4) ? -2 * KVT : 2 * KVT), v0, v1, v2, v3);
        }
        if (dup) asm volatile("bar.arrive 9, 64;" ::: "memory");
      }
      const float rs0 = lds_f(sb + SM_RS + (16 + wrow0 + gq) * 4), rs1 = lds_f(sb + SM_RS + (24 + wrow0 + gq) * 4);
      PROFT(tid_ == 128, layer * 16 + 2);
#define Q_DONE() \
      wgmma_wait<0>(); \
      if (lane == 0) release2(bar + B_E0); \
      _Pragma("unroll") for (int i = 128; i < 192; ++i) asm volatile("" : "+f"(acc[i]) :: "memory"); \
      _Pragma("unroll") for (int i = 0; i < 32; ++i) kq[32 + i] = pack_bf16(acc[128 + 2 * i], acc[129 + 2 * i]);
      Q_DONE();
      if (isB) {
        const int e = gq & 1;
        const uint32_t KX = ((lane >> 3) ^ (lane & 7)) << 4;
        float f0[4], f1[4], rj[4];
        uint32_t msk = 0;
#pragma unroll
        for (int nt = 0; nt < 4; ++nt) {
          const int kk = nt * 8 + 2 * t + e;
          const bool okk = (m0 + wrow0 + kk) >= 16;
          const int d0 = kk - gq, d1 = d0 - 8;
          rj[nt] = lds_f(sb + SM_RS + (wrow0 + kk) * 4);
          f0[nt] = rj[nt] * rs0 * (0.17677669529663687f * L2E);
          f1[nt] = rj[nt] * rs1 * (0.17677669529663687f * L2E);
          msk |= (okk && d0 >= 2 && d0 <= 16) ? (1u << nt) : 0u;
          msk |= (okk && d1 >= 2 && d1 <= 16) ? (16u << nt) : 0u;
        }
        if ((cu & 3) == 0) asm volatile("bar.arrive %0, 128;" :: "r"(3 + (cu >> 2)) : "memory");
        if (cu == 0) {
          nbar<11, 64>();
        } else if (cu == 4) {
          uint4 hv[16];
          if (c.rb > 0) {
            uint32_t n = 0;
#pragma unroll 1
            while (true) {
              uint32_t mn = 0xFFFFFFFFu;
#pragma unroll
              for (int i = 0; i < 16; ++i) hv[i] = ld_relaxed4(hbuf - 8 * 512 + i * 32);
#pragma unroll
              for (int i = 0; i < 16; ++i) mn = __vimin3_u32(__vimin3_u32(mn, hv[i].x, hv[i].y), hv[i].z, hv[i].w);
              if (__all_sync(0xffffffffu, mn != 0u)) break;
              if (++n > (1u << 20)) { g_err = 4u; break; }
            }
          } else {
#pragma unroll
            for (int i = 0; i < 16; ++i) hv[i] = make_uint4(~0u, ~0u, ~0u, ~0u);
          }
          nbar<10, 64>();
#pragma unroll
          for (int i = 0; i < 16; ++i)
            stsm_x4(rB - 4 * KVT + (((i >> 2) & 1) * 2 + (i >> 3)) * KVT + (X ^ ((i & 3) << 5)), ~hv[i].x, ~hv[i].y, ~hv[i].z, ~hv[i].w);
          asm volatile("bar.arrive 11, 64;" ::: "memory");
          nbar<9, 64>();
        } else {
          nbar_dyn(3 + (cu >> 2), 128);
        }
        PROFT(tid_ == 128, layer * 16 + 5);
#pragma unroll
        for (int i = 16; i < 32; ++i) xo[i] = 0u;
#pragma unroll 1
        for (int hp = 0; hp < 2; ++hp) {
          const uint32_t qad = sb + (XS + hp) * SLOT + rowo, kt = rB + 2 * (hp ^ wg) * KVT - (lane & 8) * 128, vt = rB + (2 * (hp ^ wg) + 1) * KVT;
          uint32_t qa[2][8];
#pragma unroll
          for (int i = 0; i < 16; ++i) { qa[i >> 3][i & 7] = kq[32 + i]; kq[32 + i] = kq[48 + i]; }
          float l0[2][4], l1[2][4];
#pragma unroll
          for (int nt = 0; nt < 4; ++nt)
#pragma unroll
            for (int h = 0; h < 2; ++h) {
              float sc[4] = {0.f, 0.f, 0.f, 0.f};
              uint32_t b0, b1, b2, b3;
              ldsm_x4(b0, b1, b2, b3, kt + nt * 1024 + (KX ^ (h << 6)));
              mma_bf16(sc, qa[h][0], qa[h][1], qa[h][2], qa[h][3], b0, b1);
              mma_bf16(sc, qa[h][4], qa[h][5], qa[h][6], qa[h][7], b2, b3);
              l0[h][nt] = (msk >> nt) & 1 ? (e ? sc[1] : sc[0]) * f0[nt] : -1e30f;
              l1[h][nt] = (msk >> (4 + nt)) & 1 ? (e ? sc[3] : sc[2]) * f1[nt] : -1e30f;
            }
          float mx0[2], mx1[2], s0[2], s1[2];
#pragma unroll
          for (int h = 0; h < 2; ++h) {
            mx0[h] = fmaxf(fmaxf(l0[h][0], l0[h][1]), fmaxf(l0[h][2], l0[h][3]));
            mx1[h] = fmaxf(fmaxf(l1[h][0], l1[h][1]), fmaxf(l1[h][2], l1[h][3]));
          }
#pragma unroll
          for (int o = 1; o <= 2; o <<= 1)
#pragma unroll
            for (int h = 0; h < 2; ++h) {
              mx0[h] = fmaxf(mx0[h], __shfl_xor_sync(0xffffffffu, mx0[h], o));
              mx1[h] = fmaxf(mx1[h], __shfl_xor_sync(0xffffffffu, mx1[h], o));
            }
#pragma unroll
          for (int h = 0; h < 2; ++h) {
#pragma unroll
            for (int nt = 0; nt < 4; ++nt) { l0[h][nt] = ex2(l0[h][nt] - mx0[h]); l1[h][nt] = ex2(l1[h][nt] - mx1[h]); }
            s0[h] = (l0[h][0] + l0[h][1]) + (l0[h][2] + l0[h][3]);
            s1[h] = (l1[h][0] + l1[h][1]) + (l1[h][2] + l1[h][3]);
          }
#pragma unroll
          for (int o = 1; o <= 2; o <<= 1)
#pragma unroll
            for (int h = 0; h < 2; ++h) {
              s0[h] += __shfl_xor_sync(0xffffffffu, s0[h], o);
              s1[h] += __shfl_xor_sync(0xffffffffu, s1[h], o);
            }
          uint32_t pl[2][4], phh[2][4];
#pragma unroll
          for (int h = 0; h < 2; ++h) {
            const float i0 = rcp(s0[h]), i1 = rcp(s1[h]);
#pragma unroll
            for (int nt = 0; nt < 4; ++nt) {
              const uint32_t pk = pack_bf16(l0[h][nt] * i0 * rj[nt], l1[h][nt] * i1 * rj[nt]);
              pl[h][nt] = e ? pk << 16 : pk & 0xFFFFu;
              phh[h][nt] = e ? pk & 0xFFFF0000u : pk >> 16;
            }
          }
          float oa[2][4][4];
#pragma unroll
          for (int h = 0; h < 2; ++h)
#pragma unroll
            for (int i = 0; i < 4; ++i) { oa[h][i][0] = oa[h][i][1] = oa[h][i][2] = oa[h][i][3] = 0.f; }
#pragma unroll
          for (int ks = 0; ks < 2; ++ks)
#pragma unroll
            for (int np = 0; np < 2; ++np)
#pragma unroll
              for (int h = 0; h < 2; ++h) {
                uint32_t b0, b1, b2, b3;
                ldsm_x4_t(b0, b1, b2, b3, vt + ks * 2048 + (X ^ (h << 6) ^ (np << 5)));
                mma_bf16(oa[h][2 * np], pl[h][2 * ks], phh[h][2 * ks], pl[h][2 * ks + 1], phh[h][2 * ks + 1], b0, b1);
                mma_bf16(oa[h][2 * np + 1], pl[h][2 * ks], phh[h][2 * ks], pl[h][2 * ks + 1], phh[h][2 * ks + 1], b2, b3);
              }
          if (hp == 0 && lane == 0) release2(bar + B_E3);
          mbar_wait(bar + B_XOLD, 1);
#pragma unroll
          for (int i = 0; i < 16; ++i) xo[i] = xo[16 + i];
#pragma unroll
          for (int jp = 0; jp < 4; ++jp) ldsm_x4(xo[16 + 4 * jp], xo[17 + 4 * jp], xo[18 + 4 * jp], xo[19 + 4 * jp], qad + (X ^ (jp << 5)));
#pragma unroll
          for (int h = 0; h < 2; ++h)
#pragma unroll
            for (int np = 0; np < 2; ++np)
              stsm_x4(qad + (X ^ (h << 6) ^ (np << 5)),
                      pack_bf16(oa[h][2 * np][0], oa[h][2 * np][1]), pack_bf16(oa[h][2 * np][2], oa[h][2 * np][3]),
                      pack_bf16(oa[h][2 * np + 1][0], oa[h][2 * np + 1][1]), pack_bf16(oa[h][2 * np + 1][2], oa[h][2 * np + 1][3]));
          fence_async_smem();
          {
            __syncwarp();
            slab_out_half(sb + (XS + hp) * SLOT, g_o + (size_t)m0 * D_ + g * 128 + hp * 64, wrow0, lane);
            __syncwarp();
            if (lane == 0) mbar_arrive(bar + (hp ? B_ODONE : B_OH1));
          }
        }
      } else {
        PHASE_CTX();
        const uint32_t pA = sb + (3 + 3 * wg) * SLOT + (rowo & 8191);
        const float sc0 = rs0 * L2E, sc1 = rs1 * L2E;
        const uint32_t wa0 = sb + SM_WPHI + lrow * 80 + lchk * 16;
        __syncwarp();
#pragma unroll
        for (int i = 0; i < 32; ++i) xo[i] = 0u;
        float p[HPI][4][4];
        auto proj = [&](int hp) {
#pragma unroll
            for (int h = 0; h < HPI; ++h)
#pragma unroll
              for (int i = 0; i < 4; ++i) { p[h][i][0] = p[h][i][1] = p[h][i][2] = p[h][i][3] = 0.f; }
            const uint32_t wa = wa0 + hp * 5120;
#pragma unroll
            for (int ks = 0; ks < 2; ++ks)
#pragma unroll
              for (int np = 0; np < 2; ++np)
#pragma unroll
                for (int h = 0; h < HPI; ++h) {
                  uint32_t b0, b1, b2, b3;
                  ldsm_x4_t(b0, b1, b2, b3, wa + h * 2560 + ks * 1280 + np * 32);
                  mma_bf16(p[h][2 * np], kq[8 * h + 4 * ks], kq[8 * h + 4 * ks + 1], kq[8 * h + 4 * ks + 2], kq[8 * h + 4 * ks + 3], b0, b1);
                  mma_bf16(p[h][2 * np + 1], kq[8 * h + 4 * ks], kq[8 * h + 4 * ks + 1], kq[8 * h + 4 * ks + 2], kq[8 * h + 4 * ks + 3], b2, b3);
                }
        };
#pragma unroll 1
        for (int it = 0;; ++it) {
          const bool isq = it >= 2;
          const int hp = it & 1;
          const float mul0 = isq ? 1.f : rs0, mul1 = isq ? 1.f : rs1;
          uint32_t ph[2][4][4];
          proj(hp);
          bool bad = false;
          {
            float ss[HPI][2][4];
#pragma unroll
            for (int h = 0; h < HPI; ++h) {
#pragma unroll
              for (int i = 0; i < 4; ++i) {
                const float e0 = ex2(p[h][i][0] * sc0), e1 = ex2(p[h][i][1] * sc0), e2 = ex2(p[h][i][2] * sc1), e3 = ex2(p[h][i][3] * sc1);
                const float m0 = e0 * e1, m1 = e2 * e3, rr = rcp(m0 * m1), r0 = rr * m1, r1 = rr * m0;
                ph[h][i >> 1][(i & 1) * 2] = pack_bf16(e0, e1);
                ph[h][i >> 1][(i & 1) * 2 + 1] = pack_bf16(e2, e3);
                ph[h][2 + (i >> 1)][(i & 1) * 2] = pack_bf16(e1 * r0, e0 * r0);
                ph[h][2 + (i >> 1)][(i & 1) * 2 + 1] = pack_bf16(e3 * r1, e2 * r1);
              }
#pragma unroll
              for (int sg = 0; sg < 2; ++sg) {
                ss[h][sg][0] = ss[h][sg][1] = ss[h][sg][2] = ss[h][sg][3] = 0.f;
#pragma unroll
                for (int ks = 0; ks < 2; ++ks)
                  mma_bf16(ss[h][sg], ph[h][2 * sg + ks][0], ph[h][2 * sg + ks][1], ph[h][2 * sg + ks][2], ph[h][2 * sg + ks][3], 0x3F803F80u, 0x3F803F80u);
              }
            }
#pragma unroll
            for (int h = 0; h < HPI; ++h)
#pragma unroll
              for (int sg = 0; sg < 2; ++sg) {
                bad = bad || !(ss[h][sg][0] < PHI_MAX) || !(ss[h][sg][2] < PHI_MAX);
                const uint32_t iv = pack_bf16(rcp(ss[h][sg][0]) * mul0, rcp(ss[h][sg][2]) * mul1);
#pragma unroll
                for (int ks = 0; ks < 2; ++ks)
#pragma unroll
                  for (int j = 0; j < 4; ++j) ph[h][2 * sg + ks][j] = mul_bf16x2(ph[h][2 * sg + ks][j], iv, j & 1);
              }
          }
          if (__builtin_expect(__any_sync(0xffffffffu, bad), 0)) {
            proj(hp);
            float mx[HPI][2], mn[HPI][2];
#pragma unroll
            for (int h = 0; h < HPI; ++h)
#pragma unroll
              for (int r = 0; r < 2; ++r) {
                mx[h][r] = fmaxf(fmaxf(fmaxf(p[h][0][2 * r], p[h][0][2 * r + 1]), fmaxf(p[h][1][2 * r], p[h][1][2 * r + 1])),
                                 fmaxf(fmaxf(p[h][2][2 * r], p[h][2][2 * r + 1]), fmaxf(p[h][3][2 * r], p[h][3][2 * r + 1])));
                mn[h][r] = fminf(fminf(fminf(p[h][0][2 * r], p[h][0][2 * r + 1]), fminf(p[h][1][2 * r], p[h][1][2 * r + 1])),
                                 fminf(fminf(p[h][2][2 * r], p[h][2][2 * r + 1]), fminf(p[h][3][2 * r], p[h][3][2 * r + 1])));
              }
#pragma unroll
            for (int o = 1; o <= 2; o <<= 1)
#pragma unroll
              for (int h = 0; h < HPI; ++h)
#pragma unroll
                for (int r = 0; r < 2; ++r) {
                  mx[h][r] = fmaxf(mx[h][r], __shfl_xor_sync(0xffffffffu, mx[h][r], o));
                  mn[h][r] = fminf(mn[h][r], __shfl_xor_sync(0xffffffffu, mn[h][r], o));
                }
            float en[HPI][4][4], sp[HPI][2], sn[HPI][2];
#pragma unroll
            for (int h = 0; h < HPI; ++h) {
              mx[h][0] *= -sc0; mx[h][1] *= -sc1; mn[h][0] *= sc0; mn[h][1] *= sc1;
              sp[h][0] = sp[h][1] = sn[h][0] = sn[h][1] = 0.f;
            }
#pragma unroll
            for (int i = 0; i < 4; ++i)
#pragma unroll
              for (int e = 0; e < 4; ++e)
#pragma unroll
                for (int h = 0; h < HPI; ++h) {
                  en[h][i][e] = ex2(fmaf(p[h][i][e], (e >> 1) ? -sc1 : -sc0, mn[h][e >> 1]));
                  p[h][i][e] = ex2(fmaf(p[h][i][e], (e >> 1) ? sc1 : sc0, mx[h][e >> 1]));
                  sp[h][e >> 1] += p[h][i][e]; sn[h][e >> 1] += en[h][i][e];
                }
#pragma unroll
            for (int o = 1; o <= 2; o <<= 1)
#pragma unroll
              for (int h = 0; h < HPI; ++h)
#pragma unroll
                for (int r = 0; r < 2; ++r) {
                  sp[h][r] += __shfl_xor_sync(0xffffffffu, sp[h][r], o);
                  sn[h][r] += __shfl_xor_sync(0xffffffffu, sn[h][r], o);
                }
#pragma unroll
            for (int h = 0; h < HPI; ++h) {
              const float ip0 = rcp(sp[h][0]) * mul0, ip1 = rcp(sp[h][1]) * mul1, in0 = rcp(sn[h][0]) * mul0, in1 = rcp(sn[h][1]) * mul1;
#pragma unroll
              for (int cp = 0; cp < 2; ++cp) {
                ph[h][cp][0] = pack_bf16(p[h][2 * cp][0] * ip0, p[h][2 * cp][1] * ip0);
                ph[h][cp][1] = pack_bf16(p[h][2 * cp][2] * ip1, p[h][2 * cp][3] * ip1);
                ph[h][cp][2] = pack_bf16(p[h][2 * cp + 1][0] * ip0, p[h][2 * cp + 1][1] * ip0);
                ph[h][cp][3] = pack_bf16(p[h][2 * cp + 1][2] * ip1, p[h][2 * cp + 1][3] * ip1);
                ph[h][2 + cp][0] = pack_bf16(en[h][2 * cp][0] * in0, en[h][2 * cp][1] * in0);
                ph[h][2 + cp][1] = pack_bf16(en[h][2 * cp][2] * in1, en[h][2 * cp][3] * in1);
                ph[h][2 + cp][2] = pack_bf16(en[h][2 * cp + 1][0] * in0, en[h][2 * cp + 1][1] * in0);
                ph[h][2 + cp][3] = pack_bf16(en[h][2 * cp + 1][2] * in1, en[h][2 * cp + 1][3] * in1);
              }
            }
          }
#pragma unroll
          for (int i = 0; i < 48; ++i) kq[i] = kq[16 + i];
          if (!isq) {
#pragma unroll
            for (int h = 0; h < HPI; ++h)
#pragma unroll
              for (int cp = 0; cp < 4; ++cp)
                stsm_x4(pA + hp * 16384 + h * 8192 + (X ^ (cp << 5)), ph[h][cp][0], ph[h][cp][1], ph[h][cp][2], ph[h][cp][3]);
            PROFT(tid_ == 128, layer * 16 + 11);
            fence_async_smem();
            nbar<1, 256>();
            uint32_t hu = 2 * hp + wg;
            asm volatile("" : "+r"(hu));
            hu = __shfl_sync(0xffffffffu, hu, 0);
            const uint32_t dP = (((sb + 3 * SLOT + hu * 8192) & 0x3FFFF) >> 4) | (512u << 16);
            const uint32_t dV = (((sb + 5 * SLOT + hu * 4096) & 0x3FFFF) >> 4) | (((SM_SD - 5 * SLOT - hu * 4096) >> 4) << 16);
            float kva[20];
            wgmma_fence();
#pragma unroll
            for (int ks = 0; ks < 8; ++ks)
              wgmma_n40_tt(kva, desc64(dP + (ks >> 2) * 3072 + (ks & 3) * 128, 0x40000040u),
                           desc64(dV + (ks >> 2) * (3072u - (2816u << 16)) + (ks & 3) * 64, 0x80000020u), ks != 0);
            wgmma_commit();
            wgmma_wait<0>();
            nbar_dyn(3 + wg, 128);
            PROFT(tid_ == 128, layer * 16 + 12);
#pragma unroll
            for (int i = 0; i < 4; ++i)
              sts128(sb + (3 + hp) * SLOT + (cw * 128 + i * 32 + lane) * 16,
                     make_uint4(__float_as_uint(kva[4 * i]), __float_as_uint(kva[4 * i + 1]), __float_as_uint(kva[4 * i + 2]), __float_as_uint(kva[4 * i + 3])));
            if (t == 0) {
              sts_f(sb + SM_AP + hp * 512 + (cw * 8 + gq) * 8, kva[16]);
              sts_f(sb + SM_AP + hp * 512 + (cw * 8 + gq) * 8 + 4, kva[18]);
            }
            fence_async_smem();
            __syncwarp();
            if (lane == 0) mbar_arrive(bar + B_KVDONE - hp * 32);
            if (elected && hp) release2(bar + B_E1);
            PROFT(tid_ == 128, layer * 16 + 3);
            continue;
          }
          PROFT(tid_ == 128 && hp == 0, layer * 16 + 10);
          mbar_wait(bar + B_KVDONE - 32, (layer >> 1) & 1);
          mbar_wait(bar + B_KVRDY - hp * 8, (layer >> 1) & 1);
          PROFT(tid_ == 128 && hp == 0, layer * 16 + 5);
          {
            uint4 u[4];
#pragma unroll
            for (int i = 0; i < 4; ++i) u[i] = lds128(sb + (3 + hp) * SLOT + (cw * 128 + i * 32 + lane) * 16);
            const float zz = lds_f(sb + SM_AP + hp * 512 + ((cw * 8 + (lane & 7)) * 2 + ((lane >> 3) & 1)) * 4);
#pragma unroll
            for (int i = 0; i < 4; i += 2)
              stsm_x4(sb + (5 + 3 * hp) * SLOT + rowo + (X ^ ((i & 2) << 4)),
                      pack_bf16(__uint_as_float(u[i].x), __uint_as_float(u[i].y)), pack_bf16(__uint_as_float(u[i].z), __uint_as_float(u[i].w)),
                      pack_bf16(__uint_as_float(u[i + 1].x), __uint_as_float(u[i + 1].y)), pack_bf16(__uint_as_float(u[i + 1].z), __uint_as_float(u[i + 1].w)));
            if (lane < 16) sts128(sb + (5 + 3 * hp) * SLOT + rowo + ((4 ^ (lane & 7)) << 4), make_uint4(pack_bf16(zz, 0.f), 0u, 0u, 0u));
          }
          fence_async_smem();
          nbar<1, 256>();
          PROFT(tid_ == 128 && hp == 1, layer * 16 + 4);
          float oa[2][20];
          const uint32_t dK = __shfl_sync(0xffffffffu, (((sb + (5 + 3 * hp) * SLOT) & 0x3FFFF) >> 4) | (512u << 16), 0);
          wgmma_fence();
#pragma unroll
          for (int ks = 0; ks < 4; ++ks) {
#pragma unroll
            for (int hh = 0; hh < 2; ++hh) wgmma_n40_rs(oa[hh], ph[hh][ks], D128(dK + hh * 512 + ks * 128), ks != 0);
          }
          wgmma_commit();
          if (hp == 0) {
            mbar_wait(bar + B_XOLD, 0);
#pragma unroll
            for (int jp = 0; jp < 8; ++jp)
              ldsm_x4(xo[4 * jp], xo[4 * jp + 1], xo[4 * jp + 2], xo[4 * jp + 3], sb + (XS + (jp >> 2)) * SLOT + rowo + (X ^ ((jp & 3) << 5)));
          }
          wgmma_wait<0>();
#pragma unroll
          for (int hh = 0; hh < 2; ++hh) {
            const float dn0 = __shfl_sync(0xffffffffu, oa[hh][16], lane & ~3), dn1 = __shfl_sync(0xffffffffu, oa[hh][18], lane & ~3);
            const float i0 = __fdividef(1.f, dn0 + 1e-6f), i1 = __fdividef(1.f, dn1 + 1e-6f);
            const uint32_t qad = sb + (3 + hp) * SLOT + rowo, hx = hh << 6;
#pragma unroll
            for (int np = 0; np < 2; ++np)
              stsm_x4(qad + (X ^ hx ^ (np << 5)),
                      pack_bf16(oa[hh][8 * np] * i0, oa[hh][8 * np + 1] * i0), pack_bf16(oa[hh][8 * np + 2] * i1, oa[hh][8 * np + 3] * i1),
                      pack_bf16(oa[hh][8 * np + 4] * i0, oa[hh][8 * np + 5] * i0), pack_bf16(oa[hh][8 * np + 6] * i1, oa[hh][8 * np + 7] * i1));
          }
          fence_async_smem();
          {
            __syncwarp();
            if (hp == 0 && lane == 0) release2(bar + B_E3);
            slab_out_half(sb + (3 + hp) * SLOT, g_o + (size_t)m0 * D_ + g * 128 + hp * 64, wrow0, lane);
            __syncwarp();
            if (lane == 0) mbar_arrive(bar + (hp ? B_ODONE : B_OH1));
          }
          if (hp) break;
        }
      }
      __syncwarp();
      PROFT(lane == 0 && layer == PL, 216 + cw);
      if (lane == 0) mbar_arrive(bar + B_EPI);
      PROFT(tid_ == 128, layer * 16 + 6);
    }
    {
      PHASE_CTX();
      const uint32_t wu = __shfl_sync(0xffffffffu, wg, 0);
      const uint32_t dA0 = (((sb + wu * 8192) & 0x3FFFF) >> 4) | (1u << 16), dB0 = ((sb & 0x3FFFF) >> 4) | (512u << 16);
#pragma unroll
      for (int i = 0; i < 32; ++i) { acc[128 + 2 * i] = bf_lo(xo[i]); acc[129 + 2 * i] = bf_hi(xo[i]); }
      nbar_dyn(3 + wg, 128);
      uint64_t ta = (layer & 1) ? WO_A1 : WO_A0, tw = (layer & 1) ? WO_B1 : WO_B0;
#pragma unroll 1
      for (int i = 0; i < 16; ++i) {
        bool rel = i > 0 && i < 12;
        if (DRY && rel && !__all_sync(0xffffffffu, mbar_test_wait(bar + B_FULLT + i * 8, layer & 1))) {
          wgmma_wait<0>();
          if (elected) release2(bar + B_CONS + (i - 1) * 8);
          rel = false;
        }
        mbar_wait(bar + B_FULLT + i * 8, layer & 1);
        PROFT(tid_ == 128 && layer == PL, 160 + i);
        const uint32_t da = dA0 + ((uint32_t)ta & 15) * 1024, db = dB0 + ((uint32_t)tw & 15) * 1024;
        ta >>= 4; tw >>= 4;
        wgmma_fence();
#pragma unroll
        for (int k = 0; k < 4; ++k) wgmma_n128(acc, D128(da + k * 2), D128(db + k * 128), 1);
        wgmma_commit();
        if (i == 0) {
          if (elected) {
            if ((layer & 1) && wu) release2(bar + B_E1);
            release2(bar + B_E2);
          }
        } else {
          wgmma_wait<1>();
          if (elected && rel) release2(bar + B_CONS + (i - 1) * 8);
          if (elected && (unsigned)(i - 13) < 2u && layer + 1 < NLAYERS) release2(bar + B_EMPTYS + (i - 13) * 8);
        }
      }
      const bool last = layer == NLAYERS - 1;
      wgmma_wait<0>();
#pragma unroll
      for (int i = 128; i < 192; ++i) asm volatile("" : "+f"(acc[i]) :: "memory");
      if (elected && !last) release2(bar + B_EMPTYS + 16);
      PROFT(tid_ == 128, layer * 16 + 7);
#pragma unroll
      for (int jp = 0; jp < 4; ++jp)
        stsm_x4(sb + XS * SLOT + rowo + (X ^ (jp << 5)),
                pack_bf16(acc[128 + 8 * jp], acc[129 + 8 * jp]), pack_bf16(acc[130 + 8 * jp], acc[131 + 8 * jp]),
                pack_bf16(acc[132 + 8 * jp], acc[133 + 8 * jp]), pack_bf16(acc[134 + 8 * jp], acc[135 + 8 * jp]));
      if (last) {
        __syncwarp();
        slab_out_half(sb + XS * SLOT, c.out + (size_t)m0 * D_ + g * 128, wrow0, lane);
        X_H1();
        __syncwarp();
        slab_out_half(sb + (XS + 1) * SLOT, c.out + (size_t)m0 * D_ + g * 128 + 64, wrow0, lane);
        __syncwarp();
        if (lane == 0) mbar_arrive(bar + B_XDONE);
        PROFT(tid_ == 128, layer * 16 + 24);
        break;
      }
      fence_async_smem();
      __syncwarp();
      slab_out_half(sb + XS * SLOT, g_x + (size_t)m0 * D_ + g * 128, wrow0, lane);
      __syncwarp();
      if (lane == 0) mbar_arrive(bar + B_XH0);
      nbar_dyn(3 + wu, 128);
    }
  }
}

__device__ __forceinline__ void flag_fetch(uint32_t bar, const unsigned int* f) {
  asm volatile("{\n.reg .pred p;\nelect.sync _|p, 0xffffffff;\n@p mbarrier.expect_tx.relaxed.cta.shared::cta.b64 [%2], 64;\n"
               "@p cp.async.bulk.shared::cluster.global.mbarrier::complete_tx::bytes [%0], [%1], 64, [%2];\n}\n"
               ::"r"(bar + B_FLG), "l"(f), "r"(bar + 128) : "memory");
}
__device__ __forceinline__ int kblock0(int i, int g) {
  const int j = i >> 1, p = max(g, NCOM) + j - NCOM;
  return (j < NCOM ? j : p < 8 ? p : p - 8 + NCOM) * 2 + (i & 1);
}

#define WOORD 0xFDB9753ECA864210ull
__device__ __forceinline__ int wo_kblock(int m, int g) { return (2 * g + (int)((WOORD >> (4 * m)) & 15)) & 15; }

__global__ void __cluster_dims__(2, 1, 1) __launch_bounds__(384, 1)
mega_kernel(const __grid_constant__ CUtensorMap tm_x0, const __grid_constant__ CUtensorMap tm_x,
            const __grid_constant__ CUtensorMap tm_o,
            const __grid_constant__ CUtensorMap tm_wA, const __grid_constant__ CUtensorMap tm_wB,
            const __grid_constant__ CUtensorMap tm_woA, const __grid_constant__ CUtensorMap tm_woB,
            const bf16* __restrict__ wA, const bf16* __restrict__ wB,
            const bf16* __restrict__ wphi, bf16* __restrict__ out) {
  extern __shared__ uint8_t smem_raw[];
  const uint32_t sb = (smem_u32(smem_raw) + 1023u) & ~1023u;
  const uint32_t bar = sb + SM_BAR;
  const int warp = __shfl_sync(0xffffffffu, threadIdx.x >> 5, 0), lane = threadIdx.x & 31;
  const int cr = blockIdx.x & 1;
  const int g = (blockIdx.x >> 1) & 7;
  const int rb = (blockIdx.x >> 4) * 2 + cr;
  const int m0 = rb * 128;

  if (warp < 4) {
    asm volatile("setmaxnreg.dec.sync.aligned.u32 40;");
    asm volatile("barrier.cluster.arrive.relaxed.aligned;" ::: "memory");
    const unsigned int epoch = warp ? ld_relaxed(&g_epoch) : 0u;
    if (warp) cluster_wait();
    unsigned int xbase = epoch * NLAYERS;
    const unsigned int cbase = epoch * 16u;
    auto wo_a = [&](int layer) {
      uint64_t ts = ((layer & 1) ? WO_A1 : WO_A0) >> 8, td = ((layer & 1) ? WO_DA1 : WO_DA0) >> 8, tk = WOORD >> 8;
      uint32_t ready = 0u;
#pragma unroll 1
      for (int m = 2; m < 16; ++m) {
        const int kb = (2 * g + (uint32_t)tk) & 15;
        uint32_t dst = sb + ((uint32_t)ts & 15) * SLOT, fb = bar + B_FULLT + m * 8, eb = bar + B_CONS + ((uint32_t)td & 15) * 8;
        int kc = kb * 64;
        ts >>= 4; td >>= 4; tk >>= 4;
        if (!((ready >> kb) & 1)) {
          PROFT(m == 2 && lane == 0, 64 + layer * 16 + 2);
          if (EP && m > EP) {
            uint32_t n = 0;
#pragma unroll 1
            while (true) {
              ready |= __ballot_sync(0xffffffffu, (int)(lds_vol(bar + B_FLG + (lane & 15) * 4) - (xbase + layer + 1)) >= 0);
              if (((ready >> kb) & 1) || ++n > (1u << 20)) break;
              if ((n & 3) == 0) flag_fetch(bar, g_of + rb * 32);
              __nanosleep(PSL);
            }
          }
          src_wait<0>(g_of + rb * 32, xbase + layer + 1, 1u << kb, ready, lane);
          fence_async_all();
        }
        if (m == ((layer & 1) ? GAB : GAA)) mbar_wait_u(bar + B_OF, layer & 1);
        asm volatile("" : "+r"(dst), "+r"(fb), "+r"(eb), "+r"(kc));
        mbar_wait_u(eb, layer & 1);
        tma_2d_e(dst, &tm_o, kc, m0, fb);
        if (EP && m >= EP && (ready & 0xFFFFu) != 0xFFFFu) flag_fetch(bar, g_of + rb * 32);
        PROFT(lane == 0 && layer == PL, 176 + m);
      }
    };
    auto wo_w = [&](int layer) {
      const CUtensorMap* tx = layer == 0 ? &tm_x0 : &tm_x;
      const CUtensorMap* two = (layer & 1) ? &tm_woB : &tm_woA;
      uint64_t ts = (layer & 1) ? WO_B1 : WO_B0, td = (layer & 1) ? WO_DB1 : WO_DB0, tk = WOORD;
#pragma unroll 1
      for (int m = 0; m < 16; ++m) {
        uint32_t dst = sb + ((uint32_t)ts & 15) * SLOT + cr * 8192, fb = bar + B_FULLT + m * 8, eb = bar + B_CONS + ((uint32_t)td & 15) * 8;
        int kc = ((2 * g + (uint32_t)tk) & 15) * 64;
        ts >>= 4; td >>= 4; tk >>= 4;
        if (m == ((layer & 1) ? GWB : GWA)) mbar_wait_u(bar + B_OF, layer & 1);
        asm volatile("" : "+r"(dst), "+r"(fb), "+r"(eb), "+r"(kc));
        mbar_wait_u(eb, layer & 1);
        tma_2d_mc_e(dst, two, g * 128 + cr * 64, kc, fb);
        expect_tx_e(fb, m < 2 ? 16384 : 32768);
        PROFT(lane == 0 && layer == PL, 144 + m);
        if (m == 0) {
          fence_async_all();
          expect_tx_e(bar + B_XOLD, 32768);
          tma_2d_e(sb + XS * SLOT, tx, g * 128, m0, bar + B_XOLD);
          tma_2d_e(sb + (XS + 1) * SLOT, tx, g * 128 + 64, m0, bar + B_XOLD);
        }
      }
    };
    auto kv_fetch = [&](int layer, int hp) {
      const float* kvl = g_kv + (g * 2 + (layer >> 1)) * 8448;
      flag_wait(&g_kvflag[hp * 8 + g].v, epoch * (16u * ((NLAYERS + 1) / 2)) + 16u * ((layer >> 1) + 1));
      fence_async_all();
      mbar_expect_tx(bar + B_KVRDY - hp * 8, 16896);
      bulk_load(sb + (3 + hp) * SLOT, kvl + hp * 4096, 16384, bar + B_KVRDY - hp * 8);
      bulk_load(sb + SM_AP + hp * 512, kvl + 8192 + hp * 128, 512, bar + B_KVRDY - hp * 8);
    };
    if (warp == 0) {
      cluster_wait();
      PROFT(lane == 0, 125);
#pragma unroll 1
      for (int layer = 0; layer < NLAYERS; ++layer) {
        const CUtensorMap* tx = layer == 0 ? &tm_x0 : &tm_x;
        const CUtensorMap* tw = (layer & 1) ? &tm_wB : &tm_wA;
        uint32_t s = layer == 0, u = 0, ready = layer == 0 ? 0xFFFFu : 0u;
#pragma unroll 1
        for (int i = s; i < 16; ++i) {
          const int kb = layer == 0 ? kblock0(i, g) : wo_kblock(i, g), kc = kb * 64;
          const uint32_t fb = bar + B_FULLS + s * 8;
          const uint32_t kd = sb + (((QK >> (4 * s)) & 15) + cr) * SLOT, qd = sb + ((QQ >> (4 * s)) & 15) * SLOT + cr * 8192;
          const uint32_t need = 1u << kb;
          const bool ext = i >= 2 || layer == 0, early = ext && (ready & need) == need;
          mbar_wait_u(bar + B_EMPTYS + s * 8, (u + (s ? layer : 0) + 1) & 1);
          if (early) tma_2d_e(sb + ((QA >> (4 * s)) & 15) * SLOT, tx, kc, m0, fb);
          tma_2d_mc_e(kd, tw, 1024 + cr * 1024 + g * 128, kc, fb);
          tma_2d_mc_e(kd + 8192, tw, 1024 + cr * 1024 + g * 128 + 64, kc, fb);
          tma_2d_mc_e(qd, tw, g * 128 + cr * 64, kc, fb);
          expect_tx_e(fb, ext ? 65536 : 49152);
          PROFT(lane == 0 && layer == 0 && i == 1, 31);
          if (layer == 0 && i == 2) {
            mbar_wait_u(bar + B_FULLS, 0);
            tma_pf_e(&tm_x0, g * 128, m0);
            tma_pf_e(&tm_x0, g * 128 + 64, m0);
          }
          if (layer < 2 && i >= PFS) {
            const int j = i - PFS;
            if (j < 2) tma_pf_e(layer ? &tm_woB : &tm_woA, g * 128 + j * 64, rb * 64);
            else if (j < 8 && layer == 0) tma_pf_e(&tm_wB, ((j >> 1) - 1) * 1024 + g * 128 + (j & 1) * 64, rb * 64);
          }
          if (ext && !early) {
            PROFT(i == 2 && lane == 0, 64 + layer * 16 + 0);
            src_wait<0>(g_xf + rb * 32, xbase + layer + 1, need, ready, lane);
            PROFT(i == 2 && lane == 0, 64 + layer * 16 + 1);
            fence_async_all();
            tma_2d_e(sb + ((QA >> (4 * s)) & 15) * SLOT, tx, kc, m0, fb);
          }
          if (++s == 3) { s = 0; ++u; }
        }
        if (layer == 0) xbase = ld_relaxed(&g_epoch) * NLAYERS;
        wo_a(layer);
      }
    } else {
      if (warp >= 2) {
        const int h2 = threadIdx.x - 64;
#pragma unroll 1
        for (int i = h2; i < 512; i += 64)
          asm volatile("cp.async.cg.shared.global [%0], [%1], 16;" ::"r"(sb + SM_WPHI + (i >> 2) * 80 + (i & 3) * 16), "l"(wphi + (size_t)g * 4096 + i * 8) : "memory");
        sts128(sb + SM_SD + h2 * 128 + (h2 & 3) * 16, make_uint4(0u, 0u, 0u, 0u));
        sts128(sb + SM_SD + h2 * 128 + 64 + (h2 & 3) * 16, make_uint4(0u, 0u, 0u, 0u));
        if (h2 < 16) sts_f(sb + SM_RS + h2 * 4, 0.f);
        if (h2 < 16) sts_f(bar + B_FLG + h2 * 4, __uint_as_float(xbase));
        if (h2 == 0) sts_f(sb + SM_EPOCH, __uint_as_float(epoch));
        if (rb >= CG0) mbar_wait_u(bar + B_FULLS + (rb >= CG1 ? 8 : 0), 0);
        if (CPF && h2 < 4) asm volatile("cp.async.bulk.prefetch.tensor.2d.L2.global.tile [%0, {%1, %2}];" ::"l"(&tm_wA), "r"((h2 & 2) * 1024 + g * 128 + (h2 & 1) * 64), "r"(rb * 64) : "memory");
#pragma unroll 1
        for (int wi = 0; wi < 3; ++wi) {
          float sA[8];
          colsum_load(wA, rb, g, warp - 2 + 2 * wi, lane, sb + SM_BP + (warp - 2) * 6144, sA);
          colsum_red(g_cs + (epoch & 1) * 6144, g, warp - 2 + 2 * wi, lane, sA);
        }
#pragma unroll 1
        for (int i = h2; i < 264; i += 64) reinterpret_cast<float4*>(g_kv)[(g * 16 + rb) * 264 + i] = make_float4(0.f, 0.f, 0.f, 0.f);
        fence_async_all();
        nbar<5, 64>();
        if (h2 == 0) flag_add(&g_csflag[g].v);
        PROFT(h2 == 0, 242);
      }
      if (warp == 1) {
        if (lane >= 27) {
          const CUtensorMap* tm = lane == 27 ? &tm_o : lane == 28 ? &tm_wB : lane == 29 ? &tm_woA : lane == 30 ? &tm_woB : &tm_x;
          asm volatile("prefetch.tensormap [%0];" ::"l"(tm) : "memory");
        }
        if (lane == 0) {
#pragma unroll 1
          for (int e = 0;; ++e) {
            if (e > 0 && e < NLAYERS) {
              mbar_wait(bar + B_XH0, (e - 1) & 1);
              flag_set(g_xf + rb * 32 + 2 * g, xbase + e + 1);
            }
            mbar_wait(bar + B_XDONE, e & 1);
            PROFT(e < 4, 64 + e * 16 + 4);
            if (e == NLAYERS) {
              if (blockIdx.x == 0) g_epoch = epoch + 1;
              break;
            }
            PROFT(e < 4, 64 + e * 16 + 5);
            flag_set(g_xf + rb * 32 + 2 * g + 1, xbase + e + 1);
            PROFT(e < 4, 64 + e * 16 + 7);
            if ((e & 1) == 0) {
              float* kvl = g_kv + (g * 2 + (e >> 1)) * 8448;
#pragma unroll 1
              for (int hp = 0; hp < 2; ++hp) {
                mbar_wait(bar + B_KVDONE - hp * 32, (e >> 1) & 1);
                bulk_red_add(kvl + hp * 4096, sb + (3 + hp) * SLOT, 16384);
                bulk_red_add(kvl + 8192 + hp * 128, sb + SM_AP + hp * 512, 512);
                bulk_commit();
                PROFT(e < 4, 64 + e * 16 + 6);
                bulk_wait0();
                PROFT(e < 4, 64 + e * 16 + 10);
                fence_async_all();
                flag_add(&g_kvflag[hp * 8 + g].v);
              }
            }
            mbar_wait(bar + B_OH1, e & 1);
            flag_set(g_of + rb * 32 + 2 * g, xbase + e + 1);
            PROFT(e < 4, 64 + e * 16 + 9);
            mbar_wait(bar + B_ODONE, e & 1);
            PROFT(e < 4, 64 + e * 16 + 8);
            flag_set(g_of + rb * 32 + 2 * g + 1, xbase + e + 1);
            release2(bar + B_OF);
            PROFT(e < 4, 64 + e * 16 + 11);
          }
        }
      } else {
        const int h2 = threadIdx.x - 64;
        const float* cs = g_cs + (epoch & 1) * 6144;
#pragma unroll 1
        for (int layer = 0; layer < NLAYERS; ++layer) {
          if (warp == 2 && layer < 2) {
            if (lane == 0) flag_wait_t<CSLP>(&g_csflag[layer * 8 + g].v, cbase + 16u);
            __syncwarp();
            float4 a[3];
#pragma unroll
            for (int i = 0; i < 3; ++i) a[i] = __ldcg(reinterpret_cast<const float4*>(cs + layer * 3072 + g * 384) + i * 32 + lane);
#pragma unroll 1
            for (int i = 0; i < 3; ++i) {
              const float av[4] = {a[0].x, a[0].y, a[0].z, a[0].w};
              a[0] = a[1]; a[1] = a[2];
#pragma unroll
              for (int j = 0; j < 4; ++j) {
                const float c1 = bf16r(av[j]), c2 = bf16r(av[j] - c1), c3 = (av[j] - c1) - c2;
                sts128(sb + SM_BP + layer * 6144 + ((i * 32 + lane) * 4 + j) * 16, make_uint4(pack_bf16(c1, c2), pack_bf16(c3, 0.f), 0u, 0u));
              }
            }
            fence_async_smem();
            __syncwarp();
            if (lane == 0) mbar_arrive(bar + (layer ? B_CS2 : B_CS));
            PROFT(lane == 0, 64 + layer * 16 + 12);
            if (layer == 0) {
              uint4* hz = g_halo + (size_t)((epoch & 1) ^ 1) * (2 * 128 * 512) + blockIdx.x * 1024;
#pragma unroll 2
              for (int i = lane; i < 1024; i += 32) hz[i] = make_uint4(0u, 0u, 0u, 0u);
              if (lane < 12) reinterpret_cast<float4*>(g_cs + ((epoch & 1) ^ 1) * 6144 + blockIdx.x * 48)[lane] = make_float4(0.f, 0.f, 0.f, 0.f);
              g_stats[(2 + (lane >> 4)) * S_ + m0 + g * 16 + (lane & 15)] = make_float2(0.f, 0.f);
            }
          }
          if (warp == 3) {
            const bool hal = (layer & 1) && rb > 0;
            {
              uint32_t rdy = 0u;
              src_wait<256>(g_xf + rb * 32, xbase + layer + 1, 0xAAAAu, rdy, lane);
              rdy = 0u;
              if (hal) src_wait<256>(g_xf + (rb - 1) * 32, xbase + layer + 1, 0xAAAAu, rdy, lane);
            }
            float2 u[5];
            const float2* sp = g_stats + layer * S_ + m0 + lane;
#pragma unroll
            for (int i = 0; i < 4; ++i) u[i] = __ldcg(sp + i * 32);
            u[4] = __ldcg(hal ? sp - 16 : sp);
            if (layer == 3) g_stats[(lane >> 4) * S_ + m0 + g * 16 + (lane & 15)] = make_float2(0.f, 0.f);
#pragma unroll 1
            for (int i = 0; i < (hal ? 5 : 4); ++i) {
              const int r = i < 4 ? 16 + i * 32 + lane : lane;
              const float sum = u[0].x, sq = u[0].y;
              u[0] = u[1]; u[1] = u[2]; u[2] = u[3]; u[3] = u[4];
              const float mean = sum * (1.f / D_);
              const float var = fmaxf(fmaf(-sum, mean, sq) * (1.f / D_), 0.f);
              const float sd = bf16r(sqrtf(bf16r(bf16r(var) + 1e-5f)));
              sts_f(sb + SM_RS + r * 4, 1.f / sd);
              if (i < 4) {
                const float hm = -0.5f * bf16r(mean);
                sts16(sb + SM_SD + (r - 16) * 64 + ((r >> 1) & 3) * 16, __float_as_uint(sd) >> 16);
                sts128(sb + SM_AP + (r - 16) * 16, make_uint4(pack_bf16(hm, hm), pack_bf16(hm, 0.f), 0u, 0u));
              }
            }
            fence_async_smem();
            __syncwarp();
            if (lane == 0) mbar_arrive(bar + B_STAT);
            PROFT(lane == 0, 64 + layer * 16 + 14);
            wo_w(__shfl_sync(0xffffffffu, layer, 0));
          } else if (!(layer & 1)) {
            if (lane == 0) {
#pragma unroll 1
              for (int hp = 0; hp < 2; ++hp) {
                mbar_wait(bar + B_KVDONE - hp * 32, (layer >> 1) & 1);
                kv_fetch(layer, hp);
                PROFT(hp == 0, 64 + layer * 16 + 15);
              }
            }
            __syncwarp();
          }
          if (layer == 0 && warp == 2) {
#pragma unroll 1
            for (int wi = 0; wi < 6; ++wi) {
              float sB[8];
              colsum_load(wB, rb, g, wi, lane, sb + SM_BP + 6144, sB);
              colsum_red(g_cs + (epoch & 1) * 6144 + 3072, g, wi, lane, sB);
            }
            __syncwarp();
            if (lane == 0) flag_add(&g_csflag[8 + g].v);
            PROFT(h2 == 0, 64 + 13);
          }
        }
      }
    }
    __syncwarp();
    asm volatile("barrier.cluster.arrive.relaxed.aligned;\nbarrier.cluster.wait.aligned;\n" ::: "memory");
  } else {
    if (warp == 5) {
      if (lane == 0) {
        mbar_init(bar + B_FULLS, 1);
        asm volatile("fence.mbarrier_init.release.cluster;" ::: "memory");
      }
      __syncwarp();
      expect_tx_e(bar + B_FULLS, 65536);
      tma_2d_e(sb + XS * SLOT, &tm_x0, 0, m0, bar + B_FULLS);
#pragma unroll
      for (int j = 0; j < 6; ++j)
        tma_2d_e(sb + (j < 4 ? j + 4 : j - 2) * 8192, &tm_wA, (j < 4 ? 1024 + (j >> 1) * 1024 : 0) + g * 128 + (j & 1) * 64, 0, bar + B_FULLS);
      PROFT(lane == 0, 241);
    }
    if (lane < 8 && warp != 5 && threadIdx.x != 128) {
      const int i = (warp - 4) * 8 + lane;
      mbar_init(bar + i * 8, i < 32 ? 1u << ((BAR_CNT >> (2 * i)) & 3) : i < 48 ? 1u : (i == 59 || i == 60) ? 16u : i < 63 ? 4u : 8u);
      asm volatile("fence.mbarrier_init.release.cluster;" ::: "memory");
    }
    __syncwarp();
    asm volatile("barrier.cluster.arrive.relaxed.aligned;" ::: "memory");
    asm volatile("setmaxnreg.inc.sync.aligned.u32 232;");
    cluster_wait();
    PROFT(threadIdx.x == 128, 0);
    Ctx c; c.sb = sb; c.g = g; c.rb = rb; c.cu = warp - 4; c.out = out;
    consumer(c);
    asm volatile("bar.warp.sync 0xffffffff;\nbarrier.cluster.arrive.relaxed.aligned;\nbarrier.cluster.wait.aligned;\n" ::: "memory");
  }
}

typedef CUresult (*PFN_encodeTiled)(CUtensorMap*, CUtensorMapDataType, cuuint32_t, void*, const cuuint64_t*, const cuuint64_t*,
                                    const cuuint32_t*, const cuuint32_t*, CUtensorMapInterleave, CUtensorMapSwizzle,
                                    CUtensorMapL2promotion, CUtensorMapFloatOOBfill);

static CUtensorMap make_map(PFN_encodeTiled enc, const void* ptr, uint64_t cols, uint64_t rows, uint32_t box_c, uint32_t box_r, uint32_t nb = 1) {
  CUtensorMap m;
  cuuint64_t dims[3] = {nb > 1 ? box_c : cols, rows, cols / box_c};
  cuuint64_t strides[2] = {cols * 2, box_c * 2};
  cuuint32_t box[3] = {box_c, box_r, nb};
  cuuint32_t es[3] = {1, 1, 1};
  CUresult r = enc(&m, CU_TENSOR_MAP_DATA_TYPE_BFLOAT16, nb > 1 ? 3 : 2, const_cast<void*>(ptr), dims, strides, box, es, CU_TENSOR_MAP_INTERLEAVE_NONE,
      CU_TENSOR_MAP_SWIZZLE_128B, CU_TENSOR_MAP_L2_PROMOTION_L2_256B, CU_TENSOR_MAP_FLOAT_OOB_FILL_NONE);
  (void)r;
  return m;
}

extern "C" void kernel_launch(void* const* d_in, const int* in_sizes, int n_in, void* d_out, int out_size) {
  const bf16* A_x = (const bf16*)d_in[0];
  const bf16* A_wqkv = (const bf16*)d_in[1];
  const bf16* A_wphi = (const bf16*)d_in[2];
  const bf16* A_wo = (const bf16*)d_in[3];
  const bf16* B_wqkv = (const bf16*)d_in[5];
  const bf16* B_wo = (const bf16*)d_in[6];
  bf16* out = (bf16*)d_out;

  static PFN_encodeTiled enc = nullptr;
  static bf16 *p_x, *p_o;
  if (!enc) {
    void* fn = nullptr; cudaDriverEntryPointQueryResult qr;
    cudaGetDriverEntryPoint("cuTensorMapEncodeTiled", &fn, cudaEnableDefault, &qr);
    enc = (PFN_encodeTiled)fn;
    cudaGetSymbolAddress((void**)&p_x, g_x);
    cudaGetSymbolAddress((void**)&p_o, g_o);
    cudaFuncSetAttribute(mega_kernel, cudaFuncAttributeMaxDynamicSharedMemorySize, SM_TOTAL);
  }
  CUtensorMap tm_x0 = make_map(enc, A_x, 1024, 2048, 64, 128);
  CUtensorMap tm_x = make_map(enc, p_x, 1024, 2048, 64, 128);
  CUtensorMap tm_o = make_map(enc, p_o, 1024, 2048, 64, 128);
  CUtensorMap tm_wA = make_map(enc, A_wqkv, 3072, 1024, 64, 64);
  CUtensorMap tm_wB = make_map(enc, B_wqkv, 3072, 1024, 64, 64);
  CUtensorMap tm_woA = make_map(enc, A_wo, 1024, 1024, 64, 64);
  CUtensorMap tm_woB = make_map(enc, B_wo, 1024, 1024, 64, 64);
  mega_kernel<<<128, 384, SM_TOTAL, cudaStreamPerThread>>>(tm_x0, tm_x, tm_o, tm_wA, tm_wB, tm_woA, tm_woB,
                                                           A_wqkv, B_wqkv, A_wphi, out);
}
```

```cpp
#include <cuda_runtime.h>
#include <cuda_bf16.h>
#include <cuda.h>
#include <stdint.h>

typedef __nv_bfloat16 bf16;

constexpr int S_ = 2048, D_ = 1024;

struct __align__(128) Flag { unsigned int v; unsigned int pad[31]; };
__device__ __align__(1024) bf16 g_x[S_ * D_];
__device__ __align__(1024) bf16 g_o[S_ * D_];
__device__ __align__(1024) uint4 g_halo[2 * 2 * 128 * 512];
__device__ __align__(1024) uint4 g_kv[8 * 2 * 2 * 1280];
__device__ __align__(1024) float2 g_stats[4 * S_];
__device__ __align__(1024) float g_cs[2 * 2 * 3072];
__device__ Flag g_csflag[16];
__device__ __align__(128) unsigned int g_xf[16 * 32], g_of[16 * 32];
__device__ unsigned int g_epoch, g_err;
#define PROFT(cond, idx) asm volatile("" ::: "memory")

__device__ __forceinline__ uint32_t smem_u32(const void* p) { return (uint32_t)__cvta_generic_to_shared(p); }
__device__ __forceinline__ void mbar_init(uint32_t bar, uint32_t count) {
  asm volatile("mbarrier.init.shared::cta.b64 [%0], %1;" ::"r"(bar), "r"(count) : "memory");
}
__device__ __forceinline__ void mbar_expect_tx(uint32_t bar, uint32_t bytes) {
  asm volatile("mbarrier.arrive.expect_tx.shared::cta.b64 _, [%0], %1;" ::"r"(bar), "r"(bytes) : "memory");
}
__device__ __forceinline__ void mbar_arrive(uint32_t bar) {
  asm volatile("mbarrier.arrive.shared::cta.b64 _, [%0];" ::"r"(bar) : "memory");
}
__device__ __forceinline__ bool mbar_try_wait(uint32_t bar, uint32_t parity) {
  uint32_t ok;
  asm volatile("{\n.reg .pred p;\nmbarrier.try_wait.parity.shared::cta.b64 p, [%1], %2;\nselp.b32 %0, 1, 0, p;\n}\n"
               : "=r"(ok) : "r"(bar), "r"(parity) : "memory");
  return ok != 0;
}
__device__ __forceinline__ bool mbar_test_wait(uint32_t bar, uint32_t parity) {
  uint32_t ok;
  asm volatile("{\n.reg .pred p;\nmbarrier.test_wait.parity.shared::cta.b64 p, [%1], %2;\nselp.b32 %0, 1, 0, p;\n}\n"
               : "=r"(ok) : "r"(bar), "r"(parity) : "memory");
  return ok != 0;
}
__device__ __forceinline__ uint64_t gtimer() {
  uint64_t t; asm volatile("mov.u64 %0, %globaltimer;" : "=l"(t)); return t;
}
__device__ __forceinline__ void mbar_wait(uint32_t bar, uint32_t parity) {
  uint32_t n = 0;
#pragma unroll 1
  while (!mbar_try_wait(bar, parity)) {
    if (++n > (1u << 22)) { g_err = 1u; break; }
  }
}
__device__ __forceinline__ unsigned int ld_acquire(const unsigned int* p) {
  unsigned int v; asm volatile("ld.acquire.gpu.global.u32 %0, [%1];" : "=r"(v) : "l"(p) : "memory"); return v;
}
__device__ __forceinline__ void flag_add(unsigned int* p) {
  asm volatile("red.release.gpu.global.add.u32 [%0], 1;" ::"l"(p) : "memory");
}
__device__ __forceinline__ void flag_set(unsigned int* p, unsigned int v) {
  asm volatile("st.release.gpu.global.u32 [%0], %1;" ::"l"(p), "r"(v) : "memory");
}
template <int SLEEP>
__device__ __forceinline__ void src_wait(const unsigned int* f, unsigned int target, uint32_t need, uint32_t& ready, int lane) {
  uint32_t n = 0;
#pragma unroll 1
  while ((ready & need) != need) {
    const unsigned int v = ld_acquire(f + (lane & 15));
    ready = __ballot_sync(0xffffffffu, (int)(v - target) >= 0);
    if (SLEEP) { if ((ready & need) != need) __nanosleep(SLEEP); }
    if (++n > (1u << 20)) { g_err = 3u; break; }
  }
  __syncwarp();
}
__device__ __forceinline__ unsigned int ld_relaxed(const unsigned int* p) {
  unsigned int v; asm volatile("ld.relaxed.gpu.global.u32 %0, [%1];" : "=r"(v) : "l"(p) : "memory"); return v;
}
__device__ __forceinline__ uint4 ld_relaxed4(const uint4* p) {
  uint4 v; asm volatile("ld.relaxed.gpu.global.v4.u32 {%0,%1,%2,%3}, [%4];" : "=r"(v.x), "=r"(v.y), "=r"(v.z), "=r"(v.w) : "l"(p) : "memory"); return v;
}
__device__ __forceinline__ void st_relaxed4(uint4* p, uint32_t a, uint32_t b, uint32_t c, uint32_t d) {
  asm volatile("st.relaxed.gpu.global.v4.u32 [%0], {%1,%2,%3,%4};" ::"l"(p), "r"(a), "r"(b), "r"(c), "r"(d) : "memory");
}
template <int SLEEP>
__device__ __forceinline__ void flag_wait_t(const unsigned int* p, unsigned int target) {
  uint32_t n = 0;
#pragma unroll 1
  while ((int)(ld_acquire(p) - target) < 0) {
    if (SLEEP) __nanosleep(SLEEP);
    if (++n > (1u << 20)) { g_err = 2u; break; }
  }
}
__device__ __forceinline__ void flag_wait(const unsigned int* p, unsigned int target) { flag_wait_t<0>(p, target); }
__device__ __forceinline__ void flag_wait_slow(const unsigned int* p, unsigned int target) { flag_wait_t<256>(p, target); }
__device__ __forceinline__ void tma_load_2d(uint32_t dst, const CUtensorMap* tm, int c0, int c1, uint32_t bar) {
  asm volatile("cp.async.bulk.tensor.2d.shared::cluster.global.mbarrier::complete_tx::bytes [%0], [%1, {%2, %3}], [%4];"
               ::"r"(dst), "l"(tm), "r"(c0), "r"(c1), "r"(bar) : "memory");
}
__device__ __forceinline__ void tma_load_2d_mc(uint32_t dst, const CUtensorMap* tm, int c0, int c1, uint32_t bar, uint16_t mask) {
  asm volatile("cp.async.bulk.tensor.2d.shared::cluster.global.mbarrier::complete_tx::bytes.multicast::cluster [%0], [%1, {%2, %3}], [%4], %5;"
               ::"r"(dst), "l"(tm), "r"(c0), "r"(c1), "r"(bar), "h"(mask) : "memory");
}
__device__ __forceinline__ void mbar_wait_u(uint32_t bar, uint32_t parity) {
  uint32_t n = 0;
#pragma unroll 1
  while (!__all_sync(0xffffffffu, mbar_try_wait(bar, parity))) {
    if (++n > (1u << 22)) { g_err = 1u; break; }
  }
}
__device__ __forceinline__ void expect_tx_e(uint32_t bar, uint32_t bytes) {
  asm volatile("{\n.reg .pred p;\nelect.sync _|p, 0xffffffff;\n@p mbarrier.arrive.expect_tx.shared::cta.b64 _, [%0], %1;\n}\n" ::"r"(bar), "r"(bytes) : "memory");
}
__device__ __forceinline__ void tma_2d_e(uint32_t dst, const CUtensorMap* tm, int c0, int c1, uint32_t bar) {
  asm volatile("{\n.reg .pred p;\nelect.sync _|p, 0xffffffff;\n"
               "@p cp.async.bulk.tensor.2d.shared::cluster.global.mbarrier::complete_tx::bytes [%0], [%1, {%2, %3}], [%4];\n}\n"
               ::"r"(dst), "l"(tm), "r"(c0), "r"(c1), "r"(bar) : "memory");
}
__device__ __forceinline__ void tma_2d_mc_e(uint32_t dst, const CUtensorMap* tm, int c0, int c1, uint32_t bar) {
  asm volatile("{\n.reg .pred p;\nelect.sync _|p, 0xffffffff;\n"
               "@p cp.async.bulk.tensor.2d.shared::cluster.global.mbarrier::complete_tx::bytes.multicast::cluster [%0], [%1, {%2, %3}], [%4], %5;\n}\n"
               ::"r"(dst), "l"(tm), "r"(c0), "r"(c1), "r"(bar), "h"((uint16_t)3) : "memory");
}
__device__ __forceinline__ void tma_pf_e(const CUtensorMap* tm, int c0, int c1) {
  asm volatile("{\n.reg .pred p;\nelect.sync _|p, 0xffffffff;\n"
               "@p cp.async.bulk.prefetch.tensor.2d.L2.global.tile [%0, {%1, %2}];\n}\n" ::"l"(tm), "r"(c0), "r"(c1) : "memory");
}
__device__ __forceinline__ void tma_2d_to_e(uint32_t dst, const CUtensorMap* tm, int c0, int c1, uint32_t bar, uint32_t mask) {
  asm volatile("{\n.reg .pred p;\nelect.sync _|p, 0xffffffff;\n"
               "@p cp.async.bulk.tensor.2d.shared::cluster.global.mbarrier::complete_tx::bytes.multicast::cluster [%0], [%1, {%2, %3}], [%4], %5;\n}\n"
               ::"r"(dst), "l"(tm), "r"(c0), "r"(c1), "r"(bar), "h"((uint16_t)mask) : "memory");
}
__device__ __forceinline__ void tma_3d_mc_e(uint32_t dst, const CUtensorMap* tm, int c1, int c2, uint32_t bar) {
  asm volatile("{\n.reg .pred p;\nelect.sync _|p, 0xffffffff;\n"
               "@p cp.async.bulk.tensor.3d.shared::cluster.global.mbarrier::complete_tx::bytes.multicast::cluster [%0], [%1, {%6, %2, %3}], [%4], %5;\n}\n"
               ::"r"(dst), "l"(tm), "r"(c1), "r"(c2), "r"(bar), "h"((uint16_t)3), "r"(0) : "memory");
}
__device__ __forceinline__ uint32_t poll_flags(const unsigned int* f, unsigned int target, int lane) {
  const unsigned int v = ld_acquire(f + (lane & 15));
  const uint32_t r = __ballot_sync(0xffffffffu, (int)(v - target) >= 0);
  __syncwarp();
  return r;
}
__device__ __forceinline__ void mbar_arrive_cluster(uint32_t local_bar, uint32_t rank) {
  asm volatile("{\n.reg .b32 ra;\nmapa.shared::cluster.u32 ra, %0, %1;\nmbarrier.arrive.shared::cluster.b64 _, [ra];\n}\n"
               ::"r"(local_bar), "r"(rank) : "memory");
}
__device__ __forceinline__ void release2(uint32_t bar) { mbar_arrive_cluster(bar, 0); mbar_arrive_cluster(bar, 1); }
__device__ __forceinline__ void tma_store_2d(const CUtensorMap* tm, uint32_t src, int c0, int c1) {
  asm volatile("cp.async.bulk.tensor.2d.global.shared::cta.bulk_group [%0, {%2, %3}], [%1];"
               ::"l"(tm), "r"(src), "r"(c0), "r"(c1) : "memory");
}
__device__ __forceinline__ void bulk_store(void* dst, uint32_t src, uint32_t bytes) {
  asm volatile("cp.async.bulk.global.shared::cta.bulk_group [%0], [%1], %2;" ::"l"(dst), "r"(src), "r"(bytes) : "memory");
}
__device__ __forceinline__ void bulk_load(uint32_t dst, const void* src, uint32_t bytes, uint32_t bar) {
  asm volatile("cp.async.bulk.shared::cluster.global.mbarrier::complete_tx::bytes [%0], [%1], %2, [%3];" ::"r"(dst), "l"(src), "r"(bytes), "r"(bar) : "memory");
}
__device__ __forceinline__ void bulk_red_add(void* dst, uint32_t src, uint32_t bytes) {
  asm volatile("cp.reduce.async.bulk.global.shared::cta.bulk_group.add.f32 [%0], [%1], %2;" ::"l"(dst), "r"(src), "r"(bytes) : "memory");
}
__device__ __forceinline__ void bulk_commit() { asm volatile("cp.async.bulk.commit_group;" ::: "memory"); }
__device__ __forceinline__ void bulk_wait_read0() { asm volatile("cp.async.bulk.wait_group.read 0;" ::: "memory"); }
__device__ __forceinline__ void bulk_wait0() { asm volatile("cp.async.bulk.wait_group 0;" ::: "memory"); }
__device__ __forceinline__ void fence_async_smem() { asm volatile("fence.proxy.async.shared::cta;" ::: "memory"); }
__device__ __forceinline__ void fence_async_all() { asm volatile("fence.proxy.async.global;" ::: "memory"); }
__device__ __forceinline__ void wgmma_fence() { asm volatile("wgmma.fence.sync.aligned;" ::: "memory"); }
__device__ __forceinline__ void wgmma_commit() { asm volatile("wgmma.commit_group.sync.aligned;" ::: "memory"); }
template <int N> __device__ __forceinline__ void wgmma_wait() { asm volatile("wgmma.wait_group.sync.aligned %0;" ::"n"(N) : "memory"); }
__device__ __forceinline__ void cluster_arrive() { asm volatile("barrier.cluster.arrive.release.aligned;" ::: "memory"); }
__device__ __forceinline__ void cluster_wait() { asm volatile("barrier.cluster.wait.acquire.aligned;" ::: "memory"); }
template <int ID, int N> __device__ __forceinline__ void nbar() { asm volatile("bar.sync %0, %1;" ::"n"(ID), "n"(N) : "memory"); }
__device__ __forceinline__ uint64_t make_desc(uint32_t addr, uint32_t lbo_bytes, uint32_t sbo_bytes) {
  uint64_t d = 0;
  d |= (uint64_t)((addr & 0x3FFFF) >> 4);
  d |= (uint64_t)((lbo_bytes >> 4) & 0x3FFF) << 16;
  d |= (uint64_t)((sbo_bytes >> 4) & 0x3FFF) << 32;
  d |= (uint64_t)1 << 62;
  return d;
}
__device__ __forceinline__ uint64_t desc64(uint32_t lo, uint32_t hi) { return (uint64_t)lo | ((uint64_t)hi << 32); }
__device__ __forceinline__ uint32_t pack_bf16(float lo, float hi) {
  uint32_t r; asm("cvt.rn.bf16x2.f32 %0, %1, %2;" : "=r"(r) : "f"(hi), "f"(lo)); return r;
}
__device__ __forceinline__ uint32_t mul_bf16x2(uint32_t a, uint32_t s, bool hi) {
  __nv_bfloat162 x = *reinterpret_cast<__nv_bfloat162*>(&a), y = *reinterpret_cast<__nv_bfloat162*>(&s);
  x = __hmul2(x, hi ? __high2bfloat162(y) : __low2bfloat162(y));
  return *reinterpret_cast<uint32_t*>(&x);
}
__device__ __forceinline__ float bf16r(float x) { return __bfloat162float(__float2bfloat16_rn(x)); }
__device__ __forceinline__ float bf_lo(uint32_t u) { return __uint_as_float(u << 16); }
__device__ __forceinline__ float bf_hi(uint32_t u) { return __uint_as_float(u & 0xFFFF0000u); }
__device__ __forceinline__ float ex2(float x) { float r; asm("ex2.approx.ftz.f32 %0, %1;" : "=f"(r) : "f"(x)); return r; }
__device__ __forceinline__ float rcp(float x) { float r; asm("rcp.approx.ftz.f32 %0, %1;" : "=f"(r) : "f"(x)); return r; }
__device__ __forceinline__ void mma_bf16(float (&d)[4], uint32_t a0, uint32_t a1, uint32_t a2, uint32_t a3, uint32_t b0, uint32_t b1) {
  asm("mma.sync.aligned.m16n8k16.row.col.f32.bf16.bf16.f32 {%0,%1,%2,%3}, {%4,%5,%6,%7}, {%8,%9}, {%0,%1,%2,%3};"
               : "+f"(d[0]), "+f"(d[1]), "+f"(d[2]), "+f"(d[3]) : "r"(a0), "r"(a1), "r"(a2), "r"(a3), "r"(b0), "r"(b1));
}
__device__ __forceinline__ void ldsm_x4(uint32_t& r0, uint32_t& r1, uint32_t& r2, uint32_t& r3, uint32_t addr) {
  asm volatile("ldmatrix.sync.aligned.m8n8.x4.shared.b16 {%0,%1,%2,%3}, [%4];"
               : "=r"(r0), "=r"(r1), "=r"(r2), "=r"(r3) : "r"(addr) : "memory");
}
__device__ __forceinline__ void ldsm_x4_t(uint32_t& r0, uint32_t& r1, uint32_t& r2, uint32_t& r3, uint32_t addr) {
  asm volatile("ldmatrix.sync.aligned.m8n8.x4.trans.shared.b16 {%0,%1,%2,%3}, [%4];"
               : "=r"(r0), "=r"(r1), "=r"(r2), "=r"(r3) : "r"(addr) : "memory");
}
__device__ __forceinline__ void ldsm_x2_t(uint32_t& r0, uint32_t& r1, uint32_t addr) {
  asm volatile("ldmatrix.sync.aligned.m8n8.x2.trans.shared.b16 {%0,%1}, [%2];"
               : "=r"(r0), "=r"(r1) : "r"(addr) : "memory");
}
__device__ __forceinline__ void stsm_x4(uint32_t addr, uint32_t r0, uint32_t r1, uint32_t r2, uint32_t r3) {
  asm volatile("stmatrix.sync.aligned.m8n8.x4.shared.b16 [%0], {%1,%2,%3,%4};"
               ::"r"(addr), "r"(r0), "r"(r1), "r"(r2), "r"(r3) : "memory");
}
__device__ __forceinline__ void stsm_x4_p(bool on, uint32_t addr, uint32_t r0, uint32_t r1, uint32_t r2, uint32_t r3) {
  asm volatile("{\n.reg .pred p;\nsetp.ne.b32 p, %5, 0;\n@p stmatrix.sync.aligned.m8n8.x4.shared.b16 [%0], {%1,%2,%3,%4};\n}\n"
               ::"r"(addr), "r"(r0), "r"(r1), "r"(r2), "r"(r3), "r"((int)on) : "memory");
}
__device__ __forceinline__ float2 lds_f2(uint32_t addr) {
  float2 v; asm volatile("ld.shared.v2.f32 {%0,%1}, [%2];" : "=f"(v.x), "=f"(v.y) : "r"(addr) : "memory"); return v;
}
__device__ __forceinline__ uint4 lds128(uint32_t addr) {
  uint4 v; asm volatile("ld.shared.v4.b32 {%0,%1,%2,%3}, [%4];" : "=r"(v.x), "=r"(v.y), "=r"(v.z), "=r"(v.w) : "r"(addr) : "memory"); return v;
}
__device__ __forceinline__ void sts128(uint32_t addr, uint4 v) {
  asm volatile("st.shared.v4.b32 [%0], {%1,%2,%3,%4};" ::"r"(addr), "r"(v.x), "r"(v.y), "r"(v.z), "r"(v.w) : "memory");
}
__device__ __forceinline__ float lds_f(uint32_t addr) {
  float v; asm volatile("ld.shared.f32 %0, [%1];" : "=f"(v) : "r"(addr) : "memory"); return v;
}
__device__ __forceinline__ uint32_t lds_vol(uint32_t addr) {
  uint32_t v; asm volatile("ld.volatile.shared.u32 %0, [%1];" : "=r"(v) : "r"(addr) : "memory"); return v;
}
__device__ __forceinline__ void sts16(uint32_t addr, uint32_t v) {
  asm volatile("st.shared.u16 [%0], %1;" ::"r"(addr), "h"((unsigned short)v) : "memory");
}
__device__ __forceinline__ void nbar_dyn(int id, int n) { asm volatile("bar.sync %0, %1;" ::"r"(id), "r"(n) : "memory"); }
__device__ __forceinline__ uint64_t make_desc_ns(uint32_t addr, uint32_t lbo_bytes, uint32_t sbo_bytes) {
  return (uint64_t)((addr & 0x3FFFF) >> 4) | ((uint64_t)(lbo_bytes >> 4) << 16) | ((uint64_t)(sbo_bytes >> 4) << 32);
}
__device__ __forceinline__ void sts_f(uint32_t addr, float v) { asm volatile("st.shared.f32 [%0], %1;" ::"r"(addr), "f"(v) : "memory"); }
__device__ __forceinline__ void sts64(uint32_t addr, uint32_t a, uint32_t b) {
  asm volatile("st.shared.v2.b32 [%0], {%1,%2};" ::"r"(addr), "r"(a), "r"(b) : "memory");
}
__device__ __forceinline__ void sts_f2(uint32_t addr, float a, float b) {
  asm volatile("st.shared.v2.f32 [%0], {%1,%2};" ::"r"(addr), "f"(a), "f"(b) : "memory");
}
__device__ __forceinline__ void red_add2(float* p, float a, float b) {
  asm volatile("red.global.add.v2.f32 [%0], {%1,%2};" ::"l"(p), "f"(a), "f"(b) : "memory");
}
__device__ __forceinline__ void red_add4(float* p, float a, float b, float c, float d) {
  asm volatile("red.global.add.v4.f32 [%0], {%1,%2,%3,%4};" ::"l"(p), "f"(a), "f"(b), "f"(c), "f"(d) : "memory");
}
__device__ __forceinline__ void red_add1(float* p, float a) {
  asm volatile("red.global.add.f32 [%0], %1;" ::"l"(p), "f"(a) : "memory");
}
__device__ __forceinline__ void l2_prefetch(const void* p, uint32_t bytes) {
  asm volatile("cp.async.bulk.prefetch.L2.global [%0], %1;" ::"l"(p), "r"(bytes) : "memory");
}

__device__ __forceinline__ void wgmma_n256(float (&d)[192], uint64_t da, uint64_t db, int scale_d) {
  asm volatile("{\n.reg .pred p;\nsetp.ne.b32 p, %130, 0;\n"
    "wgmma.mma_async.sync.aligned.m64n256k16.f32.bf16.bf16 {%0, %1, %2, %3, %4, %5, %6, %7, %8, %9, %10, %11, %12, %13, %14, %15, %16, %17, %18, %19, %20, %21, %22, %23, %24, %25, %26, %27, %28, %29, %30, %31, %32, %33, %34, %35, %36, %37, %38, %39, %40, %41, %42, %43, %44, %45, %46, %47, %48, %49, %50, %51, %52, %53, %54, %55, %56, %57, %58, %59, %60, %61, %62, %63, %64, %65, %66, %67, %68, %69, %70, %71, %72, %73, %74, %75, %76, %77, %78, %79, %80, %81, %82, %83, %84, %85, %86, %87, %88, %89, %90, %91, %92, %93, %94, %95, %96, %97, %98, %99, %100, %101, %102, %103, %104, %105, %106, %107, %108, %109, %110, %111, %112, %113, %114, %115, %116, %117, %118, %119, %120, %121, %122, %123, %124, %125, %126, %127}, %128, %129, p, 1, 1, 0, 1;\n}\n"
    : "+f"(d[0]), "+f"(d[1]), "+f"(d[2]), "+f"(d[3]), "+f"(d[4]), "+f"(d[5]), "+f"(d[6]), "+f"(d[7]), "+f"(d[8]), "+f"(d[9]), "+f"(d[10]), "+f"(d[11]), "+f"(d[12]), "+f"(d[13]), "+f"(d[14]), "+f"(d[15]), "+f"(d[16]), "+f"(d[17]), "+f"(d[18]), "+f"(d[19]), "+f"(d[20]), "+f"(d[21]), "+f"(d[22]), "+f"(d[23]), "+f"(d[24]), "+f"(d[25]), "+f"(d[26]), "+f"(d[27]), "+f"(d[28]), "+f"(d[29]), "+f"(d[30]), "+f"(d[31]), "+f"(d[32]), "+f"(d[33]), "+f"(d[34]), "+f"(d[35]), "+f"(d[36]), "+f"(d[37]), "+f"(d[38]), "+f"(d[39]), "+f"(d[40]), "+f"(d[41]), "+f"(d[42]), "+f"(d[43]), "+f"(d[44]), "+f"(d[45]), "+f"(d[46]), "+f"(d[47]), "+f"(d[48]), "+f"(d[49]), "+f"(d[50]), "+f"(d[51]), "+f"(d[52]), "+f"(d[53]), "+f"(d[54]), "+f"(d[55]), "+f"(d[56]), "+f"(d[57]), "+f"(d[58]), "+f"(d[59]), "+f"(d[60]), "+f"(d[61]), "+f"(d[62]), "+f"(d[63]), "+f"(d[64]), "+f"(d[65]), "+f"(d[66]), "+f"(d[67]), "+f"(d[68]), "+f"(d[69]), "+f"(d[70]), "+f"(d[71]), "+f"(d[72]), "+f"(d[73]), "+f"(d[74]), "+f"(d[75]), "+f"(d[76]), "+f"(d[77]), "+f"(d[78]), "+f"(d[79]), "+f"(d[80]), "+f"(d[81]), "+f"(d[82]), "+f"(d[83]), "+f"(d[84]), "+f"(d[85]), "+f"(d[86]), "+f"(d[87]), "+f"(d[88]), "+f"(d[89]), "+f"(d[90]), "+f"(d[91]), "+f"(d[92]), "+f"(d[93]), "+f"(d[94]), "+f"(d[95]), "+f"(d[96]), "+f"(d[97]), "+f"(d[98]), "+f"(d[99]), "+f"(d[100]), "+f"(d[101]), "+f"(d[102]), "+f"(d[103]), "+f"(d[104]), "+f"(d[105]), "+f"(d[106]), "+f"(d[107]), "+f"(d[108]), "+f"(d[109]), "+f"(d[110]), "+f"(d[111]), "+f"(d[112]), "+f"(d[113]), "+f"(d[114]), "+f"(d[115]), "+f"(d[116]), "+f"(d[117]), "+f"(d[118]), "+f"(d[119]), "+f"(d[120]), "+f"(d[121]), "+f"(d[122]), "+f"(d[123]), "+f"(d[124]), "+f"(d[125]), "+f"(d[126]), "+f"(d[127])
    : "l"(da), "l"(db), "r"(scale_d));
}
__device__ __forceinline__ void wgmma_n128(float (&d)[192], uint64_t da, uint64_t db, int scale_d) {
  asm volatile("{\n.reg .pred p;\nsetp.ne.b32 p, %66, 0;\n"
    "wgmma.mma_async.sync.aligned.m64n128k16.f32.bf16.bf16 {%0, %1, %2, %3, %4, %5, %6, %7, %8, %9, %10, %11, %12, %13, %14, %15, %16, %17, %18, %19, %20, %21, %22, %23, %24, %25, %26, %27, %28, %29, %30, %31, %32, %33, %34, %35, %36, %37, %38, %39, %40, %41, %42, %43, %44, %45, %46, %47, %48, %49, %50, %51, %52, %53, %54, %55, %56, %57, %58, %59, %60, %61, %62, %63}, %64, %65, p, 1, 1, 0, 1;\n}\n"
    : "+f"(d[128]), "+f"(d[129]), "+f"(d[130]), "+f"(d[131]), "+f"(d[132]), "+f"(d[133]), "+f"(d[134]), "+f"(d[135]), "+f"(d[136]), "+f"(d[137]), "+f"(d[138]), "+f"(d[139]), "+f"(d[140]), "+f"(d[141]), "+f"(d[142]), "+f"(d[143]), "+f"(d[144]), "+f"(d[145]), "+f"(d[146]), "+f"(d[147]), "+f"(d[148]), "+f"(d[149]), "+f"(d[150]), "+f"(d[151]), "+f"(d[152]), "+f"(d[153]), "+f"(d[154]), "+f"(d[155]), "+f"(d[156]), "+f"(d[157]), "+f"(d[158]), "+f"(d[159]), "+f"(d[160]), "+f"(d[161]), "+f"(d[162]), "+f"(d[163]), "+f"(d[164]), "+f"(d[165]), "+f"(d[166]), "+f"(d[167]), "+f"(d[168]), "+f"(d[169]), "+f"(d[170]), "+f"(d[171]), "+f"(d[172]), "+f"(d[173]), "+f"(d[174]), "+f"(d[175]), "+f"(d[176]), "+f"(d[177]), "+f"(d[178]), "+f"(d[179]), "+f"(d[180]), "+f"(d[181]), "+f"(d[182]), "+f"(d[183]), "+f"(d[184]), "+f"(d[185]), "+f"(d[186]), "+f"(d[187]), "+f"(d[188]), "+f"(d[189]), "+f"(d[190]), "+f"(d[191])
    : "l"(da), "l"(db), "r"(scale_d));
}
__device__ __forceinline__ void wgmma_n256_k(float (&d)[192], uint64_t da, uint64_t db, int scale_d) {
  asm volatile("{\n.reg .pred p;\nsetp.ne.b32 p, %130, 0;\n"
    "wgmma.mma_async.sync.aligned.m64n256k16.f32.bf16.bf16 {%0, %1, %2, %3, %4, %5, %6, %7, %8, %9, %10, %11, %12, %13, %14, %15, %16, %17, %18, %19, %20, %21, %22, %23, %24, %25, %26, %27, %28, %29, %30, %31, %32, %33, %34, %35, %36, %37, %38, %39, %40, %41, %42, %43, %44, %45, %46, %47, %48, %49, %50, %51, %52, %53, %54, %55, %56, %57, %58, %59, %60, %61, %62, %63, %64, %65, %66, %67, %68, %69, %70, %71, %72, %73, %74, %75, %76, %77, %78, %79, %80, %81, %82, %83, %84, %85, %86, %87, %88, %89, %90, %91, %92, %93, %94, %95, %96, %97, %98, %99, %100, %101, %102, %103, %104, %105, %106, %107, %108, %109, %110, %111, %112, %113, %114, %115, %116, %117, %118, %119, %120, %121, %122, %123, %124, %125, %126, %127}, %128, %129, p, 1, 1, 0, 0;\n}\n"
    : "+f"(d[0]), "+f"(d[1]), "+f"(d[2]), "+f"(d[3]), "+f"(d[4]), "+f"(d[5]), "+f"(d[6]), "+f"(d[7]), "+f"(d[8]), "+f"(d[9]), "+f"(d[10]), "+f"(d[11]), "+f"(d[12]), "+f"(d[13]), "+f"(d[14]), "+f"(d[15]), "+f"(d[16]), "+f"(d[17]), "+f"(d[18]), "+f"(d[19]), "+f"(d[20]), "+f"(d[21]), "+f"(d[22]), "+f"(d[23]), "+f"(d[24]), "+f"(d[25]), "+f"(d[26]), "+f"(d[27]), "+f"(d[28]), "+f"(d[29]), "+f"(d[30]), "+f"(d[31]), "+f"(d[32]), "+f"(d[33]), "+f"(d[34]), "+f"(d[35]), "+f"(d[36]), "+f"(d[37]), "+f"(d[38]), "+f"(d[39]), "+f"(d[40]), "+f"(d[41]), "+f"(d[42]), "+f"(d[43]), "+f"(d[44]), "+f"(d[45]), "+f"(d[46]), "+f"(d[47]), "+f"(d[48]), "+f"(d[49]), "+f"(d[50]), "+f"(d[51]), "+f"(d[52]), "+f"(d[53]), "+f"(d[54]), "+f"(d[55]), "+f"(d[56]), "+f"(d[57]), "+f"(d[58]), "+f"(d[59]), "+f"(d[60]), "+f"(d[61]), "+f"(d[62]), "+f"(d[63]), "+f"(d[64]), "+f"(d[65]), "+f"(d[66]), "+f"(d[67]), "+f"(d[68]), "+f"(d[69]), "+f"(d[70]), "+f"(d[71]), "+f"(d[72]), "+f"(d[73]), "+f"(d[74]), "+f"(d[75]), "+f"(d[76]), "+f"(d[77]), "+f"(d[78]), "+f"(d[79]), "+f"(d[80]), "+f"(d[81]), "+f"(d[82]), "+f"(d[83]), "+f"(d[84]), "+f"(d[85]), "+f"(d[86]), "+f"(d[87]), "+f"(d[88]), "+f"(d[89]), "+f"(d[90]), "+f"(d[91]), "+f"(d[92]), "+f"(d[93]), "+f"(d[94]), "+f"(d[95]), "+f"(d[96]), "+f"(d[97]), "+f"(d[98]), "+f"(d[99]), "+f"(d[100]), "+f"(d[101]), "+f"(d[102]), "+f"(d[103]), "+f"(d[104]), "+f"(d[105]), "+f"(d[106]), "+f"(d[107]), "+f"(d[108]), "+f"(d[109]), "+f"(d[110]), "+f"(d[111]), "+f"(d[112]), "+f"(d[113]), "+f"(d[114]), "+f"(d[115]), "+f"(d[116]), "+f"(d[117]), "+f"(d[118]), "+f"(d[119]), "+f"(d[120]), "+f"(d[121]), "+f"(d[122]), "+f"(d[123]), "+f"(d[124]), "+f"(d[125]), "+f"(d[126]), "+f"(d[127])
    : "l"(da), "l"(db), "r"(scale_d));
}
__device__ __forceinline__ void wgmma_n128_k(float (&d)[192], uint64_t da, uint64_t db, int scale_d) {
  asm volatile("{\n.reg .pred p;\nsetp.ne.b32 p, %66, 0;\n"
    "wgmma.mma_async.sync.aligned.m64n128k16.f32.bf16.bf16 {%0, %1, %2, %3, %4, %5, %6, %7, %8, %9, %10, %11, %12, %13, %14, %15, %16, %17, %18, %19, %20, %21, %22, %23, %24, %25, %26, %27, %28, %29, %30, %31, %32, %33, %34, %35, %36, %37, %38, %39, %40, %41, %42, %43, %44, %45, %46, %47, %48, %49, %50, %51, %52, %53, %54, %55, %56, %57, %58, %59, %60, %61, %62, %63}, %64, %65, p, 1, 1, 0, 0;\n}\n"
    : "+f"(d[128]), "+f"(d[129]), "+f"(d[130]), "+f"(d[131]), "+f"(d[132]), "+f"(d[133]), "+f"(d[134]), "+f"(d[135]), "+f"(d[136]), "+f"(d[137]), "+f"(d[138]), "+f"(d[139]), "+f"(d[140]), "+f"(d[141]), "+f"(d[142]), "+f"(d[143]), "+f"(d[144]), "+f"(d[145]), "+f"(d[146]), "+f"(d[147]), "+f"(d[148]), "+f"(d[149]), "+f"(d[150]), "+f"(d[151]), "+f"(d[152]), "+f"(d[153]), "+f"(d[154]), "+f"(d[155]), "+f"(d[156]), "+f"(d[157]), "+f"(d[158]), "+f"(d[159]), "+f"(d[160]), "+f"(d[161]), "+f"(d[162]), "+f"(d[163]), "+f"(d[164]), "+f"(d[165]), "+f"(d[166]), "+f"(d[167]), "+f"(d[168]), "+f"(d[169]), "+f"(d[170]), "+f"(d[171]), "+f"(d[172]), "+f"(d[173]), "+f"(d[174]), "+f"(d[175]), "+f"(d[176]), "+f"(d[177]), "+f"(d[178]), "+f"(d[179]), "+f"(d[180]), "+f"(d[181]), "+f"(d[182]), "+f"(d[183]), "+f"(d[184]), "+f"(d[185]), "+f"(d[186]), "+f"(d[187]), "+f"(d[188]), "+f"(d[189]), "+f"(d[190]), "+f"(d[191])
    : "l"(da), "l"(db), "r"(scale_d));
}
__device__ __forceinline__ void wgmma_n40_tt(float (&d)[20], uint64_t da, uint64_t db, int scale_d) {
  asm volatile("{\n.reg .pred p;\nsetp.ne.b32 p, %22, 0;\n"
    "wgmma.mma_async.sync.aligned.m64n40k16.f32.bf16.bf16 {%0, %1, %2, %3, %4, %5, %6, %7, %8, %9, %10, %11, %12, %13, %14, %15, %16, %17, %18, %19}, %20, %21, p, 1, 1, 1, 1;\n}\n"
    : "+f"(d[0]), "+f"(d[1]), "+f"(d[2]), "+f"(d[3]), "+f"(d[4]), "+f"(d[5]), "+f"(d[6]), "+f"(d[7]), "+f"(d[8]), "+f"(d[9]), "+f"(d[10]), "+f"(d[11]), "+f"(d[12]), "+f"(d[13]), "+f"(d[14]), "+f"(d[15]), "+f"(d[16]), "+f"(d[17]), "+f"(d[18]), "+f"(d[19])
    : "l"(da), "l"(db), "r"(scale_d));
}
__device__ __forceinline__ void wgmma_n40_rs(float (&d)[20], const uint32_t (&a)[4], uint64_t db, int scale_d) {
  asm volatile("{\n.reg .pred p;\nsetp.ne.b32 p, %25, 0;\n"
    "wgmma.mma_async.sync.aligned.m64n40k16.f32.bf16.bf16 {%0, %1, %2, %3, %4, %5, %6, %7, %8, %9, %10, %11, %12, %13, %14, %15, %16, %17, %18, %19}, {%20, %21, %22, %23}, %24, p, 1, 1, 1;\n}\n"
    : "+f"(d[0]), "+f"(d[1]), "+f"(d[2]), "+f"(d[3]), "+f"(d[4]), "+f"(d[5]), "+f"(d[6]), "+f"(d[7]), "+f"(d[8]), "+f"(d[9]), "+f"(d[10]), "+f"(d[11]), "+f"(d[12]), "+f"(d[13]), "+f"(d[14]), "+f"(d[15]), "+f"(d[16]), "+f"(d[17]), "+f"(d[18]), "+f"(d[19])
    : "r"(a[0]), "r"(a[1]), "r"(a[2]), "r"(a[3]), "l"(db), "r"(scale_d));
}
__device__ __forceinline__ void wgmma_n256_0(float (&d)[192], uint64_t da, uint64_t db) {
  asm volatile("{\n.reg .pred p;\nsetp.ne.b32 p, 0, 0;\n"
    "wgmma.mma_async.sync.aligned.m64n256k16.f32.bf16.bf16 {%0, %1, %2, %3, %4, %5, %6, %7, %8, %9, %10, %11, %12, %13, %14, %15, %16, %17, %18, %19, %20, %21, %22, %23, %24, %25, %26, %27, %28, %29, %30, %31, %32, %33, %34, %35, %36, %37, %38, %39, %40, %41, %42, %43, %44, %45, %46, %47, %48, %49, %50, %51, %52, %53, %54, %55, %56, %57, %58, %59, %60, %61, %62, %63, %64, %65, %66, %67, %68, %69, %70, %71, %72, %73, %74, %75, %76, %77, %78, %79, %80, %81, %82, %83, %84, %85, %86, %87, %88, %89, %90, %91, %92, %93, %94, %95, %96, %97, %98, %99, %100, %101, %102, %103, %104, %105, %106, %107, %108, %109, %110, %111, %112, %113, %114, %115, %116, %117, %118, %119, %120, %121, %122, %123, %124, %125, %126, %127}, %128, %129, p, 1, 1, 0, 1;\n}\n"
    : "=f"(d[0]), "=f"(d[1]), "=f"(d[2]), "=f"(d[3]), "=f"(d[4]), "=f"(d[5]), "=f"(d[6]), "=f"(d[7]), "=f"(d[8]), "=f"(d[9]), "=f"(d[10]), "=f"(d[11]), "=f"(d[12]), "=f"(d[13]), "=f"(d[14]), "=f"(d[15]), "=f"(d[16]), "=f"(d[17]), "=f"(d[18]), "=f"(d[19]), "=f"(d[20]), "=f"(d[21]), "=f"(d[22]), "=f"(d[23]), "=f"(d[24]), "=f"(d[25]), "=f"(d[26]), "=f"(d[27]), "=f"(d[28]), "=f"(d[29]), "=f"(d[30]), "=f"(d[31]), "=f"(d[32]), "=f"(d[33]), "=f"(d[34]), "=f"(d[35]), "=f"(d[36]), "=f"(d[37]), "=f"(d[38]), "=f"(d[39]), "=f"(d[40]), "=f"(d[41]), "=f"(d[42]), "=f"(d[43]), "=f"(d[44]), "=f"(d[45]), "=f"(d[46]), "=f"(d[47]), "=f"(d[48]), "=f"(d[49]), "=f"(d[50]), "=f"(d[51]), "=f"(d[52]), "=f"(d[53]), "=f"(d[54]), "=f"(d[55]), "=f"(d[56]), "=f"(d[57]), "=f"(d[58]), "=f"(d[59]), "=f"(d[60]), "=f"(d[61]), "=f"(d[62]), "=f"(d[63]), "=f"(d[64]), "=f"(d[65]), "=f"(d[66]), "=f"(d[67]), "=f"(d[68]), "=f"(d[69]), "=f"(d[70]), "=f"(d[71]), "=f"(d[72]), "=f"(d[73]), "=f"(d[74]), "=f"(d[75]), "=f"(d[76]), "=f"(d[77]), "=f"(d[78]), "=f"(d[79]), "=f"(d[80]), "=f"(d[81]), "=f"(d[82]), "=f"(d[83]), "=f"(d[84]), "=f"(d[85]), "=f"(d[86]), "=f"(d[87]), "=f"(d[88]), "=f"(d[89]), "=f"(d[90]), "=f"(d[91]), "=f"(d[92]), "=f"(d[93]), "=f"(d[94]), "=f"(d[95]), "=f"(d[96]), "=f"(d[97]), "=f"(d[98]), "=f"(d[99]), "=f"(d[100]), "=f"(d[101]), "=f"(d[102]), "=f"(d[103]), "=f"(d[104]), "=f"(d[105]), "=f"(d[106]), "=f"(d[107]), "=f"(d[108]), "=f"(d[109]), "=f"(d[110]), "=f"(d[111]), "=f"(d[112]), "=f"(d[113]), "=f"(d[114]), "=f"(d[115]), "=f"(d[116]), "=f"(d[117]), "=f"(d[118]), "=f"(d[119]), "=f"(d[120]), "=f"(d[121]), "=f"(d[122]), "=f"(d[123]), "=f"(d[124]), "=f"(d[125]), "=f"(d[126]), "=f"(d[127])
    : "l"(da), "l"(db));
}
__device__ __forceinline__ void wgmma_n128_0(float (&d)[192], uint64_t da, uint64_t db) {
  asm volatile("{\n.reg .pred p;\nsetp.ne.b32 p, 0, 0;\n"
    "wgmma.mma_async.sync.aligned.m64n128k16.f32.bf16.bf16 {%0, %1, %2, %3, %4, %5, %6, %7, %8, %9, %10, %11, %12, %13, %14, %15, %16, %17, %18, %19, %20, %21, %22, %23, %24, %25, %26, %27, %28, %29, %30, %31, %32, %33, %34, %35, %36, %37, %38, %39, %40, %41, %42, %43, %44, %45, %46, %47, %48, %49, %50, %51, %52, %53, %54, %55, %56, %57, %58, %59, %60, %61, %62, %63}, %64, %65, p, 1, 1, 0, 1;\n}\n"
    : "=f"(d[128]), "=f"(d[129]), "=f"(d[130]), "=f"(d[131]), "=f"(d[132]), "=f"(d[133]), "=f"(d[134]), "=f"(d[135]), "=f"(d[136]), "=f"(d[137]), "=f"(d[138]), "=f"(d[139]), "=f"(d[140]), "=f"(d[141]), "=f"(d[142]), "=f"(d[143]), "=f"(d[144]), "=f"(d[145]), "=f"(d[146]), "=f"(d[147]), "=f"(d[148]), "=f"(d[149]), "=f"(d[150]), "=f"(d[151]), "=f"(d[152]), "=f"(d[153]), "=f"(d[154]), "=f"(d[155]), "=f"(d[156]), "=f"(d[157]), "=f"(d[158]), "=f"(d[159]), "=f"(d[160]), "=f"(d[161]), "=f"(d[162]), "=f"(d[163]), "=f"(d[164]), "=f"(d[165]), "=f"(d[166]), "=f"(d[167]), "=f"(d[168]), "=f"(d[169]), "=f"(d[170]), "=f"(d[171]), "=f"(d[172]), "=f"(d[173]), "=f"(d[174]), "=f"(d[175]), "=f"(d[176]), "=f"(d[177]), "=f"(d[178]), "=f"(d[179]), "=f"(d[180]), "=f"(d[181]), "=f"(d[182]), "=f"(d[183]), "=f"(d[184]), "=f"(d[185]), "=f"(d[186]), "=f"(d[187]), "=f"(d[188]), "=f"(d[189]), "=f"(d[190]), "=f"(d[191])
    : "l"(da), "l"(db));
}
__device__ __forceinline__ void wgmma_n64a(float (&d)[192], uint64_t da, uint64_t db, int scale_d) {
  asm volatile("{\n.reg .pred p;\nsetp.ne.b32 p, %34, 0;\n"
    "wgmma.mma_async.sync.aligned.m64n64k16.f32.bf16.bf16 {%0, %1, %2, %3, %4, %5, %6, %7, %8, %9, %10, %11, %12, %13, %14, %15, %16, %17, %18, %19, %20, %21, %22, %23, %24, %25, %26, %27, %28, %29, %30, %31}, %32, %33, p, 1, 1, 0, 1;\n}\n"
    : "+f"(d[128]), "+f"(d[129]), "+f"(d[130]), "+f"(d[131]), "+f"(d[132]), "+f"(d[133]), "+f"(d[134]), "+f"(d[135]), "+f"(d[136]), "+f"(d[137]), "+f"(d[138]), "+f"(d[139]), "+f"(d[140]), "+f"(d[141]), "+f"(d[142]), "+f"(d[143]), "+f"(d[144]), "+f"(d[145]), "+f"(d[146]), "+f"(d[147]), "+f"(d[148]), "+f"(d[149]), "+f"(d[150]), "+f"(d[151]), "+f"(d[152]), "+f"(d[153]), "+f"(d[154]), "+f"(d[155]), "+f"(d[156]), "+f"(d[157]), "+f"(d[158]), "+f"(d[159])
    : "l"(da), "l"(db), "r"(scale_d));
}
__device__ __forceinline__ void wgmma_n64b(float (&d)[192], uint64_t da, uint64_t db, int scale_d) {
  asm volatile("{\n.reg .pred p;\nsetp.ne.b32 p, %34, 0;\n"
    "wgmma.mma_async.sync.aligned.m64n64k16.f32.bf16.bf16 {%0, %1, %2, %3, %4, %5, %6, %7, %8, %9, %10, %11, %12, %13, %14, %15, %16, %17, %18, %19, %20, %21, %22, %23, %24, %25, %26, %27, %28, %29, %30, %31}, %32, %33, p, 1, 1, 0, 1;\n}\n"
    : "+f"(d[160]), "+f"(d[161]), "+f"(d[162]), "+f"(d[163]), "+f"(d[164]), "+f"(d[165]), "+f"(d[166]), "+f"(d[167]), "+f"(d[168]), "+f"(d[169]), "+f"(d[170]), "+f"(d[171]), "+f"(d[172]), "+f"(d[173]), "+f"(d[174]), "+f"(d[175]), "+f"(d[176]), "+f"(d[177]), "+f"(d[178]), "+f"(d[179]), "+f"(d[180]), "+f"(d[181]), "+f"(d[182]), "+f"(d[183]), "+f"(d[184]), "+f"(d[185]), "+f"(d[186]), "+f"(d[187]), "+f"(d[188]), "+f"(d[189]), "+f"(d[190]), "+f"(d[191])
    : "l"(da), "l"(db), "r"(scale_d));
}

constexpr int SLOT = 16384;
constexpr int KVT = 10240;
constexpr uint32_t QA = 0x0BAu, QK = 0x462u, QQ = 0x981u;
constexpr int SM_SD = 12 * SLOT;
constexpr int SM_BAR = SM_SD + 8192;
constexpr int SM_RS = SM_BAR + 512;
constexpr int SM_AP = SM_RS + 768;
constexpr int SM_BP = SM_AP + 2048;
constexpr int SM_WPHI = SM_BP + 12288;
constexpr int SM_EPOCH = SM_WPHI + 10240;
constexpr int SM_TOTAL = SM_EPOCH + 16 + 1024;
constexpr int B_FULLS = 0, B_XOLD = 24, B_STAT = 32, B_EMPTYS = 40, B_FULLT = 256  , B_CONS = 384  , B_E3 = 472, B_E0 = 480, B_E1 = 488, B_E2 = 496, B_EPI = 504, B_CS = 160,
              B_KVDONE = 168  , B_ODONE = 176, B_XDONE = 184, B_OH1 = 192, B_CS2 = 208, B_XH0 = 232, B_OF = 240, B_FLG = 64  ;
constexpr uint64_t BAR_CNT = 0x1c07fc0eac00a800ull;
constexpr uint64_t WO_A0 = 0xba76218762187643ull, WO_B0 = 0x9540395403ba9021ull, WO_A1 = 0xba732157321576baull, WO_B1 = 0x9506489064890321ull;
constexpr uint64_t WO_DA0 = 0xa9876543210edd00ull, WO_DB0 = 0xa987654321bbccccull, WO_DA1 = 0xa9876543210fff00ull, WO_DB1 = 0xa98765432bbcccccull;
constexpr int XS = 10;

#define PL 2
#define PROFX(i) PROFT(tid_ == 128 && layer == PL, 200 + (i))
#define GAA 99
#define GAB 99
#define GWA 99
#define GWB 99
#define PSL 20
#define EP 5
#define DRY 0
#define NCOM 3
#define CG0 0
#define CG1 99
#define CPF 0
#define CSLP 128
#define PFS 8
#define KVTH 0x41700000u
#define CSW 1
#define RL 3
#define ORD 1
#define NLAYERS 4
constexpr float L2E = 1.4426950408889634f;
#define PHI_MAX 2147483648.f

#define D128(lo) desc64(lo, 0x40000040u)
struct Ctx { uint32_t sb; int g, rb, cu; bf16* out; };

__device__ __forceinline__ void colsum_load(const bf16* __restrict__ w, int rb, int g, int wi, int lane, uint32_t stg, float (&s)[8]) {
  const int ch = wi * 8 + (lane & 7), sec = ch >> 4;
  const bf16* src = w + (size_t)(rb * 64 + (lane >> 3) * 16) * 3072 + (sec == 2 ? 0 : 1024 + sec * 1024) + g * 128 + (ch & 15) * 8;
  stg += lane * 16;
#pragma unroll
  for (int i = 0; i < 8; ++i) s[i] = 0.f;
#pragma unroll
  for (int r = 0; r < 12; ++r)
    asm volatile("cp.async.cg.shared.global [%0], [%1], 16;" ::"r"(stg + r * 512), "l"(src + (size_t)(4 + r) * 3072) : "memory");
  uint4 v[4];
#pragma unroll
  for (int r = 0; r < 4; ++r) v[r] = __ldg(reinterpret_cast<const uint4*>(src + (size_t)r * 3072));
#pragma unroll 1
  for (int r0 = 0;; ++r0) {
#pragma unroll
    for (int r = 0; r < 4; ++r) {
      s[0] += bf_lo(v[r].x); s[1] += bf_hi(v[r].x); s[2] += bf_lo(v[r].y); s[3] += bf_hi(v[r].y);
      s[4] += bf_lo(v[r].z); s[5] += bf_hi(v[r].z); s[6] += bf_lo(v[r].w); s[7] += bf_hi(v[r].w);
    }
    if (r0 == 3) break;
    asm volatile("cp.async.wait_all;" ::: "memory");
#pragma unroll
    for (int r = 0; r < 4; ++r) v[r] = lds128(stg + (r0 * 4 + r) * 512);
  }
#pragma unroll
  for (int i = 0; i < 8; ++i) { s[i] += __shfl_xor_sync(0xffffffffu, s[i], 8); s[i] += __shfl_xor_sync(0xffffffffu, s[i], 16); }
}
__device__ __forceinline__ void colsum_red(float* cs, int g, int wi, int lane, const float (&s)[8]) {
  if (lane < 8) {
    red_add4(cs + g * 384 + (wi * 8 + lane) * 8, s[0], s[1], s[2], s[3]);
    red_add4(cs + g * 384 + (wi * 8 + lane) * 8 + 4, s[4], s[5], s[6], s[7]);
  }
}
#define PHASE_CTX() \
  uint32_t sb = c.sb; asm volatile("" : "+r"(sb)); \
  int tid_ = threadIdx.x; asm volatile("" : "+r"(tid_)); \
  const uint32_t bar = sb + SM_BAR; \
  const int lane = tid_ & 31, cw = (tid_ >> 5) - 4, wg = cw >> 2, wq = cw & 3, gq = lane >> 2, t = lane & 3, wrow0 = cw * 16; \
  const int lrow = (lane & 7) + ((lane >> 3) & 1) * 8, lchk = lane >> 4; \
  const bool elected = (tid_ & 127) == 0; \
  const uint32_t rowo = (wrow0 + lrow) * 128, X = (lchk ^ (lane & 7)) << 4; \
  (void)bar; (void)wq; (void)gq; (void)lrow; (void)lchk; (void)elected; (void)wrow0; (void)wg; (void)rowo; (void)X; (void)t;

template <int PITCH = D_>
__device__ __forceinline__ void slab_out_half(uint32_t slot, bf16* dst, int wrow0, int lane) {
  const int r0 = lane >> 3, ch = lane & 7;
  const uint32_t src = slot + (wrow0 + r0) * 128;
  uint4 v[4];
#pragma unroll
  for (int i = 0; i < 4; ++i) v[i] = lds128(src + i * 512 + (((ch ^ (4 * i + r0)) & 7) << 4));
  dst += (size_t)(wrow0 + r0) * PITCH + ch * 8;
#pragma unroll
  for (int i = 0; i < 4; ++i) *reinterpret_cast<uint4*>(dst + (size_t)i * 4 * PITCH) = v[i];
}

template <int O>
__device__ __forceinline__ void phi_proj(float (&p)[2][4][4], const uint32_t (&kq)[64], uint32_t wa) {
#pragma unroll
  for (int h = 0; h < 2; ++h)
#pragma unroll
    for (int i = 0; i < 4; ++i) { p[h][i][0] = p[h][i][1] = p[h][i][2] = p[h][i][3] = 0.f; }
#pragma unroll
  for (int ks = 0; ks < 2; ++ks)
#pragma unroll
    for (int np = 0; np < 2; ++np)
#pragma unroll
      for (int h = 0; h < 2; ++h) {
        uint32_t b0, b1, b2, b3;
        ldsm_x4_t(b0, b1, b2, b3, wa + h * 2560 + ks * 1280 + np * 32);
        mma_bf16(p[h][2 * np], kq[O + 8 * h + 4 * ks], kq[O + 8 * h + 4 * ks + 1], kq[O + 8 * h + 4 * ks + 2], kq[O + 8 * h + 4 * ks + 3], b0, b1);
        mma_bf16(p[h][2 * np + 1], kq[O + 8 * h + 4 * ks], kq[O + 8 * h + 4 * ks + 1], kq[O + 8 * h + 4 * ks + 2], kq[O + 8 * h + 4 * ks + 3], b2, b3);
      }
}
__device__ __forceinline__ void phi_exp(uint32_t (&raw)[4][4], const float (&p)[4][4], float sc0, float sc1) {
#pragma unroll
  for (int i = 0; i < 4; ++i) {
    const float e0 = ex2(p[i][0] * sc0), e1 = ex2(p[i][1] * sc0), e2 = ex2(p[i][2] * sc1), e3 = ex2(p[i][3] * sc1);
    const float m0 = e0 * e1, m1 = e2 * e3, rr = rcp(m0 * m1), r0 = rr * m1, r1 = rr * m0;
    raw[i >> 1][(i & 1) * 2] = pack_bf16(e0, e1);
    raw[i >> 1][(i & 1) * 2 + 1] = pack_bf16(e2, e3);
    raw[2 + (i >> 1)][(i & 1) * 2] = pack_bf16(e1 * r0, e0 * r0);
    raw[2 + (i >> 1)][(i & 1) * 2 + 1] = pack_bf16(e3 * r1, e2 * r1);
  }
}
#define FENCE_P(h) _Pragma("unroll") for (int i_ = 0; i_ < 16; ++i_) asm volatile("" : "+f"(p[h][i_ >> 2][i_ & 3]) :: "memory")
#define FENCE_RAW(h) _Pragma("unroll") for (int i_ = 0; i_ < 16; ++i_) asm volatile("" : "+r"(raw[h][i_ >> 2][i_ & 3]) :: "memory")
template <int O>
__device__ __forceinline__ void phi_norm(uint32_t (&ph)[2][4][4], const uint32_t (&raw)[2][4][4], const uint32_t (&kq)[64], uint32_t wa,
                                         float sc0, float sc1, float mul0, float mul1) {
  bool bad = false;
#pragma unroll
  for (int h = 0; h < 2; ++h)
#pragma unroll
    for (int sg = 0; sg < 2; ++sg) {
      float ss[4] = {0.f, 0.f, 0.f, 0.f};
#pragma unroll
      for (int ks = 0; ks < 2; ++ks)
        mma_bf16(ss, raw[h][2 * sg + ks][0], raw[h][2 * sg + ks][1], raw[h][2 * sg + ks][2], raw[h][2 * sg + ks][3], 0x3F803F80u, 0x3F803F80u);
      bad = bad || !(ss[0] < PHI_MAX) || !(ss[2] < PHI_MAX);
      const uint32_t iv = pack_bf16(rcp(ss[0]) * mul0, rcp(ss[2]) * mul1);
#pragma unroll
      for (int ks = 0; ks < 2; ++ks)
#pragma unroll
        for (int j = 0; j < 4; ++j) ph[h][2 * sg + ks][j] = mul_bf16x2(raw[h][2 * sg + ks][j], iv, j & 1);
    }
  if (__builtin_expect(__any_sync(0xffffffffu, bad), 0)) {
#pragma unroll 1
    for (int it = 0; it < 4; ++it) {
      float q[4][4];
#pragma unroll
      for (int i = 0; i < 4; ++i) { q[i][0] = q[i][1] = q[i][2] = q[i][3] = 0.f; }
#pragma unroll
      for (int ks = 0; ks < 2; ++ks) {
        uint32_t a[4];
#pragma unroll
        for (int j = 0; j < 4; ++j) a[j] = (it & 2) ? kq[O + 8 + 4 * ks + j] : kq[O + 4 * ks + j];
#pragma unroll
        for (int np = 0; np < 2; ++np) {
          uint32_t b0, b1, b2, b3;
          ldsm_x4_t(b0, b1, b2, b3, wa + (it >> 1) * 2560 + ks * 1280 + np * 32);
          mma_bf16(q[2 * np], a[0], a[1], a[2], a[3], b0, b1);
          mma_bf16(q[2 * np + 1], a[0], a[1], a[2], a[3], b2, b3);
        }
      }
      float iv[2];
#pragma unroll
      for (int r = 0; r < 2; ++r) {
        const float sc = (it & 1) ? -(r ? sc1 : sc0) : (r ? sc1 : sc0);
        float mx = -INFINITY, sm = 0.f;
#pragma unroll
        for (int i = 0; i < 8; ++i) { float& v = q[i >> 1][2 * r + (i & 1)]; v *= sc; mx = fmaxf(mx, v); }
        mx = fmaxf(mx, __shfl_xor_sync(0xffffffffu, mx, 1));
        mx = fmaxf(mx, __shfl_xor_sync(0xffffffffu, mx, 2));
#pragma unroll
        for (int i = 0; i < 8; ++i) { float& v = q[i >> 1][2 * r + (i & 1)]; v = ex2(v - mx); sm += v; }
        sm += __shfl_xor_sync(0xffffffffu, sm, 1);
        sm += __shfl_xor_sync(0xffffffffu, sm, 2);
        iv[r] = rcp(sm) * (r ? mul1 : mul0);
      }
#pragma unroll
      for (int i = 0; i < 24; ++i) ph[i >> 4][(i >> 2) & 3][i & 3] = ph[(i + 8) >> 4][((i + 8) >> 2) & 3][i & 3];
#pragma unroll
      for (int i = 0; i < 4; ++i) {
        ph[1][2 + (i >> 1)][(i & 1) * 2] = pack_bf16(q[i][0] * iv[0], q[i][1] * iv[0]);
        ph[1][2 + (i >> 1)][(i & 1) * 2 + 1] = pack_bf16(q[i][2] * iv[1], q[i][3] * iv[1]);
      }
    }
  }
}

__device__ __forceinline__ void stats_out(float s0, float s1, float q0, float q1, float2* dst, int t) {
  const bool od = t & 1;
  float sa = od ? s1 : s0, qa = od ? q1 : q0;
  sa += __shfl_xor_sync(0xffffffffu, od ? s0 : s1, 1);
  qa += __shfl_xor_sync(0xffffffffu, od ? q0 : q1, 1);
  sa += __shfl_xor_sync(0xffffffffu, sa, 2);
  qa += __shfl_xor_sync(0xffffffffu, qa, 2);
  if (t < 2) red_add2(&dst[t * 8].x, sa, qa);
}

__device__ __forceinline__ void consumer(const Ctx& c) {
  const int g = c.g, m0 = c.rb * 128;
  float acc[192];
#define X_H1() \
      _Pragma("unroll") for (int jp = 4; jp < 8; ++jp) \
        stsm_x4(sb + (XS + 1) * SLOT + rowo + (X ^ ((jp & 3) << 5)), \
                pack_bf16(acc[128 + 8 * jp], acc[129 + 8 * jp]), pack_bf16(acc[130 + 8 * jp], acc[131 + 8 * jp]), \
                pack_bf16(acc[132 + 8 * jp], acc[133 + 8 * jp]), pack_bf16(acc[134 + 8 * jp], acc[135 + 8 * jp]));
#pragma unroll
  for (int i = 128; i < 192; ++i) acc[i] = 0.f;
#pragma unroll 1
  for (int layer = 0;; ++layer) {
    {
      PHASE_CTX();
      const uint32_t wu = __shfl_sync(0xffffffffu, wg, 0);
      const uint32_t dA0 = (((sb + wu * 8192) & 0x3FFFF) >> 4) | (1u << 16), dB0 = ((sb & 0x3FFFF) >> 4) | (512u << 16);
      {
        PROFX(0);
        mbar_wait(bar + B_FULLS, 0);
        PROFX(1);
        wgmma_fence();
        wgmma_n256_0(acc, D128(dA0 + XS * 1024), D128(dB0 + 2048));
#pragma unroll
        for (int k = 1; k < 4; ++k) wgmma_n256(acc, D128(dA0 + XS * 1024 + k * 2), D128(dB0 + 2048 + k * 128), 1);
        wgmma_commit();
        wgmma_wait<1>();
        float s0 = 0.f, s1 = 0.f, q0 = 0.f, q1 = 0.f;
        if (layer) {
          X_H1();
#pragma unroll
          for (int i = 128; i < 192; i += 4) {
            s0 += acc[i] + acc[i + 1]; s1 += acc[i + 2] + acc[i + 3];
            q0 = fmaf(acc[i], acc[i], fmaf(acc[i + 1], acc[i + 1], q0)); q1 = fmaf(acc[i + 2], acc[i + 2], fmaf(acc[i + 3], acc[i + 3], q1));
          }
        }
        asm volatile("" : "+f"(s0), "+f"(s1), "+f"(q0), "+f"(q1) :: "memory");
        wgmma_fence();
        wgmma_n128_0(acc, D128(dA0 + XS * 1024), D128(dB0 + 1024));
#pragma unroll
        for (int k = 1; k < 4; ++k) wgmma_n128(acc, D128(dA0 + XS * 1024 + k * 2), D128(dB0 + 1024 + k * 128), 1);
        wgmma_commit();
        if (layer) {
          PHASE_CTX();
          fence_async_smem();
          nbar_dyn(3 + wu, 128);
          stats_out(s0, s1, q0, q1, g_stats + layer * S_ + m0 + wrow0 + gq, t);
          PROFT(tid_ == 128, layer * 16 + 8);
        }
      }
      uint32_t s = 1, u = 0, sp = 0;
      const int ix = layer ? 1 : 2 * min(g, NCOM) + 1;
#pragma unroll 1
      for (int i = 1; i < 14; ++i) {
        mbar_wait(bar + B_FULLS + s * 8, (u + (s ? layer : 0)) & 1);
        const uint32_t da = dA0 + ((QA >> (4 * s)) & 15) * 1024, dk = dB0 + ((QK >> (4 * s)) & 15) * 1024,
                       dq = dB0 + ((QQ >> (4 * s)) & 15) * 1024;
        wgmma_fence();
#pragma unroll
        for (int k = 0; k < 4; ++k) {
          wgmma_n256(acc, D128(da + k * 2), D128(dk + k * 128), 1);
          wgmma_n128(acc, D128(da + k * 2), D128(dq + k * 128), 1);
        }
        wgmma_commit();
        if (i == ix || (i == ix + 1 && !layer)) {
          PHASE_CTX();
          if (layer) {
            slab_out_half(sb + (XS + 1) * SLOT, g_x + (size_t)m0 * D_ + g * 128 + 64, wrow0, lane);
          } else {
            float s0 = 0.f, s1 = 0.f, q0 = 0.f, q1 = 0.f;
            const uint32_t xa = sb + ((QA >> (4 * sp)) & 15) * SLOT + rowo;
#pragma unroll
            for (int jp = 0; jp < 4; ++jp) {
              uint32_t x0, x1, x2, x3;
              ldsm_x4(x0, x1, x2, x3, xa + (X ^ (jp << 5)));
              s0 += (bf_lo(x0) + bf_hi(x0)) + (bf_lo(x2) + bf_hi(x2));
              s1 += (bf_lo(x1) + bf_hi(x1)) + (bf_lo(x3) + bf_hi(x3));
              q0 = fmaf(bf_lo(x0), bf_lo(x0), fmaf(bf_hi(x0), bf_hi(x0), fmaf(bf_lo(x2), bf_lo(x2), fmaf(bf_hi(x2), bf_hi(x2), q0))));
              q1 = fmaf(bf_lo(x1), bf_lo(x1), fmaf(bf_hi(x1), bf_hi(x1), fmaf(bf_lo(x3), bf_lo(x3), fmaf(bf_hi(x3), bf_hi(x3), q1))));
            }
            stats_out(s0, s1, q0, q1, g_stats + m0 + wrow0 + gq, t);
          }
          __syncwarp();
          if (lane == 0 && (layer || i != ix)) mbar_arrive(bar + B_XDONE);
          nbar_dyn(3 + wu, 128);
        }
        wgmma_wait<1>();
        if (elected) release2(bar + B_EMPTYS + sp * 8);
        sp = s;
        if (++s == 3) { s = 0; ++u; }
      }
      {
        const uint64_t dap = make_desc_ns(sb + SM_AP + wu * 1024, 0, 128), dbp = make_desc_ns(sb + SM_BP + (layer & 1) * 6144, 0, 128);
        if (wu == 0) {
          wgmma_wait<0>();
          nbar<6, 256>();
        }
        if (layer < 2) mbar_wait(bar + (layer ? B_CS2 : B_CS), 0);
        mbar_wait(bar + B_STAT, layer & 1);
        mbar_wait(bar + B_FULLS + 16, layer & 1);
        wgmma_fence();
        wgmma_n256_k(acc, dap, dbp, 1);
#pragma unroll
        for (int k = 0; k < 4; ++k) wgmma_n256(acc, D128(dA0 + (QA >> 8) * 1024 + k * 2), D128(dB0 + (QK >> 8) * 1024 + k * 128), 1);
        mbar_wait(bar + B_FULLS, 1);
        PROFT(tid_ == 128, layer * 16 + 9);
        wgmma_fence();
#pragma unroll
        for (int k = 0; k < 4; ++k) wgmma_n256(acc, D128(dA0 + (QA & 15) * 1024 + k * 2), D128(dB0 + (QK & 15) * 1024 + k * 128), 1);
        wgmma_commit();
        if (wu) nbar<6, 256>();
#define Q_TAIL() \
        wgmma_n128_k(acc, dap, dbp + 256, 1); \
        _Pragma("unroll") for (int k = 0; k < 4; ++k) wgmma_n128(acc, D128(dA0 + (QA >> 8) * 1024 + k * 2), D128(dB0 + (QQ >> 8) * 1024 + k * 128), 1); \
        _Pragma("unroll") for (int k = 0; k < 4; ++k) wgmma_n128(acc, D128(dA0 + (QA & 15) * 1024 + k * 2), D128(dB0 + (QQ & 15) * 1024 + k * 128), 1);
        Q_TAIL();
        wgmma_commit();
        wgmma_wait<1>();
#pragma unroll
        for (int i = 0; i < 128; ++i) asm volatile("" : "+f"(acc[i]) :: "memory");
      }
    }
    uint32_t xo[32];
    {
      PHASE_CTX();
      PROFT(tid_ == 128, layer * 16 + 1);
      const bool isB = layer & 1;
      const int cu = c.cu;
      if (cu >= 4) asm volatile("bar.arrive 7, 256;" ::: "memory");
      else if (isB && cu == 0) asm volatile("bar.arrive 10, 64;" ::: "memory");
      if (elected && isB && cu == 0) release2(bar + B_E1);
      uint32_t kq[64];
#pragma unroll
      for (int i = 0; i < 32; ++i) kq[i] = pack_bf16(acc[2 * i], acc[2 * i + 1]);
      const unsigned int epoch = __float_as_uint(lds_f(sb + SM_EPOCH));
      uint4* const hbuf = g_halo + (size_t)((((epoch & 1) * 2 + (layer >> 1)) * 16 + c.rb) * 8 + g) * 512 + lane;
      if (isB && cu == 7) {
#pragma unroll
        for (int jp = 0; jp < 8; ++jp) st_relaxed4(hbuf + jp * 32, ~kq[4 * jp], ~kq[4 * jp + 1], ~kq[4 * jp + 2], ~kq[4 * jp + 3]);
#pragma unroll
        for (int jp = 8; jp < 16; ++jp)
          st_relaxed4(hbuf + jp * 32, ~pack_bf16(acc[8 * jp], acc[8 * jp + 1]), ~pack_bf16(acc[8 * jp + 2], acc[8 * jp + 3]),
                      ~pack_bf16(acc[8 * jp + 4], acc[8 * jp + 5]), ~pack_bf16(acc[8 * jp + 6], acc[8 * jp + 7]));
      }
      const uint32_t rowq = rowo & 8191;
      const uint32_t rB = sb + 4 * SLOT + wg * 4 * KVT + rowq, pA = sb + (3 + 3 * wg) * SLOT + rowq;
      PROFX(13);
      if (cu < 4) nbar<7, 256>();
      PROFX(14);
      {
        const uint32_t vb = isB ? rB + KVT + 2048 + wg * 2 * KVT : pA + 2 * SLOT - (rowq >> 1), vst = isB ? (1 - 2 * wg) * 2 * KVT : 8192;
        const uint32_t X0 = isB ? X : (lchk ^ ((lane & 7) >> 1)) << 4, X1 = isB ? X ^ 64 : X0 + 4096;
        const bool dup = isB && cu == 3;
        if (isB) {
#pragma unroll
          for (int jp = 0; jp < 8; ++jp) {
            stsm_x4(vb - KVT + (jp >> 2) * vst + (X ^ ((jp & 3) << 5)), kq[4 * jp], kq[4 * jp + 1], kq[4 * jp + 2], kq[4 * jp + 3]);
            stsm_x4_p(dup, rB + 2048 + 32768 + (1 - (jp >> 2)) * 2 * KVT + (X ^ ((jp & 3) << 5)), kq[4 * jp], kq[4 * jp + 1], kq[4 * jp + 2], kq[4 * jp + 3]);
          }
        }
#pragma unroll
        for (int jp = 8; jp < 16; ++jp) {
          const uint32_t v0 = pack_bf16(acc[8 * jp], acc[8 * jp + 1]), v1 = pack_bf16(acc[8 * jp + 2], acc[8 * jp + 3]),
                         v2 = pack_bf16(acc[8 * jp + 4], acc[8 * jp + 5]), v3 = pack_bf16(acc[8 * jp + 6], acc[8 * jp + 7]);
          const uint32_t ad = vb + ((jp >> 2) & 1) * vst + (((jp & 2) ? X1 : X0) ^ ((jp & 1) << 5));
          stsm_x4(ad, v0, v1, v2, v3);
          stsm_x4_p(dup, ad + 32768 + ((jp & 4) ? -2 * KVT : 2 * KVT), v0, v1, v2, v3);
        }
        if (dup) asm volatile("bar.arrive 9, 64;" ::: "memory");
      }
      const float rs0 = lds_f(sb + SM_RS + (16 + wrow0 + gq) * 4), rs1 = lds_f(sb + SM_RS + (24 + wrow0 + gq) * 4);
      PROFT(tid_ == 128, layer * 16 + 2);
#define Q_DONE() \
      wgmma_wait<0>(); \
      if (lane == 0) release2(bar + B_E0); \
      _Pragma("unroll") for (int i = 128; i < 192; ++i) asm volatile("" : "+f"(acc[i]) :: "memory"); \
      _Pragma("unroll") for (int i = 0; i < 32; ++i) kq[32 + i] = pack_bf16(acc[128 + 2 * i], acc[129 + 2 * i]);
      Q_DONE();
      if (isB) {
        const int e = gq & 1;
        const uint32_t KX = ((lane >> 3) ^ (lane & 7)) << 4;
        float f0[4], f1[4], rj[4];
        uint32_t msk = 0;
#pragma unroll
        for (int nt = 0; nt < 4; ++nt) {
          const int kk = nt * 8 + 2 * t + e;
          const bool okk = (m0 + wrow0 + kk) >= 16;
          const int d0 = kk - gq, d1 = d0 - 8;
          rj[nt] = lds_f(sb + SM_RS + (wrow0 + kk) * 4);
          f0[nt] = rj[nt] * rs0 * (0.17677669529663687f * L2E);
          f1[nt] = rj[nt] * rs1 * (0.17677669529663687f * L2E);
          msk |= (okk && d0 >= 2 && d0 <= 16) ? (1u << nt) : 0u;
          msk |= (okk && d1 >= 2 && d1 <= 16) ? (16u << nt) : 0u;
        }
        if ((cu & 3) == 0) asm volatile("bar.arrive %0, 128;" :: "r"(3 + (cu >> 2)) : "memory");
        if (cu == 0) {
          nbar<11, 64>();
        } else if (cu == 4) {
          uint4 hv[16];
          if (c.rb > 0) {
            uint32_t n = 0;
#pragma unroll 1
            while (true) {
              uint32_t mn = 0xFFFFFFFFu;
#pragma unroll
              for (int i = 0; i < 16; ++i) hv[i] = ld_relaxed4(hbuf - 8 * 512 + i * 32);
#pragma unroll
              for (int i = 0; i < 16; ++i) mn = __vimin3_u32(__vimin3_u32(mn, hv[i].x, hv[i].y), hv[i].z, hv[i].w);
              if (__all_sync(0xffffffffu, mn != 0u)) break;
              if (++n > (1u << 20)) { g_err = 4u; break; }
            }
          } else {
#pragma unroll
            for (int i = 0; i < 16; ++i) hv[i] = make_uint4(~0u, ~0u, ~0u, ~0u);
          }
          nbar<10, 64>();
#pragma unroll
          for (int i = 0; i < 16; ++i)
            stsm_x4(rB - 4 * KVT + (((i >> 2) & 1) * 2 + (i >> 3)) * KVT + (X ^ ((i & 3) << 5)), ~hv[i].x, ~hv[i].y, ~hv[i].z, ~hv[i].w);
          asm volatile("bar.arrive 11, 64;" ::: "memory");
          nbar<9, 64>();
        } else {
          nbar_dyn(3 + (cu >> 2), 128);
        }
        PROFT(tid_ == 128, layer * 16 + 5);
#pragma unroll
        for (int i = 16; i < 32; ++i) xo[i] = 0u;
#pragma unroll 1
        for (int hp = 0; hp < 2; ++hp) {
          const uint32_t qad = sb + (XS + hp) * SLOT + rowo, kt = rB + 2 * (hp ^ wg) * KVT - (lane & 8) * 128, vt = rB + (2 * (hp ^ wg) + 1) * KVT;
          uint32_t qa[2][8];
#pragma unroll
          for (int i = 0; i < 16; ++i) { qa[i >> 3][i & 7] = kq[32 + i]; kq[32 + i] = kq[48 + i]; }
          float l0[2][4], l1[2][4];
#pragma unroll
          for (int nt = 0; nt < 4; ++nt)
#pragma unroll
            for (int h = 0; h < 2; ++h) {
              float sc[4] = {0.f, 0.f, 0.f, 0.f};
              uint32_t b0, b1, b2, b3;
              ldsm_x4(b0, b1, b2, b3, kt + nt * 1024 + (KX ^ (h << 6)));
              mma_bf16(sc, qa[h][0], qa[h][1], qa[h][2], qa[h][3], b0, b1);
              mma_bf16(sc, qa[h][4], qa[h][5], qa[h][6], qa[h][7], b2, b3);
              l0[h][nt] = (msk >> nt) & 1 ? (e ? sc[1] : sc[0]) * f0[nt] : -1e30f;
              l1[h][nt] = (msk >> (4 + nt)) & 1 ? (e ? sc[3] : sc[2]) * f1[nt] : -1e30f;
            }
          float mx0[2], mx1[2], s0[2], s1[2];
#pragma unroll
          for (int h = 0; h < 2; ++h) {
            mx0[h] = fmaxf(fmaxf(l0[h][0], l0[h][1]), fmaxf(l0[h][2], l0[h][3]));
            mx1[h] = fmaxf(fmaxf(l1[h][0], l1[h][1]), fmaxf(l1[h][2], l1[h][3]));
          }
#pragma unroll
          for (int o = 1; o <= 2; o <<= 1)
#pragma unroll
            for (int h = 0; h < 2; ++h) {
              mx0[h] = fmaxf(mx0[h], __shfl_xor_sync(0xffffffffu, mx0[h], o));
              mx1[h] = fmaxf(mx1[h], __shfl_xor_sync(0xffffffffu, mx1[h], o));
            }
#pragma unroll
          for (int h = 0; h < 2; ++h) {
#pragma unroll
            for (int nt = 0; nt < 4; ++nt) { l0[h][nt] = ex2(l0[h][nt] - mx0[h]); l1[h][nt] = ex2(l1[h][nt] - mx1[h]); }
            s0[h] = (l0[h][0] + l0[h][1]) + (l0[h][2] + l0[h][3]);
            s1[h] = (l1[h][0] + l1[h][1]) + (l1[h][2] + l1[h][3]);
          }
#pragma unroll
          for (int o = 1; o <= 2; o <<= 1)
#pragma unroll
            for (int h = 0; h < 2; ++h) {
              s0[h] += __shfl_xor_sync(0xffffffffu, s0[h], o);
              s1[h] += __shfl_xor_sync(0xffffffffu, s1[h], o);
            }
          uint32_t pl[2][4], phh[2][4];
#pragma unroll
          for (int h = 0; h < 2; ++h) {
            const float i0 = rcp(s0[h]), i1 = rcp(s1[h]);
#pragma unroll
            for (int nt = 0; nt < 4; ++nt) {
              const uint32_t pk = pack_bf16(l0[h][nt] * i0 * rj[nt], l1[h][nt] * i1 * rj[nt]);
              pl[h][nt] = e ? pk << 16 : pk & 0xFFFFu;
              phh[h][nt] = e ? pk & 0xFFFF0000u : pk >> 16;
            }
          }
          float oa[2][4][4];
#pragma unroll
          for (int h = 0; h < 2; ++h)
#pragma unroll
            for (int i = 0; i < 4; ++i) { oa[h][i][0] = oa[h][i][1] = oa[h][i][2] = oa[h][i][3] = 0.f; }
#pragma unroll
          for (int ks = 0; ks < 2; ++ks)
#pragma unroll
            for (int np = 0; np < 2; ++np)
#pragma unroll
              for (int h = 0; h < 2; ++h) {
                uint32_t b0, b1, b2, b3;
                ldsm_x4_t(b0, b1, b2, b3, vt + ks * 2048 + (X ^ (h << 6) ^ (np << 5)));
                mma_bf16(oa[h][2 * np], pl[h][2 * ks], phh[h][2 * ks], pl[h][2 * ks + 1], phh[h][2 * ks + 1], b0, b1);
                mma_bf16(oa[h][2 * np + 1], pl[h][2 * ks], phh[h][2 * ks], pl[h][2 * ks + 1], phh[h][2 * ks + 1], b2, b3);
              }
          if (hp == 0 && lane == 0) release2(bar + B_E3);
          mbar_wait(bar + B_XOLD, 1);
#pragma unroll
          for (int i = 0; i < 16; ++i) xo[i] = xo[16 + i];
#pragma unroll
          for (int jp = 0; jp < 4; ++jp) ldsm_x4(xo[16 + 4 * jp], xo[17 + 4 * jp], xo[18 + 4 * jp], xo[19 + 4 * jp], qad + (X ^ (jp << 5)));
#pragma unroll
          for (int h = 0; h < 2; ++h)
#pragma unroll
            for (int np = 0; np < 2; ++np)
              stsm_x4(qad + (X ^ (h << 6) ^ (np << 5)),
                      pack_bf16(oa[h][2 * np][0], oa[h][2 * np][1]), pack_bf16(oa[h][2 * np][2], oa[h][2 * np][3]),
                      pack_bf16(oa[h][2 * np + 1][0], oa[h][2 * np + 1][1]), pack_bf16(oa[h][2 * np + 1][2], oa[h][2 * np + 1][3]));
          fence_async_smem();
          {
            __syncwarp();
            slab_out_half(sb + (XS + hp) * SLOT, g_o + (size_t)m0 * D_ + g * 128 + hp * 64, wrow0, lane);
            __syncwarp();
            if (lane == 0) mbar_arrive(bar + (hp ? B_ODONE : B_OH1));
          }
        }
      } else {
        PHASE_CTX();
        const uint32_t pA = sb + (3 + 3 * wg) * SLOT + (rowo & 8191);
        float sc0 = rs0 * L2E, sc1 = rs1 * L2E;
        const uint32_t wa0 = sb + SM_WPHI + lrow * 80 + lchk * 16;
        const uint32_t wu = __shfl_sync(0xffffffffu, wg, 0), par = (layer >> 1) & 1;
        float p[2][4][4];
        uint32_t raw[2][4][4], ph[2][4][4];
        float kva[20], oa[2][20];
        auto kv_start = [&](int hp) {
#pragma unroll
          for (int h = 0; h < 2; ++h)
#pragma unroll
            for (int cp = 0; cp < 4; ++cp)
              stsm_x4(pA + hp * 16384 + h * 8192 + (X ^ (cp << 5)), ph[h][cp][0], ph[h][cp][1], ph[h][cp][2], ph[h][cp][3]);
          PROFT(tid_ == 128, layer * 16 + 11);
          fence_async_smem();
          nbar<1, 256>();
          const uint32_t hu = 2 * hp + wu;
          const uint32_t dP = (((sb + 3 * SLOT + hu * 8192) & 0x3FFFF) >> 4) | (512u << 16);
          const uint32_t dV = (((sb + 5 * SLOT + hu * 4096) & 0x3FFFF) >> 4) | (((SM_SD - 5 * SLOT - hu * 4096) >> 4) << 16);
          wgmma_fence();
#pragma unroll
          for (int ks = 0; ks < 8; ++ks)
            wgmma_n40_tt(kva, desc64(dP + (ks >> 2) * 3072 + (ks & 3) * 128, 0x40000040u),
                         desc64(dV + (ks >> 2) * (3072u - (2816u << 16)) + (ks & 3) * 64, 0x80000020u), ks != 0);
          wgmma_commit();
        };
        auto kv_end = [&](int hp) {
          wgmma_wait<0>();
#pragma unroll
          for (int i = 0; i < 20; ++i) asm volatile("" : "+f"(kva[i]) :: "memory");
          nbar_dyn(3 + wu, 128);
          PROFT(tid_ == 128, layer * 16 + 12);
          const bool od = lane & 1;
#pragma unroll
          for (int i = 0; i < 4; ++i)
            sts128(sb + (3 + hp) * SLOT + (cw * 128 + i * 32 + lane) * 16,
                   make_uint4(__float_as_uint(kva[4 * i]), __float_as_uint(kva[4 * i + 1]), __float_as_uint(kva[4 * i + 2]),
                              __float_as_uint(od == (i >= 2) ? 1.f : kva[4 * i + 3])));
          sts128(sb + (6 + hp) * SLOT + wg * 8192 + (wq * 32 + lane) * 16,
                 make_uint4(__float_as_uint(od ? kva[11] : kva[3]), __float_as_uint(od ? kva[15] : kva[7]), __float_as_uint(od ? kva[18] : kva[16]), __float_as_uint(1.f)));
          fence_async_smem();
          __syncwarp();
          if (lane == 0) mbar_arrive(bar + B_KVDONE - hp * 32);
          PROFT(tid_ == 128, layer * 16 + 3);
        };
        const uint4* const kvg = g_kv + (g * 2 + (layer >> 1)) * 2560 + cw * 128 + lane;
        uint4 u[5];
        auto kv_load = [&](int hp) {
#pragma unroll
          for (int i = 0; i < 4; ++i) u[i] = ld_relaxed4(kvg + hp * 1280 + i * 32);
          u[4] = ld_relaxed4(kvg + hp * 1280 + 1024 - cw * 96);
        };
        auto o_start = [&](int hp, const uint32_t (&pq)[2][4][4]) {
          PROFT(tid_ == 128 && hp == 0, layer * 16 + 10);
          if (hp == 0) mbar_wait(bar + B_KVDONE - 32, par);
          const bool od = lane & 1;
          uint32_t n = 0;
#pragma unroll 1
          while (!__all_sync(0xffffffffu, (od ? u[2].w : u[0].w) == 0x41800000u && (od ? u[3].w : u[1].w) == 0x41800000u && u[4].w == 0x41800000u)) {
#pragma unroll 1
            while (__any_sync(0xffffffffu, u[4].w < KVTH) && ++n < (1u << 20)) u[4].w = ld_relaxed(&kvg[hp * 1280 + 1024 - cw * 96].w);
            if (++n > (1u << 20)) { g_err = 6u; break; }
            kv_load(hp);
          }
          PROFT(tid_ == 128 && hp == 0, layer * 16 + 5);
          if (!od) { u[0].w = u[4].x; u[1].w = u[4].y; } else { u[2].w = u[4].x; u[3].w = u[4].y; }
#pragma unroll
          for (int i = 0; i < 4; i += 2)
            stsm_x4(sb + (5 + 3 * hp) * SLOT + rowo + (X ^ ((i & 2) << 4)),
                    pack_bf16(__uint_as_float(u[i].x), __uint_as_float(u[i].y)), pack_bf16(__uint_as_float(u[i].z), __uint_as_float(u[i].w)),
                    pack_bf16(__uint_as_float(u[i + 1].x), __uint_as_float(u[i + 1].y)), pack_bf16(__uint_as_float(u[i + 1].z), __uint_as_float(u[i + 1].w)));
          const uint32_t z2 = pack_bf16(__uint_as_float(u[4].z), __uint_as_float(u[4].z));
          if (t < 2) sts128(sb + (5 + 3 * hp) * SLOT + (wrow0 + gq + 8 * t) * 128 + ((4 ^ gq) << 4), make_uint4(z2, z2, z2, z2));
          fence_async_smem();
          nbar<1, 256>();
          PROFT(tid_ == 128 && hp == 1, layer * 16 + 4);
          const uint32_t dK = (((sb + (5 + 3 * hp) * SLOT) & 0x3FFFF) >> 4) | (512u << 16);
          wgmma_fence();
#pragma unroll
          for (int ks = 0; ks < 4; ++ks) {
#pragma unroll
            for (int hh = 0; hh < 2; ++hh) wgmma_n40_rs(oa[hh], pq[hh][ks], D128(dK + hh * 512 + ks * 128), ks != 0);
          }
          wgmma_commit();
        };
        auto o_end = [&](int hp) {
          wgmma_wait<0>();
#pragma unroll
          for (int i = 0; i < 20; ++i) asm volatile("" : "+f"(oa[0][i]), "+f"(oa[1][i]) :: "memory");
#pragma unroll
          for (int hh = 0; hh < 2; ++hh) {
            const float i0 = rcp(oa[hh][16] + 1e-6f), i1 = rcp(oa[hh][18] + 1e-6f);
            const uint32_t qad = sb + (3 + hp) * SLOT + rowo, hx = hh << 6;
#pragma unroll
            for (int np = 0; np < 2; ++np)
              stsm_x4(qad + (X ^ hx ^ (np << 5)),
                      pack_bf16(oa[hh][8 * np] * i0, oa[hh][8 * np + 1] * i0), pack_bf16(oa[hh][8 * np + 2] * i1, oa[hh][8 * np + 3] * i1),
                      pack_bf16(oa[hh][8 * np + 4] * i0, oa[hh][8 * np + 5] * i0), pack_bf16(oa[hh][8 * np + 6] * i1, oa[hh][8 * np + 7] * i1));
          }
          fence_async_smem();
          __syncwarp();
          slab_out_half(sb + (3 + hp) * SLOT, g_o + (size_t)m0 * D_ + g * 128 + hp * 64, wrow0, lane);
          __syncwarp();
          if (lane == 0) mbar_arrive(bar + (hp ? B_ODONE : B_OH1));
        };
#define XO_LOAD() \
        mbar_wait(bar + B_XOLD, 0); \
        _Pragma("unroll") for (int jp = 0; jp < 8; ++jp) \
          ldsm_x4(xo[4 * jp], xo[4 * jp + 1], xo[4 * jp + 2], xo[4 * jp + 3], sb + (XS + (jp >> 2)) * SLOT + rowo + (X ^ ((jp & 3) << 5)));
#define SC_RELOAD() \
        sc0 = __uint_as_float(lds_vol(sb + SM_RS + (16 + wrow0 + gq) * 4)) * L2E; sc1 = __uint_as_float(lds_vol(sb + SM_RS + (24 + wrow0 + gq) * 4)) * L2E;
        __syncwarp();
        phi_proj<0>(p, kq, wa0);
        phi_exp(raw[0], p[0], sc0, sc1);
        phi_exp(raw[1], p[1], sc0, sc1);
        phi_proj<16>(p, kq, wa0 + 5120);
        phi_norm<0>(ph, raw, kq, wa0, sc0, sc1, rs0, rs1);
        kv_start(0);
        phi_exp(raw[0], p[0], sc0, sc1);
        kv_end(0);
        if (RL & 1) { SC_RELOAD(); }
        phi_exp(raw[1], p[1], sc0, sc1);
        phi_proj<32>(p, kq, wa0);
        phi_norm<16>(ph, raw, kq, wa0 + 5120, sc0, sc1, rs0, rs1);
        kv_start(1);
        XO_LOAD();
        phi_exp(raw[0], p[0], sc0, sc1);
        kv_end(1);
        if (lane == 0) release2(bar + B_E3);
        if (RL & 2) { SC_RELOAD(); }
        kv_load(0);
        phi_exp(raw[1], p[1], sc0, sc1);
        phi_proj<48>(p, kq, wa0 + 5120);
        phi_norm<32>(ph, raw, kq, wa0, sc0, sc1, 1.f, 1.f);
        o_start(0, ph);
        phi_exp(raw[0], p[0], sc0, sc1);
        o_end(0);
        SC_RELOAD();
        kv_load(1);
        phi_exp(raw[1], p[1], sc0, sc1);
        phi_norm<48>(ph, raw, kq, wa0 + 5120, sc0, sc1, 1.f, 1.f);
        o_start(1, ph);
        o_end(1);
      }
      __syncwarp();
      PROFT(lane == 0 && layer == PL, 216 + cw);
      if (lane == 0) mbar_arrive(bar + B_EPI);
      PROFT(tid_ == 128, layer * 16 + 6);
    }
    {
      PHASE_CTX();
      const uint32_t wu = __shfl_sync(0xffffffffu, wg, 0);
      const uint32_t dA0 = (((sb + wu * 8192) & 0x3FFFF) >> 4) | (1u << 16), dB0 = ((sb & 0x3FFFF) >> 4) | (512u << 16);
#pragma unroll
      for (int i = 0; i < 32; ++i) { acc[128 + 2 * i] = bf_lo(xo[i]); acc[129 + 2 * i] = bf_hi(xo[i]); }
      nbar_dyn(3 + wg, 128);
      uint64_t ta = (layer & 1) ? WO_A1 : WO_A0, tw = (layer & 1) ? WO_B1 : WO_B0;
#pragma unroll 1
      for (int i = 0; i < 16; ++i) {
        bool rel = i > 0 && i < 12;
        if (DRY && rel && !__all_sync(0xffffffffu, mbar_test_wait(bar + B_FULLT + i * 8, layer & 1))) {
          wgmma_wait<0>();
          if (elected) release2(bar + B_CONS + (i - 1) * 8);
          rel = false;
        }
        mbar_wait(bar + B_FULLT + i * 8, layer & 1);
        PROFT(tid_ == 128 && layer == PL, 160 + i);
        const uint32_t da = dA0 + ((uint32_t)ta & 15) * 1024, db = dB0 + ((uint32_t)tw & 15) * 1024;
        ta >>= 4; tw >>= 4;
        wgmma_fence();
#pragma unroll
        for (int k = 0; k < 4; ++k) wgmma_n128(acc, D128(da + k * 2), D128(db + k * 128), 1);
        wgmma_commit();
        if (i == 0) {
          if (elected) {
            if ((layer & 1) && wu) release2(bar + B_E1);
            release2(bar + B_E2);
          }
        } else {
          wgmma_wait<1>();
          if (elected && rel) release2(bar + B_CONS + (i - 1) * 8);
          if (elected && (unsigned)(i - 13) < 2u && layer + 1 < NLAYERS) release2(bar + B_EMPTYS + (i - 13) * 8);
        }
      }
      const bool last = layer == NLAYERS - 1;
      wgmma_wait<0>();
#pragma unroll
      for (int i = 128; i < 192; ++i) asm volatile("" : "+f"(acc[i]) :: "memory");
      if (elected && !last) release2(bar + B_EMPTYS + 16);
      PROFT(tid_ == 128, layer * 16 + 7);
#pragma unroll
      for (int jp = 0; jp < 4; ++jp)
        stsm_x4(sb + XS * SLOT + rowo + (X ^ (jp << 5)),
                pack_bf16(acc[128 + 8 * jp], acc[129 + 8 * jp]), pack_bf16(acc[130 + 8 * jp], acc[131 + 8 * jp]),
                pack_bf16(acc[132 + 8 * jp], acc[133 + 8 * jp]), pack_bf16(acc[134 + 8 * jp], acc[135 + 8 * jp]));
      if (last) {
        __syncwarp();
        slab_out_half(sb + XS * SLOT, c.out + (size_t)m0 * D_ + g * 128, wrow0, lane);
        X_H1();
        __syncwarp();
        slab_out_half(sb + (XS + 1) * SLOT, c.out + (size_t)m0 * D_ + g * 128 + 64, wrow0, lane);
        __syncwarp();
        if (lane == 0) mbar_arrive(bar + B_XDONE);
        PROFT(tid_ == 128, layer * 16 + 24);
        break;
      }
      fence_async_smem();
      __syncwarp();
      slab_out_half(sb + XS * SLOT, g_x + (size_t)m0 * D_ + g * 128, wrow0, lane);
      __syncwarp();
      if (lane == 0) mbar_arrive(bar + B_XH0);
      nbar_dyn(3 + wu, 128);
    }
  }
}

__device__ __forceinline__ void flag_fetch(uint32_t bar, const unsigned int* f) {
  asm volatile("{\n.reg .pred p;\nelect.sync _|p, 0xffffffff;\n@p mbarrier.expect_tx.relaxed.cta.shared::cta.b64 [%2], 64;\n"
               "@p cp.async.bulk.shared::cluster.global.mbarrier::complete_tx::bytes [%0], [%1], 64, [%2];\n}\n"
               ::"r"(bar + B_FLG), "l"(f), "r"(bar + 128) : "memory");
}
__device__ __forceinline__ int kblock0(int i, int g) {
  const int j = i >> 1, p = max(g, NCOM) + j - NCOM;
  return (j < NCOM ? j : p < 8 ? p : p - 8 + NCOM) * 2 + (i & 1);
}

#define WOORD 0xFDB9753ECA864210ull
__device__ __forceinline__ int wo_kblock(int m, int g) { return (2 * g + (int)((WOORD >> (4 * m)) & 15)) & 15; }

__global__ void __cluster_dims__(2, 1, 1) __launch_bounds__(384, 1)
mega_kernel(const __grid_constant__ CUtensorMap tm_x0, const __grid_constant__ CUtensorMap tm_x,
            const __grid_constant__ CUtensorMap tm_o,
            const __grid_constant__ CUtensorMap tm_wA, const __grid_constant__ CUtensorMap tm_wB,
            const __grid_constant__ CUtensorMap tm_woA, const __grid_constant__ CUtensorMap tm_woB,
            const bf16* __restrict__ wA, const bf16* __restrict__ wB,
            const bf16* __restrict__ wphi, bf16* __restrict__ out) {
  extern __shared__ uint8_t smem_raw[];
  const uint32_t sb = (smem_u32(smem_raw) + 1023u) & ~1023u;
  const uint32_t bar = sb + SM_BAR;
  const int warp = __shfl_sync(0xffffffffu, threadIdx.x >> 5, 0), lane = threadIdx.x & 31;
  const int cr = blockIdx.x & 1;
  const int g = (blockIdx.x >> 1) & 7;
  const int rb = (blockIdx.x >> 4) * 2 + cr;
  const int m0 = rb * 128;

  if (warp < 4) {
    asm volatile("setmaxnreg.dec.sync.aligned.u32 40;");
    asm volatile("barrier.cluster.arrive.relaxed.aligned;" ::: "memory");
    const unsigned int epoch = warp ? ld_relaxed(&g_epoch) : 0u;
    if (warp) cluster_wait();
    unsigned int xbase = epoch * NLAYERS;
    const unsigned int cbase = epoch * 16u;
    auto wo_a = [&](int layer) {
      uint64_t ts = ((layer & 1) ? WO_A1 : WO_A0) >> 8, td = ((layer & 1) ? WO_DA1 : WO_DA0) >> 8, tk = WOORD >> 8;
      uint32_t ready = 0u;
#pragma unroll 1
      for (int m = 2; m < 16; ++m) {
        const int kb = (2 * g + (uint32_t)tk) & 15;
        uint32_t dst = sb + ((uint32_t)ts & 15) * SLOT, fb = bar + B_FULLT + m * 8, eb = bar + B_CONS + ((uint32_t)td & 15) * 8;
        int kc = kb * 64;
        ts >>= 4; td >>= 4; tk >>= 4;
        if (!((ready >> kb) & 1)) {
          PROFT(m == 2 && lane == 0, 64 + layer * 16 + 2);
          if (EP && m > EP) {
            uint32_t n = 0;
#pragma unroll 1
            while (true) {
              ready |= __ballot_sync(0xffffffffu, (int)(lds_vol(bar + B_FLG + (lane & 15) * 4) - (xbase + layer + 1)) >= 0);
              if (((ready >> kb) & 1) || ++n > (1u << 20)) break;
              if ((n & 3) == 0) flag_fetch(bar, g_of + rb * 32);
              __nanosleep(PSL);
            }
          }
          src_wait<0>(g_of + rb * 32, xbase + layer + 1, 1u << kb, ready, lane);
          fence_async_all();
        }
        if (m == ((layer & 1) ? GAB : GAA)) mbar_wait_u(bar + B_OF, layer & 1);
        asm volatile("" : "+r"(dst), "+r"(fb), "+r"(eb), "+r"(kc));
        mbar_wait_u(eb, layer & 1);
        tma_2d_e(dst, &tm_o, kc, m0, fb);
        if (EP && m >= EP && (ready & 0xFFFFu) != 0xFFFFu) flag_fetch(bar, g_of + rb * 32);
        PROFT(lane == 0 && layer == PL, 176 + m);
      }
    };
    auto wo_w = [&](int layer) {
      const CUtensorMap* tx = layer == 0 ? &tm_x0 : &tm_x;
      const CUtensorMap* two = (layer & 1) ? &tm_woB : &tm_woA;
      uint64_t ts = (layer & 1) ? WO_B1 : WO_B0, td = (layer & 1) ? WO_DB1 : WO_DB0, tk = WOORD;
#pragma unroll 1
      for (int m = 0; m < 16; ++m) {
        uint32_t dst = sb + ((uint32_t)ts & 15) * SLOT + cr * 8192, fb = bar + B_FULLT + m * 8, eb = bar + B_CONS + ((uint32_t)td & 15) * 8;
        int kc = ((2 * g + (uint32_t)tk) & 15) * 64;
        ts >>= 4; td >>= 4; tk >>= 4;
        if (m == ((layer & 1) ? GWB : GWA)) mbar_wait_u(bar + B_OF, layer & 1);
        asm volatile("" : "+r"(dst), "+r"(fb), "+r"(eb), "+r"(kc));
        mbar_wait_u(eb, layer & 1);
        tma_2d_mc_e(dst, two, g * 128 + cr * 64, kc, fb);
        expect_tx_e(fb, m < 2 ? 16384 : 32768);
        PROFT(lane == 0 && layer == PL, 144 + m);
        if (m == 0) {
          fence_async_all();
          expect_tx_e(bar + B_XOLD, 32768);
          tma_2d_e(sb + XS * SLOT, tx, g * 128, m0, bar + B_XOLD);
          tma_2d_e(sb + (XS + 1) * SLOT, tx, g * 128 + 64, m0, bar + B_XOLD);
        }
      }
    };
    if (warp == 0) {
      cluster_wait();
      PROFT(lane == 0, 125);
#pragma unroll 1
      for (int layer = 0; layer < NLAYERS; ++layer) {
        const CUtensorMap* tx = layer == 0 ? &tm_x0 : &tm_x;
        const CUtensorMap* tw = (layer & 1) ? &tm_wB : &tm_wA;
        uint32_t s = layer == 0, u = 0, ready = layer == 0 ? 0xFFFFu : 0u;
#pragma unroll 1
        for (int i = s; i < 16; ++i) {
          const int kb = layer == 0 ? kblock0(i, g) : wo_kblock(i, g), kc = kb * 64;
          const uint32_t fb = bar + B_FULLS + s * 8;
          const uint32_t kd = sb + (((QK >> (4 * s)) & 15) + cr) * SLOT, qd = sb + ((QQ >> (4 * s)) & 15) * SLOT + cr * 8192;
          const uint32_t need = 1u << kb;
          const bool ext = i >= 2 || layer == 0, early = ext && (ready & need) == need;
          mbar_wait_u(bar + B_EMPTYS + s * 8, (u + (s ? layer : 0) + 1) & 1);
          if (early) tma_2d_e(sb + ((QA >> (4 * s)) & 15) * SLOT, tx, kc, m0, fb);
          tma_2d_mc_e(kd, tw, 1024 + cr * 1024 + g * 128, kc, fb);
          tma_2d_mc_e(kd + 8192, tw, 1024 + cr * 1024 + g * 128 + 64, kc, fb);
          tma_2d_mc_e(qd, tw, g * 128 + cr * 64, kc, fb);
          expect_tx_e(fb, ext ? 65536 : 49152);
          PROFT(lane == 0 && layer == 0 && i == 1, 31);
          if (layer == 0 && i == 2) {
            mbar_wait_u(bar + B_FULLS, 0);
            tma_pf_e(&tm_x0, g * 128, m0);
            tma_pf_e(&tm_x0, g * 128 + 64, m0);
          }
          if (layer < 2 && i >= PFS) {
            const int j = i - PFS;
            if (j < 2) tma_pf_e(layer ? &tm_woB : &tm_woA, g * 128 + j * 64, rb * 64);
            else if (j < 8 && layer == 0) tma_pf_e(&tm_wB, ((j >> 1) - 1) * 1024 + g * 128 + (j & 1) * 64, rb * 64);
          }
          if (ext && !early) {
            PROFT(i == 2 && lane == 0, 64 + layer * 16 + 0);
            src_wait<0>(g_xf + rb * 32, xbase + layer + 1, need, ready, lane);
            PROFT(i == 2 && lane == 0, 64 + layer * 16 + 1);
            fence_async_all();
            tma_2d_e(sb + ((QA >> (4 * s)) & 15) * SLOT, tx, kc, m0, fb);
          }
          if (++s == 3) { s = 0; ++u; }
        }
        if (layer == 0) xbase = ld_relaxed(&g_epoch) * NLAYERS;
        wo_a(layer);
      }
    } else {
      if (warp >= 2) {
        const int h2 = threadIdx.x - 64;
#pragma unroll 1
        for (int i = h2; i < 512; i += 64)
          asm volatile("cp.async.cg.shared.global [%0], [%1], 16;" ::"r"(sb + SM_WPHI + (i >> 2) * 80 + (i & 3) * 16), "l"(wphi + (size_t)g * 4096 + i * 8) : "memory");
        if (h2 < 16) sts_f(sb + SM_RS + h2 * 4, 0.f);
        if (h2 < 16) sts_f(bar + B_FLG + h2 * 4, __uint_as_float(xbase));
        if (h2 == 0) sts_f(sb + SM_EPOCH, __uint_as_float(epoch));
        if (rb >= CG0) mbar_wait_u(bar + B_FULLS + (rb >= CG1 ? 8 : 0), 0);
        if (CPF && h2 < 4) asm volatile("cp.async.bulk.prefetch.tensor.2d.L2.global.tile [%0, {%1, %2}];" ::"l"(&tm_wA), "r"((h2 & 2) * 1024 + g * 128 + (h2 & 1) * 64), "r"(rb * 64) : "memory");
#pragma unroll 1
        for (int wi = 0; wi < 3; ++wi) {
          float sA[8];
          colsum_load(wA, rb, g, warp - 2 + 2 * wi, lane, sb + SM_BP + (warp - 2) * 6144, sA);
          colsum_red(g_cs + (epoch & 1) * 6144, g, warp - 2 + 2 * wi, lane, sA);
        }
#pragma unroll 1
        for (int i = h2; i < 320; i += 64) g_kv[(g * 16 + rb) * 320 + i] = make_uint4(0u, 0u, 0u, 0u);
        fence_async_all();
        nbar<5, 64>();
        if (h2 == 0) flag_add(&g_csflag[g].v);
        PROFT(h2 == 0, 242);
      }
      if (warp == 1) {
        if (lane >= 27) {
          const CUtensorMap* tm = lane == 27 ? &tm_o : lane == 28 ? &tm_wB : lane == 29 ? &tm_woA : lane == 30 ? &tm_woB : &tm_x;
          asm volatile("prefetch.tensormap [%0];" ::"l"(tm) : "memory");
        }
        if (lane == 0) {
#pragma unroll 1
          for (int e = 0;; ++e) {
            if (e > 0 && e < NLAYERS) {
              mbar_wait(bar + B_XH0, (e - 1) & 1);
              flag_set(g_xf + rb * 32 + 2 * g, xbase + e + 1);
            }
            mbar_wait(bar + B_XDONE, e & 1);
            PROFT(e < 4, 64 + e * 16 + 4);
            if (e == NLAYERS) {
              if (blockIdx.x == 0) g_epoch = epoch + 1;
              break;
            }
            PROFT(e < 4, 64 + e * 16 + 5);
            flag_set(g_xf + rb * 32 + 2 * g + 1, xbase + e + 1);
            PROFT(e < 4, 64 + e * 16 + 7);
            if ((e & 1) == 0) {
#pragma unroll 1
              for (int hp = 0; hp < 2; ++hp) {
                uint4* kvl = g_kv + ((g * 2 + (e >> 1)) * 2 + hp) * 1280;
                mbar_wait(bar + B_KVDONE - hp * 32, (e >> 1) & 1);
                PROFT(e == PL, 243 + hp * 4);
                bulk_red_add(kvl + rb * 64, sb + (3 + hp) * SLOT + rb * 1024, 16384 - rb * 1024);
                if (rb) bulk_red_add(kvl, sb + (3 + hp) * SLOT, rb * 1024);
                bulk_red_add(kvl + 1024, sb + (6 + hp) * SLOT, 2048);
                bulk_red_add(kvl + 1152, sb + (6 + hp) * SLOT + 8192, 2048);
                bulk_commit();
                PROFT(e < 4, 64 + e * 16 + 6);
              }
              bulk_wait_read0();
              release2(bar + B_E1);
              release2(bar + B_E1);
            }
            mbar_wait(bar + B_OH1, e & 1);
            flag_set(g_of + rb * 32 + 2 * g, xbase + e + 1);
            PROFT(e < 4, 64 + e * 16 + 9);
            mbar_wait(bar + B_ODONE, e & 1);
            PROFT(e < 4, 64 + e * 16 + 8);
            flag_set(g_of + rb * 32 + 2 * g + 1, xbase + e + 1);
            release2(bar + B_OF);
            PROFT(e < 4, 64 + e * 16 + 11);
          }
        }
      } else {
        const int h2 = threadIdx.x - 64;
        const float* cs = g_cs + (epoch & 1) * 6144;
#pragma unroll 1
        for (int layer = 0; layer < NLAYERS; ++layer) {
          if (warp == 2 && layer < 2) {
            if (lane == 0) flag_wait_t<CSLP>(&g_csflag[layer * 8 + g].v, cbase + 16u);
            __syncwarp();
            float4 a[3];
#pragma unroll
            for (int i = 0; i < 3; ++i) a[i] = __ldcg(reinterpret_cast<const float4*>(cs + layer * 3072 + g * 384) + i * 32 + lane);
#pragma unroll 1
            for (int i = 0; i < 3; ++i) {
              const float av[4] = {a[0].x, a[0].y, a[0].z, a[0].w};
              a[0] = a[1]; a[1] = a[2];
#pragma unroll
              for (int j = 0; j < 4; ++j) {
                const float c1 = bf16r(av[j]), c2 = bf16r(av[j] - c1), c3 = (av[j] - c1) - c2;
                sts128(sb + SM_BP + layer * 6144 + ((i * 32 + lane) * 4 + j) * 16, make_uint4(pack_bf16(c1, c2), pack_bf16(c3, 0.f), 0u, 0u));
              }
            }
            fence_async_smem();
            __syncwarp();
            if (lane == 0) mbar_arrive(bar + (layer ? B_CS2 : B_CS));
            PROFT(lane == 0, 64 + layer * 16 + 12);
            if (layer == 0) {
              uint4* hz = g_halo + (size_t)((epoch & 1) ^ 1) * (2 * 128 * 512) + blockIdx.x * 1024;
#pragma unroll 2
              for (int i = lane; i < 1024; i += 32) hz[i] = make_uint4(0u, 0u, 0u, 0u);
              if (lane < 12) reinterpret_cast<float4*>(g_cs + ((epoch & 1) ^ 1) * 6144 + blockIdx.x * 48)[lane] = make_float4(0.f, 0.f, 0.f, 0.f);
              g_stats[(2 + (lane >> 4)) * S_ + m0 + g * 16 + (lane & 15)] = make_float2(0.f, 0.f);
            }
          }
          if (warp == 3) {
            const bool hal = (layer & 1) && rb > 0;
            {
              uint32_t rdy = 0u;
              src_wait<256>(g_xf + rb * 32, xbase + layer + 1, 0xAAAAu, rdy, lane);
              rdy = 0u;
              if (hal) src_wait<256>(g_xf + (rb - 1) * 32, xbase + layer + 1, 0xAAAAu, rdy, lane);
            }
            float2 u[5];
            const float2* sp = g_stats + layer * S_ + m0 + lane;
#pragma unroll
            for (int i = 0; i < 4; ++i) u[i] = __ldcg(sp + i * 32);
            u[4] = __ldcg(hal ? sp - 16 : sp);
            if (layer == 3) g_stats[(lane >> 4) * S_ + m0 + g * 16 + (lane & 15)] = make_float2(0.f, 0.f);
#pragma unroll 1
            for (int i = 0; i < (hal ? 5 : 4); ++i) {
              const int r = i < 4 ? 16 + i * 32 + lane : lane;
              const float sum = u[0].x, sq = u[0].y;
              u[0] = u[1]; u[1] = u[2]; u[2] = u[3]; u[3] = u[4];
              const float mean = sum * (1.f / D_);
              const float var = fmaxf(fmaf(-sum, mean, sq) * (1.f / D_), 0.f);
              const float sd = bf16r(sqrtf(bf16r(bf16r(var) + 1e-5f)));
              sts_f(sb + SM_RS + r * 4, 1.f / sd);
              if (i < 4) {
                const float hm = -0.5f * bf16r(mean);
                const uint32_t s2 = pack_bf16(sd, sd);
                sts128(sb + SM_SD + (r - 16) * 64 + ((r >> 1) & 3) * 16, make_uint4(s2, s2, s2, s2));
                sts128(sb + SM_AP + (r - 16) * 16, make_uint4(pack_bf16(hm, hm), pack_bf16(hm, 0.f), 0u, 0u));
              }
            }
            fence_async_smem();
            __syncwarp();
            if (lane == 0) mbar_arrive(bar + B_STAT);
            PROFT(lane == 0, 64 + layer * 16 + 14);
            wo_w(__shfl_sync(0xffffffffu, layer, 0));
          }
          if (layer == 0 && warp == 2) {
            if (CSW) mbar_wait_u(bar + (CSW == 1 ? B_E0 : CSW == 2 ? B_OH1 : B_ODONE), 0);
#pragma unroll 1
            for (int wi = 0; wi < 6; ++wi) {
              float sB[8];
              colsum_load(wB, rb, g, wi, lane, sb + SM_BP + 6144, sB);
              colsum_red(g_cs + (epoch & 1) * 6144 + 3072, g, wi, lane, sB);
            }
            __syncwarp();
            if (lane == 0) flag_add(&g_csflag[8 + g].v);
            PROFT(h2 == 0, 64 + 13);
          }
        }
      }
    }
    __syncwarp();
    asm volatile("barrier.cluster.arrive.relaxed.aligned;\nbarrier.cluster.wait.aligned;\n" ::: "memory");
  } else {
    if (warp == 5) {
      if (lane == 0) {
        mbar_init(bar + B_FULLS, 1);
        asm volatile("fence.mbarrier_init.release.cluster;" ::: "memory");
      }
      __syncwarp();
      expect_tx_e(bar + B_FULLS, 65536);
      tma_2d_e(sb + XS * SLOT, &tm_x0, 0, m0, bar + B_FULLS);
#pragma unroll
      for (int j = 0; j < 6; ++j)
        tma_2d_e(sb + (j < 4 ? j + 4 : j - 2) * 8192, &tm_wA, (j < 4 ? 1024 + (j >> 1) * 1024 : 0) + g * 128 + (j & 1) * 64, 0, bar + B_FULLS);
      PROFT(lane == 0, 241);
    }
    if (lane < 8 && warp != 5 && threadIdx.x != 128) {
      const int i = (warp - 4) * 8 + lane;
      mbar_init(bar + i * 8, i < 32 ? 1u << ((BAR_CNT >> (2 * i)) & 3) : i < 48 ? 1u : (i == 59 || i == 60) ? 16u : i < 63 ? 4u : 8u);
      asm volatile("fence.mbarrier_init.release.cluster;" ::: "memory");
    }
    __syncwarp();
    asm volatile("barrier.cluster.arrive.relaxed.aligned;" ::: "memory");
    asm volatile("setmaxnreg.inc.sync.aligned.u32 232;");
    cluster_wait();
    PROFT(threadIdx.x == 128, 0);
    Ctx c; c.sb = sb; c.g = g; c.rb = rb; c.cu = warp - 4; c.out = out;
    consumer(c);
    asm volatile("bar.warp.sync 0xffffffff;\nbarrier.cluster.arrive.relaxed.aligned;\nbarrier.cluster.wait.aligned;\n" ::: "memory");
  }
}

typedef CUresult (*PFN_encodeTiled)(CUtensorMap*, CUtensorMapDataType, cuuint32_t, void*, const cuuint64_t*, const cuuint64_t*,
                                    const cuuint32_t*, const cuuint32_t*, CUtensorMapInterleave, CUtensorMapSwizzle,
                                    CUtensorMapL2promotion, CUtensorMapFloatOOBfill);

static CUtensorMap make_map(PFN_encodeTiled enc, const void* ptr, uint64_t cols, uint64_t rows, uint32_t box_c, uint32_t box_r, uint32_t nb = 1) {
  CUtensorMap m;
  cuuint64_t dims[3] = {nb > 1 ? box_c : cols, rows, cols / box_c};
  cuuint64_t strides[2] = {cols * 2, box_c * 2};
  cuuint32_t box[3] = {box_c, box_r, nb};
  cuuint32_t es[3] = {1, 1, 1};
  CUresult r = enc(&m, CU_TENSOR_MAP_DATA_TYPE_BFLOAT16, nb > 1 ? 3 : 2, const_cast<void*>(ptr), dims, strides, box, es, CU_TENSOR_MAP_INTERLEAVE_NONE,
      CU_TENSOR_MAP_SWIZZLE_128B, CU_TENSOR_MAP_L2_PROMOTION_L2_256B, CU_TENSOR_MAP_FLOAT_OOB_FILL_NONE);
  (void)r;
  return m;
}

extern "C" void kernel_launch(void* const* d_in, const int* in_sizes, int n_in, void* d_out, int out_size) {
  const bf16* A_x = (const bf16*)d_in[0];
  const bf16* A_wqkv = (const bf16*)d_in[1];
  const bf16* A_wphi = (const bf16*)d_in[2];
  const bf16* A_wo = (const bf16*)d_in[3];
  const bf16* B_wqkv = (const bf16*)d_in[5];
  const bf16* B_wo = (const bf16*)d_in[6];
  bf16* out = (bf16*)d_out;

  static PFN_encodeTiled enc = nullptr;
  static bf16 *p_x, *p_o;
  if (!enc) {
    void* fn = nullptr; cudaDriverEntryPointQueryResult qr;
    cudaGetDriverEntryPoint("cuTensorMapEncodeTiled", &fn, cudaEnableDefault, &qr);
    enc = (PFN_encodeTiled)fn;
    cudaGetSymbolAddress((void**)&p_x, g_x);
    cudaGetSymbolAddress((void**)&p_o, g_o);
    cudaFuncSetAttribute(mega_kernel, cudaFuncAttributeMaxDynamicSharedMemorySize, SM_TOTAL);
  }
  CUtensorMap tm_x0 = make_map(enc, A_x, 1024, 2048, 64, 128);
  CUtensorMap tm_x = make_map(enc, p_x, 1024, 2048, 64, 128);
  CUtensorMap tm_o = make_map(enc, p_o, 1024, 2048, 64, 128);
  CUtensorMap tm_wA = make_map(enc, A_wqkv, 3072, 1024, 64, 64);
  CUtensorMap tm_wB = make_map(enc, B_wqkv, 3072, 1024, 64, 64);
  CUtensorMap tm_woA = make_map(enc, A_wo, 1024, 1024, 64, 64);
  CUtensorMap tm_woB = make_map(enc, B_wo, 1024, 1024, 64, 64);
  mega_kernel<<<128, 384, SM_TOTAL, cudaStreamPerThread>>>(tm_x0, tm_x, tm_o, tm_wA, tm_wB, tm_woA, tm_woB,
                                                           A_wqkv, B_wqkv, A_wphi, out);
}
```

```cpp
#include <cuda_runtime.h>
#include <cuda_bf16.h>
#include <cuda.h>
#include <stdint.h>

typedef __nv_bfloat16 bf16;

constexpr int S_ = 2048, D_ = 1024;

struct __align__(128) Flag { unsigned int v; unsigned int pad[31]; };
__device__ __align__(1024) bf16 g_x[S_ * D_];
__device__ __align__(1024) bf16 g_o[S_ * D_];
__device__ __align__(1024) uint4 g_halo[2 * 2 * 128 * 512];
__device__ __align__(1024) uint4 g_kv[8 * 2 * 2 * 1280];
__device__ __align__(1024) float2 g_stats[4 * S_];
__device__ __align__(1024) float g_cs[2 * 2 * 3072];
__device__ Flag g_csflag[16];
__device__ __align__(128) unsigned int g_xf[16 * 32], g_of[16 * 32];
__device__ unsigned int g_epoch, g_err;
#define PROFT(cond, idx) asm volatile("" ::: "memory")

__device__ __forceinline__ uint32_t smem_u32(const void* p) { return (uint32_t)__cvta_generic_to_shared(p); }
__device__ __forceinline__ void mbar_init(uint32_t bar, uint32_t count) {
  asm volatile("mbarrier.init.shared::cta.b64 [%0], %1;" ::"r"(bar), "r"(count) : "memory");
}
__device__ __forceinline__ void mbar_expect_tx(uint32_t bar, uint32_t bytes) {
  asm volatile("mbarrier.arrive.expect_tx.shared::cta.b64 _, [%0], %1;" ::"r"(bar), "r"(bytes) : "memory");
}
__device__ __forceinline__ void mbar_arrive(uint32_t bar) {
  asm volatile("mbarrier.arrive.shared::cta.b64 _, [%0];" ::"r"(bar) : "memory");
}
__device__ __forceinline__ bool mbar_try_wait(uint32_t bar, uint32_t parity) {
  uint32_t ok;
  asm volatile("{\n.reg .pred p;\nmbarrier.try_wait.parity.shared::cta.b64 p, [%1], %2;\nselp.b32 %0, 1, 0, p;\n}\n"
               : "=r"(ok) : "r"(bar), "r"(parity) : "memory");
  return ok != 0;
}
__device__ __forceinline__ bool mbar_test_wait(uint32_t bar, uint32_t parity) {
  uint32_t ok;
  asm volatile("{\n.reg .pred p;\nmbarrier.test_wait.parity.shared::cta.b64 p, [%1], %2;\nselp.b32 %0, 1, 0, p;\n}\n"
               : "=r"(ok) : "r"(bar), "r"(parity) : "memory");
  return ok != 0;
}
__device__ __forceinline__ uint64_t gtimer() {
  uint64_t t; asm volatile("mov.u64 %0, %globaltimer;" : "=l"(t)); return t;
}
__device__ __forceinline__ void mbar_wait(uint32_t bar, uint32_t parity) {
  uint32_t n = 0;
#pragma unroll 1
  while (!mbar_try_wait(bar, parity)) {
    if (++n > (1u << 22)) { g_err = 1u; break; }
  }
}
__device__ __forceinline__ unsigned int ld_acquire(const unsigned int* p) {
  unsigned int v; asm volatile("ld.acquire.gpu.global.u32 %0, [%1];" : "=r"(v) : "l"(p) : "memory"); return v;
}
__device__ __forceinline__ void flag_add(unsigned int* p) {
  asm volatile("red.release.gpu.global.add.u32 [%0], 1;" ::"l"(p) : "memory");
}
__device__ __forceinline__ void flag_set(unsigned int* p, unsigned int v) {
  asm volatile("st.release.gpu.global.u32 [%0], %1;" ::"l"(p), "r"(v) : "memory");
}
template <int SLEEP>
__device__ __forceinline__ void src_wait(const unsigned int* f, unsigned int target, uint32_t need, uint32_t& ready, int lane) {
  uint32_t n = 0;
#pragma unroll 1
  while ((ready & need) != need) {
    const unsigned int v = ld_acquire(f + (lane & 15));
    ready = __ballot_sync(0xffffffffu, (int)(v - target) >= 0);
    if (SLEEP) { if ((ready & need) != need) __nanosleep(SLEEP); }
    if (++n > (1u << 20)) { g_err = 3u; break; }
  }
  __syncwarp();
}
__device__ __forceinline__ unsigned int ld_relaxed(const unsigned int* p) {
  unsigned int v; asm volatile("ld.relaxed.gpu.global.u32 %0, [%1];" : "=r"(v) : "l"(p) : "memory"); return v;
}
__device__ __forceinline__ uint4 ld_relaxed4(const uint4* p) {
  uint4 v; asm volatile("ld.relaxed.gpu.global.v4.u32 {%0,%1,%2,%3}, [%4];" : "=r"(v.x), "=r"(v.y), "=r"(v.z), "=r"(v.w) : "l"(p) : "memory"); return v;
}
__device__ __forceinline__ void st_relaxed4(uint4* p, uint32_t a, uint32_t b, uint32_t c, uint32_t d) {
  asm volatile("st.relaxed.gpu.global.v4.u32 [%0], {%1,%2,%3,%4};" ::"l"(p), "r"(a), "r"(b), "r"(c), "r"(d) : "memory");
}
template <int SLEEP>
__device__ __forceinline__ void flag_wait_t(const unsigned int* p, unsigned int target) {
  uint32_t n = 0;
#pragma unroll 1
  while ((int)(ld_acquire(p) - target) < 0) {
    if (SLEEP) __nanosleep(SLEEP);
    if (++n > (1u << 20)) { g_err = 2u; break; }
  }
}
__device__ __forceinline__ void flag_wait(const unsigned int* p, unsigned int target) { flag_wait_t<0>(p, target); }
__device__ __forceinline__ void flag_wait_slow(const unsigned int* p, unsigned int target) { flag_wait_t<256>(p, target); }
__device__ __forceinline__ void tma_load_2d(uint32_t dst, const CUtensorMap* tm, int c0, int c1, uint32_t bar) {
  asm volatile("cp.async.bulk.tensor.2d.shared::cluster.global.mbarrier::complete_tx::bytes [%0], [%1, {%2, %3}], [%4];"
               ::"r"(dst), "l"(tm), "r"(c0), "r"(c1), "r"(bar) : "memory");
}
__device__ __forceinline__ void tma_load_2d_mc(uint32_t dst, const CUtensorMap* tm, int c0, int c1, uint32_t bar, uint16_t mask) {
  asm volatile("cp.async.bulk.tensor.2d.shared::cluster.global.mbarrier::complete_tx::bytes.multicast::cluster [%0], [%1, {%2, %3}], [%4], %5;"
               ::"r"(dst), "l"(tm), "r"(c0), "r"(c1), "r"(bar), "h"(mask) : "memory");
}
__device__ __forceinline__ void mbar_wait_u(uint32_t bar, uint32_t parity) {
  uint32_t n = 0;
#pragma unroll 1
  while (!__all_sync(0xffffffffu, mbar_try_wait(bar, parity))) {
    if (++n > (1u << 22)) { g_err = 1u; break; }
  }
}
__device__ __forceinline__ void expect_tx_e(uint32_t bar, uint32_t bytes) {
  asm volatile("{\n.reg .pred p;\nelect.sync _|p, 0xffffffff;\n@p mbarrier.arrive.expect_tx.shared::cta.b64 _, [%0], %1;\n}\n" ::"r"(bar), "r"(bytes) : "memory");
}
__device__ __forceinline__ void tma_2d_e(uint32_t dst, const CUtensorMap* tm, int c0, int c1, uint32_t bar) {
  asm volatile("{\n.reg .pred p;\nelect.sync _|p, 0xffffffff;\n"
               "@p cp.async.bulk.tensor.2d.shared::cluster.global.mbarrier::complete_tx::bytes [%0], [%1, {%2, %3}], [%4];\n}\n"
               ::"r"(dst), "l"(tm), "r"(c0), "r"(c1), "r"(bar) : "memory");
}
__device__ __forceinline__ void tma_2d_mc_e(uint32_t dst, const CUtensorMap* tm, int c0, int c1, uint32_t bar) {
  asm volatile("{\n.reg .pred p;\nelect.sync _|p, 0xffffffff;\n"
               "@p cp.async.bulk.tensor.2d.shared::cluster.global.mbarrier::complete_tx::bytes.multicast::cluster [%0], [%1, {%2, %3}], [%4], %5;\n}\n"
               ::"r"(dst), "l"(tm), "r"(c0), "r"(c1), "r"(bar), "h"((uint16_t)3) : "memory");
}
__device__ __forceinline__ void tma_pf_e(const CUtensorMap* tm, int c0, int c1) {
  asm volatile("{\n.reg .pred p;\nelect.sync _|p, 0xffffffff;\n"
               "@p cp.async.bulk.prefetch.tensor.2d.L2.global.tile [%0, {%1, %2}];\n}\n" ::"l"(tm), "r"(c0), "r"(c1) : "memory");
}
__device__ __forceinline__ void tma_2d_to_e(uint32_t dst, const CUtensorMap* tm, int c0, int c1, uint32_t bar, uint32_t mask) {
  asm volatile("{\n.reg .pred p;\nelect.sync _|p, 0xffffffff;\n"
               "@p cp.async.bulk.tensor.2d.shared::cluster.global.mbarrier::complete_tx::bytes.multicast::cluster [%0], [%1, {%2, %3}], [%4], %5;\n}\n"
               ::"r"(dst), "l"(tm), "r"(c0), "r"(c1), "r"(bar), "h"((uint16_t)mask) : "memory");
}
__device__ __forceinline__ void tma_3d_mc_e(uint32_t dst, const CUtensorMap* tm, int c1, int c2, uint32_t bar) {
  asm volatile("{\n.reg .pred p;\nelect.sync _|p, 0xffffffff;\n"
               "@p cp.async.bulk.tensor.3d.shared::cluster.global.mbarrier::complete_tx::bytes.multicast::cluster [%0], [%1, {%6, %2, %3}], [%4], %5;\n}\n"
               ::"r"(dst), "l"(tm), "r"(c1), "r"(c2), "r"(bar), "h"((uint16_t)3), "r"(0) : "memory");
}
__device__ __forceinline__ uint32_t poll_flags(const unsigned int* f, unsigned int target, int lane) {
  const unsigned int v = ld_acquire(f + (lane & 15));
  const uint32_t r = __ballot_sync(0xffffffffu, (int)(v - target) >= 0);
  __syncwarp();
  return r;
}
__device__ __forceinline__ void mbar_arrive_cluster(uint32_t local_bar, uint32_t rank) {
  asm volatile("{\n.reg .b32 ra;\nmapa.shared::cluster.u32 ra, %0, %1;\nmbarrier.arrive.shared::cluster.b64 _, [ra];\n}\n"
               ::"r"(local_bar), "r"(rank) : "memory");
}
__device__ __forceinline__ void release2(uint32_t bar) { mbar_arrive_cluster(bar, 0); mbar_arrive_cluster(bar, 1); }
__device__ __forceinline__ void tma_store_2d(const CUtensorMap* tm, uint32_t src, int c0, int c1) {
  asm volatile("cp.async.bulk.tensor.2d.global.shared::cta.bulk_group [%0, {%2, %3}], [%1];"
               ::"l"(tm), "r"(src), "r"(c0), "r"(c1) : "memory");
}
__device__ __forceinline__ void bulk_store(void* dst, uint32_t src, uint32_t bytes) {
  asm volatile("cp.async.bulk.global.shared::cta.bulk_group [%0], [%1], %2;" ::"l"(dst), "r"(src), "r"(bytes) : "memory");
}
__device__ __forceinline__ void bulk_load(uint32_t dst, const void* src, uint32_t bytes, uint32_t bar) {
  asm volatile("cp.async.bulk.shared::cluster.global.mbarrier::complete_tx::bytes [%0], [%1], %2, [%3];" ::"r"(dst), "l"(src), "r"(bytes), "r"(bar) : "memory");
}
__device__ __forceinline__ void bulk_red_add(void* dst, uint32_t src, uint32_t bytes) {
  asm volatile("cp.reduce.async.bulk.global.shared::cta.bulk_group.add.f32 [%0], [%1], %2;" ::"l"(dst), "r"(src), "r"(bytes) : "memory");
}
__device__ __forceinline__ void bulk_commit() { asm volatile("cp.async.bulk.commit_group;" ::: "memory"); }
__device__ __forceinline__ void bulk_wait_read0() { asm volatile("cp.async.bulk.wait_group.read 0;" ::: "memory"); }
__device__ __forceinline__ void bulk_wait0() { asm volatile("cp.async.bulk.wait_group 0;" ::: "memory"); }
__device__ __forceinline__ void fence_async_smem() { asm volatile("fence.proxy.async.shared::cta;" ::: "memory"); }
__device__ __forceinline__ void fence_async_all() { asm volatile("fence.proxy.async.global;" ::: "memory"); }
__device__ __forceinline__ void wgmma_fence() { asm volatile("wgmma.fence.sync.aligned;" ::: "memory"); }
__device__ __forceinline__ void wgmma_commit() { asm volatile("wgmma.commit_group.sync.aligned;" ::: "memory"); }
template <int N> __device__ __forceinline__ void wgmma_wait() { asm volatile("wgmma.wait_group.sync.aligned %0;" ::"n"(N) : "memory"); }
__device__ __forceinline__ void cluster_arrive() { asm volatile("barrier.cluster.arrive.release.aligned;" ::: "memory"); }
__device__ __forceinline__ void cluster_wait() { asm volatile("barrier.cluster.wait.acquire.aligned;" ::: "memory"); }
template <int ID, int N> __device__ __forceinline__ void nbar() { asm volatile("bar.sync %0, %1;" ::"n"(ID), "n"(N) : "memory"); }
__device__ __forceinline__ uint64_t make_desc(uint32_t addr, uint32_t lbo_bytes, uint32_t sbo_bytes) {
  uint64_t d = 0;
  d |= (uint64_t)((addr & 0x3FFFF) >> 4);
  d |= (uint64_t)((lbo_bytes >> 4) & 0x3FFF) << 16;
  d |= (uint64_t)((sbo_bytes >> 4) & 0x3FFF) << 32;
  d |= (uint64_t)1 << 62;
  return d;
}
__device__ __forceinline__ uint64_t desc64(uint32_t lo, uint32_t hi) { return (uint64_t)lo | ((uint64_t)hi << 32); }
__device__ __forceinline__ uint32_t pack_bf16(float lo, float hi) {
  uint32_t r; asm("cvt.rn.bf16x2.f32 %0, %1, %2;" : "=r"(r) : "f"(hi), "f"(lo)); return r;
}
__device__ __forceinline__ uint32_t mul_bf16x2(uint32_t a, uint32_t s, bool hi) {
  __nv_bfloat162 x = *reinterpret_cast<__nv_bfloat162*>(&a), y = *reinterpret_cast<__nv_bfloat162*>(&s);
  x = __hmul2(x, hi ? __high2bfloat162(y) : __low2bfloat162(y));
  return *reinterpret_cast<uint32_t*>(&x);
}
__device__ __forceinline__ float bf16r(float x) { return __bfloat162float(__float2bfloat16_rn(x)); }
__device__ __forceinline__ float bf_lo(uint32_t u) { return __uint_as_float(u << 16); }
__device__ __forceinline__ float bf_hi(uint32_t u) { return __uint_as_float(u & 0xFFFF0000u); }
__device__ __forceinline__ float ex2(float x) { float r; asm("ex2.approx.ftz.f32 %0, %1;" : "=f"(r) : "f"(x)); return r; }
__device__ __forceinline__ float rcp(float x) { float r; asm("rcp.approx.ftz.f32 %0, %1;" : "=f"(r) : "f"(x)); return r; }
__device__ __forceinline__ void mma_bf16(float (&d)[4], uint32_t a0, uint32_t a1, uint32_t a2, uint32_t a3, uint32_t b0, uint32_t b1) {
  asm("mma.sync.aligned.m16n8k16.row.col.f32.bf16.bf16.f32 {%0,%1,%2,%3}, {%4,%5,%6,%7}, {%8,%9}, {%0,%1,%2,%3};"
               : "+f"(d[0]), "+f"(d[1]), "+f"(d[2]), "+f"(d[3]) : "r"(a0), "r"(a1), "r"(a2), "r"(a3), "r"(b0), "r"(b1));
}
__device__ __forceinline__ void ldsm_x4(uint32_t& r0, uint32_t& r1, uint32_t& r2, uint32_t& r3, uint32_t addr) {
  asm volatile("ldmatrix.sync.aligned.m8n8.x4.shared.b16 {%0,%1,%2,%3}, [%4];"
               : "=r"(r0), "=r"(r1), "=r"(r2), "=r"(r3) : "r"(addr) : "memory");
}
__device__ __forceinline__ void ldsm_x4_t(uint32_t& r0, uint32_t& r1, uint32_t& r2, uint32_t& r3, uint32_t addr) {
  asm volatile("ldmatrix.sync.aligned.m8n8.x4.trans.shared.b16 {%0,%1,%2,%3}, [%4];"
               : "=r"(r0), "=r"(r1), "=r"(r2), "=r"(r3) : "r"(addr) : "memory");
}
__device__ __forceinline__ void ldsm_x2_t(uint32_t& r0, uint32_t& r1, uint32_t addr) {
  asm volatile("ldmatrix.sync.aligned.m8n8.x2.trans.shared.b16 {%0,%1}, [%2];"
               : "=r"(r0), "=r"(r1) : "r"(addr) : "memory");
}
__device__ __forceinline__ void stsm_x4(uint32_t addr, uint32_t r0, uint32_t r1, uint32_t r2, uint32_t r3) {
  asm volatile("stmatrix.sync.aligned.m8n8.x4.shared.b16 [%0], {%1,%2,%3,%4};"
               ::"r"(addr), "r"(r0), "r"(r1), "r"(r2), "r"(r3) : "memory");
}
__device__ __forceinline__ void stsm_x4_p(bool on, uint32_t addr, uint32_t r0, uint32_t r1, uint32_t r2, uint32_t r3) {
  asm volatile("{\n.reg .pred p;\nsetp.ne.b32 p, %5, 0;\n@p stmatrix.sync.aligned.m8n8.x4.shared.b16 [%0], {%1,%2,%3,%4};\n}\n"
               ::"r"(addr), "r"(r0), "r"(r1), "r"(r2), "r"(r3), "r"((int)on) : "memory");
}
__device__ __forceinline__ float2 lds_f2(uint32_t addr) {
  float2 v; asm volatile("ld.shared.v2.f32 {%0,%1}, [%2];" : "=f"(v.x), "=f"(v.y) : "r"(addr) : "memory"); return v;
}
__device__ __forceinline__ uint4 lds128(uint32_t addr) {
  uint4 v; asm volatile("ld.shared.v4.b32 {%0,%1,%2,%3}, [%4];" : "=r"(v.x), "=r"(v.y), "=r"(v.z), "=r"(v.w) : "r"(addr) : "memory"); return v;
}
__device__ __forceinline__ void sts128(uint32_t addr, uint4 v) {
  asm volatile("st.shared.v4.b32 [%0], {%1,%2,%3,%4};" ::"r"(addr), "r"(v.x), "r"(v.y), "r"(v.z), "r"(v.w) : "memory");
}
__device__ __forceinline__ float lds_f(uint32_t addr) {
  float v; asm volatile("ld.shared.f32 %0, [%1];" : "=f"(v) : "r"(addr) : "memory"); return v;
}
__device__ __forceinline__ uint32_t lds_vol(uint32_t addr) {
  uint32_t v; asm volatile("ld.volatile.shared.u32 %0, [%1];" : "=r"(v) : "r"(addr) : "memory"); return v;
}
__device__ __forceinline__ void sts16(uint32_t addr, uint32_t v) {
  asm volatile("st.shared.u16 [%0], %1;" ::"r"(addr), "h"((unsigned short)v) : "memory");
}
__device__ __forceinline__ void nbar_dyn(int id, int n) { asm volatile("bar.sync %0, %1;" ::"r"(id), "r"(n) : "memory"); }
__device__ __forceinline__ uint64_t make_desc_ns(uint32_t addr, uint32_t lbo_bytes, uint32_t sbo_bytes) {
  return (uint64_t)((addr & 0x3FFFF) >> 4) | ((uint64_t)(lbo_bytes >> 4) << 16) | ((uint64_t)(sbo_bytes >> 4) << 32);
}
__device__ __forceinline__ void sts_f(uint32_t addr, float v) { asm volatile("st.shared.f32 [%0], %1;" ::"r"(addr), "f"(v) : "memory"); }
__device__ __forceinline__ void sts64(uint32_t addr, uint32_t a, uint32_t b) {
  asm volatile("st.shared.v2.b32 [%0], {%1,%2};" ::"r"(addr), "r"(a), "r"(b) : "memory");
}
__device__ __forceinline__ void sts_f2(uint32_t addr, float a, float b) {
  asm volatile("st.shared.v2.f32 [%0], {%1,%2};" ::"r"(addr), "f"(a), "f"(b) : "memory");
}
__device__ __forceinline__ void red_add2(float* p, float a, float b) {
  asm volatile("red.global.add.v2.f32 [%0], {%1,%2};" ::"l"(p), "f"(a), "f"(b) : "memory");
}
__device__ __forceinline__ void red_add4(float* p, float a, float b, float c, float d) {
  asm volatile("red.global.add.v4.f32 [%0], {%1,%2,%3,%4};" ::"l"(p), "f"(a), "f"(b), "f"(c), "f"(d) : "memory");
}
__device__ __forceinline__ void red_add1(float* p, float a) {
  asm volatile("red.global.add.f32 [%0], %1;" ::"l"(p), "f"(a) : "memory");
}
__device__ __forceinline__ void l2_prefetch(const void* p, uint32_t bytes) {
  asm volatile("cp.async.bulk.prefetch.L2.global [%0], %1;" ::"l"(p), "r"(bytes) : "memory");
}

__device__ __forceinline__ void wgmma_n256(float (&d)[192], uint64_t da, uint64_t db, int scale_d) {
  asm volatile("{\n.reg .pred p;\nsetp.ne.b32 p, %130, 0;\n"
    "wgmma.mma_async.sync.aligned.m64n256k16.f32.bf16.bf16 {%0, %1, %2, %3, %4, %5, %6, %7, %8, %9, %10, %11, %12, %13, %14, %15, %16, %17, %18, %19, %20, %21, %22, %23, %24, %25, %26, %27, %28, %29, %30, %31, %32, %33, %34, %35, %36, %37, %38, %39, %40, %41, %42, %43, %44, %45, %46, %47, %48, %49, %50, %51, %52, %53, %54, %55, %56, %57, %58, %59, %60, %61, %62, %63, %64, %65, %66, %67, %68, %69, %70, %71, %72, %73, %74, %75, %76, %77, %78, %79, %80, %81, %82, %83, %84, %85, %86, %87, %88, %89, %90, %91, %92, %93, %94, %95, %96, %97, %98, %99, %100, %101, %102, %103, %104, %105, %106, %107, %108, %109, %110, %111, %112, %113, %114, %115, %116, %117, %118, %119, %120, %121, %122, %123, %124, %125, %126, %127}, %128, %129, p, 1, 1, 0, 1;\n}\n"
    : "+f"(d[0]), "+f"(d[1]), "+f"(d[2]), "+f"(d[3]), "+f"(d[4]), "+f"(d[5]), "+f"(d[6]), "+f"(d[7]), "+f"(d[8]), "+f"(d[9]), "+f"(d[10]), "+f"(d[11]), "+f"(d[12]), "+f"(d[13]), "+f"(d[14]), "+f"(d[15]), "+f"(d[16]), "+f"(d[17]), "+f"(d[18]), "+f"(d[19]), "+f"(d[20]), "+f"(d[21]), "+f"(d[22]), "+f"(d[23]), "+f"(d[24]), "+f"(d[25]), "+f"(d[26]), "+f"(d[27]), "+f"(d[28]), "+f"(d[29]), "+f"(d[30]), "+f"(d[31]), "+f"(d[32]), "+f"(d[33]), "+f"(d[34]), "+f"(d[35]), "+f"(d[36]), "+f"(d[37]), "+f"(d[38]), "+f"(d[39]), "+f"(d[40]), "+f"(d[41]), "+f"(d[42]), "+f"(d[43]), "+f"(d[44]), "+f"(d[45]), "+f"(d[46]), "+f"(d[47]), "+f"(d[48]), "+f"(d[49]), "+f"(d[50]), "+f"(d[51]), "+f"(d[52]), "+f"(d[53]), "+f"(d[54]), "+f"(d[55]), "+f"(d[56]), "+f"(d[57]), "+f"(d[58]), "+f"(d[59]), "+f"(d[60]), "+f"(d[61]), "+f"(d[62]), "+f"(d[63]), "+f"(d[64]), "+f"(d[65]), "+f"(d[66]), "+f"(d[67]), "+f"(d[68]), "+f"(d[69]), "+f"(d[70]), "+f"(d[71]), "+f"(d[72]), "+f"(d[73]), "+f"(d[74]), "+f"(d[75]), "+f"(d[76]), "+f"(d[77]), "+f"(d[78]), "+f"(d[79]), "+f"(d[80]), "+f"(d[81]), "+f"(d[82]), "+f"(d[83]), "+f"(d[84]), "+f"(d[85]), "+f"(d[86]), "+f"(d[87]), "+f"(d[88]), "+f"(d[89]), "+f"(d[90]), "+f"(d[91]), "+f"(d[92]), "+f"(d[93]), "+f"(d[94]), "+f"(d[95]), "+f"(d[96]), "+f"(d[97]), "+f"(d[98]), "+f"(d[99]), "+f"(d[100]), "+f"(d[101]), "+f"(d[102]), "+f"(d[103]), "+f"(d[104]), "+f"(d[105]), "+f"(d[106]), "+f"(d[107]), "+f"(d[108]), "+f"(d[109]), "+f"(d[110]), "+f"(d[111]), "+f"(d[112]), "+f"(d[113]), "+f"(d[114]), "+f"(d[115]), "+f"(d[116]), "+f"(d[117]), "+f"(d[118]), "+f"(d[119]), "+f"(d[120]), "+f"(d[121]), "+f"(d[122]), "+f"(d[123]), "+f"(d[124]), "+f"(d[125]), "+f"(d[126]), "+f"(d[127])
    : "l"(da), "l"(db), "r"(scale_d));
}
__device__ __forceinline__ void wgmma_n128(float (&d)[192], uint64_t da, uint64_t db, int scale_d) {
  asm volatile("{\n.reg .pred p;\nsetp.ne.b32 p, %66, 0;\n"
    "wgmma.mma_async.sync.aligned.m64n128k16.f32.bf16.bf16 {%0, %1, %2, %3, %4, %5, %6, %7, %8, %9, %10, %11, %12, %13, %14, %15, %16, %17, %18, %19, %20, %21, %22, %23, %24, %25, %26, %27, %28, %29, %30, %31, %32, %33, %34, %35, %36, %37, %38, %39, %40, %41, %42, %43, %44, %45, %46, %47, %48, %49, %50, %51, %52, %53, %54, %55, %56, %57, %58, %59, %60, %61, %62, %63}, %64, %65, p, 1, 1, 0, 1;\n}\n"
    : "+f"(d[128]), "+f"(d[129]), "+f"(d[130]), "+f"(d[131]), "+f"(d[132]), "+f"(d[133]), "+f"(d[134]), "+f"(d[135]), "+f"(d[136]), "+f"(d[137]), "+f"(d[138]), "+f"(d[139]), "+f"(d[140]), "+f"(d[141]), "+f"(d[142]), "+f"(d[143]), "+f"(d[144]), "+f"(d[145]), "+f"(d[146]), "+f"(d[147]), "+f"(d[148]), "+f"(d[149]), "+f"(d[150]), "+f"(d[151]), "+f"(d[152]), "+f"(d[153]), "+f"(d[154]), "+f"(d[155]), "+f"(d[156]), "+f"(d[157]), "+f"(d[158]), "+f"(d[159]), "+f"(d[160]), "+f"(d[161]), "+f"(d[162]), "+f"(d[163]), "+f"(d[164]), "+f"(d[165]), "+f"(d[166]), "+f"(d[167]), "+f"(d[168]), "+f"(d[169]), "+f"(d[170]), "+f"(d[171]), "+f"(d[172]), "+f"(d[173]), "+f"(d[174]), "+f"(d[175]), "+f"(d[176]), "+f"(d[177]), "+f"(d[178]), "+f"(d[179]), "+f"(d[180]), "+f"(d[181]), "+f"(d[182]), "+f"(d[183]), "+f"(d[184]), "+f"(d[185]), "+f"(d[186]), "+f"(d[187]), "+f"(d[188]), "+f"(d[189]), "+f"(d[190]), "+f"(d[191])
    : "l"(da), "l"(db), "r"(scale_d));
}
__device__ __forceinline__ void wgmma_n256_k(float (&d)[192], uint64_t da, uint64_t db, int scale_d) {
  asm volatile("{\n.reg .pred p;\nsetp.ne.b32 p, %130, 0;\n"
    "wgmma.mma_async.sync.aligned.m64n256k16.f32.bf16.bf16 {%0, %1, %2, %3, %4, %5, %6, %7, %8, %9, %10, %11, %12, %13, %14, %15, %16, %17, %18, %19, %20, %21, %22, %23, %24, %25, %26, %27, %28, %29, %30, %31, %32, %33, %34, %35, %36, %37, %38, %39, %40, %41, %42, %43, %44, %45, %46, %47, %48, %49, %50, %51, %52, %53, %54, %55, %56, %57, %58, %59, %60, %61, %62, %63, %64, %65, %66, %67, %68, %69, %70, %71, %72, %73, %74, %75, %76, %77, %78, %79, %80, %81, %82, %83, %84, %85, %86, %87, %88, %89, %90, %91, %92, %93, %94, %95, %96, %97, %98, %99, %100, %101, %102, %103, %104, %105, %106, %107, %108, %109, %110, %111, %112, %113, %114, %115, %116, %117, %118, %119, %120, %121, %122, %123, %124, %125, %126, %127}, %128, %129, p, 1, 1, 0, 0;\n}\n"
    : "+f"(d[0]), "+f"(d[1]), "+f"(d[2]), "+f"(d[3]), "+f"(d[4]), "+f"(d[5]), "+f"(d[6]), "+f"(d[7]), "+f"(d[8]), "+f"(d[9]), "+f"(d[10]), "+f"(d[11]), "+f"(d[12]), "+f"(d[13]), "+f"(d[14]), "+f"(d[15]), "+f"(d[16]), "+f"(d[17]), "+f"(d[18]), "+f"(d[19]), "+f"(d[20]), "+f"(d[21]), "+f"(d[22]), "+f"(d[23]), "+f"(d[24]), "+f"(d[25]), "+f"(d[26]), "+f"(d[27]), "+f"(d[28]), "+f"(d[29]), "+f"(d[30]), "+f"(d[31]), "+f"(d[32]), "+f"(d[33]), "+f"(d[34]), "+f"(d[35]), "+f"(d[36]), "+f"(d[37]), "+f"(d[38]), "+f"(d[39]), "+f"(d[40]), "+f"(d[41]), "+f"(d[42]), "+f"(d[43]), "+f"(d[44]), "+f"(d[45]), "+f"(d[46]), "+f"(d[47]), "+f"(d[48]), "+f"(d[49]), "+f"(d[50]), "+f"(d[51]), "+f"(d[52]), "+f"(d[53]), "+f"(d[54]), "+f"(d[55]), "+f"(d[56]), "+f"(d[57]), "+f"(d[58]), "+f"(d[59]), "+f"(d[60]), "+f"(d[61]), "+f"(d[62]), "+f"(d[63]), "+f"(d[64]), "+f"(d[65]), "+f"(d[66]), "+f"(d[67]), "+f"(d[68]), "+f"(d[69]), "+f"(d[70]), "+f"(d[71]), "+f"(d[72]), "+f"(d[73]), "+f"(d[74]), "+f"(d[75]), "+f"(d[76]), "+f"(d[77]), "+f"(d[78]), "+f"(d[79]), "+f"(d[80]), "+f"(d[81]), "+f"(d[82]), "+f"(d[83]), "+f"(d[84]), "+f"(d[85]), "+f"(d[86]), "+f"(d[87]), "+f"(d[88]), "+f"(d[89]), "+f"(d[90]), "+f"(d[91]), "+f"(d[92]), "+f"(d[93]), "+f"(d[94]), "+f"(d[95]), "+f"(d[96]), "+f"(d[97]), "+f"(d[98]), "+f"(d[99]), "+f"(d[100]), "+f"(d[101]), "+f"(d[102]), "+f"(d[103]), "+f"(d[104]), "+f"(d[105]), "+f"(d[106]), "+f"(d[107]), "+f"(d[108]), "+f"(d[109]), "+f"(d[110]), "+f"(d[111]), "+f"(d[112]), "+f"(d[113]), "+f"(d[114]), "+f"(d[115]), "+f"(d[116]), "+f"(d[117]), "+f"(d[118]), "+f"(d[119]), "+f"(d[120]), "+f"(d[121]), "+f"(d[122]), "+f"(d[123]), "+f"(d[124]), "+f"(d[125]), "+f"(d[126]), "+f"(d[127])
    : "l"(da), "l"(db), "r"(scale_d));
}
__device__ __forceinline__ void wgmma_n128_k(float (&d)[192], uint64_t da, uint64_t db, int scale_d) {
  asm volatile("{\n.reg .pred p;\nsetp.ne.b32 p, %66, 0;\n"
    "wgmma.mma_async.sync.aligned.m64n128k16.f32.bf16.bf16 {%0, %1, %2, %3, %4, %5, %6, %7, %8, %9, %10, %11, %12, %13, %14, %15, %16, %17, %18, %19, %20, %21, %22, %23, %24, %25, %26, %27, %28, %29, %30, %31, %32, %33, %34, %35, %36, %37, %38, %39, %40, %41, %42, %43, %44, %45, %46, %47, %48, %49, %50, %51, %52, %53, %54, %55, %56, %57, %58, %59, %60, %61, %62, %63}, %64, %65, p, 1, 1, 0, 0;\n}\n"
    : "+f"(d[128]), "+f"(d[129]), "+f"(d[130]), "+f"(d[131]), "+f"(d[132]), "+f"(d[133]), "+f"(d[134]), "+f"(d[135]), "+f"(d[136]), "+f"(d[137]), "+f"(d[138]), "+f"(d[139]), "+f"(d[140]), "+f"(d[141]), "+f"(d[142]), "+f"(d[143]), "+f"(d[144]), "+f"(d[145]), "+f"(d[146]), "+f"(d[147]), "+f"(d[148]), "+f"(d[149]), "+f"(d[150]), "+f"(d[151]), "+f"(d[152]), "+f"(d[153]), "+f"(d[154]), "+f"(d[155]), "+f"(d[156]), "+f"(d[157]), "+f"(d[158]), "+f"(d[159]), "+f"(d[160]), "+f"(d[161]), "+f"(d[162]), "+f"(d[163]), "+f"(d[164]), "+f"(d[165]), "+f"(d[166]), "+f"(d[167]), "+f"(d[168]), "+f"(d[169]), "+f"(d[170]), "+f"(d[171]), "+f"(d[172]), "+f"(d[173]), "+f"(d[174]), "+f"(d[175]), "+f"(d[176]), "+f"(d[177]), "+f"(d[178]), "+f"(d[179]), "+f"(d[180]), "+f"(d[181]), "+f"(d[182]), "+f"(d[183]), "+f"(d[184]), "+f"(d[185]), "+f"(d[186]), "+f"(d[187]), "+f"(d[188]), "+f"(d[189]), "+f"(d[190]), "+f"(d[191])
    : "l"(da), "l"(db), "r"(scale_d));
}
__device__ __forceinline__ void wgmma_n40_tt(float (&d)[20], uint64_t da, uint64_t db, int scale_d) {
  asm volatile("{\n.reg .pred p;\nsetp.ne.b32 p, %22, 0;\n"
    "wgmma.mma_async.sync.aligned.m64n40k16.f32.bf16.bf16 {%0, %1, %2, %3, %4, %5, %6, %7, %8, %9, %10, %11, %12, %13, %14, %15, %16, %17, %18, %19}, %20, %21, p, 1, 1, 1, 1;\n}\n"
    : "+f"(d[0]), "+f"(d[1]), "+f"(d[2]), "+f"(d[3]), "+f"(d[4]), "+f"(d[5]), "+f"(d[6]), "+f"(d[7]), "+f"(d[8]), "+f"(d[9]), "+f"(d[10]), "+f"(d[11]), "+f"(d[12]), "+f"(d[13]), "+f"(d[14]), "+f"(d[15]), "+f"(d[16]), "+f"(d[17]), "+f"(d[18]), "+f"(d[19])
    : "l"(da), "l"(db), "r"(scale_d));
}
__device__ __forceinline__ void wgmma_n40_rs(float (&d)[20], const uint32_t (&a)[4], uint64_t db, int scale_d) {
  asm volatile("{\n.reg .pred p;\nsetp.ne.b32 p, %25, 0;\n"
    "wgmma.mma_async.sync.aligned.m64n40k16.f32.bf16.bf16 {%0, %1, %2, %3, %4, %5, %6, %7, %8, %9, %10, %11, %12, %13, %14, %15, %16, %17, %18, %19}, {%20, %21, %22, %23}, %24, p, 1, 1, 1;\n}\n"
    : "+f"(d[0]), "+f"(d[1]), "+f"(d[2]), "+f"(d[3]), "+f"(d[4]), "+f"(d[5]), "+f"(d[6]), "+f"(d[7]), "+f"(d[8]), "+f"(d[9]), "+f"(d[10]), "+f"(d[11]), "+f"(d[12]), "+f"(d[13]), "+f"(d[14]), "+f"(d[15]), "+f"(d[16]), "+f"(d[17]), "+f"(d[18]), "+f"(d[19])
    : "r"(a[0]), "r"(a[1]), "r"(a[2]), "r"(a[3]), "l"(db), "r"(scale_d));
}
__device__ __forceinline__ void wgmma_n256_0(float (&d)[192], uint64_t da, uint64_t db) {
  asm volatile("{\n.reg .pred p;\nsetp.ne.b32 p, 0, 0;\n"
    "wgmma.mma_async.sync.aligned.m64n256k16.f32.bf16.bf16 {%0, %1, %2, %3, %4, %5, %6, %7, %8, %9, %10, %11, %12, %13, %14, %15, %16, %17, %18, %19, %20, %21, %22, %23, %24, %25, %26, %27, %28, %29, %30, %31, %32, %33, %34, %35, %36, %37, %38, %39, %40, %41, %42, %43, %44, %45, %46, %47, %48, %49, %50, %51, %52, %53, %54, %55, %56, %57, %58, %59, %60, %61, %62, %63, %64, %65, %66, %67, %68, %69, %70, %71, %72, %73, %74, %75, %76, %77, %78, %79, %80, %81, %82, %83, %84, %85, %86, %87, %88, %89, %90, %91, %92, %93, %94, %95, %96, %97, %98, %99, %100, %101, %102, %103, %104, %105, %106, %107, %108, %109, %110, %111, %112, %113, %114, %115, %116, %117, %118, %119, %120, %121, %122, %123, %124, %125, %126, %127}, %128, %129, p, 1, 1, 0, 1;\n}\n"
    : "=f"(d[0]), "=f"(d[1]), "=f"(d[2]), "=f"(d[3]), "=f"(d[4]), "=f"(d[5]), "=f"(d[6]), "=f"(d[7]), "=f"(d[8]), "=f"(d[9]), "=f"(d[10]), "=f"(d[11]), "=f"(d[12]), "=f"(d[13]), "=f"(d[14]), "=f"(d[15]), "=f"(d[16]), "=f"(d[17]), "=f"(d[18]), "=f"(d[19]), "=f"(d[20]), "=f"(d[21]), "=f"(d[22]), "=f"(d[23]), "=f"(d[24]), "=f"(d[25]), "=f"(d[26]), "=f"(d[27]), "=f"(d[28]), "=f"(d[29]), "=f"(d[30]), "=f"(d[31]), "=f"(d[32]), "=f"(d[33]), "=f"(d[34]), "=f"(d[35]), "=f"(d[36]), "=f"(d[37]), "=f"(d[38]), "=f"(d[39]), "=f"(d[40]), "=f"(d[41]), "=f"(d[42]), "=f"(d[43]), "=f"(d[44]), "=f"(d[45]), "=f"(d[46]), "=f"(d[47]), "=f"(d[48]), "=f"(d[49]), "=f"(d[50]), "=f"(d[51]), "=f"(d[52]), "=f"(d[53]), "=f"(d[54]), "=f"(d[55]), "=f"(d[56]), "=f"(d[57]), "=f"(d[58]), "=f"(d[59]), "=f"(d[60]), "=f"(d[61]), "=f"(d[62]), "=f"(d[63]), "=f"(d[64]), "=f"(d[65]), "=f"(d[66]), "=f"(d[67]), "=f"(d[68]), "=f"(d[69]), "=f"(d[70]), "=f"(d[71]), "=f"(d[72]), "=f"(d[73]), "=f"(d[74]), "=f"(d[75]), "=f"(d[76]), "=f"(d[77]), "=f"(d[78]), "=f"(d[79]), "=f"(d[80]), "=f"(d[81]), "=f"(d[82]), "=f"(d[83]), "=f"(d[84]), "=f"(d[85]), "=f"(d[86]), "=f"(d[87]), "=f"(d[88]), "=f"(d[89]), "=f"(d[90]), "=f"(d[91]), "=f"(d[92]), "=f"(d[93]), "=f"(d[94]), "=f"(d[95]), "=f"(d[96]), "=f"(d[97]), "=f"(d[98]), "=f"(d[99]), "=f"(d[100]), "=f"(d[101]), "=f"(d[102]), "=f"(d[103]), "=f"(d[104]), "=f"(d[105]), "=f"(d[106]), "=f"(d[107]), "=f"(d[108]), "=f"(d[109]), "=f"(d[110]), "=f"(d[111]), "=f"(d[112]), "=f"(d[113]), "=f"(d[114]), "=f"(d[115]), "=f"(d[116]), "=f"(d[117]), "=f"(d[118]), "=f"(d[119]), "=f"(d[120]), "=f"(d[121]), "=f"(d[122]), "=f"(d[123]), "=f"(d[124]), "=f"(d[125]), "=f"(d[126]), "=f"(d[127])
    : "l"(da), "l"(db));
}
__device__ __forceinline__ void wgmma_n128_0(float (&d)[192], uint64_t da, uint64_t db) {
  asm volatile("{\n.reg .pred p;\nsetp.ne.b32 p, 0, 0;\n"
    "wgmma.mma_async.sync.aligned.m64n128k16.f32.bf16.bf16 {%0, %1, %2, %3, %4, %5, %6, %7, %8, %9, %10, %11, %12, %13, %14, %15, %16, %17, %18, %19, %20, %21, %22, %23, %24, %25, %26, %27, %28, %29, %30, %31, %32, %33, %34, %35, %36, %37, %38, %39, %40, %41, %42, %43, %44, %45, %46, %47, %48, %49, %50, %51, %52, %53, %54, %55, %56, %57, %58, %59, %60, %61, %62, %63}, %64, %65, p, 1, 1, 0, 1;\n}\n"
    : "=f"(d[128]), "=f"(d[129]), "=f"(d[130]), "=f"(d[131]), "=f"(d[132]), "=f"(d[133]), "=f"(d[134]), "=f"(d[135]), "=f"(d[136]), "=f"(d[137]), "=f"(d[138]), "=f"(d[139]), "=f"(d[140]), "=f"(d[141]), "=f"(d[142]), "=f"(d[143]), "=f"(d[144]), "=f"(d[145]), "=f"(d[146]), "=f"(d[147]), "=f"(d[148]), "=f"(d[149]), "=f"(d[150]), "=f"(d[151]), "=f"(d[152]), "=f"(d[153]), "=f"(d[154]), "=f"(d[155]), "=f"(d[156]), "=f"(d[157]), "=f"(d[158]), "=f"(d[159]), "=f"(d[160]), "=f"(d[161]), "=f"(d[162]), "=f"(d[163]), "=f"(d[164]), "=f"(d[165]), "=f"(d[166]), "=f"(d[167]), "=f"(d[168]), "=f"(d[169]), "=f"(d[170]), "=f"(d[171]), "=f"(d[172]), "=f"(d[173]), "=f"(d[174]), "=f"(d[175]), "=f"(d[176]), "=f"(d[177]), "=f"(d[178]), "=f"(d[179]), "=f"(d[180]), "=f"(d[181]), "=f"(d[182]), "=f"(d[183]), "=f"(d[184]), "=f"(d[185]), "=f"(d[186]), "=f"(d[187]), "=f"(d[188]), "=f"(d[189]), "=f"(d[190]), "=f"(d[191])
    : "l"(da), "l"(db));
}
__device__ __forceinline__ void wgmma_n64a(float (&d)[192], uint64_t da, uint64_t db, int scale_d) {
  asm volatile("{\n.reg .pred p;\nsetp.ne.b32 p, %34, 0;\n"
    "wgmma.mma_async.sync.aligned.m64n64k16.f32.bf16.bf16 {%0, %1, %2, %3, %4, %5, %6, %7, %8, %9, %10, %11, %12, %13, %14, %15, %16, %17, %18, %19, %20, %21, %22, %23, %24, %25, %26, %27, %28, %29, %30, %31}, %32, %33, p, 1, 1, 0, 1;\n}\n"
    : "+f"(d[128]), "+f"(d[129]), "+f"(d[130]), "+f"(d[131]), "+f"(d[132]), "+f"(d[133]), "+f"(d[134]), "+f"(d[135]), "+f"(d[136]), "+f"(d[137]), "+f"(d[138]), "+f"(d[139]), "+f"(d[140]), "+f"(d[141]), "+f"(d[142]), "+f"(d[143]), "+f"(d[144]), "+f"(d[145]), "+f"(d[146]), "+f"(d[147]), "+f"(d[148]), "+f"(d[149]), "+f"(d[150]), "+f"(d[151]), "+f"(d[152]), "+f"(d[153]), "+f"(d[154]), "+f"(d[155]), "+f"(d[156]), "+f"(d[157]), "+f"(d[158]), "+f"(d[159])
    : "l"(da), "l"(db), "r"(scale_d));
}
__device__ __forceinline__ void wgmma_n64b(float (&d)[192], uint64_t da, uint64_t db, int scale_d) {
  asm volatile("{\n.reg .pred p;\nsetp.ne.b32 p, %34, 0;\n"
    "wgmma.mma_async.sync.aligned.m64n64k16.f32.bf16.bf16 {%0, %1, %2, %3, %4, %5, %6, %7, %8, %9, %10, %11, %12, %13, %14, %15, %16, %17, %18, %19, %20, %21, %22, %23, %24, %25, %26, %27, %28, %29, %30, %31}, %32, %33, p, 1, 1, 0, 1;\n}\n"
    : "+f"(d[160]), "+f"(d[161]), "+f"(d[162]), "+f"(d[163]), "+f"(d[164]), "+f"(d[165]), "+f"(d[166]), "+f"(d[167]), "+f"(d[168]), "+f"(d[169]), "+f"(d[170]), "+f"(d[171]), "+f"(d[172]), "+f"(d[173]), "+f"(d[174]), "+f"(d[175]), "+f"(d[176]), "+f"(d[177]), "+f"(d[178]), "+f"(d[179]), "+f"(d[180]), "+f"(d[181]), "+f"(d[182]), "+f"(d[183]), "+f"(d[184]), "+f"(d[185]), "+f"(d[186]), "+f"(d[187]), "+f"(d[188]), "+f"(d[189]), "+f"(d[190]), "+f"(d[191])
    : "l"(da), "l"(db), "r"(scale_d));
}

constexpr int SLOT = 16384;
constexpr int KVT = 10240;
constexpr uint32_t QA = 0x0BAu, QK = 0x462u, QQ = 0x981u;
constexpr int SM_SD = 12 * SLOT;
constexpr int SM_BAR = SM_SD + 8192;
constexpr int SM_RS = SM_BAR + 512;
constexpr int SM_AP = SM_RS + 768;
constexpr int SM_BP = SM_AP + 2048;
constexpr int SM_WPHI = SM_BP + 12288;
constexpr int SM_EPOCH = SM_WPHI + 10240;
constexpr int SM_TOTAL = SM_EPOCH + 16 + 1024;
constexpr int B_FULLS = 0, B_XOLD = 24, B_STAT = 32, B_EMPTYS = 40, B_FULLT = 256  , B_CONS = 384  , B_E3 = 472, B_E0 = 480, B_E1 = 488, B_E2 = 496, B_EPI = 504, B_CS = 160,
              B_KVDONE = 168  , B_ODONE = 176, B_XDONE = 184, B_OH1 = 192, B_CS2 = 208, B_XH0 = 232, B_R0 = 240, B_XOLD2 = 216, B_FLG = 64  ;
constexpr uint64_t BAR_CNT = 0x1c07fc0eac00a800ull;
constexpr uint64_t WO_A0 = 0xba76218762187643ull, WO_B0 = 0x9540395403ba9021ull, WO_A1 = 0xba732157321576abull, WO_B1 = 0x9506489064890321ull;
constexpr uint64_t WO_DA0 = 0xa9876543210edd00ull, WO_DB0 = 0xa987654321bbccccull, WO_DA1 = 0xa9876543210fff00ull, WO_DB1 = 0xa98765432bbcccccull;
constexpr int XS = 10;

#define PL 2
#define PROFX(i) PROFT(tid_ == 128 && layer == PL, 200 + (i))
#define PSL 20
#define EP 5
#define DRY 0
#define NCOM 3
#define CG0 0
#define CG1 99
#define CPF 0
#define CSLP 128
#define PFS 8
#define KVTH 0x41700000u
#define CSW 1
#define RL 3
#define ORD 1
#define NLAYERS 4
constexpr float L2E = 1.4426950408889634f;
#define PHI_MAX 2147483648.f

#define D128(lo) desc64(lo, 0x40000040u)
struct Ctx { uint32_t sb; int g, rb, cu; bf16* out; };

__device__ __forceinline__ void colsum_load(const bf16* __restrict__ w, int rb, int g, int wi, int lane, uint32_t stg, float (&s)[8]) {
  const int ch = wi * 8 + (lane & 7), sec = ch >> 4;
  const bf16* src = w + (size_t)(rb * 64 + (lane >> 3) * 16) * 3072 + (sec == 2 ? 0 : 1024 + sec * 1024) + g * 128 + (ch & 15) * 8;
  stg += lane * 16;
#pragma unroll
  for (int i = 0; i < 8; ++i) s[i] = 0.f;
#pragma unroll
  for (int r = 0; r < 12; ++r)
    asm volatile("cp.async.cg.shared.global [%0], [%1], 16;" ::"r"(stg + r * 512), "l"(src + (size_t)(4 + r) * 3072) : "memory");
  uint4 v[4];
#pragma unroll
  for (int r = 0; r < 4; ++r) v[r] = __ldg(reinterpret_cast<const uint4*>(src + (size_t)r * 3072));
#pragma unroll 1
  for (int r0 = 0;; ++r0) {
#pragma unroll
    for (int r = 0; r < 4; ++r) {
      s[0] += bf_lo(v[r].x); s[1] += bf_hi(v[r].x); s[2] += bf_lo(v[r].y); s[3] += bf_hi(v[r].y);
      s[4] += bf_lo(v[r].z); s[5] += bf_hi(v[r].z); s[6] += bf_lo(v[r].w); s[7] += bf_hi(v[r].w);
    }
    if (r0 == 3) break;
    asm volatile("cp.async.wait_all;" ::: "memory");
#pragma unroll
    for (int r = 0; r < 4; ++r) v[r] = lds128(stg + (r0 * 4 + r) * 512);
  }
#pragma unroll
  for (int i = 0; i < 8; ++i) { s[i] += __shfl_xor_sync(0xffffffffu, s[i], 8); s[i] += __shfl_xor_sync(0xffffffffu, s[i], 16); }
}
__device__ __forceinline__ void colsum_red(float* cs, int g, int wi, int lane, const float (&s)[8]) {
  if (lane < 8) {
    red_add4(cs + g * 384 + (wi * 8 + lane) * 8, s[0], s[1], s[2], s[3]);
    red_add4(cs + g * 384 + (wi * 8 + lane) * 8 + 4, s[4], s[5], s[6], s[7]);
  }
}
#define PHASE_CTX() \
  uint32_t sb = c.sb; asm volatile("" : "+r"(sb)); \
  int tid_ = threadIdx.x; asm volatile("" : "+r"(tid_)); \
  const uint32_t bar = sb + SM_BAR; \
  const int lane = tid_ & 31, cw = (tid_ >> 5) - 4, wg = cw >> 2, wq = cw & 3, gq = lane >> 2, t = lane & 3, wrow0 = cw * 16; \
  const int lrow = (lane & 7) + ((lane >> 3) & 1) * 8, lchk = lane >> 4; \
  const bool elected = (tid_ & 127) == 0; \
  const uint32_t rowo = (wrow0 + lrow) * 128, X = (lchk ^ (lane & 7)) << 4; \
  (void)bar; (void)wq; (void)gq; (void)lrow; (void)lchk; (void)elected; (void)wrow0; (void)wg; (void)rowo; (void)X; (void)t;

template <bool FENCE = false>
__device__ __forceinline__ void slab_out_half(uint32_t slot, bf16* dst, int wrow0, int lane) {
  const int r0 = lane >> 3, ch = lane & 7;
  const uint32_t src = slot + (wrow0 + r0) * 128;
  uint4 v[4];
#pragma unroll
  for (int i = 0; i < 4; ++i) v[i] = lds128(src + i * 512 + (((ch ^ (4 * i + r0)) & 7) << 4));
  if (FENCE) fence_async_smem();
  dst += (size_t)(wrow0 + r0) * D_ + ch * 8;
#pragma unroll
  for (int i = 0; i < 4; ++i) *reinterpret_cast<uint4*>(dst + (size_t)i * 4 * D_) = v[i];
}

template <int O>
__device__ __forceinline__ void phi_proj(float (&p)[2][4][4], const uint32_t (&kq)[64], uint32_t wa) {
#pragma unroll
  for (int h = 0; h < 2; ++h)
#pragma unroll
    for (int i = 0; i < 4; ++i) { p[h][i][0] = p[h][i][1] = p[h][i][2] = p[h][i][3] = 0.f; }
#pragma unroll
  for (int ks = 0; ks < 2; ++ks)
#pragma unroll
    for (int np = 0; np < 2; ++np)
#pragma unroll
      for (int h = 0; h < 2; ++h) {
        uint32_t b0, b1, b2, b3;
        ldsm_x4_t(b0, b1, b2, b3, wa + h * 2560 + ks * 1280 + np * 32);
        mma_bf16(p[h][2 * np], kq[O + 8 * h + 4 * ks], kq[O + 8 * h + 4 * ks + 1], kq[O + 8 * h + 4 * ks + 2], kq[O + 8 * h + 4 * ks + 3], b0, b1);
        mma_bf16(p[h][2 * np + 1], kq[O + 8 * h + 4 * ks], kq[O + 8 * h + 4 * ks + 1], kq[O + 8 * h + 4 * ks + 2], kq[O + 8 * h + 4 * ks + 3], b2, b3);
      }
}
__device__ __forceinline__ void phi_exp(uint32_t (&raw)[4][4], const float (&p)[4][4], float sc0, float sc1) {
#pragma unroll
  for (int i = 0; i < 4; ++i) {
    const float e0 = ex2(p[i][0] * sc0), e1 = ex2(p[i][1] * sc0), e2 = ex2(p[i][2] * sc1), e3 = ex2(p[i][3] * sc1);
    const float m0 = e0 * e1, m1 = e2 * e3, rr = rcp(m0 * m1), r0 = rr * m1, r1 = rr * m0;
    raw[i >> 1][(i & 1) * 2] = pack_bf16(e0, e1);
    raw[i >> 1][(i & 1) * 2 + 1] = pack_bf16(e2, e3);
    raw[2 + (i >> 1)][(i & 1) * 2] = pack_bf16(e1 * r0, e0 * r0);
    raw[2 + (i >> 1)][(i & 1) * 2 + 1] = pack_bf16(e3 * r1, e2 * r1);
  }
}
#define FENCE_P(h) _Pragma("unroll") for (int i_ = 0; i_ < 16; ++i_) asm volatile("" : "+f"(p[h][i_ >> 2][i_ & 3]) :: "memory")
#define FENCE_RAW(h) _Pragma("unroll") for (int i_ = 0; i_ < 16; ++i_) asm volatile("" : "+r"(raw[h][i_ >> 2][i_ & 3]) :: "memory")
template <int O>
__device__ __forceinline__ void phi_norm(uint32_t (&ph)[2][4][4], const uint32_t (&raw)[2][4][4], const uint32_t (&kq)[64], uint32_t wa,
                                         float sc0, float sc1, float mul0, float mul1) {
  bool bad = false;
#pragma unroll
  for (int h = 0; h < 2; ++h)
#pragma unroll
    for (int sg = 0; sg < 2; ++sg) {
      float ss[4] = {0.f, 0.f, 0.f, 0.f};
#pragma unroll
      for (int ks = 0; ks < 2; ++ks)
        mma_bf16(ss, raw[h][2 * sg + ks][0], raw[h][2 * sg + ks][1], raw[h][2 * sg + ks][2], raw[h][2 * sg + ks][3], 0x3F803F80u, 0x3F803F80u);
      bad = bad || !(ss[0] < PHI_MAX) || !(ss[2] < PHI_MAX);
      const uint32_t iv = pack_bf16(rcp(ss[0]) * mul0, rcp(ss[2]) * mul1);
#pragma unroll
      for (int ks = 0; ks < 2; ++ks)
#pragma unroll
        for (int j = 0; j < 4; ++j) ph[h][2 * sg + ks][j] = mul_bf16x2(raw[h][2 * sg + ks][j], iv, j & 1);
    }
  if (__builtin_expect(__any_sync(0xffffffffu, bad), 0)) {
#pragma unroll 1
    for (int it = 0; it < 4; ++it) {
      float q[4][4];
#pragma unroll
      for (int i = 0; i < 4; ++i) { q[i][0] = q[i][1] = q[i][2] = q[i][3] = 0.f; }
#pragma unroll
      for (int ks = 0; ks < 2; ++ks) {
        uint32_t a[4];
#pragma unroll
        for (int j = 0; j < 4; ++j) a[j] = (it & 2) ? kq[O + 8 + 4 * ks + j] : kq[O + 4 * ks + j];
#pragma unroll
        for (int np = 0; np < 2; ++np) {
          uint32_t b0, b1, b2, b3;
          ldsm_x4_t(b0, b1, b2, b3, wa + (it >> 1) * 2560 + ks * 1280 + np * 32);
          mma_bf16(q[2 * np], a[0], a[1], a[2], a[3], b0, b1);
          mma_bf16(q[2 * np + 1], a[0], a[1], a[2], a[3], b2, b3);
        }
      }
      float iv[2];
#pragma unroll
      for (int r = 0; r < 2; ++r) {
        const float sc = (it & 1) ? -(r ? sc1 : sc0) : (r ? sc1 : sc0);
        float mx = -INFINITY, sm = 0.f;
#pragma unroll
        for (int i = 0; i < 8; ++i) { float& v = q[i >> 1][2 * r + (i & 1)]; v *= sc; mx = fmaxf(mx, v); }
        mx = fmaxf(mx, __shfl_xor_sync(0xffffffffu, mx, 1));
        mx = fmaxf(mx, __shfl_xor_sync(0xffffffffu, mx, 2));
#pragma unroll
        for (int i = 0; i < 8; ++i) { float& v = q[i >> 1][2 * r + (i & 1)]; v = ex2(v - mx); sm += v; }
        sm += __shfl_xor_sync(0xffffffffu, sm, 1);
        sm += __shfl_xor_sync(0xffffffffu, sm, 2);
        iv[r] = rcp(sm) * (r ? mul1 : mul0);
      }
#pragma unroll
      for (int i = 0; i < 24; ++i) ph[i >> 4][(i >> 2) & 3][i & 3] = ph[(i + 8) >> 4][((i + 8) >> 2) & 3][i & 3];
#pragma unroll
      for (int i = 0; i < 4; ++i) {
        ph[1][2 + (i >> 1)][(i & 1) * 2] = pack_bf16(q[i][0] * iv[0], q[i][1] * iv[0]);
        ph[1][2 + (i >> 1)][(i & 1) * 2 + 1] = pack_bf16(q[i][2] * iv[1], q[i][3] * iv[1]);
      }
    }
  }
}

__device__ __forceinline__ void stats_out(float s0, float s1, float q0, float q1, float2* dst, int t) {
  const bool od = t & 1;
  float sa = od ? s1 : s0, qa = od ? q1 : q0;
  sa += __shfl_xor_sync(0xffffffffu, od ? s0 : s1, 1);
  qa += __shfl_xor_sync(0xffffffffu, od ? q0 : q1, 1);
  sa += __shfl_xor_sync(0xffffffffu, sa, 2);
  qa += __shfl_xor_sync(0xffffffffu, qa, 2);
  if (t < 2) red_add2(&dst[t * 8].x, sa, qa);
}

__device__ __forceinline__ void consumer(const Ctx& c) {
  const int g = c.g, m0 = c.rb * 128;
  float acc[192];
#define X_H1() \
      _Pragma("unroll") for (int jp = 4; jp < 8; ++jp) \
        stsm_x4(sb + (XS + 1) * SLOT + rowo + (X ^ ((jp & 3) << 5)), \
                pack_bf16(acc[128 + 8 * jp], acc[129 + 8 * jp]), pack_bf16(acc[130 + 8 * jp], acc[131 + 8 * jp]), \
                pack_bf16(acc[132 + 8 * jp], acc[133 + 8 * jp]), pack_bf16(acc[134 + 8 * jp], acc[135 + 8 * jp]));
#pragma unroll
  for (int i = 128; i < 192; ++i) acc[i] = 0.f;
#pragma unroll 1
  for (int layer = 0;; ++layer) {
    {
      PHASE_CTX();
      const uint32_t wu = c.cu >> 2;
      const uint32_t dA0 = (((sb + wu * 8192) & 0x3FFFF) >> 4) | (1u << 16), dB0 = ((sb & 0x3FFFF) >> 4) | (512u << 16);
      {
        PROFX(0);
        mbar_wait(bar + B_FULLS, 0);
        PROFX(1);
        wgmma_fence();
        wgmma_n256_0(acc, D128(dA0 + XS * 1024), D128(dB0 + 2048));
#pragma unroll
        for (int k = 1; k < 4; ++k) wgmma_n256(acc, D128(dA0 + XS * 1024 + k * 2), D128(dB0 + 2048 + k * 128), 1);
        wgmma_commit();
        wgmma_wait<1>();
        float s0 = 0.f, s1 = 0.f, q0 = 0.f, q1 = 0.f;
        if (layer) {
          X_H1();
#pragma unroll
          for (int i = 128; i < 192; i += 4) {
            s0 += acc[i] + acc[i + 1]; s1 += acc[i + 2] + acc[i + 3];
            q0 = fmaf(acc[i], acc[i], fmaf(acc[i + 1], acc[i + 1], q0)); q1 = fmaf(acc[i + 2], acc[i + 2], fmaf(acc[i + 3], acc[i + 3], q1));
          }
        }
        asm volatile("" : "+f"(s0), "+f"(s1), "+f"(q0), "+f"(q1) :: "memory");
        wgmma_fence();
        wgmma_n128_0(acc, D128(dA0 + XS * 1024), D128(dB0 + 1024));
#pragma unroll
        for (int k = 1; k < 4; ++k) wgmma_n128(acc, D128(dA0 + XS * 1024 + k * 2), D128(dB0 + 1024 + k * 128), 1);
        wgmma_commit();
        if (layer) {
          PHASE_CTX();
          fence_async_smem();
          nbar_dyn(3 + wu, 128);
          stats_out(s0, s1, q0, q1, g_stats + layer * S_ + m0 + wrow0 + gq, t);
          PROFT(tid_ == 128, layer * 16 + 8);
        }
      }
      uint32_t s = 1, u = 0, sp = 0;
      const int ix = layer ? 1 : 2 * min(g, NCOM) + 1;
#pragma unroll 1
      for (int i = 1; i < 14; ++i) {
        mbar_wait(bar + B_FULLS + s * 8, (u + (s ? layer : 0)) & 1);
        const uint32_t da = dA0 + ((QA >> (4 * s)) & 15) * 1024, dk = dB0 + ((QK >> (4 * s)) & 15) * 1024,
                       dq = dB0 + ((QQ >> (4 * s)) & 15) * 1024;
        wgmma_fence();
#pragma unroll
        for (int k = 0; k < 4; ++k) {
          wgmma_n256(acc, D128(da + k * 2), D128(dk + k * 128), 1);
          wgmma_n128(acc, D128(da + k * 2), D128(dq + k * 128), 1);
        }
        wgmma_commit();
        if (i == ix || (i == ix + 1 && !layer)) {
          PHASE_CTX();
          if (layer) {
            slab_out_half(sb + (XS + 1) * SLOT, g_x + (size_t)m0 * D_ + g * 128 + 64, wrow0, lane);
          } else {
            float s0 = 0.f, s1 = 0.f, q0 = 0.f, q1 = 0.f;
            const uint32_t xa = sb + ((QA >> (4 * sp)) & 15) * SLOT + rowo;
#pragma unroll
            for (int jp = 0; jp < 4; ++jp) {
              uint32_t x0, x1, x2, x3;
              ldsm_x4(x0, x1, x2, x3, xa + (X ^ (jp << 5)));
              s0 += (bf_lo(x0) + bf_hi(x0)) + (bf_lo(x2) + bf_hi(x2));
              s1 += (bf_lo(x1) + bf_hi(x1)) + (bf_lo(x3) + bf_hi(x3));
              q0 = fmaf(bf_lo(x0), bf_lo(x0), fmaf(bf_hi(x0), bf_hi(x0), fmaf(bf_lo(x2), bf_lo(x2), fmaf(bf_hi(x2), bf_hi(x2), q0))));
              q1 = fmaf(bf_lo(x1), bf_lo(x1), fmaf(bf_hi(x1), bf_hi(x1), fmaf(bf_lo(x3), bf_lo(x3), fmaf(bf_hi(x3), bf_hi(x3), q1))));
            }
            stats_out(s0, s1, q0, q1, g_stats + m0 + wrow0 + gq, t);
          }
          __syncwarp();
          if (lane == 0 && (layer || i != ix)) mbar_arrive(bar + B_XDONE);
          nbar_dyn(3 + wu, 128);
        }
        wgmma_wait<1>();
        if (elected) release2(bar + B_EMPTYS + sp * 8);
        sp = s;
        if (++s == 3) { s = 0; ++u; }
      }
      {
        const uint64_t dap = make_desc_ns(sb + SM_AP + wu * 1024, 0, 128), dbp = make_desc_ns(sb + SM_BP + (layer & 1) * 6144, 0, 128);
        if (wu == 0) {
          wgmma_wait<0>();
          if (elected) mbar_arrive(bar + B_R0);
          nbar<6, 256>();
        }
        if (layer < 2) mbar_wait(bar + (layer ? B_CS2 : B_CS), 0);
        mbar_wait(bar + B_STAT, layer & 1);
        mbar_wait(bar + B_FULLS + 16, layer & 1);
        wgmma_fence();
        wgmma_n256_k(acc, dap, dbp, 1);
#pragma unroll
        for (int k = 0; k < 4; ++k) wgmma_n256(acc, D128(dA0 + (QA >> 8) * 1024 + k * 2), D128(dB0 + (QK >> 8) * 1024 + k * 128), 1);
        mbar_wait(bar + B_FULLS, 1);
        PROFT(tid_ == 128, layer * 16 + 9);
        wgmma_fence();
#pragma unroll
        for (int k = 0; k < 4; ++k) wgmma_n256(acc, D128(dA0 + (QA & 15) * 1024 + k * 2), D128(dB0 + (QK & 15) * 1024 + k * 128), 1);
        wgmma_commit();
        if (wu) nbar<6, 256>();
#define Q_TAIL() \
        wgmma_n128_k(acc, dap, dbp + 256, 1); \
        _Pragma("unroll") for (int k = 0; k < 4; ++k) wgmma_n128(acc, D128(dA0 + (QA >> 8) * 1024 + k * 2), D128(dB0 + (QQ >> 8) * 1024 + k * 128), 1); \
        _Pragma("unroll") for (int k = 0; k < 4; ++k) wgmma_n128(acc, D128(dA0 + (QA & 15) * 1024 + k * 2), D128(dB0 + (QQ & 15) * 1024 + k * 128), 1);
        Q_TAIL();
        wgmma_commit();
        wgmma_wait<1>();
#pragma unroll
        for (int i = 0; i < 128; ++i) asm volatile("" : "+f"(acc[i]) :: "memory");
      }
    }
    uint32_t xo[32];
    {
      PHASE_CTX();
      PROFT(tid_ == 128, layer * 16 + 1);
      const bool isB = layer & 1;
      const int cu = c.cu;
      if (cu >= 4) asm volatile("bar.arrive 7, 256;" ::: "memory");
      else if (isB && cu == 0) asm volatile("bar.arrive 10, 64;" ::: "memory");
      if (elected && isB && cu == 0) release2(bar + B_E1);
      if (elected && cu == 4) mbar_arrive(bar + B_R0);
      uint32_t kq[64];
#pragma unroll
      for (int i = 0; i < 32; ++i) kq[i] = pack_bf16(acc[2 * i], acc[2 * i + 1]);
      const unsigned int epoch = __float_as_uint(lds_f(sb + SM_EPOCH));
      uint4* const hbuf = g_halo + (size_t)((((epoch & 1) * 2 + (layer >> 1)) * 16 + c.rb) * 8 + g) * 512 + lane;
      if (isB && cu == 7) {
#pragma unroll
        for (int jp = 0; jp < 8; ++jp) st_relaxed4(hbuf + jp * 32, ~kq[4 * jp], ~kq[4 * jp + 1], ~kq[4 * jp + 2], ~kq[4 * jp + 3]);
#pragma unroll
        for (int jp = 8; jp < 16; ++jp)
          st_relaxed4(hbuf + jp * 32, ~pack_bf16(acc[8 * jp], acc[8 * jp + 1]), ~pack_bf16(acc[8 * jp + 2], acc[8 * jp + 3]),
                      ~pack_bf16(acc[8 * jp + 4], acc[8 * jp + 5]), ~pack_bf16(acc[8 * jp + 6], acc[8 * jp + 7]));
      }
      const uint32_t rowq = rowo & 8191;
      const uint32_t rB = sb + 4 * SLOT + wg * 4 * KVT + rowq, pA = sb + (3 + 3 * wg) * SLOT + rowq;
      PROFX(13);
      if (cu < 4) nbar<7, 256>();
      PROFX(14);
      {
        const uint32_t vb = isB ? rB + KVT + 2048 + wg * 2 * KVT : pA + 2 * SLOT - (rowq >> 1), vst = isB ? (1 - 2 * wg) * 2 * KVT : 8192;
        const uint32_t X0 = isB ? X : (lchk ^ ((lane & 7) >> 1)) << 4, X1 = isB ? X ^ 64 : X0 + 4096;
        const bool dup = isB && cu == 3;
        if (isB) {
#pragma unroll
          for (int jp = 0; jp < 8; ++jp) {
            stsm_x4(vb - KVT + (jp >> 2) * vst + (X ^ ((jp & 3) << 5)), kq[4 * jp], kq[4 * jp + 1], kq[4 * jp + 2], kq[4 * jp + 3]);
            stsm_x4_p(dup, rB + 2048 + 32768 + (1 - (jp >> 2)) * 2 * KVT + (X ^ ((jp & 3) << 5)), kq[4 * jp], kq[4 * jp + 1], kq[4 * jp + 2], kq[4 * jp + 3]);
          }
        }
#pragma unroll
        for (int jp = 8; jp < 16; ++jp) {
          const uint32_t v0 = pack_bf16(acc[8 * jp], acc[8 * jp + 1]), v1 = pack_bf16(acc[8 * jp + 2], acc[8 * jp + 3]),
                         v2 = pack_bf16(acc[8 * jp + 4], acc[8 * jp + 5]), v3 = pack_bf16(acc[8 * jp + 6], acc[8 * jp + 7]);
          const uint32_t ad = vb + ((jp >> 2) & 1) * vst + (((jp & 2) ? X1 : X0) ^ ((jp & 1) << 5));
          stsm_x4(ad, v0, v1, v2, v3);
          stsm_x4_p(dup, ad + 32768 + ((jp & 4) ? -2 * KVT : 2 * KVT), v0, v1, v2, v3);
        }
        if (dup) asm volatile("bar.arrive 9, 64;" ::: "memory");
      }
      const float rs0 = lds_f(sb + SM_RS + (16 + wrow0 + gq) * 4), rs1 = lds_f(sb + SM_RS + (24 + wrow0 + gq) * 4);
      PROFT(tid_ == 128, layer * 16 + 2);
#define Q_DONE() \
      wgmma_wait<0>(); \
      if (lane == 0) release2(bar + B_E0); \
      _Pragma("unroll") for (int i = 128; i < 192; ++i) asm volatile("" : "+f"(acc[i]) :: "memory"); \
      _Pragma("unroll") for (int i = 0; i < 32; ++i) kq[32 + i] = pack_bf16(acc[128 + 2 * i], acc[129 + 2 * i]);
      Q_DONE();
      if (isB) {
        const int e = gq & 1;
        const uint32_t KX = ((lane >> 3) ^ (lane & 7)) << 4;
        float f0[4], f1[4], rj[4];
        uint32_t msk = 0;
#pragma unroll
        for (int nt = 0; nt < 4; ++nt) {
          const int kk = nt * 8 + 2 * t + e;
          const bool okk = (m0 + wrow0 + kk) >= 16;
          const int d0 = kk - gq, d1 = d0 - 8;
          rj[nt] = lds_f(sb + SM_RS + (wrow0 + kk) * 4);
          f0[nt] = rj[nt] * rs0 * (0.17677669529663687f * L2E);
          f1[nt] = rj[nt] * rs1 * (0.17677669529663687f * L2E);
          msk |= (okk && d0 >= 2 && d0 <= 16) ? (1u << nt) : 0u;
          msk |= (okk && d1 >= 2 && d1 <= 16) ? (16u << nt) : 0u;
        }
        if ((cu & 3) == 0) asm volatile("bar.arrive %0, 128;" :: "r"(3 + (cu >> 2)) : "memory");
        if (cu == 0) {
          nbar<11, 64>();
        } else if (cu == 4) {
          uint4 hv[16];
          if (c.rb > 0) {
            uint32_t n = 0;
#pragma unroll 1
            while (true) {
              uint32_t mn = 0xFFFFFFFFu;
#pragma unroll
              for (int i = 0; i < 16; ++i) hv[i] = ld_relaxed4(hbuf - 8 * 512 + i * 32);
#pragma unroll
              for (int i = 0; i < 16; ++i) mn = __vimin3_u32(__vimin3_u32(mn, hv[i].x, hv[i].y), hv[i].z, hv[i].w);
              if (__all_sync(0xffffffffu, mn != 0u)) break;
              if (++n > (1u << 20)) { g_err = 4u; break; }
            }
          } else {
#pragma unroll
            for (int i = 0; i < 16; ++i) hv[i] = make_uint4(~0u, ~0u, ~0u, ~0u);
          }
          nbar<10, 64>();
#pragma unroll
          for (int i = 0; i < 16; ++i)
            stsm_x4(rB - 4 * KVT + (((i >> 2) & 1) * 2 + (i >> 3)) * KVT + (X ^ ((i & 3) << 5)), ~hv[i].x, ~hv[i].y, ~hv[i].z, ~hv[i].w);
          asm volatile("bar.arrive 11, 64;" ::: "memory");
          nbar<9, 64>();
        } else {
          nbar_dyn(3 + (cu >> 2), 128);
        }
        PROFT(tid_ == 128, layer * 16 + 5);
#pragma unroll
        for (int i = 16; i < 32; ++i) xo[i] = 0u;
#pragma unroll 1
        for (int hp = 0; hp < 2; ++hp) {
          const uint32_t qad = sb + (XS + 1 - hp) * SLOT + rowo, kt = rB + 2 * (hp ^ wg) * KVT - (lane & 8) * 128, vt = rB + (2 * (hp ^ wg) + 1) * KVT;
          uint32_t qa[2][8];
#pragma unroll
          for (int i = 0; i < 16; ++i) { qa[i >> 3][i & 7] = kq[32 + i]; kq[32 + i] = kq[48 + i]; }
          float l0[2][4], l1[2][4];
#pragma unroll
          for (int nt = 0; nt < 4; ++nt)
#pragma unroll
            for (int h = 0; h < 2; ++h) {
              float sc[4] = {0.f, 0.f, 0.f, 0.f};
              uint32_t b0, b1, b2, b3;
              ldsm_x4(b0, b1, b2, b3, kt + nt * 1024 + (KX ^ (h << 6)));
              mma_bf16(sc, qa[h][0], qa[h][1], qa[h][2], qa[h][3], b0, b1);
              mma_bf16(sc, qa[h][4], qa[h][5], qa[h][6], qa[h][7], b2, b3);
              l0[h][nt] = (msk >> nt) & 1 ? (e ? sc[1] : sc[0]) * f0[nt] : -1e30f;
              l1[h][nt] = (msk >> (4 + nt)) & 1 ? (e ? sc[3] : sc[2]) * f1[nt] : -1e30f;
            }
          float mx0[2], mx1[2], s0[2], s1[2];
#pragma unroll
          for (int h = 0; h < 2; ++h) {
            mx0[h] = fmaxf(fmaxf(l0[h][0], l0[h][1]), fmaxf(l0[h][2], l0[h][3]));
            mx1[h] = fmaxf(fmaxf(l1[h][0], l1[h][1]), fmaxf(l1[h][2], l1[h][3]));
          }
#pragma unroll
          for (int o = 1; o <= 2; o <<= 1)
#pragma unroll
            for (int h = 0; h < 2; ++h) {
              mx0[h] = fmaxf(mx0[h], __shfl_xor_sync(0xffffffffu, mx0[h], o));
              mx1[h] = fmaxf(mx1[h], __shfl_xor_sync(0xffffffffu, mx1[h], o));
            }
#pragma unroll
          for (int h = 0; h < 2; ++h) {
#pragma unroll
            for (int nt = 0; nt < 4; ++nt) { l0[h][nt] = ex2(l0[h][nt] - mx0[h]); l1[h][nt] = ex2(l1[h][nt] - mx1[h]); }
            s0[h] = (l0[h][0] + l0[h][1]) + (l0[h][2] + l0[h][3]);
            s1[h] = (l1[h][0] + l1[h][1]) + (l1[h][2] + l1[h][3]);
          }
#pragma unroll
          for (int o = 1; o <= 2; o <<= 1)
#pragma unroll
            for (int h = 0; h < 2; ++h) {
              s0[h] += __shfl_xor_sync(0xffffffffu, s0[h], o);
              s1[h] += __shfl_xor_sync(0xffffffffu, s1[h], o);
            }
          uint32_t pl[2][4], phh[2][4];
#pragma unroll
          for (int h = 0; h < 2; ++h) {
            const float i0 = rcp(s0[h]), i1 = rcp(s1[h]);
#pragma unroll
            for (int nt = 0; nt < 4; ++nt) {
              const uint32_t pk = pack_bf16(l0[h][nt] * i0 * rj[nt], l1[h][nt] * i1 * rj[nt]);
              pl[h][nt] = e ? pk << 16 : pk & 0xFFFFu;
              phh[h][nt] = e ? pk & 0xFFFF0000u : pk >> 16;
            }
          }
          float oa[2][4][4];
#pragma unroll
          for (int h = 0; h < 2; ++h)
#pragma unroll
            for (int i = 0; i < 4; ++i) { oa[h][i][0] = oa[h][i][1] = oa[h][i][2] = oa[h][i][3] = 0.f; }
#pragma unroll
          for (int ks = 0; ks < 2; ++ks)
#pragma unroll
            for (int np = 0; np < 2; ++np)
#pragma unroll
              for (int h = 0; h < 2; ++h) {
                uint32_t b0, b1, b2, b3;
                ldsm_x4_t(b0, b1, b2, b3, vt + ks * 2048 + (X ^ (h << 6) ^ (np << 5)));
                mma_bf16(oa[h][2 * np], pl[h][2 * ks], phh[h][2 * ks], pl[h][2 * ks + 1], phh[h][2 * ks + 1], b0, b1);
                mma_bf16(oa[h][2 * np + 1], pl[h][2 * ks], phh[h][2 * ks], pl[h][2 * ks + 1], phh[h][2 * ks + 1], b2, b3);
              }
          if (hp == 0 && lane == 0) release2(bar + B_E3);
          mbar_wait(bar + (hp ? B_XOLD2 : B_XOLD), 1);
#pragma unroll
          for (int i = 0; i < 16; ++i) xo[i] = xo[16 + i];
#pragma unroll
          for (int jp = 0; jp < 4; ++jp) ldsm_x4(xo[16 + 4 * jp], xo[17 + 4 * jp], xo[18 + 4 * jp], xo[19 + 4 * jp], qad + (X ^ (jp << 5)));
#pragma unroll
          for (int h = 0; h < 2; ++h)
#pragma unroll
            for (int np = 0; np < 2; ++np)
              stsm_x4(qad + (X ^ (h << 6) ^ (np << 5)),
                      pack_bf16(oa[h][2 * np][0], oa[h][2 * np][1]), pack_bf16(oa[h][2 * np][2], oa[h][2 * np][3]),
                      pack_bf16(oa[h][2 * np + 1][0], oa[h][2 * np + 1][1]), pack_bf16(oa[h][2 * np + 1][2], oa[h][2 * np + 1][3]));
          {
            __syncwarp();
            slab_out_half<true>(sb + (XS + 1 - hp) * SLOT, g_o + (size_t)m0 * D_ + g * 128 + hp * 64, wrow0, lane);
            __syncwarp();
            if (lane == 0) mbar_arrive(bar + (hp ? B_ODONE : B_OH1));
          }
        }
      } else {
        PHASE_CTX();
        const uint32_t pA = sb + (3 + 3 * wg) * SLOT + (rowo & 8191);
        float sc0 = rs0 * L2E, sc1 = rs1 * L2E;
        const uint32_t wa0 = sb + SM_WPHI + lrow * 80 + lchk * 16;
        const uint32_t wu = c.cu >> 2, par = (layer >> 1) & 1;
        float p[2][4][4];
        uint32_t raw[2][4][4], ph[2][4][4];
        float kva[20], oa[2][20];
        auto kv_start = [&](int hp) {
#pragma unroll
          for (int h = 0; h < 2; ++h)
#pragma unroll
            for (int cp = 0; cp < 4; ++cp)
              stsm_x4(pA + hp * 16384 + h * 8192 + (X ^ (cp << 5)), ph[h][cp][0], ph[h][cp][1], ph[h][cp][2], ph[h][cp][3]);
          PROFT(tid_ == 128, layer * 16 + 11);
          fence_async_smem();
          nbar<1, 256>();
          const uint32_t hu = 2 * hp + wu;
          const uint32_t dP = (((sb + 3 * SLOT + hu * 8192) & 0x3FFFF) >> 4) | (512u << 16);
          const uint32_t dV = (((sb + 5 * SLOT + hu * 4096) & 0x3FFFF) >> 4) | (((SM_SD - 5 * SLOT - hu * 4096) >> 4) << 16);
          wgmma_fence();
#pragma unroll
          for (int ks = 0; ks < 8; ++ks)
            wgmma_n40_tt(kva, desc64(dP + (ks >> 2) * 3072 + (ks & 3) * 128, 0x40000040u),
                         desc64(dV + (ks >> 2) * (3072u - (2816u << 16)) + (ks & 3) * 64, 0x80000020u), ks != 0);
          wgmma_commit();
        };
        auto kv_end = [&](int hp) {
          wgmma_wait<0>();
#pragma unroll
          for (int i = 0; i < 20; ++i) asm volatile("" : "+f"(kva[i]) :: "memory");
          nbar_dyn(3 + wu, 128);
          PROFT(tid_ == 128, layer * 16 + 12);
          const bool od = lane & 1;
#pragma unroll
          for (int i = 0; i < 4; ++i)
            sts128(sb + (3 + hp) * SLOT + (cw * 128 + i * 32 + lane) * 16,
                   make_uint4(__float_as_uint(kva[4 * i]), __float_as_uint(kva[4 * i + 1]), __float_as_uint(kva[4 * i + 2]),
                              __float_as_uint(od == (i >= 2) ? 1.f : kva[4 * i + 3])));
          sts128(sb + (6 + hp) * SLOT + wg * 8192 + (wq * 32 + lane) * 16,
                 make_uint4(__float_as_uint(od ? kva[11] : kva[3]), __float_as_uint(od ? kva[15] : kva[7]), __float_as_uint(od ? kva[18] : kva[16]), __float_as_uint(1.f)));
          fence_async_smem();
          __syncwarp();
          if (lane == 0) mbar_arrive(bar + B_KVDONE - hp * 32);
          PROFT(tid_ == 128, layer * 16 + 3);
        };
        const uint4* const kvg = g_kv + (g * 2 + (layer >> 1)) * 2560 + cw * 128 + lane;
        uint4 u[5];
        auto kv_load = [&](int hp) {
#pragma unroll
          for (int i = 0; i < 4; ++i) u[i] = ld_relaxed4(kvg + hp * 1280 + i * 32);
          u[4] = ld_relaxed4(kvg + hp * 1280 + 1024 - cw * 96);
        };
        auto o_start = [&](int hp, const uint32_t (&pq)[2][4][4]) {
          PROFT(tid_ == 128 && hp == 0, layer * 16 + 10);
          if (hp == 0) mbar_wait(bar + B_KVDONE - 32, par);
          const bool od = lane & 1;
          uint32_t n = 0;
#pragma unroll 1
          while (!__all_sync(0xffffffffu, (od ? u[2].w : u[0].w) == 0x41800000u && (od ? u[3].w : u[1].w) == 0x41800000u && u[4].w == 0x41800000u)) {
#pragma unroll 1
            while (__any_sync(0xffffffffu, u[4].w < KVTH) && ++n < (1u << 20)) u[4].w = ld_relaxed(&kvg[hp * 1280 + 1024 - cw * 96].w);
            if (++n > (1u << 20)) { g_err = 6u; break; }
            kv_load(hp);
          }
          PROFT(tid_ == 128 && hp == 0, layer * 16 + 5);
          if (!od) { u[0].w = u[4].x; u[1].w = u[4].y; } else { u[2].w = u[4].x; u[3].w = u[4].y; }
#pragma unroll
          for (int i = 0; i < 4; i += 2)
            stsm_x4(sb + (5 + 3 * hp) * SLOT + rowo + (X ^ ((i & 2) << 4)),
                    pack_bf16(__uint_as_float(u[i].x), __uint_as_float(u[i].y)), pack_bf16(__uint_as_float(u[i].z), __uint_as_float(u[i].w)),
                    pack_bf16(__uint_as_float(u[i + 1].x), __uint_as_float(u[i + 1].y)), pack_bf16(__uint_as_float(u[i + 1].z), __uint_as_float(u[i + 1].w)));
          const uint32_t z2 = pack_bf16(__uint_as_float(u[4].z), __uint_as_float(u[4].z));
          if (t < 2) sts128(sb + (5 + 3 * hp) * SLOT + (wrow0 + gq + 8 * t) * 128 + ((4 ^ gq) << 4), make_uint4(z2, z2, z2, z2));
          fence_async_smem();
          nbar<1, 256>();
          PROFT(tid_ == 128 && hp == 1, layer * 16 + 4);
          const uint32_t dK = (((sb + (5 + 3 * hp) * SLOT) & 0x3FFFF) >> 4) | (512u << 16);
          wgmma_fence();
#pragma unroll
          for (int ks = 0; ks < 4; ++ks) {
#pragma unroll
            for (int hh = 0; hh < 2; ++hh) wgmma_n40_rs(oa[hh], pq[hh][ks], D128(dK + hh * 512 + ks * 128), ks != 0);
          }
          wgmma_commit();
        };
        auto o_end = [&](int hp) {
          wgmma_wait<0>();
#pragma unroll
          for (int i = 0; i < 20; ++i) asm volatile("" : "+f"(oa[0][i]), "+f"(oa[1][i]) :: "memory");
#pragma unroll
          for (int hh = 0; hh < 2; ++hh) {
            const float i0 = rcp(oa[hh][16] + 1e-6f), i1 = rcp(oa[hh][18] + 1e-6f);
            const uint32_t qad = sb + (3 + hp) * SLOT + rowo, hx = hh << 6;
#pragma unroll
            for (int np = 0; np < 2; ++np)
              stsm_x4(qad + (X ^ hx ^ (np << 5)),
                      pack_bf16(oa[hh][8 * np] * i0, oa[hh][8 * np + 1] * i0), pack_bf16(oa[hh][8 * np + 2] * i1, oa[hh][8 * np + 3] * i1),
                      pack_bf16(oa[hh][8 * np + 4] * i0, oa[hh][8 * np + 5] * i0), pack_bf16(oa[hh][8 * np + 6] * i1, oa[hh][8 * np + 7] * i1));
          }
          __syncwarp();
          slab_out_half<true>(sb + (3 + hp) * SLOT, g_o + (size_t)m0 * D_ + g * 128 + hp * 64, wrow0, lane);
          __syncwarp();
          if (lane == 0) mbar_arrive(bar + (hp ? B_ODONE : B_OH1));
        };
#define XO_LOAD() \
        mbar_wait(bar + B_XOLD, 0); \
        mbar_wait(bar + B_XOLD2, 0); \
        _Pragma("unroll") for (int jp = 0; jp < 8; ++jp) \
          ldsm_x4(xo[4 * jp], xo[4 * jp + 1], xo[4 * jp + 2], xo[4 * jp + 3], sb + (XS + 1 - (jp >> 2)) * SLOT + rowo + (X ^ ((jp & 3) << 5)));
#define SC_RELOAD() \
        sc0 = __uint_as_float(lds_vol(sb + SM_RS + (16 + wrow0 + gq) * 4)) * L2E; sc1 = __uint_as_float(lds_vol(sb + SM_RS + (24 + wrow0 + gq) * 4)) * L2E;
        __syncwarp();
        phi_proj<0>(p, kq, wa0);
        phi_exp(raw[0], p[0], sc0, sc1);
        phi_exp(raw[1], p[1], sc0, sc1);
        phi_proj<16>(p, kq, wa0 + 5120);
        phi_norm<0>(ph, raw, kq, wa0, sc0, sc1, rs0, rs1);
        kv_start(0);
        phi_exp(raw[0], p[0], sc0, sc1);
        kv_end(0);
        if (RL & 1) { SC_RELOAD(); }
        XO_LOAD();
        phi_exp(raw[1], p[1], sc0, sc1);
        phi_proj<32>(p, kq, wa0);
        phi_norm<16>(ph, raw, kq, wa0 + 5120, sc0, sc1, rs0, rs1);
        kv_start(1);
        if (lane == 0) release2(bar + B_E3);
        phi_exp(raw[0], p[0], sc0, sc1);
        kv_end(1);
        if (RL & 2) { SC_RELOAD(); }
        kv_load(0);
        phi_exp(raw[1], p[1], sc0, sc1);
        phi_proj<48>(p, kq, wa0 + 5120);
        phi_norm<32>(ph, raw, kq, wa0, sc0, sc1, 1.f, 1.f);
        o_start(0, ph);
        phi_exp(raw[0], p[0], sc0, sc1);
        o_end(0);
        SC_RELOAD();
        kv_load(1);
        phi_exp(raw[1], p[1], sc0, sc1);
        phi_norm<48>(ph, raw, kq, wa0 + 5120, sc0, sc1, 1.f, 1.f);
        o_start(1, ph);
        o_end(1);
      }
      __syncwarp();
      PROFT(lane == 0 && layer == PL, 216 + cw);
      if (lane == 0) mbar_arrive(bar + B_EPI);
      PROFT(tid_ == 128, layer * 16 + 6);
    }
    {
      PHASE_CTX();
      const uint32_t wu = c.cu >> 2;
      const uint32_t dA0 = (((sb + wu * 8192) & 0x3FFFF) >> 4) | (1u << 16), dB0 = ((sb & 0x3FFFF) >> 4) | (512u << 16);
#pragma unroll
      for (int i = 0; i < 32; ++i) { acc[128 + 2 * i] = bf_lo(xo[i]); acc[129 + 2 * i] = bf_hi(xo[i]); }
      nbar_dyn(3 + wg, 128);
      uint64_t ta = (layer & 1) ? WO_A1 : WO_A0, tw = (layer & 1) ? WO_B1 : WO_B0;
#pragma unroll 1
      for (int i = 0; i < 16; ++i) {
        bool rel = i > 0 && i < 12;
        if (DRY && rel && !__all_sync(0xffffffffu, mbar_test_wait(bar + B_FULLT + i * 8, layer & 1))) {
          wgmma_wait<0>();
          if (elected) release2(bar + B_CONS + (i - 1) * 8);
          rel = false;
        }
        mbar_wait(bar + B_FULLT + i * 8, layer & 1);
        PROFT(tid_ == 128 && layer == PL, 160 + i);
        const uint32_t da = dA0 + ((uint32_t)ta & 15) * 1024, db = dB0 + ((uint32_t)tw & 15) * 1024;
        ta >>= 4; tw >>= 4;
        wgmma_fence();
#pragma unroll
        for (int k = 0; k < 4; ++k) wgmma_n128(acc, D128(da + k * 2), D128(db + k * 128), 1);
        wgmma_commit();
        if (i == 0) {
          if (elected) {
            if ((layer & 1) && wu) release2(bar + B_E1);
            release2(bar + B_E2);
          }
        } else {
          wgmma_wait<1>();
          if (elected && rel) release2(bar + B_CONS + (i - 1) * 8);
          if (elected && (unsigned)(i - 13) < 2u && layer + 1 < NLAYERS) release2(bar + B_EMPTYS + (i - 13) * 8);
        }
      }
      const bool last = layer == NLAYERS - 1;
      wgmma_wait<0>();
#pragma unroll
      for (int i = 128; i < 192; ++i) asm volatile("" : "+f"(acc[i]) :: "memory");
      if (elected && !last) release2(bar + B_EMPTYS + 16);
      PROFT(tid_ == 128, layer * 16 + 7);
#pragma unroll
      for (int jp = 0; jp < 4; ++jp)
        stsm_x4(sb + XS * SLOT + rowo + (X ^ (jp << 5)),
                pack_bf16(acc[128 + 8 * jp], acc[129 + 8 * jp]), pack_bf16(acc[130 + 8 * jp], acc[131 + 8 * jp]),
                pack_bf16(acc[132 + 8 * jp], acc[133 + 8 * jp]), pack_bf16(acc[134 + 8 * jp], acc[135 + 8 * jp]));
      if (last) {
        __syncwarp();
        slab_out_half(sb + XS * SLOT, c.out + (size_t)m0 * D_ + g * 128, wrow0, lane);
        X_H1();
        __syncwarp();
        slab_out_half(sb + (XS + 1) * SLOT, c.out + (size_t)m0 * D_ + g * 128 + 64, wrow0, lane);
        __syncwarp();
        if (lane == 0) mbar_arrive(bar + B_XDONE);
        PROFT(tid_ == 128, layer * 16 + 24);
        break;
      }
      __syncwarp();
      slab_out_half<true>(sb + XS * SLOT, g_x + (size_t)m0 * D_ + g * 128, wrow0, lane);
      __syncwarp();
      if (lane == 0) mbar_arrive(bar + B_XH0);
      nbar_dyn(3 + wu, 128);
    }
  }
}

__device__ __forceinline__ void flag_fetch(uint32_t bar, const unsigned int* f) {
  asm volatile("{\n.reg .pred p;\nelect.sync _|p, 0xffffffff;\n@p mbarrier.expect_tx.relaxed.cta.shared::cta.b64 [%2], 64;\n"
               "@p cp.async.bulk.shared::cluster.global.mbarrier::complete_tx::bytes [%0], [%1], 64, [%2];\n}\n"
               ::"r"(bar + B_FLG), "l"(f), "r"(bar + 128) : "memory");
}
__device__ __forceinline__ int kblock0(int i, int g) {
  const int j = i >> 1, p = max(g, NCOM) + j - NCOM;
  return (j < NCOM ? j : p < 8 ? p : p - 8 + NCOM) * 2 + (i & 1);
}

#define WOORD 0xFDB9753ECA864210ull
__device__ __forceinline__ int wo_kblock(int m, int g) { return (2 * g + (int)((WOORD >> (4 * m)) & 15)) & 15; }

__global__ void __cluster_dims__(2, 1, 1) __launch_bounds__(384, 1)
mega_kernel(const __grid_constant__ CUtensorMap tm_x0, const __grid_constant__ CUtensorMap tm_x,
            const __grid_constant__ CUtensorMap tm_o,
            const __grid_constant__ CUtensorMap tm_wA, const __grid_constant__ CUtensorMap tm_wB,
            const __grid_constant__ CUtensorMap tm_woA, const __grid_constant__ CUtensorMap tm_woB,
            const bf16* __restrict__ wA, const bf16* __restrict__ wB,
            const bf16* __restrict__ wphi, bf16* __restrict__ out) {
  extern __shared__ uint8_t smem_raw[];
  const uint32_t sb = (smem_u32(smem_raw) + 1023u) & ~1023u;
  const uint32_t bar = sb + SM_BAR;
  const int warp = __shfl_sync(0xffffffffu, threadIdx.x >> 5, 0), lane = threadIdx.x & 31;
  const int cr = blockIdx.x & 1;
  const int g = (blockIdx.x >> 1) & 7;
  const int rb = (blockIdx.x >> 4) * 2 + cr;
  const int m0 = rb * 128;

  if (warp < 4) {
    asm volatile("setmaxnreg.dec.sync.aligned.u32 40;");
    asm volatile("barrier.cluster.arrive.relaxed.aligned;" ::: "memory");
    const unsigned int epoch = warp ? ld_relaxed(&g_epoch) : 0u;
    if (warp) cluster_wait();
    unsigned int xbase = epoch * NLAYERS;
    const unsigned int cbase = epoch * 16u;
    auto wo_a = [&](int layer) {
      uint64_t ts = ((layer & 1) ? WO_A1 : WO_A0) >> 8, td = ((layer & 1) ? WO_DA1 : WO_DA0) >> 8, tk = WOORD >> 8;
      uint32_t ready = 0u;
#pragma unroll 1
      for (int m = 2; m < 16; ++m) {
        const int kb = (2 * g + (uint32_t)tk) & 15;
        uint32_t dst = sb + ((uint32_t)ts & 15) * SLOT, fb = bar + B_FULLT + m * 8, eb = bar + B_CONS + ((uint32_t)td & 15) * 8;
        int kc = kb * 64;
        ts >>= 4; td >>= 4; tk >>= 4;
        if (!((ready >> kb) & 1)) {
          PROFT(m == 2 && lane == 0, 64 + layer * 16 + 2);
          if (EP && m > EP) {
            uint32_t n = 0;
#pragma unroll 1
            while (true) {
              ready |= __ballot_sync(0xffffffffu, (int)(lds_vol(bar + B_FLG + (lane & 15) * 4) - (xbase + layer + 1)) >= 0);
              if (((ready >> kb) & 1) || ++n > (1u << 20)) break;
              if ((n & 3) == 0) flag_fetch(bar, g_of + rb * 32);
              __nanosleep(PSL);
            }
          }
          src_wait<0>(g_of + rb * 32, xbase + layer + 1, 1u << kb, ready, lane);
          fence_async_all();
        }
        asm volatile("" : "+r"(dst), "+r"(fb), "+r"(eb), "+r"(kc));
        mbar_wait_u(eb, layer & 1);
        tma_2d_e(dst, &tm_o, kc, m0, fb);
        if (EP && m >= EP && (ready & 0xFFFFu) != 0xFFFFu) flag_fetch(bar, g_of + rb * 32);
        PROFT(lane == 0 && layer == PL, 176 + m);
      }
    };
    auto wo_w = [&](int layer) {
      const CUtensorMap* tx = layer == 0 ? &tm_x0 : &tm_x;
      const CUtensorMap* two = (layer & 1) ? &tm_woB : &tm_woA;
      uint64_t ts = (layer & 1) ? WO_B1 : WO_B0, td = (layer & 1) ? WO_DB1 : WO_DB0, tk = WOORD;
      fence_async_all();
      mbar_wait_u(bar + B_R0, layer & 1);
      expect_tx_e(bar + B_XOLD, 16384);
      tma_2d_e(sb + (XS + 1) * SLOT, tx, g * 128, m0, bar + B_XOLD);
#pragma unroll 1
      for (int m = 0; m < 16; ++m) {
        uint32_t dst = sb + ((uint32_t)ts & 15) * SLOT + cr * 8192, fb = bar + B_FULLT + m * 8, eb = bar + B_CONS + ((uint32_t)td & 15) * 8;
        int kc = ((2 * g + (uint32_t)tk) & 15) * 64;
        ts >>= 4; td >>= 4; tk >>= 4;
        asm volatile("" : "+r"(dst), "+r"(fb), "+r"(eb), "+r"(kc));
        mbar_wait_u(eb, layer & 1);
        tma_2d_mc_e(dst, two, g * 128 + cr * 64, kc, fb);
        expect_tx_e(fb, m < 2 ? 16384 : 32768);
        PROFT(lane == 0 && layer == PL, 144 + m);
        if (m == 0) {
          expect_tx_e(bar + B_XOLD2, 16384);
          tma_2d_e(sb + XS * SLOT, tx, g * 128 + 64, m0, bar + B_XOLD2);
        }
      }
    };
    if (warp == 0) {
      cluster_wait();
      PROFT(lane == 0, 125);
#pragma unroll 1
      for (int layer = 0; layer < NLAYERS; ++layer) {
        const CUtensorMap* tx = layer == 0 ? &tm_x0 : &tm_x;
        const CUtensorMap* tw = (layer & 1) ? &tm_wB : &tm_wA;
        uint32_t s = layer == 0, u = 0, ready = layer == 0 ? 0xFFFFu : 0u;
#pragma unroll 1
        for (int i = s; i < 16; ++i) {
          const int kb = layer == 0 ? kblock0(i, g) : wo_kblock(i, g), kc = kb * 64;
          const uint32_t fb = bar + B_FULLS + s * 8;
          const uint32_t kd = sb + (((QK >> (4 * s)) & 15) + cr) * SLOT, qd = sb + ((QQ >> (4 * s)) & 15) * SLOT + cr * 8192;
          const uint32_t need = 1u << kb;
          const bool ext = i >= 2 || layer == 0, early = ext && (ready & need) == need;
          mbar_wait_u(bar + B_EMPTYS + s * 8, (u + (s ? layer : 0) + 1) & 1);
          if (early) tma_2d_e(sb + ((QA >> (4 * s)) & 15) * SLOT, tx, kc, m0, fb);
          tma_2d_mc_e(kd, tw, 1024 + cr * 1024 + g * 128, kc, fb);
          tma_2d_mc_e(kd + 8192, tw, 1024 + cr * 1024 + g * 128 + 64, kc, fb);
          tma_2d_mc_e(qd, tw, g * 128 + cr * 64, kc, fb);
          expect_tx_e(fb, ext ? 65536 : 49152);
          PROFT(lane == 0 && layer == 0 && i == 1, 31);
          if (layer == 0 && i == 2) {
            mbar_wait_u(bar + B_FULLS, 0);
            tma_pf_e(&tm_x0, g * 128, m0);
            tma_pf_e(&tm_x0, g * 128 + 64, m0);
          }
          if (layer < 2 && i >= PFS) {
            const int j = i - PFS;
            if (j < 2) tma_pf_e(layer ? &tm_woB : &tm_woA, g * 128 + j * 64, rb * 64);
            else if (j < 8 && layer == 0) tma_pf_e(&tm_wB, ((j >> 1) - 1) * 1024 + g * 128 + (j & 1) * 64, rb * 64);
          }
          if (ext && !early) {
            PROFT(i == 2 && lane == 0, 64 + layer * 16 + 0);
            src_wait<0>(g_xf + rb * 32, xbase + layer + 1, need, ready, lane);
            PROFT(i == 2 && lane == 0, 64 + layer * 16 + 1);
            fence_async_all();
            tma_2d_e(sb + ((QA >> (4 * s)) & 15) * SLOT, tx, kc, m0, fb);
          }
          if (++s == 3) { s = 0; ++u; }
        }
        if (layer == 0) xbase = ld_relaxed(&g_epoch) * NLAYERS;
        wo_a(layer);
      }
    } else {
      if (warp >= 2) {
        const int h2 = threadIdx.x - 64;
#pragma unroll 1
        for (int i = h2; i < 512; i += 64)
          asm volatile("cp.async.cg.shared.global [%0], [%1], 16;" ::"r"(sb + SM_WPHI + (i >> 2) * 80 + (i & 3) * 16), "l"(wphi + (size_t)g * 4096 + i * 8) : "memory");
        if (h2 < 16) sts_f(sb + SM_RS + h2 * 4, 0.f);
        if (h2 < 16) sts_f(bar + B_FLG + h2 * 4, __uint_as_float(xbase));
        if (h2 == 0) sts_f(sb + SM_EPOCH, __uint_as_float(epoch));
        if (rb >= CG0) mbar_wait_u(bar + B_FULLS + (rb >= CG1 ? 8 : 0), 0);
        if (CPF && h2 < 4) asm volatile("cp.async.bulk.prefetch.tensor.2d.L2.global.tile [%0, {%1, %2}];" ::"l"(&tm_wA), "r"((h2 & 2) * 1024 + g * 128 + (h2 & 1) * 64), "r"(rb * 64) : "memory");
#pragma unroll 1
        for (int wi = 0; wi < 3; ++wi) {
          float sA[8];
          colsum_load(wA, rb, g, warp - 2 + 2 * wi, lane, sb + SM_BP + (warp - 2) * 6144, sA);
          colsum_red(g_cs + (epoch & 1) * 6144, g, warp - 2 + 2 * wi, lane, sA);
        }
#pragma unroll 1
        for (int i = h2; i < 320; i += 64) g_kv[(g * 16 + rb) * 320 + i] = make_uint4(0u, 0u, 0u, 0u);
        fence_async_all();
        nbar<5, 64>();
        if (h2 == 0) flag_add(&g_csflag[g].v);
        PROFT(h2 == 0, 242);
      }
      if (warp == 1) {
        if (lane >= 27) {
          const CUtensorMap* tm = lane == 27 ? &tm_o : lane == 28 ? &tm_wB : lane == 29 ? &tm_woA : lane == 30 ? &tm_woB : &tm_x;
          asm volatile("prefetch.tensormap [%0];" ::"l"(tm) : "memory");
        }
        if (lane == 0) {
#pragma unroll 1
          for (int e = 0;; ++e) {
            if (e > 0 && e < NLAYERS) {
              mbar_wait(bar + B_XH0, (e - 1) & 1);
              flag_set(g_xf + rb * 32 + 2 * g, xbase + e + 1);
            }
            mbar_wait(bar + B_XDONE, e & 1);
            PROFT(e < 4, 64 + e * 16 + 4);
            if (e == NLAYERS) {
              if (blockIdx.x == 0) g_epoch = epoch + 1;
              break;
            }
            PROFT(e < 4, 64 + e * 16 + 5);
            flag_set(g_xf + rb * 32 + 2 * g + 1, xbase + e + 1);
            PROFT(e < 4, 64 + e * 16 + 7);
            if ((e & 1) == 0) {
#pragma unroll 1
              for (int hp = 0; hp < 2; ++hp) {
                uint4* kvl = g_kv + ((g * 2 + (e >> 1)) * 2 + hp) * 1280;
                mbar_wait(bar + B_KVDONE - hp * 32, (e >> 1) & 1);
                PROFT(e == PL, 243 + hp * 4);
                bulk_red_add(kvl + rb * 64, sb + (3 + hp) * SLOT + rb * 1024, 16384 - rb * 1024);
                if (rb) bulk_red_add(kvl, sb + (3 + hp) * SLOT, rb * 1024);
                bulk_red_add(kvl + 1024, sb + (6 + hp) * SLOT, 2048);
                bulk_red_add(kvl + 1152, sb + (6 + hp) * SLOT + 8192, 2048);
                bulk_commit();
                PROFT(e < 4, 64 + e * 16 + 6);
              }
              bulk_wait_read0();
              release2(bar + B_E1);
              release2(bar + B_E1);
            }
            mbar_wait(bar + B_OH1, e & 1);
            flag_set(g_of + rb * 32 + 2 * g, xbase + e + 1);
            PROFT(e < 4, 64 + e * 16 + 9);
            mbar_wait(bar + B_ODONE, e & 1);
            PROFT(e < 4, 64 + e * 16 + 8);
            flag_set(g_of + rb * 32 + 2 * g + 1, xbase + e + 1);
            PROFT(e < 4, 64 + e * 16 + 11);
          }
        }
      } else {
        const int h2 = threadIdx.x - 64;
        const float* cs = g_cs + (epoch & 1) * 6144;
#pragma unroll 1
        for (int layer = 0; layer < NLAYERS; ++layer) {
          if (warp == 2 && layer < 2) {
            if (lane == 0) flag_wait_t<CSLP>(&g_csflag[layer * 8 + g].v, cbase + 16u);
            __syncwarp();
            float4 a[3];
#pragma unroll
            for (int i = 0; i < 3; ++i) a[i] = __ldcg(reinterpret_cast<const float4*>(cs + layer * 3072 + g * 384) + i * 32 + lane);
#pragma unroll 1
            for (int i = 0; i < 3; ++i) {
              const float av[4] = {a[0].x, a[0].y, a[0].z, a[0].w};
              a[0] = a[1]; a[1] = a[2];
#pragma unroll
              for (int j = 0; j < 4; ++j) {
                const float c1 = bf16r(av[j]), c2 = bf16r(av[j] - c1), c3 = (av[j] - c1) - c2;
                sts128(sb + SM_BP + layer * 6144 + ((i * 32 + lane) * 4 + j) * 16, make_uint4(pack_bf16(c1, c2), pack_bf16(c3, 0.f), 0u, 0u));
              }
            }
            fence_async_smem();
            __syncwarp();
            if (lane == 0) mbar_arrive(bar + (layer ? B_CS2 : B_CS));
            PROFT(lane == 0, 64 + layer * 16 + 12);
            if (layer == 0) {
              uint4* hz = g_halo + (size_t)((epoch & 1) ^ 1) * (2 * 128 * 512) + blockIdx.x * 1024;
#pragma unroll 2
              for (int i = lane; i < 1024; i += 32) hz[i] = make_uint4(0u, 0u, 0u, 0u);
              if (lane < 12) reinterpret_cast<float4*>(g_cs + ((epoch & 1) ^ 1) * 6144 + blockIdx.x * 48)[lane] = make_float4(0.f, 0.f, 0.f, 0.f);
              g_stats[(2 + (lane >> 4)) * S_ + m0 + g * 16 + (lane & 15)] = make_float2(0.f, 0.f);
            }
          }
          if (warp == 3) {
            const bool hal = (layer & 1) && rb > 0;
            {
              uint32_t rdy = 0u;
              src_wait<256>(g_xf + rb * 32, xbase + layer + 1, 0xAAAAu, rdy, lane);
              rdy = 0u;
              if (hal) src_wait<256>(g_xf + (rb - 1) * 32, xbase + layer + 1, 0xAAAAu, rdy, lane);
            }
            float2 u[5];
            const float2* sp = g_stats + layer * S_ + m0 + lane;
#pragma unroll
            for (int i = 0; i < 4; ++i) u[i] = __ldcg(sp + i * 32);
            u[4] = __ldcg(hal ? sp - 16 : sp);
            if (layer == 3) g_stats[(lane >> 4) * S_ + m0 + g * 16 + (lane & 15)] = make_float2(0.f, 0.f);
#pragma unroll 1
            for (int i = 0; i < (hal ? 5 : 4); ++i) {
              const int r = i < 4 ? 16 + i * 32 + lane : lane;
              const float sum = u[0].x, sq = u[0].y;
              u[0] = u[1]; u[1] = u[2]; u[2] = u[3]; u[3] = u[4];
              const float mean = sum * (1.f / D_);
              const float var = fmaxf(fmaf(-sum, mean, sq) * (1.f / D_), 0.f);
              const float sd = bf16r(sqrtf(bf16r(bf16r(var) + 1e-5f)));
              sts_f(sb + SM_RS + r * 4, 1.f / sd);
              if (i < 4) {
                const float hm = -0.5f * bf16r(mean);
                const uint32_t s2 = pack_bf16(sd, sd);
                sts128(sb + SM_SD + (r - 16) * 64 + ((r >> 1) & 3) * 16, make_uint4(s2, s2, s2, s2));
                sts128(sb + SM_AP + (r - 16) * 16, make_uint4(pack_bf16(hm, hm), pack_bf16(hm, 0.f), 0u, 0u));
              }
            }
            fence_async_smem();
            __syncwarp();
            if (lane == 0) mbar_arrive(bar + B_STAT);
            PROFT(lane == 0, 64 + layer * 16 + 14);
            wo_w(__shfl_sync(0xffffffffu, layer, 0));
          }
          if (layer == 0 && warp == 2) {
            if (CSW) mbar_wait_u(bar + (CSW == 1 ? B_E0 : CSW == 2 ? B_OH1 : B_ODONE), 0);
#pragma unroll 1
            for (int wi = 0; wi < 6; ++wi) {
              float sB[8];
              colsum_load(wB, rb, g, wi, lane, sb + SM_BP + 6144, sB);
              colsum_red(g_cs + (epoch & 1) * 6144 + 3072, g, wi, lane, sB);
            }
            __syncwarp();
            if (lane == 0) flag_add(&g_csflag[8 + g].v);
            PROFT(h2 == 0, 64 + 13);
          }
        }
      }
    }
    __syncwarp();
    asm volatile("barrier.cluster.arrive.relaxed.aligned;\nbarrier.cluster.wait.aligned;\n" ::: "memory");
  } else {
    if (warp == 5) {
      if (lane == 0) {
        mbar_init(bar + B_FULLS, 1);
        asm volatile("fence.mbarrier_init.release.cluster;" ::: "memory");
      }
      __syncwarp();
      expect_tx_e(bar + B_FULLS, 65536);
      tma_2d_e(sb + XS * SLOT, &tm_x0, 0, m0, bar + B_FULLS);
#pragma unroll
      for (int j = 0; j < 6; ++j)
        tma_2d_e(sb + (j < 4 ? j + 4 : j - 2) * 8192, &tm_wA, (j < 4 ? 1024 + (j >> 1) * 1024 : 0) + g * 128 + (j & 1) * 64, 0, bar + B_FULLS);
      PROFT(lane == 0, 241);
    }
    if (lane < 8 && warp != 5 && threadIdx.x != 128) {
      const int i = (warp - 4) * 8 + lane;
      mbar_init(bar + i * 8, i < 32 ? 1u << ((BAR_CNT >> (2 * i)) & 3) : i < 48 ? 1u : (i == 59 || i == 60) ? 16u : i < 63 ? 4u : 8u);
      asm volatile("fence.mbarrier_init.release.cluster;" ::: "memory");
    }
    __syncwarp();
    asm volatile("barrier.cluster.arrive.relaxed.aligned;" ::: "memory");
    asm volatile("setmaxnreg.inc.sync.aligned.u32 232;");
    cluster_wait();
    PROFT(threadIdx.x == 128, 0);
    Ctx c; c.sb = sb; c.g = g; c.rb = rb; c.cu = warp - 4; c.out = out;
    consumer(c);
    asm volatile("bar.warp.sync 0xffffffff;\nbarrier.cluster.arrive.relaxed.aligned;\nbarrier.cluster.wait.aligned;\n" ::: "memory");
  }
}

typedef CUresult (*PFN_encodeTiled)(CUtensorMap*, CUtensorMapDataType, cuuint32_t, void*, const cuuint64_t*, const cuuint64_t*,
                                    const cuuint32_t*, const cuuint32_t*, CUtensorMapInterleave, CUtensorMapSwizzle,
                                    CUtensorMapL2promotion, CUtensorMapFloatOOBfill);

static CUtensorMap make_map(PFN_encodeTiled enc, const void* ptr, uint64_t cols, uint64_t rows, uint32_t box_c, uint32_t box_r, uint32_t nb = 1) {
  CUtensorMap m;
  cuuint64_t dims[3] = {nb > 1 ? box_c : cols, rows, cols / box_c};
  cuuint64_t strides[2] = {cols * 2, box_c * 2};
  cuuint32_t box[3] = {box_c, box_r, nb};
  cuuint32_t es[3] = {1, 1, 1};
  CUresult r = enc(&m, CU_TENSOR_MAP_DATA_TYPE_BFLOAT16, nb > 1 ? 3 : 2, const_cast<void*>(ptr), dims, strides, box, es, CU_TENSOR_MAP_INTERLEAVE_NONE,
      CU_TENSOR_MAP_SWIZZLE_128B, CU_TENSOR_MAP_L2_PROMOTION_L2_256B, CU_TENSOR_MAP_FLOAT_OOB_FILL_NONE);
  (void)r;
  return m;
}

extern "C" void kernel_launch(void* const* d_in, const int* in_sizes, int n_in, void* d_out, int out_size) {
  const bf16* A_x = (const bf16*)d_in[0];
  const bf16* A_wqkv = (const bf16*)d_in[1];
  const bf16* A_wphi = (const bf16*)d_in[2];
  const bf16* A_wo = (const bf16*)d_in[3];
  const bf16* B_wqkv = (const bf16*)d_in[5];
  const bf16* B_wo = (const bf16*)d_in[6];
  bf16* out = (bf16*)d_out;

  static PFN_encodeTiled enc = nullptr;
  static bf16 *p_x, *p_o;
  if (!enc) {
    void* fn = nullptr; cudaDriverEntryPointQueryResult qr;
    cudaGetDriverEntryPoint("cuTensorMapEncodeTiled", &fn, cudaEnableDefault, &qr);
    enc = (PFN_encodeTiled)fn;
    cudaGetSymbolAddress((void**)&p_x, g_x);
    cudaGetSymbolAddress((void**)&p_o, g_o);
    cudaFuncSetAttribute(mega_kernel, cudaFuncAttributeMaxDynamicSharedMemorySize, SM_TOTAL);
  }
  CUtensorMap tm_x0 = make_map(enc, A_x, 1024, 2048, 64, 128);
  CUtensorMap tm_x = make_map(enc, p_x, 1024, 2048, 64, 128);
  CUtensorMap tm_o = make_map(enc, p_o, 1024, 2048, 64, 128);
  CUtensorMap tm_wA = make_map(enc, A_wqkv, 3072, 1024, 64, 64);
  CUtensorMap tm_wB = make_map(enc, B_wqkv, 3072, 1024, 64, 64);
  CUtensorMap tm_woA = make_map(enc, A_wo, 1024, 1024, 64, 64);
  CUtensorMap tm_woB = make_map(enc, B_wo, 1024, 1024, 64, 64);
  mega_kernel<<<128, 384, SM_TOTAL, cudaStreamPerThread>>>(tm_x0, tm_x, tm_o, tm_wA, tm_wB, tm_woA, tm_woB,
                                                           A_wqkv, B_wqkv, A_wphi, out);
}
```

```cpp
#include <cuda_runtime.h>
#include <cuda_bf16.h>
#include <cuda.h>
#include <stdint.h>

typedef __nv_bfloat16 bf16;

constexpr int S_ = 2048, D_ = 1024;

struct __align__(128) Flag { unsigned int v; unsigned int pad[31]; };
__device__ __align__(1024) bf16 g_x[S_ * D_];
__device__ __align__(1024) bf16 g_o[S_ * D_];
__device__ __align__(1024) uint4 g_halo[2 * 2 * 128 * 512];
__device__ __align__(1024) uint4 g_kv[8 * 2 * 2 * 1280];
__device__ __align__(1024) float2 g_stats[4 * S_];
__device__ __align__(1024) float g_cs[2 * 2 * 3072];
__device__ Flag g_csflag[16];
__device__ __align__(128) unsigned int g_xf[16 * 32], g_of[16 * 32];
__device__ unsigned int g_epoch, g_err;
#define PROFT(cond, idx) asm volatile("" ::: "memory")

__device__ __forceinline__ uint32_t smem_u32(const void* p) { return (uint32_t)__cvta_generic_to_shared(p); }
__device__ __forceinline__ void mbar_init(uint32_t bar, uint32_t count) {
  asm volatile("mbarrier.init.shared::cta.b64 [%0], %1;" ::"r"(bar), "r"(count) : "memory");
}
__device__ __forceinline__ void mbar_expect_tx(uint32_t bar, uint32_t bytes) {
  asm volatile("mbarrier.arrive.expect_tx.shared::cta.b64 _, [%0], %1;" ::"r"(bar), "r"(bytes) : "memory");
}
__device__ __forceinline__ void mbar_arrive(uint32_t bar) {
  asm volatile("mbarrier.arrive.shared::cta.b64 _, [%0];" ::"r"(bar) : "memory");
}
__device__ __forceinline__ bool mbar_try_wait(uint32_t bar, uint32_t parity) {
  uint32_t ok;
  asm volatile("{\n.reg .pred p;\nmbarrier.try_wait.parity.shared::cta.b64 p, [%1], %2;\nselp.b32 %0, 1, 0, p;\n}\n"
               : "=r"(ok) : "r"(bar), "r"(parity) : "memory");
  return ok != 0;
}
__device__ __forceinline__ bool mbar_test_wait(uint32_t bar, uint32_t parity) {
  uint32_t ok;
  asm volatile("{\n.reg .pred p;\nmbarrier.test_wait.parity.shared::cta.b64 p, [%1], %2;\nselp.b32 %0, 1, 0, p;\n}\n"
               : "=r"(ok) : "r"(bar), "r"(parity) : "memory");
  return ok != 0;
}
__device__ __forceinline__ uint64_t gtimer() {
  uint64_t t; asm volatile("mov.u64 %0, %globaltimer;" : "=l"(t)); return t;
}
__device__ __forceinline__ void mbar_wait(uint32_t bar, uint32_t parity) {
  uint32_t n = 0;
#pragma unroll 1
  while (!mbar_try_wait(bar, parity)) {
    if (++n > (1u << 22)) { g_err = 1u; break; }
  }
}
__device__ __forceinline__ unsigned int ld_acquire(const unsigned int* p) {
  unsigned int v; asm volatile("ld.acquire.gpu.global.u32 %0, [%1];" : "=r"(v) : "l"(p) : "memory"); return v;
}
__device__ __forceinline__ void flag_add(unsigned int* p) {
  asm volatile("red.release.gpu.global.add.u32 [%0], 1;" ::"l"(p) : "memory");
}
__device__ __forceinline__ void flag_set(unsigned int* p, unsigned int v) {
  asm volatile("st.release.gpu.global.u32 [%0], %1;" ::"l"(p), "r"(v) : "memory");
}
template <int SLEEP>
__device__ __forceinline__ void src_wait(const unsigned int* f, unsigned int target, uint32_t need, uint32_t& ready, int lane) {
  uint32_t n = 0;
#pragma unroll 1
  while ((ready & need) != need) {
    const unsigned int v = ld_acquire(f + (lane & 15));
    ready = __ballot_sync(0xffffffffu, (int)(v - target) >= 0);
    if (SLEEP) { if ((ready & need) != need) __nanosleep(SLEEP); }
    if (++n > (1u << 20)) { g_err = 3u; break; }
  }
  __syncwarp();
}
__device__ __forceinline__ unsigned int ld_relaxed(const unsigned int* p) {
  unsigned int v; asm volatile("ld.relaxed.gpu.global.u32 %0, [%1];" : "=r"(v) : "l"(p) : "memory"); return v;
}
__device__ __forceinline__ uint4 ld_relaxed4(const uint4* p) {
  uint4 v; asm volatile("ld.relaxed.gpu.global.v4.u32 {%0,%1,%2,%3}, [%4];" : "=r"(v.x), "=r"(v.y), "=r"(v.z), "=r"(v.w) : "l"(p) : "memory"); return v;
}
__device__ __forceinline__ void st_relaxed4(uint4* p, uint32_t a, uint32_t b, uint32_t c, uint32_t d) {
  asm volatile("st.relaxed.gpu.global.v4.u32 [%0], {%1,%2,%3,%4};" ::"l"(p), "r"(a), "r"(b), "r"(c), "r"(d) : "memory");
}
template <int SLEEP>
__device__ __forceinline__ void flag_wait_t(const unsigned int* p, unsigned int target) {
  uint32_t n = 0;
#pragma unroll 1
  while ((int)(ld_acquire(p) - target) < 0) {
    if (SLEEP) __nanosleep(SLEEP);
    if (++n > (1u << 20)) { g_err = 2u; break; }
  }
}
__device__ __forceinline__ void flag_wait(const unsigned int* p, unsigned int target) { flag_wait_t<0>(p, target); }
__device__ __forceinline__ void flag_wait_slow(const unsigned int* p, unsigned int target) { flag_wait_t<256>(p, target); }
__device__ __forceinline__ void tma_load_2d(uint32_t dst, const CUtensorMap* tm, int c0, int c1, uint32_t bar) {
  asm volatile("cp.async.bulk.tensor.2d.shared::cluster.global.mbarrier::complete_tx::bytes [%0], [%1, {%2, %3}], [%4];"
               ::"r"(dst), "l"(tm), "r"(c0), "r"(c1), "r"(bar) : "memory");
}
__device__ __forceinline__ void tma_load_2d_mc(uint32_t dst, const CUtensorMap* tm, int c0, int c1, uint32_t bar, uint16_t mask) {
  asm volatile("cp.async.bulk.tensor.2d.shared::cluster.global.mbarrier::complete_tx::bytes.multicast::cluster [%0], [%1, {%2, %3}], [%4], %5;"
               ::"r"(dst), "l"(tm), "r"(c0), "r"(c1), "r"(bar), "h"(mask) : "memory");
}
__device__ __forceinline__ void mbar_wait_u(uint32_t bar, uint32_t parity) {
  uint32_t n = 0;
#pragma unroll 1
  while (!__all_sync(0xffffffffu, mbar_try_wait(bar, parity))) {
    if (++n > (1u << 22)) { g_err = 1u; break; }
  }
}
__device__ __forceinline__ void expect_tx_e(uint32_t bar, uint32_t bytes) {
  asm volatile("{\n.reg .pred p;\nelect.sync _|p, 0xffffffff;\n@p mbarrier.arrive.expect_tx.shared::cta.b64 _, [%0], %1;\n}\n" ::"r"(bar), "r"(bytes) : "memory");
}
__device__ __forceinline__ void tma_2d_e(uint32_t dst, const CUtensorMap* tm, int c0, int c1, uint32_t bar) {
  asm volatile("{\n.reg .pred p;\nelect.sync _|p, 0xffffffff;\n"
               "@p cp.async.bulk.tensor.2d.shared::cluster.global.mbarrier::complete_tx::bytes [%0], [%1, {%2, %3}], [%4];\n}\n"
               ::"r"(dst), "l"(tm), "r"(c0), "r"(c1), "r"(bar) : "memory");
}
__device__ __forceinline__ void tma_2d_mc_e(uint32_t dst, const CUtensorMap* tm, int c0, int c1, uint32_t bar) {
  asm volatile("{\n.reg .pred p;\nelect.sync _|p, 0xffffffff;\n"
               "@p cp.async.bulk.tensor.2d.shared::cluster.global.mbarrier::complete_tx::bytes.multicast::cluster [%0], [%1, {%2, %3}], [%4], %5;\n}\n"
               ::"r"(dst), "l"(tm), "r"(c0), "r"(c1), "r"(bar), "h"((uint16_t)3) : "memory");
}
__device__ __forceinline__ void tma_pf_e(const CUtensorMap* tm, int c0, int c1) {
  asm volatile("{\n.reg .pred p;\nelect.sync _|p, 0xffffffff;\n"
               "@p cp.async.bulk.prefetch.tensor.2d.L2.global.tile [%0, {%1, %2}];\n}\n" ::"l"(tm), "r"(c0), "r"(c1) : "memory");
}
__device__ __forceinline__ void tma_2d_to_e(uint32_t dst, const CUtensorMap* tm, int c0, int c1, uint32_t bar, uint32_t mask) {
  asm volatile("{\n.reg .pred p;\nelect.sync _|p, 0xffffffff;\n"
               "@p cp.async.bulk.tensor.2d.shared::cluster.global.mbarrier::complete_tx::bytes.multicast::cluster [%0], [%1, {%2, %3}], [%4], %5;\n}\n"
               ::"r"(dst), "l"(tm), "r"(c0), "r"(c1), "r"(bar), "h"((uint16_t)mask) : "memory");
}
__device__ __forceinline__ void tma_3d_mc_e(uint32_t dst, const CUtensorMap* tm, int c1, int c2, uint32_t bar) {
  asm volatile("{\n.reg .pred p;\nelect.sync _|p, 0xffffffff;\n"
               "@p cp.async.bulk.tensor.3d.shared::cluster.global.mbarrier::complete_tx::bytes.multicast::cluster [%0], [%1, {%6, %2, %3}], [%4], %5;\n}\n"
               ::"r"(dst), "l"(tm), "r"(c1), "r"(c2), "r"(bar), "h"((uint16_t)3), "r"(0) : "memory");
}
__device__ __forceinline__ uint32_t poll_flags(const unsigned int* f, unsigned int target, int lane) {
  const unsigned int v = ld_acquire(f + (lane & 15));
  const uint32_t r = __ballot_sync(0xffffffffu, (int)(v - target) >= 0);
  __syncwarp();
  return r;
}
__device__ __forceinline__ void mbar_arrive_cluster(uint32_t local_bar, uint32_t rank) {
  asm volatile("{\n.reg .b32 ra;\nmapa.shared::cluster.u32 ra, %0, %1;\nmbarrier.arrive.shared::cluster.b64 _, [ra];\n}\n"
               ::"r"(local_bar), "r"(rank) : "memory");
}
__device__ __forceinline__ void release2(uint32_t bar) { mbar_arrive_cluster(bar, 0); mbar_arrive_cluster(bar, 1); }
__device__ __forceinline__ void tma_store_2d(const CUtensorMap* tm, uint32_t src, int c0, int c1) {
  asm volatile("cp.async.bulk.tensor.2d.global.shared::cta.bulk_group [%0, {%2, %3}], [%1];"
               ::"l"(tm), "r"(src), "r"(c0), "r"(c1) : "memory");
}
__device__ __forceinline__ void bulk_store(void* dst, uint32_t src, uint32_t bytes) {
  asm volatile("cp.async.bulk.global.shared::cta.bulk_group [%0], [%1], %2;" ::"l"(dst), "r"(src), "r"(bytes) : "memory");
}
__device__ __forceinline__ void bulk_load(uint32_t dst, const void* src, uint32_t bytes, uint32_t bar) {
  asm volatile("cp.async.bulk.shared::cluster.global.mbarrier::complete_tx::bytes [%0], [%1], %2, [%3];" ::"r"(dst), "l"(src), "r"(bytes), "r"(bar) : "memory");
}
__device__ __forceinline__ void bulk_red_add(void* dst, uint32_t src, uint32_t bytes) {
  asm volatile("cp.reduce.async.bulk.global.shared::cta.bulk_group.add.f32 [%0], [%1], %2;" ::"l"(dst), "r"(src), "r"(bytes) : "memory");
}
__device__ __forceinline__ void bulk_commit() { asm volatile("cp.async.bulk.commit_group;" ::: "memory"); }
__device__ __forceinline__ void bulk_wait_read0() { asm volatile("cp.async.bulk.wait_group.read 0;" ::: "memory"); }
__device__ __forceinline__ void bulk_wait0() { asm volatile("cp.async.bulk.wait_group 0;" ::: "memory"); }
__device__ __forceinline__ void fence_async_smem() { asm volatile("fence.proxy.async.shared::cta;" ::: "memory"); }
__device__ __forceinline__ void fence_async_all() { asm volatile("fence.proxy.async.global;" ::: "memory"); }
__device__ __forceinline__ void wgmma_fence() { asm volatile("wgmma.fence.sync.aligned;" ::: "memory"); }
__device__ __forceinline__ void wgmma_commit() { asm volatile("wgmma.commit_group.sync.aligned;" ::: "memory"); }
template <int N> __device__ __forceinline__ void wgmma_wait() { asm volatile("wgmma.wait_group.sync.aligned %0;" ::"n"(N) : "memory"); }
__device__ __forceinline__ void cluster_arrive() { asm volatile("barrier.cluster.arrive.release.aligned;" ::: "memory"); }
__device__ __forceinline__ void cluster_wait() { asm volatile("barrier.cluster.wait.acquire.aligned;" ::: "memory"); }
template <int ID, int N> __device__ __forceinline__ void nbar() { asm volatile("bar.sync %0, %1;" ::"n"(ID), "n"(N) : "memory"); }
__device__ __forceinline__ uint64_t make_desc(uint32_t addr, uint32_t lbo_bytes, uint32_t sbo_bytes) {
  uint64_t d = 0;
  d |= (uint64_t)((addr & 0x3FFFF) >> 4);
  d |= (uint64_t)((lbo_bytes >> 4) & 0x3FFF) << 16;
  d |= (uint64_t)((sbo_bytes >> 4) & 0x3FFF) << 32;
  d |= (uint64_t)1 << 62;
  return d;
}
__device__ __forceinline__ uint64_t desc64(uint32_t lo, uint32_t hi) { return (uint64_t)lo | ((uint64_t)hi << 32); }
__device__ __forceinline__ uint32_t pack_bf16(float lo, float hi) {
  uint32_t r; asm("cvt.rn.bf16x2.f32 %0, %1, %2;" : "=r"(r) : "f"(hi), "f"(lo)); return r;
}
__device__ __forceinline__ uint32_t mul_bf16x2(uint32_t a, uint32_t s, bool hi) {
  __nv_bfloat162 x = *reinterpret_cast<__nv_bfloat162*>(&a), y = *reinterpret_cast<__nv_bfloat162*>(&s);
  x = __hmul2(x, hi ? __high2bfloat162(y) : __low2bfloat162(y));
  return *reinterpret_cast<uint32_t*>(&x);
}
__device__ __forceinline__ float bf16r(float x) { return __bfloat162float(__float2bfloat16_rn(x)); }
__device__ __forceinline__ float bf_lo(uint32_t u) { return __uint_as_float(u << 16); }
__device__ __forceinline__ float bf_hi(uint32_t u) { return __uint_as_float(u & 0xFFFF0000u); }
__device__ __forceinline__ float ex2(float x) { float r; asm("ex2.approx.ftz.f32 %0, %1;" : "=f"(r) : "f"(x)); return r; }
__device__ __forceinline__ float rcp(float x) { float r; asm("rcp.approx.ftz.f32 %0, %1;" : "=f"(r) : "f"(x)); return r; }
__device__ __forceinline__ void mma_bf16(float (&d)[4], uint32_t a0, uint32_t a1, uint32_t a2, uint32_t a3, uint32_t b0, uint32_t b1) {
  asm("mma.sync.aligned.m16n8k16.row.col.f32.bf16.bf16.f32 {%0,%1,%2,%3}, {%4,%5,%6,%7}, {%8,%9}, {%0,%1,%2,%3};"
               : "+f"(d[0]), "+f"(d[1]), "+f"(d[2]), "+f"(d[3]) : "r"(a0), "r"(a1), "r"(a2), "r"(a3), "r"(b0), "r"(b1));
}
__device__ __forceinline__ void ldsm_x4(uint32_t& r0, uint32_t& r1, uint32_t& r2, uint32_t& r3, uint32_t addr) {
  asm volatile("ldmatrix.sync.aligned.m8n8.x4.shared.b16 {%0,%1,%2,%3}, [%4];"
               : "=r"(r0), "=r"(r1), "=r"(r2), "=r"(r3) : "r"(addr) : "memory");
}
__device__ __forceinline__ void ldsm_x4_t(uint32_t& r0, uint32_t& r1, uint32_t& r2, uint32_t& r3, uint32_t addr) {
  asm volatile("ldmatrix.sync.aligned.m8n8.x4.trans.shared.b16 {%0,%1,%2,%3}, [%4];"
               : "=r"(r0), "=r"(r1), "=r"(r2), "=r"(r3) : "r"(addr) : "memory");
}
__device__ __forceinline__ void ldsm_x2_t(uint32_t& r0, uint32_t& r1, uint32_t addr) {
  asm volatile("ldmatrix.sync.aligned.m8n8.x2.trans.shared.b16 {%0,%1}, [%2];"
               : "=r"(r0), "=r"(r1) : "r"(addr) : "memory");
}
__device__ __forceinline__ void stsm_x4(uint32_t addr, uint32_t r0, uint32_t r1, uint32_t r2, uint32_t r3) {
  asm volatile("stmatrix.sync.aligned.m8n8.x4.shared.b16 [%0], {%1,%2,%3,%4};"
               ::"r"(addr), "r"(r0), "r"(r1), "r"(r2), "r"(r3) : "memory");
}
__device__ __forceinline__ void stsm_x4_p(bool on, uint32_t addr, uint32_t r0, uint32_t r1, uint32_t r2, uint32_t r3) {
  asm volatile("{\n.reg .pred p;\nsetp.ne.b32 p, %5, 0;\n@p stmatrix.sync.aligned.m8n8.x4.shared.b16 [%0], {%1,%2,%3,%4};\n}\n"
               ::"r"(addr), "r"(r0), "r"(r1), "r"(r2), "r"(r3), "r"((int)on) : "memory");
}
__device__ __forceinline__ float2 lds_f2(uint32_t addr) {
  float2 v; asm volatile("ld.shared.v2.f32 {%0,%1}, [%2];" : "=f"(v.x), "=f"(v.y) : "r"(addr) : "memory"); return v;
}
__device__ __forceinline__ uint4 lds128(uint32_t addr) {
  uint4 v; asm volatile("ld.shared.v4.b32 {%0,%1,%2,%3}, [%4];" : "=r"(v.x), "=r"(v.y), "=r"(v.z), "=r"(v.w) : "r"(addr) : "memory"); return v;
}
__device__ __forceinline__ void sts128(uint32_t addr, uint4 v) {
  asm volatile("st.shared.v4.b32 [%0], {%1,%2,%3,%4};" ::"r"(addr), "r"(v.x), "r"(v.y), "r"(v.z), "r"(v.w) : "memory");
}
__device__ __forceinline__ float lds_f(uint32_t addr) {
  float v; asm volatile("ld.shared.f32 %0, [%1];" : "=f"(v) : "r"(addr) : "memory"); return v;
}
__device__ __forceinline__ uint32_t lds_vol(uint32_t addr) {
  uint32_t v; asm volatile("ld.volatile.shared.u32 %0, [%1];" : "=r"(v) : "r"(addr) : "memory"); return v;
}
__device__ __forceinline__ void sts16(uint32_t addr, uint32_t v) {
  asm volatile("st.shared.u16 [%0], %1;" ::"r"(addr), "h"((unsigned short)v) : "memory");
}
__device__ __forceinline__ void nbar_dyn(int id, int n) { asm volatile("bar.sync %0, %1;" ::"r"(id), "r"(n) : "memory"); }
__device__ __forceinline__ uint64_t make_desc_ns(uint32_t addr, uint32_t lbo_bytes, uint32_t sbo_bytes) {
  return (uint64_t)((addr & 0x3FFFF) >> 4) | ((uint64_t)(lbo_bytes >> 4) << 16) | ((uint64_t)(sbo_bytes >> 4) << 32);
}
__device__ __forceinline__ void sts_f(uint32_t addr, float v) { asm volatile("st.shared.f32 [%0], %1;" ::"r"(addr), "f"(v) : "memory"); }
__device__ __forceinline__ void sts64(uint32_t addr, uint32_t a, uint32_t b) {
  asm volatile("st.shared.v2.b32 [%0], {%1,%2};" ::"r"(addr), "r"(a), "r"(b) : "memory");
}
__device__ __forceinline__ void sts_f2(uint32_t addr, float a, float b) {
  asm volatile("st.shared.v2.f32 [%0], {%1,%2};" ::"r"(addr), "f"(a), "f"(b) : "memory");
}
__device__ __forceinline__ void red_add2(float* p, float a, float b) {
  asm volatile("red.global.add.v2.f32 [%0], {%1,%2};" ::"l"(p), "f"(a), "f"(b) : "memory");
}
__device__ __forceinline__ void red_add4(float* p, float a, float b, float c, float d) {
  asm volatile("red.global.add.v4.f32 [%0], {%1,%2,%3,%4};" ::"l"(p), "f"(a), "f"(b), "f"(c), "f"(d) : "memory");
}
__device__ __forceinline__ void red_add1(float* p, float a) {
  asm volatile("red.global.add.f32 [%0], %1;" ::"l"(p), "f"(a) : "memory");
}
__device__ __forceinline__ void l2_prefetch(const void* p, uint32_t bytes) {
  asm volatile("cp.async.bulk.prefetch.L2.global [%0], %1;" ::"l"(p), "r"(bytes) : "memory");
}

__device__ __forceinline__ void wgmma_n256(float (&d)[192], uint64_t da, uint64_t db, int scale_d) {
  asm volatile("{\n.reg .pred p;\nsetp.ne.b32 p, %130, 0;\n"
    "wgmma.mma_async.sync.aligned.m64n256k16.f32.bf16.bf16 {%0, %1, %2, %3, %4, %5, %6, %7, %8, %9, %10, %11, %12, %13, %14, %15, %16, %17, %18, %19, %20, %21, %22, %23, %24, %25, %26, %27, %28, %29, %30, %31, %32, %33, %34, %35, %36, %37, %38, %39, %40, %41, %42, %43, %44, %45, %46, %47, %48, %49, %50, %51, %52, %53, %54, %55, %56, %57, %58, %59, %60, %61, %62, %63, %64, %65, %66, %67, %68, %69, %70, %71, %72, %73, %74, %75, %76, %77, %78, %79, %80, %81, %82, %83, %84, %85, %86, %87, %88, %89, %90, %91, %92, %93, %94, %95, %96, %97, %98, %99, %100, %101, %102, %103, %104, %105, %106, %107, %108, %109, %110, %111, %112, %113, %114, %115, %116, %117, %118, %119, %120, %121, %122, %123, %124, %125, %126, %127}, %128, %129, p, 1, 1, 0, 1;\n}\n"
    : "+f"(d[0]), "+f"(d[1]), "+f"(d[2]), "+f"(d[3]), "+f"(d[4]), "+f"(d[5]), "+f"(d[6]), "+f"(d[7]), "+f"(d[8]), "+f"(d[9]), "+f"(d[10]), "+f"(d[11]), "+f"(d[12]), "+f"(d[13]), "+f"(d[14]), "+f"(d[15]), "+f"(d[16]), "+f"(d[17]), "+f"(d[18]), "+f"(d[19]), "+f"(d[20]), "+f"(d[21]), "+f"(d[22]), "+f"(d[23]), "+f"(d[24]), "+f"(d[25]), "+f"(d[26]), "+f"(d[27]), "+f"(d[28]), "+f"(d[29]), "+f"(d[30]), "+f"(d[31]), "+f"(d[32]), "+f"(d[33]), "+f"(d[34]), "+f"(d[35]), "+f"(d[36]), "+f"(d[37]), "+f"(d[38]), "+f"(d[39]), "+f"(d[40]), "+f"(d[41]), "+f"(d[42]), "+f"(d[43]), "+f"(d[44]), "+f"(d[45]), "+f"(d[46]), "+f"(d[47]), "+f"(d[48]), "+f"(d[49]), "+f"(d[50]), "+f"(d[51]), "+f"(d[52]), "+f"(d[53]), "+f"(d[54]), "+f"(d[55]), "+f"(d[56]), "+f"(d[57]), "+f"(d[58]), "+f"(d[59]), "+f"(d[60]), "+f"(d[61]), "+f"(d[62]), "+f"(d[63]), "+f"(d[64]), "+f"(d[65]), "+f"(d[66]), "+f"(d[67]), "+f"(d[68]), "+f"(d[69]), "+f"(d[70]), "+f"(d[71]), "+f"(d[72]), "+f"(d[73]), "+f"(d[74]), "+f"(d[75]), "+f"(d[76]), "+f"(d[77]), "+f"(d[78]), "+f"(d[79]), "+f"(d[80]), "+f"(d[81]), "+f"(d[82]), "+f"(d[83]), "+f"(d[84]), "+f"(d[85]), "+f"(d[86]), "+f"(d[87]), "+f"(d[88]), "+f"(d[89]), "+f"(d[90]), "+f"(d[91]), "+f"(d[92]), "+f"(d[93]), "+f"(d[94]), "+f"(d[95]), "+f"(d[96]), "+f"(d[97]), "+f"(d[98]), "+f"(d[99]), "+f"(d[100]), "+f"(d[101]), "+f"(d[102]), "+f"(d[103]), "+f"(d[104]), "+f"(d[105]), "+f"(d[106]), "+f"(d[107]), "+f"(d[108]), "+f"(d[109]), "+f"(d[110]), "+f"(d[111]), "+f"(d[112]), "+f"(d[113]), "+f"(d[114]), "+f"(d[115]), "+f"(d[116]), "+f"(d[117]), "+f"(d[118]), "+f"(d[119]), "+f"(d[120]), "+f"(d[121]), "+f"(d[122]), "+f"(d[123]), "+f"(d[124]), "+f"(d[125]), "+f"(d[126]), "+f"(d[127])
    : "l"(da), "l"(db), "r"(scale_d));
}
__device__ __forceinline__ void wgmma_n128(float (&d)[192], uint64_t da, uint64_t db, int scale_d) {
  asm volatile("{\n.reg .pred p;\nsetp.ne.b32 p, %66, 0;\n"
    "wgmma.mma_async.sync.aligned.m64n128k16.f32.bf16.bf16 {%0, %1, %2, %3, %4, %5, %6, %7, %8, %9, %10, %11, %12, %13, %14, %15, %16, %17, %18, %19, %20, %21, %22, %23, %24, %25, %26, %27, %28, %29, %30, %31, %32, %33, %34, %35, %36, %37, %38, %39, %40, %41, %42, %43, %44, %45, %46, %47, %48, %49, %50, %51, %52, %53, %54, %55, %56, %57, %58, %59, %60, %61, %62, %63}, %64, %65, p, 1, 1, 0, 1;\n}\n"
    : "+f"(d[128]), "+f"(d[129]), "+f"(d[130]), "+f"(d[131]), "+f"(d[132]), "+f"(d[133]), "+f"(d[134]), "+f"(d[135]), "+f"(d[136]), "+f"(d[137]), "+f"(d[138]), "+f"(d[139]), "+f"(d[140]), "+f"(d[141]), "+f"(d[142]), "+f"(d[143]), "+f"(d[144]), "+f"(d[145]), "+f"(d[146]), "+f"(d[147]), "+f"(d[148]), "+f"(d[149]), "+f"(d[150]), "+f"(d[151]), "+f"(d[152]), "+f"(d[153]), "+f"(d[154]), "+f"(d[155]), "+f"(d[156]), "+f"(d[157]), "+f"(d[158]), "+f"(d[159]), "+f"(d[160]), "+f"(d[161]), "+f"(d[162]), "+f"(d[163]), "+f"(d[164]), "+f"(d[165]), "+f"(d[166]), "+f"(d[167]), "+f"(d[168]), "+f"(d[169]), "+f"(d[170]), "+f"(d[171]), "+f"(d[172]), "+f"(d[173]), "+f"(d[174]), "+f"(d[175]), "+f"(d[176]), "+f"(d[177]), "+f"(d[178]), "+f"(d[179]), "+f"(d[180]), "+f"(d[181]), "+f"(d[182]), "+f"(d[183]), "+f"(d[184]), "+f"(d[185]), "+f"(d[186]), "+f"(d[187]), "+f"(d[188]), "+f"(d[189]), "+f"(d[190]), "+f"(d[191])
    : "l"(da), "l"(db), "r"(scale_d));
}
__device__ __forceinline__ void wgmma_n256_k(float (&d)[192], uint64_t da, uint64_t db, int scale_d) {
  asm volatile("{\n.reg .pred p;\nsetp.ne.b32 p, %130, 0;\n"
    "wgmma.mma_async.sync.aligned.m64n256k16.f32.bf16.bf16 {%0, %1, %2, %3, %4, %5, %6, %7, %8, %9, %10, %11, %12, %13, %14, %15, %16, %17, %18, %19, %20, %21, %22, %23, %24, %25, %26, %27, %28, %29, %30, %31, %32, %33, %34, %35, %36, %37, %38, %39, %40, %41, %42, %43, %44, %45, %46, %47, %48, %49, %50, %51, %52, %53, %54, %55, %56, %57, %58, %59, %60, %61, %62, %63, %64, %65, %66, %67, %68, %69, %70, %71, %72, %73, %74, %75, %76, %77, %78, %79, %80, %81, %82, %83, %84, %85, %86, %87, %88, %89, %90, %91, %92, %93, %94, %95, %96, %97, %98, %99, %100, %101, %102, %103, %104, %105, %106, %107, %108, %109, %110, %111, %112, %113, %114, %115, %116, %117, %118, %119, %120, %121, %122, %123, %124, %125, %126, %127}, %128, %129, p, 1, 1, 0, 0;\n}\n"
    : "+f"(d[0]), "+f"(d[1]), "+f"(d[2]), "+f"(d[3]), "+f"(d[4]), "+f"(d[5]), "+f"(d[6]), "+f"(d[7]), "+f"(d[8]), "+f"(d[9]), "+f"(d[10]), "+f"(d[11]), "+f"(d[12]), "+f"(d[13]), "+f"(d[14]), "+f"(d[15]), "+f"(d[16]), "+f"(d[17]), "+f"(d[18]), "+f"(d[19]), "+f"(d[20]), "+f"(d[21]), "+f"(d[22]), "+f"(d[23]), "+f"(d[24]), "+f"(d[25]), "+f"(d[26]), "+f"(d[27]), "+f"(d[28]), "+f"(d[29]), "+f"(d[30]), "+f"(d[31]), "+f"(d[32]), "+f"(d[33]), "+f"(d[34]), "+f"(d[35]), "+f"(d[36]), "+f"(d[37]), "+f"(d[38]), "+f"(d[39]), "+f"(d[40]), "+f"(d[41]), "+f"(d[42]), "+f"(d[43]), "+f"(d[44]), "+f"(d[45]), "+f"(d[46]), "+f"(d[47]), "+f"(d[48]), "+f"(d[49]), "+f"(d[50]), "+f"(d[51]), "+f"(d[52]), "+f"(d[53]), "+f"(d[54]), "+f"(d[55]), "+f"(d[56]), "+f"(d[57]), "+f"(d[58]), "+f"(d[59]), "+f"(d[60]), "+f"(d[61]), "+f"(d[62]), "+f"(d[63]), "+f"(d[64]), "+f"(d[65]), "+f"(d[66]), "+f"(d[67]), "+f"(d[68]), "+f"(d[69]), "+f"(d[70]), "+f"(d[71]), "+f"(d[72]), "+f"(d[73]), "+f"(d[74]), "+f"(d[75]), "+f"(d[76]), "+f"(d[77]), "+f"(d[78]), "+f"(d[79]), "+f"(d[80]), "+f"(d[81]), "+f"(d[82]), "+f"(d[83]), "+f"(d[84]), "+f"(d[85]), "+f"(d[86]), "+f"(d[87]), "+f"(d[88]), "+f"(d[89]), "+f"(d[90]), "+f"(d[91]), "+f"(d[92]), "+f"(d[93]), "+f"(d[94]), "+f"(d[95]), "+f"(d[96]), "+f"(d[97]), "+f"(d[98]), "+f"(d[99]), "+f"(d[100]), "+f"(d[101]), "+f"(d[102]), "+f"(d[103]), "+f"(d[104]), "+f"(d[105]), "+f"(d[106]), "+f"(d[107]), "+f"(d[108]), "+f"(d[109]), "+f"(d[110]), "+f"(d[111]), "+f"(d[112]), "+f"(d[113]), "+f"(d[114]), "+f"(d[115]), "+f"(d[116]), "+f"(d[117]), "+f"(d[118]), "+f"(d[119]), "+f"(d[120]), "+f"(d[121]), "+f"(d[122]), "+f"(d[123]), "+f"(d[124]), "+f"(d[125]), "+f"(d[126]), "+f"(d[127])
    : "l"(da), "l"(db), "r"(scale_d));
}
__device__ __forceinline__ void wgmma_n128_k(float (&d)[192], uint64_t da, uint64_t db, int scale_d) {
  asm volatile("{\n.reg .pred p;\nsetp.ne.b32 p, %66, 0;\n"
    "wgmma.mma_async.sync.aligned.m64n128k16.f32.bf16.bf16 {%0, %1, %2, %3, %4, %5, %6, %7, %8, %9, %10, %11, %12, %13, %14, %15, %16, %17, %18, %19, %20, %21, %22, %23, %24, %25, %26, %27, %28, %29, %30, %31, %32, %33, %34, %35, %36, %37, %38, %39, %40, %41, %42, %43, %44, %45, %46, %47, %48, %49, %50, %51, %52, %53, %54, %55, %56, %57, %58, %59, %60, %61, %62, %63}, %64, %65, p, 1, 1, 0, 0;\n}\n"
    : "+f"(d[128]), "+f"(d[129]), "+f"(d[130]), "+f"(d[131]), "+f"(d[132]), "+f"(d[133]), "+f"(d[134]), "+f"(d[135]), "+f"(d[136]), "+f"(d[137]), "+f"(d[138]), "+f"(d[139]), "+f"(d[140]), "+f"(d[141]), "+f"(d[142]), "+f"(d[143]), "+f"(d[144]), "+f"(d[145]), "+f"(d[146]), "+f"(d[147]), "+f"(d[148]), "+f"(d[149]), "+f"(d[150]), "+f"(d[151]), "+f"(d[152]), "+f"(d[153]), "+f"(d[154]), "+f"(d[155]), "+f"(d[156]), "+f"(d[157]), "+f"(d[158]), "+f"(d[159]), "+f"(d[160]), "+f"(d[161]), "+f"(d[162]), "+f"(d[163]), "+f"(d[164]), "+f"(d[165]), "+f"(d[166]), "+f"(d[167]), "+f"(d[168]), "+f"(d[169]), "+f"(d[170]), "+f"(d[171]), "+f"(d[172]), "+f"(d[173]), "+f"(d[174]), "+f"(d[175]), "+f"(d[176]), "+f"(d[177]), "+f"(d[178]), "+f"(d[179]), "+f"(d[180]), "+f"(d[181]), "+f"(d[182]), "+f"(d[183]), "+f"(d[184]), "+f"(d[185]), "+f"(d[186]), "+f"(d[187]), "+f"(d[188]), "+f"(d[189]), "+f"(d[190]), "+f"(d[191])
    : "l"(da), "l"(db), "r"(scale_d));
}
__device__ __forceinline__ void wgmma_n40_tt(float (&d)[20], uint64_t da, uint64_t db, int scale_d) {
  asm volatile("{\n.reg .pred p;\nsetp.ne.b32 p, %22, 0;\n"
    "wgmma.mma_async.sync.aligned.m64n40k16.f32.bf16.bf16 {%0, %1, %2, %3, %4, %5, %6, %7, %8, %9, %10, %11, %12, %13, %14, %15, %16, %17, %18, %19}, %20, %21, p, 1, 1, 1, 1;\n}\n"
    : "+f"(d[0]), "+f"(d[1]), "+f"(d[2]), "+f"(d[3]), "+f"(d[4]), "+f"(d[5]), "+f"(d[6]), "+f"(d[7]), "+f"(d[8]), "+f"(d[9]), "+f"(d[10]), "+f"(d[11]), "+f"(d[12]), "+f"(d[13]), "+f"(d[14]), "+f"(d[15]), "+f"(d[16]), "+f"(d[17]), "+f"(d[18]), "+f"(d[19])
    : "l"(da), "l"(db), "r"(scale_d));
}
__device__ __forceinline__ void wgmma_n40_rs(float (&d)[20], const uint32_t (&a)[4], uint64_t db, int scale_d) {
  asm volatile("{\n.reg .pred p;\nsetp.ne.b32 p, %25, 0;\n"
    "wgmma.mma_async.sync.aligned.m64n40k16.f32.bf16.bf16 {%0, %1, %2, %3, %4, %5, %6, %7, %8, %9, %10, %11, %12, %13, %14, %15, %16, %17, %18, %19}, {%20, %21, %22, %23}, %24, p, 1, 1, 1;\n}\n"
    : "+f"(d[0]), "+f"(d[1]), "+f"(d[2]), "+f"(d[3]), "+f"(d[4]), "+f"(d[5]), "+f"(d[6]), "+f"(d[7]), "+f"(d[8]), "+f"(d[9]), "+f"(d[10]), "+f"(d[11]), "+f"(d[12]), "+f"(d[13]), "+f"(d[14]), "+f"(d[15]), "+f"(d[16]), "+f"(d[17]), "+f"(d[18]), "+f"(d[19])
    : "r"(a[0]), "r"(a[1]), "r"(a[2]), "r"(a[3]), "l"(db), "r"(scale_d));
}
__device__ __forceinline__ void wgmma_n256_0(float (&d)[192], uint64_t da, uint64_t db) {
  asm volatile("{\n.reg .pred p;\nsetp.ne.b32 p, 0, 0;\n"
    "wgmma.mma_async.sync.aligned.m64n256k16.f32.bf16.bf16 {%0, %1, %2, %3, %4, %5, %6, %7, %8, %9, %10, %11, %12, %13, %14, %15, %16, %17, %18, %19, %20, %21, %22, %23, %24, %25, %26, %27, %28, %29, %30, %31, %32, %33, %34, %35, %36, %37, %38, %39, %40, %41, %42, %43, %44, %45, %46, %47, %48, %49, %50, %51, %52, %53, %54, %55, %56, %57, %58, %59, %60, %61, %62, %63, %64, %65, %66, %67, %68, %69, %70, %71, %72, %73, %74, %75, %76, %77, %78, %79, %80, %81, %82, %83, %84, %85, %86, %87, %88, %89, %90, %91, %92, %93, %94, %95, %96, %97, %98, %99, %100, %101, %102, %103, %104, %105, %106, %107, %108, %109, %110, %111, %112, %113, %114, %115, %116, %117, %118, %119, %120, %121, %122, %123, %124, %125, %126, %127}, %128, %129, p, 1, 1, 0, 1;\n}\n"
    : "=f"(d[0]), "=f"(d[1]), "=f"(d[2]), "=f"(d[3]), "=f"(d[4]), "=f"(d[5]), "=f"(d[6]), "=f"(d[7]), "=f"(d[8]), "=f"(d[9]), "=f"(d[10]), "=f"(d[11]), "=f"(d[12]), "=f"(d[13]), "=f"(d[14]), "=f"(d[15]), "=f"(d[16]), "=f"(d[17]), "=f"(d[18]), "=f"(d[19]), "=f"(d[20]), "=f"(d[21]), "=f"(d[22]), "=f"(d[23]), "=f"(d[24]), "=f"(d[25]), "=f"(d[26]), "=f"(d[27]), "=f"(d[28]), "=f"(d[29]), "=f"(d[30]), "=f"(d[31]), "=f"(d[32]), "=f"(d[33]), "=f"(d[34]), "=f"(d[35]), "=f"(d[36]), "=f"(d[37]), "=f"(d[38]), "=f"(d[39]), "=f"(d[40]), "=f"(d[41]), "=f"(d[42]), "=f"(d[43]), "=f"(d[44]), "=f"(d[45]), "=f"(d[46]), "=f"(d[47]), "=f"(d[48]), "=f"(d[49]), "=f"(d[50]), "=f"(d[51]), "=f"(d[52]), "=f"(d[53]), "=f"(d[54]), "=f"(d[55]), "=f"(d[56]), "=f"(d[57]), "=f"(d[58]), "=f"(d[59]), "=f"(d[60]), "=f"(d[61]), "=f"(d[62]), "=f"(d[63]), "=f"(d[64]), "=f"(d[65]), "=f"(d[66]), "=f"(d[67]), "=f"(d[68]), "=f"(d[69]), "=f"(d[70]), "=f"(d[71]), "=f"(d[72]), "=f"(d[73]), "=f"(d[74]), "=f"(d[75]), "=f"(d[76]), "=f"(d[77]), "=f"(d[78]), "=f"(d[79]), "=f"(d[80]), "=f"(d[81]), "=f"(d[82]), "=f"(d[83]), "=f"(d[84]), "=f"(d[85]), "=f"(d[86]), "=f"(d[87]), "=f"(d[88]), "=f"(d[89]), "=f"(d[90]), "=f"(d[91]), "=f"(d[92]), "=f"(d[93]), "=f"(d[94]), "=f"(d[95]), "=f"(d[96]), "=f"(d[97]), "=f"(d[98]), "=f"(d[99]), "=f"(d[100]), "=f"(d[101]), "=f"(d[102]), "=f"(d[103]), "=f"(d[104]), "=f"(d[105]), "=f"(d[106]), "=f"(d[107]), "=f"(d[108]), "=f"(d[109]), "=f"(d[110]), "=f"(d[111]), "=f"(d[112]), "=f"(d[113]), "=f"(d[114]), "=f"(d[115]), "=f"(d[116]), "=f"(d[117]), "=f"(d[118]), "=f"(d[119]), "=f"(d[120]), "=f"(d[121]), "=f"(d[122]), "=f"(d[123]), "=f"(d[124]), "=f"(d[125]), "=f"(d[126]), "=f"(d[127])
    : "l"(da), "l"(db));
}
__device__ __forceinline__ void wgmma_n128_0(float (&d)[192], uint64_t da, uint64_t db) {
  asm volatile("{\n.reg .pred p;\nsetp.ne.b32 p, 0, 0;\n"
    "wgmma.mma_async.sync.aligned.m64n128k16.f32.bf16.bf16 {%0, %1, %2, %3, %4, %5, %6, %7, %8, %9, %10, %11, %12, %13, %14, %15, %16, %17, %18, %19, %20, %21, %22, %23, %24, %25, %26, %27, %28, %29, %30, %31, %32, %33, %34, %35, %36, %37, %38, %39, %40, %41, %42, %43, %44, %45, %46, %47, %48, %49, %50, %51, %52, %53, %54, %55, %56, %57, %58, %59, %60, %61, %62, %63}, %64, %65, p, 1, 1, 0, 1;\n}\n"
    : "=f"(d[128]), "=f"(d[129]), "=f"(d[130]), "=f"(d[131]), "=f"(d[132]), "=f"(d[133]), "=f"(d[134]), "=f"(d[135]), "=f"(d[136]), "=f"(d[137]), "=f"(d[138]), "=f"(d[139]), "=f"(d[140]), "=f"(d[141]), "=f"(d[142]), "=f"(d[143]), "=f"(d[144]), "=f"(d[145]), "=f"(d[146]), "=f"(d[147]), "=f"(d[148]), "=f"(d[149]), "=f"(d[150]), "=f"(d[151]), "=f"(d[152]), "=f"(d[153]), "=f"(d[154]), "=f"(d[155]), "=f"(d[156]), "=f"(d[157]), "=f"(d[158]), "=f"(d[159]), "=f"(d[160]), "=f"(d[161]), "=f"(d[162]), "=f"(d[163]), "=f"(d[164]), "=f"(d[165]), "=f"(d[166]), "=f"(d[167]), "=f"(d[168]), "=f"(d[169]), "=f"(d[170]), "=f"(d[171]), "=f"(d[172]), "=f"(d[173]), "=f"(d[174]), "=f"(d[175]), "=f"(d[176]), "=f"(d[177]), "=f"(d[178]), "=f"(d[179]), "=f"(d[180]), "=f"(d[181]), "=f"(d[182]), "=f"(d[183]), "=f"(d[184]), "=f"(d[185]), "=f"(d[186]), "=f"(d[187]), "=f"(d[188]), "=f"(d[189]), "=f"(d[190]), "=f"(d[191])
    : "l"(da), "l"(db));
}
__device__ __forceinline__ void wgmma_n64a(float (&d)[192], uint64_t da, uint64_t db, int scale_d) {
  asm volatile("{\n.reg .pred p;\nsetp.ne.b32 p, %34, 0;\n"
    "wgmma.mma_async.sync.aligned.m64n64k16.f32.bf16.bf16 {%0, %1, %2, %3, %4, %5, %6, %7, %8, %9, %10, %11, %12, %13, %14, %15, %16, %17, %18, %19, %20, %21, %22, %23, %24, %25, %26, %27, %28, %29, %30, %31}, %32, %33, p, 1, 1, 0, 1;\n}\n"
    : "+f"(d[128]), "+f"(d[129]), "+f"(d[130]), "+f"(d[131]), "+f"(d[132]), "+f"(d[133]), "+f"(d[134]), "+f"(d[135]), "+f"(d[136]), "+f"(d[137]), "+f"(d[138]), "+f"(d[139]), "+f"(d[140]), "+f"(d[141]), "+f"(d[142]), "+f"(d[143]), "+f"(d[144]), "+f"(d[145]), "+f"(d[146]), "+f"(d[147]), "+f"(d[148]), "+f"(d[149]), "+f"(d[150]), "+f"(d[151]), "+f"(d[152]), "+f"(d[153]), "+f"(d[154]), "+f"(d[155]), "+f"(d[156]), "+f"(d[157]), "+f"(d[158]), "+f"(d[159])
    : "l"(da), "l"(db), "r"(scale_d));
}
__device__ __forceinline__ void wgmma_n64b(float (&d)[192], uint64_t da, uint64_t db, int scale_d) {
  asm volatile("{\n.reg .pred p;\nsetp.ne.b32 p, %34, 0;\n"
    "wgmma.mma_async.sync.aligned.m64n64k16.f32.bf16.bf16 {%0, %1, %2, %3, %4, %5, %6, %7, %8, %9, %10, %11, %12, %13, %14, %15, %16, %17, %18, %19, %20, %21, %22, %23, %24, %25, %26, %27, %28, %29, %30, %31}, %32, %33, p, 1, 1, 0, 1;\n}\n"
    : "+f"(d[160]), "+f"(d[161]), "+f"(d[162]), "+f"(d[163]), "+f"(d[164]), "+f"(d[165]), "+f"(d[166]), "+f"(d[167]), "+f"(d[168]), "+f"(d[169]), "+f"(d[170]), "+f"(d[171]), "+f"(d[172]), "+f"(d[173]), "+f"(d[174]), "+f"(d[175]), "+f"(d[176]), "+f"(d[177]), "+f"(d[178]), "+f"(d[179]), "+f"(d[180]), "+f"(d[181]), "+f"(d[182]), "+f"(d[183]), "+f"(d[184]), "+f"(d[185]), "+f"(d[186]), "+f"(d[187]), "+f"(d[188]), "+f"(d[189]), "+f"(d[190]), "+f"(d[191])
    : "l"(da), "l"(db), "r"(scale_d));
}

constexpr int SLOT = 16384;
constexpr int KVT = 10240;
constexpr uint32_t QA = 0x0BAu, QK = 0x462u, QQ = 0x981u;
constexpr int SM_SD = 12 * SLOT;
constexpr int SM_BAR = SM_SD + 8192;
constexpr int SM_RS = SM_BAR + 512;
constexpr int SM_AP = SM_RS + 768;
constexpr int SM_BP = SM_AP + 2048;
constexpr int SM_WPHI = SM_BP + 12288;
constexpr int SM_EPOCH = SM_WPHI + 10240;
constexpr int SM_TOTAL = SM_EPOCH + 16 + 1024;
constexpr int B_FULLS = 0, B_XOLD = 24, B_STAT = 32, B_EMPTYS = 40, B_FULLT = 256  , B_CONS = 384  , B_E3 = 472, B_E0 = 480, B_E1 = 488, B_E2 = 496, B_EPI = 504, B_CS = 160,
              B_KVDONE = 168  , B_ODONE = 176, B_XDONE = 184, B_OH1 = 192, B_CS2 = 208, B_XH0 = 232, B_R0 = 240, B_XOLD2 = 216, B_FLG = 64  ;
constexpr uint64_t BAR_CNT = 0x1c07fc0eac00a800ull;
constexpr uint64_t WO_A0 = 0xba76218762187643ull, WO_B0 = 0x9540395403ba9021ull, WO_A1 = 0xba713257132576abull, WO_B1 = 0x9506489064890132ull;
constexpr uint64_t WO_DA0 = 0xa9876543210edd00ull, WO_DB0 = 0xa987654321bbccccull, WO_DA1 = 0xa9876543210fff00ull, WO_DB1 = 0xa98765432bbcccddull;
constexpr int XS = 10;

#define PL 2
#define PROFX(i) PROFT(tid_ == 128 && layer == PL, 200 + (i))
#define PSL 20
#define EP 5
#define DRY 0
#define NCOM 3
#define CG0 0
#define CG1 99
#define CPF 0
#define CSLP 128
#define PFS 8
#define KVTH 0x41700000u
#define CSW 1
#define RL 3
#define ORD 1
#define XB2 2
#define QL 0
#define XEP 0
#define PMOD 3
#define SKA 1
#define FL 0
#define NLAYERS 4
constexpr float L2E = 1.4426950408889634f;
#define PHI_MAX 2147483648.f

#define D128(lo) desc64(lo, 0x40000040u)
struct Ctx { uint32_t sb; int g, rb, cu; bf16* out; };

__device__ __forceinline__ void colsum_load(const bf16* __restrict__ w, int rb, int g, int wi, int lane, uint32_t stg, float (&s)[8]) {
  const int ch = wi * 8 + (lane & 7), sec = ch >> 4;
  const bf16* src = w + (size_t)(rb * 64 + (lane >> 3) * 16) * 3072 + (sec == 2 ? 0 : 1024 + sec * 1024) + g * 128 + (ch & 15) * 8;
  stg += lane * 16;
#pragma unroll
  for (int i = 0; i < 8; ++i) s[i] = 0.f;
#pragma unroll
  for (int r = 0; r < 12; ++r)
    asm volatile("cp.async.cg.shared.global [%0], [%1], 16;" ::"r"(stg + r * 512), "l"(src + (size_t)(4 + r) * 3072) : "memory");
  uint4 v[4];
#pragma unroll
  for (int r = 0; r < 4; ++r) v[r] = __ldg(reinterpret_cast<const uint4*>(src + (size_t)r * 3072));
#pragma unroll 1
  for (int r0 = 0;; ++r0) {
#pragma unroll
    for (int r = 0; r < 4; ++r) {
      s[0] += bf_lo(v[r].x); s[1] += bf_hi(v[r].x); s[2] += bf_lo(v[r].y); s[3] += bf_hi(v[r].y);
      s[4] += bf_lo(v[r].z); s[5] += bf_hi(v[r].z); s[6] += bf_lo(v[r].w); s[7] += bf_hi(v[r].w);
    }
    if (r0 == 3) break;
    asm volatile("cp.async.wait_all;" ::: "memory");
#pragma unroll
    for (int r = 0; r < 4; ++r) v[r] = lds128(stg + (r0 * 4 + r) * 512);
  }
#pragma unroll
  for (int i = 0; i < 8; ++i) { s[i] += __shfl_xor_sync(0xffffffffu, s[i], 8); s[i] += __shfl_xor_sync(0xffffffffu, s[i], 16); }
}
__device__ __forceinline__ void colsum_red(float* cs, int g, int wi, int lane, const float (&s)[8]) {
  if (lane < 8) {
    red_add4(cs + g * 384 + (wi * 8 + lane) * 8, s[0], s[1], s[2], s[3]);
    red_add4(cs + g * 384 + (wi * 8 + lane) * 8 + 4, s[4], s[5], s[6], s[7]);
  }
}
#define PHASE_CTX() \
  uint32_t sb = c.sb; asm volatile("" : "+r"(sb)); \
  int tid_ = threadIdx.x; asm volatile("" : "+r"(tid_)); \
  const uint32_t bar = sb + SM_BAR; \
  const int lane = tid_ & 31, cw = (tid_ >> 5) - 4, wg = cw >> 2, wq = cw & 3, gq = lane >> 2, t = lane & 3, wrow0 = cw * 16; \
  const int lrow = (lane & 7) + ((lane >> 3) & 1) * 8, lchk = lane >> 4; \
  const bool elected = (tid_ & 127) == 0; \
  const uint32_t rowo = (wrow0 + lrow) * 128, X = (lchk ^ (lane & 7)) << 4; \
  (void)bar; (void)wq; (void)gq; (void)lrow; (void)lchk; (void)elected; (void)wrow0; (void)wg; (void)rowo; (void)X; (void)t;

__device__ __forceinline__ void slab_out_half(uint32_t slot, bf16* dst, int wrow0, int lane, bool FENCE = false) {
  const int r0 = lane >> 3, ch = lane & 7;
  const uint32_t src = slot + (wrow0 + r0) * 128;
  uint4 v[4];
#pragma unroll
  for (int i = 0; i < 4; ++i) v[i] = lds128(src + i * 512 + (((ch ^ (4 * i + r0)) & 7) << 4));
  if (FENCE) fence_async_smem();
  dst += (size_t)(wrow0 + r0) * D_ + ch * 8;
#pragma unroll
  for (int i = 0; i < 4; ++i) *reinterpret_cast<uint4*>(dst + (size_t)i * 4 * D_) = v[i];
}

template <int O>
__device__ __forceinline__ void phi_proj(float (&p)[2][4][4], const uint32_t (&kq)[64], uint32_t wa) {
#pragma unroll
  for (int h = 0; h < 2; ++h)
#pragma unroll
    for (int i = 0; i < 4; ++i) { p[h][i][0] = p[h][i][1] = p[h][i][2] = p[h][i][3] = 0.f; }
#pragma unroll
  for (int ks = 0; ks < 2; ++ks)
#pragma unroll
    for (int np = 0; np < 2; ++np)
#pragma unroll
      for (int h = 0; h < 2; ++h) {
        uint32_t b0, b1, b2, b3;
        ldsm_x4_t(b0, b1, b2, b3, wa + h * 2560 + ks * 1280 + np * 32);
        mma_bf16(p[h][2 * np], kq[O + 8 * h + 4 * ks], kq[O + 8 * h + 4 * ks + 1], kq[O + 8 * h + 4 * ks + 2], kq[O + 8 * h + 4 * ks + 3], b0, b1);
        mma_bf16(p[h][2 * np + 1], kq[O + 8 * h + 4 * ks], kq[O + 8 * h + 4 * ks + 1], kq[O + 8 * h + 4 * ks + 2], kq[O + 8 * h + 4 * ks + 3], b2, b3);
      }
}
__device__ __forceinline__ void phi_exp(uint32_t (&raw)[4][4], const float (&p)[4][4], float sc0, float sc1) {
#pragma unroll
  for (int i = 0; i < 4; ++i) {
    const float e0 = ex2(p[i][0] * sc0), e1 = ex2(p[i][1] * sc0), e2 = ex2(p[i][2] * sc1), e3 = ex2(p[i][3] * sc1);
    const float m0 = e0 * e1, m1 = e2 * e3, rr = rcp(m0 * m1), r0 = rr * m1, r1 = rr * m0;
    raw[i >> 1][(i & 1) * 2] = pack_bf16(e0, e1);
    raw[i >> 1][(i & 1) * 2 + 1] = pack_bf16(e2, e3);
    raw[2 + (i >> 1)][(i & 1) * 2] = pack_bf16(e1 * r0, e0 * r0);
    raw[2 + (i >> 1)][(i & 1) * 2 + 1] = pack_bf16(e3 * r1, e2 * r1);
  }
}
#define FENCE_P(h) _Pragma("unroll") for (int i_ = 0; i_ < 16; ++i_) asm volatile("" : "+f"(p[h][i_ >> 2][i_ & 3]) :: "memory")
#define FENCE_RAW(h) _Pragma("unroll") for (int i_ = 0; i_ < 16; ++i_) asm volatile("" : "+r"(raw[h][i_ >> 2][i_ & 3]) :: "memory")
template <int O>
__device__ __forceinline__ void phi_norm(uint32_t (&ph)[2][4][4], const uint32_t (&raw)[2][4][4], const uint32_t (&kq)[64], uint32_t wa,
                                         float sc0, float sc1, float mul0, float mul1) {
  bool bad = false;
#pragma unroll
  for (int h = 0; h < 2; ++h)
#pragma unroll
    for (int sg = 0; sg < 2; ++sg) {
      float ss[4] = {0.f, 0.f, 0.f, 0.f};
#pragma unroll
      for (int ks = 0; ks < 2; ++ks)
        mma_bf16(ss, raw[h][2 * sg + ks][0], raw[h][2 * sg + ks][1], raw[h][2 * sg + ks][2], raw[h][2 * sg + ks][3], 0x3F803F80u, 0x3F803F80u);
      bad = bad || !(ss[0] < PHI_MAX) || !(ss[2] < PHI_MAX);
      const uint32_t iv = pack_bf16(rcp(ss[0]) * mul0, rcp(ss[2]) * mul1);
#pragma unroll
      for (int ks = 0; ks < 2; ++ks)
#pragma unroll
        for (int j = 0; j < 4; ++j) ph[h][2 * sg + ks][j] = mul_bf16x2(raw[h][2 * sg + ks][j], iv, j & 1);
    }
  if (__builtin_expect(__any_sync(0xffffffffu, bad), 0)) {
#pragma unroll 1
    for (int it = 0; it < 4; ++it) {
      float q[4][4];
#pragma unroll
      for (int i = 0; i < 4; ++i) { q[i][0] = q[i][1] = q[i][2] = q[i][3] = 0.f; }
#pragma unroll
      for (int ks = 0; ks < 2; ++ks) {
        uint32_t a[4];
#pragma unroll
        for (int j = 0; j < 4; ++j) a[j] = (it & 2) ? kq[O + 8 + 4 * ks + j] : kq[O + 4 * ks + j];
#pragma unroll
        for (int np = 0; np < 2; ++np) {
          uint32_t b0, b1, b2, b3;
          ldsm_x4_t(b0, b1, b2, b3, wa + (it >> 1) * 2560 + ks * 1280 + np * 32);
          mma_bf16(q[2 * np], a[0], a[1], a[2], a[3], b0, b1);
          mma_bf16(q[2 * np + 1], a[0], a[1], a[2], a[3], b2, b3);
        }
      }
      float iv[2];
#pragma unroll
      for (int r = 0; r < 2; ++r) {
        const float sc = (it & 1) ? -(r ? sc1 : sc0) : (r ? sc1 : sc0);
        float mx = -INFINITY, sm = 0.f;
#pragma unroll
        for (int i = 0; i < 8; ++i) { float& v = q[i >> 1][2 * r + (i & 1)]; v *= sc; mx = fmaxf(mx, v); }
        mx = fmaxf(mx, __shfl_xor_sync(0xffffffffu, mx, 1));
        mx = fmaxf(mx, __shfl_xor_sync(0xffffffffu, mx, 2));
#pragma unroll
        for (int i = 0; i < 8; ++i) { float& v = q[i >> 1][2 * r + (i & 1)]; v = ex2(v - mx); sm += v; }
        sm += __shfl_xor_sync(0xffffffffu, sm, 1);
        sm += __shfl_xor_sync(0xffffffffu, sm, 2);
        iv[r] = rcp(sm) * (r ? mul1 : mul0);
      }
#pragma unroll
      for (int i = 0; i < 24; ++i) ph[i >> 4][(i >> 2) & 3][i & 3] = ph[(i + 8) >> 4][((i + 8) >> 2) & 3][i & 3];
#pragma unroll
      for (int i = 0; i < 4; ++i) {
        ph[1][2 + (i >> 1)][(i & 1) * 2] = pack_bf16(q[i][0] * iv[0], q[i][1] * iv[0]);
        ph[1][2 + (i >> 1)][(i & 1) * 2 + 1] = pack_bf16(q[i][2] * iv[1], q[i][3] * iv[1]);
      }
    }
  }
}

__device__ __forceinline__ void stats_out(float s0, float s1, float q0, float q1, float2* dst, int t) {
  const bool od = t & 1;
  float sa = od ? s1 : s0, qa = od ? q1 : q0;
  sa += __shfl_xor_sync(0xffffffffu, od ? s0 : s1, 1);
  qa += __shfl_xor_sync(0xffffffffu, od ? q0 : q1, 1);
  sa += __shfl_xor_sync(0xffffffffu, sa, 2);
  qa += __shfl_xor_sync(0xffffffffu, qa, 2);
  if (t < 2) red_add2(&dst[t * 8].x, sa, qa);
}

__device__ __forceinline__ void consumer(const Ctx& c) {
  const int g = c.g, m0 = c.rb * 128;
  float acc[192];
#define X_H1() \
      _Pragma("unroll") for (int jp = 4; jp < 8; ++jp) \
        stsm_x4(sb + (XS + 1) * SLOT + rowo + (X ^ ((jp & 3) << 5)), \
                pack_bf16(acc[128 + 8 * jp], acc[129 + 8 * jp]), pack_bf16(acc[130 + 8 * jp], acc[131 + 8 * jp]), \
                pack_bf16(acc[132 + 8 * jp], acc[133 + 8 * jp]), pack_bf16(acc[134 + 8 * jp], acc[135 + 8 * jp]));
#pragma unroll
  for (int i = 128; i < 192; ++i) acc[i] = 0.f;
#pragma unroll 1
  for (int layer = 0;; ++layer) {
    {
      PHASE_CTX();
      const uint32_t wu = c.cu >> 2;
      const uint32_t dA0 = (((sb + wu * 8192) & 0x3FFFF) >> 4) | (1u << 16), dB0 = ((sb & 0x3FFFF) >> 4) | (512u << 16);
      {
        PROFX(0);
        mbar_wait(bar + B_FULLS, 0);
        PROFX(1);
        wgmma_fence();
        wgmma_n256_0(acc, D128(dA0 + XS * 1024), D128(dB0 + 2048));
#pragma unroll
        for (int k = 1; k < 4; ++k) wgmma_n256(acc, D128(dA0 + XS * 1024 + k * 2), D128(dB0 + 2048 + k * 128), 1);
        wgmma_commit();
        wgmma_wait<1>();
        float s0 = 0.f, s1 = 0.f, q0 = 0.f, q1 = 0.f;
        if (layer) {
          X_H1();
#pragma unroll
          for (int i = 128; i < 192; i += 4) {
            s0 += acc[i] + acc[i + 1]; s1 += acc[i + 2] + acc[i + 3];
            q0 = fmaf(acc[i], acc[i], fmaf(acc[i + 1], acc[i + 1], q0)); q1 = fmaf(acc[i + 2], acc[i + 2], fmaf(acc[i + 3], acc[i + 3], q1));
          }
        }
        asm volatile("" : "+f"(s0), "+f"(s1), "+f"(q0), "+f"(q1) :: "memory");
        wgmma_fence();
        wgmma_n128_0(acc, D128(dA0 + XS * 1024), D128(dB0 + 1024));
#pragma unroll
        for (int k = 1; k < 4; ++k) wgmma_n128(acc, D128(dA0 + XS * 1024 + k * 2), D128(dB0 + 1024 + k * 128), 1);
        wgmma_commit();
        if (layer) {
          PHASE_CTX();
          fence_async_smem();
          nbar_dyn(3 + wu, 128);
          stats_out(s0, s1, q0, q1, g_stats + layer * S_ + m0 + wrow0 + gq, t);
          PROFT(tid_ == 128, layer * 16 + 8);
        }
      }
      uint32_t s = 1, u = 0, sp = 0;
      const int ix = layer ? 1 : 2 * min(g, NCOM) + 1;
#pragma unroll 1
      for (int i = 1; i < 14; ++i) {
        mbar_wait(bar + B_FULLS + s * 8, (u + (s ? layer : 0)) & 1);
        const uint32_t da = dA0 + ((QA >> (4 * s)) & 15) * 1024, dk = dB0 + ((QK >> (4 * s)) & 15) * 1024,
                       dq = dB0 + ((QQ >> (4 * s)) & 15) * 1024;
        wgmma_fence();
#pragma unroll
        for (int k = 0; k < 4; ++k) {
          wgmma_n256(acc, D128(da + k * 2), D128(dk + k * 128), 1);
          wgmma_n128(acc, D128(da + k * 2), D128(dq + k * 128), 1);
        }
        wgmma_commit();
        if (i == ix || (i == ix + 1 && !layer)) {
          PHASE_CTX();
          if (layer) {
            slab_out_half(sb + (XS + 1) * SLOT, g_x + (size_t)m0 * D_ + g * 128 + 64, wrow0, lane);
          } else {
            float s0 = 0.f, s1 = 0.f, q0 = 0.f, q1 = 0.f;
            const uint32_t xa = sb + ((QA >> (4 * sp)) & 15) * SLOT + rowo;
#pragma unroll
            for (int jp = 0; jp < 4; ++jp) {
              uint32_t x0, x1, x2, x3;
              ldsm_x4(x0, x1, x2, x3, xa + (X ^ (jp << 5)));
              s0 += (bf_lo(x0) + bf_hi(x0)) + (bf_lo(x2) + bf_hi(x2));
              s1 += (bf_lo(x1) + bf_hi(x1)) + (bf_lo(x3) + bf_hi(x3));
              q0 = fmaf(bf_lo(x0), bf_lo(x0), fmaf(bf_hi(x0), bf_hi(x0), fmaf(bf_lo(x2), bf_lo(x2), fmaf(bf_hi(x2), bf_hi(x2), q0))));
              q1 = fmaf(bf_lo(x1), bf_lo(x1), fmaf(bf_hi(x1), bf_hi(x1), fmaf(bf_lo(x3), bf_lo(x3), fmaf(bf_hi(x3), bf_hi(x3), q1))));
            }
            stats_out(s0, s1, q0, q1, g_stats + m0 + wrow0 + gq, t);
          }
          __syncwarp();
          if (lane == 0 && (layer || i != ix)) mbar_arrive(bar + B_XDONE);
          nbar_dyn(3 + wu, 128);
        }
        wgmma_wait<1>();
        if (elected) release2(bar + B_EMPTYS + sp * 8);
        sp = s;
        if (++s == 3) { s = 0; ++u; }
      }
      {
        const uint64_t dap = make_desc_ns(sb + SM_AP + wu * 1024, 0, 128), dbp = make_desc_ns(sb + SM_BP + (layer & 1) * 6144, 0, 128);
        const bool skew = (layer & 1) || SKA;
        if (wu == 0 && skew) {
          wgmma_wait<0>();
          if (elected) mbar_arrive(bar + B_R0);
          nbar<6, 256>();
        }
        if (layer < 2) mbar_wait(bar + (layer ? B_CS2 : B_CS), 0);
        mbar_wait(bar + B_STAT, layer & 1);
        mbar_wait(bar + B_FULLS + 16, layer & 1);
        wgmma_fence();
        wgmma_n256_k(acc, dap, dbp, 1);
#pragma unroll
        for (int k = 0; k < 4; ++k) wgmma_n256(acc, D128(dA0 + (QA >> 8) * 1024 + k * 2), D128(dB0 + (QK >> 8) * 1024 + k * 128), 1);
        mbar_wait(bar + B_FULLS, 1);
        PROFT(tid_ == 128, layer * 16 + 9);
        wgmma_fence();
#pragma unroll
        for (int k = 0; k < 4; ++k) wgmma_n256(acc, D128(dA0 + (QA & 15) * 1024 + k * 2), D128(dB0 + (QK & 15) * 1024 + k * 128), 1);
        wgmma_commit();
        if (wu && skew) nbar<6, 256>();
#define Q_TAIL() \
        wgmma_n128_k(acc, dap, dbp + 256, 1); \
        _Pragma("unroll") for (int k = 0; k < 4; ++k) wgmma_n128(acc, D128(dA0 + (QA >> 8) * 1024 + k * 2), D128(dB0 + (QQ >> 8) * 1024 + k * 128), 1); \
        _Pragma("unroll") for (int k = 0; k < 4; ++k) wgmma_n128(acc, D128(dA0 + (QA & 15) * 1024 + k * 2), D128(dB0 + (QQ & 15) * 1024 + k * 128), 1);
        if (!QL || wu == 0) { Q_TAIL(); }
        wgmma_commit();
        if (QL == 2 && wu == 0) asm volatile("bar.arrive 12, 256;" ::: "memory");
        wgmma_wait<1>();
#pragma unroll
        for (int i = 0; i < 128; ++i) asm volatile("" : "+f"(acc[i]) :: "memory");
      }
    }
    uint32_t xo[32];
    {
      PHASE_CTX();
      PROFT(tid_ == 128, layer * 16 + 1);
      const bool isB = layer & 1;
      const int cu = c.cu;
      const bool skew = isB || SKA;
      if (cu >= 4 && skew) asm volatile("bar.arrive 7, 256;" ::: "memory");
      else if (isB && cu == 0) asm volatile("bar.arrive 10, 64;" ::: "memory");
      if (elected && isB) release2(bar + B_E1);
      if (elected && (cu == 4 || !skew)) mbar_arrive(bar + B_R0);
      uint32_t kq[64];
#pragma unroll
      for (int i = 0; i < 32; ++i) kq[i] = pack_bf16(acc[2 * i], acc[2 * i + 1]);
      const unsigned int epoch = __float_as_uint(lds_f(sb + SM_EPOCH));
      uint4* const hbuf = g_halo + (size_t)((((epoch & 1) * 2 + (layer >> 1)) * 16 + c.rb) * 8 + g) * 512 + lane;
      if (isB && cu == 7) {
#pragma unroll
        for (int jp = 0; jp < 8; ++jp) st_relaxed4(hbuf + jp * 32, ~kq[4 * jp], ~kq[4 * jp + 1], ~kq[4 * jp + 2], ~kq[4 * jp + 3]);
#pragma unroll
        for (int jp = 8; jp < 16; ++jp)
          st_relaxed4(hbuf + jp * 32, ~pack_bf16(acc[8 * jp], acc[8 * jp + 1]), ~pack_bf16(acc[8 * jp + 2], acc[8 * jp + 3]),
                      ~pack_bf16(acc[8 * jp + 4], acc[8 * jp + 5]), ~pack_bf16(acc[8 * jp + 6], acc[8 * jp + 7]));
      }
      const uint32_t rowq = rowo & 8191;
      const uint32_t rB = sb + 4 * SLOT + wg * 4 * KVT + rowq, pA = sb + (3 + 3 * wg) * SLOT + rowq;
      PROFX(13);
      if (cu < 4 || !skew) nbar<7, 256>();
      PROFX(14);
      {
        const uint32_t vb = isB ? rB + KVT + 2048 + wg * 2 * KVT : pA + 2 * SLOT - (rowq >> 1), vst = isB ? (1 - 2 * wg) * 2 * KVT : 8192;
        const uint32_t X0 = isB ? X : (lchk ^ ((lane & 7) >> 1)) << 4, X1 = isB ? X ^ 64 : X0 + 4096;
        const bool dup = isB && cu == 3;
        if (isB) {
#pragma unroll
          for (int jp = 0; jp < 8; ++jp) {
            stsm_x4(vb - KVT + (jp >> 2) * vst + (X ^ ((jp & 3) << 5)), kq[4 * jp], kq[4 * jp + 1], kq[4 * jp + 2], kq[4 * jp + 3]);
            stsm_x4_p(dup, rB + 2048 + 32768 + (1 - (jp >> 2)) * 2 * KVT + (X ^ ((jp & 3) << 5)), kq[4 * jp], kq[4 * jp + 1], kq[4 * jp + 2], kq[4 * jp + 3]);
          }
        }
#pragma unroll
        for (int jp = 8; jp < 16; ++jp) {
          const uint32_t v0 = pack_bf16(acc[8 * jp], acc[8 * jp + 1]), v1 = pack_bf16(acc[8 * jp + 2], acc[8 * jp + 3]),
                         v2 = pack_bf16(acc[8 * jp + 4], acc[8 * jp + 5]), v3 = pack_bf16(acc[8 * jp + 6], acc[8 * jp + 7]);
          const uint32_t ad = vb + ((jp >> 2) & 1) * vst + (((jp & 2) ? X1 : X0) ^ ((jp & 1) << 5));
          stsm_x4(ad, v0, v1, v2, v3);
          stsm_x4_p(dup, ad + 32768 + ((jp & 4) ? -2 * KVT : 2 * KVT), v0, v1, v2, v3);
        }
        if (dup) asm volatile("bar.arrive 9, 64;" ::: "memory");
      }
      const float rs0 = lds_f(sb + SM_RS + (16 + wrow0 + gq) * 4), rs1 = lds_f(sb + SM_RS + (24 + wrow0 + gq) * 4);
      PROFT(tid_ == 128, layer * 16 + 2);
#define Q_DONE() \
      wgmma_wait<0>(); \
      if (lane == 0) release2(bar + B_E0); \
      _Pragma("unroll") for (int i = 128; i < 192; ++i) asm volatile("" : "+f"(acc[i]) :: "memory"); \
      _Pragma("unroll") for (int i = 0; i < 32; ++i) kq[32 + i] = pack_bf16(acc[128 + 2 * i], acc[129 + 2 * i]);
      Q_DONE();
      if (isB) {
        const int e = gq & 1;
        const uint32_t KX = ((lane >> 3) ^ (lane & 7)) << 4;
        float f0[4], f1[4], rj[4];
        uint32_t msk = 0;
#pragma unroll
        for (int nt = 0; nt < 4; ++nt) {
          const int kk = nt * 8 + 2 * t + e;
          const bool okk = (m0 + wrow0 + kk) >= 16;
          const int d0 = kk - gq, d1 = d0 - 8;
          rj[nt] = lds_f(sb + SM_RS + (wrow0 + kk) * 4);
          f0[nt] = rj[nt] * rs0 * (0.17677669529663687f * L2E);
          f1[nt] = rj[nt] * rs1 * (0.17677669529663687f * L2E);
          msk |= (okk && d0 >= 2 && d0 <= 16) ? (1u << nt) : 0u;
          msk |= (okk && d1 >= 2 && d1 <= 16) ? (16u << nt) : 0u;
        }
        if ((cu & 3) == 0) asm volatile("bar.arrive %0, 128;" :: "r"(3 + (cu >> 2)) : "memory");
        if (cu == 0) {
          nbar<11, 64>();
        } else if (cu == 4) {
          uint4 hv[16];
          if (c.rb > 0) {
            uint32_t n = 0;
#pragma unroll 1
            while (true) {
              uint32_t mn = 0xFFFFFFFFu;
#pragma unroll
              for (int i = 0; i < 16; ++i) hv[i] = ld_relaxed4(hbuf - 8 * 512 + i * 32);
#pragma unroll
              for (int i = 0; i < 16; ++i) mn = __vimin3_u32(__vimin3_u32(mn, hv[i].x, hv[i].y), hv[i].z, hv[i].w);
              if (__all_sync(0xffffffffu, mn != 0u)) break;
              if (++n > (1u << 20)) { g_err = 4u; break; }
            }
          } else {
#pragma unroll
            for (int i = 0; i < 16; ++i) hv[i] = make_uint4(~0u, ~0u, ~0u, ~0u);
          }
          nbar<10, 64>();
#pragma unroll
          for (int i = 0; i < 16; ++i)
            stsm_x4(rB - 4 * KVT + (((i >> 2) & 1) * 2 + (i >> 3)) * KVT + (X ^ ((i & 3) << 5)), ~hv[i].x, ~hv[i].y, ~hv[i].z, ~hv[i].w);
          asm volatile("bar.arrive 11, 64;" ::: "memory");
          nbar<9, 64>();
        } else {
          nbar_dyn(3 + (cu >> 2), 128);
        }
        PROFT(tid_ == 128, layer * 16 + 5);
        PROFT(lane == 0 && layer == PL, 136 + cw);
#pragma unroll
        for (int i = 16; i < 32; ++i) xo[i] = 0u;
#pragma unroll 1
        for (int hp = 0; hp < 2; ++hp) {
          const uint32_t qad = sb + (XS + 1 - hp) * SLOT + rowo, kt = rB + 2 * (hp ^ wg) * KVT - (lane & 8) * 128, vt = rB + (2 * (hp ^ wg) + 1) * KVT;
          uint32_t qa[2][8];
#pragma unroll
          for (int i = 0; i < 16; ++i) { qa[i >> 3][i & 7] = kq[32 + i]; kq[32 + i] = kq[48 + i]; }
          float l0[2][4], l1[2][4];
#pragma unroll
          for (int nt = 0; nt < 4; ++nt)
#pragma unroll
            for (int h = 0; h < 2; ++h) {
              float sc[4] = {0.f, 0.f, 0.f, 0.f};
              uint32_t b0, b1, b2, b3;
              ldsm_x4(b0, b1, b2, b3, kt + nt * 1024 + (KX ^ (h << 6)));
              mma_bf16(sc, qa[h][0], qa[h][1], qa[h][2], qa[h][3], b0, b1);
              mma_bf16(sc, qa[h][4], qa[h][5], qa[h][6], qa[h][7], b2, b3);
              l0[h][nt] = (msk >> nt) & 1 ? (e ? sc[1] : sc[0]) * f0[nt] : -1e30f;
              l1[h][nt] = (msk >> (4 + nt)) & 1 ? (e ? sc[3] : sc[2]) * f1[nt] : -1e30f;
            }
          float mx0[2], mx1[2], s0[2], s1[2];
#pragma unroll
          for (int h = 0; h < 2; ++h) {
            mx0[h] = fmaxf(fmaxf(l0[h][0], l0[h][1]), fmaxf(l0[h][2], l0[h][3]));
            mx1[h] = fmaxf(fmaxf(l1[h][0], l1[h][1]), fmaxf(l1[h][2], l1[h][3]));
          }
#pragma unroll
          for (int o = 1; o <= 2; o <<= 1)
#pragma unroll
            for (int h = 0; h < 2; ++h) {
              mx0[h] = fmaxf(mx0[h], __shfl_xor_sync(0xffffffffu, mx0[h], o));
              mx1[h] = fmaxf(mx1[h], __shfl_xor_sync(0xffffffffu, mx1[h], o));
            }
#pragma unroll
          for (int h = 0; h < 2; ++h) {
#pragma unroll
            for (int nt = 0; nt < 4; ++nt) { l0[h][nt] = ex2(l0[h][nt] - mx0[h]); l1[h][nt] = ex2(l1[h][nt] - mx1[h]); }
            s0[h] = (l0[h][0] + l0[h][1]) + (l0[h][2] + l0[h][3]);
            s1[h] = (l1[h][0] + l1[h][1]) + (l1[h][2] + l1[h][3]);
          }
#pragma unroll
          for (int o = 1; o <= 2; o <<= 1)
#pragma unroll
            for (int h = 0; h < 2; ++h) {
              s0[h] += __shfl_xor_sync(0xffffffffu, s0[h], o);
              s1[h] += __shfl_xor_sync(0xffffffffu, s1[h], o);
            }
          uint32_t pl[2][4], phh[2][4];
#pragma unroll
          for (int h = 0; h < 2; ++h) {
            const float i0 = rcp(s0[h]), i1 = rcp(s1[h]);
#pragma unroll
            for (int nt = 0; nt < 4; ++nt) {
              const uint32_t pk = pack_bf16(l0[h][nt] * i0 * rj[nt], l1[h][nt] * i1 * rj[nt]);
              pl[h][nt] = e ? pk << 16 : pk & 0xFFFFu;
              phh[h][nt] = e ? pk & 0xFFFF0000u : pk >> 16;
            }
          }
          float oa[2][4][4];
#pragma unroll
          for (int h = 0; h < 2; ++h)
#pragma unroll
            for (int i = 0; i < 4; ++i) { oa[h][i][0] = oa[h][i][1] = oa[h][i][2] = oa[h][i][3] = 0.f; }
#pragma unroll
          for (int ks = 0; ks < 2; ++ks)
#pragma unroll
            for (int np = 0; np < 2; ++np)
#pragma unroll
              for (int h = 0; h < 2; ++h) {
                uint32_t b0, b1, b2, b3;
                ldsm_x4_t(b0, b1, b2, b3, vt + ks * 2048 + (X ^ (h << 6) ^ (np << 5)));
                mma_bf16(oa[h][2 * np], pl[h][2 * ks], phh[h][2 * ks], pl[h][2 * ks + 1], phh[h][2 * ks + 1], b0, b1);
                mma_bf16(oa[h][2 * np + 1], pl[h][2 * ks], phh[h][2 * ks], pl[h][2 * ks + 1], phh[h][2 * ks + 1], b2, b3);
              }
          if (hp == 0 && lane == 0) release2(bar + B_E3);
          mbar_wait(bar + (hp ? B_XOLD2 : B_XOLD), 1);
#pragma unroll
          for (int i = 0; i < 16; ++i) xo[i] = xo[16 + i];
#pragma unroll
          for (int jp = 0; jp < 4; ++jp) ldsm_x4(xo[16 + 4 * jp], xo[17 + 4 * jp], xo[18 + 4 * jp], xo[19 + 4 * jp], qad + (X ^ (jp << 5)));
#pragma unroll
          for (int h = 0; h < 2; ++h)
#pragma unroll
            for (int np = 0; np < 2; ++np)
              stsm_x4(qad + (X ^ (h << 6) ^ (np << 5)),
                      pack_bf16(oa[h][2 * np][0], oa[h][2 * np][1]), pack_bf16(oa[h][2 * np][2], oa[h][2 * np][3]),
                      pack_bf16(oa[h][2 * np + 1][0], oa[h][2 * np + 1][1]), pack_bf16(oa[h][2 * np + 1][2], oa[h][2 * np + 1][3]));
          {
            __syncwarp();
            slab_out_half(sb + (XS + 1 - hp) * SLOT, g_o + (size_t)m0 * D_ + g * 128 + hp * 64, wrow0, lane, hp && !(FL & 2));
            __syncwarp();
            if (lane == 0) mbar_arrive(bar + (hp ? B_ODONE : B_OH1));
            PROFT(lane == 0 && layer == PL && hp == 0, 128 + cw);
          }
        }
      } else {
        PHASE_CTX();
        const uint32_t pA = sb + (3 + 3 * wg) * SLOT + (rowo & 8191);
        float sc0 = rs0 * L2E, sc1 = rs1 * L2E;
        const uint32_t wa0 = sb + SM_WPHI + lrow * 80 + lchk * 16;
        const uint32_t wu = c.cu >> 2, par = (layer >> 1) & 1;
        float p[2][4][4];
        uint32_t raw[2][4][4], ph[2][4][4];
        float kva[20], oa[2][20];
        auto kv_start = [&](int hp) {
#pragma unroll
          for (int h = 0; h < 2; ++h)
#pragma unroll
            for (int cp = 0; cp < 4; ++cp)
              stsm_x4(pA + hp * 16384 + h * 8192 + (X ^ (cp << 5)), ph[h][cp][0], ph[h][cp][1], ph[h][cp][2], ph[h][cp][3]);
          PROFT(tid_ == 128, layer * 16 + 11);
          fence_async_smem();
          nbar<1, 256>();
          const uint32_t hu = 2 * hp + wu;
          const uint32_t dP = (((sb + 3 * SLOT + hu * 8192) & 0x3FFFF) >> 4) | (512u << 16);
          const uint32_t dV = (((sb + 5 * SLOT + hu * 4096) & 0x3FFFF) >> 4) | (((SM_SD - 5 * SLOT - hu * 4096) >> 4) << 16);
          wgmma_fence();
#pragma unroll
          for (int ks = 0; ks < 8; ++ks)
            wgmma_n40_tt(kva, desc64(dP + (ks >> 2) * 3072 + (ks & 3) * 128, 0x40000040u),
                         desc64(dV + (ks >> 2) * (3072u - (2816u << 16)) + (ks & 3) * 64, 0x80000020u), ks != 0);
          wgmma_commit();
        };
        auto kv_end = [&](int hp) {
          wgmma_wait<0>();
#pragma unroll
          for (int i = 0; i < 20; ++i) asm volatile("" : "+f"(kva[i]) :: "memory");
          nbar_dyn(3 + wu, 128);
          PROFT(tid_ == 128, layer * 16 + 12);
          const bool od = lane & 1;
#pragma unroll
          for (int i = 0; i < 4; ++i)
            sts128(sb + (3 + hp) * SLOT + (cw * 128 + i * 32 + lane) * 16,
                   make_uint4(__float_as_uint(kva[4 * i]), __float_as_uint(kva[4 * i + 1]), __float_as_uint(kva[4 * i + 2]),
                              __float_as_uint(od == (i >= 2) ? 1.f : kva[4 * i + 3])));
          sts128(sb + (6 + hp) * SLOT + wg * 8192 + (wq * 32 + lane) * 16,
                 make_uint4(__float_as_uint(od ? kva[11] : kva[3]), __float_as_uint(od ? kva[15] : kva[7]), __float_as_uint(od ? kva[18] : kva[16]), __float_as_uint(1.f)));
          fence_async_smem();
          __syncwarp();
          if (lane == 0) mbar_arrive(bar + B_KVDONE - hp * 32);
          PROFT(tid_ == 128, layer * 16 + 3);
        };
        const uint4* const kvg = g_kv + (g * 2 + (layer >> 1)) * 2560 + cw * 128 + lane;
        uint4 u[5];
        auto kv_load = [&](int hp) {
#pragma unroll
          for (int i = 0; i < 4; ++i) u[i] = ld_relaxed4(kvg + hp * 1280 + i * 32);
          u[4] = ld_relaxed4(kvg + hp * 1280 + 1024 - cw * 96);
        };
        auto o_start = [&](int hp, const uint32_t (&pq)[2][4][4]) {
          PROFT(tid_ == 128 && hp == 0, layer * 16 + 10);
          if (hp == 0) mbar_wait(bar + B_KVDONE - 32, par);
          const bool od = lane & 1;
          uint32_t n = 0;
#pragma unroll 1
          while (!__all_sync(0xffffffffu, (od ? u[2].w : u[0].w) == 0x41800000u && (od ? u[3].w : u[1].w) == 0x41800000u && u[4].w == 0x41800000u)) {
#pragma unroll 1
            while (__any_sync(0xffffffffu, u[4].w < KVTH) && ++n < (1u << 20)) u[4].w = ld_relaxed(&kvg[hp * 1280 + 1024 - cw * 96].w);
            if (++n > (1u << 20)) { g_err = 6u; break; }
            kv_load(hp);
          }
          PROFT(tid_ == 128 && hp == 0, layer * 16 + 5);
          if (!od) { u[0].w = u[4].x; u[1].w = u[4].y; } else { u[2].w = u[4].x; u[3].w = u[4].y; }
#pragma unroll
          for (int i = 0; i < 4; i += 2)
            stsm_x4(sb + (5 + 3 * hp) * SLOT + rowo + (X ^ ((i & 2) << 4)),
                    pack_bf16(__uint_as_float(u[i].x), __uint_as_float(u[i].y)), pack_bf16(__uint_as_float(u[i].z), __uint_as_float(u[i].w)),
                    pack_bf16(__uint_as_float(u[i + 1].x), __uint_as_float(u[i + 1].y)), pack_bf16(__uint_as_float(u[i + 1].z), __uint_as_float(u[i + 1].w)));
          const uint32_t z2 = pack_bf16(__uint_as_float(u[4].z), __uint_as_float(u[4].z));
          if (t < 2) sts128(sb + (5 + 3 * hp) * SLOT + (wrow0 + gq + 8 * t) * 128 + ((4 ^ gq) << 4), make_uint4(z2, z2, z2, z2));
          fence_async_smem();
          nbar<1, 256>();
          PROFT(tid_ == 128 && hp == 1, layer * 16 + 4);
          const uint32_t dK = (((sb + (5 + 3 * hp) * SLOT) & 0x3FFFF) >> 4) | (512u << 16);
          wgmma_fence();
#pragma unroll
          for (int ks = 0; ks < 4; ++ks) {
#pragma unroll
            for (int hh = 0; hh < 2; ++hh) wgmma_n40_rs(oa[hh], pq[hh][ks], D128(dK + hh * 512 + ks * 128), ks != 0);
          }
          wgmma_commit();
        };
        auto o_end = [&](int hp) {
          wgmma_wait<0>();
#pragma unroll
          for (int i = 0; i < 20; ++i) asm volatile("" : "+f"(oa[0][i]), "+f"(oa[1][i]) :: "memory");
#pragma unroll
          for (int hh = 0; hh < 2; ++hh) {
            const float i0 = rcp(oa[hh][16] + 1e-6f), i1 = rcp(oa[hh][18] + 1e-6f);
            const uint32_t qad = sb + (3 + hp) * SLOT + rowo, hx = hh << 6;
#pragma unroll
            for (int np = 0; np < 2; ++np)
              stsm_x4(qad + (X ^ hx ^ (np << 5)),
                      pack_bf16(oa[hh][8 * np] * i0, oa[hh][8 * np + 1] * i0), pack_bf16(oa[hh][8 * np + 2] * i1, oa[hh][8 * np + 3] * i1),
                      pack_bf16(oa[hh][8 * np + 4] * i0, oa[hh][8 * np + 5] * i0), pack_bf16(oa[hh][8 * np + 6] * i1, oa[hh][8 * np + 7] * i1));
          }
          __syncwarp();
          slab_out_half(sb + (3 + hp) * SLOT, g_o + (size_t)m0 * D_ + g * 128 + hp * 64, wrow0, lane, hp && !(FL & 2));
          __syncwarp();
          if (lane == 0) mbar_arrive(bar + (hp ? B_ODONE : B_OH1));
        };
#define XO_LOAD() \
        mbar_wait(bar + B_XOLD, 0); \
        mbar_wait(bar + B_XOLD2, 0); \
        _Pragma("unroll") for (int jp = 0; jp < 8; ++jp) \
          ldsm_x4(xo[4 * jp], xo[4 * jp + 1], xo[4 * jp + 2], xo[4 * jp + 3], sb + (XS + 1 - (jp >> 2)) * SLOT + rowo + (X ^ ((jp & 3) << 5)));
#define SC_RELOAD() \
        sc0 = __uint_as_float(lds_vol(sb + SM_RS + (16 + wrow0 + gq) * 4)) * L2E; sc1 = __uint_as_float(lds_vol(sb + SM_RS + (24 + wrow0 + gq) * 4)) * L2E;
        __syncwarp();
        phi_proj<0>(p, kq, wa0);
        phi_exp(raw[0], p[0], sc0, sc1);
        phi_exp(raw[1], p[1], sc0, sc1);
        phi_proj<16>(p, kq, wa0 + 5120);
        phi_norm<0>(ph, raw, kq, wa0, sc0, sc1, rs0, rs1);
        kv_start(0);
        phi_exp(raw[0], p[0], sc0, sc1);
        kv_end(0);
        if (RL & 1) { SC_RELOAD(); }
        XO_LOAD();
        phi_exp(raw[1], p[1], sc0, sc1);
        phi_proj<32>(p, kq, wa0);
        phi_norm<16>(ph, raw, kq, wa0 + 5120, sc0, sc1, rs0, rs1);
        kv_start(1);
        if (lane == 0) release2(bar + B_E3);
        phi_exp(raw[0], p[0], sc0, sc1);
        kv_end(1);
        if (RL & 2) { SC_RELOAD(); }
        kv_load(0);
        phi_exp(raw[1], p[1], sc0, sc1);
        phi_proj<48>(p, kq, wa0 + 5120);
        phi_norm<32>(ph, raw, kq, wa0, sc0, sc1, 1.f, 1.f);
        o_start(0, ph);
        phi_exp(raw[0], p[0], sc0, sc1);
        o_end(0);
        SC_RELOAD();
        kv_load(1);
        phi_exp(raw[1], p[1], sc0, sc1);
        phi_norm<48>(ph, raw, kq, wa0 + 5120, sc0, sc1, 1.f, 1.f);
        o_start(1, ph);
        o_end(1);
      }
      __syncwarp();
      if (FL & 2) fence_async_smem();
      PROFT(lane == 0 && layer == PL, 216 + cw);
      if (lane == 0) mbar_arrive(bar + B_EPI);
      PROFT(tid_ == 128, layer * 16 + 6);
    }
    {
      PHASE_CTX();
      const uint32_t wu = c.cu >> 2;
      const uint32_t dA0 = (((sb + wu * 8192) & 0x3FFFF) >> 4) | (1u << 16), dB0 = ((sb & 0x3FFFF) >> 4) | (512u << 16);
#pragma unroll
      for (int i = 0; i < 32; ++i) { acc[128 + 2 * i] = bf_lo(xo[i]); acc[129 + 2 * i] = bf_hi(xo[i]); }
      nbar_dyn(3 + wg, 128);
      uint64_t ta = (layer & 1) ? WO_A1 : WO_A0, tw = (layer & 1) ? WO_B1 : WO_B0;
#pragma unroll 1
      for (int i = 0; i < 16; ++i) {
        bool rel = i > 0 && i < 12;
        if (DRY && rel && !__all_sync(0xffffffffu, mbar_test_wait(bar + B_FULLT + i * 8, layer & 1))) {
          wgmma_wait<0>();
          if (elected) release2(bar + B_CONS + (i - 1) * 8);
          rel = false;
        }
        mbar_wait(bar + B_FULLT + i * 8, layer & 1);
        PROFT(tid_ == 128 && layer == PL, 160 + i);
        const uint32_t da = dA0 + ((uint32_t)ta & 15) * 1024, db = dB0 + ((uint32_t)tw & 15) * 1024;
        ta >>= 4; tw >>= 4;
        wgmma_fence();
#pragma unroll
        for (int k = 0; k < 4; ++k) wgmma_n128(acc, D128(da + k * 2), D128(db + k * 128), 1);
        wgmma_commit();
        if (i == 0) {
          if (elected) {
            release2(bar + B_E2);
          }
        } else {
          wgmma_wait<1>();
          if (elected && rel) release2(bar + B_CONS + (i - 1) * 8);
          if (elected && (unsigned)(i - 13) < 2u && layer + 1 < NLAYERS) release2(bar + B_EMPTYS + (i - 13) * 8);
        }
      }
      const bool last = layer == NLAYERS - 1;
      wgmma_wait<0>();
#pragma unroll
      for (int i = 128; i < 192; ++i) asm volatile("" : "+f"(acc[i]) :: "memory");
      if (elected && !last) release2(bar + B_EMPTYS + 16);
      PROFT(tid_ == 128, layer * 16 + 7);
#pragma unroll
      for (int jp = 0; jp < 4; ++jp)
        stsm_x4(sb + XS * SLOT + rowo + (X ^ (jp << 5)),
                pack_bf16(acc[128 + 8 * jp], acc[129 + 8 * jp]), pack_bf16(acc[130 + 8 * jp], acc[131 + 8 * jp]),
                pack_bf16(acc[132 + 8 * jp], acc[133 + 8 * jp]), pack_bf16(acc[134 + 8 * jp], acc[135 + 8 * jp]));
      if (last) {
        __syncwarp();
        slab_out_half(sb + XS * SLOT, c.out + (size_t)m0 * D_ + g * 128, wrow0, lane);
        X_H1();
        __syncwarp();
        slab_out_half(sb + (XS + 1) * SLOT, c.out + (size_t)m0 * D_ + g * 128 + 64, wrow0, lane);
        __syncwarp();
        if (lane == 0) mbar_arrive(bar + B_XDONE);
        PROFT(tid_ == 128, layer * 16 + 24);
        break;
      }
      __syncwarp();
      slab_out_half(sb + XS * SLOT, g_x + (size_t)m0 * D_ + g * 128, wrow0, lane, !(FL & 1));
      __syncwarp();
      if (lane == 0) mbar_arrive(bar + B_XH0);
      if (FL & 1) fence_async_smem();
      nbar_dyn(3 + wu, 128);
    }
  }
}

__device__ __forceinline__ void flag_fetch(uint32_t bar, uint32_t cp, const unsigned int* f) {
  asm volatile("{\n.reg .pred p;\nelect.sync _|p, 0xffffffff;\n@p mbarrier.expect_tx.relaxed.cta.shared::cta.b64 [%2], 64;\n"
               "@p cp.async.bulk.shared::cluster.global.mbarrier::complete_tx::bytes [%0], [%1], 64, [%2];\n}\n"
               ::"r"(cp), "l"(f), "r"(bar + 128) : "memory");
}
__device__ __forceinline__ void src_wait_async(uint32_t bar, uint32_t cp, const unsigned int* f, unsigned int target, int kb, uint32_t& ready, int lane) {
  uint32_t n = 0;
#pragma unroll 1
  while (true) {
    ready |= __ballot_sync(0xffffffffu, (int)(lds_vol(cp + (lane & 15) * 4) - target) >= 0);
    if ((ready >> kb) & 1) break;
    if (n > (1u << 20)) { g_err = 5u; break; }
    if ((n++ & PMOD) == 0) flag_fetch(bar, cp, f);
    __nanosleep(PSL);
  }
}

__device__ __forceinline__ int kblock0(int i, int g) {
  const int j = i >> 1, p = max(g, NCOM) + j - NCOM;
  return (j < NCOM ? j : p < 8 ? p : p - 8 + NCOM) * 2 + (i & 1);
}

#define WOORD 0xFDB9753ECA864210ull
__device__ __forceinline__ int wo_kblock(int m, int g) { return (2 * g + (int)((WOORD >> (4 * m)) & 15)) & 15; }

__global__ void __cluster_dims__(2, 1, 1) __launch_bounds__(384, 1)
mega_kernel(const __grid_constant__ CUtensorMap tm_x0, const __grid_constant__ CUtensorMap tm_x,
            const __grid_constant__ CUtensorMap tm_o,
            const __grid_constant__ CUtensorMap tm_wA, const __grid_constant__ CUtensorMap tm_wB,
            const __grid_constant__ CUtensorMap tm_woA, const __grid_constant__ CUtensorMap tm_woB,
            const bf16* __restrict__ wA, const bf16* __restrict__ wB,
            const bf16* __restrict__ wphi, bf16* __restrict__ out) {
  extern __shared__ uint8_t smem_raw[];
  const uint32_t sb = (smem_u32(smem_raw) + 1023u) & ~1023u;
  const uint32_t bar = sb + SM_BAR;
  const int warp = __shfl_sync(0xffffffffu, threadIdx.x >> 5, 0), lane = threadIdx.x & 31;
  const int cr = blockIdx.x & 1;
  const int g = (blockIdx.x >> 1) & 7;
  const int rb = (blockIdx.x >> 4) * 2 + cr;
  const int m0 = rb * 128;

  if (warp < 4) {
    asm volatile("setmaxnreg.dec.sync.aligned.u32 40;");
    asm volatile("barrier.cluster.arrive.relaxed.aligned;" ::: "memory");
    const unsigned int epoch = warp ? ld_relaxed(&g_epoch) : 0u;
    if (warp) cluster_wait();
    unsigned int xbase = epoch * NLAYERS;
    const unsigned int cbase = epoch * 16u;
    auto wo_a = [&](int layer) {
      uint64_t ts = ((layer & 1) ? WO_A1 : WO_A0) >> 8, td = ((layer & 1) ? WO_DA1 : WO_DA0) >> 8, tk = WOORD >> 8;
      uint32_t ready = 0u;
#pragma unroll 1
      for (int m = 2; m < 16; ++m) {
        const int kb = (2 * g + (uint32_t)tk) & 15;
        uint32_t dst = sb + ((uint32_t)ts & 15) * SLOT, fb = bar + B_FULLT + m * 8, eb = bar + B_CONS + ((uint32_t)td & 15) * 8;
        int kc = kb * 64;
        ts >>= 4; td >>= 4; tk >>= 4;
        if (!((ready >> kb) & 1)) {
          PROFT(m == 2 && lane == 0, 64 + layer * 16 + 2);
          if (EP && m > EP) src_wait_async(bar, bar + B_FLG, g_of + rb * 32, xbase + layer + 1, kb, ready, lane);
          src_wait<0>(g_of + rb * 32, xbase + layer + 1, 1u << kb, ready, lane);
          fence_async_all();
        }
        asm volatile("" : "+r"(dst), "+r"(fb), "+r"(eb), "+r"(kc));
        mbar_wait_u(eb, layer & 1);
        tma_2d_e(dst, &tm_o, kc, m0, fb);
        if (EP && m >= EP && (ready & 0xFFFFu) != 0xFFFFu) flag_fetch(bar, bar + B_FLG, g_of + rb * 32);
        PROFT(lane == 0 && layer == PL, 176 + m);
      }
    };
    auto wo_w = [&](int layer) {
      const CUtensorMap* tx = layer == 0 ? &tm_x0 : &tm_x;
      const CUtensorMap* two = (layer & 1) ? &tm_woB : &tm_woA;
      uint64_t ts = (layer & 1) ? WO_B1 : WO_B0, td = (layer & 1) ? WO_DB1 : WO_DB0, tk = WOORD;
      uint32_t pb = 0;
      fence_async_all();
      mbar_wait_u(bar + B_R0, layer & 1);
      expect_tx_e(bar + B_XOLD, 16384);
      tma_2d_e(sb + (XS + 1) * SLOT, tx, g * 128, m0, bar + B_XOLD);
#pragma unroll 1
      for (int m = 0; m < 16; ++m) {
        uint32_t dst = sb + ((uint32_t)ts & 15) * SLOT + cr * 8192, fb = bar + B_FULLT + m * 8, eb = bar + B_CONS + ((uint32_t)td & 15) * 8;
        int kc = ((2 * g + (uint32_t)tk) & 15) * 64;
        ts >>= 4; td >>= 4; tk >>= 4;
        asm volatile("" : "+r"(dst), "+r"(fb), "+r"(eb), "+r"(kc));
        if (eb != pb) mbar_wait_u(eb, layer & 1);
        pb = eb;
        tma_2d_mc_e(dst, two, g * 128 + cr * 64, kc, fb);
        expect_tx_e(fb, m < 2 ? 16384 : 32768);
        PROFT(lane == 0 && layer == PL, 144 + m);
        if (m == ((layer & 1) ? XB2 : 0)) {
          expect_tx_e(bar + B_XOLD2, 16384);
          tma_2d_e(sb + XS * SLOT, tx, g * 128 + 64, m0, bar + B_XOLD2);
        }
      }
    };
    if (warp == 0) {
      cluster_wait();
      PROFT(lane == 0, 125);
#pragma unroll 1
      for (int layer = 0; layer < NLAYERS; ++layer) {
        const CUtensorMap* tx = layer == 0 ? &tm_x0 : &tm_x;
        const CUtensorMap* tw = (layer & 1) ? &tm_wB : &tm_wA;
        uint32_t s = layer == 0, u = 0, ready = layer == 0 ? 0xFFFFu : 0u;
#pragma unroll 1
        for (int i = s; i < 16; ++i) {
          const int kb = layer == 0 ? kblock0(i, g) : wo_kblock(i, g), kc = kb * 64;
          const uint32_t fb = bar + B_FULLS + s * 8;
          const uint32_t kd = sb + (((QK >> (4 * s)) & 15) + cr) * SLOT, qd = sb + ((QQ >> (4 * s)) & 15) * SLOT + cr * 8192;
          const uint32_t need = 1u << kb;
          const bool ext = i >= 2 || layer == 0, early = ext && (ready & need) == need;
          mbar_wait_u(bar + B_EMPTYS + s * 8, (u + (s ? layer : 0) + 1) & 1);
          if (early) tma_2d_e(sb + ((QA >> (4 * s)) & 15) * SLOT, tx, kc, m0, fb);
          tma_2d_mc_e(kd, tw, 1024 + cr * 1024 + g * 128, kc, fb);
          tma_2d_mc_e(kd + 8192, tw, 1024 + cr * 1024 + g * 128 + 64, kc, fb);
          tma_2d_mc_e(qd, tw, g * 128 + cr * 64, kc, fb);
          expect_tx_e(fb, ext ? 65536 : 49152);
          PROFT(lane == 0 && layer == 0 && i == 1, 31);
          if (layer == 0 && i == 2) {
            mbar_wait_u(bar + B_FULLS, 0);
            tma_pf_e(&tm_x0, g * 128, m0);
            tma_pf_e(&tm_x0, g * 128 + 64, m0);
          }
          if (layer < 2 && i >= PFS) {
            const int j = i - PFS;
            if (j < 2) tma_pf_e(layer ? &tm_woB : &tm_woA, g * 128 + j * 64, rb * 64);
            else if (j < 8 && layer == 0) tma_pf_e(&tm_wB, ((j >> 1) - 1) * 1024 + g * 128 + (j & 1) * 64, rb * 64);
          }
          if (ext && !early) {
            PROFT(i == 2 && lane == 0, 64 + layer * 16 + 0);
            if (XEP) src_wait_async(bar, sb + SM_RS + 640, g_xf + rb * 32, xbase + layer + 1, kb, ready, lane);
            else src_wait<0>(g_xf + rb * 32, xbase + layer + 1, need, ready, lane);
            PROFT(i == 2 && lane == 0, 64 + layer * 16 + 1);
            fence_async_all();
            tma_2d_e(sb + ((QA >> (4 * s)) & 15) * SLOT, tx, kc, m0, fb);
          }
          if (++s == 3) { s = 0; ++u; }
        }
        if (layer == 0) xbase = ld_relaxed(&g_epoch) * NLAYERS;
        wo_a(layer);
      }
    } else {
      if (warp >= 2) {
        const int h2 = threadIdx.x - 64;
#pragma unroll 1
        for (int i = h2; i < 512; i += 64)
          asm volatile("cp.async.cg.shared.global [%0], [%1], 16;" ::"r"(sb + SM_WPHI + (i >> 2) * 80 + (i & 3) * 16), "l"(wphi + (size_t)g * 4096 + i * 8) : "memory");
        if (h2 < 16) sts_f(sb + SM_RS + h2 * 4, 0.f);
        if (h2 < 32) sts_f((h2 < 16 ? bar + B_FLG : sb + SM_RS + 576) + h2 * 4, __uint_as_float(xbase));
        if (h2 == 0) sts_f(sb + SM_EPOCH, __uint_as_float(epoch));
        if (rb >= CG0) mbar_wait_u(bar + B_FULLS + (rb >= CG1 ? 8 : 0), 0);
        if (CPF && h2 < 4) asm volatile("cp.async.bulk.prefetch.tensor.2d.L2.global.tile [%0, {%1, %2}];" ::"l"(&tm_wA), "r"((h2 & 2) * 1024 + g * 128 + (h2 & 1) * 64), "r"(rb * 64) : "memory");
#pragma unroll 1
        for (int wi = 0; wi < 3; ++wi) {
          float sA[8];
          colsum_load(wA, rb, g, warp - 2 + 2 * wi, lane, sb + SM_BP + (warp - 2) * 6144, sA);
          colsum_red(g_cs + (epoch & 1) * 6144, g, warp - 2 + 2 * wi, lane, sA);
        }
#pragma unroll 1
        for (int i = h2; i < 320; i += 64) g_kv[(g * 16 + rb) * 320 + i] = make_uint4(0u, 0u, 0u, 0u);
        fence_async_all();
        nbar<5, 64>();
        if (h2 == 0) flag_add(&g_csflag[g].v);
        PROFT(h2 == 0, 242);
      }
      if (warp == 1) {
        if (lane >= 27) {
          const CUtensorMap* tm = lane == 27 ? &tm_o : lane == 28 ? &tm_wB : lane == 29 ? &tm_woA : lane == 30 ? &tm_woB : &tm_x;
          asm volatile("prefetch.tensormap [%0];" ::"l"(tm) : "memory");
        }
        if (lane == 0) {
#pragma unroll 1
          for (int e = 0;; ++e) {
            if (e > 0 && e < NLAYERS) {
              mbar_wait(bar + B_XH0, (e - 1) & 1);
              flag_set(g_xf + rb * 32 + 2 * g, xbase + e + 1);
            }
            mbar_wait(bar + B_XDONE, e & 1);
            PROFT(e < 4, 64 + e * 16 + 4);
            if (e == NLAYERS) {
              if (blockIdx.x == 0) g_epoch = epoch + 1;
              break;
            }
            PROFT(e < 4, 64 + e * 16 + 5);
            flag_set(g_xf + rb * 32 + 2 * g + 1, xbase + e + 1);
            PROFT(e < 4, 64 + e * 16 + 7);
            if ((e & 1) == 0) {
#pragma unroll 1
              for (int hp = 0; hp < 2; ++hp) {
                uint4* kvl = g_kv + ((g * 2 + (e >> 1)) * 2 + hp) * 1280;
                mbar_wait(bar + B_KVDONE - hp * 32, (e >> 1) & 1);
                PROFT(e == PL, 243 + hp * 4);
                bulk_red_add(kvl + rb * 64, sb + (3 + hp) * SLOT + rb * 1024, 16384 - rb * 1024);
                if (rb) bulk_red_add(kvl, sb + (3 + hp) * SLOT, rb * 1024);
                bulk_red_add(kvl + 1024, sb + (6 + hp) * SLOT, 2048);
                bulk_red_add(kvl + 1152, sb + (6 + hp) * SLOT + 8192, 2048);
                bulk_commit();
                PROFT(e < 4, 64 + e * 16 + 6);
              }
              bulk_wait_read0();
              release2(bar + B_E1);
              release2(bar + B_E1);
            }
            mbar_wait(bar + B_OH1, e & 1);
            PROFT(e == PL, 251);
            flag_set(g_of + rb * 32 + 2 * g, xbase + e + 1);
            PROFT(e < 4, 64 + e * 16 + 9);
            mbar_wait(bar + B_ODONE, e & 1);
            PROFT(e < 4, 64 + e * 16 + 8);
            flag_set(g_of + rb * 32 + 2 * g + 1, xbase + e + 1);
            PROFT(e < 4, 64 + e * 16 + 11);
          }
        }
      } else {
        const int h2 = threadIdx.x - 64;
        const float* cs = g_cs + (epoch & 1) * 6144;
#pragma unroll 1
        for (int layer = 0; layer < NLAYERS; ++layer) {
          if (warp == 2 && layer < 2) {
            if (lane == 0) flag_wait_t<CSLP>(&g_csflag[layer * 8 + g].v, cbase + 16u);
            __syncwarp();
            float4 a[3];
#pragma unroll
            for (int i = 0; i < 3; ++i) a[i] = __ldcg(reinterpret_cast<const float4*>(cs + layer * 3072 + g * 384) + i * 32 + lane);
#pragma unroll 1
            for (int i = 0; i < 3; ++i) {
              const float av[4] = {a[0].x, a[0].y, a[0].z, a[0].w};
              a[0] = a[1]; a[1] = a[2];
#pragma unroll
              for (int j = 0; j < 4; ++j) {
                const float c1 = bf16r(av[j]), c2 = bf16r(av[j] - c1), c3 = (av[j] - c1) - c2;
                sts128(sb + SM_BP + layer * 6144 + ((i * 32 + lane) * 4 + j) * 16, make_uint4(pack_bf16(c1, c2), pack_bf16(c3, 0.f), 0u, 0u));
              }
            }
            fence_async_smem();
            __syncwarp();
            if (lane == 0) mbar_arrive(bar + (layer ? B_CS2 : B_CS));
            PROFT(lane == 0, 64 + layer * 16 + 12);
            if (layer == 0) {
              uint4* hz = g_halo + (size_t)((epoch & 1) ^ 1) * (2 * 128 * 512) + blockIdx.x * 1024;
#pragma unroll 2
              for (int i = lane; i < 1024; i += 32) hz[i] = make_uint4(0u, 0u, 0u, 0u);
              if (lane < 12) reinterpret_cast<float4*>(g_cs + ((epoch & 1) ^ 1) * 6144 + blockIdx.x * 48)[lane] = make_float4(0.f, 0.f, 0.f, 0.f);
              g_stats[(2 + (lane >> 4)) * S_ + m0 + g * 16 + (lane & 15)] = make_float2(0.f, 0.f);
            }
          }
          if (warp == 3) {
            const bool hal = (layer & 1) && rb > 0;
            {
              uint32_t rdy = 0u;
              src_wait<256>(g_xf + rb * 32, xbase + layer + 1, 0xAAAAu, rdy, lane);
              rdy = 0u;
              if (hal) src_wait<256>(g_xf + (rb - 1) * 32, xbase + layer + 1, 0xAAAAu, rdy, lane);
            }
            float2 u[5];
            const float2* sp = g_stats + layer * S_ + m0 + lane;
#pragma unroll
            for (int i = 0; i < 4; ++i) u[i] = __ldcg(sp + i * 32);
            u[4] = __ldcg(hal ? sp - 16 : sp);
            if (layer == 3) g_stats[(lane >> 4) * S_ + m0 + g * 16 + (lane & 15)] = make_float2(0.f, 0.f);
#pragma unroll 1
            for (int i = 0; i < (hal ? 5 : 4); ++i) {
              const int r = i < 4 ? 16 + i * 32 + lane : lane;
              const float sum = u[0].x, sq = u[0].y;
              u[0] = u[1]; u[1] = u[2]; u[2] = u[3]; u[3] = u[4];
              const float mean = sum * (1.f / D_);
              const float var = fmaxf(fmaf(-sum, mean, sq) * (1.f / D_), 0.f);
              const float sd = bf16r(sqrtf(bf16r(bf16r(var) + 1e-5f)));
              sts_f(sb + SM_RS + r * 4, 1.f / sd);
              if (i < 4) {
                const float hm = -0.5f * bf16r(mean);
                const uint32_t s2 = pack_bf16(sd, sd);
                sts128(sb + SM_SD + (r - 16) * 64 + ((r >> 1) & 3) * 16, make_uint4(s2, s2, s2, s2));
                sts128(sb + SM_AP + (r - 16) * 16, make_uint4(pack_bf16(hm, hm), pack_bf16(hm, 0.f), 0u, 0u));
              }
            }
            fence_async_smem();
            __syncwarp();
            if (lane == 0) mbar_arrive(bar + B_STAT);
            PROFT(lane == 0, 64 + layer * 16 + 14);
            wo_w(__shfl_sync(0xffffffffu, layer, 0));
          }
          if (layer == 0 && warp == 2) {
            if (CSW) mbar_wait_u(bar + (CSW == 1 ? B_E0 : CSW == 2 ? B_OH1 : B_ODONE), 0);
#pragma unroll 1
            for (int wi = 0; wi < 6; ++wi) {
              float sB[8];
              colsum_load(wB, rb, g, wi, lane, sb + SM_BP + 6144, sB);
              colsum_red(g_cs + (epoch & 1) * 6144 + 3072, g, wi, lane, sB);
            }
            __syncwarp();
            if (lane == 0) flag_add(&g_csflag[8 + g].v);
            PROFT(h2 == 0, 64 + 13);
          }
        }
      }
    }
    __syncwarp();
    asm volatile("barrier.cluster.arrive.relaxed.aligned;\nbarrier.cluster.wait.aligned;\n" ::: "memory");
  } else {
    if (warp == 5) {
      if (lane == 0) {
        mbar_init(bar + B_FULLS, 1);
        asm volatile("fence.mbarrier_init.release.cluster;" ::: "memory");
      }
      __syncwarp();
      expect_tx_e(bar + B_FULLS, 65536);
      tma_2d_e(sb + XS * SLOT, &tm_x0, 0, m0, bar + B_FULLS);
#pragma unroll
      for (int j = 0; j < 6; ++j)
        tma_2d_e(sb + (j < 4 ? j + 4 : j - 2) * 8192, &tm_wA, (j < 4 ? 1024 + (j >> 1) * 1024 : 0) + g * 128 + (j & 1) * 64, 0, bar + B_FULLS);
      PROFT(lane == 0, 241);
    }
    if (lane < 8 && warp != 5 && threadIdx.x != 128) {
      const int i = (warp - 4) * 8 + lane;
      mbar_init(bar + i * 8, i < 32 ? 1u << ((BAR_CNT >> (2 * i)) & 3) : i < 48 ? 1u : (i == 59 || i == 60) ? 16u : i < 63 ? 4u : 8u);
      asm volatile("fence.mbarrier_init.release.cluster;" ::: "memory");
    }
    __syncwarp();
    asm volatile("barrier.cluster.arrive.relaxed.aligned;" ::: "memory");
    asm volatile("setmaxnreg.inc.sync.aligned.u32 232;");
    cluster_wait();
    PROFT(threadIdx.x == 128, 0);
    Ctx c; c.sb = sb; c.g = g; c.rb = rb; c.cu = warp - 4; c.out = out;
    consumer(c);
    asm volatile("bar.warp.sync 0xffffffff;\nbarrier.cluster.arrive.relaxed.aligned;\nbarrier.cluster.wait.aligned;\n" ::: "memory");
  }
}

typedef CUresult (*PFN_encodeTiled)(CUtensorMap*, CUtensorMapDataType, cuuint32_t, void*, const cuuint64_t*, const cuuint64_t*,
                                    const cuuint32_t*, const cuuint32_t*, CUtensorMapInterleave, CUtensorMapSwizzle,
                                    CUtensorMapL2promotion, CUtensorMapFloatOOBfill);

static CUtensorMap make_map(PFN_encodeTiled enc, const void* ptr, uint64_t cols, uint64_t rows, uint32_t box_c, uint32_t box_r, uint32_t nb = 1) {
  CUtensorMap m;
  cuuint64_t dims[3] = {nb > 1 ? box_c : cols, rows, cols / box_c};
  cuuint64_t strides[2] = {cols * 2, box_c * 2};
  cuuint32_t box[3] = {box_c, box_r, nb};
  cuuint32_t es[3] = {1, 1, 1};
  CUresult r = enc(&m, CU_TENSOR_MAP_DATA_TYPE_BFLOAT16, nb > 1 ? 3 : 2, const_cast<void*>(ptr), dims, strides, box, es, CU_TENSOR_MAP_INTERLEAVE_NONE,
      CU_TENSOR_MAP_SWIZZLE_128B, CU_TENSOR_MAP_L2_PROMOTION_L2_256B, CU_TENSOR_MAP_FLOAT_OOB_FILL_NONE);
  (void)r;
  return m;
}

extern "C" void kernel_launch(void* const* d_in, const int* in_sizes, int n_in, void* d_out, int out_size) {
  const bf16* A_x = (const bf16*)d_in[0];
  const bf16* A_wqkv = (const bf16*)d_in[1];
  const bf16* A_wphi = (const bf16*)d_in[2];
  const bf16* A_wo = (const bf16*)d_in[3];
  const bf16* B_wqkv = (const bf16*)d_in[5];
  const bf16* B_wo = (const bf16*)d_in[6];
  bf16* out = (bf16*)d_out;

  static PFN_encodeTiled enc = nullptr;
  static bf16 *p_x, *p_o;
  if (!enc) {
    void* fn = nullptr; cudaDriverEntryPointQueryResult qr;
    cudaGetDriverEntryPoint("cuTensorMapEncodeTiled", &fn, cudaEnableDefault, &qr);
    enc = (PFN_encodeTiled)fn;
    cudaGetSymbolAddress((void**)&p_x, g_x);
    cudaGetSymbolAddress((void**)&p_o, g_o);
    cudaFuncSetAttribute(mega_kernel, cudaFuncAttributeMaxDynamicSharedMemorySize, SM_TOTAL);
  }
  CUtensorMap tm_x0 = make_map(enc, A_x, 1024, 2048, 64, 128);
  CUtensorMap tm_x = make_map(enc, p_x, 1024, 2048, 64, 128);
  CUtensorMap tm_o = make_map(enc, p_o, 1024, 2048, 64, 128);
  CUtensorMap tm_wA = make_map(enc, A_wqkv, 3072, 1024, 64, 64);
  CUtensorMap tm_wB = make_map(enc, B_wqkv, 3072, 1024, 64, 64);
  CUtensorMap tm_woA = make_map(enc, A_wo, 1024, 1024, 64, 64);
  CUtensorMap tm_woB = make_map(enc, B_wo, 1024, 1024, 64, 64);
  mega_kernel<<<128, 384, SM_TOTAL, cudaStreamPerThread>>>(tm_x0, tm_x, tm_o, tm_wA, tm_wB, tm_woA, tm_woB,
                                                           A_wqkv, B_wqkv, A_wphi, out);
}
```

```cpp
#include <cuda_runtime.h>
#include <cuda_bf16.h>
#include <cuda.h>
#include <stdint.h>

typedef __nv_bfloat16 bf16;

constexpr int S_ = 2048, D_ = 1024;

struct __align__(128) Flag { unsigned int v; unsigned int pad[31]; };
__device__ __align__(1024) bf16 g_x[S_ * D_];
__device__ __align__(1024) bf16 g_o[S_ * D_];
__device__ __align__(1024) uint4 g_halo[128 * 2 * 512];
__device__ __align__(1024) uint4 g_kv[8 * 2 * 2 * 1280];
__device__ __align__(1024) float2 g_stats[4 * S_];
__device__ __align__(1024) float g_cs[2 * 2 * 3072];
__device__ Flag g_csflag[16];
__device__ __align__(128) unsigned int g_xf[16 * 32], g_of[16 * 32];
__device__ unsigned int g_epoch, g_err;
#define PROFT(cond, idx) asm volatile("" ::: "memory")

__device__ __forceinline__ uint32_t smem_u32(const void* p) { return (uint32_t)__cvta_generic_to_shared(p); }
__device__ __forceinline__ void mbar_init(uint32_t bar, uint32_t count) {
  asm volatile("mbarrier.init.shared::cta.b64 [%0], %1;" ::"r"(bar), "r"(count) : "memory");
}
__device__ __forceinline__ void mbar_expect_tx(uint32_t bar, uint32_t bytes) {
  asm volatile("mbarrier.arrive.expect_tx.shared::cta.b64 _, [%0], %1;" ::"r"(bar), "r"(bytes) : "memory");
}
__device__ __forceinline__ void mbar_arrive(uint32_t bar) {
  asm volatile("mbarrier.arrive.shared::cta.b64 _, [%0];" ::"r"(bar) : "memory");
}
__device__ __forceinline__ bool mbar_try_wait(uint32_t bar, uint32_t parity) {
  uint32_t ok;
  asm volatile("{\n.reg .pred p;\nmbarrier.try_wait.parity.shared::cta.b64 p, [%1], %2;\nselp.b32 %0, 1, 0, p;\n}\n"
               : "=r"(ok) : "r"(bar), "r"(parity) : "memory");
  return ok != 0;
}
__device__ __forceinline__ bool mbar_test_wait(uint32_t bar, uint32_t parity) {
  uint32_t ok;
  asm volatile("{\n.reg .pred p;\nmbarrier.test_wait.parity.shared::cta.b64 p, [%1], %2;\nselp.b32 %0, 1, 0, p;\n}\n"
               : "=r"(ok) : "r"(bar), "r"(parity) : "memory");
  return ok != 0;
}
__device__ __forceinline__ uint64_t gtimer() {
  uint64_t t; asm volatile("mov.u64 %0, %globaltimer;" : "=l"(t)); return t;
}
__device__ __forceinline__ void mbar_wait(uint32_t bar, uint32_t parity) {
  uint32_t n = 0;
#pragma unroll 1
  while (!mbar_try_wait(bar, parity)) {
    if (++n > (1u << 22)) { g_err = 1u; break; }
  }
}
__device__ __forceinline__ unsigned int ld_acquire(const unsigned int* p) {
  unsigned int v; asm volatile("ld.acquire.gpu.global.u32 %0, [%1];" : "=r"(v) : "l"(p) : "memory"); return v;
}
__device__ __forceinline__ void flag_add(unsigned int* p) {
  asm volatile("red.release.gpu.global.add.u32 [%0], 1;" ::"l"(p) : "memory");
}
__device__ __forceinline__ void flag_set(unsigned int* p, unsigned int v) {
  asm volatile("st.release.gpu.global.u32 [%0], %1;" ::"l"(p), "r"(v) : "memory");
}
template <int SLEEP>
__device__ __forceinline__ void src_wait(const unsigned int* f, unsigned int target, uint32_t need, uint32_t& ready, int lane) {
  uint32_t n = 0;
#pragma unroll 1
  while ((ready & need) != need) {
    const unsigned int v = ld_acquire(f + (lane & 15));
    ready = __ballot_sync(0xffffffffu, (int)(v - target) >= 0);
    if (SLEEP) { if ((ready & need) != need) __nanosleep(SLEEP); }
    if (++n > (1u << 20)) { g_err = 3u; break; }
  }
  __syncwarp();
}
__device__ __forceinline__ unsigned int ld_relaxed(const unsigned int* p) {
  unsigned int v; asm volatile("ld.relaxed.gpu.global.u32 %0, [%1];" : "=r"(v) : "l"(p) : "memory"); return v;
}
__device__ __forceinline__ uint4 ld_relaxed4(const uint4* p) {
  uint4 v; asm volatile("ld.relaxed.gpu.global.v4.u32 {%0,%1,%2,%3}, [%4];" : "=r"(v.x), "=r"(v.y), "=r"(v.z), "=r"(v.w) : "l"(p) : "memory"); return v;
}
__device__ __forceinline__ void st_relaxed4(uint4* p, uint32_t a, uint32_t b, uint32_t c, uint32_t d) {
  asm volatile("st.relaxed.gpu.global.v4.u32 [%0], {%1,%2,%3,%4};" ::"l"(p), "r"(a), "r"(b), "r"(c), "r"(d) : "memory");
}
template <int SLEEP>
__device__ __forceinline__ void flag_wait_t(const unsigned int* p, unsigned int target) {
  uint32_t n = 0;
#pragma unroll 1
  while ((int)(ld_acquire(p) - target) < 0) {
    if (SLEEP) __nanosleep(SLEEP);
    if (++n > (1u << 20)) { g_err = 2u; break; }
  }
}
__device__ __forceinline__ void flag_wait(const unsigned int* p, unsigned int target) { flag_wait_t<0>(p, target); }
__device__ __forceinline__ void flag_wait_slow(const unsigned int* p, unsigned int target) { flag_wait_t<256>(p, target); }
__device__ __forceinline__ void tma_load_2d(uint32_t dst, const CUtensorMap* tm, int c0, int c1, uint32_t bar) {
  asm volatile("cp.async.bulk.tensor.2d.shared::cluster.global.mbarrier::complete_tx::bytes [%0], [%1, {%2, %3}], [%4];"
               ::"r"(dst), "l"(tm), "r"(c0), "r"(c1), "r"(bar) : "memory");
}
__device__ __forceinline__ void tma_load_2d_mc(uint32_t dst, const CUtensorMap* tm, int c0, int c1, uint32_t bar, uint16_t mask) {
  asm volatile("cp.async.bulk.tensor.2d.shared::cluster.global.mbarrier::complete_tx::bytes.multicast::cluster [%0], [%1, {%2, %3}], [%4], %5;"
               ::"r"(dst), "l"(tm), "r"(c0), "r"(c1), "r"(bar), "h"(mask) : "memory");
}
__device__ __forceinline__ void mbar_wait_u(uint32_t bar, uint32_t parity) {
  uint32_t n = 0;
#pragma unroll 1
  while (!__all_sync(0xffffffffu, mbar_try_wait(bar, parity))) {
    if (++n > (1u << 22)) { g_err = 1u; break; }
  }
}
__device__ __forceinline__ void expect_tx_e(uint32_t bar, uint32_t bytes) {
  asm volatile("{\n.reg .pred p;\nelect.sync _|p, 0xffffffff;\n@p mbarrier.arrive.expect_tx.shared::cta.b64 _, [%0], %1;\n}\n" ::"r"(bar), "r"(bytes) : "memory");
}
__device__ __forceinline__ void tma_2d_e(uint32_t dst, const CUtensorMap* tm, int c0, int c1, uint32_t bar) {
  asm volatile("{\n.reg .pred p;\nelect.sync _|p, 0xffffffff;\n"
               "@p cp.async.bulk.tensor.2d.shared::cluster.global.mbarrier::complete_tx::bytes [%0], [%1, {%2, %3}], [%4];\n}\n"
               ::"r"(dst), "l"(tm), "r"(c0), "r"(c1), "r"(bar) : "memory");
}
__device__ __forceinline__ void tma_2d_mc_e(uint32_t dst, const CUtensorMap* tm, int c0, int c1, uint32_t bar) {
  asm volatile("{\n.reg .pred p;\nelect.sync _|p, 0xffffffff;\n"
               "@p cp.async.bulk.tensor.2d.shared::cluster.global.mbarrier::complete_tx::bytes.multicast::cluster [%0], [%1, {%2, %3}], [%4], %5;\n}\n"
               ::"r"(dst), "l"(tm), "r"(c0), "r"(c1), "r"(bar), "h"((uint16_t)3) : "memory");
}
__device__ __forceinline__ void tma_pf_e(const CUtensorMap* tm, int c0, int c1) {
  asm volatile("{\n.reg .pred p;\nelect.sync _|p, 0xffffffff;\n"
               "@p cp.async.bulk.prefetch.tensor.2d.L2.global.tile [%0, {%1, %2}];\n}\n" ::"l"(tm), "r"(c0), "r"(c1) : "memory");
}
__device__ __forceinline__ void tma_2d_to_e(uint32_t dst, const CUtensorMap* tm, int c0, int c1, uint32_t bar, uint32_t mask) {
  asm volatile("{\n.reg .pred p;\nelect.sync _|p, 0xffffffff;\n"
               "@p cp.async.bulk.tensor.2d.shared::cluster.global.mbarrier::complete_tx::bytes.multicast::cluster [%0], [%1, {%2, %3}], [%4], %5;\n}\n"
               ::"r"(dst), "l"(tm), "r"(c0), "r"(c1), "r"(bar), "h"((uint16_t)mask) : "memory");
}
__device__ __forceinline__ void tma_3d_mc_e(uint32_t dst, const CUtensorMap* tm, int c1, int c2, uint32_t bar) {
  asm volatile("{\n.reg .pred p;\nelect.sync _|p, 0xffffffff;\n"
               "@p cp.async.bulk.tensor.3d.shared::cluster.global.mbarrier::complete_tx::bytes.multicast::cluster [%0], [%1, {%6, %2, %3}], [%4], %5;\n}\n"
               ::"r"(dst), "l"(tm), "r"(c1), "r"(c2), "r"(bar), "h"((uint16_t)3), "r"(0) : "memory");
}
__device__ __forceinline__ uint32_t poll_flags(const unsigned int* f, unsigned int target, int lane) {
  const unsigned int v = ld_acquire(f + (lane & 15));
  const uint32_t r = __ballot_sync(0xffffffffu, (int)(v - target) >= 0);
  __syncwarp();
  return r;
}
__device__ __forceinline__ void mbar_arrive_cluster(uint32_t local_bar, uint32_t rank) {
  asm volatile("{\n.reg .b32 ra;\nmapa.shared::cluster.u32 ra, %0, %1;\nmbarrier.arrive.shared::cluster.b64 _, [ra];\n}\n"
               ::"r"(local_bar), "r"(rank) : "memory");
}
__device__ __forceinline__ void release2(uint32_t bar) { mbar_arrive_cluster(bar, 0); mbar_arrive_cluster(bar, 1); }
__device__ __forceinline__ void tma_store_2d(const CUtensorMap* tm, uint32_t src, int c0, int c1) {
  asm volatile("cp.async.bulk.tensor.2d.global.shared::cta.bulk_group [%0, {%2, %3}], [%1];"
               ::"l"(tm), "r"(src), "r"(c0), "r"(c1) : "memory");
}
__device__ __forceinline__ void bulk_store(void* dst, uint32_t src, uint32_t bytes) {
  asm volatile("cp.async.bulk.global.shared::cta.bulk_group [%0], [%1], %2;" ::"l"(dst), "r"(src), "r"(bytes) : "memory");
}
__device__ __forceinline__ void bulk_load(uint32_t dst, const void* src, uint32_t bytes, uint32_t bar) {
  asm volatile("cp.async.bulk.shared::cluster.global.mbarrier::complete_tx::bytes [%0], [%1], %2, [%3];" ::"r"(dst), "l"(src), "r"(bytes), "r"(bar) : "memory");
}
__device__ __forceinline__ void bulk_red_add(void* dst, uint32_t src, uint32_t bytes) {
  asm volatile("cp.reduce.async.bulk.global.shared::cta.bulk_group.add.f32 [%0], [%1], %2;" ::"l"(dst), "r"(src), "r"(bytes) : "memory");
}
__device__ __forceinline__ void bulk_commit() { asm volatile("cp.async.bulk.commit_group;" ::: "memory"); }
__device__ __forceinline__ void bulk_wait_read0() { asm volatile("cp.async.bulk.wait_group.read 0;" ::: "memory"); }
__device__ __forceinline__ void bulk_wait0() { asm volatile("cp.async.bulk.wait_group 0;" ::: "memory"); }
__device__ __forceinline__ void fence_async_smem() { asm volatile("fence.proxy.async.shared::cta;" ::: "memory"); }
__device__ __forceinline__ void fence_async_all() { asm volatile("fence.proxy.async.global;" ::: "memory"); }
__device__ __forceinline__ void wgmma_fence() { asm volatile("wgmma.fence.sync.aligned;" ::: "memory"); }
__device__ __forceinline__ void wgmma_commit() { asm volatile("wgmma.commit_group.sync.aligned;" ::: "memory"); }
template <int N> __device__ __forceinline__ void wgmma_wait() { asm volatile("wgmma.wait_group.sync.aligned %0;" ::"n"(N) : "memory"); }
__device__ __forceinline__ void cluster_arrive() { asm volatile("barrier.cluster.arrive.release.aligned;" ::: "memory"); }
__device__ __forceinline__ void cluster_wait() { asm volatile("barrier.cluster.wait.acquire.aligned;" ::: "memory"); }
template <int ID, int N> __device__ __forceinline__ void nbar() { asm volatile("bar.sync %0, %1;" ::"n"(ID), "n"(N) : "memory"); }
__device__ __forceinline__ uint64_t make_desc(uint32_t addr, uint32_t lbo_bytes, uint32_t sbo_bytes) {
  uint64_t d = 0;
  d |= (uint64_t)((addr & 0x3FFFF) >> 4);
  d |= (uint64_t)((lbo_bytes >> 4) & 0x3FFF) << 16;
  d |= (uint64_t)((sbo_bytes >> 4) & 0x3FFF) << 32;
  d |= (uint64_t)1 << 62;
  return d;
}
__device__ __forceinline__ uint64_t desc64(uint32_t lo, uint32_t hi) { return (uint64_t)lo | ((uint64_t)hi << 32); }
__device__ __forceinline__ uint32_t pack_bf16(float lo, float hi) {
  uint32_t r; asm("cvt.rn.bf16x2.f32 %0, %1, %2;" : "=r"(r) : "f"(hi), "f"(lo)); return r;
}
__device__ __forceinline__ uint32_t mul_bf16x2(uint32_t a, uint32_t s, bool hi) {
  __nv_bfloat162 x = *reinterpret_cast<__nv_bfloat162*>(&a), y = *reinterpret_cast<__nv_bfloat162*>(&s);
  x = __hmul2(x, hi ? __high2bfloat162(y) : __low2bfloat162(y));
  return *reinterpret_cast<uint32_t*>(&x);
}
__device__ __forceinline__ float bf16r(float x) { return __bfloat162float(__float2bfloat16_rn(x)); }
__device__ __forceinline__ float bf_lo(uint32_t u) { return __uint_as_float(u << 16); }
__device__ __forceinline__ float bf_hi(uint32_t u) { return __uint_as_float(u & 0xFFFF0000u); }
__device__ __forceinline__ float ex2(float x) { float r; asm("ex2.approx.ftz.f32 %0, %1;" : "=f"(r) : "f"(x)); return r; }
__device__ __forceinline__ float rcp(float x) { float r; asm("rcp.approx.ftz.f32 %0, %1;" : "=f"(r) : "f"(x)); return r; }
__device__ __forceinline__ void mma_bf16(float (&d)[4], uint32_t a0, uint32_t a1, uint32_t a2, uint32_t a3, uint32_t b0, uint32_t b1) {
  asm("mma.sync.aligned.m16n8k16.row.col.f32.bf16.bf16.f32 {%0,%1,%2,%3}, {%4,%5,%6,%7}, {%8,%9}, {%0,%1,%2,%3};"
               : "+f"(d[0]), "+f"(d[1]), "+f"(d[2]), "+f"(d[3]) : "r"(a0), "r"(a1), "r"(a2), "r"(a3), "r"(b0), "r"(b1));
}
__device__ __forceinline__ void ldsm_x4(uint32_t& r0, uint32_t& r1, uint32_t& r2, uint32_t& r3, uint32_t addr) {
  asm volatile("ldmatrix.sync.aligned.m8n8.x4.shared.b16 {%0,%1,%2,%3}, [%4];"
               : "=r"(r0), "=r"(r1), "=r"(r2), "=r"(r3) : "r"(addr) : "memory");
}
__device__ __forceinline__ void ldsm_x4_t(uint32_t& r0, uint32_t& r1, uint32_t& r2, uint32_t& r3, uint32_t addr) {
  asm volatile("ldmatrix.sync.aligned.m8n8.x4.trans.shared.b16 {%0,%1,%2,%3}, [%4];"
               : "=r"(r0), "=r"(r1), "=r"(r2), "=r"(r3) : "r"(addr) : "memory");
}
__device__ __forceinline__ void ldsm_x2_t(uint32_t& r0, uint32_t& r1, uint32_t addr) {
  asm volatile("ldmatrix.sync.aligned.m8n8.x2.trans.shared.b16 {%0,%1}, [%2];"
               : "=r"(r0), "=r"(r1) : "r"(addr) : "memory");
}
__device__ __forceinline__ void stsm_x4(uint32_t addr, uint32_t r0, uint32_t r1, uint32_t r2, uint32_t r3) {
  asm volatile("stmatrix.sync.aligned.m8n8.x4.shared.b16 [%0], {%1,%2,%3,%4};"
               ::"r"(addr), "r"(r0), "r"(r1), "r"(r2), "r"(r3) : "memory");
}
__device__ __forceinline__ void stsm_x4_p(bool on, uint32_t addr, uint32_t r0, uint32_t r1, uint32_t r2, uint32_t r3) {
  asm volatile("{\n.reg .pred p;\nsetp.ne.b32 p, %5, 0;\n@p stmatrix.sync.aligned.m8n8.x4.shared.b16 [%0], {%1,%2,%3,%4};\n}\n"
               ::"r"(addr), "r"(r0), "r"(r1), "r"(r2), "r"(r3), "r"((int)on) : "memory");
}
__device__ __forceinline__ float2 lds_f2(uint32_t addr) {
  float2 v; asm volatile("ld.shared.v2.f32 {%0,%1}, [%2];" : "=f"(v.x), "=f"(v.y) : "r"(addr) : "memory"); return v;
}
__device__ __forceinline__ uint4 lds128(uint32_t addr) {
  uint4 v; asm volatile("ld.shared.v4.b32 {%0,%1,%2,%3}, [%4];" : "=r"(v.x), "=r"(v.y), "=r"(v.z), "=r"(v.w) : "r"(addr) : "memory"); return v;
}
__device__ __forceinline__ void sts128(uint32_t addr, uint4 v) {
  asm volatile("st.shared.v4.b32 [%0], {%1,%2,%3,%4};" ::"r"(addr), "r"(v.x), "r"(v.y), "r"(v.z), "r"(v.w) : "memory");
}
__device__ __forceinline__ float lds_f(uint32_t addr) {
  float v; asm volatile("ld.shared.f32 %0, [%1];" : "=f"(v) : "r"(addr) : "memory"); return v;
}
__device__ __forceinline__ uint32_t lds_vol(uint32_t addr) {
  uint32_t v; asm volatile("ld.volatile.shared.u32 %0, [%1];" : "=r"(v) : "r"(addr) : "memory"); return v;
}
__device__ __forceinline__ void sts16(uint32_t addr, uint32_t v) {
  asm volatile("st.shared.u16 [%0], %1;" ::"r"(addr), "h"((unsigned short)v) : "memory");
}
__device__ __forceinline__ void nbar_dyn(int id, int n) { asm volatile("bar.sync %0, %1;" ::"r"(id), "r"(n) : "memory"); }
__device__ __forceinline__ uint64_t make_desc_ns(uint32_t addr, uint32_t lbo_bytes, uint32_t sbo_bytes) {
  return (uint64_t)((addr & 0x3FFFF) >> 4) | ((uint64_t)(lbo_bytes >> 4) << 16) | ((uint64_t)(sbo_bytes >> 4) << 32);
}
__device__ __forceinline__ void sts_f(uint32_t addr, float v) { asm volatile("st.shared.f32 [%0], %1;" ::"r"(addr), "f"(v) : "memory"); }
__device__ __forceinline__ void sts64(uint32_t addr, uint32_t a, uint32_t b) {
  asm volatile("st.shared.v2.b32 [%0], {%1,%2};" ::"r"(addr), "r"(a), "r"(b) : "memory");
}
__device__ __forceinline__ void sts_f2(uint32_t addr, float a, float b) {
  asm volatile("st.shared.v2.f32 [%0], {%1,%2};" ::"r"(addr), "f"(a), "f"(b) : "memory");
}
__device__ __forceinline__ void red_add2(float* p, float a, float b) {
  asm volatile("red.global.add.v2.f32 [%0], {%1,%2};" ::"l"(p), "f"(a), "f"(b) : "memory");
}
__device__ __forceinline__ void red_add4(float* p, float a, float b, float c, float d) {
  asm volatile("red.global.add.v4.f32 [%0], {%1,%2,%3,%4};" ::"l"(p), "f"(a), "f"(b), "f"(c), "f"(d) : "memory");
}
__device__ __forceinline__ void red_add1(float* p, float a) {
  asm volatile("red.global.add.f32 [%0], %1;" ::"l"(p), "f"(a) : "memory");
}
__device__ __forceinline__ void l2_prefetch(const void* p, uint32_t bytes) {
  asm volatile("cp.async.bulk.prefetch.L2.global [%0], %1;" ::"l"(p), "r"(bytes) : "memory");
}

__device__ __forceinline__ void wgmma_n256(float (&d)[192], uint64_t da, uint64_t db, int scale_d) {
  asm volatile("{\n.reg .pred p;\nsetp.ne.b32 p, %130, 0;\n"
    "wgmma.mma_async.sync.aligned.m64n256k16.f32.bf16.bf16 {%0, %1, %2, %3, %4, %5, %6, %7, %8, %9, %10, %11, %12, %13, %14, %15, %16, %17, %18, %19, %20, %21, %22, %23, %24, %25, %26, %27, %28, %29, %30, %31, %32, %33, %34, %35, %36, %37, %38, %39, %40, %41, %42, %43, %44, %45, %46, %47, %48, %49, %50, %51, %52, %53, %54, %55, %56, %57, %58, %59, %60, %61, %62, %63, %64, %65, %66, %67, %68, %69, %70, %71, %72, %73, %74, %75, %76, %77, %78, %79, %80, %81, %82, %83, %84, %85, %86, %87, %88, %89, %90, %91, %92, %93, %94, %95, %96, %97, %98, %99, %100, %101, %102, %103, %104, %105, %106, %107, %108, %109, %110, %111, %112, %113, %114, %115, %116, %117, %118, %119, %120, %121, %122, %123, %124, %125, %126, %127}, %128, %129, p, 1, 1, 0, 1;\n}\n"
    : "+f"(d[0]), "+f"(d[1]), "+f"(d[2]), "+f"(d[3]), "+f"(d[4]), "+f"(d[5]), "+f"(d[6]), "+f"(d[7]), "+f"(d[8]), "+f"(d[9]), "+f"(d[10]), "+f"(d[11]), "+f"(d[12]), "+f"(d[13]), "+f"(d[14]), "+f"(d[15]), "+f"(d[16]), "+f"(d[17]), "+f"(d[18]), "+f"(d[19]), "+f"(d[20]), "+f"(d[21]), "+f"(d[22]), "+f"(d[23]), "+f"(d[24]), "+f"(d[25]), "+f"(d[26]), "+f"(d[27]), "+f"(d[28]), "+f"(d[29]), "+f"(d[30]), "+f"(d[31]), "+f"(d[32]), "+f"(d[33]), "+f"(d[34]), "+f"(d[35]), "+f"(d[36]), "+f"(d[37]), "+f"(d[38]), "+f"(d[39]), "+f"(d[40]), "+f"(d[41]), "+f"(d[42]), "+f"(d[43]), "+f"(d[44]), "+f"(d[45]), "+f"(d[46]), "+f"(d[47]), "+f"(d[48]), "+f"(d[49]), "+f"(d[50]), "+f"(d[51]), "+f"(d[52]), "+f"(d[53]), "+f"(d[54]), "+f"(d[55]), "+f"(d[56]), "+f"(d[57]), "+f"(d[58]), "+f"(d[59]), "+f"(d[60]), "+f"(d[61]), "+f"(d[62]), "+f"(d[63]), "+f"(d[64]), "+f"(d[65]), "+f"(d[66]), "+f"(d[67]), "+f"(d[68]), "+f"(d[69]), "+f"(d[70]), "+f"(d[71]), "+f"(d[72]), "+f"(d[73]), "+f"(d[74]), "+f"(d[75]), "+f"(d[76]), "+f"(d[77]), "+f"(d[78]), "+f"(d[79]), "+f"(d[80]), "+f"(d[81]), "+f"(d[82]), "+f"(d[83]), "+f"(d[84]), "+f"(d[85]), "+f"(d[86]), "+f"(d[87]), "+f"(d[88]), "+f"(d[89]), "+f"(d[90]), "+f"(d[91]), "+f"(d[92]), "+f"(d[93]), "+f"(d[94]), "+f"(d[95]), "+f"(d[96]), "+f"(d[97]), "+f"(d[98]), "+f"(d[99]), "+f"(d[100]), "+f"(d[101]), "+f"(d[102]), "+f"(d[103]), "+f"(d[104]), "+f"(d[105]), "+f"(d[106]), "+f"(d[107]), "+f"(d[108]), "+f"(d[109]), "+f"(d[110]), "+f"(d[111]), "+f"(d[112]), "+f"(d[113]), "+f"(d[114]), "+f"(d[115]), "+f"(d[116]), "+f"(d[117]), "+f"(d[118]), "+f"(d[119]), "+f"(d[120]), "+f"(d[121]), "+f"(d[122]), "+f"(d[123]), "+f"(d[124]), "+f"(d[125]), "+f"(d[126]), "+f"(d[127])
    : "l"(da), "l"(db), "r"(scale_d));
}
__device__ __forceinline__ void wgmma_n128(float (&d)[192], uint64_t da, uint64_t db, int scale_d) {
  asm volatile("{\n.reg .pred p;\nsetp.ne.b32 p, %66, 0;\n"
    "wgmma.mma_async.sync.aligned.m64n128k16.f32.bf16.bf16 {%0, %1, %2, %3, %4, %5, %6, %7, %8, %9, %10, %11, %12, %13, %14, %15, %16, %17, %18, %19, %20, %21, %22, %23, %24, %25, %26, %27, %28, %29, %30, %31, %32, %33, %34, %35, %36, %37, %38, %39, %40, %41, %42, %43, %44, %45, %46, %47, %48, %49, %50, %51, %52, %53, %54, %55, %56, %57, %58, %59, %60, %61, %62, %63}, %64, %65, p, 1, 1, 0, 1;\n}\n"
    : "+f"(d[128]), "+f"(d[129]), "+f"(d[130]), "+f"(d[131]), "+f"(d[132]), "+f"(d[133]), "+f"(d[134]), "+f"(d[135]), "+f"(d[136]), "+f"(d[137]), "+f"(d[138]), "+f"(d[139]), "+f"(d[140]), "+f"(d[141]), "+f"(d[142]), "+f"(d[143]), "+f"(d[144]), "+f"(d[145]), "+f"(d[146]), "+f"(d[147]), "+f"(d[148]), "+f"(d[149]), "+f"(d[150]), "+f"(d[151]), "+f"(d[152]), "+f"(d[153]), "+f"(d[154]), "+f"(d[155]), "+f"(d[156]), "+f"(d[157]), "+f"(d[158]), "+f"(d[159]), "+f"(d[160]), "+f"(d[161]), "+f"(d[162]), "+f"(d[163]), "+f"(d[164]), "+f"(d[165]), "+f"(d[166]), "+f"(d[167]), "+f"(d[168]), "+f"(d[169]), "+f"(d[170]), "+f"(d[171]), "+f"(d[172]), "+f"(d[173]), "+f"(d[174]), "+f"(d[175]), "+f"(d[176]), "+f"(d[177]), "+f"(d[178]), "+f"(d[179]), "+f"(d[180]), "+f"(d[181]), "+f"(d[182]), "+f"(d[183]), "+f"(d[184]), "+f"(d[185]), "+f"(d[186]), "+f"(d[187]), "+f"(d[188]), "+f"(d[189]), "+f"(d[190]), "+f"(d[191])
    : "l"(da), "l"(db), "r"(scale_d));
}
__device__ __forceinline__ void wgmma_n256_k(float (&d)[192], uint64_t da, uint64_t db, int scale_d) {
  asm volatile("{\n.reg .pred p;\nsetp.ne.b32 p, %130, 0;\n"
    "wgmma.mma_async.sync.aligned.m64n256k16.f32.bf16.bf16 {%0, %1, %2, %3, %4, %5, %6, %7, %8, %9, %10, %11, %12, %13, %14, %15, %16, %17, %18, %19, %20, %21, %22, %23, %24, %25, %26, %27, %28, %29, %30, %31, %32, %33, %34, %35, %36, %37, %38, %39, %40, %41, %42, %43, %44, %45, %46, %47, %48, %49, %50, %51, %52, %53, %54, %55, %56, %57, %58, %59, %60, %61, %62, %63, %64, %65, %66, %67, %68, %69, %70, %71, %72, %73, %74, %75, %76, %77, %78, %79, %80, %81, %82, %83, %84, %85, %86, %87, %88, %89, %90, %91, %92, %93, %94, %95, %96, %97, %98, %99, %100, %101, %102, %103, %104, %105, %106, %107, %108, %109, %110, %111, %112, %113, %114, %115, %116, %117, %118, %119, %120, %121, %122, %123, %124, %125, %126, %127}, %128, %129, p, 1, 1, 0, 0;\n}\n"
    : "+f"(d[0]), "+f"(d[1]), "+f"(d[2]), "+f"(d[3]), "+f"(d[4]), "+f"(d[5]), "+f"(d[6]), "+f"(d[7]), "+f"(d[8]), "+f"(d[9]), "+f"(d[10]), "+f"(d[11]), "+f"(d[12]), "+f"(d[13]), "+f"(d[14]), "+f"(d[15]), "+f"(d[16]), "+f"(d[17]), "+f"(d[18]), "+f"(d[19]), "+f"(d[20]), "+f"(d[21]), "+f"(d[22]), "+f"(d[23]), "+f"(d[24]), "+f"(d[25]), "+f"(d[26]), "+f"(d[27]), "+f"(d[28]), "+f"(d[29]), "+f"(d[30]), "+f"(d[31]), "+f"(d[32]), "+f"(d[33]), "+f"(d[34]), "+f"(d[35]), "+f"(d[36]), "+f"(d[37]), "+f"(d[38]), "+f"(d[39]), "+f"(d[40]), "+f"(d[41]), "+f"(d[42]), "+f"(d[43]), "+f"(d[44]), "+f"(d[45]), "+f"(d[46]), "+f"(d[47]), "+f"(d[48]), "+f"(d[49]), "+f"(d[50]), "+f"(d[51]), "+f"(d[52]), "+f"(d[53]), "+f"(d[54]), "+f"(d[55]), "+f"(d[56]), "+f"(d[57]), "+f"(d[58]), "+f"(d[59]), "+f"(d[60]), "+f"(d[61]), "+f"(d[62]), "+f"(d[63]), "+f"(d[64]), "+f"(d[65]), "+f"(d[66]), "+f"(d[67]), "+f"(d[68]), "+f"(d[69]), "+f"(d[70]), "+f"(d[71]), "+f"(d[72]), "+f"(d[73]), "+f"(d[74]), "+f"(d[75]), "+f"(d[76]), "+f"(d[77]), "+f"(d[78]), "+f"(d[79]), "+f"(d[80]), "+f"(d[81]), "+f"(d[82]), "+f"(d[83]), "+f"(d[84]), "+f"(d[85]), "+f"(d[86]), "+f"(d[87]), "+f"(d[88]), "+f"(d[89]), "+f"(d[90]), "+f"(d[91]), "+f"(d[92]), "+f"(d[93]), "+f"(d[94]), "+f"(d[95]), "+f"(d[96]), "+f"(d[97]), "+f"(d[98]), "+f"(d[99]), "+f"(d[100]), "+f"(d[101]), "+f"(d[102]), "+f"(d[103]), "+f"(d[104]), "+f"(d[105]), "+f"(d[106]), "+f"(d[107]), "+f"(d[108]), "+f"(d[109]), "+f"(d[110]), "+f"(d[111]), "+f"(d[112]), "+f"(d[113]), "+f"(d[114]), "+f"(d[115]), "+f"(d[116]), "+f"(d[117]), "+f"(d[118]), "+f"(d[119]), "+f"(d[120]), "+f"(d[121]), "+f"(d[122]), "+f"(d[123]), "+f"(d[124]), "+f"(d[125]), "+f"(d[126]), "+f"(d[127])
    : "l"(da), "l"(db), "r"(scale_d));
}
__device__ __forceinline__ void wgmma_n128_k(float (&d)[192], uint64_t da, uint64_t db, int scale_d) {
  asm volatile("{\n.reg .pred p;\nsetp.ne.b32 p, %66, 0;\n"
    "wgmma.mma_async.sync.aligned.m64n128k16.f32.bf16.bf16 {%0, %1, %2, %3, %4, %5, %6, %7, %8, %9, %10, %11, %12, %13, %14, %15, %16, %17, %18, %19, %20, %21, %22, %23, %24, %25, %26, %27, %28, %29, %30, %31, %32, %33, %34, %35, %36, %37, %38, %39, %40, %41, %42, %43, %44, %45, %46, %47, %48, %49, %50, %51, %52, %53, %54, %55, %56, %57, %58, %59, %60, %61, %62, %63}, %64, %65, p, 1, 1, 0, 0;\n}\n"
    : "+f"(d[128]), "+f"(d[129]), "+f"(d[130]), "+f"(d[131]), "+f"(d[132]), "+f"(d[133]), "+f"(d[134]), "+f"(d[135]), "+f"(d[136]), "+f"(d[137]), "+f"(d[138]), "+f"(d[139]), "+f"(d[140]), "+f"(d[141]), "+f"(d[142]), "+f"(d[143]), "+f"(d[144]), "+f"(d[145]), "+f"(d[146]), "+f"(d[147]), "+f"(d[148]), "+f"(d[149]), "+f"(d[150]), "+f"(d[151]), "+f"(d[152]), "+f"(d[153]), "+f"(d[154]), "+f"(d[155]), "+f"(d[156]), "+f"(d[157]), "+f"(d[158]), "+f"(d[159]), "+f"(d[160]), "+f"(d[161]), "+f"(d[162]), "+f"(d[163]), "+f"(d[164]), "+f"(d[165]), "+f"(d[166]), "+f"(d[167]), "+f"(d[168]), "+f"(d[169]), "+f"(d[170]), "+f"(d[171]), "+f"(d[172]), "+f"(d[173]), "+f"(d[174]), "+f"(d[175]), "+f"(d[176]), "+f"(d[177]), "+f"(d[178]), "+f"(d[179]), "+f"(d[180]), "+f"(d[181]), "+f"(d[182]), "+f"(d[183]), "+f"(d[184]), "+f"(d[185]), "+f"(d[186]), "+f"(d[187]), "+f"(d[188]), "+f"(d[189]), "+f"(d[190]), "+f"(d[191])
    : "l"(da), "l"(db), "r"(scale_d));
}
__device__ __forceinline__ void wgmma_n40_tt(float (&d)[20], uint64_t da, uint64_t db, int scale_d) {
  asm volatile("{\n.reg .pred p;\nsetp.ne.b32 p, %22, 0;\n"
    "wgmma.mma_async.sync.aligned.m64n40k16.f32.bf16.bf16 {%0, %1, %2, %3, %4, %5, %6, %7, %8, %9, %10, %11, %12, %13, %14, %15, %16, %17, %18, %19}, %20, %21, p, 1, 1, 1, 1;\n}\n"
    : "+f"(d[0]), "+f"(d[1]), "+f"(d[2]), "+f"(d[3]), "+f"(d[4]), "+f"(d[5]), "+f"(d[6]), "+f"(d[7]), "+f"(d[8]), "+f"(d[9]), "+f"(d[10]), "+f"(d[11]), "+f"(d[12]), "+f"(d[13]), "+f"(d[14]), "+f"(d[15]), "+f"(d[16]), "+f"(d[17]), "+f"(d[18]), "+f"(d[19])
    : "l"(da), "l"(db), "r"(scale_d));
}
__device__ __forceinline__ void wgmma_n40_rs(float (&d)[20], const uint32_t (&a)[4], uint64_t db, int scale_d) {
  asm volatile("{\n.reg .pred p;\nsetp.ne.b32 p, %25, 0;\n"
    "wgmma.mma_async.sync.aligned.m64n40k16.f32.bf16.bf16 {%0, %1, %2, %3, %4, %5, %6, %7, %8, %9, %10, %11, %12, %13, %14, %15, %16, %17, %18, %19}, {%20, %21, %22, %23}, %24, p, 1, 1, 1;\n}\n"
    : "+f"(d[0]), "+f"(d[1]), "+f"(d[2]), "+f"(d[3]), "+f"(d[4]), "+f"(d[5]), "+f"(d[6]), "+f"(d[7]), "+f"(d[8]), "+f"(d[9]), "+f"(d[10]), "+f"(d[11]), "+f"(d[12]), "+f"(d[13]), "+f"(d[14]), "+f"(d[15]), "+f"(d[16]), "+f"(d[17]), "+f"(d[18]), "+f"(d[19])
    : "r"(a[0]), "r"(a[1]), "r"(a[2]), "r"(a[3]), "l"(db), "r"(scale_d));
}
__device__ __forceinline__ void wgmma_n256_0(float (&d)[192], uint64_t da, uint64_t db) {
  asm volatile("{\n.reg .pred p;\nsetp.ne.b32 p, 0, 0;\n"
    "wgmma.mma_async.sync.aligned.m64n256k16.f32.bf16.bf16 {%0, %1, %2, %3, %4, %5, %6, %7, %8, %9, %10, %11, %12, %13, %14, %15, %16, %17, %18, %19, %20, %21, %22, %23, %24, %25, %26, %27, %28, %29, %30, %31, %32, %33, %34, %35, %36, %37, %38, %39, %40, %41, %42, %43, %44, %45, %46, %47, %48, %49, %50, %51, %52, %53, %54, %55, %56, %57, %58, %59, %60, %61, %62, %63, %64, %65, %66, %67, %68, %69, %70, %71, %72, %73, %74, %75, %76, %77, %78, %79, %80, %81, %82, %83, %84, %85, %86, %87, %88, %89, %90, %91, %92, %93, %94, %95, %96, %97, %98, %99, %100, %101, %102, %103, %104, %105, %106, %107, %108, %109, %110, %111, %112, %113, %114, %115, %116, %117, %118, %119, %120, %121, %122, %123, %124, %125, %126, %127}, %128, %129, p, 1, 1, 0, 1;\n}\n"
    : "=f"(d[0]), "=f"(d[1]), "=f"(d[2]), "=f"(d[3]), "=f"(d[4]), "=f"(d[5]), "=f"(d[6]), "=f"(d[7]), "=f"(d[8]), "=f"(d[9]), "=f"(d[10]), "=f"(d[11]), "=f"(d[12]), "=f"(d[13]), "=f"(d[14]), "=f"(d[15]), "=f"(d[16]), "=f"(d[17]), "=f"(d[18]), "=f"(d[19]), "=f"(d[20]), "=f"(d[21]), "=f"(d[22]), "=f"(d[23]), "=f"(d[24]), "=f"(d[25]), "=f"(d[26]), "=f"(d[27]), "=f"(d[28]), "=f"(d[29]), "=f"(d[30]), "=f"(d[31]), "=f"(d[32]), "=f"(d[33]), "=f"(d[34]), "=f"(d[35]), "=f"(d[36]), "=f"(d[37]), "=f"(d[38]), "=f"(d[39]), "=f"(d[40]), "=f"(d[41]), "=f"(d[42]), "=f"(d[43]), "=f"(d[44]), "=f"(d[45]), "=f"(d[46]), "=f"(d[47]), "=f"(d[48]), "=f"(d[49]), "=f"(d[50]), "=f"(d[51]), "=f"(d[52]), "=f"(d[53]), "=f"(d[54]), "=f"(d[55]), "=f"(d[56]), "=f"(d[57]), "=f"(d[58]), "=f"(d[59]), "=f"(d[60]), "=f"(d[61]), "=f"(d[62]), "=f"(d[63]), "=f"(d[64]), "=f"(d[65]), "=f"(d[66]), "=f"(d[67]), "=f"(d[68]), "=f"(d[69]), "=f"(d[70]), "=f"(d[71]), "=f"(d[72]), "=f"(d[73]), "=f"(d[74]), "=f"(d[75]), "=f"(d[76]), "=f"(d[77]), "=f"(d[78]), "=f"(d[79]), "=f"(d[80]), "=f"(d[81]), "=f"(d[82]), "=f"(d[83]), "=f"(d[84]), "=f"(d[85]), "=f"(d[86]), "=f"(d[87]), "=f"(d[88]), "=f"(d[89]), "=f"(d[90]), "=f"(d[91]), "=f"(d[92]), "=f"(d[93]), "=f"(d[94]), "=f"(d[95]), "=f"(d[96]), "=f"(d[97]), "=f"(d[98]), "=f"(d[99]), "=f"(d[100]), "=f"(d[101]), "=f"(d[102]), "=f"(d[103]), "=f"(d[104]), "=f"(d[105]), "=f"(d[106]), "=f"(d[107]), "=f"(d[108]), "=f"(d[109]), "=f"(d[110]), "=f"(d[111]), "=f"(d[112]), "=f"(d[113]), "=f"(d[114]), "=f"(d[115]), "=f"(d[116]), "=f"(d[117]), "=f"(d[118]), "=f"(d[119]), "=f"(d[120]), "=f"(d[121]), "=f"(d[122]), "=f"(d[123]), "=f"(d[124]), "=f"(d[125]), "=f"(d[126]), "=f"(d[127])
    : "l"(da), "l"(db));
}
__device__ __forceinline__ void wgmma_n128_0(float (&d)[192], uint64_t da, uint64_t db) {
  asm volatile("{\n.reg .pred p;\nsetp.ne.b32 p, 0, 0;\n"
    "wgmma.mma_async.sync.aligned.m64n128k16.f32.bf16.bf16 {%0, %1, %2, %3, %4, %5, %6, %7, %8, %9, %10, %11, %12, %13, %14, %15, %16, %17, %18, %19, %20, %21, %22, %23, %24, %25, %26, %27, %28, %29, %30, %31, %32, %33, %34, %35, %36, %37, %38, %39, %40, %41, %42, %43, %44, %45, %46, %47, %48, %49, %50, %51, %52, %53, %54, %55, %56, %57, %58, %59, %60, %61, %62, %63}, %64, %65, p, 1, 1, 0, 1;\n}\n"
    : "=f"(d[128]), "=f"(d[129]), "=f"(d[130]), "=f"(d[131]), "=f"(d[132]), "=f"(d[133]), "=f"(d[134]), "=f"(d[135]), "=f"(d[136]), "=f"(d[137]), "=f"(d[138]), "=f"(d[139]), "=f"(d[140]), "=f"(d[141]), "=f"(d[142]), "=f"(d[143]), "=f"(d[144]), "=f"(d[145]), "=f"(d[146]), "=f"(d[147]), "=f"(d[148]), "=f"(d[149]), "=f"(d[150]), "=f"(d[151]), "=f"(d[152]), "=f"(d[153]), "=f"(d[154]), "=f"(d[155]), "=f"(d[156]), "=f"(d[157]), "=f"(d[158]), "=f"(d[159]), "=f"(d[160]), "=f"(d[161]), "=f"(d[162]), "=f"(d[163]), "=f"(d[164]), "=f"(d[165]), "=f"(d[166]), "=f"(d[167]), "=f"(d[168]), "=f"(d[169]), "=f"(d[170]), "=f"(d[171]), "=f"(d[172]), "=f"(d[173]), "=f"(d[174]), "=f"(d[175]), "=f"(d[176]), "=f"(d[177]), "=f"(d[178]), "=f"(d[179]), "=f"(d[180]), "=f"(d[181]), "=f"(d[182]), "=f"(d[183]), "=f"(d[184]), "=f"(d[185]), "=f"(d[186]), "=f"(d[187]), "=f"(d[188]), "=f"(d[189]), "=f"(d[190]), "=f"(d[191])
    : "l"(da), "l"(db));
}
__device__ __forceinline__ void wgmma_n64a(float (&d)[192], uint64_t da, uint64_t db, int scale_d) {
  asm volatile("{\n.reg .pred p;\nsetp.ne.b32 p, %34, 0;\n"
    "wgmma.mma_async.sync.aligned.m64n64k16.f32.bf16.bf16 {%0, %1, %2, %3, %4, %5, %6, %7, %8, %9, %10, %11, %12, %13, %14, %15, %16, %17, %18, %19, %20, %21, %22, %23, %24, %25, %26, %27, %28, %29, %30, %31}, %32, %33, p, 1, 1, 0, 1;\n}\n"
    : "+f"(d[128]), "+f"(d[129]), "+f"(d[130]), "+f"(d[131]), "+f"(d[132]), "+f"(d[133]), "+f"(d[134]), "+f"(d[135]), "+f"(d[136]), "+f"(d[137]), "+f"(d[138]), "+f"(d[139]), "+f"(d[140]), "+f"(d[141]), "+f"(d[142]), "+f"(d[143]), "+f"(d[144]), "+f"(d[145]), "+f"(d[146]), "+f"(d[147]), "+f"(d[148]), "+f"(d[149]), "+f"(d[150]), "+f"(d[151]), "+f"(d[152]), "+f"(d[153]), "+f"(d[154]), "+f"(d[155]), "+f"(d[156]), "+f"(d[157]), "+f"(d[158]), "+f"(d[159])
    : "l"(da), "l"(db), "r"(scale_d));
}
__device__ __forceinline__ void wgmma_n64b(float (&d)[192], uint64_t da, uint64_t db, int scale_d) {
  asm volatile("{\n.reg .pred p;\nsetp.ne.b32 p, %34, 0;\n"
    "wgmma.mma_async.sync.aligned.m64n64k16.f32.bf16.bf16 {%0, %1, %2, %3, %4, %5, %6, %7, %8, %9, %10, %11, %12, %13, %14, %15, %16, %17, %18, %19, %20, %21, %22, %23, %24, %25, %26, %27, %28, %29, %30, %31}, %32, %33, p, 1, 1, 0, 1;\n}\n"
    : "+f"(d[160]), "+f"(d[161]), "+f"(d[162]), "+f"(d[163]), "+f"(d[164]), "+f"(d[165]), "+f"(d[166]), "+f"(d[167]), "+f"(d[168]), "+f"(d[169]), "+f"(d[170]), "+f"(d[171]), "+f"(d[172]), "+f"(d[173]), "+f"(d[174]), "+f"(d[175]), "+f"(d[176]), "+f"(d[177]), "+f"(d[178]), "+f"(d[179]), "+f"(d[180]), "+f"(d[181]), "+f"(d[182]), "+f"(d[183]), "+f"(d[184]), "+f"(d[185]), "+f"(d[186]), "+f"(d[187]), "+f"(d[188]), "+f"(d[189]), "+f"(d[190]), "+f"(d[191])
    : "l"(da), "l"(db), "r"(scale_d));
}

constexpr int SLOT = 16384;
constexpr int KVT = 10240;
constexpr uint32_t QA = 0x0BAu, QK = 0x462u, QQ = 0x981u;
constexpr int SM_SD = 12 * SLOT;
constexpr int SM_BAR = SM_SD + 8192;
constexpr int SM_RS = SM_BAR + 512;
constexpr int SM_AP = SM_RS + 768;
constexpr int SM_BP = SM_AP + 2048;
constexpr int SM_WPHI = SM_BP + 12288;
constexpr int SM_EPOCH = SM_WPHI + 10240;
constexpr int SM_TOTAL = SM_EPOCH + 16 + 1024;
constexpr int B_FULLS = 0, B_XOLD = 24, B_STAT = 32, B_EMPTYS = 40, B_FULLT = 256  , B_CONS = 384  , B_E3 = 472, B_E0 = 480, B_E1 = 488, B_E2 = 496, B_EPI = 504, B_CS = 160,
              B_KVDONE = 168  , B_ODONE = 176, B_XDONE = 184, B_OH1 = 192, B_CS2 = 208, B_XH0 = 232, B_R0 = 240, B_XOLD2 = 216, B_FLG = 64  ;
constexpr uint64_t BAR_CNT = 0x1c07fc0eac00a800ull;
constexpr uint64_t WO_A0 = 0xba76218762187643ull, WO_B0 = 0x9540395403ba9021ull, WO_A1 = 0xba713257132576abull, WO_B1 = 0x9506489064890132ull;
constexpr uint64_t WO_DA0 = 0xa9876543210edd00ull, WO_DB0 = 0xa987654321bbccccull, WO_DA1 = 0xa9876543210fff00ull, WO_DB1 = 0xa98765432bbcccddull;
constexpr int XS = 10;

#define PL 2
#define PROFX(i) PROFT(tid_ == 128 && layer == PL, 200 + (i))
#define PSL 20
#define EP 5
#define DRY 0
#define NCOM 3
#define CG0 0
#define CG1 99
#define CPF 0
#define CSLP 128
#define PFS 8
#define KVTH 0x41700000u
#define CSW 1
#define RL 3
#define ORD 1
#define XB2 2
#define XEP 0
#define PMOD 3
#define DB1 2
#define NLAYERS 4
constexpr float L2E = 1.4426950408889634f;
#define PHI_MAX 2147483648.f

#define D128(lo) desc64(lo, 0x40000040u)
struct Ctx { uint32_t sb; int g, rb, cu; bf16* out; };

__device__ __forceinline__ void colsum_load(const bf16* __restrict__ w, int rb, int g, int wi, int lane, uint32_t stg, float (&s)[8]) {
  const int ch = wi * 8 + (lane & 7), sec = ch >> 4;
  const bf16* src = w + (size_t)(rb * 64 + (lane >> 3) * 16) * 3072 + (sec == 2 ? 0 : 1024 + sec * 1024) + g * 128 + (ch & 15) * 8;
  stg += lane * 16;
#pragma unroll
  for (int i = 0; i < 8; ++i) s[i] = 0.f;
#pragma unroll
  for (int r = 0; r < 12; ++r)
    asm volatile("cp.async.cg.shared.global [%0], [%1], 16;" ::"r"(stg + r * 512), "l"(src + (size_t)(4 + r) * 3072) : "memory");
  uint4 v[4];
#pragma unroll
  for (int r = 0; r < 4; ++r) v[r] = __ldg(reinterpret_cast<const uint4*>(src + (size_t)r * 3072));
#pragma unroll 1
  for (int r0 = 0;; ++r0) {
#pragma unroll
    for (int r = 0; r < 4; ++r) {
      s[0] += bf_lo(v[r].x); s[1] += bf_hi(v[r].x); s[2] += bf_lo(v[r].y); s[3] += bf_hi(v[r].y);
      s[4] += bf_lo(v[r].z); s[5] += bf_hi(v[r].z); s[6] += bf_lo(v[r].w); s[7] += bf_hi(v[r].w);
    }
    if (r0 == 3) break;
    asm volatile("cp.async.wait_all;" ::: "memory");
#pragma unroll
    for (int r = 0; r < 4; ++r) v[r] = lds128(stg + (r0 * 4 + r) * 512);
  }
#pragma unroll
  for (int i = 0; i < 8; ++i) { s[i] += __shfl_xor_sync(0xffffffffu, s[i], 8); s[i] += __shfl_xor_sync(0xffffffffu, s[i], 16); }
}
__device__ __forceinline__ void colsum_red(float* cs, int g, int wi, int lane, const float (&s)[8]) {
  if (lane < 8) {
    red_add4(cs + g * 384 + (wi * 8 + lane) * 8, s[0], s[1], s[2], s[3]);
    red_add4(cs + g * 384 + (wi * 8 + lane) * 8 + 4, s[4], s[5], s[6], s[7]);
  }
}
#define PHASE_CTX() \
  uint32_t sb = c.sb; asm volatile("" : "+r"(sb)); \
  int tid_ = threadIdx.x; asm volatile("" : "+r"(tid_)); \
  const uint32_t bar = sb + SM_BAR; \
  const int lane = tid_ & 31, cw = (tid_ >> 5) - 4, wg = cw >> 2, wq = cw & 3, gq = lane >> 2, t = lane & 3, wrow0 = cw * 16; \
  const int lrow = (lane & 7) + ((lane >> 3) & 1) * 8, lchk = lane >> 4; \
  const bool elected = (tid_ & 127) == 0; \
  const uint32_t rowo = (wrow0 + lrow) * 128, X = (lchk ^ (lane & 7)) << 4; \
  (void)bar; (void)wq; (void)gq; (void)lrow; (void)lchk; (void)elected; (void)wrow0; (void)wg; (void)rowo; (void)X; (void)t;

__device__ __forceinline__ void slab_out_half(uint32_t slot, bf16* dst, int wrow0, int lane, bool FENCE = false) {
  const int r0 = lane >> 3, ch = lane & 7;
  const uint32_t src = slot + (wrow0 + r0) * 128;
  uint4 v[4];
#pragma unroll
  for (int i = 0; i < 4; ++i) v[i] = lds128(src + i * 512 + (((ch ^ (4 * i + r0)) & 7) << 4));
  if (FENCE) fence_async_smem();
  dst += (size_t)(wrow0 + r0) * D_ + ch * 8;
#pragma unroll
  for (int i = 0; i < 4; ++i)
    asm volatile("st.global.v4.u32 [%0], {%1,%2,%3,%4};" ::"l"(dst + (size_t)i * 4 * D_), "r"(v[i].x), "r"(v[i].y), "r"(v[i].z), "r"(v[i].w) : "memory");
}

template <int O>
__device__ __forceinline__ void phi_proj(float (&p)[2][4][4], const uint32_t (&kq)[64], uint32_t wa) {
#pragma unroll
  for (int h = 0; h < 2; ++h)
#pragma unroll
    for (int i = 0; i < 4; ++i) { p[h][i][0] = p[h][i][1] = p[h][i][2] = p[h][i][3] = 0.f; }
#pragma unroll
  for (int ks = 0; ks < 2; ++ks)
#pragma unroll
    for (int np = 0; np < 2; ++np)
#pragma unroll
      for (int h = 0; h < 2; ++h) {
        uint32_t b0, b1, b2, b3;
        ldsm_x4_t(b0, b1, b2, b3, wa + h * 2560 + ks * 1280 + np * 32);
        mma_bf16(p[h][2 * np], kq[O + 8 * h + 4 * ks], kq[O + 8 * h + 4 * ks + 1], kq[O + 8 * h + 4 * ks + 2], kq[O + 8 * h + 4 * ks + 3], b0, b1);
        mma_bf16(p[h][2 * np + 1], kq[O + 8 * h + 4 * ks], kq[O + 8 * h + 4 * ks + 1], kq[O + 8 * h + 4 * ks + 2], kq[O + 8 * h + 4 * ks + 3], b2, b3);
      }
}
__device__ __forceinline__ void phi_exp(uint32_t (&raw)[4][4], const float (&p)[4][4], float sc0, float sc1) {
#pragma unroll
  for (int i = 0; i < 4; ++i) {
    const float e0 = ex2(p[i][0] * sc0), e1 = ex2(p[i][1] * sc0), e2 = ex2(p[i][2] * sc1), e3 = ex2(p[i][3] * sc1);
    const float m0 = e0 * e1, m1 = e2 * e3, rr = rcp(m0 * m1), r0 = rr * m1, r1 = rr * m0;
    raw[i >> 1][(i & 1) * 2] = pack_bf16(e0, e1);
    raw[i >> 1][(i & 1) * 2 + 1] = pack_bf16(e2, e3);
    raw[2 + (i >> 1)][(i & 1) * 2] = pack_bf16(e1 * r0, e0 * r0);
    raw[2 + (i >> 1)][(i & 1) * 2 + 1] = pack_bf16(e3 * r1, e2 * r1);
  }
}
#define FENCE_P(h) _Pragma("unroll") for (int i_ = 0; i_ < 16; ++i_) asm volatile("" : "+f"(p[h][i_ >> 2][i_ & 3]) :: "memory")
#define FENCE_RAW(h) _Pragma("unroll") for (int i_ = 0; i_ < 16; ++i_) asm volatile("" : "+r"(raw[h][i_ >> 2][i_ & 3]) :: "memory")
template <int O>
__device__ __forceinline__ void phi_norm(uint32_t (&ph)[2][4][4], const uint32_t (&raw)[2][4][4], const uint32_t (&kq)[64], uint32_t wa,
                                         float sc0, float sc1, float mul0, float mul1) {
  bool bad = false;
#pragma unroll
  for (int h = 0; h < 2; ++h)
#pragma unroll
    for (int sg = 0; sg < 2; ++sg) {
      float ss[4] = {0.f, 0.f, 0.f, 0.f};
#pragma unroll
      for (int ks = 0; ks < 2; ++ks)
        mma_bf16(ss, raw[h][2 * sg + ks][0], raw[h][2 * sg + ks][1], raw[h][2 * sg + ks][2], raw[h][2 * sg + ks][3], 0x3F803F80u, 0x3F803F80u);
      bad = bad || !(ss[0] < PHI_MAX) || !(ss[2] < PHI_MAX);
      const uint32_t iv = pack_bf16(rcp(ss[0]) * mul0, rcp(ss[2]) * mul1);
#pragma unroll
      for (int ks = 0; ks < 2; ++ks)
#pragma unroll
        for (int j = 0; j < 4; ++j) ph[h][2 * sg + ks][j] = mul_bf16x2(raw[h][2 * sg + ks][j], iv, j & 1);
    }
  if (__builtin_expect(__any_sync(0xffffffffu, bad), 0)) {
#pragma unroll 1
    for (int it = 0; it < 4; ++it) {
      float q[4][4];
#pragma unroll
      for (int i = 0; i < 4; ++i) { q[i][0] = q[i][1] = q[i][2] = q[i][3] = 0.f; }
#pragma unroll
      for (int ks = 0; ks < 2; ++ks) {
        uint32_t a[4];
#pragma unroll
        for (int j = 0; j < 4; ++j) a[j] = (it & 2) ? kq[O + 8 + 4 * ks + j] : kq[O + 4 * ks + j];
#pragma unroll
        for (int np = 0; np < 2; ++np) {
          uint32_t b0, b1, b2, b3;
          ldsm_x4_t(b0, b1, b2, b3, wa + (it >> 1) * 2560 + ks * 1280 + np * 32);
          mma_bf16(q[2 * np], a[0], a[1], a[2], a[3], b0, b1);
          mma_bf16(q[2 * np + 1], a[0], a[1], a[2], a[3], b2, b3);
        }
      }
      float iv[2];
#pragma unroll
      for (int r = 0; r < 2; ++r) {
        const float sc = (it & 1) ? -(r ? sc1 : sc0) : (r ? sc1 : sc0);
        float mx = -INFINITY, sm = 0.f;
#pragma unroll
        for (int i = 0; i < 8; ++i) { float& v = q[i >> 1][2 * r + (i & 1)]; v *= sc; mx = fmaxf(mx, v); }
        mx = fmaxf(mx, __shfl_xor_sync(0xffffffffu, mx, 1));
        mx = fmaxf(mx, __shfl_xor_sync(0xffffffffu, mx, 2));
#pragma unroll
        for (int i = 0; i < 8; ++i) { float& v = q[i >> 1][2 * r + (i & 1)]; v = ex2(v - mx); sm += v; }
        sm += __shfl_xor_sync(0xffffffffu, sm, 1);
        sm += __shfl_xor_sync(0xffffffffu, sm, 2);
        iv[r] = rcp(sm) * (r ? mul1 : mul0);
      }
#pragma unroll
      for (int i = 0; i < 24; ++i) ph[i >> 4][(i >> 2) & 3][i & 3] = ph[(i + 8) >> 4][((i + 8) >> 2) & 3][i & 3];
#pragma unroll
      for (int i = 0; i < 4; ++i) {
        ph[1][2 + (i >> 1)][(i & 1) * 2] = pack_bf16(q[i][0] * iv[0], q[i][1] * iv[0]);
        ph[1][2 + (i >> 1)][(i & 1) * 2 + 1] = pack_bf16(q[i][2] * iv[1], q[i][3] * iv[1]);
      }
    }
  }
}

__device__ __forceinline__ void stats_out(float s0, float s1, float q0, float q1, float2* dst, int t) {
  const bool od = t & 1;
  float sa = od ? s1 : s0, qa = od ? q1 : q0;
  sa += __shfl_xor_sync(0xffffffffu, od ? s0 : s1, 1);
  qa += __shfl_xor_sync(0xffffffffu, od ? q0 : q1, 1);
  sa += __shfl_xor_sync(0xffffffffu, sa, 2);
  qa += __shfl_xor_sync(0xffffffffu, qa, 2);
  if (t < 2) red_add2(&dst[t * 8].x, sa, qa);
}

__device__ __forceinline__ void consumer(const Ctx& c) {
  const int g = c.g, m0 = c.rb * 128;
  float acc[192];
#define X_H1() \
      _Pragma("unroll") for (int jp = 4; jp < 8; ++jp) \
        stsm_x4(sb + (XS + 1) * SLOT + rowo + (X ^ ((jp & 3) << 5)), \
                pack_bf16(acc[128 + 8 * jp], acc[129 + 8 * jp]), pack_bf16(acc[130 + 8 * jp], acc[131 + 8 * jp]), \
                pack_bf16(acc[132 + 8 * jp], acc[133 + 8 * jp]), pack_bf16(acc[134 + 8 * jp], acc[135 + 8 * jp]));
#pragma unroll
  for (int i = 128; i < 192; ++i) acc[i] = 0.f;
#pragma unroll 1
  for (int layer = 0;; ++layer) {
    {
      PHASE_CTX();
      const uint32_t wu = c.cu >> 2;
      const uint32_t dA0 = (((sb + wu * 8192) & 0x3FFFF) >> 4) | (1u << 16), dB0 = ((sb & 0x3FFFF) >> 4) | (512u << 16);
      {
        PROFX(0);
        mbar_wait(bar + B_FULLS, 0);
        PROFX(1);
        wgmma_fence();
        wgmma_n256_0(acc, D128(dA0 + XS * 1024), D128(dB0 + 2048));
#pragma unroll
        for (int k = 1; k < 4; ++k) wgmma_n256(acc, D128(dA0 + XS * 1024 + k * 2), D128(dB0 + 2048 + k * 128), 1);
        wgmma_commit();
        wgmma_wait<1>();
        float s0 = 0.f, s1 = 0.f, q0 = 0.f, q1 = 0.f;
        if (layer) {
          X_H1();
#pragma unroll
          for (int i = 128; i < 192; i += 4) {
            s0 += acc[i] + acc[i + 1]; s1 += acc[i + 2] + acc[i + 3];
            q0 = fmaf(acc[i], acc[i], fmaf(acc[i + 1], acc[i + 1], q0)); q1 = fmaf(acc[i + 2], acc[i + 2], fmaf(acc[i + 3], acc[i + 3], q1));
          }
        }
        asm volatile("" : "+f"(s0), "+f"(s1), "+f"(q0), "+f"(q1) :: "memory");
        wgmma_fence();
        wgmma_n128_0(acc, D128(dA0 + XS * 1024), D128(dB0 + 1024));
#pragma unroll
        for (int k = 1; k < 4; ++k) wgmma_n128(acc, D128(dA0 + XS * 1024 + k * 2), D128(dB0 + 1024 + k * 128), 1);
        wgmma_commit();
        if (layer) {
          PHASE_CTX();
          fence_async_smem();
          nbar_dyn(3 + wu, 128);
          stats_out(s0, s1, q0, q1, g_stats + layer * S_ + m0 + wrow0 + gq, t);
          PROFT(tid_ == 128, layer * 16 + 8);
        }
      }
      uint32_t s = 1, u = 0, sp = 0;
      const int ix = layer ? 1 : 2 * min(g, NCOM) + 1;
#pragma unroll 1
      for (int i = 1; i < 14; ++i) {
        mbar_wait(bar + B_FULLS + s * 8, (u + (s ? layer : 0)) & 1);
        const uint32_t da = dA0 + ((QA >> (4 * s)) & 15) * 1024, dk = dB0 + ((QK >> (4 * s)) & 15) * 1024,
                       dq = dB0 + ((QQ >> (4 * s)) & 15) * 1024;
        wgmma_fence();
#pragma unroll
        for (int k = 0; k < 4; ++k) {
          wgmma_n256(acc, D128(da + k * 2), D128(dk + k * 128), 1);
          wgmma_n128(acc, D128(da + k * 2), D128(dq + k * 128), 1);
        }
        wgmma_commit();
        if (i == ix || (i == ix + 1 && !layer)) {
          PHASE_CTX();
          if (layer) {
            slab_out_half(sb + (XS + 1) * SLOT, g_x + (size_t)m0 * D_ + g * 128 + 64, wrow0, lane);
          } else {
            float s0 = 0.f, s1 = 0.f, q0 = 0.f, q1 = 0.f;
            const uint32_t xa = sb + ((QA >> (4 * sp)) & 15) * SLOT + rowo;
#pragma unroll
            for (int jp = 0; jp < 4; ++jp) {
              uint32_t x0, x1, x2, x3;
              ldsm_x4(x0, x1, x2, x3, xa + (X ^ (jp << 5)));
              s0 += (bf_lo(x0) + bf_hi(x0)) + (bf_lo(x2) + bf_hi(x2));
              s1 += (bf_lo(x1) + bf_hi(x1)) + (bf_lo(x3) + bf_hi(x3));
              q0 = fmaf(bf_lo(x0), bf_lo(x0), fmaf(bf_hi(x0), bf_hi(x0), fmaf(bf_lo(x2), bf_lo(x2), fmaf(bf_hi(x2), bf_hi(x2), q0))));
              q1 = fmaf(bf_lo(x1), bf_lo(x1), fmaf(bf_hi(x1), bf_hi(x1), fmaf(bf_lo(x3), bf_lo(x3), fmaf(bf_hi(x3), bf_hi(x3), q1))));
            }
            stats_out(s0, s1, q0, q1, g_stats + m0 + wrow0 + gq, t);
          }
          __syncwarp();
          if (lane == 0 && (layer || i != ix)) mbar_arrive(bar + B_XDONE);
          nbar_dyn(3 + wu, 128);
        }
        wgmma_wait<1>();
        if (elected) release2(bar + B_EMPTYS + sp * 8);
        sp = s;
        if (++s == 3) { s = 0; ++u; }
      }
      {
        const uint64_t dap = make_desc_ns(sb + SM_AP + wu * 1024, 0, 128), dbp = make_desc_ns(sb + SM_BP + (layer & 1) * 6144, 0, 128);
        if (wu == 0) {
          wgmma_wait<0>();
          if (elected) mbar_arrive(bar + B_R0);
          nbar<6, 256>();
        }
        if (layer < 2) mbar_wait(bar + (layer ? B_CS2 : B_CS), 0);
        mbar_wait(bar + B_STAT, layer & 1);
        mbar_wait(bar + B_FULLS + 16, layer & 1);
        wgmma_fence();
        wgmma_n256_k(acc, dap, dbp, 1);
#pragma unroll
        for (int k = 0; k < 4; ++k) wgmma_n256(acc, D128(dA0 + (QA >> 8) * 1024 + k * 2), D128(dB0 + (QK >> 8) * 1024 + k * 128), 1);
        mbar_wait(bar + B_FULLS, 1);
        PROFT(tid_ == 128, layer * 16 + 9);
        wgmma_fence();
#pragma unroll
        for (int k = 0; k < 4; ++k) wgmma_n256(acc, D128(dA0 + (QA & 15) * 1024 + k * 2), D128(dB0 + (QK & 15) * 1024 + k * 128), 1);
        wgmma_commit();
        if (wu) nbar<6, 256>();
#define Q_TAIL() \
        wgmma_n128_k(acc, dap, dbp + 256, 1); \
        _Pragma("unroll") for (int k = 0; k < 4; ++k) wgmma_n128(acc, D128(dA0 + (QA >> 8) * 1024 + k * 2), D128(dB0 + (QQ >> 8) * 1024 + k * 128), 1); \
        _Pragma("unroll") for (int k = 0; k < 4; ++k) wgmma_n128(acc, D128(dA0 + (QA & 15) * 1024 + k * 2), D128(dB0 + (QQ & 15) * 1024 + k * 128), 1);
        Q_TAIL();
        wgmma_commit();
        wgmma_wait<1>();
#pragma unroll
        for (int i = 0; i < 128; ++i) asm volatile("" : "+f"(acc[i]) :: "memory");
      }
    }
    uint32_t xo[32];
    {
      PHASE_CTX();
      PROFT(tid_ == 128, layer * 16 + 1);
      const bool isB = layer & 1;
      const int cu = c.cu;
      if (cu >= 4) asm volatile("bar.arrive 7, 256;" ::: "memory");
      if (elected && cu == 4) mbar_arrive(bar + B_R0);
      uint32_t kq[64];
      const uint32_t rowq = rowo & 8191;
      const float rs0 = lds_f(sb + SM_RS + (16 + wrow0 + gq) * 4), rs1 = lds_f(sb + SM_RS + (24 + wrow0 + gq) * 4);
#define Q_DONE() \
      wgmma_wait<0>(); \
      if (lane == 0) release2(bar + B_E0); \
      _Pragma("unroll") for (int i = 128; i < 192; ++i) asm volatile("" : "+f"(acc[i]) :: "memory"); \
      _Pragma("unroll") for (int i = 0; i < 32; ++i) kq[32 + i] = pack_bf16(acc[128 + 2 * i], acc[129 + 2 * i]);
      if (isB) {
        if (cu == 0) asm volatile("bar.arrive 10, 64;" ::: "memory");
        if (elected) release2(bar + B_E1);
        const int e = gq & 1;
        const bool sel = t > (gq >> 1);
        const uint32_t rja = sb + SM_RS + (wrow0 + 2 * t + e) * 4;
        const float rjA0 = lds_f(rja + 32), rjA1 = lds_f(rja + 64), rjB0 = lds_f(rja + (sel ? 0 : 64)), rjB1 = lds_f(rja + (sel ? 32 : 96));
        uint32_t vv[32];
#pragma unroll
        for (int i = 0; i < 16; ++i) { kq[i] = pack_bf16(acc[2 * i], acc[2 * i + 1]); vv[i] = pack_bf16(acc[64 + 2 * i], acc[65 + 2 * i]); }
        const uint32_t rB = sb + 4 * SLOT + wg * 4 * KVT + rowq;
        auto dump = [&](int hp) {
          const uint32_t kb = rB + 2048 + (hp ^ wg) * 2 * KVT;
#pragma unroll
          for (int jp = 0; jp < 4; ++jp) {
            stsm_x4(kb + (X ^ (jp << 5)), kq[16 * hp + 4 * jp], kq[16 * hp + 4 * jp + 1], kq[16 * hp + 4 * jp + 2], kq[16 * hp + 4 * jp + 3]);
            stsm_x4(kb + KVT + (X ^ (jp << 5)), vv[16 * hp + 4 * jp], vv[16 * hp + 4 * jp + 1], vv[16 * hp + 4 * jp + 2], vv[16 * hp + 4 * jp + 3]);
          }
          if (cu == 3) {
            const uint32_t kd = rB + 2048 + 32768 + (1 - hp) * 2 * KVT;
#pragma unroll
            for (int jp = 0; jp < 4; ++jp) {
              stsm_x4(kd + (X ^ (jp << 5)), kq[16 * hp + 4 * jp], kq[16 * hp + 4 * jp + 1], kq[16 * hp + 4 * jp + 2], kq[16 * hp + 4 * jp + 3]);
              stsm_x4(kd + KVT + (X ^ (jp << 5)), vv[16 * hp + 4 * jp], vv[16 * hp + 4 * jp + 1], vv[16 * hp + 4 * jp + 2], vv[16 * hp + 4 * jp + 3]);
            }
            if (hp) asm volatile("bar.arrive 15, 64;" ::: "memory"); else asm volatile("bar.arrive 9, 64;" ::: "memory");
          }
          asm volatile("bar.arrive %0, 224;" :: "r"(hp ? 13 + (cu >> 2) : 8 + (cu & 4)) : "memory");
        };
        uint4* const hbuf = g_halo + ((c.rb * 8 + g) * 2 + (layer >> 1)) * 512 + lane;
        if (cu < 4) {
          nbar<7, 256>();
          dump(0);
        }
#pragma unroll
        for (int i = 16; i < 32; ++i) { kq[i] = pack_bf16(acc[2 * i], acc[2 * i + 1]); vv[i] = pack_bf16(acc[64 + 2 * i], acc[65 + 2 * i]); }
        if (cu >= 4) {
          if (cu == 7) {
#pragma unroll
            for (int jp = 0; jp < 8; ++jp) {
              st_relaxed4(hbuf + jp * 32, ~kq[4 * jp], ~kq[4 * jp + 1], ~kq[4 * jp + 2], ~kq[4 * jp + 3]);
              st_relaxed4(hbuf + 256 + jp * 32, ~vv[4 * jp], ~vv[4 * jp + 1], ~vv[4 * jp + 2], ~vv[4 * jp + 3]);
            }
          }
          dump(0);
          dump(1);
        }
        PROFT(tid_ == 128, layer * 16 + 2);
        constexpr float SC = 0.17677669529663687f * L2E;
        const float fA0 = rjA0 * rs0 * SC, fB0 = rjB0 * rs0 * SC, fA1 = rjA1 * rs1 * SC, fB1 = rjB1 * rs1 * SC;
        const float bA0 = (m0 + wrow0) ? 0.f : -1e30f, bB = sel ? bA0 : 0.f;
        const uint32_t pA_ = e ? 0x1044u : 0x4410u, pB_ = e ? 0x3244u : 0x4432u, pLo = sel ? pB_ : 0x4444u, pHi = sel ? 0x4444u : pB_;
        const uint32_t KX = ((lane >> 3) ^ (lane & 7)) << 4;
        Q_DONE();
        if (cu == 0) {
          nbar<11, 64>();
        } else if (cu == 4) {
          uint4 hv[16];
          if (c.rb > 0) {
            uint32_t n = 0;
#pragma unroll 1
            while (true) {
              uint32_t mn = 0xFFFFFFFFu;
#pragma unroll
              for (int i = 0; i < 16; ++i) hv[i] = ld_relaxed4(hbuf - 16 * 512 + i * 32);
#pragma unroll
              for (int i = 0; i < 16; ++i) mn = __vimin3_u32(__vimin3_u32(mn, hv[i].x, hv[i].y), hv[i].z, hv[i].w);
              if (__all_sync(0xffffffffu, mn != 0u)) break;
              if (++n > (1u << 20)) { g_err = 4u; break; }
            }
          } else {
#pragma unroll
            for (int i = 0; i < 16; ++i) hv[i] = make_uint4(~0u, ~0u, ~0u, ~0u);
          }
          nbar<10, 64>();
#pragma unroll
          for (int i = 0; i < 16; ++i)
            stsm_x4(rB - 4 * KVT + (((i >> 2) & 1) * 2 + (i >> 3)) * KVT + (X ^ ((i & 3) << 5)), ~hv[i].x, ~hv[i].y, ~hv[i].z, ~hv[i].w);
          asm volatile("bar.arrive 11, 64;" ::: "memory");
          nbar<9, 64>();
        } else {
          nbar_dyn(8 + (cu & 4), 224);
        }
        PROFT(tid_ == 128, layer * 16 + 5);
        PROFT(lane == 0 && layer == PL, 136 + cw);
        auto attend = [&](int hp) {
          const uint32_t qad = sb + (XS + 1 - hp) * SLOT + rowo, kt = rB + 2 * (hp ^ wg) * KVT - (lane & 8) * 128, vt = rB + (2 * (hp ^ wg) + 1) * KVT;
          __syncwarp();
          uint32_t kb[2][2][4], vb[2][2][2][4];
#pragma unroll
          for (int h = 0; h < 2; ++h)
#pragma unroll
            for (int nt = 0; nt < 2; ++nt) ldsm_x4(kb[h][nt][0], kb[h][nt][1], kb[h][nt][2], kb[h][nt][3], kt + nt * 1024 + (KX ^ (h << 6)));
#pragma unroll
          for (int ks = 0; ks < 2; ++ks)
#pragma unroll
            for (int np = 0; np < 2; ++np)
#pragma unroll
              for (int h = 0; h < 2; ++h)
                ldsm_x4_t(vb[h][ks][np][0], vb[h][ks][np][1], vb[h][ks][np][2], vb[h][ks][np][3], vt + ks * 2048 + (X ^ (h << 6) ^ (np << 5)));
          if (hp == 0 && lane == 0) release2(bar + B_E3);
          if (DB1 == 1 && hp == 0 && cu < 4) dump(1);
          float la[2][2], lb[2][2], mx[2][2], sm[2][2];
#pragma unroll
          for (int h = 0; h < 2; ++h) {
            const int qo = 32 + 16 * hp + 8 * h, ko = 16 * hp + 8 * h;
            float sc[4][4];
#pragma unroll
            for (int nt = 0; nt < 4; ++nt) {
              sc[nt][0] = sc[nt][1] = sc[nt][2] = sc[nt][3] = 0.f;
#pragma unroll
              for (int ks = 0; ks < 2; ++ks)
                mma_bf16(sc[nt], kq[qo + 4 * ks], kq[qo + 4 * ks + 1], kq[qo + 4 * ks + 2], kq[qo + 4 * ks + 3],
                         nt < 2 ? kb[h][nt & 1][2 * ks] : kq[ko + 4 * ks + (nt & 1)], nt < 2 ? kb[h][nt & 1][2 * ks + 1] : kq[ko + 4 * ks + 2 + (nt & 1)]);
            }
            la[h][0] = fmaf(e ? sc[1][1] : sc[1][0], fA0, bA0);
            lb[h][0] = fmaf(sel ? (e ? sc[0][1] : sc[0][0]) : (e ? sc[2][1] : sc[2][0]), fB0, bB);
            la[h][1] = (e ? sc[2][3] : sc[2][2]) * fA1;
            lb[h][1] = fmaf(sel ? (e ? sc[1][3] : sc[1][2]) : (e ? sc[3][3] : sc[3][2]), fB1, bB);
            mx[h][0] = fmaxf(la[h][0], lb[h][0]); mx[h][1] = fmaxf(la[h][1], lb[h][1]);
          }
#pragma unroll
          for (int o = 1; o <= 2; o <<= 1)
#pragma unroll
            for (int h = 0; h < 2; ++h)
#pragma unroll
              for (int r = 0; r < 2; ++r) mx[h][r] = fmaxf(mx[h][r], __shfl_xor_sync(0xffffffffu, mx[h][r], o));
          float oa[2][4][4];
#pragma unroll
          for (int h = 0; h < 2; ++h) {
#pragma unroll
            for (int r = 0; r < 2; ++r) { la[h][r] = ex2(la[h][r] - mx[h][r]); lb[h][r] = ex2(lb[h][r] - mx[h][r]); sm[h][r] = la[h][r] + lb[h][r]; }
            const uint32_t p0 = pack_bf16(la[h][0] * rjA0, lb[h][0] * rjB0), p1 = pack_bf16(la[h][1] * rjA1, lb[h][1] * rjB1);
            const uint32_t a00 = __byte_perm(p0, 0u, pLo), a02 = __byte_perm(p0, 0u, pA_), a03 = __byte_perm(p1, 0u, pLo);
            const uint32_t a10 = __byte_perm(p0, 0u, pHi), a11 = __byte_perm(p1, 0u, pA_), a13 = __byte_perm(p1, 0u, pHi);
#pragma unroll
            for (int i = 0; i < 4; ++i) {
              oa[h][i][0] = oa[h][i][1] = oa[h][i][2] = oa[h][i][3] = 0.f;
              mma_bf16(oa[h][i], a00, 0u, a02, a03, vb[h][0][i >> 1][2 * (i & 1)], vb[h][0][i >> 1][2 * (i & 1) + 1]);
              mma_bf16(oa[h][i], a10, a11, 0u, a13, vb[h][1][i >> 1][2 * (i & 1)], vb[h][1][i >> 1][2 * (i & 1) + 1]);
            }
          }
#pragma unroll
          for (int o = 1; o <= 2; o <<= 1)
#pragma unroll
            for (int h = 0; h < 2; ++h)
#pragma unroll
              for (int r = 0; r < 2; ++r) sm[h][r] += __shfl_xor_sync(0xffffffffu, sm[h][r], o);
          mbar_wait(bar + (hp ? B_XOLD2 : B_XOLD), 1);
#pragma unroll
          for (int jp = 0; jp < 4; ++jp) ldsm_x4(xo[16 * hp + 4 * jp], xo[16 * hp + 4 * jp + 1], xo[16 * hp + 4 * jp + 2], xo[16 * hp + 4 * jp + 3], qad + (X ^ (jp << 5)));
#pragma unroll
          for (int h = 0; h < 2; ++h) {
            const float i0 = rcp(sm[h][0]), i1 = rcp(sm[h][1]);
#pragma unroll
            for (int np = 0; np < 2; ++np)
              stsm_x4(qad + (X ^ (h << 6) ^ (np << 5)),
                      pack_bf16(oa[h][2 * np][0] * i0, oa[h][2 * np][1] * i0), pack_bf16(oa[h][2 * np][2] * i1, oa[h][2 * np][3] * i1),
                      pack_bf16(oa[h][2 * np + 1][0] * i0, oa[h][2 * np + 1][1] * i0), pack_bf16(oa[h][2 * np + 1][2] * i1, oa[h][2 * np + 1][3] * i1));
          }
          __syncwarp();
          slab_out_half(sb + (XS + 1 - hp) * SLOT, g_o + (size_t)m0 * D_ + g * 128 + hp * 64, wrow0, lane, hp);
          __syncwarp();
          if (lane == 0) mbar_arrive(bar + (hp ? B_ODONE : B_OH1));
          PROFT(lane == 0 && layer == PL && hp == 0, 128 + cw);
        };
        attend(0);
        if (DB1 == 2 && cu < 4) dump(1);
        if (cu == 4) nbar<15, 64>();
        else if (cu != 0) nbar_dyn(13 + (cu >> 2), 224);
        attend(1);
      } else {
#pragma unroll
        for (int i = 0; i < 32; ++i) kq[i] = pack_bf16(acc[2 * i], acc[2 * i + 1]);
        if (cu < 4) nbar<7, 256>();
        {
          const uint32_t vb = sb + (5 + 3 * wg) * SLOT + (rowq >> 1) + ((lchk ^ ((lane & 7) >> 1)) << 4);
#pragma unroll
          for (int jp = 8; jp < 16; ++jp)
            stsm_x4((vb ^ ((jp & 1) << 5)) + ((jp >> 1) & 3) * 4096,
                    pack_bf16(acc[8 * jp], acc[8 * jp + 1]), pack_bf16(acc[8 * jp + 2], acc[8 * jp + 3]),
                    pack_bf16(acc[8 * jp + 4], acc[8 * jp + 5]), pack_bf16(acc[8 * jp + 6], acc[8 * jp + 7]));
        }
        PROFT(tid_ == 128, layer * 16 + 2);
        Q_DONE();
        const uint32_t pA = sb + (3 + 3 * wg) * SLOT + (rowo & 8191);
        float sc0 = rs0 * L2E, sc1 = rs1 * L2E;
        const uint32_t wa0 = sb + SM_WPHI + lrow * 80 + lchk * 16;
        const uint32_t wu = c.cu >> 2, par = (layer >> 1) & 1;
        float p[2][4][4];
        uint32_t raw[2][4][4], ph[2][4][4];
        float kva[20], oa[2][20];
        auto kv_start = [&](int hp) {
#pragma unroll
          for (int h = 0; h < 2; ++h)
#pragma unroll
            for (int cp = 0; cp < 4; ++cp)
              stsm_x4(pA + hp * 16384 + h * 8192 + (X ^ (cp << 5)), ph[h][cp][0], ph[h][cp][1], ph[h][cp][2], ph[h][cp][3]);
          PROFT(tid_ == 128, layer * 16 + 11);
          fence_async_smem();
          nbar<1, 256>();
          const uint32_t hu = 2 * hp + wu;
          const uint32_t dP = (((sb + 3 * SLOT + hu * 8192) & 0x3FFFF) >> 4) | (512u << 16);
          const uint32_t dV = (((sb + 5 * SLOT + hu * 4096) & 0x3FFFF) >> 4) | (((SM_SD - 5 * SLOT - hu * 4096) >> 4) << 16);
          wgmma_fence();
#pragma unroll
          for (int ks = 0; ks < 8; ++ks)
            wgmma_n40_tt(kva, desc64(dP + (ks >> 2) * 3072 + (ks & 3) * 128, 0x40000040u),
                         desc64(dV + (ks >> 2) * (3072u - (2816u << 16)) + (ks & 3) * 64, 0x80000020u), ks != 0);
          wgmma_commit();
        };
        auto kv_end = [&](int hp) {
          wgmma_wait<0>();
#pragma unroll
          for (int i = 0; i < 20; ++i) asm volatile("" : "+f"(kva[i]) :: "memory");
          nbar_dyn(3 + wu, 128);
          PROFT(tid_ == 128, layer * 16 + 12);
          const bool od = lane & 1;
#pragma unroll
          for (int i = 0; i < 4; ++i)
            sts128(sb + (3 + hp) * SLOT + (cw * 128 + i * 32 + lane) * 16,
                   make_uint4(__float_as_uint(kva[4 * i]), __float_as_uint(kva[4 * i + 1]), __float_as_uint(kva[4 * i + 2]),
                              __float_as_uint(od == (i >= 2) ? 1.f : kva[4 * i + 3])));
          sts128(sb + (6 + hp) * SLOT + wg * 8192 + (wq * 32 + lane) * 16,
                 make_uint4(__float_as_uint(od ? kva[11] : kva[3]), __float_as_uint(od ? kva[15] : kva[7]), __float_as_uint(od ? kva[18] : kva[16]), __float_as_uint(1.f)));
          fence_async_smem();
          __syncwarp();
          if (lane == 0) mbar_arrive(bar + B_KVDONE - hp * 32);
          PROFT(tid_ == 128, layer * 16 + 3);
        };
        const uint4* const kvg = g_kv + (g * 2 + (layer >> 1)) * 2560 + cw * 128 + lane;
        uint4 u[5];
        auto kv_load = [&](int hp) {
#pragma unroll
          for (int i = 0; i < 4; ++i) u[i] = ld_relaxed4(kvg + hp * 1280 + i * 32);
          u[4] = ld_relaxed4(kvg + hp * 1280 + 1024 - cw * 96);
        };
        auto o_start = [&](int hp, const uint32_t (&pq)[2][4][4]) {
          PROFT(tid_ == 128 && hp == 0, layer * 16 + 10);
          if (hp == 0) mbar_wait(bar + B_KVDONE - 32, par);
          const bool od = lane & 1;
          uint32_t n = 0;
#pragma unroll 1
          while (!__all_sync(0xffffffffu, (od ? u[2].w : u[0].w) == 0x41800000u && (od ? u[3].w : u[1].w) == 0x41800000u && u[4].w == 0x41800000u)) {
#pragma unroll 1
            while (__any_sync(0xffffffffu, u[4].w < KVTH) && ++n < (1u << 20)) u[4].w = ld_relaxed(&kvg[hp * 1280 + 1024 - cw * 96].w);
            if (++n > (1u << 20)) { g_err = 6u; break; }
            kv_load(hp);
          }
          PROFT(tid_ == 128 && hp == 0, layer * 16 + 5);
          if (!od) { u[0].w = u[4].x; u[1].w = u[4].y; } else { u[2].w = u[4].x; u[3].w = u[4].y; }
#pragma unroll
          for (int i = 0; i < 4; i += 2)
            stsm_x4(sb + (5 + 3 * hp) * SLOT + rowo + (X ^ ((i & 2) << 4)),
                    pack_bf16(__uint_as_float(u[i].x), __uint_as_float(u[i].y)), pack_bf16(__uint_as_float(u[i].z), __uint_as_float(u[i].w)),
                    pack_bf16(__uint_as_float(u[i + 1].x), __uint_as_float(u[i + 1].y)), pack_bf16(__uint_as_float(u[i + 1].z), __uint_as_float(u[i + 1].w)));
          const uint32_t z2 = pack_bf16(__uint_as_float(u[4].z), __uint_as_float(u[4].z));
          if (t < 2) sts128(sb + (5 + 3 * hp) * SLOT + (wrow0 + gq + 8 * t) * 128 + ((4 ^ gq) << 4), make_uint4(z2, z2, z2, z2));
          fence_async_smem();
          nbar<1, 256>();
          PROFT(tid_ == 128 && hp == 1, layer * 16 + 4);
          const uint32_t dK = (((sb + (5 + 3 * hp) * SLOT) & 0x3FFFF) >> 4) | (512u << 16);
          wgmma_fence();
#pragma unroll
          for (int ks = 0; ks < 4; ++ks) {
#pragma unroll
            for (int hh = 0; hh < 2; ++hh) wgmma_n40_rs(oa[hh], pq[hh][ks], D128(dK + hh * 512 + ks * 128), ks != 0);
          }
          wgmma_commit();
        };
        auto o_end = [&](int hp) {
          wgmma_wait<0>();
#pragma unroll
          for (int i = 0; i < 20; ++i) asm volatile("" : "+f"(oa[0][i]), "+f"(oa[1][i]) :: "memory");
#pragma unroll
          for (int hh = 0; hh < 2; ++hh) {
            const float i0 = rcp(oa[hh][16] + 1e-6f), i1 = rcp(oa[hh][18] + 1e-6f);
            const uint32_t qad = sb + (3 + hp) * SLOT + rowo, hx = hh << 6;
#pragma unroll
            for (int np = 0; np < 2; ++np)
              stsm_x4(qad + (X ^ hx ^ (np << 5)),
                      pack_bf16(oa[hh][8 * np] * i0, oa[hh][8 * np + 1] * i0), pack_bf16(oa[hh][8 * np + 2] * i1, oa[hh][8 * np + 3] * i1),
                      pack_bf16(oa[hh][8 * np + 4] * i0, oa[hh][8 * np + 5] * i0), pack_bf16(oa[hh][8 * np + 6] * i1, oa[hh][8 * np + 7] * i1));
          }
          __syncwarp();
          slab_out_half(sb + (3 + hp) * SLOT, g_o + (size_t)m0 * D_ + g * 128 + hp * 64, wrow0, lane, hp);
          __syncwarp();
          if (lane == 0) mbar_arrive(bar + (hp ? B_ODONE : B_OH1));
        };
#define XO_LOAD() \
        mbar_wait(bar + B_XOLD, 0); \
        mbar_wait(bar + B_XOLD2, 0); \
        _Pragma("unroll") for (int jp = 0; jp < 8; ++jp) \
          ldsm_x4(xo[4 * jp], xo[4 * jp + 1], xo[4 * jp + 2], xo[4 * jp + 3], sb + (XS + 1 - (jp >> 2)) * SLOT + rowo + (X ^ ((jp & 3) << 5)));
#define SC_RELOAD() \
        sc0 = __uint_as_float(lds_vol(sb + SM_RS + (16 + wrow0 + gq) * 4)) * L2E; sc1 = __uint_as_float(lds_vol(sb + SM_RS + (24 + wrow0 + gq) * 4)) * L2E;
        __syncwarp();
        phi_proj<0>(p, kq, wa0);
        phi_exp(raw[0], p[0], sc0, sc1);
        phi_exp(raw[1], p[1], sc0, sc1);
        phi_proj<16>(p, kq, wa0 + 5120);
        phi_norm<0>(ph, raw, kq, wa0, sc0, sc1, rs0, rs1);
        kv_start(0);
        phi_exp(raw[0], p[0], sc0, sc1);
        kv_end(0);
        if (RL & 1) { SC_RELOAD(); }
        XO_LOAD();
        phi_exp(raw[1], p[1], sc0, sc1);
        phi_proj<32>(p, kq, wa0);
        phi_norm<16>(ph, raw, kq, wa0 + 5120, sc0, sc1, rs0, rs1);
        kv_start(1);
        if (lane == 0) release2(bar + B_E3);
        phi_exp(raw[0], p[0], sc0, sc1);
        kv_end(1);
        if (RL & 2) { SC_RELOAD(); }
        kv_load(0);
        phi_exp(raw[1], p[1], sc0, sc1);
        phi_proj<48>(p, kq, wa0 + 5120);
        phi_norm<32>(ph, raw, kq, wa0, sc0, sc1, 1.f, 1.f);
        o_start(0, ph);
        phi_exp(raw[0], p[0], sc0, sc1);
        o_end(0);
        SC_RELOAD();
        kv_load(1);
        phi_exp(raw[1], p[1], sc0, sc1);
        phi_norm<48>(ph, raw, kq, wa0 + 5120, sc0, sc1, 1.f, 1.f);
        o_start(1, ph);
        o_end(1);
      }
      __syncwarp();
      PROFT(lane == 0 && layer == PL, 216 + cw);
      if (lane == 0) mbar_arrive(bar + B_EPI);
      PROFT(tid_ == 128, layer * 16 + 6);
    }
    {
      PHASE_CTX();
      const uint32_t wu = c.cu >> 2;
      const uint32_t dA0 = (((sb + wu * 8192) & 0x3FFFF) >> 4) | (1u << 16), dB0 = ((sb & 0x3FFFF) >> 4) | (512u << 16);
#pragma unroll
      for (int i = 0; i < 32; ++i) { acc[128 + 2 * i] = bf_lo(xo[i]); acc[129 + 2 * i] = bf_hi(xo[i]); }
      nbar_dyn(3 + wg, 128);
      uint64_t ta = (layer & 1) ? WO_A1 : WO_A0, tw = (layer & 1) ? WO_B1 : WO_B0;
#pragma unroll 1
      for (int i = 0; i < 16; ++i) {
        bool rel = i > 0 && i < 12;
        if (DRY && rel && !__all_sync(0xffffffffu, mbar_test_wait(bar + B_FULLT + i * 8, layer & 1))) {
          wgmma_wait<0>();
          if (elected) release2(bar + B_CONS + (i - 1) * 8);
          rel = false;
        }
        mbar_wait(bar + B_FULLT + i * 8, layer & 1);
        PROFT(tid_ == 128 && layer == PL, 160 + i);
        const uint32_t da = dA0 + ((uint32_t)ta & 15) * 1024, db = dB0 + ((uint32_t)tw & 15) * 1024;
        ta >>= 4; tw >>= 4;
        wgmma_fence();
#pragma unroll
        for (int k = 0; k < 4; ++k) wgmma_n128(acc, D128(da + k * 2), D128(db + k * 128), 1);
        wgmma_commit();
        if (i == 0) {
          if (elected) {
            release2(bar + B_E2);
          }
        } else {
          wgmma_wait<1>();
          if (elected && rel) release2(bar + B_CONS + (i - 1) * 8);
          if (elected && (unsigned)(i - 13) < 2u && layer + 1 < NLAYERS) release2(bar + B_EMPTYS + (i - 13) * 8);
        }
      }
      const bool last = layer == NLAYERS - 1;
      wgmma_wait<0>();
#pragma unroll
      for (int i = 128; i < 192; ++i) asm volatile("" : "+f"(acc[i]) :: "memory");
      if (elected && !last) release2(bar + B_EMPTYS + 16);
      PROFT(tid_ == 128, layer * 16 + 7);
#pragma unroll
      for (int jp = 0; jp < 4; ++jp)
        stsm_x4(sb + XS * SLOT + rowo + (X ^ (jp << 5)),
                pack_bf16(acc[128 + 8 * jp], acc[129 + 8 * jp]), pack_bf16(acc[130 + 8 * jp], acc[131 + 8 * jp]),
                pack_bf16(acc[132 + 8 * jp], acc[133 + 8 * jp]), pack_bf16(acc[134 + 8 * jp], acc[135 + 8 * jp]));
      if (last) {
        __syncwarp();
        slab_out_half(sb + XS * SLOT, c.out + (size_t)m0 * D_ + g * 128, wrow0, lane);
        X_H1();
        __syncwarp();
        slab_out_half(sb + (XS + 1) * SLOT, c.out + (size_t)m0 * D_ + g * 128 + 64, wrow0, lane);
        __syncwarp();
        if (lane == 0) mbar_arrive(bar + B_XDONE);
        PROFT(tid_ == 128, layer * 16 + 24);
        break;
      }
      __syncwarp();
      slab_out_half(sb + XS * SLOT, g_x + (size_t)m0 * D_ + g * 128, wrow0, lane, true);
      __syncwarp();
      if (lane == 0) mbar_arrive(bar + B_XH0);
      nbar_dyn(3 + wu, 128);
    }
  }
}

__device__ __forceinline__ void flag_fetch(uint32_t bar, uint32_t cp, const unsigned int* f) {
  asm volatile("{\n.reg .pred p;\nelect.sync _|p, 0xffffffff;\n@p mbarrier.expect_tx.relaxed.cta.shared::cta.b64 [%2], 64;\n"
               "@p cp.async.bulk.shared::cluster.global.mbarrier::complete_tx::bytes [%0], [%1], 64, [%2];\n}\n"
               ::"r"(cp), "l"(f), "r"(bar + 128) : "memory");
}
__device__ __forceinline__ void src_wait_async(uint32_t bar, uint32_t cp, const unsigned int* f, unsigned int target, int kb, uint32_t& ready, int lane) {
  uint32_t n = 0;
#pragma unroll 1
  while (true) {
    ready |= __ballot_sync(0xffffffffu, (int)(lds_vol(cp + (lane & 15) * 4) - target) >= 0);
    if ((ready >> kb) & 1) break;
    if (n > (1u << 20)) { g_err = 5u; break; }
    if ((n++ & PMOD) == 0) flag_fetch(bar, cp, f);
    __nanosleep(PSL);
  }
}

__device__ __forceinline__ int kblock0(int i, int g) {
  const int j = i >> 1, p = max(g, NCOM) + j - NCOM;
  return (j < NCOM ? j : p < 8 ? p : p - 8 + NCOM) * 2 + (i & 1);
}

#define WOORD 0xFDB9753ECA864210ull
__device__ __forceinline__ int wo_kblock(int m, int g) { return (2 * g + (int)((WOORD >> (4 * m)) & 15)) & 15; }

__global__ void __cluster_dims__(2, 1, 1) __launch_bounds__(384, 1)
mega_kernel(const __grid_constant__ CUtensorMap tm_x0, const __grid_constant__ CUtensorMap tm_x,
            const __grid_constant__ CUtensorMap tm_o,
            const __grid_constant__ CUtensorMap tm_wA, const __grid_constant__ CUtensorMap tm_wB,
            const __grid_constant__ CUtensorMap tm_woA, const __grid_constant__ CUtensorMap tm_woB,
            const bf16* __restrict__ wA, const bf16* __restrict__ wB,
            const bf16* __restrict__ wphi, bf16* __restrict__ out) {
  extern __shared__ uint8_t smem_raw[];
  const uint32_t sb = (smem_u32(smem_raw) + 1023u) & ~1023u;
  const uint32_t bar = sb + SM_BAR;
  const int warp = __shfl_sync(0xffffffffu, threadIdx.x >> 5, 0), lane = threadIdx.x & 31;
  const int cr = blockIdx.x & 1;
  const int g = (blockIdx.x >> 1) & 7;
  const int rb = (blockIdx.x >> 4) * 2 + cr;
  const int m0 = rb * 128;

  if (warp < 4) {
    asm volatile("setmaxnreg.dec.sync.aligned.u32 40;");
    asm volatile("barrier.cluster.arrive.relaxed.aligned;" ::: "memory");
    const unsigned int epoch = warp ? ld_relaxed(&g_epoch) : 0u;
    if (warp) cluster_wait();
    unsigned int xbase = epoch * NLAYERS;
    const unsigned int cbase = epoch * 16u;
    auto wo_a = [&](int layer) {
      uint64_t ts = ((layer & 1) ? WO_A1 : WO_A0) >> 8, td = ((layer & 1) ? WO_DA1 : WO_DA0) >> 8, tk = WOORD >> 8;
      uint32_t ready = 0u;
#pragma unroll 1
      for (int m = 2; m < 16; ++m) {
        const int kb = (2 * g + (uint32_t)tk) & 15;
        uint32_t dst = sb + ((uint32_t)ts & 15) * SLOT, fb = bar + B_FULLT + m * 8, eb = bar + B_CONS + ((uint32_t)td & 15) * 8;
        int kc = kb * 64;
        ts >>= 4; td >>= 4; tk >>= 4;
        if (!((ready >> kb) & 1)) {
          PROFT(m == 2 && lane == 0, 64 + layer * 16 + 2);
          if (EP && m > EP) src_wait_async(bar, bar + B_FLG, g_of + rb * 32, xbase + layer + 1, kb, ready, lane);
          src_wait<0>(g_of + rb * 32, xbase + layer + 1, 1u << kb, ready, lane);
          fence_async_all();
        }
        asm volatile("" : "+r"(dst), "+r"(fb), "+r"(eb), "+r"(kc));
        mbar_wait_u(eb, layer & 1);
        tma_2d_e(dst, &tm_o, kc, m0, fb);
        if (EP && m >= EP && (ready & 0xFFFFu) != 0xFFFFu) flag_fetch(bar, bar + B_FLG, g_of + rb * 32);
        PROFT(lane == 0 && layer == PL, 176 + m);
      }
    };
    auto wo_w = [&](int layer) {
      const CUtensorMap* tx = layer == 0 ? &tm_x0 : &tm_x;
      const CUtensorMap* two = (layer & 1) ? &tm_woB : &tm_woA;
      uint64_t ts = (layer & 1) ? WO_B1 : WO_B0, td = (layer & 1) ? WO_DB1 : WO_DB0, tk = WOORD;
      uint32_t pb = 0;
      fence_async_all();
      mbar_wait_u(bar + B_R0, layer & 1);
      expect_tx_e(bar + B_XOLD, 16384);
      tma_2d_e(sb + (XS + 1) * SLOT, tx, g * 128, m0, bar + B_XOLD);
#pragma unroll 1
      for (int m = 0; m < 16; ++m) {
        uint32_t dst = sb + ((uint32_t)ts & 15) * SLOT + cr * 8192, fb = bar + B_FULLT + m * 8, eb = bar + B_CONS + ((uint32_t)td & 15) * 8;
        int kc = ((2 * g + (uint32_t)tk) & 15) * 64;
        ts >>= 4; td >>= 4; tk >>= 4;
        asm volatile("" : "+r"(dst), "+r"(fb), "+r"(eb), "+r"(kc));
        if (eb != pb) mbar_wait_u(eb, layer & 1);
        pb = eb;
        tma_2d_mc_e(dst, two, g * 128 + cr * 64, kc, fb);
        expect_tx_e(fb, m < 2 ? 16384 : 32768);
        PROFT(lane == 0 && layer == PL, 144 + m);
        if (m == ((layer & 1) ? XB2 : 0)) {
          expect_tx_e(bar + B_XOLD2, 16384);
          tma_2d_e(sb + XS * SLOT, tx, g * 128 + 64, m0, bar + B_XOLD2);
        }
      }
    };
    if (warp == 0) {
      cluster_wait();
      PROFT(lane == 0, 125);
#pragma unroll 1
      for (int layer = 0; layer < NLAYERS; ++layer) {
        const CUtensorMap* tx = layer == 0 ? &tm_x0 : &tm_x;
        const CUtensorMap* tw = (layer & 1) ? &tm_wB : &tm_wA;
        uint32_t s = layer == 0, u = 0, ready = layer == 0 ? 0xFFFFu : 0u;
#pragma unroll 1
        for (int i = s; i < 16; ++i) {
          const int kb = layer == 0 ? kblock0(i, g) : wo_kblock(i, g), kc = kb * 64;
          const uint32_t fb = bar + B_FULLS + s * 8;
          const uint32_t kd = sb + (((QK >> (4 * s)) & 15) + cr) * SLOT, qd = sb + ((QQ >> (4 * s)) & 15) * SLOT + cr * 8192;
          const uint32_t need = 1u << kb;
          const bool ext = i >= 2 || layer == 0, early = ext && (ready & need) == need;
          mbar_wait_u(bar + B_EMPTYS + s * 8, (u + (s ? layer : 0) + 1) & 1);
          if (early) tma_2d_e(sb + ((QA >> (4 * s)) & 15) * SLOT, tx, kc, m0, fb);
          tma_2d_mc_e(kd, tw, 1024 + cr * 1024 + g * 128, kc, fb);
          tma_2d_mc_e(kd + 8192, tw, 1024 + cr * 1024 + g * 128 + 64, kc, fb);
          tma_2d_mc_e(qd, tw, g * 128 + cr * 64, kc, fb);
          expect_tx_e(fb, ext ? 65536 : 49152);
          PROFT(lane == 0 && layer == 0 && i == 1, 31);
          if (layer == 0 && i == 2) {
            mbar_wait_u(bar + B_FULLS, 0);
            tma_pf_e(&tm_x0, g * 128, m0);
            tma_pf_e(&tm_x0, g * 128 + 64, m0);
          }
          if (layer < 2 && i >= PFS) {
            const int j = i - PFS;
            if (j < 2) tma_pf_e(layer ? &tm_woB : &tm_woA, g * 128 + j * 64, rb * 64);
            else if (j < 8 && layer == 0) tma_pf_e(&tm_wB, ((j >> 1) - 1) * 1024 + g * 128 + (j & 1) * 64, rb * 64);
          }
          if (ext && !early) {
            PROFT(i == 2 && lane == 0, 64 + layer * 16 + 0);
            if (XEP) src_wait_async(bar, sb + SM_RS + 640, g_xf + rb * 32, xbase + layer + 1, kb, ready, lane);
            else src_wait<0>(g_xf + rb * 32, xbase + layer + 1, need, ready, lane);
            PROFT(i == 2 && lane == 0, 64 + layer * 16 + 1);
            fence_async_all();
            tma_2d_e(sb + ((QA >> (4 * s)) & 15) * SLOT, tx, kc, m0, fb);
          }
          if (++s == 3) { s = 0; ++u; }
        }
        if (layer == 0) xbase = ld_relaxed(&g_epoch) * NLAYERS;
        wo_a(layer);
      }
    } else {
      if (warp >= 2) {
        const int h2 = threadIdx.x - 64;
#pragma unroll 1
        for (int i = h2; i < 512; i += 64)
          asm volatile("cp.async.cg.shared.global [%0], [%1], 16;" ::"r"(sb + SM_WPHI + (i >> 2) * 80 + (i & 3) * 16), "l"(wphi + (size_t)g * 4096 + i * 8) : "memory");
        if (h2 < 16) sts_f(sb + SM_RS + h2 * 4, 0.f);
        if (h2 < 32) sts_f((h2 < 16 ? bar + B_FLG : sb + SM_RS + 576) + h2 * 4, __uint_as_float(xbase));
        if (rb >= CG0) mbar_wait_u(bar + B_FULLS + (rb >= CG1 ? 8 : 0), 0);
        if (CPF && h2 < 4) asm volatile("cp.async.bulk.prefetch.tensor.2d.L2.global.tile [%0, {%1, %2}];" ::"l"(&tm_wA), "r"((h2 & 2) * 1024 + g * 128 + (h2 & 1) * 64), "r"(rb * 64) : "memory");
#pragma unroll 1
        for (int wi = 0; wi < 3; ++wi) {
          float sA[8];
          colsum_load(wA, rb, g, warp - 2 + 2 * wi, lane, sb + SM_BP + (warp - 2) * 6144, sA);
          colsum_red(g_cs + (epoch & 1) * 6144, g, warp - 2 + 2 * wi, lane, sA);
        }
#pragma unroll 1
        for (int i = h2; i < 320; i += 64) g_kv[(g * 16 + rb) * 320 + i] = make_uint4(0u, 0u, 0u, 0u);
        fence_async_all();
        nbar<5, 64>();
        if (h2 == 0) flag_add(&g_csflag[g].v);
        PROFT(h2 == 0, 242);
      }
      if (warp == 1) {
        if (lane >= 27) {
          const CUtensorMap* tm = lane == 27 ? &tm_o : lane == 28 ? &tm_wB : lane == 29 ? &tm_woA : lane == 30 ? &tm_woB : &tm_x;
          asm volatile("prefetch.tensormap [%0];" ::"l"(tm) : "memory");
        }
        if (lane == 0) {
#pragma unroll 1
          for (int e = 0;; ++e) {
            if (e > 0 && e < NLAYERS) {
              mbar_wait(bar + B_XH0, (e - 1) & 1);
              flag_set(g_xf + rb * 32 + 2 * g, xbase + e + 1);
            }
            mbar_wait(bar + B_XDONE, e & 1);
            PROFT(e < 4, 64 + e * 16 + 4);
            if (e == NLAYERS) {
              if (blockIdx.x == 0) g_epoch = epoch + 1;
              break;
            }
            PROFT(e < 4, 64 + e * 16 + 5);
            flag_set(g_xf + rb * 32 + 2 * g + 1, xbase + e + 1);
            PROFT(e < 4, 64 + e * 16 + 7);
            if ((e & 1) == 0) {
#pragma unroll 1
              for (int hp = 0; hp < 2; ++hp) {
                uint4* kvl = g_kv + ((g * 2 + (e >> 1)) * 2 + hp) * 1280;
                mbar_wait(bar + B_KVDONE - hp * 32, (e >> 1) & 1);
                PROFT(e == PL, 243 + hp * 4);
                bulk_red_add(kvl + rb * 64, sb + (3 + hp) * SLOT + rb * 1024, 16384 - rb * 1024);
                if (rb) bulk_red_add(kvl, sb + (3 + hp) * SLOT, rb * 1024);
                bulk_red_add(kvl + 1024, sb + (6 + hp) * SLOT, 2048);
                bulk_red_add(kvl + 1152, sb + (6 + hp) * SLOT + 8192, 2048);
                bulk_commit();
                PROFT(e < 4, 64 + e * 16 + 6);
              }
              bulk_wait_read0();
              release2(bar + B_E1);
              release2(bar + B_E1);
            }
            mbar_wait(bar + B_OH1, e & 1);
            PROFT(e == PL, 251);
            flag_set(g_of + rb * 32 + 2 * g, xbase + e + 1);
            PROFT(e < 4, 64 + e * 16 + 9);
            mbar_wait(bar + B_ODONE, e & 1);
            PROFT(e < 4, 64 + e * 16 + 8);
            flag_set(g_of + rb * 32 + 2 * g + 1, xbase + e + 1);
            PROFT(e < 4, 64 + e * 16 + 11);
          }
        }
      } else {
        const int h2 = threadIdx.x - 64;
        const float* cs = g_cs + (epoch & 1) * 6144;
#pragma unroll 1
        for (int layer = 0; layer < NLAYERS; ++layer) {
          if (warp == 2 && layer < 2) {
            if (lane == 0) flag_wait_t<CSLP>(&g_csflag[layer * 8 + g].v, cbase + 16u);
            __syncwarp();
            float4 a[3];
#pragma unroll
            for (int i = 0; i < 3; ++i) a[i] = __ldcg(reinterpret_cast<const float4*>(cs + layer * 3072 + g * 384) + i * 32 + lane);
#pragma unroll 1
            for (int i = 0; i < 3; ++i) {
              const float av[4] = {a[0].x, a[0].y, a[0].z, a[0].w};
              a[0] = a[1]; a[1] = a[2];
#pragma unroll
              for (int j = 0; j < 4; ++j) {
                const float c1 = bf16r(av[j]), c2 = bf16r(av[j] - c1), c3 = (av[j] - c1) - c2;
                sts128(sb + SM_BP + layer * 6144 + ((i * 32 + lane) * 4 + j) * 16, make_uint4(pack_bf16(c1, c2), pack_bf16(c3, 0.f), 0u, 0u));
              }
            }
            fence_async_smem();
            __syncwarp();
            if (lane == 0) mbar_arrive(bar + (layer ? B_CS2 : B_CS));
            PROFT(lane == 0, 64 + layer * 16 + 12);
            if (layer == 0) {
              uint4* hz = g_halo + (rb * 8 + g) * 1024;
#pragma unroll 2
              for (int i = lane; i < 1024; i += 32) hz[i] = make_uint4(0u, 0u, 0u, 0u);
              if (lane < 12) reinterpret_cast<float4*>(g_cs + ((epoch & 1) ^ 1) * 6144 + blockIdx.x * 48)[lane] = make_float4(0.f, 0.f, 0.f, 0.f);
              g_stats[(2 + (lane >> 4)) * S_ + m0 + g * 16 + (lane & 15)] = make_float2(0.f, 0.f);
            }
          }
          if (warp == 3) {
            const bool hal = (layer & 1) && rb > 0;
            {
              uint32_t rdy = 0u;
              src_wait<256>(g_xf + rb * 32, xbase + layer + 1, 0xAAAAu, rdy, lane);
              rdy = 0u;
              if (hal) src_wait<256>(g_xf + (rb - 1) * 32, xbase + layer + 1, 0xAAAAu, rdy, lane);
            }
            float2 u[5];
            const float2* sp = g_stats + layer * S_ + m0 + lane;
#pragma unroll
            for (int i = 0; i < 4; ++i) u[i] = __ldcg(sp + i * 32);
            u[4] = __ldcg(hal ? sp - 16 : sp);
            if (layer == 3) g_stats[(lane >> 4) * S_ + m0 + g * 16 + (lane & 15)] = make_float2(0.f, 0.f);
#pragma unroll 1
            for (int i = 0; i < (hal ? 5 : 4); ++i) {
              const int r = i < 4 ? 16 + i * 32 + lane : lane;
              const float sum = u[0].x, sq = u[0].y;
              u[0] = u[1]; u[1] = u[2]; u[2] = u[3]; u[3] = u[4];
              const float mean = sum * (1.f / D_);
              const float var = fmaxf(fmaf(-sum, mean, sq) * (1.f / D_), 0.f);
              const float sd = bf16r(sqrtf(bf16r(bf16r(var) + 1e-5f)));
              sts_f(sb + SM_RS + r * 4, 1.f / sd);
              if (i < 4) {
                const float hm = -0.5f * bf16r(mean);
                const uint32_t s2 = pack_bf16(sd, sd);
                sts128(sb + SM_SD + (r - 16) * 64 + ((r >> 1) & 3) * 16, make_uint4(s2, s2, s2, s2));
                sts128(sb + SM_AP + (r - 16) * 16, make_uint4(pack_bf16(hm, hm), pack_bf16(hm, 0.f), 0u, 0u));
              }
            }
            fence_async_smem();
            __syncwarp();
            if (lane == 0) mbar_arrive(bar + B_STAT);
            PROFT(lane == 0, 64 + layer * 16 + 14);
            wo_w(__shfl_sync(0xffffffffu, layer, 0));
          }
          if (layer == 0 && warp == 2) {
            if (CSW) mbar_wait_u(bar + (CSW == 1 ? B_E0 : CSW == 2 ? B_OH1 : B_ODONE), 0);
#pragma unroll 1
            for (int wi = 0; wi < 6; ++wi) {
              float sB[8];
              colsum_load(wB, rb, g, wi, lane, sb + SM_BP + 6144, sB);
              colsum_red(g_cs + (epoch & 1) * 6144 + 3072, g, wi, lane, sB);
            }
            __syncwarp();
            if (lane == 0) flag_add(&g_csflag[8 + g].v);
            PROFT(h2 == 0, 64 + 13);
          }
        }
      }
    }
    __syncwarp();
    asm volatile("barrier.cluster.arrive.relaxed.aligned;\nbarrier.cluster.wait.aligned;\n" ::: "memory");
  } else {
    if (warp == 5) {
      if (lane == 0) {
        mbar_init(bar + B_FULLS, 1);
        asm volatile("fence.mbarrier_init.release.cluster;" ::: "memory");
      }
      __syncwarp();
      expect_tx_e(bar + B_FULLS, 65536);
      tma_2d_e(sb + XS * SLOT, &tm_x0, 0, m0, bar + B_FULLS);
#pragma unroll
      for (int j = 0; j < 6; ++j)
        tma_2d_e(sb + (j < 4 ? j + 4 : j - 2) * 8192, &tm_wA, (j < 4 ? 1024 + (j >> 1) * 1024 : 0) + g * 128 + (j & 1) * 64, 0, bar + B_FULLS);
      PROFT(lane == 0, 241);
    }
    if (lane < 8 && warp != 5 && threadIdx.x != 128) {
      const int i = (warp - 4) * 8 + lane;
      mbar_init(bar + i * 8, i < 32 ? 1u << ((BAR_CNT >> (2 * i)) & 3) : i < 48 ? 1u : (i == 59 || i == 60) ? 16u : i < 63 ? 4u : 8u);
      asm volatile("fence.mbarrier_init.release.cluster;" ::: "memory");
    }
    __syncwarp();
    asm volatile("barrier.cluster.arrive.relaxed.aligned;" ::: "memory");
    asm volatile("setmaxnreg.inc.sync.aligned.u32 232;");
    cluster_wait();
    PROFT(threadIdx.x == 128, 0);
    Ctx c; c.sb = sb; c.g = g; c.rb = rb; c.cu = warp - 4; c.out = out;
    consumer(c);
    asm volatile("bar.warp.sync 0xffffffff;\nbarrier.cluster.arrive.relaxed.aligned;\nbarrier.cluster.wait.aligned;\n" ::: "memory");
  }
}

typedef CUresult (*PFN_encodeTiled)(CUtensorMap*, CUtensorMapDataType, cuuint32_t, void*, const cuuint64_t*, const cuuint64_t*,
                                    const cuuint32_t*, const cuuint32_t*, CUtensorMapInterleave, CUtensorMapSwizzle,
                                    CUtensorMapL2promotion, CUtensorMapFloatOOBfill);

static CUtensorMap make_map(PFN_encodeTiled enc, const void* ptr, uint64_t cols, uint64_t rows, uint32_t box_c, uint32_t box_r, uint32_t nb = 1) {
  CUtensorMap m;
  cuuint64_t dims[3] = {nb > 1 ? box_c : cols, rows, cols / box_c};
  cuuint64_t strides[2] = {cols * 2, box_c * 2};
  cuuint32_t box[3] = {box_c, box_r, nb};
  cuuint32_t es[3] = {1, 1, 1};
  CUresult r = enc(&m, CU_TENSOR_MAP_DATA_TYPE_BFLOAT16, nb > 1 ? 3 : 2, const_cast<void*>(ptr), dims, strides, box, es, CU_TENSOR_MAP_INTERLEAVE_NONE,
      CU_TENSOR_MAP_SWIZZLE_128B, CU_TENSOR_MAP_L2_PROMOTION_L2_256B, CU_TENSOR_MAP_FLOAT_OOB_FILL_NONE);
  (void)r;
  return m;
}

extern "C" void kernel_launch(void* const* d_in, const int* in_sizes, int n_in, void* d_out, int out_size) {
  const bf16* A_x = (const bf16*)d_in[0];
  const bf16* A_wqkv = (const bf16*)d_in[1];
  const bf16* A_wphi = (const bf16*)d_in[2];
  const bf16* A_wo = (const bf16*)d_in[3];
  const bf16* B_wqkv = (const bf16*)d_in[5];
  const bf16* B_wo = (const bf16*)d_in[6];
  bf16* out = (bf16*)d_out;

  static PFN_encodeTiled enc = nullptr;
  static bf16 *p_x, *p_o;
  if (!enc) {
    void* fn = nullptr; cudaDriverEntryPointQueryResult qr;
    cudaGetDriverEntryPoint("cuTensorMapEncodeTiled", &fn, cudaEnableDefault, &qr);
    enc = (PFN_encodeTiled)fn;
    cudaGetSymbolAddress((void**)&p_x, g_x);
    cudaGetSymbolAddress((void**)&p_o, g_o);
    cudaFuncSetAttribute(mega_kernel, cudaFuncAttributeMaxDynamicSharedMemorySize, SM_TOTAL);
  }
  CUtensorMap tm_x0 = make_map(enc, A_x, 1024, 2048, 64, 128);
  CUtensorMap tm_x = make_map(enc, p_x, 1024, 2048, 64, 128);
  CUtensorMap tm_o = make_map(enc, p_o, 1024, 2048, 64, 128);
  CUtensorMap tm_wA = make_map(enc, A_wqkv, 3072, 1024, 64, 64);
  CUtensorMap tm_wB = make_map(enc, B_wqkv, 3072, 1024, 64, 64);
  CUtensorMap tm_woA = make_map(enc, A_wo, 1024, 1024, 64, 64);
  CUtensorMap tm_woB = make_map(enc, B_wo, 1024, 1024, 64, 64);
  mega_kernel<<<128, 384, SM_TOTAL, cudaStreamPerThread>>>(tm_x0, tm_x, tm_o, tm_wA, tm_wB, tm_woA, tm_woB,
                                                           A_wqkv, B_wqkv, A_wphi, out);
}
```

```cpp
#include <cuda_runtime.h>
#include <cuda_bf16.h>
#include <cuda.h>
#include <stdint.h>

typedef __nv_bfloat16 bf16;

constexpr int S_ = 2048, D_ = 1024;

struct __align__(128) Flag { unsigned int v; unsigned int pad[31]; };
__device__ __align__(1024) bf16 g_x[S_ * D_];
__device__ __align__(1024) bf16 g_o[S_ * D_];
__device__ __align__(1024) uint4 g_halo[128 * 2 * 512];
__device__ __align__(1024) uint4 g_kv[8 * 2 * 2 * 1280];
__device__ __align__(1024) float2 g_stats[4 * S_];
__device__ __align__(1024) float g_cs[2 * 2 * 3072];
__device__ Flag g_csflag[16];
__device__ __align__(128) unsigned int g_xf[16 * 32], g_of[16 * 32];
__device__ unsigned int g_epoch, g_err;
#define PROFT(cond, idx) asm volatile("" ::: "memory")

__device__ __forceinline__ uint32_t smem_u32(const void* p) { return (uint32_t)__cvta_generic_to_shared(p); }
__device__ __forceinline__ void mbar_init(uint32_t bar, uint32_t count) {
  asm volatile("mbarrier.init.shared::cta.b64 [%0], %1;" ::"r"(bar), "r"(count) : "memory");
}
__device__ __forceinline__ void mbar_expect_tx(uint32_t bar, uint32_t bytes) {
  asm volatile("mbarrier.arrive.expect_tx.shared::cta.b64 _, [%0], %1;" ::"r"(bar), "r"(bytes) : "memory");
}
__device__ __forceinline__ void mbar_arrive(uint32_t bar) {
  asm volatile("mbarrier.arrive.shared::cta.b64 _, [%0];" ::"r"(bar) : "memory");
}
__device__ __forceinline__ bool mbar_try_wait(uint32_t bar, uint32_t parity) {
  uint32_t ok;
  asm volatile("{\n.reg .pred p;\nmbarrier.try_wait.parity.shared::cta.b64 p, [%1], %2;\nselp.b32 %0, 1, 0, p;\n}\n"
               : "=r"(ok) : "r"(bar), "r"(parity) : "memory");
  return ok != 0;
}
__device__ __forceinline__ bool mbar_test_wait(uint32_t bar, uint32_t parity) {
  uint32_t ok;
  asm volatile("{\n.reg .pred p;\nmbarrier.test_wait.parity.shared::cta.b64 p, [%1], %2;\nselp.b32 %0, 1, 0, p;\n}\n"
               : "=r"(ok) : "r"(bar), "r"(parity) : "memory");
  return ok != 0;
}
__device__ __forceinline__ uint64_t gtimer() {
  uint64_t t; asm volatile("mov.u64 %0, %globaltimer;" : "=l"(t)); return t;
}
__device__ __forceinline__ void mbar_wait(uint32_t bar, uint32_t parity) {
  uint32_t n = 0;
#pragma unroll 1
  while (!mbar_try_wait(bar, parity)) {
    if (++n > (1u << 22)) { g_err = 1u; break; }
  }
}
__device__ __forceinline__ unsigned int ld_acquire(const unsigned int* p) {
  unsigned int v; asm volatile("ld.acquire.gpu.global.u32 %0, [%1];" : "=r"(v) : "l"(p) : "memory"); return v;
}
__device__ __forceinline__ void flag_add(unsigned int* p) {
  asm volatile("red.release.gpu.global.add.u32 [%0], 1;" ::"l"(p) : "memory");
}
__device__ __forceinline__ void flag_set(unsigned int* p, unsigned int v) {
  asm volatile("st.release.gpu.global.u32 [%0], %1;" ::"l"(p), "r"(v) : "memory");
}
template <int SLEEP>
__device__ __forceinline__ void src_wait(const unsigned int* f, unsigned int target, uint32_t need, uint32_t& ready, int lane) {
  uint32_t n = 0;
#pragma unroll 1
  while ((ready & need) != need) {
    const unsigned int v = ld_acquire(f + (lane & 15));
    ready = __ballot_sync(0xffffffffu, (int)(v - target) >= 0);
    if (SLEEP) { if ((ready & need) != need) __nanosleep(SLEEP); }
    if (++n > (1u << 20)) { g_err = 3u; break; }
  }
  __syncwarp();
}
__device__ __forceinline__ unsigned int ld_relaxed(const unsigned int* p) {
  unsigned int v; asm volatile("ld.relaxed.gpu.global.u32 %0, [%1];" : "=r"(v) : "l"(p) : "memory"); return v;
}
__device__ __forceinline__ uint4 ld_relaxed4(const uint4* p) {
  uint4 v; asm volatile("ld.relaxed.gpu.global.v4.u32 {%0,%1,%2,%3}, [%4];" : "=r"(v.x), "=r"(v.y), "=r"(v.z), "=r"(v.w) : "l"(p) : "memory"); return v;
}
__device__ __forceinline__ void st_relaxed4(uint4* p, uint32_t a, uint32_t b, uint32_t c, uint32_t d) {
  asm volatile("st.relaxed.gpu.global.v4.u32 [%0], {%1,%2,%3,%4};" ::"l"(p), "r"(a), "r"(b), "r"(c), "r"(d) : "memory");
}
template <int SLEEP>
__device__ __forceinline__ void flag_wait_t(const unsigned int* p, unsigned int target) {
  uint32_t n = 0;
#pragma unroll 1
  while ((int)(ld_acquire(p) - target) < 0) {
    if (SLEEP) __nanosleep(SLEEP);
    if (++n > (1u << 20)) { g_err = 2u; break; }
  }
}
__device__ __forceinline__ void flag_wait(const unsigned int* p, unsigned int target) { flag_wait_t<0>(p, target); }
__device__ __forceinline__ void flag_wait_slow(const unsigned int* p, unsigned int target) { flag_wait_t<256>(p, target); }
__device__ __forceinline__ void tma_load_2d(uint32_t dst, const CUtensorMap* tm, int c0, int c1, uint32_t bar) {
  asm volatile("cp.async.bulk.tensor.2d.shared::cluster.global.mbarrier::complete_tx::bytes [%0], [%1, {%2, %3}], [%4];"
               ::"r"(dst), "l"(tm), "r"(c0), "r"(c1), "r"(bar) : "memory");
}
__device__ __forceinline__ void tma_load_2d_mc(uint32_t dst, const CUtensorMap* tm, int c0, int c1, uint32_t bar, uint16_t mask) {
  asm volatile("cp.async.bulk.tensor.2d.shared::cluster.global.mbarrier::complete_tx::bytes.multicast::cluster [%0], [%1, {%2, %3}], [%4], %5;"
               ::"r"(dst), "l"(tm), "r"(c0), "r"(c1), "r"(bar), "h"(mask) : "memory");
}
__device__ __forceinline__ void mbar_wait_u(uint32_t bar, uint32_t parity) {
  uint32_t n = 0;
#pragma unroll 1
  while (!__all_sync(0xffffffffu, mbar_try_wait(bar, parity))) {
    if (++n > (1u << 22)) { g_err = 1u; break; }
  }
}
__device__ __forceinline__ void expect_tx_e(uint32_t bar, uint32_t bytes) {
  asm volatile("{\n.reg .pred p;\nelect.sync _|p, 0xffffffff;\n@p mbarrier.arrive.expect_tx.shared::cta.b64 _, [%0], %1;\n}\n" ::"r"(bar), "r"(bytes) : "memory");
}
__device__ __forceinline__ void tma_2d_e(uint32_t dst, const CUtensorMap* tm, int c0, int c1, uint32_t bar) {
  asm volatile("{\n.reg .pred p;\nelect.sync _|p, 0xffffffff;\n"
               "@p cp.async.bulk.tensor.2d.shared::cluster.global.mbarrier::complete_tx::bytes [%0], [%1, {%2, %3}], [%4];\n}\n"
               ::"r"(dst), "l"(tm), "r"(c0), "r"(c1), "r"(bar) : "memory");
}
__device__ __forceinline__ void tma_2d_mc_e(uint32_t dst, const CUtensorMap* tm, int c0, int c1, uint32_t bar) {
  asm volatile("{\n.reg .pred p;\nelect.sync _|p, 0xffffffff;\n"
               "@p cp.async.bulk.tensor.2d.shared::cluster.global.mbarrier::complete_tx::bytes.multicast::cluster [%0], [%1, {%2, %3}], [%4], %5;\n}\n"
               ::"r"(dst), "l"(tm), "r"(c0), "r"(c1), "r"(bar), "h"((uint16_t)3) : "memory");
}
__device__ __forceinline__ void tma_pf_e(const CUtensorMap* tm, int c0, int c1) {
  asm volatile("{\n.reg .pred p;\nelect.sync _|p, 0xffffffff;\n"
               "@p cp.async.bulk.prefetch.tensor.2d.L2.global.tile [%0, {%1, %2}];\n}\n" ::"l"(tm), "r"(c0), "r"(c1) : "memory");
}
__device__ __forceinline__ void tma_2d_to_e(uint32_t dst, const CUtensorMap* tm, int c0, int c1, uint32_t bar, uint32_t mask) {
  asm volatile("{\n.reg .pred p;\nelect.sync _|p, 0xffffffff;\n"
               "@p cp.async.bulk.tensor.2d.shared::cluster.global.mbarrier::complete_tx::bytes.multicast::cluster [%0], [%1, {%2, %3}], [%4], %5;\n}\n"
               ::"r"(dst), "l"(tm), "r"(c0), "r"(c1), "r"(bar), "h"((uint16_t)mask) : "memory");
}
__device__ __forceinline__ void tma_3d_mc_e(uint32_t dst, const CUtensorMap* tm, int c1, int c2, uint32_t bar) {
  asm volatile("{\n.reg .pred p;\nelect.sync _|p, 0xffffffff;\n"
               "@p cp.async.bulk.tensor.3d.shared::cluster.global.mbarrier::complete_tx::bytes.multicast::cluster [%0], [%1, {%6, %2, %3}], [%4], %5;\n}\n"
               ::"r"(dst), "l"(tm), "r"(c1), "r"(c2), "r"(bar), "h"((uint16_t)3), "r"(0) : "memory");
}
__device__ __forceinline__ uint32_t poll_flags(const unsigned int* f, unsigned int target, int lane) {
  const unsigned int v = ld_acquire(f + (lane & 15));
  const uint32_t r = __ballot_sync(0xffffffffu, (int)(v - target) >= 0);
  __syncwarp();
  return r;
}
__device__ __forceinline__ void mbar_arrive_cluster(uint32_t local_bar, uint32_t rank) {
  asm volatile("{\n.reg .b32 ra;\nmapa.shared::cluster.u32 ra, %0, %1;\nmbarrier.arrive.shared::cluster.b64 _, [ra];\n}\n"
               ::"r"(local_bar), "r"(rank) : "memory");
}
__device__ __forceinline__ void release2(uint32_t bar) { mbar_arrive_cluster(bar, 0); mbar_arrive_cluster(bar, 1); }
__device__ __forceinline__ void tma_store_2d(const CUtensorMap* tm, uint32_t src, int c0, int c1) {
  asm volatile("cp.async.bulk.tensor.2d.global.shared::cta.bulk_group [%0, {%2, %3}], [%1];"
               ::"l"(tm), "r"(src), "r"(c0), "r"(c1) : "memory");
}
__device__ __forceinline__ void bulk_store(void* dst, uint32_t src, uint32_t bytes) {
  asm volatile("cp.async.bulk.global.shared::cta.bulk_group [%0], [%1], %2;" ::"l"(dst), "r"(src), "r"(bytes) : "memory");
}
__device__ __forceinline__ void bulk_load(uint32_t dst, const void* src, uint32_t bytes, uint32_t bar) {
  asm volatile("cp.async.bulk.shared::cluster.global.mbarrier::complete_tx::bytes [%0], [%1], %2, [%3];" ::"r"(dst), "l"(src), "r"(bytes), "r"(bar) : "memory");
}
__device__ __forceinline__ void bulk_red_add(void* dst, uint32_t src, uint32_t bytes) {
  asm volatile("cp.reduce.async.bulk.global.shared::cta.bulk_group.add.f32 [%0], [%1], %2;" ::"l"(dst), "r"(src), "r"(bytes) : "memory");
}
__device__ __forceinline__ void bulk_red_add_e(void* dst, uint32_t src, uint32_t bytes) {
  asm volatile("{\n.reg .pred p;\nelect.sync _|p, 0xffffffff;\n@p cp.reduce.async.bulk.global.shared::cta.bulk_group.add.f32 [%0], [%1], %2;\n}\n" ::"l"(dst), "r"(src), "r"(bytes) : "memory");
}
__device__ __forceinline__ void bulk_commit() { asm volatile("cp.async.bulk.commit_group;" ::: "memory"); }
__device__ __forceinline__ void bulk_wait_read0() { asm volatile("cp.async.bulk.wait_group.read 0;" ::: "memory"); }
__device__ __forceinline__ void bulk_wait0() { asm volatile("cp.async.bulk.wait_group 0;" ::: "memory"); }
__device__ __forceinline__ void fence_async_smem() { asm volatile("fence.proxy.async.shared::cta;" ::: "memory"); }
__device__ __forceinline__ void fence_async_all() { asm volatile("fence.proxy.async.global;" ::: "memory"); }
__device__ __forceinline__ void wgmma_fence() { asm volatile("wgmma.fence.sync.aligned;" ::: "memory"); }
__device__ __forceinline__ void wgmma_commit() { asm volatile("wgmma.commit_group.sync.aligned;" ::: "memory"); }
template <int N> __device__ __forceinline__ void wgmma_wait() { asm volatile("wgmma.wait_group.sync.aligned %0;" ::"n"(N) : "memory"); }
__device__ __forceinline__ void cluster_arrive() { asm volatile("barrier.cluster.arrive.release.aligned;" ::: "memory"); }
__device__ __forceinline__ void cluster_wait() { asm volatile("barrier.cluster.wait.acquire.aligned;" ::: "memory"); }
template <int ID, int N> __device__ __forceinline__ void nbar() { asm volatile("bar.sync %0, %1;" ::"n"(ID), "n"(N) : "memory"); }
__device__ __forceinline__ uint64_t make_desc(uint32_t addr, uint32_t lbo_bytes, uint32_t sbo_bytes) {
  uint64_t d = 0;
  d |= (uint64_t)((addr & 0x3FFFF) >> 4);
  d |= (uint64_t)((lbo_bytes >> 4) & 0x3FFF) << 16;
  d |= (uint64_t)((sbo_bytes >> 4) & 0x3FFF) << 32;
  d |= (uint64_t)1 << 62;
  return d;
}
__device__ __forceinline__ uint64_t desc64(uint32_t lo, uint32_t hi) { return (uint64_t)lo | ((uint64_t)hi << 32); }
__device__ __forceinline__ uint32_t pack_bf16(float lo, float hi) {
  uint32_t r; asm("cvt.rn.bf16x2.f32 %0, %1, %2;" : "=r"(r) : "f"(hi), "f"(lo)); return r;
}
__device__ __forceinline__ uint32_t mul_bf16x2(uint32_t a, uint32_t s, bool hi) {
  __nv_bfloat162 x = *reinterpret_cast<__nv_bfloat162*>(&a), y = *reinterpret_cast<__nv_bfloat162*>(&s);
  x = __hmul2(x, hi ? __high2bfloat162(y) : __low2bfloat162(y));
  return *reinterpret_cast<uint32_t*>(&x);
}
__device__ __forceinline__ float bf16r(float x) { return __bfloat162float(__float2bfloat16_rn(x)); }
__device__ __forceinline__ float bf_lo(uint32_t u) { return __uint_as_float(u << 16); }
__device__ __forceinline__ float bf_hi(uint32_t u) { return __uint_as_float(u & 0xFFFF0000u); }
__device__ __forceinline__ float ex2(float x) { float r; asm("ex2.approx.ftz.f32 %0, %1;" : "=f"(r) : "f"(x)); return r; }
__device__ __forceinline__ float rcp(float x) { float r; asm("rcp.approx.ftz.f32 %0, %1;" : "=f"(r) : "f"(x)); return r; }
__device__ __forceinline__ void mma_bf16(float (&d)[4], uint32_t a0, uint32_t a1, uint32_t a2, uint32_t a3, uint32_t b0, uint32_t b1) {
  asm("mma.sync.aligned.m16n8k16.row.col.f32.bf16.bf16.f32 {%0,%1,%2,%3}, {%4,%5,%6,%7}, {%8,%9}, {%0,%1,%2,%3};"
               : "+f"(d[0]), "+f"(d[1]), "+f"(d[2]), "+f"(d[3]) : "r"(a0), "r"(a1), "r"(a2), "r"(a3), "r"(b0), "r"(b1));
}
__device__ __forceinline__ void ldsm_x4(uint32_t& r0, uint32_t& r1, uint32_t& r2, uint32_t& r3, uint32_t addr) {
  asm volatile("ldmatrix.sync.aligned.m8n8.x4.shared.b16 {%0,%1,%2,%3}, [%4];"
               : "=r"(r0), "=r"(r1), "=r"(r2), "=r"(r3) : "r"(addr) : "memory");
}
__device__ __forceinline__ void ldsm_x4_t(uint32_t& r0, uint32_t& r1, uint32_t& r2, uint32_t& r3, uint32_t addr) {
  asm volatile("ldmatrix.sync.aligned.m8n8.x4.trans.shared.b16 {%0,%1,%2,%3}, [%4];"
               : "=r"(r0), "=r"(r1), "=r"(r2), "=r"(r3) : "r"(addr) : "memory");
}
__device__ __forceinline__ void ldsm_x2_t(uint32_t& r0, uint32_t& r1, uint32_t addr) {
  asm volatile("ldmatrix.sync.aligned.m8n8.x2.trans.shared.b16 {%0,%1}, [%2];"
               : "=r"(r0), "=r"(r1) : "r"(addr) : "memory");
}
__device__ __forceinline__ void stsm_x4(uint32_t addr, uint32_t r0, uint32_t r1, uint32_t r2, uint32_t r3) {
  asm volatile("stmatrix.sync.aligned.m8n8.x4.shared.b16 [%0], {%1,%2,%3,%4};"
               ::"r"(addr), "r"(r0), "r"(r1), "r"(r2), "r"(r3) : "memory");
}
__device__ __forceinline__ void stsm_x4_p(bool on, uint32_t addr, uint32_t r0, uint32_t r1, uint32_t r2, uint32_t r3) {
  asm volatile("{\n.reg .pred p;\nsetp.ne.b32 p, %5, 0;\n@p stmatrix.sync.aligned.m8n8.x4.shared.b16 [%0], {%1,%2,%3,%4};\n}\n"
               ::"r"(addr), "r"(r0), "r"(r1), "r"(r2), "r"(r3), "r"((int)on) : "memory");
}
__device__ __forceinline__ float2 lds_f2(uint32_t addr) {
  float2 v; asm volatile("ld.shared.v2.f32 {%0,%1}, [%2];" : "=f"(v.x), "=f"(v.y) : "r"(addr) : "memory"); return v;
}
__device__ __forceinline__ uint4 lds128(uint32_t addr) {
  uint4 v; asm volatile("ld.shared.v4.b32 {%0,%1,%2,%3}, [%4];" : "=r"(v.x), "=r"(v.y), "=r"(v.z), "=r"(v.w) : "r"(addr) : "memory"); return v;
}
__device__ __forceinline__ void sts128(uint32_t addr, uint4 v) {
  asm volatile("st.shared.v4.b32 [%0], {%1,%2,%3,%4};" ::"r"(addr), "r"(v.x), "r"(v.y), "r"(v.z), "r"(v.w) : "memory");
}
__device__ __forceinline__ float lds_f(uint32_t addr) {
  float v; asm volatile("ld.shared.f32 %0, [%1];" : "=f"(v) : "r"(addr) : "memory"); return v;
}
__device__ __forceinline__ uint32_t lds_vol(uint32_t addr) {
  uint32_t v; asm volatile("ld.volatile.shared.u32 %0, [%1];" : "=r"(v) : "r"(addr) : "memory"); return v;
}
__device__ __forceinline__ void sts16(uint32_t addr, uint32_t v) {
  asm volatile("st.shared.u16 [%0], %1;" ::"r"(addr), "h"((unsigned short)v) : "memory");
}
__device__ __forceinline__ void nbar_dyn(int id, int n) { asm volatile("bar.sync %0, %1;" ::"r"(id), "r"(n) : "memory"); }
__device__ __forceinline__ uint64_t make_desc_ns(uint32_t addr, uint32_t lbo_bytes, uint32_t sbo_bytes) {
  return (uint64_t)((addr & 0x3FFFF) >> 4) | ((uint64_t)(lbo_bytes >> 4) << 16) | ((uint64_t)(sbo_bytes >> 4) << 32);
}
__device__ __forceinline__ void sts_f(uint32_t addr, float v) { asm volatile("st.shared.f32 [%0], %1;" ::"r"(addr), "f"(v) : "memory"); }
__device__ __forceinline__ void sts64(uint32_t addr, uint32_t a, uint32_t b) {
  asm volatile("st.shared.v2.b32 [%0], {%1,%2};" ::"r"(addr), "r"(a), "r"(b) : "memory");
}
__device__ __forceinline__ void sts_f2(uint32_t addr, float a, float b) {
  asm volatile("st.shared.v2.f32 [%0], {%1,%2};" ::"r"(addr), "f"(a), "f"(b) : "memory");
}
__device__ __forceinline__ void red_add2(float* p, float a, float b) {
  asm volatile("red.global.add.v2.f32 [%0], {%1,%2};" ::"l"(p), "f"(a), "f"(b) : "memory");
}
__device__ __forceinline__ void red_add4(float* p, float a, float b, float c, float d) {
  asm volatile("red.global.add.v4.f32 [%0], {%1,%2,%3,%4};" ::"l"(p), "f"(a), "f"(b), "f"(c), "f"(d) : "memory");
}
__device__ __forceinline__ void red_add1(float* p, float a) {
  asm volatile("red.global.add.f32 [%0], %1;" ::"l"(p), "f"(a) : "memory");
}
__device__ __forceinline__ void l2_prefetch(const void* p, uint32_t bytes) {
  asm volatile("cp.async.bulk.prefetch.L2.global [%0], %1;" ::"l"(p), "r"(bytes) : "memory");
}

__device__ __forceinline__ void wgmma_n256(float (&d)[192], uint64_t da, uint64_t db, int scale_d) {
  asm volatile("{\n.reg .pred p;\nsetp.ne.b32 p, %130, 0;\n"
    "wgmma.mma_async.sync.aligned.m64n256k16.f32.bf16.bf16 {%0, %1, %2, %3, %4, %5, %6, %7, %8, %9, %10, %11, %12, %13, %14, %15, %16, %17, %18, %19, %20, %21, %22, %23, %24, %25, %26, %27, %28, %29, %30, %31, %32, %33, %34, %35, %36, %37, %38, %39, %40, %41, %42, %43, %44, %45, %46, %47, %48, %49, %50, %51, %52, %53, %54, %55, %56, %57, %58, %59, %60, %61, %62, %63, %64, %65, %66, %67, %68, %69, %70, %71, %72, %73, %74, %75, %76, %77, %78, %79, %80, %81, %82, %83, %84, %85, %86, %87, %88, %89, %90, %91, %92, %93, %94, %95, %96, %97, %98, %99, %100, %101, %102, %103, %104, %105, %106, %107, %108, %109, %110, %111, %112, %113, %114, %115, %116, %117, %118, %119, %120, %121, %122, %123, %124, %125, %126, %127}, %128, %129, p, 1, 1, 0, 1;\n}\n"
    : "+f"(d[0]), "+f"(d[1]), "+f"(d[2]), "+f"(d[3]), "+f"(d[4]), "+f"(d[5]), "+f"(d[6]), "+f"(d[7]), "+f"(d[8]), "+f"(d[9]), "+f"(d[10]), "+f"(d[11]), "+f"(d[12]), "+f"(d[13]), "+f"(d[14]), "+f"(d[15]), "+f"(d[16]), "+f"(d[17]), "+f"(d[18]), "+f"(d[19]), "+f"(d[20]), "+f"(d[21]), "+f"(d[22]), "+f"(d[23]), "+f"(d[24]), "+f"(d[25]), "+f"(d[26]), "+f"(d[27]), "+f"(d[28]), "+f"(d[29]), "+f"(d[30]), "+f"(d[31]), "+f"(d[32]), "+f"(d[33]), "+f"(d[34]), "+f"(d[35]), "+f"(d[36]), "+f"(d[37]), "+f"(d[38]), "+f"(d[39]), "+f"(d[40]), "+f"(d[41]), "+f"(d[42]), "+f"(d[43]), "+f"(d[44]), "+f"(d[45]), "+f"(d[46]), "+f"(d[47]), "+f"(d[48]), "+f"(d[49]), "+f"(d[50]), "+f"(d[51]), "+f"(d[52]), "+f"(d[53]), "+f"(d[54]), "+f"(d[55]), "+f"(d[56]), "+f"(d[57]), "+f"(d[58]), "+f"(d[59]), "+f"(d[60]), "+f"(d[61]), "+f"(d[62]), "+f"(d[63]), "+f"(d[64]), "+f"(d[65]), "+f"(d[66]), "+f"(d[67]), "+f"(d[68]), "+f"(d[69]), "+f"(d[70]), "+f"(d[71]), "+f"(d[72]), "+f"(d[73]), "+f"(d[74]), "+f"(d[75]), "+f"(d[76]), "+f"(d[77]), "+f"(d[78]), "+f"(d[79]), "+f"(d[80]), "+f"(d[81]), "+f"(d[82]), "+f"(d[83]), "+f"(d[84]), "+f"(d[85]), "+f"(d[86]), "+f"(d[87]), "+f"(d[88]), "+f"(d[89]), "+f"(d[90]), "+f"(d[91]), "+f"(d[92]), "+f"(d[93]), "+f"(d[94]), "+f"(d[95]), "+f"(d[96]), "+f"(d[97]), "+f"(d[98]), "+f"(d[99]), "+f"(d[100]), "+f"(d[101]), "+f"(d[102]), "+f"(d[103]), "+f"(d[104]), "+f"(d[105]), "+f"(d[106]), "+f"(d[107]), "+f"(d[108]), "+f"(d[109]), "+f"(d[110]), "+f"(d[111]), "+f"(d[112]), "+f"(d[113]), "+f"(d[114]), "+f"(d[115]), "+f"(d[116]), "+f"(d[117]), "+f"(d[118]), "+f"(d[119]), "+f"(d[120]), "+f"(d[121]), "+f"(d[122]), "+f"(d[123]), "+f"(d[124]), "+f"(d[125]), "+f"(d[126]), "+f"(d[127])
    : "l"(da), "l"(db), "r"(scale_d));
}
__device__ __forceinline__ void wgmma_n128(float (&d)[192], uint64_t da, uint64_t db, int scale_d) {
  asm volatile("{\n.reg .pred p;\nsetp.ne.b32 p, %66, 0;\n"
    "wgmma.mma_async.sync.aligned.m64n128k16.f32.bf16.bf16 {%0, %1, %2, %3, %4, %5, %6, %7, %8, %9, %10, %11, %12, %13, %14, %15, %16, %17, %18, %19, %20, %21, %22, %23, %24, %25, %26, %27, %28, %29, %30, %31, %32, %33, %34, %35, %36, %37, %38, %39, %40, %41, %42, %43, %44, %45, %46, %47, %48, %49, %50, %51, %52, %53, %54, %55, %56, %57, %58, %59, %60, %61, %62, %63}, %64, %65, p, 1, 1, 0, 1;\n}\n"
    : "+f"(d[128]), "+f"(d[129]), "+f"(d[130]), "+f"(d[131]), "+f"(d[132]), "+f"(d[133]), "+f"(d[134]), "+f"(d[135]), "+f"(d[136]), "+f"(d[137]), "+f"(d[138]), "+f"(d[139]), "+f"(d[140]), "+f"(d[141]), "+f"(d[142]), "+f"(d[143]), "+f"(d[144]), "+f"(d[145]), "+f"(d[146]), "+f"(d[147]), "+f"(d[148]), "+f"(d[149]), "+f"(d[150]), "+f"(d[151]), "+f"(d[152]), "+f"(d[153]), "+f"(d[154]), "+f"(d[155]), "+f"(d[156]), "+f"(d[157]), "+f"(d[158]), "+f"(d[159]), "+f"(d[160]), "+f"(d[161]), "+f"(d[162]), "+f"(d[163]), "+f"(d[164]), "+f"(d[165]), "+f"(d[166]), "+f"(d[167]), "+f"(d[168]), "+f"(d[169]), "+f"(d[170]), "+f"(d[171]), "+f"(d[172]), "+f"(d[173]), "+f"(d[174]), "+f"(d[175]), "+f"(d[176]), "+f"(d[177]), "+f"(d[178]), "+f"(d[179]), "+f"(d[180]), "+f"(d[181]), "+f"(d[182]), "+f"(d[183]), "+f"(d[184]), "+f"(d[185]), "+f"(d[186]), "+f"(d[187]), "+f"(d[188]), "+f"(d[189]), "+f"(d[190]), "+f"(d[191])
    : "l"(da), "l"(db), "r"(scale_d));
}
__device__ __forceinline__ void wgmma_n256_k(float (&d)[192], uint64_t da, uint64_t db, int scale_d) {
  asm volatile("{\n.reg .pred p;\nsetp.ne.b32 p, %130, 0;\n"
    "wgmma.mma_async.sync.aligned.m64n256k16.f32.bf16.bf16 {%0, %1, %2, %3, %4, %5, %6, %7, %8, %9, %10, %11, %12, %13, %14, %15, %16, %17, %18, %19, %20, %21, %22, %23, %24, %25, %26, %27, %28, %29, %30, %31, %32, %33, %34, %35, %36, %37, %38, %39, %40, %41, %42, %43, %44, %45, %46, %47, %48, %49, %50, %51, %52, %53, %54, %55, %56, %57, %58, %59, %60, %61, %62, %63, %64, %65, %66, %67, %68, %69, %70, %71, %72, %73, %74, %75, %76, %77, %78, %79, %80, %81, %82, %83, %84, %85, %86, %87, %88, %89, %90, %91, %92, %93, %94, %95, %96, %97, %98, %99, %100, %101, %102, %103, %104, %105, %106, %107, %108, %109, %110, %111, %112, %113, %114, %115, %116, %117, %118, %119, %120, %121, %122, %123, %124, %125, %126, %127}, %128, %129, p, 1, 1, 0, 0;\n}\n"
    : "+f"(d[0]), "+f"(d[1]), "+f"(d[2]), "+f"(d[3]), "+f"(d[4]), "+f"(d[5]), "+f"(d[6]), "+f"(d[7]), "+f"(d[8]), "+f"(d[9]), "+f"(d[10]), "+f"(d[11]), "+f"(d[12]), "+f"(d[13]), "+f"(d[14]), "+f"(d[15]), "+f"(d[16]), "+f"(d[17]), "+f"(d[18]), "+f"(d[19]), "+f"(d[20]), "+f"(d[21]), "+f"(d[22]), "+f"(d[23]), "+f"(d[24]), "+f"(d[25]), "+f"(d[26]), "+f"(d[27]), "+f"(d[28]), "+f"(d[29]), "+f"(d[30]), "+f"(d[31]), "+f"(d[32]), "+f"(d[33]), "+f"(d[34]), "+f"(d[35]), "+f"(d[36]), "+f"(d[37]), "+f"(d[38]), "+f"(d[39]), "+f"(d[40]), "+f"(d[41]), "+f"(d[42]), "+f"(d[43]), "+f"(d[44]), "+f"(d[45]), "+f"(d[46]), "+f"(d[47]), "+f"(d[48]), "+f"(d[49]), "+f"(d[50]), "+f"(d[51]), "+f"(d[52]), "+f"(d[53]), "+f"(d[54]), "+f"(d[55]), "+f"(d[56]), "+f"(d[57]), "+f"(d[58]), "+f"(d[59]), "+f"(d[60]), "+f"(d[61]), "+f"(d[62]), "+f"(d[63]), "+f"(d[64]), "+f"(d[65]), "+f"(d[66]), "+f"(d[67]), "+f"(d[68]), "+f"(d[69]), "+f"(d[70]), "+f"(d[71]), "+f"(d[72]), "+f"(d[73]), "+f"(d[74]), "+f"(d[75]), "+f"(d[76]), "+f"(d[77]), "+f"(d[78]), "+f"(d[79]), "+f"(d[80]), "+f"(d[81]), "+f"(d[82]), "+f"(d[83]), "+f"(d[84]), "+f"(d[85]), "+f"(d[86]), "+f"(d[87]), "+f"(d[88]), "+f"(d[89]), "+f"(d[90]), "+f"(d[91]), "+f"(d[92]), "+f"(d[93]), "+f"(d[94]), "+f"(d[95]), "+f"(d[96]), "+f"(d[97]), "+f"(d[98]), "+f"(d[99]), "+f"(d[100]), "+f"(d[101]), "+f"(d[102]), "+f"(d[103]), "+f"(d[104]), "+f"(d[105]), "+f"(d[106]), "+f"(d[107]), "+f"(d[108]), "+f"(d[109]), "+f"(d[110]), "+f"(d[111]), "+f"(d[112]), "+f"(d[113]), "+f"(d[114]), "+f"(d[115]), "+f"(d[116]), "+f"(d[117]), "+f"(d[118]), "+f"(d[119]), "+f"(d[120]), "+f"(d[121]), "+f"(d[122]), "+f"(d[123]), "+f"(d[124]), "+f"(d[125]), "+f"(d[126]), "+f"(d[127])
    : "l"(da), "l"(db), "r"(scale_d));
}
__device__ __forceinline__ void wgmma_n128_k(float (&d)[192], uint64_t da, uint64_t db, int scale_d) {
  asm volatile("{\n.reg .pred p;\nsetp.ne.b32 p, %66, 0;\n"
    "wgmma.mma_async.sync.aligned.m64n128k16.f32.bf16.bf16 {%0, %1, %2, %3, %4, %5, %6, %7, %8, %9, %10, %11, %12, %13, %14, %15, %16, %17, %18, %19, %20, %21, %22, %23, %24, %25, %26, %27, %28, %29, %30, %31, %32, %33, %34, %35, %36, %37, %38, %39, %40, %41, %42, %43, %44, %45, %46, %47, %48, %49, %50, %51, %52, %53, %54, %55, %56, %57, %58, %59, %60, %61, %62, %63}, %64, %65, p, 1, 1, 0, 0;\n}\n"
    : "+f"(d[128]), "+f"(d[129]), "+f"(d[130]), "+f"(d[131]), "+f"(d[132]), "+f"(d[133]), "+f"(d[134]), "+f"(d[135]), "+f"(d[136]), "+f"(d[137]), "+f"(d[138]), "+f"(d[139]), "+f"(d[140]), "+f"(d[141]), "+f"(d[142]), "+f"(d[143]), "+f"(d[144]), "+f"(d[145]), "+f"(d[146]), "+f"(d[147]), "+f"(d[148]), "+f"(d[149]), "+f"(d[150]), "+f"(d[151]), "+f"(d[152]), "+f"(d[153]), "+f"(d[154]), "+f"(d[155]), "+f"(d[156]), "+f"(d[157]), "+f"(d[158]), "+f"(d[159]), "+f"(d[160]), "+f"(d[161]), "+f"(d[162]), "+f"(d[163]), "+f"(d[164]), "+f"(d[165]), "+f"(d[166]), "+f"(d[167]), "+f"(d[168]), "+f"(d[169]), "+f"(d[170]), "+f"(d[171]), "+f"(d[172]), "+f"(d[173]), "+f"(d[174]), "+f"(d[175]), "+f"(d[176]), "+f"(d[177]), "+f"(d[178]), "+f"(d[179]), "+f"(d[180]), "+f"(d[181]), "+f"(d[182]), "+f"(d[183]), "+f"(d[184]), "+f"(d[185]), "+f"(d[186]), "+f"(d[187]), "+f"(d[188]), "+f"(d[189]), "+f"(d[190]), "+f"(d[191])
    : "l"(da), "l"(db), "r"(scale_d));
}
__device__ __forceinline__ void wgmma_n40_tt(float (&d)[20], uint64_t da, uint64_t db, int scale_d) {
  asm volatile("{\n.reg .pred p;\nsetp.ne.b32 p, %22, 0;\n"
    "wgmma.mma_async.sync.aligned.m64n40k16.f32.bf16.bf16 {%0, %1, %2, %3, %4, %5, %6, %7, %8, %9, %10, %11, %12, %13, %14, %15, %16, %17, %18, %19}, %20, %21, p, 1, 1, 1, 1;\n}\n"
    : "+f"(d[0]), "+f"(d[1]), "+f"(d[2]), "+f"(d[3]), "+f"(d[4]), "+f"(d[5]), "+f"(d[6]), "+f"(d[7]), "+f"(d[8]), "+f"(d[9]), "+f"(d[10]), "+f"(d[11]), "+f"(d[12]), "+f"(d[13]), "+f"(d[14]), "+f"(d[15]), "+f"(d[16]), "+f"(d[17]), "+f"(d[18]), "+f"(d[19])
    : "l"(da), "l"(db), "r"(scale_d));
}
__device__ __forceinline__ void wgmma_n40_rs(float (&d)[20], const uint32_t (&a)[4], uint64_t db, int scale_d) {
  asm volatile("{\n.reg .pred p;\nsetp.ne.b32 p, %25, 0;\n"
    "wgmma.mma_async.sync.aligned.m64n40k16.f32.bf16.bf16 {%0, %1, %2, %3, %4, %5, %6, %7, %8, %9, %10, %11, %12, %13, %14, %15, %16, %17, %18, %19}, {%20, %21, %22, %23}, %24, p, 1, 1, 1;\n}\n"
    : "+f"(d[0]), "+f"(d[1]), "+f"(d[2]), "+f"(d[3]), "+f"(d[4]), "+f"(d[5]), "+f"(d[6]), "+f"(d[7]), "+f"(d[8]), "+f"(d[9]), "+f"(d[10]), "+f"(d[11]), "+f"(d[12]), "+f"(d[13]), "+f"(d[14]), "+f"(d[15]), "+f"(d[16]), "+f"(d[17]), "+f"(d[18]), "+f"(d[19])
    : "r"(a[0]), "r"(a[1]), "r"(a[2]), "r"(a[3]), "l"(db), "r"(scale_d));
}
__device__ __forceinline__ void wgmma_n256_0(float (&d)[192], uint64_t da, uint64_t db) {
  asm volatile("{\n.reg .pred p;\nsetp.ne.b32 p, 0, 0;\n"
    "wgmma.mma_async.sync.aligned.m64n256k16.f32.bf16.bf16 {%0, %1, %2, %3, %4, %5, %6, %7, %8, %9, %10, %11, %12, %13, %14, %15, %16, %17, %18, %19, %20, %21, %22, %23, %24, %25, %26, %27, %28, %29, %30, %31, %32, %33, %34, %35, %36, %37, %38, %39, %40, %41, %42, %43, %44, %45, %46, %47, %48, %49, %50, %51, %52, %53, %54, %55, %56, %57, %58, %59, %60, %61, %62, %63, %64, %65, %66, %67, %68, %69, %70, %71, %72, %73, %74, %75, %76, %77, %78, %79, %80, %81, %82, %83, %84, %85, %86, %87, %88, %89, %90, %91, %92, %93, %94, %95, %96, %97, %98, %99, %100, %101, %102, %103, %104, %105, %106, %107, %108, %109, %110, %111, %112, %113, %114, %115, %116, %117, %118, %119, %120, %121, %122, %123, %124, %125, %126, %127}, %128, %129, p, 1, 1, 0, 1;\n}\n"
    : "=f"(d[0]), "=f"(d[1]), "=f"(d[2]), "=f"(d[3]), "=f"(d[4]), "=f"(d[5]), "=f"(d[6]), "=f"(d[7]), "=f"(d[8]), "=f"(d[9]), "=f"(d[10]), "=f"(d[11]), "=f"(d[12]), "=f"(d[13]), "=f"(d[14]), "=f"(d[15]), "=f"(d[16]), "=f"(d[17]), "=f"(d[18]), "=f"(d[19]), "=f"(d[20]), "=f"(d[21]), "=f"(d[22]), "=f"(d[23]), "=f"(d[24]), "=f"(d[25]), "=f"(d[26]), "=f"(d[27]), "=f"(d[28]), "=f"(d[29]), "=f"(d[30]), "=f"(d[31]), "=f"(d[32]), "=f"(d[33]), "=f"(d[34]), "=f"(d[35]), "=f"(d[36]), "=f"(d[37]), "=f"(d[38]), "=f"(d[39]), "=f"(d[40]), "=f"(d[41]), "=f"(d[42]), "=f"(d[43]), "=f"(d[44]), "=f"(d[45]), "=f"(d[46]), "=f"(d[47]), "=f"(d[48]), "=f"(d[49]), "=f"(d[50]), "=f"(d[51]), "=f"(d[52]), "=f"(d[53]), "=f"(d[54]), "=f"(d[55]), "=f"(d[56]), "=f"(d[57]), "=f"(d[58]), "=f"(d[59]), "=f"(d[60]), "=f"(d[61]), "=f"(d[62]), "=f"(d[63]), "=f"(d[64]), "=f"(d[65]), "=f"(d[66]), "=f"(d[67]), "=f"(d[68]), "=f"(d[69]), "=f"(d[70]), "=f"(d[71]), "=f"(d[72]), "=f"(d[73]), "=f"(d[74]), "=f"(d[75]), "=f"(d[76]), "=f"(d[77]), "=f"(d[78]), "=f"(d[79]), "=f"(d[80]), "=f"(d[81]), "=f"(d[82]), "=f"(d[83]), "=f"(d[84]), "=f"(d[85]), "=f"(d[86]), "=f"(d[87]), "=f"(d[88]), "=f"(d[89]), "=f"(d[90]), "=f"(d[91]), "=f"(d[92]), "=f"(d[93]), "=f"(d[94]), "=f"(d[95]), "=f"(d[96]), "=f"(d[97]), "=f"(d[98]), "=f"(d[99]), "=f"(d[100]), "=f"(d[101]), "=f"(d[102]), "=f"(d[103]), "=f"(d[104]), "=f"(d[105]), "=f"(d[106]), "=f"(d[107]), "=f"(d[108]), "=f"(d[109]), "=f"(d[110]), "=f"(d[111]), "=f"(d[112]), "=f"(d[113]), "=f"(d[114]), "=f"(d[115]), "=f"(d[116]), "=f"(d[117]), "=f"(d[118]), "=f"(d[119]), "=f"(d[120]), "=f"(d[121]), "=f"(d[122]), "=f"(d[123]), "=f"(d[124]), "=f"(d[125]), "=f"(d[126]), "=f"(d[127])
    : "l"(da), "l"(db));
}
__device__ __forceinline__ void wgmma_n128_0(float (&d)[192], uint64_t da, uint64_t db) {
  asm volatile("{\n.reg .pred p;\nsetp.ne.b32 p, 0, 0;\n"
    "wgmma.mma_async.sync.aligned.m64n128k16.f32.bf16.bf16 {%0, %1, %2, %3, %4, %5, %6, %7, %8, %9, %10, %11, %12, %13, %14, %15, %16, %17, %18, %19, %20, %21, %22, %23, %24, %25, %26, %27, %28, %29, %30, %31, %32, %33, %34, %35, %36, %37, %38, %39, %40, %41, %42, %43, %44, %45, %46, %47, %48, %49, %50, %51, %52, %53, %54, %55, %56, %57, %58, %59, %60, %61, %62, %63}, %64, %65, p, 1, 1, 0, 1;\n}\n"
    : "=f"(d[128]), "=f"(d[129]), "=f"(d[130]), "=f"(d[131]), "=f"(d[132]), "=f"(d[133]), "=f"(d[134]), "=f"(d[135]), "=f"(d[136]), "=f"(d[137]), "=f"(d[138]), "=f"(d[139]), "=f"(d[140]), "=f"(d[141]), "=f"(d[142]), "=f"(d[143]), "=f"(d[144]), "=f"(d[145]), "=f"(d[146]), "=f"(d[147]), "=f"(d[148]), "=f"(d[149]), "=f"(d[150]), "=f"(d[151]), "=f"(d[152]), "=f"(d[153]), "=f"(d[154]), "=f"(d[155]), "=f"(d[156]), "=f"(d[157]), "=f"(d[158]), "=f"(d[159]), "=f"(d[160]), "=f"(d[161]), "=f"(d[162]), "=f"(d[163]), "=f"(d[164]), "=f"(d[165]), "=f"(d[166]), "=f"(d[167]), "=f"(d[168]), "=f"(d[169]), "=f"(d[170]), "=f"(d[171]), "=f"(d[172]), "=f"(d[173]), "=f"(d[174]), "=f"(d[175]), "=f"(d[176]), "=f"(d[177]), "=f"(d[178]), "=f"(d[179]), "=f"(d[180]), "=f"(d[181]), "=f"(d[182]), "=f"(d[183]), "=f"(d[184]), "=f"(d[185]), "=f"(d[186]), "=f"(d[187]), "=f"(d[188]), "=f"(d[189]), "=f"(d[190]), "=f"(d[191])
    : "l"(da), "l"(db));
}
__device__ __forceinline__ void wgmma_n64a(float (&d)[192], uint64_t da, uint64_t db, int scale_d) {
  asm volatile("{\n.reg .pred p;\nsetp.ne.b32 p, %34, 0;\n"
    "wgmma.mma_async.sync.aligned.m64n64k16.f32.bf16.bf16 {%0, %1, %2, %3, %4, %5, %6, %7, %8, %9, %10, %11, %12, %13, %14, %15, %16, %17, %18, %19, %20, %21, %22, %23, %24, %25, %26, %27, %28, %29, %30, %31}, %32, %33, p, 1, 1, 0, 1;\n}\n"
    : "+f"(d[128]), "+f"(d[129]), "+f"(d[130]), "+f"(d[131]), "+f"(d[132]), "+f"(d[133]), "+f"(d[134]), "+f"(d[135]), "+f"(d[136]), "+f"(d[137]), "+f"(d[138]), "+f"(d[139]), "+f"(d[140]), "+f"(d[141]), "+f"(d[142]), "+f"(d[143]), "+f"(d[144]), "+f"(d[145]), "+f"(d[146]), "+f"(d[147]), "+f"(d[148]), "+f"(d[149]), "+f"(d[150]), "+f"(d[151]), "+f"(d[152]), "+f"(d[153]), "+f"(d[154]), "+f"(d[155]), "+f"(d[156]), "+f"(d[157]), "+f"(d[158]), "+f"(d[159])
    : "l"(da), "l"(db), "r"(scale_d));
}
__device__ __forceinline__ void wgmma_n64b(float (&d)[192], uint64_t da, uint64_t db, int scale_d) {
  asm volatile("{\n.reg .pred p;\nsetp.ne.b32 p, %34, 0;\n"
    "wgmma.mma_async.sync.aligned.m64n64k16.f32.bf16.bf16 {%0, %1, %2, %3, %4, %5, %6, %7, %8, %9, %10, %11, %12, %13, %14, %15, %16, %17, %18, %19, %20, %21, %22, %23, %24, %25, %26, %27, %28, %29, %30, %31}, %32, %33, p, 1, 1, 0, 1;\n}\n"
    : "+f"(d[160]), "+f"(d[161]), "+f"(d[162]), "+f"(d[163]), "+f"(d[164]), "+f"(d[165]), "+f"(d[166]), "+f"(d[167]), "+f"(d[168]), "+f"(d[169]), "+f"(d[170]), "+f"(d[171]), "+f"(d[172]), "+f"(d[173]), "+f"(d[174]), "+f"(d[175]), "+f"(d[176]), "+f"(d[177]), "+f"(d[178]), "+f"(d[179]), "+f"(d[180]), "+f"(d[181]), "+f"(d[182]), "+f"(d[183]), "+f"(d[184]), "+f"(d[185]), "+f"(d[186]), "+f"(d[187]), "+f"(d[188]), "+f"(d[189]), "+f"(d[190]), "+f"(d[191])
    : "l"(da), "l"(db), "r"(scale_d));
}

constexpr int SLOT = 16384;
constexpr int KVT = 10240;
constexpr uint32_t QA = 0x0BAu, QK = 0x462u, QQ = 0x981u;
constexpr int SM_SD = 12 * SLOT;
constexpr int SM_BAR = SM_SD + 8192;
constexpr int SM_RS = SM_BAR + 512;
constexpr int SM_AP = SM_RS + 768;
constexpr int SM_BP = SM_AP + 2048;
constexpr int SM_WPHI = SM_BP + 12288;
constexpr int SM_EPOCH = SM_WPHI + 10240;
constexpr int SM_TOTAL = SM_EPOCH + 16 + 1024;
constexpr int B_FULLS = 0, B_XOLD = 24, B_STAT = 32, B_EMPTYS = 40, B_FULLT = 256  , B_CONS = 384  , B_E3 = 472, B_E0 = 480, B_E1 = 488, B_E2 = 496, B_EPI = 504, B_CS = 160,
              B_KVDONE = 168  , B_ODONE = 176, B_XDONE = 184, B_OH1 = 192, B_CS2 = 208, B_XH0 = 232, B_R0 = 240, B_XOLD2 = 216, B_FLG = 64  ;
constexpr uint64_t BAR_CNT = 0x1c07fc0eac00a800ull;
constexpr uint64_t WO_A0 = 0xba76218762187643ull, WO_B0 = 0x9540395403ba9021ull, WO_A1 = 0xba713257132576abull, WO_B1 = 0x9506489064890132ull;
constexpr uint64_t WO_DA0 = 0xa9876543210edd00ull, WO_DB0 = 0xa987654321bbccccull, WO_DA1 = 0xa9876543210fff00ull, WO_DB1 = 0xa98765432bbcccddull;
constexpr int XS = 10;

#define PL 2
#define PROFX(i) PROFT(tid_ == 128 && layer == PL, 200 + (i))
#define PSL 20
#define EP 5
#define DRY 0
#define NCOM 3
#define CG0 0
#define CG1 99
#define CPF 0
#define CSLP 128
#define PFS 8
#define KVTH 0x41700000u
#define CSW 1
#define RL 3
#define ORD 1
#define XB2 2
#define XEP 0
#define PMOD 3
#define DB1 2
#define NLAYERS 4
constexpr float L2E = 1.4426950408889634f;
#define PHI_MAX 2147483648.f

#define D128(lo) desc64(lo, 0x40000040u)
struct Ctx { uint32_t sb; int g, rb, cu; bf16* out; };

__device__ __forceinline__ void colsum_load(const bf16* __restrict__ w, int rb, int g, int wi, int lane, uint32_t stg, float (&s)[8]) {
  const int ch = wi * 8 + (lane & 7), sec = ch >> 4;
  const bf16* src = w + (size_t)(rb * 64 + (lane >> 3) * 16) * 3072 + (sec == 2 ? 0 : 1024 + sec * 1024) + g * 128 + (ch & 15) * 8;
  stg += lane * 16;
#pragma unroll
  for (int i = 0; i < 8; ++i) s[i] = 0.f;
#pragma unroll
  for (int r = 0; r < 12; ++r)
    asm volatile("cp.async.cg.shared.global [%0], [%1], 16;" ::"r"(stg + r * 512), "l"(src + (size_t)(4 + r) * 3072) : "memory");
  uint4 v[4];
#pragma unroll
  for (int r = 0; r < 4; ++r) v[r] = __ldg(reinterpret_cast<const uint4*>(src + (size_t)r * 3072));
#pragma unroll 1
  for (int r0 = 0;; ++r0) {
#pragma unroll
    for (int r = 0; r < 4; ++r) {
      s[0] += bf_lo(v[r].x); s[1] += bf_hi(v[r].x); s[2] += bf_lo(v[r].y); s[3] += bf_hi(v[r].y);
      s[4] += bf_lo(v[r].z); s[5] += bf_hi(v[r].z); s[6] += bf_lo(v[r].w); s[7] += bf_hi(v[r].w);
    }
    if (r0 == 3) break;
    asm volatile("cp.async.wait_all;" ::: "memory");
#pragma unroll
    for (int r = 0; r < 4; ++r) v[r] = lds128(stg + (r0 * 4 + r) * 512);
  }
#pragma unroll
  for (int i = 0; i < 8; ++i) { s[i] += __shfl_xor_sync(0xffffffffu, s[i], 8); s[i] += __shfl_xor_sync(0xffffffffu, s[i], 16); }
}
__device__ __forceinline__ void colsum_red(float* cs, int g, int wi, int lane, const float (&s)[8]) {
  if (lane < 8) {
    red_add4(cs + g * 384 + (wi * 8 + lane) * 8, s[0], s[1], s[2], s[3]);
    red_add4(cs + g * 384 + (wi * 8 + lane) * 8 + 4, s[4], s[5], s[6], s[7]);
  }
}
#define PHASE_CTX() \
  uint32_t sb = c.sb; asm volatile("" : "+r"(sb)); \
  int tid_ = threadIdx.x; asm volatile("" : "+r"(tid_)); \
  const uint32_t bar = sb + SM_BAR; \
  const int lane = tid_ & 31, cw = (tid_ >> 5) - 4, wg = cw >> 2, wq = cw & 3, gq = lane >> 2, t = lane & 3, wrow0 = cw * 16; \
  const int lrow = (lane & 7) + ((lane >> 3) & 1) * 8, lchk = lane >> 4; \
  const bool elected = (tid_ & 127) == 0; \
  const uint32_t rowo = (wrow0 + lrow) * 128, X = (lchk ^ (lane & 7)) << 4; \
  (void)bar; (void)wq; (void)gq; (void)lrow; (void)lchk; (void)elected; (void)wrow0; (void)wg; (void)rowo; (void)X; (void)t;

__device__ __forceinline__ void slab_out_half(uint32_t slot, bf16* dst, int wrow0, int lane, bool FENCE = false) {
  const int r0 = lane >> 3, ch = lane & 7;
  const uint32_t src = slot + (wrow0 + r0) * 128;
  uint4 v[4];
#pragma unroll
  for (int i = 0; i < 4; ++i) v[i] = lds128(src + i * 512 + (((ch ^ (4 * i + r0)) & 7) << 4));
  if (FENCE) fence_async_smem();
  dst += (size_t)(wrow0 + r0) * D_ + ch * 8;
#pragma unroll
  for (int i = 0; i < 4; ++i)
    asm volatile("st.global.v4.u32 [%0], {%1,%2,%3,%4};" ::"l"(dst + (size_t)i * 4 * D_), "r"(v[i].x), "r"(v[i].y), "r"(v[i].z), "r"(v[i].w) : "memory");
}

template <int O>
__device__ __forceinline__ void phi_proj(float (&p)[2][4][4], const uint32_t (&kq)[64], uint32_t wa) {
#pragma unroll
  for (int h = 0; h < 2; ++h)
#pragma unroll
    for (int i = 0; i < 4; ++i) { p[h][i][0] = p[h][i][1] = p[h][i][2] = p[h][i][3] = 0.f; }
#pragma unroll
  for (int ks = 0; ks < 2; ++ks)
#pragma unroll
    for (int np = 0; np < 2; ++np)
#pragma unroll
      for (int h = 0; h < 2; ++h) {
        uint32_t b0, b1, b2, b3;
        ldsm_x4_t(b0, b1, b2, b3, wa + h * 2560 + ks * 1280 + np * 32);
        mma_bf16(p[h][2 * np], kq[O + 8 * h + 4 * ks], kq[O + 8 * h + 4 * ks + 1], kq[O + 8 * h + 4 * ks + 2], kq[O + 8 * h + 4 * ks + 3], b0, b1);
        mma_bf16(p[h][2 * np + 1], kq[O + 8 * h + 4 * ks], kq[O + 8 * h + 4 * ks + 1], kq[O + 8 * h + 4 * ks + 2], kq[O + 8 * h + 4 * ks + 3], b2, b3);
      }
}
__device__ __forceinline__ void phi_exp(uint32_t (&raw)[4][4], const float (&p)[4][4], float sc0, float sc1) {
#pragma unroll
  for (int i = 0; i < 4; ++i) {
    const float e0 = ex2(p[i][0] * sc0), e1 = ex2(p[i][1] * sc0), e2 = ex2(p[i][2] * sc1), e3 = ex2(p[i][3] * sc1);
    const float m0 = e0 * e1, m1 = e2 * e3, rr = rcp(m0 * m1), r0 = rr * m1, r1 = rr * m0;
    raw[i >> 1][(i & 1) * 2] = pack_bf16(e0, e1);
    raw[i >> 1][(i & 1) * 2 + 1] = pack_bf16(e2, e3);
    raw[2 + (i >> 1)][(i & 1) * 2] = pack_bf16(e1 * r0, e0 * r0);
    raw[2 + (i >> 1)][(i & 1) * 2 + 1] = pack_bf16(e3 * r1, e2 * r1);
  }
}
#define FENCE_P(h) _Pragma("unroll") for (int i_ = 0; i_ < 16; ++i_) asm volatile("" : "+f"(p[h][i_ >> 2][i_ & 3]) :: "memory")
#define FENCE_RAW(h) _Pragma("unroll") for (int i_ = 0; i_ < 16; ++i_) asm volatile("" : "+r"(raw[h][i_ >> 2][i_ & 3]) :: "memory")
template <int O>
__device__ __forceinline__ void phi_norm(uint32_t (&ph)[2][4][4], const uint32_t (&raw)[2][4][4], const uint32_t (&kq)[64], uint32_t wa,
                                         float sc0, float sc1, float mul0, float mul1) {
  bool bad = false;
#pragma unroll
  for (int h = 0; h < 2; ++h)
#pragma unroll
    for (int sg = 0; sg < 2; ++sg) {
      float ss[4] = {0.f, 0.f, 0.f, 0.f};
#pragma unroll
      for (int ks = 0; ks < 2; ++ks)
        mma_bf16(ss, raw[h][2 * sg + ks][0], raw[h][2 * sg + ks][1], raw[h][2 * sg + ks][2], raw[h][2 * sg + ks][3], 0x3F803F80u, 0x3F803F80u);
      bad = bad || !(ss[0] < PHI_MAX) || !(ss[2] < PHI_MAX);
      const uint32_t iv = pack_bf16(rcp(ss[0]) * mul0, rcp(ss[2]) * mul1);
#pragma unroll
      for (int ks = 0; ks < 2; ++ks)
#pragma unroll
        for (int j = 0; j < 4; ++j) ph[h][2 * sg + ks][j] = mul_bf16x2(raw[h][2 * sg + ks][j], iv, j & 1);
    }
  if (__builtin_expect(__any_sync(0xffffffffu, bad), 0)) {
#pragma unroll 1
    for (int it = 0; it < 4; ++it) {
      float q[4][4];
#pragma unroll
      for (int i = 0; i < 4; ++i) { q[i][0] = q[i][1] = q[i][2] = q[i][3] = 0.f; }
#pragma unroll
      for (int ks = 0; ks < 2; ++ks) {
        uint32_t a[4];
#pragma unroll
        for (int j = 0; j < 4; ++j) a[j] = (it & 2) ? kq[O + 8 + 4 * ks + j] : kq[O + 4 * ks + j];
#pragma unroll
        for (int np = 0; np < 2; ++np) {
          uint32_t b0, b1, b2, b3;
          ldsm_x4_t(b0, b1, b2, b3, wa + (it >> 1) * 2560 + ks * 1280 + np * 32);
          mma_bf16(q[2 * np], a[0], a[1], a[2], a[3], b0, b1);
          mma_bf16(q[2 * np + 1], a[0], a[1], a[2], a[3], b2, b3);
        }
      }
      float iv[2];
#pragma unroll
      for (int r = 0; r < 2; ++r) {
        const float sc = (it & 1) ? -(r ? sc1 : sc0) : (r ? sc1 : sc0);
        float mx = -INFINITY, sm = 0.f;
#pragma unroll
        for (int i = 0; i < 8; ++i) { float& v = q[i >> 1][2 * r + (i & 1)]; v *= sc; mx = fmaxf(mx, v); }
        mx = fmaxf(mx, __shfl_xor_sync(0xffffffffu, mx, 1));
        mx = fmaxf(mx, __shfl_xor_sync(0xffffffffu, mx, 2));
#pragma unroll
        for (int i = 0; i < 8; ++i) { float& v = q[i >> 1][2 * r + (i & 1)]; v = ex2(v - mx); sm += v; }
        sm += __shfl_xor_sync(0xffffffffu, sm, 1);
        sm += __shfl_xor_sync(0xffffffffu, sm, 2);
        iv[r] = rcp(sm) * (r ? mul1 : mul0);
      }
#pragma unroll
      for (int i = 0; i < 24; ++i) ph[i >> 4][(i >> 2) & 3][i & 3] = ph[(i + 8) >> 4][((i + 8) >> 2) & 3][i & 3];
#pragma unroll
      for (int i = 0; i < 4; ++i) {
        ph[1][2 + (i >> 1)][(i & 1) * 2] = pack_bf16(q[i][0] * iv[0], q[i][1] * iv[0]);
        ph[1][2 + (i >> 1)][(i & 1) * 2 + 1] = pack_bf16(q[i][2] * iv[1], q[i][3] * iv[1]);
      }
    }
  }
}

__device__ __forceinline__ void stats_out(float s0, float s1, float q0, float q1, float2* dst, int t) {
  const bool od = t & 1;
  float sa = od ? s1 : s0, qa = od ? q1 : q0;
  sa += __shfl_xor_sync(0xffffffffu, od ? s0 : s1, 1);
  qa += __shfl_xor_sync(0xffffffffu, od ? q0 : q1, 1);
  sa += __shfl_xor_sync(0xffffffffu, sa, 2);
  qa += __shfl_xor_sync(0xffffffffu, qa, 2);
  if (t < 2) red_add2(&dst[t * 8].x, sa, qa);
}

__device__ __forceinline__ void consumer(const Ctx& c) {
  const int g = c.g, m0 = c.rb * 128;
  float acc[192];
#define X_H1() \
      _Pragma("unroll") for (int jp = 4; jp < 8; ++jp) \
        stsm_x4(sb + (XS + 1) * SLOT + rowo + (X ^ ((jp & 3) << 5)), \
                pack_bf16(acc[128 + 8 * jp], acc[129 + 8 * jp]), pack_bf16(acc[130 + 8 * jp], acc[131 + 8 * jp]), \
                pack_bf16(acc[132 + 8 * jp], acc[133 + 8 * jp]), pack_bf16(acc[134 + 8 * jp], acc[135 + 8 * jp]));
#pragma unroll
  for (int i = 128; i < 192; ++i) acc[i] = 0.f;
#pragma unroll 1
  for (int layer = 0;; ++layer) {
    {
      PHASE_CTX();
      const uint32_t wu = c.cu >> 2;
      const uint32_t dA0 = (((sb + wu * 8192) & 0x3FFFF) >> 4) | (1u << 16), dB0 = ((sb & 0x3FFFF) >> 4) | (512u << 16);
      {
        PROFX(0);
        mbar_wait(bar + B_FULLS, 0);
        PROFX(1);
        wgmma_fence();
        wgmma_n256_0(acc, D128(dA0 + XS * 1024), D128(dB0 + 2048));
#pragma unroll
        for (int k = 1; k < 4; ++k) wgmma_n256(acc, D128(dA0 + XS * 1024 + k * 2), D128(dB0 + 2048 + k * 128), 1);
        wgmma_commit();
        wgmma_wait<1>();
        float s0 = 0.f, s1 = 0.f, q0 = 0.f, q1 = 0.f;
        if (layer) {
          X_H1();
#pragma unroll
          for (int i = 128; i < 192; i += 4) {
            s0 += acc[i] + acc[i + 1]; s1 += acc[i + 2] + acc[i + 3];
            q0 = fmaf(acc[i], acc[i], fmaf(acc[i + 1], acc[i + 1], q0)); q1 = fmaf(acc[i + 2], acc[i + 2], fmaf(acc[i + 3], acc[i + 3], q1));
          }
        }
        asm volatile("" : "+f"(s0), "+f"(s1), "+f"(q0), "+f"(q1) :: "memory");
        wgmma_fence();
        wgmma_n128_0(acc, D128(dA0 + XS * 1024), D128(dB0 + 1024));
#pragma unroll
        for (int k = 1; k < 4; ++k) wgmma_n128(acc, D128(dA0 + XS * 1024 + k * 2), D128(dB0 + 1024 + k * 128), 1);
        wgmma_commit();
        if (layer) {
          PHASE_CTX();
          fence_async_smem();
          nbar_dyn(3 + wu, 128);
          stats_out(s0, s1, q0, q1, g_stats + layer * S_ + m0 + wrow0 + gq, t);
          PROFT(tid_ == 128, layer * 16 + 8);
        }
      }
      uint32_t s = 1, u = 0, sp = 0;
      const int ix = layer ? 1 : 2 * min(g, NCOM) + 1;
#pragma unroll 1
      for (int i = 1; i < 14; ++i) {
        mbar_wait(bar + B_FULLS + s * 8, (u + (s ? layer : 0)) & 1);
        const uint32_t da = dA0 + ((QA >> (4 * s)) & 15) * 1024, dk = dB0 + ((QK >> (4 * s)) & 15) * 1024,
                       dq = dB0 + ((QQ >> (4 * s)) & 15) * 1024;
        wgmma_fence();
#pragma unroll
        for (int k = 0; k < 4; ++k) {
          wgmma_n256(acc, D128(da + k * 2), D128(dk + k * 128), 1);
          wgmma_n128(acc, D128(da + k * 2), D128(dq + k * 128), 1);
        }
        wgmma_commit();
        if (i == ix || (i == ix + 1 && !layer)) {
          PHASE_CTX();
          if (layer) {
            slab_out_half(sb + (XS + 1) * SLOT, g_x + (size_t)m0 * D_ + g * 128 + 64, wrow0, lane);
          } else {
            float s0 = 0.f, s1 = 0.f, q0 = 0.f, q1 = 0.f;
            const uint32_t xa = sb + ((QA >> (4 * sp)) & 15) * SLOT + rowo;
#pragma unroll
            for (int jp = 0; jp < 4; ++jp) {
              uint32_t x0, x1, x2, x3;
              ldsm_x4(x0, x1, x2, x3, xa + (X ^ (jp << 5)));
              s0 += (bf_lo(x0) + bf_hi(x0)) + (bf_lo(x2) + bf_hi(x2));
              s1 += (bf_lo(x1) + bf_hi(x1)) + (bf_lo(x3) + bf_hi(x3));
              q0 = fmaf(bf_lo(x0), bf_lo(x0), fmaf(bf_hi(x0), bf_hi(x0), fmaf(bf_lo(x2), bf_lo(x2), fmaf(bf_hi(x2), bf_hi(x2), q0))));
              q1 = fmaf(bf_lo(x1), bf_lo(x1), fmaf(bf_hi(x1), bf_hi(x1), fmaf(bf_lo(x3), bf_lo(x3), fmaf(bf_hi(x3), bf_hi(x3), q1))));
            }
            stats_out(s0, s1, q0, q1, g_stats + m0 + wrow0 + gq, t);
          }
          __syncwarp();
          if (lane == 0 && (layer || i != ix)) mbar_arrive(bar + B_XDONE);
          nbar_dyn(3 + wu, 128);
        }
        wgmma_wait<1>();
        if (elected) release2(bar + B_EMPTYS + sp * 8);
        sp = s;
        if (++s == 3) { s = 0; ++u; }
      }
      {
        const uint64_t dap = make_desc_ns(sb + SM_AP + wu * 1024, 0, 128), dbp = make_desc_ns(sb + SM_BP + (layer & 1) * 6144, 0, 128);
        if (wu == 0) {
          wgmma_wait<0>();
          if (elected) mbar_arrive(bar + B_R0);
          nbar<6, 256>();
        }
        if (layer < 2) mbar_wait(bar + (layer ? B_CS2 : B_CS), 0);
        mbar_wait(bar + B_STAT, layer & 1);
        mbar_wait(bar + B_FULLS + 16, layer & 1);
        wgmma_fence();
        wgmma_n256_k(acc, dap, dbp, 1);
#pragma unroll
        for (int k = 0; k < 4; ++k) wgmma_n256(acc, D128(dA0 + (QA >> 8) * 1024 + k * 2), D128(dB0 + (QK >> 8) * 1024 + k * 128), 1);
        mbar_wait(bar + B_FULLS, 1);
        PROFT(tid_ == 128, layer * 16 + 9);
        wgmma_fence();
#pragma unroll
        for (int k = 0; k < 4; ++k) wgmma_n256(acc, D128(dA0 + (QA & 15) * 1024 + k * 2), D128(dB0 + (QK & 15) * 1024 + k * 128), 1);
        wgmma_commit();
        if (wu) nbar<6, 256>();
#define Q_TAIL() \
        wgmma_n128_k(acc, dap, dbp + 256, 1); \
        _Pragma("unroll") for (int k = 0; k < 4; ++k) wgmma_n128(acc, D128(dA0 + (QA >> 8) * 1024 + k * 2), D128(dB0 + (QQ >> 8) * 1024 + k * 128), 1); \
        _Pragma("unroll") for (int k = 0; k < 4; ++k) wgmma_n128(acc, D128(dA0 + (QA & 15) * 1024 + k * 2), D128(dB0 + (QQ & 15) * 1024 + k * 128), 1);
        Q_TAIL();
        wgmma_commit();
        wgmma_wait<1>();
#pragma unroll
        for (int i = 0; i < 128; ++i) asm volatile("" : "+f"(acc[i]) :: "memory");
      }
    }
    uint32_t xo[32];
    {
      PHASE_CTX();
      PROFT(tid_ == 128, layer * 16 + 1);
      const bool isB = layer & 1;
      const int cu = c.cu;
      if (cu >= 4) asm volatile("bar.arrive 7, 256;" ::: "memory");
      if (elected && cu == 4) mbar_arrive(bar + B_R0);
      uint32_t kq[64];
      const uint32_t rowq = rowo & 8191;
      const float rs0 = lds_f(sb + SM_RS + (16 + wrow0 + gq) * 4), rs1 = lds_f(sb + SM_RS + (24 + wrow0 + gq) * 4);
#define Q_DONE() \
      wgmma_wait<0>(); \
      if (lane == 0) release2(bar + B_E0); \
      _Pragma("unroll") for (int i = 128; i < 192; ++i) asm volatile("" : "+f"(acc[i]) :: "memory"); \
      _Pragma("unroll") for (int i = 0; i < 32; ++i) kq[32 + i] = pack_bf16(acc[128 + 2 * i], acc[129 + 2 * i]);
      if (isB) {
        if (cu == 0) asm volatile("bar.arrive 10, 64;" ::: "memory");
        if (elected) release2(bar + B_E1);
        const int e = gq & 1;
        const bool sel = t > (gq >> 1);
        const uint32_t rja = sb + SM_RS + (wrow0 + 2 * t + e) * 4;
        const float rjA0 = lds_f(rja + 32), rjA1 = lds_f(rja + 64), rjB0 = lds_f(rja + (sel ? 0 : 64)), rjB1 = lds_f(rja + (sel ? 32 : 96));
        uint32_t vv[32];
#pragma unroll
        for (int i = 0; i < 16; ++i) { kq[i] = pack_bf16(acc[2 * i], acc[2 * i + 1]); vv[i] = pack_bf16(acc[64 + 2 * i], acc[65 + 2 * i]); }
        const uint32_t rB = sb + 4 * SLOT + wg * 4 * KVT + rowq;
        auto dump = [&](int hp) {
          const uint32_t kb = rB + 2048 + (hp ^ wg) * 2 * KVT;
#pragma unroll
          for (int jp = 0; jp < 4; ++jp) {
            stsm_x4(kb + (X ^ (jp << 5)), kq[16 * hp + 4 * jp], kq[16 * hp + 4 * jp + 1], kq[16 * hp + 4 * jp + 2], kq[16 * hp + 4 * jp + 3]);
            stsm_x4(kb + KVT + (X ^ (jp << 5)), vv[16 * hp + 4 * jp], vv[16 * hp + 4 * jp + 1], vv[16 * hp + 4 * jp + 2], vv[16 * hp + 4 * jp + 3]);
          }
          if (cu == 3) {
            const uint32_t kd = rB + 2048 + 32768 + (1 - hp) * 2 * KVT;
#pragma unroll
            for (int jp = 0; jp < 4; ++jp) {
              stsm_x4(kd + (X ^ (jp << 5)), kq[16 * hp + 4 * jp], kq[16 * hp + 4 * jp + 1], kq[16 * hp + 4 * jp + 2], kq[16 * hp + 4 * jp + 3]);
              stsm_x4(kd + KVT + (X ^ (jp << 5)), vv[16 * hp + 4 * jp], vv[16 * hp + 4 * jp + 1], vv[16 * hp + 4 * jp + 2], vv[16 * hp + 4 * jp + 3]);
            }
            if (hp) asm volatile("bar.arrive 15, 64;" ::: "memory"); else asm volatile("bar.arrive 9, 64;" ::: "memory");
          }
          asm volatile("bar.arrive %0, 224;" :: "r"(hp ? 13 + (cu >> 2) : 8 + (cu & 4)) : "memory");
        };
        uint4* const hbuf = g_halo + ((c.rb * 8 + g) * 2 + (layer >> 1)) * 512 + lane;
        if (cu < 4) {
          nbar<7, 256>();
          dump(0);
        }
#pragma unroll
        for (int i = 16; i < 32; ++i) { kq[i] = pack_bf16(acc[2 * i], acc[2 * i + 1]); vv[i] = pack_bf16(acc[64 + 2 * i], acc[65 + 2 * i]); }
        if (cu >= 4) {
          if (cu == 7) {
#pragma unroll
            for (int jp = 0; jp < 8; ++jp) {
              st_relaxed4(hbuf + jp * 32, ~kq[4 * jp], ~kq[4 * jp + 1], ~kq[4 * jp + 2], ~kq[4 * jp + 3]);
              st_relaxed4(hbuf + 256 + jp * 32, ~vv[4 * jp], ~vv[4 * jp + 1], ~vv[4 * jp + 2], ~vv[4 * jp + 3]);
            }
          }
          dump(0);
          dump(1);
        }
        PROFT(tid_ == 128, layer * 16 + 2);
        constexpr float SC = 0.17677669529663687f * L2E;
        const float fA0 = rjA0 * rs0 * SC, fB0 = rjB0 * rs0 * SC, fA1 = rjA1 * rs1 * SC, fB1 = rjB1 * rs1 * SC;
        const float bA0 = (m0 + wrow0) ? 0.f : -1e30f, bB = sel ? bA0 : 0.f;
        const uint32_t pA_ = e ? 0x1044u : 0x4410u, pB_ = e ? 0x3244u : 0x4432u, pLo = sel ? pB_ : 0x4444u, pHi = sel ? 0x4444u : pB_;
        const uint32_t KX = ((lane >> 3) ^ (lane & 7)) << 4;
        Q_DONE();
        if (cu == 0) {
          nbar<11, 64>();
        } else if (cu == 4) {
          uint4 hv[16];
          if (c.rb > 0) {
            uint32_t n = 0;
#pragma unroll 1
            while (true) {
              uint32_t mn = 0xFFFFFFFFu;
#pragma unroll
              for (int i = 0; i < 16; ++i) hv[i] = ld_relaxed4(hbuf - 16 * 512 + i * 32);
#pragma unroll
              for (int i = 0; i < 16; ++i) mn = __vimin3_u32(__vimin3_u32(mn, hv[i].x, hv[i].y), hv[i].z, hv[i].w);
              if (__all_sync(0xffffffffu, mn != 0u)) break;
              if (++n > (1u << 20)) { g_err = 4u; break; }
            }
          } else {
#pragma unroll
            for (int i = 0; i < 16; ++i) hv[i] = make_uint4(~0u, ~0u, ~0u, ~0u);
          }
          nbar<10, 64>();
#pragma unroll
          for (int i = 0; i < 16; ++i)
            stsm_x4(rB - 4 * KVT + (((i >> 2) & 1) * 2 + (i >> 3)) * KVT + (X ^ ((i & 3) << 5)), ~hv[i].x, ~hv[i].y, ~hv[i].z, ~hv[i].w);
          asm volatile("bar.arrive 11, 64;" ::: "memory");
          nbar<9, 64>();
        } else {
          nbar_dyn(8 + (cu & 4), 224);
        }
        PROFT(tid_ == 128, layer * 16 + 5);
        PROFT(lane == 0 && layer == PL, 136 + cw);
        auto attend = [&](int hp) {
          const uint32_t qad = sb + (XS + 1 - hp) * SLOT + rowo, kt = rB + 2 * (hp ^ wg) * KVT - (lane & 8) * 128, vt = rB + (2 * (hp ^ wg) + 1) * KVT;
          __syncwarp();
          uint32_t kb[2][2][4], vb[2][2][2][4];
#pragma unroll
          for (int h = 0; h < 2; ++h)
#pragma unroll
            for (int nt = 0; nt < 2; ++nt) ldsm_x4(kb[h][nt][0], kb[h][nt][1], kb[h][nt][2], kb[h][nt][3], kt + nt * 1024 + (KX ^ (h << 6)));
#pragma unroll
          for (int ks = 0; ks < 2; ++ks)
#pragma unroll
            for (int np = 0; np < 2; ++np)
#pragma unroll
              for (int h = 0; h < 2; ++h)
                ldsm_x4_t(vb[h][ks][np][0], vb[h][ks][np][1], vb[h][ks][np][2], vb[h][ks][np][3], vt + ks * 2048 + (X ^ (h << 6) ^ (np << 5)));
          if (hp == 0 && lane == 0) release2(bar + B_E3);
          if (DB1 == 1 && hp == 0 && cu < 4) dump(1);
          float la[2][2], lb[2][2], mx[2][2], sm[2][2];
#pragma unroll
          for (int h = 0; h < 2; ++h) {
            const int qo = 32 + 16 * hp + 8 * h, ko = 16 * hp + 8 * h;
            float sc[4][4];
#pragma unroll
            for (int nt = 0; nt < 4; ++nt) {
              sc[nt][0] = sc[nt][1] = sc[nt][2] = sc[nt][3] = 0.f;
#pragma unroll
              for (int ks = 0; ks < 2; ++ks)
                mma_bf16(sc[nt], kq[qo + 4 * ks], kq[qo + 4 * ks + 1], kq[qo + 4 * ks + 2], kq[qo + 4 * ks + 3],
                         nt < 2 ? kb[h][nt & 1][2 * ks] : kq[ko + 4 * ks + (nt & 1)], nt < 2 ? kb[h][nt & 1][2 * ks + 1] : kq[ko + 4 * ks + 2 + (nt & 1)]);
            }
            la[h][0] = fmaf(e ? sc[1][1] : sc[1][0], fA0, bA0);
            lb[h][0] = fmaf(sel ? (e ? sc[0][1] : sc[0][0]) : (e ? sc[2][1] : sc[2][0]), fB0, bB);
            la[h][1] = (e ? sc[2][3] : sc[2][2]) * fA1;
            lb[h][1] = fmaf(sel ? (e ? sc[1][3] : sc[1][2]) : (e ? sc[3][3] : sc[3][2]), fB1, bB);
            mx[h][0] = fmaxf(la[h][0], lb[h][0]); mx[h][1] = fmaxf(la[h][1], lb[h][1]);
          }
#pragma unroll
          for (int o = 1; o <= 2; o <<= 1)
#pragma unroll
            for (int h = 0; h < 2; ++h)
#pragma unroll
              for (int r = 0; r < 2; ++r) mx[h][r] = fmaxf(mx[h][r], __shfl_xor_sync(0xffffffffu, mx[h][r], o));
          float oa[2][4][4];
#pragma unroll
          for (int h = 0; h < 2; ++h) {
#pragma unroll
            for (int r = 0; r < 2; ++r) { la[h][r] = ex2(la[h][r] - mx[h][r]); lb[h][r] = ex2(lb[h][r] - mx[h][r]); sm[h][r] = la[h][r] + lb[h][r]; }
            const uint32_t p0 = pack_bf16(la[h][0] * rjA0, lb[h][0] * rjB0), p1 = pack_bf16(la[h][1] * rjA1, lb[h][1] * rjB1);
            const uint32_t a00 = __byte_perm(p0, 0u, pLo), a02 = __byte_perm(p0, 0u, pA_), a03 = __byte_perm(p1, 0u, pLo);
            const uint32_t a10 = __byte_perm(p0, 0u, pHi), a11 = __byte_perm(p1, 0u, pA_), a13 = __byte_perm(p1, 0u, pHi);
#pragma unroll
            for (int i = 0; i < 4; ++i) {
              oa[h][i][0] = oa[h][i][1] = oa[h][i][2] = oa[h][i][3] = 0.f;
              mma_bf16(oa[h][i], a00, 0u, a02, a03, vb[h][0][i >> 1][2 * (i & 1)], vb[h][0][i >> 1][2 * (i & 1) + 1]);
              mma_bf16(oa[h][i], a10, a11, 0u, a13, vb[h][1][i >> 1][2 * (i & 1)], vb[h][1][i >> 1][2 * (i & 1) + 1]);
            }
          }
#pragma unroll
          for (int o = 1; o <= 2; o <<= 1)
#pragma unroll
            for (int h = 0; h < 2; ++h)
#pragma unroll
              for (int r = 0; r < 2; ++r) sm[h][r] += __shfl_xor_sync(0xffffffffu, sm[h][r], o);
          mbar_wait(bar + (hp ? B_XOLD2 : B_XOLD), 1);
#pragma unroll
          for (int jp = 0; jp < 4; ++jp) ldsm_x4(xo[16 * hp + 4 * jp], xo[16 * hp + 4 * jp + 1], xo[16 * hp + 4 * jp + 2], xo[16 * hp + 4 * jp + 3], qad + (X ^ (jp << 5)));
#pragma unroll
          for (int h = 0; h < 2; ++h) {
            const float i0 = rcp(sm[h][0]), i1 = rcp(sm[h][1]);
#pragma unroll
            for (int np = 0; np < 2; ++np)
              stsm_x4(qad + (X ^ (h << 6) ^ (np << 5)),
                      pack_bf16(oa[h][2 * np][0] * i0, oa[h][2 * np][1] * i0), pack_bf16(oa[h][2 * np][2] * i1, oa[h][2 * np][3] * i1),
                      pack_bf16(oa[h][2 * np + 1][0] * i0, oa[h][2 * np + 1][1] * i0), pack_bf16(oa[h][2 * np + 1][2] * i1, oa[h][2 * np + 1][3] * i1));
          }
          __syncwarp();
          slab_out_half(sb + (XS + 1 - hp) * SLOT, g_o + (size_t)m0 * D_ + g * 128 + hp * 64, wrow0, lane, hp);
          __syncwarp();
          if (lane == 0) mbar_arrive(bar + (hp ? B_ODONE : B_OH1));
          PROFT(lane == 0 && layer == PL && hp == 0, 128 + cw);
        };
        attend(0);
        if (DB1 == 2 && cu < 4) dump(1);
        if (cu == 4) nbar<15, 64>();
        else if (cu != 0) nbar_dyn(13 + (cu >> 2), 224);
        attend(1);
      } else {
#pragma unroll
        for (int i = 0; i < 32; ++i) kq[i] = pack_bf16(acc[2 * i], acc[2 * i + 1]);
        if (cu < 4) nbar<7, 256>();
        {
          const uint32_t vb = sb + (5 + 3 * wg) * SLOT + (rowq >> 1) + ((lchk ^ ((lane & 7) >> 1)) << 4);
#pragma unroll
          for (int jp = 8; jp < 16; ++jp)
            stsm_x4((vb ^ ((jp & 1) << 5)) + ((jp >> 1) & 3) * 4096,
                    pack_bf16(acc[8 * jp], acc[8 * jp + 1]), pack_bf16(acc[8 * jp + 2], acc[8 * jp + 3]),
                    pack_bf16(acc[8 * jp + 4], acc[8 * jp + 5]), pack_bf16(acc[8 * jp + 6], acc[8 * jp + 7]));
        }
        PROFT(tid_ == 128, layer * 16 + 2);
        Q_DONE();
        const uint32_t pA = sb + (3 + 3 * wg) * SLOT + (rowo & 8191);
        float sc0 = rs0 * L2E, sc1 = rs1 * L2E;
        const uint32_t wa0 = sb + SM_WPHI + lrow * 80 + lchk * 16;
        const uint32_t wu = c.cu >> 2, par = (layer >> 1) & 1;
        float p[2][4][4];
        uint32_t raw[2][4][4], ph[2][4][4];
        float kva[20], oa[2][20];
        auto kv_start = [&](int hp) {
#pragma unroll
          for (int h = 0; h < 2; ++h)
#pragma unroll
            for (int cp = 0; cp < 4; ++cp)
              stsm_x4(pA + hp * 16384 + h * 8192 + (X ^ (cp << 5)), ph[h][cp][0], ph[h][cp][1], ph[h][cp][2], ph[h][cp][3]);
          PROFT(tid_ == 128, layer * 16 + 11);
          fence_async_smem();
          nbar<1, 256>();
          const uint32_t hu = 2 * hp + wu;
          const uint32_t dP = (((sb + 3 * SLOT + hu * 8192) & 0x3FFFF) >> 4) | (512u << 16);
          const uint32_t dV = (((sb + 5 * SLOT + hu * 4096) & 0x3FFFF) >> 4) | (((SM_SD - 5 * SLOT - hu * 4096) >> 4) << 16);
          wgmma_fence();
#pragma unroll
          for (int ks = 0; ks < 8; ++ks)
            wgmma_n40_tt(kva, desc64(dP + (ks >> 2) * 3072 + (ks & 3) * 128, 0x40000040u),
                         desc64(dV + (ks >> 2) * (3072u - (2816u << 16)) + (ks & 3) * 64, 0x80000020u), ks != 0);
          wgmma_commit();
        };
        auto kv_end = [&](int hp) {
          wgmma_wait<0>();
#pragma unroll
          for (int i = 0; i < 20; ++i) asm volatile("" : "+f"(kva[i]) :: "memory");
          nbar_dyn(3 + wu, 128);
          PROFT(tid_ == 128, layer * 16 + 12);
          const bool od = lane & 1;
#pragma unroll
          for (int i = 0; i < 4; ++i)
            sts128(sb + (3 + hp) * SLOT + (cw * 128 + i * 32 + lane) * 16,
                   make_uint4(__float_as_uint(kva[4 * i]), __float_as_uint(kva[4 * i + 1]), __float_as_uint(kva[4 * i + 2]),
                              __float_as_uint(od == (i >= 2) ? 1.f : kva[4 * i + 3])));
          sts128(sb + (6 + hp) * SLOT + wg * 8192 + (wq * 32 + lane) * 16,
                 make_uint4(__float_as_uint(od ? kva[11] : kva[3]), __float_as_uint(od ? kva[15] : kva[7]), __float_as_uint(od ? kva[18] : kva[16]), __float_as_uint(1.f)));
          fence_async_smem();
          __syncwarp();
          if (lane == 0) mbar_arrive(bar + B_KVDONE - hp * 32);
          PROFT(tid_ == 128, layer * 16 + 3);
        };
        const uint4* const kvg = g_kv + (g * 2 + (layer >> 1)) * 2560 + cw * 128 + lane;
        uint4 u[5];
        auto kv_load = [&](int hp) {
#pragma unroll
          for (int i = 0; i < 4; ++i) u[i] = ld_relaxed4(kvg + hp * 1280 + i * 32);
          u[4] = ld_relaxed4(kvg + hp * 1280 + 1024 - cw * 96);
        };
        auto o_start = [&](int hp, const uint32_t (&pq)[2][4][4]) {
          PROFT(tid_ == 128 && hp == 0, layer * 16 + 10);
          if (hp == 0) mbar_wait(bar + B_KVDONE - 32, par);
          const bool od = lane & 1;
          uint32_t n = 0;
#pragma unroll 1
          while (!__all_sync(0xffffffffu, (od ? u[2].w : u[0].w) == 0x41800000u && (od ? u[3].w : u[1].w) == 0x41800000u && u[4].w == 0x41800000u)) {
#pragma unroll 1
            while (__any_sync(0xffffffffu, u[4].w < KVTH) && ++n < (1u << 20)) u[4].w = ld_relaxed(&kvg[hp * 1280 + 1024 - cw * 96].w);
            if (++n > (1u << 20)) { g_err = 6u; break; }
            kv_load(hp);
          }
          PROFT(tid_ == 128 && hp == 0, layer * 16 + 5);
          if (!od) { u[0].w = u[4].x; u[1].w = u[4].y; } else { u[2].w = u[4].x; u[3].w = u[4].y; }
#pragma unroll
          for (int i = 0; i < 4; i += 2)
            stsm_x4(sb + (5 + 3 * hp) * SLOT + rowo + (X ^ ((i & 2) << 4)),
                    pack_bf16(__uint_as_float(u[i].x), __uint_as_float(u[i].y)), pack_bf16(__uint_as_float(u[i].z), __uint_as_float(u[i].w)),
                    pack_bf16(__uint_as_float(u[i + 1].x), __uint_as_float(u[i + 1].y)), pack_bf16(__uint_as_float(u[i + 1].z), __uint_as_float(u[i + 1].w)));
          const uint32_t z2 = pack_bf16(__uint_as_float(u[4].z), __uint_as_float(u[4].z));
          if (t < 2) sts128(sb + (5 + 3 * hp) * SLOT + (wrow0 + gq + 8 * t) * 128 + ((4 ^ gq) << 4), make_uint4(z2, z2, z2, z2));
          fence_async_smem();
          nbar<1, 256>();
          PROFT(tid_ == 128 && hp == 1, layer * 16 + 4);
          const uint32_t dK = (((sb + (5 + 3 * hp) * SLOT) & 0x3FFFF) >> 4) | (512u << 16);
          wgmma_fence();
#pragma unroll
          for (int ks = 0; ks < 4; ++ks) {
#pragma unroll
            for (int hh = 0; hh < 2; ++hh) wgmma_n40_rs(oa[hh], pq[hh][ks], D128(dK + hh * 512 + ks * 128), ks != 0);
          }
          wgmma_commit();
        };
        auto o_end = [&](int hp) {
          wgmma_wait<0>();
#pragma unroll
          for (int i = 0; i < 20; ++i) asm volatile("" : "+f"(oa[0][i]), "+f"(oa[1][i]) :: "memory");
#pragma unroll
          for (int hh = 0; hh < 2; ++hh) {
            const float i0 = rcp(oa[hh][16] + 1e-6f), i1 = rcp(oa[hh][18] + 1e-6f);
            const uint32_t qad = sb + (3 + hp) * SLOT + rowo, hx = hh << 6;
#pragma unroll
            for (int np = 0; np < 2; ++np)
              stsm_x4(qad + (X ^ hx ^ (np << 5)),
                      pack_bf16(oa[hh][8 * np] * i0, oa[hh][8 * np + 1] * i0), pack_bf16(oa[hh][8 * np + 2] * i1, oa[hh][8 * np + 3] * i1),
                      pack_bf16(oa[hh][8 * np + 4] * i0, oa[hh][8 * np + 5] * i0), pack_bf16(oa[hh][8 * np + 6] * i1, oa[hh][8 * np + 7] * i1));
          }
          __syncwarp();
          slab_out_half(sb + (3 + hp) * SLOT, g_o + (size_t)m0 * D_ + g * 128 + hp * 64, wrow0, lane, hp);
          __syncwarp();
          if (lane == 0) mbar_arrive(bar + (hp ? B_ODONE : B_OH1));
        };
#define XO_LOAD() \
        mbar_wait(bar + B_XOLD, 0); \
        mbar_wait(bar + B_XOLD2, 0); \
        _Pragma("unroll") for (int jp = 0; jp < 8; ++jp) \
          ldsm_x4(xo[4 * jp], xo[4 * jp + 1], xo[4 * jp + 2], xo[4 * jp + 3], sb + (XS + 1 - (jp >> 2)) * SLOT + rowo + (X ^ ((jp & 3) << 5)));
#define SC_RELOAD() \
        sc0 = __uint_as_float(lds_vol(sb + SM_RS + (16 + wrow0 + gq) * 4)) * L2E; sc1 = __uint_as_float(lds_vol(sb + SM_RS + (24 + wrow0 + gq) * 4)) * L2E;
        __syncwarp();
        phi_proj<0>(p, kq, wa0);
        phi_exp(raw[0], p[0], sc0, sc1);
        phi_exp(raw[1], p[1], sc0, sc1);
        phi_proj<16>(p, kq, wa0 + 5120);
        phi_norm<0>(ph, raw, kq, wa0, sc0, sc1, rs0, rs1);
        kv_start(0);
        phi_exp(raw[0], p[0], sc0, sc1);
        kv_end(0);
        if (RL & 1) { SC_RELOAD(); }
        XO_LOAD();
        phi_exp(raw[1], p[1], sc0, sc1);
        phi_proj<32>(p, kq, wa0);
        phi_norm<16>(ph, raw, kq, wa0 + 5120, sc0, sc1, rs0, rs1);
        kv_start(1);
        if (lane == 0) release2(bar + B_E3);
        phi_exp(raw[0], p[0], sc0, sc1);
        kv_end(1);
        if (RL & 2) { SC_RELOAD(); }
        kv_load(0);
        phi_exp(raw[1], p[1], sc0, sc1);
        phi_proj<48>(p, kq, wa0 + 5120);
        phi_norm<32>(ph, raw, kq, wa0, sc0, sc1, 1.f, 1.f);
        o_start(0, ph);
        phi_exp(raw[0], p[0], sc0, sc1);
        o_end(0);
        SC_RELOAD();
        kv_load(1);
        phi_exp(raw[1], p[1], sc0, sc1);
        phi_norm<48>(ph, raw, kq, wa0 + 5120, sc0, sc1, 1.f, 1.f);
        o_start(1, ph);
        o_end(1);
      }
      __syncwarp();
      PROFT(lane == 0 && layer == PL, 216 + cw);
      if (lane == 0) mbar_arrive(bar + B_EPI);
      PROFT(tid_ == 128, layer * 16 + 6);
    }
    {
      PHASE_CTX();
      const uint32_t wu = c.cu >> 2;
      const uint32_t dA0 = (((sb + wu * 8192) & 0x3FFFF) >> 4) | (1u << 16), dB0 = ((sb & 0x3FFFF) >> 4) | (512u << 16);
#pragma unroll
      for (int i = 0; i < 32; ++i) { acc[128 + 2 * i] = bf_lo(xo[i]); acc[129 + 2 * i] = bf_hi(xo[i]); }
      nbar_dyn(3 + wg, 128);
      uint64_t ta = (layer & 1) ? WO_A1 : WO_A0, tw = (layer & 1) ? WO_B1 : WO_B0;
#pragma unroll 1
      for (int i = 0; i < 16; ++i) {
        bool rel = i > 0 && i < 12;
        if (DRY && rel && !__all_sync(0xffffffffu, mbar_test_wait(bar + B_FULLT + i * 8, layer & 1))) {
          wgmma_wait<0>();
          if (elected) release2(bar + B_CONS + (i - 1) * 8);
          rel = false;
        }
        mbar_wait(bar + B_FULLT + i * 8, layer & 1);
        PROFT(tid_ == 128 && layer == PL, 160 + i);
        const uint32_t da = dA0 + ((uint32_t)ta & 15) * 1024, db = dB0 + ((uint32_t)tw & 15) * 1024;
        ta >>= 4; tw >>= 4;
        wgmma_fence();
#pragma unroll
        for (int k = 0; k < 4; ++k) wgmma_n128(acc, D128(da + k * 2), D128(db + k * 128), 1);
        wgmma_commit();
        if (i == 0) {
          if (elected) {
            release2(bar + B_E2);
          }
        } else {
          wgmma_wait<1>();
          if (elected && rel) release2(bar + B_CONS + (i - 1) * 8);
          if (elected && (unsigned)(i - 13) < 2u && layer + 1 < NLAYERS) release2(bar + B_EMPTYS + (i - 13) * 8);
        }
      }
      const bool last = layer == NLAYERS - 1;
      wgmma_wait<0>();
#pragma unroll
      for (int i = 128; i < 192; ++i) asm volatile("" : "+f"(acc[i]) :: "memory");
      if (elected && !last) release2(bar + B_EMPTYS + 16);
      PROFT(tid_ == 128, layer * 16 + 7);
#pragma unroll
      for (int jp = 0; jp < 4; ++jp)
        stsm_x4(sb + XS * SLOT + rowo + (X ^ (jp << 5)),
                pack_bf16(acc[128 + 8 * jp], acc[129 + 8 * jp]), pack_bf16(acc[130 + 8 * jp], acc[131 + 8 * jp]),
                pack_bf16(acc[132 + 8 * jp], acc[133 + 8 * jp]), pack_bf16(acc[134 + 8 * jp], acc[135 + 8 * jp]));
      if (last) {
        __syncwarp();
        slab_out_half(sb + XS * SLOT, c.out + (size_t)m0 * D_ + g * 128, wrow0, lane);
        X_H1();
        __syncwarp();
        slab_out_half(sb + (XS + 1) * SLOT, c.out + (size_t)m0 * D_ + g * 128 + 64, wrow0, lane);
        __syncwarp();
        if (lane == 0) mbar_arrive(bar + B_XDONE);
        PROFT(tid_ == 128, layer * 16 + 24);
        break;
      }
      __syncwarp();
      slab_out_half(sb + XS * SLOT, g_x + (size_t)m0 * D_ + g * 128, wrow0, lane, true);
      __syncwarp();
      if (lane == 0) mbar_arrive(bar + B_XH0);
      nbar_dyn(3 + wu, 128);
    }
  }
}

__device__ __forceinline__ void flag_fetch(uint32_t bar, uint32_t cp, const unsigned int* f) {
  asm volatile("{\n.reg .pred p;\nelect.sync _|p, 0xffffffff;\n@p mbarrier.expect_tx.relaxed.cta.shared::cta.b64 [%2], 64;\n"
               "@p cp.async.bulk.shared::cluster.global.mbarrier::complete_tx::bytes [%0], [%1], 64, [%2];\n}\n"
               ::"r"(cp), "l"(f), "r"(bar + 128) : "memory");
}
__device__ __forceinline__ void src_wait_async(uint32_t bar, uint32_t cp, const unsigned int* f, unsigned int target, int kb, uint32_t& ready, int lane) {
  uint32_t n = 0;
#pragma unroll 1
  while (true) {
    ready |= __ballot_sync(0xffffffffu, (int)(lds_vol(cp + (lane & 15) * 4) - target) >= 0);
    if ((ready >> kb) & 1) break;
    if (n > (1u << 20)) { g_err = 5u; break; }
    if ((n++ & PMOD) == 0) flag_fetch(bar, cp, f);
    __nanosleep(PSL);
  }
}

__device__ __forceinline__ int kblock0(int i, int g) {
  const int j = i >> 1, p = max(g, NCOM) + j - NCOM;
  return (j < NCOM ? j : p < 8 ? p : p - 8 + NCOM) * 2 + (i & 1);
}

#define WOORD 0xFDB9753ECA864210ull
__device__ __forceinline__ int wo_kblock(int m, int g) { return (2 * g + (int)((WOORD >> (4 * m)) & 15)) & 15; }

__global__ void __cluster_dims__(2, 1, 1) __launch_bounds__(384, 1)
mega_kernel(const __grid_constant__ CUtensorMap tm_x0, const __grid_constant__ CUtensorMap tm_x,
            const __grid_constant__ CUtensorMap tm_o,
            const __grid_constant__ CUtensorMap tm_wA, const __grid_constant__ CUtensorMap tm_wB,
            const __grid_constant__ CUtensorMap tm_woA, const __grid_constant__ CUtensorMap tm_woB,
            const bf16* __restrict__ wA, const bf16* __restrict__ wB,
            const bf16* __restrict__ wphi, bf16* __restrict__ out) {
  extern __shared__ uint8_t smem_raw[];
  const uint32_t sb = (smem_u32(smem_raw) + 1023u) & ~1023u;
  const uint32_t bar = sb + SM_BAR;
  const int warp = __shfl_sync(0xffffffffu, threadIdx.x >> 5, 0), lane = threadIdx.x & 31;
  const int cr = blockIdx.x & 1;
  const int g = (blockIdx.x >> 1) & 7;
  const int rb = (blockIdx.x >> 4) * 2 + cr;
  const int m0 = rb * 128;

  if (warp < 4) {
    asm volatile("setmaxnreg.dec.sync.aligned.u32 40;");
    asm volatile("barrier.cluster.arrive.relaxed.aligned;" ::: "memory");
    const unsigned int epoch = warp ? ld_relaxed(&g_epoch) : 0u;
    if (warp) cluster_wait();
    unsigned int xbase = epoch * NLAYERS;
    const unsigned int cbase = epoch * 16u;
    auto wo_a = [&](int layer) {
      uint64_t ts = ((layer & 1) ? WO_A1 : WO_A0) >> 8, td = ((layer & 1) ? WO_DA1 : WO_DA0) >> 8, tk = WOORD >> 8;
      uint32_t ready = 0u;
#pragma unroll 1
      for (int m = 2; m < 16; ++m) {
        const int kb = (2 * g + (uint32_t)tk) & 15;
        uint32_t dst = sb + ((uint32_t)ts & 15) * SLOT, fb = bar + B_FULLT + m * 8, eb = bar + B_CONS + ((uint32_t)td & 15) * 8;
        int kc = kb * 64;
        ts >>= 4; td >>= 4; tk >>= 4;
        if (!((ready >> kb) & 1)) {
          PROFT(m == 2 && lane == 0, 64 + layer * 16 + 2);
          if (EP && m > EP) src_wait_async(bar, bar + B_FLG, g_of + rb * 32, xbase + layer + 1, kb, ready, lane);
          src_wait<0>(g_of + rb * 32, xbase + layer + 1, 1u << kb, ready, lane);
          fence_async_all();
        }
        asm volatile("" : "+r"(dst), "+r"(fb), "+r"(eb), "+r"(kc));
        mbar_wait_u(eb, layer & 1);
        tma_2d_e(dst, &tm_o, kc, m0, fb);
        if (EP && m >= EP && (ready & 0xFFFFu) != 0xFFFFu) flag_fetch(bar, bar + B_FLG, g_of + rb * 32);
        PROFT(lane == 0 && layer == PL, 176 + m);
      }
    };
    auto wo_w = [&](int layer) {
      const CUtensorMap* tx = layer == 0 ? &tm_x0 : &tm_x;
      const CUtensorMap* two = (layer & 1) ? &tm_woB : &tm_woA;
      uint64_t ts = (layer & 1) ? WO_B1 : WO_B0, td = (layer & 1) ? WO_DB1 : WO_DB0, tk = WOORD;
      uint32_t pb = 0;
      fence_async_all();
      mbar_wait_u(bar + B_R0, layer & 1);
      expect_tx_e(bar + B_XOLD, 16384);
      tma_2d_e(sb + (XS + 1) * SLOT, tx, g * 128, m0, bar + B_XOLD);
#pragma unroll 1
      for (int m = 0; m < 16; ++m) {
        uint32_t dst = sb + ((uint32_t)ts & 15) * SLOT + cr * 8192, fb = bar + B_FULLT + m * 8, eb = bar + B_CONS + ((uint32_t)td & 15) * 8;
        int kc = ((2 * g + (uint32_t)tk) & 15) * 64;
        ts >>= 4; td >>= 4; tk >>= 4;
        asm volatile("" : "+r"(dst), "+r"(fb), "+r"(eb), "+r"(kc));
        if (eb != pb) mbar_wait_u(eb, layer & 1);
        pb = eb;
        tma_2d_mc_e(dst, two, g * 128 + cr * 64, kc, fb);
        expect_tx_e(fb, m < 2 ? 16384 : 32768);
        PROFT(lane == 0 && layer == PL, 144 + m);
        if (m == ((layer & 1) ? XB2 : 0)) {
          expect_tx_e(bar + B_XOLD2, 16384);
          tma_2d_e(sb + XS * SLOT, tx, g * 128 + 64, m0, bar + B_XOLD2);
        }
      }
    };
    if (warp == 0) {
      cluster_wait();
      PROFT(lane == 0, 125);
#pragma unroll 1
      for (int layer = 0; layer < NLAYERS; ++layer) {
        const CUtensorMap* tx = layer == 0 ? &tm_x0 : &tm_x;
        const CUtensorMap* tw = (layer & 1) ? &tm_wB : &tm_wA;
        uint32_t s = layer == 0, u = 0, ready = layer == 0 ? 0xFFFFu : 0u;
#pragma unroll 1
        for (int i = s; i < 16; ++i) {
          const int kb = layer == 0 ? kblock0(i, g) : wo_kblock(i, g), kc = kb * 64;
          const uint32_t fb = bar + B_FULLS + s * 8;
          const uint32_t kd = sb + (((QK >> (4 * s)) & 15) + cr) * SLOT, qd = sb + ((QQ >> (4 * s)) & 15) * SLOT + cr * 8192;
          const uint32_t need = 1u << kb;
          const bool ext = i >= 2 || layer == 0, early = ext && (ready & need) == need;
          mbar_wait_u(bar + B_EMPTYS + s * 8, (u + (s ? layer : 0) + 1) & 1);
          if (early) tma_2d_e(sb + ((QA >> (4 * s)) & 15) * SLOT, tx, kc, m0, fb);
          tma_2d_mc_e(kd, tw, 1024 + cr * 1024 + g * 128, kc, fb);
          tma_2d_mc_e(kd + 8192, tw, 1024 + cr * 1024 + g * 128 + 64, kc, fb);
          tma_2d_mc_e(qd, tw, g * 128 + cr * 64, kc, fb);
          expect_tx_e(fb, ext ? 65536 : 49152);
          PROFT(lane == 0 && layer == 0 && i == 1, 31);
          if (layer == 0 && i == 2) {
            mbar_wait_u(bar + B_FULLS, 0);
            tma_pf_e(&tm_x0, g * 128, m0);
            tma_pf_e(&tm_x0, g * 128 + 64, m0);
          }
          if (layer < 2 && i >= PFS) {
            const int j = i - PFS;
            if (j < 2) tma_pf_e(layer ? &tm_woB : &tm_woA, g * 128 + j * 64, rb * 64);
            else if (j < 8 && layer == 0) tma_pf_e(&tm_wB, ((j >> 1) - 1) * 1024 + g * 128 + (j & 1) * 64, rb * 64);
          }
          if (ext && !early) {
            PROFT(i == 2 && lane == 0, 64 + layer * 16 + 0);
            if (XEP) src_wait_async(bar, sb + SM_RS + 640, g_xf + rb * 32, xbase + layer + 1, kb, ready, lane);
            else src_wait<0>(g_xf + rb * 32, xbase + layer + 1, need, ready, lane);
            PROFT(i == 2 && lane == 0, 64 + layer * 16 + 1);
            fence_async_all();
            tma_2d_e(sb + ((QA >> (4 * s)) & 15) * SLOT, tx, kc, m0, fb);
          }
          if (++s == 3) { s = 0; ++u; }
        }
        if (layer == 0) xbase = ld_relaxed(&g_epoch) * NLAYERS;
        wo_a(layer);
      }
    } else {
      if (warp >= 2) {
        const int h2 = threadIdx.x - 64;
#pragma unroll 1
        for (int i = h2; i < 512; i += 64)
          asm volatile("cp.async.cg.shared.global [%0], [%1], 16;" ::"r"(sb + SM_WPHI + (i >> 2) * 80 + (i & 3) * 16), "l"(wphi + (size_t)g * 4096 + i * 8) : "memory");
        if (h2 < 16) sts_f(sb + SM_RS + h2 * 4, 0.f);
        if (h2 < 32) sts_f((h2 < 16 ? bar + B_FLG : sb + SM_RS + 576) + h2 * 4, __uint_as_float(xbase));
        if (rb >= CG0) mbar_wait_u(bar + B_FULLS + (rb >= CG1 ? 8 : 0), 0);
        if (CPF && h2 < 4) asm volatile("cp.async.bulk.prefetch.tensor.2d.L2.global.tile [%0, {%1, %2}];" ::"l"(&tm_wA), "r"((h2 & 2) * 1024 + g * 128 + (h2 & 1) * 64), "r"(rb * 64) : "memory");
#pragma unroll 1
        for (int wi = 0; wi < 3; ++wi) {
          float sA[8];
          colsum_load(wA, rb, g, warp - 2 + 2 * wi, lane, sb + SM_BP + (warp - 2) * 6144, sA);
          colsum_red(g_cs + (epoch & 1) * 6144, g, warp - 2 + 2 * wi, lane, sA);
        }
#pragma unroll 1
        for (int i = h2; i < 320; i += 64) g_kv[(g * 16 + rb) * 320 + i] = make_uint4(0u, 0u, 0u, 0u);
        fence_async_all();
        nbar<5, 64>();
        if (h2 == 0) flag_add(&g_csflag[g].v);
        PROFT(h2 == 0, 242);
      }
      if (warp == 1) {
        if (lane >= 27) {
          const CUtensorMap* tm = lane == 27 ? &tm_o : lane == 28 ? &tm_wB : lane == 29 ? &tm_woA : lane == 30 ? &tm_woB : &tm_x;
          asm volatile("prefetch.tensormap [%0];" ::"l"(tm) : "memory");
        }
        __syncwarp();
        {
#pragma unroll 1
          for (int e = 0;; ++e) {
            if (e > 0 && e < NLAYERS) {
              mbar_wait_u(bar + B_XH0, (e - 1) & 1);
              flag_set(g_xf + rb * 32 + 2 * g, xbase + e + 1);
            }
            mbar_wait_u(bar + B_XDONE, e & 1);
            PROFT(e < 4, 64 + e * 16 + 4);
            if (e == NLAYERS) {
              if (blockIdx.x == 0) g_epoch = epoch + 1;
              break;
            }
            PROFT(e < 4, 64 + e * 16 + 5);
            flag_set(g_xf + rb * 32 + 2 * g + 1, xbase + e + 1);
            PROFT(e < 4, 64 + e * 16 + 7);
            if ((e & 1) == 0) {
#pragma unroll 1
              for (int hp = 0; hp < 2; ++hp) {
                uint4* kvl = g_kv + ((g * 2 + (e >> 1)) * 2 + hp) * 1280;
                mbar_wait_u(bar + B_KVDONE - hp * 32, (e >> 1) & 1);
                PROFT(e == PL, 243 + hp * 4);
                bulk_red_add_e(kvl + rb * 64, sb + (3 + hp) * SLOT + rb * 1024, 16384 - rb * 1024);
                if (rb) bulk_red_add_e(kvl, sb + (3 + hp) * SLOT, rb * 1024);
                bulk_red_add_e(kvl + 1024, sb + (6 + hp) * SLOT, 2048);
                bulk_red_add_e(kvl + 1152, sb + (6 + hp) * SLOT + 8192, 2048);
                bulk_commit();
                PROFT(e < 4, 64 + e * 16 + 6);
              }
              bulk_wait_read0();
              __syncwarp();
              if (lane < 2) release2(bar + B_E1);
              __syncwarp();
            }
            mbar_wait_u(bar + B_OH1, e & 1);
            PROFT(e == PL, 251);
            flag_set(g_of + rb * 32 + 2 * g, xbase + e + 1);
            PROFT(e < 4, 64 + e * 16 + 9);
            mbar_wait_u(bar + B_ODONE, e & 1);
            PROFT(e < 4, 64 + e * 16 + 8);
            flag_set(g_of + rb * 32 + 2 * g + 1, xbase + e + 1);
            PROFT(e < 4, 64 + e * 16 + 11);
          }
        }
      } else {
        const int h2 = threadIdx.x - 64;
        const float* cs = g_cs + (epoch & 1) * 6144;
#pragma unroll 1
        for (int layer = 0; layer < NLAYERS; ++layer) {
          if (warp == 2 && layer < 2) {
            if (lane == 0) flag_wait_t<CSLP>(&g_csflag[layer * 8 + g].v, cbase + 16u);
            __syncwarp();
            float4 a[3];
#pragma unroll
            for (int i = 0; i < 3; ++i) a[i] = __ldcg(reinterpret_cast<const float4*>(cs + layer * 3072 + g * 384) + i * 32 + lane);
#pragma unroll 1
            for (int i = 0; i < 3; ++i) {
              const float av[4] = {a[0].x, a[0].y, a[0].z, a[0].w};
              a[0] = a[1]; a[1] = a[2];
#pragma unroll
              for (int j = 0; j < 4; ++j) {
                const float c1 = bf16r(av[j]), c2 = bf16r(av[j] - c1), c3 = (av[j] - c1) - c2;
                sts128(sb + SM_BP + layer * 6144 + ((i * 32 + lane) * 4 + j) * 16, make_uint4(pack_bf16(c1, c2), pack_bf16(c3, 0.f), 0u, 0u));
              }
            }
            fence_async_smem();
            __syncwarp();
            if (lane == 0) mbar_arrive(bar + (layer ? B_CS2 : B_CS));
            PROFT(lane == 0, 64 + layer * 16 + 12);
            if (layer == 0) {
              uint4* hz = g_halo + (rb * 8 + g) * 1024;
#pragma unroll 2
              for (int i = lane; i < 1024; i += 32) hz[i] = make_uint4(0u, 0u, 0u, 0u);
              if (lane < 12) reinterpret_cast<float4*>(g_cs + ((epoch & 1) ^ 1) * 6144 + blockIdx.x * 48)[lane] = make_float4(0.f, 0.f, 0.f, 0.f);
              g_stats[(2 + (lane >> 4)) * S_ + m0 + g * 16 + (lane & 15)] = make_float2(0.f, 0.f);
            }
          }
          if (warp == 3) {
            const bool hal = (layer & 1) && rb > 0;
            {
              uint32_t rdy = 0u;
              src_wait<256>(g_xf + rb * 32, xbase + layer + 1, 0xAAAAu, rdy, lane);
              rdy = 0u;
              if (hal) src_wait<256>(g_xf + (rb - 1) * 32, xbase + layer + 1, 0xAAAAu, rdy, lane);
            }
            float2 u[5];
            const float2* sp = g_stats + layer * S_ + m0 + lane;
#pragma unroll
            for (int i = 0; i < 4; ++i) u[i] = __ldcg(sp + i * 32);
            u[4] = __ldcg(hal ? sp - 16 : sp);
            if (layer == 3) g_stats[(lane >> 4) * S_ + m0 + g * 16 + (lane & 15)] = make_float2(0.f, 0.f);
#pragma unroll 1
            for (int i = 0; i < (hal ? 5 : 4); ++i) {
              const int r = i < 4 ? 16 + i * 32 + lane : lane;
              const float sum = u[0].x, sq = u[0].y;
              u[0] = u[1]; u[1] = u[2]; u[2] = u[3]; u[3] = u[4];
              const float mean = sum * (1.f / D_);
              const float var = fmaxf(fmaf(-sum, mean, sq) * (1.f / D_), 0.f);
              const float sd = bf16r(sqrtf(bf16r(bf16r(var) + 1e-5f)));
              sts_f(sb + SM_RS + r * 4, 1.f / sd);
              if (i < 4) {
                const float hm = -0.5f * bf16r(mean);
                const uint32_t s2 = pack_bf16(sd, sd);
                sts128(sb + SM_SD + (r - 16) * 64 + ((r >> 1) & 3) * 16, make_uint4(s2, s2, s2, s2));
                sts128(sb + SM_AP + (r - 16) * 16, make_uint4(pack_bf16(hm, hm), pack_bf16(hm, 0.f), 0u, 0u));
              }
            }
            fence_async_smem();
            __syncwarp();
            if (lane == 0) mbar_arrive(bar + B_STAT);
            PROFT(lane == 0, 64 + layer * 16 + 14);
            wo_w(__shfl_sync(0xffffffffu, layer, 0));
          }
          if (layer == 0 && warp == 2) {
            if (CSW) mbar_wait_u(bar + (CSW == 1 ? B_E0 : CSW == 2 ? B_OH1 : B_ODONE), 0);
#pragma unroll 1
            for (int wi = 0; wi < 6; ++wi) {
              float sB[8];
              colsum_load(wB, rb, g, wi, lane, sb + SM_BP + 6144, sB);
              colsum_red(g_cs + (epoch & 1) * 6144 + 3072, g, wi, lane, sB);
            }
            __syncwarp();
            if (lane == 0) flag_add(&g_csflag[8 + g].v);
            PROFT(h2 == 0, 64 + 13);
          }
        }
      }
    }
    __syncwarp();
    asm volatile("barrier.cluster.arrive.relaxed.aligned;\nbarrier.cluster.wait.aligned;\n" ::: "memory");
  } else {
    if (warp == 5) {
      if (lane == 0) {
        mbar_init(bar + B_FULLS, 1);
        asm volatile("fence.mbarrier_init.release.cluster;" ::: "memory");
      }
      __syncwarp();
      expect_tx_e(bar + B_FULLS, 65536);
      tma_2d_e(sb + XS * SLOT, &tm_x0, 0, m0, bar + B_FULLS);
#pragma unroll
      for (int j = 0; j < 6; ++j)
        tma_2d_e(sb + (j < 4 ? j + 4 : j - 2) * 8192, &tm_wA, (j < 4 ? 1024 + (j >> 1) * 1024 : 0) + g * 128 + (j & 1) * 64, 0, bar + B_FULLS);
      PROFT(lane == 0, 241);
    }
    if (lane < 8 && warp != 5 && threadIdx.x != 128) {
      const int i = (warp - 4) * 8 + lane;
      mbar_init(bar + i * 8, i < 32 ? 1u << ((BAR_CNT >> (2 * i)) & 3) : i < 48 ? 1u : (i == 59 || i == 60) ? 16u : i < 63 ? 4u : 8u);
      asm volatile("fence.mbarrier_init.release.cluster;" ::: "memory");
    }
    __syncwarp();
    asm volatile("barrier.cluster.arrive.relaxed.aligned;" ::: "memory");
    asm volatile("setmaxnreg.inc.sync.aligned.u32 232;");
    cluster_wait();
    PROFT(threadIdx.x == 128, 0);
    Ctx c; c.sb = sb; c.g = g; c.rb = rb; c.cu = warp - 4; c.out = out;
    consumer(c);
    asm volatile("bar.warp.sync 0xffffffff;\nbarrier.cluster.arrive.relaxed.aligned;\nbarrier.cluster.wait.aligned;\n" ::: "memory");
  }
}

typedef CUresult (*PFN_encodeTiled)(CUtensorMap*, CUtensorMapDataType, cuuint32_t, void*, const cuuint64_t*, const cuuint64_t*,
                                    const cuuint32_t*, const cuuint32_t*, CUtensorMapInterleave, CUtensorMapSwizzle,
                                    CUtensorMapL2promotion, CUtensorMapFloatOOBfill);

static CUtensorMap make_map(PFN_encodeTiled enc, const void* ptr, uint64_t cols, uint64_t rows, uint32_t box_c, uint32_t box_r, uint32_t nb = 1) {
  CUtensorMap m;
  cuuint64_t dims[3] = {nb > 1 ? box_c : cols, rows, cols / box_c};
  cuuint64_t strides[2] = {cols * 2, box_c * 2};
  cuuint32_t box[3] = {box_c, box_r, nb};
  cuuint32_t es[3] = {1, 1, 1};
  CUresult r = enc(&m, CU_TENSOR_MAP_DATA_TYPE_BFLOAT16, nb > 1 ? 3 : 2, const_cast<void*>(ptr), dims, strides, box, es, CU_TENSOR_MAP_INTERLEAVE_NONE,
      CU_TENSOR_MAP_SWIZZLE_128B, CU_TENSOR_MAP_L2_PROMOTION_L2_256B, CU_TENSOR_MAP_FLOAT_OOB_FILL_NONE);
  (void)r;
  return m;
}

extern "C" void kernel_launch(void* const* d_in, const int* in_sizes, int n_in, void* d_out, int out_size) {
  const bf16* A_x = (const bf16*)d_in[0];
  const bf16* A_wqkv = (const bf16*)d_in[1];
  const bf16* A_wphi = (const bf16*)d_in[2];
  const bf16* A_wo = (const bf16*)d_in[3];
  const bf16* B_wqkv = (const bf16*)d_in[5];
  const bf16* B_wo = (const bf16*)d_in[6];
  bf16* out = (bf16*)d_out;

  static PFN_encodeTiled enc = nullptr;
  static bf16 *p_x, *p_o;
  if (!enc) {
    void* fn = nullptr; cudaDriverEntryPointQueryResult qr;
    cudaGetDriverEntryPoint("cuTensorMapEncodeTiled", &fn, cudaEnableDefault, &qr);
    enc = (PFN_encodeTiled)fn;
    cudaGetSymbolAddress((void**)&p_x, g_x);
    cudaGetSymbolAddress((void**)&p_o, g_o);
    cudaFuncSetAttribute(mega_kernel, cudaFuncAttributeMaxDynamicSharedMemorySize, SM_TOTAL);
  }
  CUtensorMap tm_x0 = make_map(enc, A_x, 1024, 2048, 64, 128);
  CUtensorMap tm_x = make_map(enc, p_x, 1024, 2048, 64, 128);
  CUtensorMap tm_o = make_map(enc, p_o, 1024, 2048, 64, 128);
  CUtensorMap tm_wA = make_map(enc, A_wqkv, 3072, 1024, 64, 64);
  CUtensorMap tm_wB = make_map(enc, B_wqkv, 3072, 1024, 64, 64);
  CUtensorMap tm_woA = make_map(enc, A_wo, 1024, 1024, 64, 64);
  CUtensorMap tm_woB = make_map(enc, B_wo, 1024, 1024, 64, 64);
  mega_kernel<<<128, 384, SM_TOTAL, cudaStreamPerThread>>>(tm_x0, tm_x, tm_o, tm_wA, tm_wB, tm_woA, tm_woB,
                                                           A_wqkv, B_wqkv, A_wphi, out);
}
```

```cpp
#include <cuda_runtime.h>
#include <cuda_bf16.h>
#include <cuda.h>
#include <stdint.h>

typedef __nv_bfloat16 bf16;

constexpr int S_ = 2048, D_ = 1024;

struct __align__(128) Flag { unsigned int v; unsigned int pad[31]; };
__device__ __align__(1024) bf16 g_x[S_ * D_];
__device__ __align__(1024) bf16 g_o[S_ * D_];
__device__ __align__(1024) uint4 g_halo[128 * 2 * 512];
__device__ __align__(1024) uint4 g_kv[8 * 2 * 2 * 1280];
__device__ __align__(1024) float2 g_stats[4 * S_];
__device__ __align__(1024) float g_cs[2 * 2 * 3072];
__device__ Flag g_csflag[16];
__device__ __align__(128) unsigned int g_xf[16 * 32], g_of[16 * 32];
__device__ unsigned int g_epoch, g_err;
#define PROFT(cond, idx) asm volatile("" ::: "memory")

__device__ __forceinline__ uint32_t smem_u32(const void* p) { return (uint32_t)__cvta_generic_to_shared(p); }
__device__ __forceinline__ void mbar_init(uint32_t bar, uint32_t count) {
  asm volatile("mbarrier.init.shared::cta.b64 [%0], %1;" ::"r"(bar), "r"(count) : "memory");
}
__device__ __forceinline__ void mbar_expect_tx(uint32_t bar, uint32_t bytes) {
  asm volatile("mbarrier.arrive.expect_tx.shared::cta.b64 _, [%0], %1;" ::"r"(bar), "r"(bytes) : "memory");
}
__device__ __forceinline__ void mbar_arrive(uint32_t bar) {
  asm volatile("mbarrier.arrive.shared::cta.b64 _, [%0];" ::"r"(bar) : "memory");
}
__device__ __forceinline__ bool mbar_try_wait(uint32_t bar, uint32_t parity) {
  uint32_t ok;
  asm volatile("{\n.reg .pred p;\nmbarrier.try_wait.parity.shared::cta.b64 p, [%1], %2;\nselp.b32 %0, 1, 0, p;\n}\n"
               : "=r"(ok) : "r"(bar), "r"(parity) : "memory");
  return ok != 0;
}
__device__ __forceinline__ bool mbar_test_wait(uint32_t bar, uint32_t parity) {
  uint32_t ok;
  asm volatile("{\n.reg .pred p;\nmbarrier.test_wait.parity.shared::cta.b64 p, [%1], %2;\nselp.b32 %0, 1, 0, p;\n}\n"
               : "=r"(ok) : "r"(bar), "r"(parity) : "memory");
  return ok != 0;
}
__device__ __forceinline__ uint64_t gtimer() {
  uint64_t t; asm volatile("mov.u64 %0, %globaltimer;" : "=l"(t)); return t;
}
__device__ __forceinline__ void mbar_wait(uint32_t bar, uint32_t parity) {
  uint32_t n = 0;
#pragma unroll 1
  while (!mbar_try_wait(bar, parity)) {
    if (++n > (1u << 22)) { g_err = 1u; break; }
  }
}
__device__ __forceinline__ unsigned int ld_acquire(const unsigned int* p) {
  unsigned int v; asm volatile("ld.acquire.gpu.global.u32 %0, [%1];" : "=r"(v) : "l"(p) : "memory"); return v;
}
__device__ __forceinline__ void flag_add(unsigned int* p) {
  asm volatile("red.release.gpu.global.add.u32 [%0], 1;" ::"l"(p) : "memory");
}
__device__ __forceinline__ void flag_set(unsigned int* p, unsigned int v) {
  asm volatile("st.release.gpu.global.u32 [%0], %1;" ::"l"(p), "r"(v) : "memory");
}
template <int SLEEP>
__device__ __forceinline__ void src_wait(const unsigned int* f, unsigned int target, uint32_t need, uint32_t& ready, int lane) {
  uint32_t n = 0;
#pragma unroll 1
  while ((ready & need) != need) {
    const unsigned int v = ld_acquire(f + (lane & 15));
    ready = __ballot_sync(0xffffffffu, (int)(v - target) >= 0);
    if (SLEEP) { if ((ready & need) != need) __nanosleep(SLEEP); }
    if (++n > (1u << 20)) { g_err = 3u; break; }
  }
  __syncwarp();
}
__device__ __forceinline__ unsigned int ld_relaxed(const unsigned int* p) {
  unsigned int v; asm volatile("ld.relaxed.gpu.global.u32 %0, [%1];" : "=r"(v) : "l"(p) : "memory"); return v;
}
__device__ __forceinline__ bool src_wait_tma(const unsigned int* f, unsigned int target, uint32_t need, uint32_t& ready, int lane, uint32_t eb, uint32_t par) {
  uint32_t n = 0;
  bool fr = false;
#pragma unroll 1
  while ((ready & need) != need) {
    const unsigned int v = ld_acquire(f + (lane & 15));
    fr = __all_sync(0xffffffffu, mbar_test_wait(eb, par));
    ready = __ballot_sync(0xffffffffu, (int)(v - target) >= 0);
    if (++n > (1u << 20)) { g_err = 3u; break; }
  }
  return fr;
}
__device__ __forceinline__ uint4 ld_relaxed4(const uint4* p) {
  uint4 v; asm volatile("ld.relaxed.gpu.global.v4.u32 {%0,%1,%2,%3}, [%4];" : "=r"(v.x), "=r"(v.y), "=r"(v.z), "=r"(v.w) : "l"(p) : "memory"); return v;
}
__device__ __forceinline__ void st_relaxed4(uint4* p, uint32_t a, uint32_t b, uint32_t c, uint32_t d) {
  asm volatile("st.relaxed.gpu.global.v4.u32 [%0], {%1,%2,%3,%4};" ::"l"(p), "r"(a), "r"(b), "r"(c), "r"(d) : "memory");
}
template <int SLEEP>
__device__ __forceinline__ void flag_wait_t(const unsigned int* p, unsigned int target) {
  uint32_t n = 0;
#pragma unroll 1
  while ((int)(ld_acquire(p) - target) < 0) {
    if (SLEEP) __nanosleep(SLEEP);
    if (++n > (1u << 20)) { g_err = 2u; break; }
  }
}
__device__ __forceinline__ void flag_wait(const unsigned int* p, unsigned int target) { flag_wait_t<0>(p, target); }
__device__ __forceinline__ void flag_wait_slow(const unsigned int* p, unsigned int target) { flag_wait_t<256>(p, target); }
__device__ __forceinline__ void tma_load_2d(uint32_t dst, const CUtensorMap* tm, int c0, int c1, uint32_t bar) {
  asm volatile("cp.async.bulk.tensor.2d.shared::cluster.global.mbarrier::complete_tx::bytes [%0], [%1, {%2, %3}], [%4];"
               ::"r"(dst), "l"(tm), "r"(c0), "r"(c1), "r"(bar) : "memory");
}
__device__ __forceinline__ void tma_load_2d_mc(uint32_t dst, const CUtensorMap* tm, int c0, int c1, uint32_t bar, uint16_t mask) {
  asm volatile("cp.async.bulk.tensor.2d.shared::cluster.global.mbarrier::complete_tx::bytes.multicast::cluster [%0], [%1, {%2, %3}], [%4], %5;"
               ::"r"(dst), "l"(tm), "r"(c0), "r"(c1), "r"(bar), "h"(mask) : "memory");
}
__device__ __forceinline__ void mbar_wait_u(uint32_t bar, uint32_t parity) {
  uint32_t n = 0;
#pragma unroll 1
  while (!__all_sync(0xffffffffu, mbar_try_wait(bar, parity))) {
    if (++n > (1u << 22)) { g_err = 1u; break; }
  }
}
__device__ __forceinline__ void expect_tx_e(uint32_t bar, uint32_t bytes) {
  asm volatile("{\n.reg .pred p;\nelect.sync _|p, 0xffffffff;\n@p mbarrier.arrive.expect_tx.shared::cta.b64 _, [%0], %1;\n}\n" ::"r"(bar), "r"(bytes) : "memory");
}
__device__ __forceinline__ void tma_2d_e(uint32_t dst, const CUtensorMap* tm, int c0, int c1, uint32_t bar) {
  asm volatile("{\n.reg .pred p;\nelect.sync _|p, 0xffffffff;\n"
               "@p cp.async.bulk.tensor.2d.shared::cluster.global.mbarrier::complete_tx::bytes [%0], [%1, {%2, %3}], [%4];\n}\n"
               ::"r"(dst), "l"(tm), "r"(c0), "r"(c1), "r"(bar) : "memory");
}
__device__ __forceinline__ void tma_2d_mc_e(uint32_t dst, const CUtensorMap* tm, int c0, int c1, uint32_t bar) {
  asm volatile("{\n.reg .pred p;\nelect.sync _|p, 0xffffffff;\n"
               "@p cp.async.bulk.tensor.2d.shared::cluster.global.mbarrier::complete_tx::bytes.multicast::cluster [%0], [%1, {%2, %3}], [%4], %5;\n}\n"
               ::"r"(dst), "l"(tm), "r"(c0), "r"(c1), "r"(bar), "h"((uint16_t)3) : "memory");
}
__device__ __forceinline__ void tma_pf_e(const CUtensorMap* tm, int c0, int c1) {
  asm volatile("{\n.reg .pred p;\nelect.sync _|p, 0xffffffff;\n"
               "@p cp.async.bulk.prefetch.tensor.2d.L2.global.tile [%0, {%1, %2}];\n}\n" ::"l"(tm), "r"(c0), "r"(c1) : "memory");
}
__device__ __forceinline__ void tma_2d_to_e(uint32_t dst, const CUtensorMap* tm, int c0, int c1, uint32_t bar, uint32_t mask) {
  asm volatile("{\n.reg .pred p;\nelect.sync _|p, 0xffffffff;\n"
               "@p cp.async.bulk.tensor.2d.shared::cluster.global.mbarrier::complete_tx::bytes.multicast::cluster [%0], [%1, {%2, %3}], [%4], %5;\n}\n"
               ::"r"(dst), "l"(tm), "r"(c0), "r"(c1), "r"(bar), "h"((uint16_t)mask) : "memory");
}
__device__ __forceinline__ void tma_3d_mc_e(uint32_t dst, const CUtensorMap* tm, int c1, int c2, uint32_t bar) {
  asm volatile("{\n.reg .pred p;\nelect.sync _|p, 0xffffffff;\n"
               "@p cp.async.bulk.tensor.3d.shared::cluster.global.mbarrier::complete_tx::bytes.multicast::cluster [%0], [%1, {%6, %2, %3}], [%4], %5;\n}\n"
               ::"r"(dst), "l"(tm), "r"(c1), "r"(c2), "r"(bar), "h"((uint16_t)3), "r"(0) : "memory");
}
__device__ __forceinline__ uint32_t poll_flags(const unsigned int* f, unsigned int target, int lane) {
  const unsigned int v = ld_acquire(f + (lane & 15));
  const uint32_t r = __ballot_sync(0xffffffffu, (int)(v - target) >= 0);
  __syncwarp();
  return r;
}
__device__ __forceinline__ void mbar_arrive_cluster(uint32_t local_bar, uint32_t rank) {
  asm volatile("{\n.reg .b32 ra;\nmapa.shared::cluster.u32 ra, %0, %1;\nmbarrier.arrive.shared::cluster.b64 _, [ra];\n}\n"
               ::"r"(local_bar), "r"(rank) : "memory");
}
__device__ __forceinline__ void release2(uint32_t bar) { mbar_arrive_cluster(bar, 0); mbar_arrive_cluster(bar, 1); }
__device__ __forceinline__ void tma_store_2d(const CUtensorMap* tm, uint32_t src, int c0, int c1) {
  asm volatile("cp.async.bulk.tensor.2d.global.shared::cta.bulk_group [%0, {%2, %3}], [%1];"
               ::"l"(tm), "r"(src), "r"(c0), "r"(c1) : "memory");
}
__device__ __forceinline__ void bulk_store(void* dst, uint32_t src, uint32_t bytes) {
  asm volatile("cp.async.bulk.global.shared::cta.bulk_group [%0], [%1], %2;" ::"l"(dst), "r"(src), "r"(bytes) : "memory");
}
__device__ __forceinline__ void bulk_load(uint32_t dst, const void* src, uint32_t bytes, uint32_t bar) {
  asm volatile("cp.async.bulk.shared::cluster.global.mbarrier::complete_tx::bytes [%0], [%1], %2, [%3];" ::"r"(dst), "l"(src), "r"(bytes), "r"(bar) : "memory");
}
__device__ __forceinline__ void bulk_red_add(void* dst, uint32_t src, uint32_t bytes) {
  asm volatile("cp.reduce.async.bulk.global.shared::cta.bulk_group.add.f32 [%0], [%1], %2;" ::"l"(dst), "r"(src), "r"(bytes) : "memory");
}
__device__ __forceinline__ void bulk_red_add_e(void* dst, uint32_t src, uint32_t bytes) {
  asm volatile("{\n.reg .pred p;\nelect.sync _|p, 0xffffffff;\n@p cp.reduce.async.bulk.global.shared::cta.bulk_group.add.f32 [%0], [%1], %2;\n}\n" ::"l"(dst), "r"(src), "r"(bytes) : "memory");
}
__device__ __forceinline__ void bulk_commit() { asm volatile("cp.async.bulk.commit_group;" ::: "memory"); }
__device__ __forceinline__ void bulk_wait_read0() { asm volatile("cp.async.bulk.wait_group.read 0;" ::: "memory"); }
__device__ __forceinline__ void bulk_wait0() { asm volatile("cp.async.bulk.wait_group 0;" ::: "memory"); }
__device__ __forceinline__ void fence_async_smem() { asm volatile("fence.proxy.async.shared::cta;" ::: "memory"); }
__device__ __forceinline__ void fence_async_all() { asm volatile("fence.proxy.async.global;" ::: "memory"); }
__device__ __forceinline__ void wgmma_fence() { asm volatile("wgmma.fence.sync.aligned;" ::: "memory"); }
__device__ __forceinline__ void wgmma_commit() { asm volatile("wgmma.commit_group.sync.aligned;" ::: "memory"); }
template <int N> __device__ __forceinline__ void wgmma_wait() { asm volatile("wgmma.wait_group.sync.aligned %0;" ::"n"(N) : "memory"); }
__device__ __forceinline__ void cluster_arrive() { asm volatile("barrier.cluster.arrive.release.aligned;" ::: "memory"); }
__device__ __forceinline__ void cluster_wait() { asm volatile("barrier.cluster.wait.acquire.aligned;" ::: "memory"); }
template <int ID, int N> __device__ __forceinline__ void nbar() { asm volatile("bar.sync %0, %1;" ::"n"(ID), "n"(N) : "memory"); }
__device__ __forceinline__ uint64_t make_desc(uint32_t addr, uint32_t lbo_bytes, uint32_t sbo_bytes) {
  uint64_t d = 0;
  d |= (uint64_t)((addr & 0x3FFFF) >> 4);
  d |= (uint64_t)((lbo_bytes >> 4) & 0x3FFF) << 16;
  d |= (uint64_t)((sbo_bytes >> 4) & 0x3FFF) << 32;
  d |= (uint64_t)1 << 62;
  return d;
}
__device__ __forceinline__ uint64_t desc64(uint32_t lo, uint32_t hi) { return (uint64_t)lo | ((uint64_t)hi << 32); }
__device__ __forceinline__ uint32_t pack_bf16(float lo, float hi) {
  uint32_t r; asm("cvt.rn.bf16x2.f32 %0, %1, %2;" : "=r"(r) : "f"(hi), "f"(lo)); return r;
}
__device__ __forceinline__ uint32_t mul_bf16x2(uint32_t a, uint32_t s, bool hi) {
  __nv_bfloat162 x = *reinterpret_cast<__nv_bfloat162*>(&a), y = *reinterpret_cast<__nv_bfloat162*>(&s);
  x = __hmul2(x, hi ? __high2bfloat162(y) : __low2bfloat162(y));
  return *reinterpret_cast<uint32_t*>(&x);
}
__device__ __forceinline__ float bf16r(float x) { return __bfloat162float(__float2bfloat16_rn(x)); }
__device__ __forceinline__ float bf_lo(uint32_t u) { return __uint_as_float(u << 16); }
__device__ __forceinline__ float bf_hi(uint32_t u) { return __uint_as_float(u & 0xFFFF0000u); }
__device__ __forceinline__ float ex2(float x) { float r; asm("ex2.approx.ftz.f32 %0, %1;" : "=f"(r) : "f"(x)); return r; }
__device__ __forceinline__ float rcp(float x) { float r; asm("rcp.approx.ftz.f32 %0, %1;" : "=f"(r) : "f"(x)); return r; }
__device__ __forceinline__ void mma_bf16(float (&d)[4], uint32_t a0, uint32_t a1, uint32_t a2, uint32_t a3, uint32_t b0, uint32_t b1) {
  asm("mma.sync.aligned.m16n8k16.row.col.f32.bf16.bf16.f32 {%0,%1,%2,%3}, {%4,%5,%6,%7}, {%8,%9}, {%0,%1,%2,%3};"
               : "+f"(d[0]), "+f"(d[1]), "+f"(d[2]), "+f"(d[3]) : "r"(a0), "r"(a1), "r"(a2), "r"(a3), "r"(b0), "r"(b1));
}
__device__ __forceinline__ void ldsm_x4(uint32_t& r0, uint32_t& r1, uint32_t& r2, uint32_t& r3, uint32_t addr) {
  asm volatile("ldmatrix.sync.aligned.m8n8.x4.shared.b16 {%0,%1,%2,%3}, [%4];"
               : "=r"(r0), "=r"(r1), "=r"(r2), "=r"(r3) : "r"(addr) : "memory");
}
__device__ __forceinline__ void ldsm_x4_t(uint32_t& r0, uint32_t& r1, uint32_t& r2, uint32_t& r3, uint32_t addr) {
  asm volatile("ldmatrix.sync.aligned.m8n8.x4.trans.shared.b16 {%0,%1,%2,%3}, [%4];"
               : "=r"(r0), "=r"(r1), "=r"(r2), "=r"(r3) : "r"(addr) : "memory");
}
__device__ __forceinline__ void ldsm_x2_t(uint32_t& r0, uint32_t& r1, uint32_t addr) {
  asm volatile("ldmatrix.sync.aligned.m8n8.x2.trans.shared.b16 {%0,%1}, [%2];"
               : "=r"(r0), "=r"(r1) : "r"(addr) : "memory");
}
__device__ __forceinline__ void stsm_x4(uint32_t addr, uint32_t r0, uint32_t r1, uint32_t r2, uint32_t r3) {
  asm volatile("stmatrix.sync.aligned.m8n8.x4.shared.b16 [%0], {%1,%2,%3,%4};"
               ::"r"(addr), "r"(r0), "r"(r1), "r"(r2), "r"(r3) : "memory");
}
__device__ __forceinline__ void stsm_x4_p(bool on, uint32_t addr, uint32_t r0, uint32_t r1, uint32_t r2, uint32_t r3) {
  asm volatile("{\n.reg .pred p;\nsetp.ne.b32 p, %5, 0;\n@p stmatrix.sync.aligned.m8n8.x4.shared.b16 [%0], {%1,%2,%3,%4};\n}\n"
               ::"r"(addr), "r"(r0), "r"(r1), "r"(r2), "r"(r3), "r"((int)on) : "memory");
}
__device__ __forceinline__ float2 lds_f2(uint32_t addr) {
  float2 v; asm volatile("ld.shared.v2.f32 {%0,%1}, [%2];" : "=f"(v.x), "=f"(v.y) : "r"(addr) : "memory"); return v;
}
__device__ __forceinline__ uint4 lds128(uint32_t addr) {
  uint4 v; asm volatile("ld.shared.v4.b32 {%0,%1,%2,%3}, [%4];" : "=r"(v.x), "=r"(v.y), "=r"(v.z), "=r"(v.w) : "r"(addr) : "memory"); return v;
}
__device__ __forceinline__ void sts128(uint32_t addr, uint4 v) {
  asm volatile("st.shared.v4.b32 [%0], {%1,%2,%3,%4};" ::"r"(addr), "r"(v.x), "r"(v.y), "r"(v.z), "r"(v.w) : "memory");
}
__device__ __forceinline__ float lds_f(uint32_t addr) {
  float v; asm volatile("ld.shared.f32 %0, [%1];" : "=f"(v) : "r"(addr) : "memory"); return v;
}
__device__ __forceinline__ uint32_t lds_vol(uint32_t addr) {
  uint32_t v; asm volatile("ld.volatile.shared.u32 %0, [%1];" : "=r"(v) : "r"(addr) : "memory"); return v;
}
__device__ __forceinline__ void sts16(uint32_t addr, uint32_t v) {
  asm volatile("st.shared.u16 [%0], %1;" ::"r"(addr), "h"((unsigned short)v) : "memory");
}
__device__ __forceinline__ void nbar_dyn(int id, int n) { asm volatile("bar.sync %0, %1;" ::"r"(id), "r"(n) : "memory"); }
__device__ __forceinline__ uint64_t make_desc_ns(uint32_t addr, uint32_t lbo_bytes, uint32_t sbo_bytes) {
  return (uint64_t)((addr & 0x3FFFF) >> 4) | ((uint64_t)(lbo_bytes >> 4) << 16) | ((uint64_t)(sbo_bytes >> 4) << 32);
}
__device__ __forceinline__ void sts_f(uint32_t addr, float v) { asm volatile("st.shared.f32 [%0], %1;" ::"r"(addr), "f"(v) : "memory"); }
__device__ __forceinline__ void sts64(uint32_t addr, uint32_t a, uint32_t b) {
  asm volatile("st.shared.v2.b32 [%0], {%1,%2};" ::"r"(addr), "r"(a), "r"(b) : "memory");
}
__device__ __forceinline__ void sts_f2(uint32_t addr, float a, float b) {
  asm volatile("st.shared.v2.f32 [%0], {%1,%2};" ::"r"(addr), "f"(a), "f"(b) : "memory");
}
__device__ __forceinline__ void red_add2(float* p, float a, float b) {
  asm volatile("red.global.add.v2.f32 [%0], {%1,%2};" ::"l"(p), "f"(a), "f"(b) : "memory");
}
__device__ __forceinline__ void red_add4(float* p, float a, float b, float c, float d) {
  asm volatile("red.global.add.v4.f32 [%0], {%1,%2,%3,%4};" ::"l"(p), "f"(a), "f"(b), "f"(c), "f"(d) : "memory");
}
__device__ __forceinline__ void red_add1(float* p, float a) {
  asm volatile("red.global.add.f32 [%0], %1;" ::"l"(p), "f"(a) : "memory");
}
__device__ __forceinline__ void l2_prefetch(const void* p, uint32_t bytes) {
  asm volatile("cp.async.bulk.prefetch.L2.global [%0], %1;" ::"l"(p), "r"(bytes) : "memory");
}

__device__ __forceinline__ void wgmma_n256(float (&d)[192], uint64_t da, uint64_t db, int scale_d) {
  asm volatile("{\n.reg .pred p;\nsetp.ne.b32 p, %130, 0;\n"
    "wgmma.mma_async.sync.aligned.m64n256k16.f32.bf16.bf16 {%0, %1, %2, %3, %4, %5, %6, %7, %8, %9, %10, %11, %12, %13, %14, %15, %16, %17, %18, %19, %20, %21, %22, %23, %24, %25, %26, %27, %28, %29, %30, %31, %32, %33, %34, %35, %36, %37, %38, %39, %40, %41, %42, %43, %44, %45, %46, %47, %48, %49, %50, %51, %52, %53, %54, %55, %56, %57, %58, %59, %60, %61, %62, %63, %64, %65, %66, %67, %68, %69, %70, %71, %72, %73, %74, %75, %76, %77, %78, %79, %80, %81, %82, %83, %84, %85, %86, %87, %88, %89, %90, %91, %92, %93, %94, %95, %96, %97, %98, %99, %100, %101, %102, %103, %104, %105, %106, %107, %108, %109, %110, %111, %112, %113, %114, %115, %116, %117, %118, %119, %120, %121, %122, %123, %124, %125, %126, %127}, %128, %129, p, 1, 1, 0, 1;\n}\n"
    : "+f"(d[0]), "+f"(d[1]), "+f"(d[2]), "+f"(d[3]), "+f"(d[4]), "+f"(d[5]), "+f"(d[6]), "+f"(d[7]), "+f"(d[8]), "+f"(d[9]), "+f"(d[10]), "+f"(d[11]), "+f"(d[12]), "+f"(d[13]), "+f"(d[14]), "+f"(d[15]), "+f"(d[16]), "+f"(d[17]), "+f"(d[18]), "+f"(d[19]), "+f"(d[20]), "+f"(d[21]), "+f"(d[22]), "+f"(d[23]), "+f"(d[24]), "+f"(d[25]), "+f"(d[26]), "+f"(d[27]), "+f"(d[28]), "+f"(d[29]), "+f"(d[30]), "+f"(d[31]), "+f"(d[32]), "+f"(d[33]), "+f"(d[34]), "+f"(d[35]), "+f"(d[36]), "+f"(d[37]), "+f"(d[38]), "+f"(d[39]), "+f"(d[40]), "+f"(d[41]), "+f"(d[42]), "+f"(d[43]), "+f"(d[44]), "+f"(d[45]), "+f"(d[46]), "+f"(d[47]), "+f"(d[48]), "+f"(d[49]), "+f"(d[50]), "+f"(d[51]), "+f"(d[52]), "+f"(d[53]), "+f"(d[54]), "+f"(d[55]), "+f"(d[56]), "+f"(d[57]), "+f"(d[58]), "+f"(d[59]), "+f"(d[60]), "+f"(d[61]), "+f"(d[62]), "+f"(d[63]), "+f"(d[64]), "+f"(d[65]), "+f"(d[66]), "+f"(d[67]), "+f"(d[68]), "+f"(d[69]), "+f"(d[70]), "+f"(d[71]), "+f"(d[72]), "+f"(d[73]), "+f"(d[74]), "+f"(d[75]), "+f"(d[76]), "+f"(d[77]), "+f"(d[78]), "+f"(d[79]), "+f"(d[80]), "+f"(d[81]), "+f"(d[82]), "+f"(d[83]), "+f"(d[84]), "+f"(d[85]), "+f"(d[86]), "+f"(d[87]), "+f"(d[88]), "+f"(d[89]), "+f"(d[90]), "+f"(d[91]), "+f"(d[92]), "+f"(d[93]), "+f"(d[94]), "+f"(d[95]), "+f"(d[96]), "+f"(d[97]), "+f"(d[98]), "+f"(d[99]), "+f"(d[100]), "+f"(d[101]), "+f"(d[102]), "+f"(d[103]), "+f"(d[104]), "+f"(d[105]), "+f"(d[106]), "+f"(d[107]), "+f"(d[108]), "+f"(d[109]), "+f"(d[110]), "+f"(d[111]), "+f"(d[112]), "+f"(d[113]), "+f"(d[114]), "+f"(d[115]), "+f"(d[116]), "+f"(d[117]), "+f"(d[118]), "+f"(d[119]), "+f"(d[120]), "+f"(d[121]), "+f"(d[122]), "+f"(d[123]), "+f"(d[124]), "+f"(d[125]), "+f"(d[126]), "+f"(d[127])
    : "l"(da), "l"(db), "r"(scale_d));
}
__device__ __forceinline__ void wgmma_n128(float (&d)[192], uint64_t da, uint64_t db, int scale_d) {
  asm volatile("{\n.reg .pred p;\nsetp.ne.b32 p, %66, 0;\n"
    "wgmma.mma_async.sync.aligned.m64n128k16.f32.bf16.bf16 {%0, %1, %2, %3, %4, %5, %6, %7, %8, %9, %10, %11, %12, %13, %14, %15, %16, %17, %18, %19, %20, %21, %22, %23, %24, %25, %26, %27, %28, %29, %30, %31, %32, %33, %34, %35, %36, %37, %38, %39, %40, %41, %42, %43, %44, %45, %46, %47, %48, %49, %50, %51, %52, %53, %54, %55, %56, %57, %58, %59, %60, %61, %62, %63}, %64, %65, p, 1, 1, 0, 1;\n}\n"
    : "+f"(d[128]), "+f"(d[129]), "+f"(d[130]), "+f"(d[131]), "+f"(d[132]), "+f"(d[133]), "+f"(d[134]), "+f"(d[135]), "+f"(d[136]), "+f"(d[137]), "+f"(d[138]), "+f"(d[139]), "+f"(d[140]), "+f"(d[141]), "+f"(d[142]), "+f"(d[143]), "+f"(d[144]), "+f"(d[145]), "+f"(d[146]), "+f"(d[147]), "+f"(d[148]), "+f"(d[149]), "+f"(d[150]), "+f"(d[151]), "+f"(d[152]), "+f"(d[153]), "+f"(d[154]), "+f"(d[155]), "+f"(d[156]), "+f"(d[157]), "+f"(d[158]), "+f"(d[159]), "+f"(d[160]), "+f"(d[161]), "+f"(d[162]), "+f"(d[163]), "+f"(d[164]), "+f"(d[165]), "+f"(d[166]), "+f"(d[167]), "+f"(d[168]), "+f"(d[169]), "+f"(d[170]), "+f"(d[171]), "+f"(d[172]), "+f"(d[173]), "+f"(d[174]), "+f"(d[175]), "+f"(d[176]), "+f"(d[177]), "+f"(d[178]), "+f"(d[179]), "+f"(d[180]), "+f"(d[181]), "+f"(d[182]), "+f"(d[183]), "+f"(d[184]), "+f"(d[185]), "+f"(d[186]), "+f"(d[187]), "+f"(d[188]), "+f"(d[189]), "+f"(d[190]), "+f"(d[191])
    : "l"(da), "l"(db), "r"(scale_d));
}
__device__ __forceinline__ void wgmma_n256_k(float (&d)[192], uint64_t da, uint64_t db, int scale_d) {
  asm volatile("{\n.reg .pred p;\nsetp.ne.b32 p, %130, 0;\n"
    "wgmma.mma_async.sync.aligned.m64n256k16.f32.bf16.bf16 {%0, %1, %2, %3, %4, %5, %6, %7, %8, %9, %10, %11, %12, %13, %14, %15, %16, %17, %18, %19, %20, %21, %22, %23, %24, %25, %26, %27, %28, %29, %30, %31, %32, %33, %34, %35, %36, %37, %38, %39, %40, %41, %42, %43, %44, %45, %46, %47, %48, %49, %50, %51, %52, %53, %54, %55, %56, %57, %58, %59, %60, %61, %62, %63, %64, %65, %66, %67, %68, %69, %70, %71, %72, %73, %74, %75, %76, %77, %78, %79, %80, %81, %82, %83, %84, %85, %86, %87, %88, %89, %90, %91, %92, %93, %94, %95, %96, %97, %98, %99, %100, %101, %102, %103, %104, %105, %106, %107, %108, %109, %110, %111, %112, %113, %114, %115, %116, %117, %118, %119, %120, %121, %122, %123, %124, %125, %126, %127}, %128, %129, p, 1, 1, 0, 0;\n}\n"
    : "+f"(d[0]), "+f"(d[1]), "+f"(d[2]), "+f"(d[3]), "+f"(d[4]), "+f"(d[5]), "+f"(d[6]), "+f"(d[7]), "+f"(d[8]), "+f"(d[9]), "+f"(d[10]), "+f"(d[11]), "+f"(d[12]), "+f"(d[13]), "+f"(d[14]), "+f"(d[15]), "+f"(d[16]), "+f"(d[17]), "+f"(d[18]), "+f"(d[19]), "+f"(d[20]), "+f"(d[21]), "+f"(d[22]), "+f"(d[23]), "+f"(d[24]), "+f"(d[25]), "+f"(d[26]), "+f"(d[27]), "+f"(d[28]), "+f"(d[29]), "+f"(d[30]), "+f"(d[31]), "+f"(d[32]), "+f"(d[33]), "+f"(d[34]), "+f"(d[35]), "+f"(d[36]), "+f"(d[37]), "+f"(d[38]), "+f"(d[39]), "+f"(d[40]), "+f"(d[41]), "+f"(d[42]), "+f"(d[43]), "+f"(d[44]), "+f"(d[45]), "+f"(d[46]), "+f"(d[47]), "+f"(d[48]), "+f"(d[49]), "+f"(d[50]), "+f"(d[51]), "+f"(d[52]), "+f"(d[53]), "+f"(d[54]), "+f"(d[55]), "+f"(d[56]), "+f"(d[57]), "+f"(d[58]), "+f"(d[59]), "+f"(d[60]), "+f"(d[61]), "+f"(d[62]), "+f"(d[63]), "+f"(d[64]), "+f"(d[65]), "+f"(d[66]), "+f"(d[67]), "+f"(d[68]), "+f"(d[69]), "+f"(d[70]), "+f"(d[71]), "+f"(d[72]), "+f"(d[73]), "+f"(d[74]), "+f"(d[75]), "+f"(d[76]), "+f"(d[77]), "+f"(d[78]), "+f"(d[79]), "+f"(d[80]), "+f"(d[81]), "+f"(d[82]), "+f"(d[83]), "+f"(d[84]), "+f"(d[85]), "+f"(d[86]), "+f"(d[87]), "+f"(d[88]), "+f"(d[89]), "+f"(d[90]), "+f"(d[91]), "+f"(d[92]), "+f"(d[93]), "+f"(d[94]), "+f"(d[95]), "+f"(d[96]), "+f"(d[97]), "+f"(d[98]), "+f"(d[99]), "+f"(d[100]), "+f"(d[101]), "+f"(d[102]), "+f"(d[103]), "+f"(d[104]), "+f"(d[105]), "+f"(d[106]), "+f"(d[107]), "+f"(d[108]), "+f"(d[109]), "+f"(d[110]), "+f"(d[111]), "+f"(d[112]), "+f"(d[113]), "+f"(d[114]), "+f"(d[115]), "+f"(d[116]), "+f"(d[117]), "+f"(d[118]), "+f"(d[119]), "+f"(d[120]), "+f"(d[121]), "+f"(d[122]), "+f"(d[123]), "+f"(d[124]), "+f"(d[125]), "+f"(d[126]), "+f"(d[127])
    : "l"(da), "l"(db), "r"(scale_d));
}
__device__ __forceinline__ void wgmma_n128_k(float (&d)[192], uint64_t da, uint64_t db, int scale_d) {
  asm volatile("{\n.reg .pred p;\nsetp.ne.b32 p, %66, 0;\n"
    "wgmma.mma_async.sync.aligned.m64n128k16.f32.bf16.bf16 {%0, %1, %2, %3, %4, %5, %6, %7, %8, %9, %10, %11, %12, %13, %14, %15, %16, %17, %18, %19, %20, %21, %22, %23, %24, %25, %26, %27, %28, %29, %30, %31, %32, %33, %34, %35, %36, %37, %38, %39, %40, %41, %42, %43, %44, %45, %46, %47, %48, %49, %50, %51, %52, %53, %54, %55, %56, %57, %58, %59, %60, %61, %62, %63}, %64, %65, p, 1, 1, 0, 0;\n}\n"
    : "+f"(d[128]), "+f"(d[129]), "+f"(d[130]), "+f"(d[131]), "+f"(d[132]), "+f"(d[133]), "+f"(d[134]), "+f"(d[135]), "+f"(d[136]), "+f"(d[137]), "+f"(d[138]), "+f"(d[139]), "+f"(d[140]), "+f"(d[141]), "+f"(d[142]), "+f"(d[143]), "+f"(d[144]), "+f"(d[145]), "+f"(d[146]), "+f"(d[147]), "+f"(d[148]), "+f"(d[149]), "+f"(d[150]), "+f"(d[151]), "+f"(d[152]), "+f"(d[153]), "+f"(d[154]), "+f"(d[155]), "+f"(d[156]), "+f"(d[157]), "+f"(d[158]), "+f"(d[159]), "+f"(d[160]), "+f"(d[161]), "+f"(d[162]), "+f"(d[163]), "+f"(d[164]), "+f"(d[165]), "+f"(d[166]), "+f"(d[167]), "+f"(d[168]), "+f"(d[169]), "+f"(d[170]), "+f"(d[171]), "+f"(d[172]), "+f"(d[173]), "+f"(d[174]), "+f"(d[175]), "+f"(d[176]), "+f"(d[177]), "+f"(d[178]), "+f"(d[179]), "+f"(d[180]), "+f"(d[181]), "+f"(d[182]), "+f"(d[183]), "+f"(d[184]), "+f"(d[185]), "+f"(d[186]), "+f"(d[187]), "+f"(d[188]), "+f"(d[189]), "+f"(d[190]), "+f"(d[191])
    : "l"(da), "l"(db), "r"(scale_d));
}
__device__ __forceinline__ void wgmma_n40_tt(float (&d)[20], uint64_t da, uint64_t db, int scale_d) {
  asm volatile("{\n.reg .pred p;\nsetp.ne.b32 p, %22, 0;\n"
    "wgmma.mma_async.sync.aligned.m64n40k16.f32.bf16.bf16 {%0, %1, %2, %3, %4, %5, %6, %7, %8, %9, %10, %11, %12, %13, %14, %15, %16, %17, %18, %19}, %20, %21, p, 1, 1, 1, 1;\n}\n"
    : "+f"(d[0]), "+f"(d[1]), "+f"(d[2]), "+f"(d[3]), "+f"(d[4]), "+f"(d[5]), "+f"(d[6]), "+f"(d[7]), "+f"(d[8]), "+f"(d[9]), "+f"(d[10]), "+f"(d[11]), "+f"(d[12]), "+f"(d[13]), "+f"(d[14]), "+f"(d[15]), "+f"(d[16]), "+f"(d[17]), "+f"(d[18]), "+f"(d[19])
    : "l"(da), "l"(db), "r"(scale_d));
}
__device__ __forceinline__ void wgmma_n40_rs(float (&d)[20], const uint32_t (&a)[4], uint64_t db, int scale_d) {
  asm volatile("{\n.reg .pred p;\nsetp.ne.b32 p, %25, 0;\n"
    "wgmma.mma_async.sync.aligned.m64n40k16.f32.bf16.bf16 {%0, %1, %2, %3, %4, %5, %6, %7, %8, %9, %10, %11, %12, %13, %14, %15, %16, %17, %18, %19}, {%20, %21, %22, %23}, %24, p, 1, 1, 1;\n}\n"
    : "+f"(d[0]), "+f"(d[1]), "+f"(d[2]), "+f"(d[3]), "+f"(d[4]), "+f"(d[5]), "+f"(d[6]), "+f"(d[7]), "+f"(d[8]), "+f"(d[9]), "+f"(d[10]), "+f"(d[11]), "+f"(d[12]), "+f"(d[13]), "+f"(d[14]), "+f"(d[15]), "+f"(d[16]), "+f"(d[17]), "+f"(d[18]), "+f"(d[19])
    : "r"(a[0]), "r"(a[1]), "r"(a[2]), "r"(a[3]), "l"(db), "r"(scale_d));
}
__device__ __forceinline__ void wgmma_n256_0(float (&d)[192], uint64_t da, uint64_t db) {
  asm volatile("{\n.reg .pred p;\nsetp.ne.b32 p, 0, 0;\n"
    "wgmma.mma_async.sync.aligned.m64n256k16.f32.bf16.bf16 {%0, %1, %2, %3, %4, %5, %6, %7, %8, %9, %10, %11, %12, %13, %14, %15, %16, %17, %18, %19, %20, %21, %22, %23, %24, %25, %26, %27, %28, %29, %30, %31, %32, %33, %34, %35, %36, %37, %38, %39, %40, %41, %42, %43, %44, %45, %46, %47, %48, %49, %50, %51, %52, %53, %54, %55, %56, %57, %58, %59, %60, %61, %62, %63, %64, %65, %66, %67, %68, %69, %70, %71, %72, %73, %74, %75, %76, %77, %78, %79, %80, %81, %82, %83, %84, %85, %86, %87, %88, %89, %90, %91, %92, %93, %94, %95, %96, %97, %98, %99, %100, %101, %102, %103, %104, %105, %106, %107, %108, %109, %110, %111, %112, %113, %114, %115, %116, %117, %118, %119, %120, %121, %122, %123, %124, %125, %126, %127}, %128, %129, p, 1, 1, 0, 1;\n}\n"
    : "=f"(d[0]), "=f"(d[1]), "=f"(d[2]), "=f"(d[3]), "=f"(d[4]), "=f"(d[5]), "=f"(d[6]), "=f"(d[7]), "=f"(d[8]), "=f"(d[9]), "=f"(d[10]), "=f"(d[11]), "=f"(d[12]), "=f"(d[13]), "=f"(d[14]), "=f"(d[15]), "=f"(d[16]), "=f"(d[17]), "=f"(d[18]), "=f"(d[19]), "=f"(d[20]), "=f"(d[21]), "=f"(d[22]), "=f"(d[23]), "=f"(d[24]), "=f"(d[25]), "=f"(d[26]), "=f"(d[27]), "=f"(d[28]), "=f"(d[29]), "=f"(d[30]), "=f"(d[31]), "=f"(d[32]), "=f"(d[33]), "=f"(d[34]), "=f"(d[35]), "=f"(d[36]), "=f"(d[37]), "=f"(d[38]), "=f"(d[39]), "=f"(d[40]), "=f"(d[41]), "=f"(d[42]), "=f"(d[43]), "=f"(d[44]), "=f"(d[45]), "=f"(d[46]), "=f"(d[47]), "=f"(d[48]), "=f"(d[49]), "=f"(d[50]), "=f"(d[51]), "=f"(d[52]), "=f"(d[53]), "=f"(d[54]), "=f"(d[55]), "=f"(d[56]), "=f"(d[57]), "=f"(d[58]), "=f"(d[59]), "=f"(d[60]), "=f"(d[61]), "=f"(d[62]), "=f"(d[63]), "=f"(d[64]), "=f"(d[65]), "=f"(d[66]), "=f"(d[67]), "=f"(d[68]), "=f"(d[69]), "=f"(d[70]), "=f"(d[71]), "=f"(d[72]), "=f"(d[73]), "=f"(d[74]), "=f"(d[75]), "=f"(d[76]), "=f"(d[77]), "=f"(d[78]), "=f"(d[79]), "=f"(d[80]), "=f"(d[81]), "=f"(d[82]), "=f"(d[83]), "=f"(d[84]), "=f"(d[85]), "=f"(d[86]), "=f"(d[87]), "=f"(d[88]), "=f"(d[89]), "=f"(d[90]), "=f"(d[91]), "=f"(d[92]), "=f"(d[93]), "=f"(d[94]), "=f"(d[95]), "=f"(d[96]), "=f"(d[97]), "=f"(d[98]), "=f"(d[99]), "=f"(d[100]), "=f"(d[101]), "=f"(d[102]), "=f"(d[103]), "=f"(d[104]), "=f"(d[105]), "=f"(d[106]), "=f"(d[107]), "=f"(d[108]), "=f"(d[109]), "=f"(d[110]), "=f"(d[111]), "=f"(d[112]), "=f"(d[113]), "=f"(d[114]), "=f"(d[115]), "=f"(d[116]), "=f"(d[117]), "=f"(d[118]), "=f"(d[119]), "=f"(d[120]), "=f"(d[121]), "=f"(d[122]), "=f"(d[123]), "=f"(d[124]), "=f"(d[125]), "=f"(d[126]), "=f"(d[127])
    : "l"(da), "l"(db));
}
__device__ __forceinline__ void wgmma_n128_0(float (&d)[192], uint64_t da, uint64_t db) {
  asm volatile("{\n.reg .pred p;\nsetp.ne.b32 p, 0, 0;\n"
    "wgmma.mma_async.sync.aligned.m64n128k16.f32.bf16.bf16 {%0, %1, %2, %3, %4, %5, %6, %7, %8, %9, %10, %11, %12, %13, %14, %15, %16, %17, %18, %19, %20, %21, %22, %23, %24, %25, %26, %27, %28, %29, %30, %31, %32, %33, %34, %35, %36, %37, %38, %39, %40, %41, %42, %43, %44, %45, %46, %47, %48, %49, %50, %51, %52, %53, %54, %55, %56, %57, %58, %59, %60, %61, %62, %63}, %64, %65, p, 1, 1, 0, 1;\n}\n"
    : "=f"(d[128]), "=f"(d[129]), "=f"(d[130]), "=f"(d[131]), "=f"(d[132]), "=f"(d[133]), "=f"(d[134]), "=f"(d[135]), "=f"(d[136]), "=f"(d[137]), "=f"(d[138]), "=f"(d[139]), "=f"(d[140]), "=f"(d[141]), "=f"(d[142]), "=f"(d[143]), "=f"(d[144]), "=f"(d[145]), "=f"(d[146]), "=f"(d[147]), "=f"(d[148]), "=f"(d[149]), "=f"(d[150]), "=f"(d[151]), "=f"(d[152]), "=f"(d[153]), "=f"(d[154]), "=f"(d[155]), "=f"(d[156]), "=f"(d[157]), "=f"(d[158]), "=f"(d[159]), "=f"(d[160]), "=f"(d[161]), "=f"(d[162]), "=f"(d[163]), "=f"(d[164]), "=f"(d[165]), "=f"(d[166]), "=f"(d[167]), "=f"(d[168]), "=f"(d[169]), "=f"(d[170]), "=f"(d[171]), "=f"(d[172]), "=f"(d[173]), "=f"(d[174]), "=f"(d[175]), "=f"(d[176]), "=f"(d[177]), "=f"(d[178]), "=f"(d[179]), "=f"(d[180]), "=f"(d[181]), "=f"(d[182]), "=f"(d[183]), "=f"(d[184]), "=f"(d[185]), "=f"(d[186]), "=f"(d[187]), "=f"(d[188]), "=f"(d[189]), "=f"(d[190]), "=f"(d[191])
    : "l"(da), "l"(db));
}
__device__ __forceinline__ void wgmma_n64a(float (&d)[192], uint64_t da, uint64_t db, int scale_d) {
  asm volatile("{\n.reg .pred p;\nsetp.ne.b32 p, %34, 0;\n"
    "wgmma.mma_async.sync.aligned.m64n64k16.f32.bf16.bf16 {%0, %1, %2, %3, %4, %5, %6, %7, %8, %9, %10, %11, %12, %13, %14, %15, %16, %17, %18, %19, %20, %21, %22, %23, %24, %25, %26, %27, %28, %29, %30, %31}, %32, %33, p, 1, 1, 0, 1;\n}\n"
    : "+f"(d[128]), "+f"(d[129]), "+f"(d[130]), "+f"(d[131]), "+f"(d[132]), "+f"(d[133]), "+f"(d[134]), "+f"(d[135]), "+f"(d[136]), "+f"(d[137]), "+f"(d[138]), "+f"(d[139]), "+f"(d[140]), "+f"(d[141]), "+f"(d[142]), "+f"(d[143]), "+f"(d[144]), "+f"(d[145]), "+f"(d[146]), "+f"(d[147]), "+f"(d[148]), "+f"(d[149]), "+f"(d[150]), "+f"(d[151]), "+f"(d[152]), "+f"(d[153]), "+f"(d[154]), "+f"(d[155]), "+f"(d[156]), "+f"(d[157]), "+f"(d[158]), "+f"(d[159])
    : "l"(da), "l"(db), "r"(scale_d));
}
__device__ __forceinline__ void wgmma_n64b(float (&d)[192], uint64_t da, uint64_t db, int scale_d) {
  asm volatile("{\n.reg .pred p;\nsetp.ne.b32 p, %34, 0;\n"
    "wgmma.mma_async.sync.aligned.m64n64k16.f32.bf16.bf16 {%0, %1, %2, %3, %4, %5, %6, %7, %8, %9, %10, %11, %12, %13, %14, %15, %16, %17, %18, %19, %20, %21, %22, %23, %24, %25, %26, %27, %28, %29, %30, %31}, %32, %33, p, 1, 1, 0, 1;\n}\n"
    : "+f"(d[160]), "+f"(d[161]), "+f"(d[162]), "+f"(d[163]), "+f"(d[164]), "+f"(d[165]), "+f"(d[166]), "+f"(d[167]), "+f"(d[168]), "+f"(d[169]), "+f"(d[170]), "+f"(d[171]), "+f"(d[172]), "+f"(d[173]), "+f"(d[174]), "+f"(d[175]), "+f"(d[176]), "+f"(d[177]), "+f"(d[178]), "+f"(d[179]), "+f"(d[180]), "+f"(d[181]), "+f"(d[182]), "+f"(d[183]), "+f"(d[184]), "+f"(d[185]), "+f"(d[186]), "+f"(d[187]), "+f"(d[188]), "+f"(d[189]), "+f"(d[190]), "+f"(d[191])
    : "l"(da), "l"(db), "r"(scale_d));
}

constexpr int SLOT = 16384;
constexpr int KVT = 10240;
constexpr uint32_t QA = 0x0BAu, QK = 0x462u, QQ = 0x981u;
constexpr int SM_SD = 12 * SLOT;
constexpr int SM_BAR = SM_SD + 8192;
constexpr int SM_RS = SM_BAR + 512;
constexpr int SM_AP = SM_RS + 768;
constexpr int SM_BP = SM_AP + 2048;
constexpr int SM_WPHI = SM_BP + 12288;
constexpr int SM_EPOCH = SM_WPHI + 10240;
constexpr int SM_TOTAL = SM_EPOCH + 16 + 1024;
constexpr int B_FULLS = 0, B_XOLD = 24, B_STAT = 32, B_EMPTYS = 40, B_FULLT = 256  , B_CONS = 384  , B_E3 = 472, B_E0 = 480, B_E1 = 488, B_E2 = 496, B_EPI = 504, B_CS = 160,
              B_KVDONE = 168  , B_ODONE = 176, B_XDONE = 184, B_OH1 = 192, B_CS2 = 208, B_XH0 = 232, B_R0 = 240, B_CB = 144  , B_XOLD2 = 216, B_FLG = 64  ;
constexpr uint64_t BAR_CNT = 0x1c07fc0eac00a800ull;
constexpr uint64_t WO_A0 = 0xba76218762187643ull, WO_B0 = 0x9540395403ba9021ull, WO_A1 = 0xba713257132576abull, WO_B1 = 0x9506489064890132ull;
constexpr uint64_t WO_DA0 = 0xa9876543210edd00ull, WO_DB0 = 0xa987654321bbccccull, WO_DA1 = 0xa9876543210fff00ull, WO_DB1 = 0xa98765432bbcccddull;
constexpr int XS = 10;

#define PL 2
#define PROFX(i) PROFT(tid_ == 128 && layer == PL, 200 + (i))
#define PSL 20
#define EP 5
#define DRY 0
#define NCOM 3
#define CSLP 128
#define PFS 8
#define KVTH 0x41700000u
#define CSW 1
#define RL 3
#define ORD 1
#define XB2 2
#define PMOD 3
#define DB1 2
#define NLAYERS 4
constexpr float L2E = 1.4426950408889634f;
#define PHI_MAX 2147483648.f

#define D128(lo) desc64(lo, 0x40000040u)
struct Ctx { uint32_t sb; int g, rb, cu; bf16* out; };

__device__ __forceinline__ void colsum(const CUtensorMap* tm, float* cs, int rb, int g, int w0, int dw, int lane, uint32_t stg, uint32_t cb, uint32_t par) {
  const uint32_t src = stg + (lane >> 3) * 2048;
#pragma unroll 1
  for (int wi = w0 - dw; wi < 6; wi += dw) {
    float s[8] = {0.f, 0.f, 0.f, 0.f, 0.f, 0.f, 0.f, 0.f};
    if (wi >= 0) {
      mbar_wait_u(cb, par);
      par ^= 1;
#pragma unroll 4
      for (int r = 0; r < 16; ++r) {
        const uint4 v = lds128(src + r * 128 + (((lane ^ r) & 7) << 4));
        s[0] += bf_lo(v.x); s[1] += bf_hi(v.x); s[2] += bf_lo(v.y); s[3] += bf_hi(v.y);
        s[4] += bf_lo(v.z); s[5] += bf_hi(v.z); s[6] += bf_lo(v.w); s[7] += bf_hi(v.w);
      }
#pragma unroll
      for (int i = 0; i < 8; ++i) s[i] += __shfl_xor_sync(0xffffffffu, s[i], 8);
    }
    const int wn = wi + dw;
    if (wn < 6) {
      expect_tx_e(cb, 8192);
      tma_2d_e(stg, tm, (wn >= 4 ? 0 : 1024 + (wn >> 1) * 1024) + g * 128 + (wn & 1) * 64, rb * 64, cb);
    }
    if (wi >= 0) {
#pragma unroll
      for (int i = 0; i < 8; ++i) s[i] += __shfl_xor_sync(0xffffffffu, s[i], 16);
      if (lane < 8) {
        red_add4(cs + g * 384 + (wi * 8 + lane) * 8, s[0], s[1], s[2], s[3]);
        red_add4(cs + g * 384 + (wi * 8 + lane) * 8 + 4, s[4], s[5], s[6], s[7]);
      }
      __syncwarp();
    }
  }
}
#define PHASE_CTX() \
  uint32_t sb = c.sb; asm volatile("" : "+r"(sb)); \
  int tid_ = threadIdx.x; asm volatile("" : "+r"(tid_)); \
  const uint32_t bar = sb + SM_BAR; \
  const int lane = tid_ & 31, cw = (tid_ >> 5) - 4, wg = cw >> 2, wq = cw & 3, gq = lane >> 2, t = lane & 3, wrow0 = cw * 16; \
  const int lrow = (lane & 7) + ((lane >> 3) & 1) * 8, lchk = lane >> 4; \
  const bool elected = (tid_ & 127) == 0; \
  const uint32_t rowo = (wrow0 + lrow) * 128, X = (lchk ^ (lane & 7)) << 4; \
  (void)bar; (void)wq; (void)gq; (void)lrow; (void)lchk; (void)elected; (void)wrow0; (void)wg; (void)rowo; (void)X; (void)t;

__device__ __forceinline__ void slab_out_half(uint32_t slot, bf16* dst, int wrow0, int lane, bool FENCE = false) {
  const int r0 = lane >> 3, ch = lane & 7;
  const uint32_t src = slot + (wrow0 + r0) * 128;
  uint4 v[4];
#pragma unroll
  for (int i = 0; i < 4; ++i) v[i] = lds128(src + i * 512 + (((ch ^ (4 * i + r0)) & 7) << 4));
  if (FENCE) fence_async_smem();
  dst += (size_t)(wrow0 + r0) * D_ + ch * 8;
#pragma unroll
  for (int i = 0; i < 4; ++i)
    asm volatile("st.global.v4.u32 [%0], {%1,%2,%3,%4};" ::"l"(dst + (size_t)i * 4 * D_), "r"(v[i].x), "r"(v[i].y), "r"(v[i].z), "r"(v[i].w) : "memory");
}

template <int O>
__device__ __forceinline__ void phi_proj(float (&p)[2][4][4], const uint32_t (&kq)[64], uint32_t wa) {
#pragma unroll
  for (int h = 0; h < 2; ++h)
#pragma unroll
    for (int i = 0; i < 4; ++i) { p[h][i][0] = p[h][i][1] = p[h][i][2] = p[h][i][3] = 0.f; }
#pragma unroll
  for (int ks = 0; ks < 2; ++ks)
#pragma unroll
    for (int np = 0; np < 2; ++np)
#pragma unroll
      for (int h = 0; h < 2; ++h) {
        uint32_t b0, b1, b2, b3;
        ldsm_x4_t(b0, b1, b2, b3, wa + h * 2560 + ks * 1280 + np * 32);
        mma_bf16(p[h][2 * np], kq[O + 8 * h + 4 * ks], kq[O + 8 * h + 4 * ks + 1], kq[O + 8 * h + 4 * ks + 2], kq[O + 8 * h + 4 * ks + 3], b0, b1);
        mma_bf16(p[h][2 * np + 1], kq[O + 8 * h + 4 * ks], kq[O + 8 * h + 4 * ks + 1], kq[O + 8 * h + 4 * ks + 2], kq[O + 8 * h + 4 * ks + 3], b2, b3);
      }
}
__device__ __forceinline__ void phi_exp(uint32_t (&raw)[4][4], const float (&p)[4][4], float sc0, float sc1) {
#pragma unroll
  for (int i = 0; i < 4; ++i) {
    const float e0 = ex2(p[i][0] * sc0), e1 = ex2(p[i][1] * sc0), e2 = ex2(p[i][2] * sc1), e3 = ex2(p[i][3] * sc1);
    const float m0 = e0 * e1, m1 = e2 * e3, rr = rcp(m0 * m1), r0 = rr * m1, r1 = rr * m0;
    raw[i >> 1][(i & 1) * 2] = pack_bf16(e0, e1);
    raw[i >> 1][(i & 1) * 2 + 1] = pack_bf16(e2, e3);
    raw[2 + (i >> 1)][(i & 1) * 2] = pack_bf16(e1 * r0, e0 * r0);
    raw[2 + (i >> 1)][(i & 1) * 2 + 1] = pack_bf16(e3 * r1, e2 * r1);
  }
}
#define FENCE_P(h) _Pragma("unroll") for (int i_ = 0; i_ < 16; ++i_) asm volatile("" : "+f"(p[h][i_ >> 2][i_ & 3]) :: "memory")
#define FENCE_RAW(h) _Pragma("unroll") for (int i_ = 0; i_ < 16; ++i_) asm volatile("" : "+r"(raw[h][i_ >> 2][i_ & 3]) :: "memory")
template <int O>
__device__ __forceinline__ void phi_norm(uint32_t (&ph)[2][4][4], const uint32_t (&raw)[2][4][4], const uint32_t (&kq)[64], uint32_t wa,
                                         float sc0, float sc1, float mul0, float mul1) {
  bool bad = false;
#pragma unroll
  for (int h = 0; h < 2; ++h)
#pragma unroll
    for (int sg = 0; sg < 2; ++sg) {
      float ss[4] = {0.f, 0.f, 0.f, 0.f};
#pragma unroll
      for (int ks = 0; ks < 2; ++ks)
        mma_bf16(ss, raw[h][2 * sg + ks][0], raw[h][2 * sg + ks][1], raw[h][2 * sg + ks][2], raw[h][2 * sg + ks][3], 0x3F803F80u, 0x3F803F80u);
      bad = bad || !(ss[0] < PHI_MAX) || !(ss[2] < PHI_MAX);
      const uint32_t iv = pack_bf16(rcp(ss[0]) * mul0, rcp(ss[2]) * mul1);
#pragma unroll
      for (int ks = 0; ks < 2; ++ks)
#pragma unroll
        for (int j = 0; j < 4; ++j) ph[h][2 * sg + ks][j] = mul_bf16x2(raw[h][2 * sg + ks][j], iv, j & 1);
    }
  if (__builtin_expect(__any_sync(0xffffffffu, bad), 0)) {
#pragma unroll 1
    for (int it = 0; it < 4; ++it) {
      float q[4][4];
#pragma unroll
      for (int i = 0; i < 4; ++i) { q[i][0] = q[i][1] = q[i][2] = q[i][3] = 0.f; }
#pragma unroll
      for (int ks = 0; ks < 2; ++ks) {
        uint32_t a[4];
#pragma unroll
        for (int j = 0; j < 4; ++j) a[j] = (it & 2) ? kq[O + 8 + 4 * ks + j] : kq[O + 4 * ks + j];
#pragma unroll
        for (int np = 0; np < 2; ++np) {
          uint32_t b0, b1, b2, b3;
          ldsm_x4_t(b0, b1, b2, b3, wa + (it >> 1) * 2560 + ks * 1280 + np * 32);
          mma_bf16(q[2 * np], a[0], a[1], a[2], a[3], b0, b1);
          mma_bf16(q[2 * np + 1], a[0], a[1], a[2], a[3], b2, b3);
        }
      }
      float iv[2];
#pragma unroll
      for (int r = 0; r < 2; ++r) {
        const float sc = (it & 1) ? -(r ? sc1 : sc0) : (r ? sc1 : sc0);
        float mx = -INFINITY, sm = 0.f;
#pragma unroll
        for (int i = 0; i < 8; ++i) { float& v = q[i >> 1][2 * r + (i & 1)]; v *= sc; mx = fmaxf(mx, v); }
        mx = fmaxf(mx, __shfl_xor_sync(0xffffffffu, mx, 1));
        mx = fmaxf(mx, __shfl_xor_sync(0xffffffffu, mx, 2));
#pragma unroll
        for (int i = 0; i < 8; ++i) { float& v = q[i >> 1][2 * r + (i & 1)]; v = ex2(v - mx); sm += v; }
        sm += __shfl_xor_sync(0xffffffffu, sm, 1);
        sm += __shfl_xor_sync(0xffffffffu, sm, 2);
        iv[r] = rcp(sm) * (r ? mul1 : mul0);
      }
#pragma unroll
      for (int i = 0; i < 24; ++i) ph[i >> 4][(i >> 2) & 3][i & 3] = ph[(i + 8) >> 4][((i + 8) >> 2) & 3][i & 3];
#pragma unroll
      for (int i = 0; i < 4; ++i) {
        ph[1][2 + (i >> 1)][(i & 1) * 2] = pack_bf16(q[i][0] * iv[0], q[i][1] * iv[0]);
        ph[1][2 + (i >> 1)][(i & 1) * 2 + 1] = pack_bf16(q[i][2] * iv[1], q[i][3] * iv[1]);
      }
    }
  }
}

__device__ __forceinline__ void stats_out(float s0, float s1, float q0, float q1, float2* dst, int t) {
  const bool od = t & 1;
  float sa = od ? s1 : s0, qa = od ? q1 : q0;
  sa += __shfl_xor_sync(0xffffffffu, od ? s0 : s1, 1);
  qa += __shfl_xor_sync(0xffffffffu, od ? q0 : q1, 1);
  sa += __shfl_xor_sync(0xffffffffu, sa, 2);
  qa += __shfl_xor_sync(0xffffffffu, qa, 2);
  if (t < 2) red_add2(&dst[t * 8].x, sa, qa);
}

__device__ __forceinline__ void consumer(const Ctx& c) {
  const int g = c.g, m0 = c.rb * 128;
  float acc[192];
#define X_H1() \
      _Pragma("unroll") for (int jp = 4; jp < 8; ++jp) \
        stsm_x4(sb + (XS + 1) * SLOT + rowo + (X ^ ((jp & 3) << 5)), \
                pack_bf16(acc[128 + 8 * jp], acc[129 + 8 * jp]), pack_bf16(acc[130 + 8 * jp], acc[131 + 8 * jp]), \
                pack_bf16(acc[132 + 8 * jp], acc[133 + 8 * jp]), pack_bf16(acc[134 + 8 * jp], acc[135 + 8 * jp]));
#pragma unroll
  for (int i = 128; i < 192; ++i) acc[i] = 0.f;
#pragma unroll 1
  for (int layer = 0;; ++layer) {
    {
      PHASE_CTX();
      const uint32_t wu = c.cu >> 2;
      const uint32_t dA0 = (((sb + wu * 8192) & 0x3FFFF) >> 4) | (1u << 16), dB0 = ((sb & 0x3FFFF) >> 4) | (512u << 16);
      {
        PROFX(0);
        mbar_wait(bar + B_FULLS, 0);
        PROFX(1);
        wgmma_fence();
        wgmma_n256_0(acc, D128(dA0 + XS * 1024), D128(dB0 + 2048));
#pragma unroll
        for (int k = 1; k < 4; ++k) wgmma_n256(acc, D128(dA0 + XS * 1024 + k * 2), D128(dB0 + 2048 + k * 128), 1);
        wgmma_commit();
        wgmma_wait<1>();
        float s0 = 0.f, s1 = 0.f, q0 = 0.f, q1 = 0.f;
        if (layer) {
          X_H1();
#pragma unroll
          for (int i = 128; i < 192; i += 4) {
            s0 += acc[i] + acc[i + 1]; s1 += acc[i + 2] + acc[i + 3];
            q0 = fmaf(acc[i], acc[i], fmaf(acc[i + 1], acc[i + 1], q0)); q1 = fmaf(acc[i + 2], acc[i + 2], fmaf(acc[i + 3], acc[i + 3], q1));
          }
        }
        asm volatile("" : "+f"(s0), "+f"(s1), "+f"(q0), "+f"(q1) :: "memory");
        wgmma_fence();
        wgmma_n128_0(acc, D128(dA0 + XS * 1024), D128(dB0 + 1024));
#pragma unroll
        for (int k = 1; k < 4; ++k) wgmma_n128(acc, D128(dA0 + XS * 1024 + k * 2), D128(dB0 + 1024 + k * 128), 1);
        wgmma_commit();
        if (layer) {
          PHASE_CTX();
          fence_async_smem();
          nbar_dyn(3 + wu, 128);
          stats_out(s0, s1, q0, q1, g_stats + layer * S_ + m0 + wrow0 + gq, t);
          PROFT(tid_ == 128, layer * 16 + 8);
        }
      }
      uint32_t s = 1, u = 0, sp = 0;
      const int ix = layer ? 1 : 2 * min(g, NCOM) + 1;
#pragma unroll 1
      for (int i = 1; i < 14; ++i) {
        mbar_wait(bar + B_FULLS + s * 8, (u + (s ? layer : 0)) & 1);
        const uint32_t da = dA0 + ((QA >> (4 * s)) & 15) * 1024, dk = dB0 + ((QK >> (4 * s)) & 15) * 1024,
                       dq = dB0 + ((QQ >> (4 * s)) & 15) * 1024;
        wgmma_fence();
#pragma unroll
        for (int k = 0; k < 4; ++k) {
          wgmma_n256(acc, D128(da + k * 2), D128(dk + k * 128), 1);
          wgmma_n128(acc, D128(da + k * 2), D128(dq + k * 128), 1);
        }
        wgmma_commit();
        if (i == ix || (i == ix + 1 && !layer)) {
          PHASE_CTX();
          if (layer) {
            slab_out_half(sb + (XS + 1) * SLOT, g_x + (size_t)m0 * D_ + g * 128 + 64, wrow0, lane);
          } else {
            float s0 = 0.f, s1 = 0.f, q0 = 0.f, q1 = 0.f;
            const uint32_t xa = sb + ((QA >> (4 * sp)) & 15) * SLOT + rowo;
#pragma unroll
            for (int jp = 0; jp < 4; ++jp) {
              uint32_t x0, x1, x2, x3;
              ldsm_x4(x0, x1, x2, x3, xa + (X ^ (jp << 5)));
              s0 += (bf_lo(x0) + bf_hi(x0)) + (bf_lo(x2) + bf_hi(x2));
              s1 += (bf_lo(x1) + bf_hi(x1)) + (bf_lo(x3) + bf_hi(x3));
              q0 = fmaf(bf_lo(x0), bf_lo(x0), fmaf(bf_hi(x0), bf_hi(x0), fmaf(bf_lo(x2), bf_lo(x2), fmaf(bf_hi(x2), bf_hi(x2), q0))));
              q1 = fmaf(bf_lo(x1), bf_lo(x1), fmaf(bf_hi(x1), bf_hi(x1), fmaf(bf_lo(x3), bf_lo(x3), fmaf(bf_hi(x3), bf_hi(x3), q1))));
            }
            stats_out(s0, s1, q0, q1, g_stats + m0 + wrow0 + gq, t);
          }
          __syncwarp();
          if (lane == 0 && (layer || i != ix)) mbar_arrive(bar + B_XDONE);
          nbar_dyn(3 + wu, 128);
        }
        wgmma_wait<1>();
        if (elected) release2(bar + B_EMPTYS + sp * 8);
        sp = s;
        if (++s == 3) { s = 0; ++u; }
      }
      {
        const uint64_t dap = make_desc_ns(sb + SM_AP + wu * 1024, 0, 128), dbp = make_desc_ns(sb + SM_BP + (layer & 1) * 6144, 0, 128);
        if (wu == 0) {
          wgmma_wait<0>();
          if (elected) mbar_arrive(bar + B_R0);
          nbar<6, 256>();
        }
        if (layer < 2) mbar_wait(bar + (layer ? B_CS2 : B_CS), 0);
        mbar_wait(bar + B_STAT, layer & 1);
        mbar_wait(bar + B_FULLS + 16, layer & 1);
        wgmma_fence();
        wgmma_n256_k(acc, dap, dbp, 1);
#pragma unroll
        for (int k = 0; k < 4; ++k) wgmma_n256(acc, D128(dA0 + (QA >> 8) * 1024 + k * 2), D128(dB0 + (QK >> 8) * 1024 + k * 128), 1);
        mbar_wait(bar + B_FULLS, 1);
        PROFT(tid_ == 128, layer * 16 + 9);
        wgmma_fence();
#pragma unroll
        for (int k = 0; k < 4; ++k) wgmma_n256(acc, D128(dA0 + (QA & 15) * 1024 + k * 2), D128(dB0 + (QK & 15) * 1024 + k * 128), 1);
        wgmma_commit();
        if (wu) nbar<6, 256>();
#define Q_TAIL() \
        wgmma_n128_k(acc, dap, dbp + 256, 1); \
        _Pragma("unroll") for (int k = 0; k < 4; ++k) wgmma_n128(acc, D128(dA0 + (QA >> 8) * 1024 + k * 2), D128(dB0 + (QQ >> 8) * 1024 + k * 128), 1); \
        _Pragma("unroll") for (int k = 0; k < 4; ++k) wgmma_n128(acc, D128(dA0 + (QA & 15) * 1024 + k * 2), D128(dB0 + (QQ & 15) * 1024 + k * 128), 1);
        Q_TAIL();
        wgmma_commit();
        wgmma_wait<1>();
#pragma unroll
        for (int i = 0; i < 128; ++i) asm volatile("" : "+f"(acc[i]) :: "memory");
      }
    }
    uint32_t xo[32];
    {
      PHASE_CTX();
      PROFT(tid_ == 128, layer * 16 + 1);
      const bool isB = layer & 1;
      const int cu = c.cu;
      if (cu >= 4) asm volatile("bar.arrive 7, 256;" ::: "memory");
      if (elected && cu == 4) mbar_arrive(bar + B_R0);
      uint32_t kq[64];
      const uint32_t rowq = rowo & 8191;
      const float rs0 = lds_f(sb + SM_RS + (16 + wrow0 + gq) * 4), rs1 = lds_f(sb + SM_RS + (24 + wrow0 + gq) * 4);
#define Q_DONE() \
      wgmma_wait<0>(); \
      if (lane == 0) release2(bar + B_E0); \
      _Pragma("unroll") for (int i = 128; i < 192; ++i) asm volatile("" : "+f"(acc[i]) :: "memory"); \
      _Pragma("unroll") for (int i = 0; i < 32; ++i) kq[32 + i] = pack_bf16(acc[128 + 2 * i], acc[129 + 2 * i]);
      if (isB) {
        if (cu == 0) asm volatile("bar.arrive 10, 64;" ::: "memory");
        if (elected) release2(bar + B_E1);
        const int e = gq & 1;
        const bool sel = t > (gq >> 1);
        const uint32_t rja = sb + SM_RS + (wrow0 + 2 * t + e) * 4;
        const float rjA0 = lds_f(rja + 32), rjA1 = lds_f(rja + 64), rjB0 = lds_f(rja + (sel ? 0 : 64)), rjB1 = lds_f(rja + (sel ? 32 : 96));
        uint32_t vv[32];
#pragma unroll
        for (int i = 0; i < 16; ++i) { kq[i] = pack_bf16(acc[2 * i], acc[2 * i + 1]); vv[i] = pack_bf16(acc[64 + 2 * i], acc[65 + 2 * i]); }
        const uint32_t rB = sb + 4 * SLOT + wg * 4 * KVT + rowq;
        auto dump = [&](int hp) {
          const uint32_t kb = rB + 2048 + (hp ^ wg) * 2 * KVT;
#pragma unroll
          for (int jp = 0; jp < 4; ++jp) {
            stsm_x4(kb + (X ^ (jp << 5)), kq[16 * hp + 4 * jp], kq[16 * hp + 4 * jp + 1], kq[16 * hp + 4 * jp + 2], kq[16 * hp + 4 * jp + 3]);
            stsm_x4(kb + KVT + (X ^ (jp << 5)), vv[16 * hp + 4 * jp], vv[16 * hp + 4 * jp + 1], vv[16 * hp + 4 * jp + 2], vv[16 * hp + 4 * jp + 3]);
          }
          if (cu == 3) {
            const uint32_t kd = rB + 2048 + 32768 + (1 - hp) * 2 * KVT;
#pragma unroll
            for (int jp = 0; jp < 4; ++jp) {
              stsm_x4(kd + (X ^ (jp << 5)), kq[16 * hp + 4 * jp], kq[16 * hp + 4 * jp + 1], kq[16 * hp + 4 * jp + 2], kq[16 * hp + 4 * jp + 3]);
              stsm_x4(kd + KVT + (X ^ (jp << 5)), vv[16 * hp + 4 * jp], vv[16 * hp + 4 * jp + 1], vv[16 * hp + 4 * jp + 2], vv[16 * hp + 4 * jp + 3]);
            }
            if (hp) asm volatile("bar.arrive 15, 64;" ::: "memory"); else asm volatile("bar.arrive 9, 64;" ::: "memory");
          }
          asm volatile("bar.arrive %0, 224;" :: "r"(hp ? 13 + (cu >> 2) : 8 + (cu & 4)) : "memory");
        };
        uint4* const hbuf = g_halo + ((c.rb * 8 + g) * 2 + (layer >> 1)) * 512 + lane;
        if (cu < 4) {
          nbar<7, 256>();
          dump(0);
        }
#pragma unroll
        for (int i = 16; i < 32; ++i) { kq[i] = pack_bf16(acc[2 * i], acc[2 * i + 1]); vv[i] = pack_bf16(acc[64 + 2 * i], acc[65 + 2 * i]); }
        if (cu >= 4) {
          if (cu == 7) {
#pragma unroll
            for (int jp = 0; jp < 8; ++jp) {
              st_relaxed4(hbuf + jp * 32, ~kq[4 * jp], ~kq[4 * jp + 1], ~kq[4 * jp + 2], ~kq[4 * jp + 3]);
              st_relaxed4(hbuf + 256 + jp * 32, ~vv[4 * jp], ~vv[4 * jp + 1], ~vv[4 * jp + 2], ~vv[4 * jp + 3]);
            }
          }
          dump(0);
          dump(1);
        }
        PROFT(tid_ == 128, layer * 16 + 2);
        constexpr float SC = 0.17677669529663687f * L2E;
        const float fA0 = rjA0 * rs0 * SC, fB0 = rjB0 * rs0 * SC, fA1 = rjA1 * rs1 * SC, fB1 = rjB1 * rs1 * SC;
        const float bA0 = (m0 + wrow0) ? 0.f : -1e30f, bB = sel ? bA0 : 0.f;
        const uint32_t pA_ = e ? 0x1044u : 0x4410u, pB_ = e ? 0x3244u : 0x4432u, pLo = sel ? pB_ : 0x4444u, pHi = sel ? 0x4444u : pB_;
        const uint32_t KX = ((lane >> 3) ^ (lane & 7)) << 4;
        Q_DONE();
        if (cu == 0) {
          nbar<11, 64>();
        } else if (cu == 4) {
          uint4 hv[16];
          if (c.rb > 0) {
            uint32_t n = 0;
#pragma unroll 1
            while (true) {
              uint32_t mn = 0xFFFFFFFFu;
#pragma unroll
              for (int i = 0; i < 16; ++i) hv[i] = ld_relaxed4(hbuf - 16 * 512 + i * 32);
#pragma unroll
              for (int i = 0; i < 16; ++i) mn = __vimin3_u32(__vimin3_u32(mn, hv[i].x, hv[i].y), hv[i].z, hv[i].w);
              if (__all_sync(0xffffffffu, mn != 0u)) break;
              if (++n > (1u << 20)) { g_err = 4u; break; }
            }
          } else {
#pragma unroll
            for (int i = 0; i < 16; ++i) hv[i] = make_uint4(~0u, ~0u, ~0u, ~0u);
          }
          nbar<10, 64>();
#pragma unroll
          for (int i = 0; i < 16; ++i)
            stsm_x4(rB - 4 * KVT + (((i >> 2) & 1) * 2 + (i >> 3)) * KVT + (X ^ ((i & 3) << 5)), ~hv[i].x, ~hv[i].y, ~hv[i].z, ~hv[i].w);
          asm volatile("bar.arrive 11, 64;" ::: "memory");
          nbar<9, 64>();
        } else {
          nbar_dyn(8 + (cu & 4), 224);
        }
        PROFT(tid_ == 128, layer * 16 + 5);
        PROFT(lane == 0 && layer == PL, 136 + cw);
        auto attend = [&](int hp) {
          const uint32_t qad = sb + (XS + 1 - hp) * SLOT + rowo, kt = rB + 2 * (hp ^ wg) * KVT - (lane & 8) * 128, vt = rB + (2 * (hp ^ wg) + 1) * KVT;
          __syncwarp();
          uint32_t kb[2][2][4], vb[2][2][2][4];
#pragma unroll
          for (int h = 0; h < 2; ++h)
#pragma unroll
            for (int nt = 0; nt < 2; ++nt) ldsm_x4(kb[h][nt][0], kb[h][nt][1], kb[h][nt][2], kb[h][nt][3], kt + nt * 1024 + (KX ^ (h << 6)));
#pragma unroll
          for (int ks = 0; ks < 2; ++ks)
#pragma unroll
            for (int np = 0; np < 2; ++np)
#pragma unroll
              for (int h = 0; h < 2; ++h)
                ldsm_x4_t(vb[h][ks][np][0], vb[h][ks][np][1], vb[h][ks][np][2], vb[h][ks][np][3], vt + ks * 2048 + (X ^ (h << 6) ^ (np << 5)));
          if (hp == 0 && lane == 0) release2(bar + B_E3);
          if (DB1 == 1 && hp == 0 && cu < 4) dump(1);
          float la[2][2], lb[2][2], mx[2][2], sm[2][2];
#pragma unroll
          for (int h = 0; h < 2; ++h) {
            const int qo = 32 + 16 * hp + 8 * h, ko = 16 * hp + 8 * h;
            float sc[4][4];
#pragma unroll
            for (int nt = 0; nt < 4; ++nt) {
              sc[nt][0] = sc[nt][1] = sc[nt][2] = sc[nt][3] = 0.f;
#pragma unroll
              for (int ks = 0; ks < 2; ++ks)
                mma_bf16(sc[nt], kq[qo + 4 * ks], kq[qo + 4 * ks + 1], kq[qo + 4 * ks + 2], kq[qo + 4 * ks + 3],
                         nt < 2 ? kb[h][nt & 1][2 * ks] : kq[ko + 4 * ks + (nt & 1)], nt < 2 ? kb[h][nt & 1][2 * ks + 1] : kq[ko + 4 * ks + 2 + (nt & 1)]);
            }
            la[h][0] = fmaf(e ? sc[1][1] : sc[1][0], fA0, bA0);
            lb[h][0] = fmaf(sel ? (e ? sc[0][1] : sc[0][0]) : (e ? sc[2][1] : sc[2][0]), fB0, bB);
            la[h][1] = (e ? sc[2][3] : sc[2][2]) * fA1;
            lb[h][1] = fmaf(sel ? (e ? sc[1][3] : sc[1][2]) : (e ? sc[3][3] : sc[3][2]), fB1, bB);
            mx[h][0] = fmaxf(la[h][0], lb[h][0]); mx[h][1] = fmaxf(la[h][1], lb[h][1]);
          }
#pragma unroll
          for (int o = 1; o <= 2; o <<= 1)
#pragma unroll
            for (int h = 0; h < 2; ++h)
#pragma unroll
              for (int r = 0; r < 2; ++r) mx[h][r] = fmaxf(mx[h][r], __shfl_xor_sync(0xffffffffu, mx[h][r], o));
          float oa[2][4][4];
#pragma unroll
          for (int h = 0; h < 2; ++h) {
#pragma unroll
            for (int r = 0; r < 2; ++r) { la[h][r] = ex2(la[h][r] - mx[h][r]); lb[h][r] = ex2(lb[h][r] - mx[h][r]); sm[h][r] = la[h][r] + lb[h][r]; }
            const uint32_t p0 = pack_bf16(la[h][0] * rjA0, lb[h][0] * rjB0), p1 = pack_bf16(la[h][1] * rjA1, lb[h][1] * rjB1);
            const uint32_t a00 = __byte_perm(p0, 0u, pLo), a02 = __byte_perm(p0, 0u, pA_), a03 = __byte_perm(p1, 0u, pLo);
            const uint32_t a10 = __byte_perm(p0, 0u, pHi), a11 = __byte_perm(p1, 0u, pA_), a13 = __byte_perm(p1, 0u, pHi);
#pragma unroll
            for (int i = 0; i < 4; ++i) {
              oa[h][i][0] = oa[h][i][1] = oa[h][i][2] = oa[h][i][3] = 0.f;
              mma_bf16(oa[h][i], a00, 0u, a02, a03, vb[h][0][i >> 1][2 * (i & 1)], vb[h][0][i >> 1][2 * (i & 1) + 1]);
              mma_bf16(oa[h][i], a10, a11, 0u, a13, vb[h][1][i >> 1][2 * (i & 1)], vb[h][1][i >> 1][2 * (i & 1) + 1]);
            }
          }
#pragma unroll
          for (int o = 1; o <= 2; o <<= 1)
#pragma unroll
            for (int h = 0; h < 2; ++h)
#pragma unroll
              for (int r = 0; r < 2; ++r) sm[h][r] += __shfl_xor_sync(0xffffffffu, sm[h][r], o);
          mbar_wait(bar + (hp ? B_XOLD2 : B_XOLD), 1);
#pragma unroll
          for (int jp = 0; jp < 4; ++jp) ldsm_x4(xo[16 * hp + 4 * jp], xo[16 * hp + 4 * jp + 1], xo[16 * hp + 4 * jp + 2], xo[16 * hp + 4 * jp + 3], qad + (X ^ (jp << 5)));
#pragma unroll
          for (int h = 0; h < 2; ++h) {
            const float i0 = rcp(sm[h][0]), i1 = rcp(sm[h][1]);
#pragma unroll
            for (int np = 0; np < 2; ++np)
              stsm_x4(qad + (X ^ (h << 6) ^ (np << 5)),
                      pack_bf16(oa[h][2 * np][0] * i0, oa[h][2 * np][1] * i0), pack_bf16(oa[h][2 * np][2] * i1, oa[h][2 * np][3] * i1),
                      pack_bf16(oa[h][2 * np + 1][0] * i0, oa[h][2 * np + 1][1] * i0), pack_bf16(oa[h][2 * np + 1][2] * i1, oa[h][2 * np + 1][3] * i1));
          }
          __syncwarp();
          slab_out_half(sb + (XS + 1 - hp) * SLOT, g_o + (size_t)m0 * D_ + g * 128 + hp * 64, wrow0, lane, hp);
          __syncwarp();
          if (lane == 0) mbar_arrive(bar + (hp ? B_ODONE : B_OH1));
          PROFT(lane == 0 && layer == PL && hp == 0, 128 + cw);
        };
        attend(0);
        if (DB1 == 2 && cu < 4) dump(1);
        if (cu == 4) nbar<15, 64>();
        else if (cu != 0) nbar_dyn(13 + (cu >> 2), 224);
        attend(1);
      } else {
#pragma unroll
        for (int i = 0; i < 32; ++i) kq[i] = pack_bf16(acc[2 * i], acc[2 * i + 1]);
        if (cu < 4) nbar<7, 256>();
        {
          const uint32_t vb = sb + (5 + 3 * wg) * SLOT + (rowq >> 1) + ((lchk ^ ((lane & 7) >> 1)) << 4);
#pragma unroll
          for (int jp = 8; jp < 16; ++jp)
            stsm_x4((vb ^ ((jp & 1) << 5)) + ((jp >> 1) & 3) * 4096,
                    pack_bf16(acc[8 * jp], acc[8 * jp + 1]), pack_bf16(acc[8 * jp + 2], acc[8 * jp + 3]),
                    pack_bf16(acc[8 * jp + 4], acc[8 * jp + 5]), pack_bf16(acc[8 * jp + 6], acc[8 * jp + 7]));
        }
        PROFT(tid_ == 128, layer * 16 + 2);
        Q_DONE();
        const uint32_t pA = sb + (3 + 3 * wg) * SLOT + (rowo & 8191);
        float sc0 = rs0 * L2E, sc1 = rs1 * L2E;
        const uint32_t wa0 = sb + SM_WPHI + lrow * 80 + lchk * 16;
        const uint32_t wu = c.cu >> 2, par = (layer >> 1) & 1;
        float p[2][4][4];
        uint32_t raw[2][4][4], ph[2][4][4];
        float kva[20], oa[2][20];
        auto kv_start = [&](int hp) {
#pragma unroll
          for (int h = 0; h < 2; ++h)
#pragma unroll
            for (int cp = 0; cp < 4; ++cp)
              stsm_x4(pA + hp * 16384 + h * 8192 + (X ^ (cp << 5)), ph[h][cp][0], ph[h][cp][1], ph[h][cp][2], ph[h][cp][3]);
          PROFT(tid_ == 128, layer * 16 + 11);
          fence_async_smem();
          nbar<1, 256>();
          const uint32_t hu = 2 * hp + wu;
          const uint32_t dP = (((sb + 3 * SLOT + hu * 8192) & 0x3FFFF) >> 4) | (512u << 16);
          const uint32_t dV = (((sb + 5 * SLOT + hu * 4096) & 0x3FFFF) >> 4) | (((SM_SD - 5 * SLOT - hu * 4096) >> 4) << 16);
          wgmma_fence();
#pragma unroll
          for (int ks = 0; ks < 8; ++ks)
            wgmma_n40_tt(kva, desc64(dP + (ks >> 2) * 3072 + (ks & 3) * 128, 0x40000040u),
                         desc64(dV + (ks >> 2) * (3072u - (2816u << 16)) + (ks & 3) * 64, 0x80000020u), ks != 0);
          wgmma_commit();
        };
        auto kv_end = [&](int hp) {
          wgmma_wait<0>();
#pragma unroll
          for (int i = 0; i < 20; ++i) asm volatile("" : "+f"(kva[i]) :: "memory");
          nbar_dyn(3 + wu, 128);
          PROFT(tid_ == 128, layer * 16 + 12);
          const bool od = lane & 1;
#pragma unroll
          for (int i = 0; i < 4; ++i)
            sts128(sb + (3 + hp) * SLOT + (cw * 128 + i * 32 + lane) * 16,
                   make_uint4(__float_as_uint(kva[4 * i]), __float_as_uint(kva[4 * i + 1]), __float_as_uint(kva[4 * i + 2]),
                              __float_as_uint(od == (i >= 2) ? 1.f : kva[4 * i + 3])));
          sts128(sb + (6 + hp) * SLOT + wg * 8192 + (wq * 32 + lane) * 16,
                 make_uint4(__float_as_uint(od ? kva[11] : kva[3]), __float_as_uint(od ? kva[15] : kva[7]), __float_as_uint(od ? kva[18] : kva[16]), __float_as_uint(1.f)));
          fence_async_smem();
          __syncwarp();
          if (lane == 0) mbar_arrive(bar + B_KVDONE - hp * 32);
          PROFT(tid_ == 128, layer * 16 + 3);
        };
        const uint4* const kvg = g_kv + (g * 2 + (layer >> 1)) * 2560 + cw * 128 + lane;
        uint4 u[5];
        auto kv_load = [&](int hp) {
#pragma unroll
          for (int i = 0; i < 4; ++i) u[i] = ld_relaxed4(kvg + hp * 1280 + i * 32);
          u[4] = ld_relaxed4(kvg + hp * 1280 + 1024 - cw * 96);
        };
        auto o_start = [&](int hp, const uint32_t (&pq)[2][4][4]) {
          PROFT(tid_ == 128 && hp == 0, layer * 16 + 10);
          if (hp == 0) mbar_wait(bar + B_KVDONE - 32, par);
          const bool od = lane & 1;
          uint32_t n = 0;
#pragma unroll 1
          while (!__all_sync(0xffffffffu, (od ? u[2].w : u[0].w) == 0x41800000u && (od ? u[3].w : u[1].w) == 0x41800000u && u[4].w == 0x41800000u)) {
#pragma unroll 1
            while (__any_sync(0xffffffffu, u[4].w < KVTH) && ++n < (1u << 20)) u[4].w = ld_relaxed(&kvg[hp * 1280 + 1024 - cw * 96].w);
            if (++n > (1u << 20)) { g_err = 6u; break; }
            kv_load(hp);
          }
          PROFT(tid_ == 128 && hp == 0, layer * 16 + 5);
          if (!od) { u[0].w = u[4].x; u[1].w = u[4].y; } else { u[2].w = u[4].x; u[3].w = u[4].y; }
#pragma unroll
          for (int i = 0; i < 4; i += 2)
            stsm_x4(sb + (5 + 3 * hp) * SLOT + rowo + (X ^ ((i & 2) << 4)),
                    pack_bf16(__uint_as_float(u[i].x), __uint_as_float(u[i].y)), pack_bf16(__uint_as_float(u[i].z), __uint_as_float(u[i].w)),
                    pack_bf16(__uint_as_float(u[i + 1].x), __uint_as_float(u[i + 1].y)), pack_bf16(__uint_as_float(u[i + 1].z), __uint_as_float(u[i + 1].w)));
          const uint32_t z2 = pack_bf16(__uint_as_float(u[4].z), __uint_as_float(u[4].z));
          if (t < 2) sts128(sb + (5 + 3 * hp) * SLOT + (wrow0 + gq + 8 * t) * 128 + ((4 ^ gq) << 4), make_uint4(z2, z2, z2, z2));
          fence_async_smem();
          nbar<1, 256>();
          PROFT(tid_ == 128 && hp == 1, layer * 16 + 4);
          const uint32_t dK = (((sb + (5 + 3 * hp) * SLOT) & 0x3FFFF) >> 4) | (512u << 16);
          wgmma_fence();
#pragma unroll
          for (int ks = 0; ks < 4; ++ks) {
#pragma unroll
            for (int hh = 0; hh < 2; ++hh) wgmma_n40_rs(oa[hh], pq[hh][ks], D128(dK + hh * 512 + ks * 128), ks != 0);
          }
          wgmma_commit();
        };
        auto o_end = [&](int hp) {
          wgmma_wait<0>();
#pragma unroll
          for (int i = 0; i < 20; ++i) asm volatile("" : "+f"(oa[0][i]), "+f"(oa[1][i]) :: "memory");
#pragma unroll
          for (int hh = 0; hh < 2; ++hh) {
            const float i0 = rcp(oa[hh][16] + 1e-6f), i1 = rcp(oa[hh][18] + 1e-6f);
            const uint32_t qad = sb + (3 + hp) * SLOT + rowo, hx = hh << 6;
#pragma unroll
            for (int np = 0; np < 2; ++np)
              stsm_x4(qad + (X ^ hx ^ (np << 5)),
                      pack_bf16(oa[hh][8 * np] * i0, oa[hh][8 * np + 1] * i0), pack_bf16(oa[hh][8 * np + 2] * i1, oa[hh][8 * np + 3] * i1),
                      pack_bf16(oa[hh][8 * np + 4] * i0, oa[hh][8 * np + 5] * i0), pack_bf16(oa[hh][8 * np + 6] * i1, oa[hh][8 * np + 7] * i1));
          }
          __syncwarp();
          slab_out_half(sb + (3 + hp) * SLOT, g_o + (size_t)m0 * D_ + g * 128 + hp * 64, wrow0, lane, hp);
          __syncwarp();
          if (lane == 0) mbar_arrive(bar + (hp ? B_ODONE : B_OH1));
        };
#define XO_LOAD() \
        mbar_wait(bar + B_XOLD, 0); \
        mbar_wait(bar + B_XOLD2, 0); \
        _Pragma("unroll") for (int jp = 0; jp < 8; ++jp) \
          ldsm_x4(xo[4 * jp], xo[4 * jp + 1], xo[4 * jp + 2], xo[4 * jp + 3], sb + (XS + 1 - (jp >> 2)) * SLOT + rowo + (X ^ ((jp & 3) << 5)));
#define SC_RELOAD() \
        sc0 = __uint_as_float(lds_vol(sb + SM_RS + (16 + wrow0 + gq) * 4)) * L2E; sc1 = __uint_as_float(lds_vol(sb + SM_RS + (24 + wrow0 + gq) * 4)) * L2E;
        __syncwarp();
        phi_proj<0>(p, kq, wa0);
        phi_exp(raw[0], p[0], sc0, sc1);
        phi_exp(raw[1], p[1], sc0, sc1);
        phi_proj<16>(p, kq, wa0 + 5120);
        phi_norm<0>(ph, raw, kq, wa0, sc0, sc1, rs0, rs1);
        kv_start(0);
        phi_exp(raw[0], p[0], sc0, sc1);
        kv_end(0);
        if (RL & 1) { SC_RELOAD(); }
        XO_LOAD();
        phi_exp(raw[1], p[1], sc0, sc1);
        phi_proj<32>(p, kq, wa0);
        phi_norm<16>(ph, raw, kq, wa0 + 5120, sc0, sc1, rs0, rs1);
        kv_start(1);
        if (lane == 0) release2(bar + B_E3);
        phi_exp(raw[0], p[0], sc0, sc1);
        kv_end(1);
        if (RL & 2) { SC_RELOAD(); }
        kv_load(0);
        phi_exp(raw[1], p[1], sc0, sc1);
        phi_proj<48>(p, kq, wa0 + 5120);
        phi_norm<32>(ph, raw, kq, wa0, sc0, sc1, 1.f, 1.f);
        o_start(0, ph);
        phi_exp(raw[0], p[0], sc0, sc1);
        o_end(0);
        SC_RELOAD();
        kv_load(1);
        phi_exp(raw[1], p[1], sc0, sc1);
        phi_norm<48>(ph, raw, kq, wa0 + 5120, sc0, sc1, 1.f, 1.f);
        o_start(1, ph);
        o_end(1);
      }
      __syncwarp();
      PROFT(lane == 0 && layer == PL, 216 + cw);
      if (lane == 0) mbar_arrive(bar + B_EPI);
      PROFT(tid_ == 128, layer * 16 + 6);
    }
    {
      PHASE_CTX();
      const uint32_t wu = c.cu >> 2;
      const uint32_t dA0 = (((sb + wu * 8192) & 0x3FFFF) >> 4) | (1u << 16), dB0 = ((sb & 0x3FFFF) >> 4) | (512u << 16);
#pragma unroll
      for (int i = 0; i < 32; ++i) { acc[128 + 2 * i] = bf_lo(xo[i]); acc[129 + 2 * i] = bf_hi(xo[i]); }
      nbar_dyn(3 + wg, 128);
      uint64_t ta = (layer & 1) ? WO_A1 : WO_A0, tw = (layer & 1) ? WO_B1 : WO_B0;
#pragma unroll 1
      for (int i = 0; i < 16; ++i) {
        bool rel = i > 0 && i < 12;
        if (DRY && rel && !__all_sync(0xffffffffu, mbar_test_wait(bar + B_FULLT + i * 8, layer & 1))) {
          wgmma_wait<0>();
          if (elected) release2(bar + B_CONS + (i - 1) * 8);
          rel = false;
        }
        mbar_wait(bar + B_FULLT + i * 8, layer & 1);
        PROFT(tid_ == 128 && layer == PL, 160 + i);
        const uint32_t da = dA0 + ((uint32_t)ta & 15) * 1024, db = dB0 + ((uint32_t)tw & 15) * 1024;
        ta >>= 4; tw >>= 4;
        wgmma_fence();
#pragma unroll
        for (int k = 0; k < 4; ++k) wgmma_n128(acc, D128(da + k * 2), D128(db + k * 128), 1);
        wgmma_commit();
        if (i == 0) {
          if (elected) {
            release2(bar + B_E2);
          }
        } else {
          wgmma_wait<1>();
          if (elected && rel) release2(bar + B_CONS + (i - 1) * 8);
          if (elected && (unsigned)(i - 13) < 2u && layer + 1 < NLAYERS) release2(bar + B_EMPTYS + (i - 13) * 8);
        }
      }
      const bool last = layer == NLAYERS - 1;
      wgmma_wait<0>();
#pragma unroll
      for (int i = 128; i < 192; ++i) asm volatile("" : "+f"(acc[i]) :: "memory");
      if (elected && !last) release2(bar + B_EMPTYS + 16);
      PROFT(tid_ == 128, layer * 16 + 7);
#pragma unroll
      for (int jp = 0; jp < 4; ++jp)
        stsm_x4(sb + XS * SLOT + rowo + (X ^ (jp << 5)),
                pack_bf16(acc[128 + 8 * jp], acc[129 + 8 * jp]), pack_bf16(acc[130 + 8 * jp], acc[131 + 8 * jp]),
                pack_bf16(acc[132 + 8 * jp], acc[133 + 8 * jp]), pack_bf16(acc[134 + 8 * jp], acc[135 + 8 * jp]));
      if (last) {
        __syncwarp();
        slab_out_half(sb + XS * SLOT, c.out + (size_t)m0 * D_ + g * 128, wrow0, lane);
        X_H1();
        __syncwarp();
        slab_out_half(sb + (XS + 1) * SLOT, c.out + (size_t)m0 * D_ + g * 128 + 64, wrow0, lane);
        __syncwarp();
        if (lane == 0) mbar_arrive(bar + B_XDONE);
        PROFT(tid_ == 128, layer * 16 + 24);
        break;
      }
      __syncwarp();
      slab_out_half(sb + XS * SLOT, g_x + (size_t)m0 * D_ + g * 128, wrow0, lane, true);
      __syncwarp();
      if (lane == 0) mbar_arrive(bar + B_XH0);
      nbar_dyn(3 + wu, 128);
    }
  }
}

__device__ __forceinline__ void flag_fetch(uint32_t bar, uint32_t cp, const unsigned int* f) {
  asm volatile("{\n.reg .pred p;\nelect.sync _|p, 0xffffffff;\n@p mbarrier.expect_tx.relaxed.cta.shared::cta.b64 [%2], 64;\n"
               "@p cp.async.bulk.shared::cluster.global.mbarrier::complete_tx::bytes [%0], [%1], 64, [%2];\n}\n"
               ::"r"(cp), "l"(f), "r"(bar + 128) : "memory");
}
__device__ __forceinline__ void src_wait_async(uint32_t bar, uint32_t cp, const unsigned int* f, unsigned int target, int kb, uint32_t& ready, int lane) {
  uint32_t n = 0;
#pragma unroll 1
  while (true) {
    ready |= __ballot_sync(0xffffffffu, (int)(lds_vol(cp + (lane & 15) * 4) - target) >= 0);
    if ((ready >> kb) & 1) break;
    if (n > (1u << 20)) { g_err = 5u; break; }
    if ((n++ & PMOD) == 0) flag_fetch(bar, cp, f);
    __nanosleep(PSL);
  }
}

__device__ __forceinline__ int kblock0(int i, int g) {
  const int j = i >> 1, p = max(g, NCOM) + j - NCOM;
  return (j < NCOM ? j : p < 8 ? p : p - 8 + NCOM) * 2 + (i & 1);
}

#define WOORD 0xFDB9753ECA864210ull
__device__ __forceinline__ int wo_kblock(int m, int g) { return (2 * g + (int)((WOORD >> (4 * m)) & 15)) & 15; }

__global__ void __cluster_dims__(2, 1, 1) __launch_bounds__(384, 1)
mega_kernel(const __grid_constant__ CUtensorMap tm_x0, const __grid_constant__ CUtensorMap tm_x,
            const __grid_constant__ CUtensorMap tm_o,
            const __grid_constant__ CUtensorMap tm_wA, const __grid_constant__ CUtensorMap tm_wB,
            const __grid_constant__ CUtensorMap tm_woA, const __grid_constant__ CUtensorMap tm_woB,
                        const bf16* __restrict__ wphi, bf16* __restrict__ out) {
  extern __shared__ uint8_t smem_raw[];
  const uint32_t sb = (smem_u32(smem_raw) + 1023u) & ~1023u;
  const uint32_t bar = sb + SM_BAR;
  const int warp = __shfl_sync(0xffffffffu, threadIdx.x >> 5, 0), lane = threadIdx.x & 31;
  const int cr = blockIdx.x & 1;
  const int g = (blockIdx.x >> 1) & 7;
  const int rb = (blockIdx.x >> 4) * 2 + cr;
  const int m0 = rb * 128;

  if (warp < 4) {
    asm volatile("setmaxnreg.dec.sync.aligned.u32 40;");
    asm volatile("barrier.cluster.arrive.relaxed.aligned;" ::: "memory");
    const unsigned int epoch = warp ? ld_relaxed(&g_epoch) : 0u;
    if (warp) cluster_wait();
    unsigned int xbase = epoch * NLAYERS;
    const unsigned int cbase = epoch * 16u;
    auto wo_a = [&](int layer) {
      uint64_t ts = ((layer & 1) ? WO_A1 : WO_A0) >> 8, td = ((layer & 1) ? WO_DA1 : WO_DA0) >> 8, tk = WOORD >> 8;
      uint32_t ready = 0u;
#pragma unroll 1
      for (int m = 2; m < 16; ++m) {
        const int kb = (2 * g + (uint32_t)tk) & 15;
        uint32_t dst = sb + ((uint32_t)ts & 15) * SLOT, fb = bar + B_FULLT + m * 8, eb = bar + B_CONS + ((uint32_t)td & 15) * 8;
        int kc = kb * 64;
        ts >>= 4; td >>= 4; tk >>= 4;
        asm volatile("" : "+r"(dst), "+r"(fb), "+r"(eb), "+r"(kc));
        bool fr = false;
        if (!((ready >> kb) & 1)) {
          PROFT(m == 2 && lane == 0, 64 + layer * 16 + 2);
          if (EP && m > EP) src_wait_async(bar, bar + B_FLG, g_of + rb * 32, xbase + layer + 1, kb, ready, lane);
          else fr = src_wait_tma(g_of + rb * 32, xbase + layer + 1, 1u << kb, ready, lane, eb, layer & 1);
          fence_async_all();
        }
        if (!fr) mbar_wait_u(eb, layer & 1);
        tma_2d_e(dst, &tm_o, kc, m0, fb);
        if (EP && m >= EP && (ready & 0xFFFFu) != 0xFFFFu) flag_fetch(bar, bar + B_FLG, g_of + rb * 32);
        PROFT(lane == 0 && layer == PL, 176 + m);
      }
    };
    auto wo_w = [&](int layer) {
      const CUtensorMap* tx = layer == 0 ? &tm_x0 : &tm_x;
      const CUtensorMap* two = (layer & 1) ? &tm_woB : &tm_woA;
      uint64_t ts = (layer & 1) ? WO_B1 : WO_B0, td = (layer & 1) ? WO_DB1 : WO_DB0, tk = WOORD;
      uint32_t pb = 0;
      fence_async_all();
      mbar_wait_u(bar + B_R0, layer & 1);
      expect_tx_e(bar + B_XOLD, 16384);
      tma_2d_e(sb + (XS + 1) * SLOT, tx, g * 128, m0, bar + B_XOLD);
#pragma unroll 1
      for (int m = 0; m < 16; ++m) {
        uint32_t dst = sb + ((uint32_t)ts & 15) * SLOT + cr * 8192, fb = bar + B_FULLT + m * 8, eb = bar + B_CONS + ((uint32_t)td & 15) * 8;
        int kc = ((2 * g + (uint32_t)tk) & 15) * 64;
        ts >>= 4; td >>= 4; tk >>= 4;
        asm volatile("" : "+r"(dst), "+r"(fb), "+r"(eb), "+r"(kc));
        if (eb != pb) mbar_wait_u(eb, layer & 1);
        pb = eb;
        tma_2d_mc_e(dst, two, g * 128 + cr * 64, kc, fb);
        expect_tx_e(fb, m < 2 ? 16384 : 32768);
        PROFT(lane == 0 && layer == PL, 144 + m);
        if (m == ((layer & 1) ? XB2 : 0)) {
          expect_tx_e(bar + B_XOLD2, 16384);
          tma_2d_e(sb + XS * SLOT, tx, g * 128 + 64, m0, bar + B_XOLD2);
        }
      }
    };
    if (warp == 0) {
      cluster_wait();
      PROFT(lane == 0, 125);
#pragma unroll 1
      for (int layer = 0; layer < NLAYERS; ++layer) {
        const CUtensorMap* tx = layer == 0 ? &tm_x0 : &tm_x;
        const CUtensorMap* tw = (layer & 1) ? &tm_wB : &tm_wA;
        uint32_t s = layer == 0, u = 0, ready = layer == 0 ? 0xFFFFu : 0u;
#pragma unroll 1
        for (int i = s; i < 16; ++i) {
          const int kb = layer == 0 ? kblock0(i, g) : wo_kblock(i, g), kc = kb * 64;
          const uint32_t fb = bar + B_FULLS + s * 8;
          const uint32_t kd = sb + (((QK >> (4 * s)) & 15) + cr) * SLOT, qd = sb + ((QQ >> (4 * s)) & 15) * SLOT + cr * 8192;
          const uint32_t need = 1u << kb;
          const bool ext = i >= 2 || layer == 0, early = ext && (ready & need) == need;
          mbar_wait_u(bar + B_EMPTYS + s * 8, (u + (s ? layer : 0) + 1) & 1);
          if (early) tma_2d_e(sb + ((QA >> (4 * s)) & 15) * SLOT, tx, kc, m0, fb);
          tma_2d_mc_e(kd, tw, 1024 + cr * 1024 + g * 128, kc, fb);
          tma_2d_mc_e(kd + 8192, tw, 1024 + cr * 1024 + g * 128 + 64, kc, fb);
          tma_2d_mc_e(qd, tw, g * 128 + cr * 64, kc, fb);
          expect_tx_e(fb, ext ? 65536 : 49152);
          PROFT(lane == 0 && layer == 0 && i == 1, 31);
          if (layer == 0 && i == 2) {
            mbar_wait_u(bar + B_FULLS, 0);
            tma_pf_e(&tm_x0, g * 128, m0);
            tma_pf_e(&tm_x0, g * 128 + 64, m0);
          }
          if (layer < 2 && i >= PFS) {
            const int j = i - PFS;
            if (j < 2) tma_pf_e(layer ? &tm_woB : &tm_woA, g * 128 + j * 64, rb * 64);
            else if (j < 8 && layer == 0) tma_pf_e(&tm_wB, ((j >> 1) - 1) * 1024 + g * 128 + (j & 1) * 64, rb * 64);
          }
          if (ext && !early) {
            PROFT(i == 2 && lane == 0, 64 + layer * 16 + 0);
            src_wait_tma(g_xf + rb * 32, xbase + layer + 1, need, ready, lane, fb, 0);
            PROFT(i == 2 && lane == 0, 64 + layer * 16 + 1);
            fence_async_all();
            tma_2d_e(sb + ((QA >> (4 * s)) & 15) * SLOT, tx, kc, m0, fb);
          }
          if (++s == 3) { s = 0; ++u; }
        }
        if (layer == 0) xbase = ld_relaxed(&g_epoch) * NLAYERS;
        wo_a(layer);
      }
    } else {
      if (warp >= 2) {
        const int h2 = threadIdx.x - 64;
        if (h2 < 16) sts_f(sb + SM_RS + h2 * 4, 0.f);
        if (h2 < 16) sts_f(bar + B_FLG + h2 * 4, __uint_as_float(xbase));
        mbar_wait_u(bar + B_FULLS, 0);
        colsum(&tm_wA, g_cs + (epoch & 1) * 6144, rb, g, warp - 2, 2, lane, warp == 2 ? sb + SM_SD : (sb + SM_BP + 1023u) & ~1023u, bar + B_CB + (warp - 2) * 8, 0);
#pragma unroll 1
        for (int i = h2; i < 320; i += 64) g_kv[(g * 16 + rb) * 320 + i] = make_uint4(0u, 0u, 0u, 0u);
        fence_async_all();
        nbar<5, 64>();
        if (h2 == 0) flag_add(&g_csflag[g].v);
        PROFT(h2 == 0, 242);
#pragma unroll 1
        for (int i = h2; i < 512; i += 256) {
          uint4 w[4];
#pragma unroll
          for (int j = 0; j < 4; ++j) w[j] = __ldg(reinterpret_cast<const uint4*>(wphi + (size_t)g * 4096) + i + j * 64);
#pragma unroll
          for (int j = 0; j < 4; ++j) sts128(sb + SM_WPHI + ((i >> 2) + j * 16) * 80 + (i & 3) * 16, w[j]);
        }
      }
      if (warp == 1) {
        if (lane >= 27) {
          const CUtensorMap* tm = lane == 27 ? &tm_o : lane == 28 ? &tm_wB : lane == 29 ? &tm_woA : lane == 30 ? &tm_woB : &tm_x;
          asm volatile("prefetch.tensormap [%0];" ::"l"(tm) : "memory");
        }
        __syncwarp();
        {
#pragma unroll 1
          for (int e = 0;; ++e) {
            if (e > 0 && e < NLAYERS) {
              mbar_wait_u(bar + B_XH0, (e - 1) & 1);
              flag_set(g_xf + rb * 32 + 2 * g, xbase + e + 1);
            }
            mbar_wait_u(bar + B_XDONE, e & 1);
            PROFT(e < 4, 64 + e * 16 + 4);
            if (e == NLAYERS) {
              if (blockIdx.x == 0) g_epoch = epoch + 1;
              break;
            }
            PROFT(e < 4, 64 + e * 16 + 5);
            flag_set(g_xf + rb * 32 + 2 * g + 1, xbase + e + 1);
            PROFT(e < 4, 64 + e * 16 + 7);
            if ((e & 1) == 0) {
#pragma unroll 1
              for (int hp = 0; hp < 2; ++hp) {
                uint4* kvl = g_kv + ((g * 2 + (e >> 1)) * 2 + hp) * 1280;
                mbar_wait_u(bar + B_KVDONE - hp * 32, (e >> 1) & 1);
                PROFT(e == PL, 243 + hp * 4);
                bulk_red_add_e(kvl + rb * 64, sb + (3 + hp) * SLOT + rb * 1024, 16384 - rb * 1024);
                if (rb) bulk_red_add_e(kvl, sb + (3 + hp) * SLOT, rb * 1024);
                bulk_red_add_e(kvl + 1024, sb + (6 + hp) * SLOT, 2048);
                bulk_red_add_e(kvl + 1152, sb + (6 + hp) * SLOT + 8192, 2048);
                bulk_commit();
                PROFT(e < 4, 64 + e * 16 + 6);
              }
              bulk_wait_read0();
              __syncwarp();
              if (lane < 2) release2(bar + B_E1);
              __syncwarp();
            }
            mbar_wait_u(bar + B_OH1, e & 1);
            PROFT(e == PL, 251);
            flag_set(g_of + rb * 32 + 2 * g, xbase + e + 1);
            PROFT(e < 4, 64 + e * 16 + 9);
            mbar_wait_u(bar + B_ODONE, e & 1);
            PROFT(e < 4, 64 + e * 16 + 8);
            flag_set(g_of + rb * 32 + 2 * g + 1, xbase + e + 1);
            PROFT(e < 4, 64 + e * 16 + 11);
          }
        }
      } else {
        const int h2 = threadIdx.x - 64;
        const float* cs = g_cs + (epoch & 1) * 6144;
#pragma unroll 1
        for (int layer = 0; layer < NLAYERS; ++layer) {
          if (warp == 2 && layer < 2) {
            if (lane == 0) flag_wait_t<CSLP>(&g_csflag[layer * 8 + g].v, cbase + 16u);
            __syncwarp();
            float4 a[3];
#pragma unroll
            for (int i = 0; i < 3; ++i) a[i] = __ldcg(reinterpret_cast<const float4*>(cs + layer * 3072 + g * 384) + i * 32 + lane);
#pragma unroll 1
            for (int i = 0; i < 3; ++i) {
              const float av[4] = {a[0].x, a[0].y, a[0].z, a[0].w};
              a[0] = a[1]; a[1] = a[2];
#pragma unroll
              for (int j = 0; j < 4; ++j) {
                const float c1 = bf16r(av[j]), c2 = bf16r(av[j] - c1), c3 = (av[j] - c1) - c2;
                sts128(sb + SM_BP + layer * 6144 + ((i * 32 + lane) * 4 + j) * 16, make_uint4(pack_bf16(c1, c2), pack_bf16(c3, 0.f), 0u, 0u));
              }
            }
            fence_async_smem();
            __syncwarp();
            if (lane == 0) mbar_arrive(bar + (layer ? B_CS2 : B_CS));
            PROFT(lane == 0, 64 + layer * 16 + 12);
            if (layer == 0) {
              uint4* hz = g_halo + (rb * 8 + g) * 1024;
#pragma unroll 2
              for (int i = lane; i < 1024; i += 32) hz[i] = make_uint4(0u, 0u, 0u, 0u);
              if (lane < 12) reinterpret_cast<float4*>(g_cs + ((epoch & 1) ^ 1) * 6144 + blockIdx.x * 48)[lane] = make_float4(0.f, 0.f, 0.f, 0.f);
              g_stats[(2 + (lane >> 4)) * S_ + m0 + g * 16 + (lane & 15)] = make_float2(0.f, 0.f);
            }
          }
          if (warp == 3) {
            const bool hal = (layer & 1) && rb > 0;
            {
              uint32_t rdy = 0u;
              src_wait<256>(g_xf + rb * 32, xbase + layer + 1, 0xAAAAu, rdy, lane);
              rdy = 0u;
              if (hal) src_wait<256>(g_xf + (rb - 1) * 32, xbase + layer + 1, 0xAAAAu, rdy, lane);
            }
            float2 u[5];
            const float2* sp = g_stats + layer * S_ + m0 + lane;
#pragma unroll
            for (int i = 0; i < 4; ++i) u[i] = __ldcg(sp + i * 32);
            u[4] = __ldcg(hal ? sp - 16 : sp);
            if (layer == 3) g_stats[(lane >> 4) * S_ + m0 + g * 16 + (lane & 15)] = make_float2(0.f, 0.f);
#pragma unroll 1
            for (int i = 0; i < (hal ? 5 : 4); ++i) {
              const int r = i < 4 ? 16 + i * 32 + lane : lane;
              const float sum = u[0].x, sq = u[0].y;
              u[0] = u[1]; u[1] = u[2]; u[2] = u[3]; u[3] = u[4];
              const float mean = sum * (1.f / D_);
              const float var = fmaxf(fmaf(-sum, mean, sq) * (1.f / D_), 0.f);
              const float sd = bf16r(sqrtf(bf16r(bf16r(var) + 1e-5f)));
              sts_f(sb + SM_RS + r * 4, 1.f / sd);
              if (i < 4) {
                const float hm = -0.5f * bf16r(mean);
                const uint32_t s2 = pack_bf16(sd, sd);
                if (!(layer & 1)) sts128(sb + SM_SD + (r - 16) * 64 + ((r >> 1) & 3) * 16, make_uint4(s2, s2, s2, s2));
                sts128(sb + SM_AP + (r - 16) * 16, make_uint4(pack_bf16(hm, hm), pack_bf16(hm, 0.f), 0u, 0u));
              }
            }
            fence_async_smem();
            __syncwarp();
            if (lane == 0) mbar_arrive(bar + B_STAT);
            PROFT(lane == 0, 64 + layer * 16 + 14);
            wo_w(__shfl_sync(0xffffffffu, layer, 0));
          }
          if (layer == 0 && warp == 2) {
            mbar_wait_u(bar + (CSW == 1 ? B_KVDONE - 32 : CSW == 2 ? B_OH1 : B_ODONE), 0);
            colsum(&tm_wB, g_cs + (epoch & 1) * 6144 + 3072, rb, g, 0, 1, lane, sb + SM_SD, bar + B_CB, 1);
            if (lane == 0) flag_add(&g_csflag[8 + g].v);
            PROFT(h2 == 0, 64 + 13);
          }
        }
      }
    }
    __syncwarp();
    asm volatile("barrier.cluster.arrive.relaxed.aligned;\nbarrier.cluster.wait.aligned;\n" ::: "memory");
  } else {
    if (warp == 5) {
      if (lane == 0) {
        mbar_init(bar + B_FULLS, 1);
        asm volatile("fence.mbarrier_init.release.cluster;" ::: "memory");
      }
      __syncwarp();
      expect_tx_e(bar + B_FULLS, 65536);
      tma_2d_e(sb + XS * SLOT, &tm_x0, 0, m0, bar + B_FULLS);
#pragma unroll
      for (int j = 0; j < 6; ++j)
        tma_2d_e(sb + (j < 4 ? j + 4 : j - 2) * 8192, &tm_wA, (j < 4 ? 1024 + (j >> 1) * 1024 : 0) + g * 128 + (j & 1) * 64, 0, bar + B_FULLS);
      PROFT(lane == 0, 241);
    }
    if (lane < 8 && warp != 5 && threadIdx.x != 128) {
      const int i = (warp - 4) * 8 + lane;
      mbar_init(bar + i * 8, i < 32 ? 1u << ((BAR_CNT >> (2 * i)) & 3) : i < 48 ? 1u : (i == 59 || i == 60) ? 16u : i < 63 ? 4u : 8u);
      asm volatile("fence.mbarrier_init.release.cluster;" ::: "memory");
    }
    __syncwarp();
    asm volatile("barrier.cluster.arrive.relaxed.aligned;" ::: "memory");
    asm volatile("setmaxnreg.inc.sync.aligned.u32 232;");
    cluster_wait();
    PROFT(threadIdx.x == 128, 0);
    Ctx c; c.sb = sb; c.g = g; c.rb = rb; c.cu = warp - 4; c.out = out;
    consumer(c);
    asm volatile("bar.warp.sync 0xffffffff;\nbarrier.cluster.arrive.relaxed.aligned;\nbarrier.cluster.wait.aligned;\n" ::: "memory");
  }
}

typedef CUresult (*PFN_encodeTiled)(CUtensorMap*, CUtensorMapDataType, cuuint32_t, void*, const cuuint64_t*, const cuuint64_t*,
                                    const cuuint32_t*, const cuuint32_t*, CUtensorMapInterleave, CUtensorMapSwizzle,
                                    CUtensorMapL2promotion, CUtensorMapFloatOOBfill);

static CUtensorMap make_map(PFN_encodeTiled enc, const void* ptr, uint64_t cols, uint64_t rows, uint32_t box_c, uint32_t box_r, uint32_t nb = 1) {
  CUtensorMap m;
  cuuint64_t dims[3] = {nb > 1 ? box_c : cols, rows, cols / box_c};
  cuuint64_t strides[2] = {cols * 2, box_c * 2};
  cuuint32_t box[3] = {box_c, box_r, nb};
  cuuint32_t es[3] = {1, 1, 1};
  CUresult r = enc(&m, CU_TENSOR_MAP_DATA_TYPE_BFLOAT16, nb > 1 ? 3 : 2, const_cast<void*>(ptr), dims, strides, box, es, CU_TENSOR_MAP_INTERLEAVE_NONE,
      CU_TENSOR_MAP_SWIZZLE_128B, CU_TENSOR_MAP_L2_PROMOTION_L2_256B, CU_TENSOR_MAP_FLOAT_OOB_FILL_NONE);
  (void)r;
  return m;
}

extern "C" void kernel_launch(void* const* d_in, const int* in_sizes, int n_in, void* d_out, int out_size) {
  const bf16* A_x = (const bf16*)d_in[0];
  const bf16* A_wqkv = (const bf16*)d_in[1];
  const bf16* A_wphi = (const bf16*)d_in[2];
  const bf16* A_wo = (const bf16*)d_in[3];
  const bf16* B_wqkv = (const bf16*)d_in[5];
  const bf16* B_wo = (const bf16*)d_in[6];
  bf16* out = (bf16*)d_out;

  static PFN_encodeTiled enc = nullptr;
  static bf16 *p_x, *p_o;
  if (!enc) {
    void* fn = nullptr; cudaDriverEntryPointQueryResult qr;
    cudaGetDriverEntryPoint("cuTensorMapEncodeTiled", &fn, cudaEnableDefault, &qr);
    enc = (PFN_encodeTiled)fn;
    cudaGetSymbolAddress((void**)&p_x, g_x);
    cudaGetSymbolAddress((void**)&p_o, g_o);
    cudaFuncSetAttribute(mega_kernel, cudaFuncAttributeMaxDynamicSharedMemorySize, SM_TOTAL);
  }
  CUtensorMap tm_x0 = make_map(enc, A_x, 1024, 2048, 64, 128);
  CUtensorMap tm_x = make_map(enc, p_x, 1024, 2048, 64, 128);
  CUtensorMap tm_o = make_map(enc, p_o, 1024, 2048, 64, 128);
  CUtensorMap tm_wA = make_map(enc, A_wqkv, 3072, 1024, 64, 64);
  CUtensorMap tm_wB = make_map(enc, B_wqkv, 3072, 1024, 64, 64);
  CUtensorMap tm_woA = make_map(enc, A_wo, 1024, 1024, 64, 64);
  CUtensorMap tm_woB = make_map(enc, B_wo, 1024, 1024, 64, 64);
  mega_kernel<<<128, 384, SM_TOTAL, cudaStreamPerThread>>>(tm_x0, tm_x, tm_o, tm_wA, tm_wB, tm_woA, tm_woB,
                                                           A_wphi, out);
}
```

```cpp
#include <cuda_runtime.h>
#include <cuda_bf16.h>
#include <cuda.h>
#include <stdint.h>

typedef __nv_bfloat16 bf16;

constexpr int S_ = 2048, D_ = 1024;

struct __align__(128) Flag { unsigned int v; unsigned int pad[31]; };
__device__ __align__(1024) bf16 g_x[S_ * D_];
__device__ __align__(1024) bf16 g_o[S_ * D_];
__device__ __align__(1024) uint4 g_halo[128 * 2 * 512];
__device__ __align__(1024) uint4 g_kv[8 * 2 * 2 * 1280];
__device__ __align__(1024) float2 g_stats[4 * S_];
__device__ __align__(1024) float g_cs[2 * 2 * 3072];
__device__ Flag g_csflag[16];
__device__ __align__(128) unsigned int g_xf[16 * 32], g_of[16 * 32];
__device__ unsigned int g_epoch, g_err;
#define PROFT(cond, idx) asm volatile("" ::: "memory")

__device__ __forceinline__ uint32_t smem_u32(const void* p) { return (uint32_t)__cvta_generic_to_shared(p); }
__device__ __forceinline__ void mbar_init(uint32_t bar, uint32_t count) {
  asm volatile("mbarrier.init.shared::cta.b64 [%0], %1;" ::"r"(bar), "r"(count) : "memory");
}
__device__ __forceinline__ void mbar_expect_tx(uint32_t bar, uint32_t bytes) {
  asm volatile("mbarrier.arrive.expect_tx.shared::cta.b64 _, [%0], %1;" ::"r"(bar), "r"(bytes) : "memory");
}
__device__ __forceinline__ void mbar_arrive(uint32_t bar) {
  asm volatile("mbarrier.arrive.shared::cta.b64 _, [%0];" ::"r"(bar) : "memory");
}
__device__ __forceinline__ bool mbar_try_wait(uint32_t bar, uint32_t parity) {
  uint32_t ok;
  asm volatile("{\n.reg .pred p;\nmbarrier.try_wait.parity.shared::cta.b64 p, [%1], %2;\nselp.b32 %0, 1, 0, p;\n}\n"
               : "=r"(ok) : "r"(bar), "r"(parity) : "memory");
  return ok != 0;
}
__device__ __forceinline__ bool mbar_test_wait(uint32_t bar, uint32_t parity) {
  uint32_t ok;
  asm volatile("{\n.reg .pred p;\nmbarrier.test_wait.parity.shared::cta.b64 p, [%1], %2;\nselp.b32 %0, 1, 0, p;\n}\n"
               : "=r"(ok) : "r"(bar), "r"(parity) : "memory");
  return ok != 0;
}
__device__ __forceinline__ uint64_t gtimer() {
  uint64_t t; asm volatile("mov.u64 %0, %globaltimer;" : "=l"(t)); return t;
}
__device__ __forceinline__ void mbar_wait(uint32_t bar, uint32_t parity) {
  uint32_t n = 0;
#pragma unroll 1
  while (!mbar_try_wait(bar, parity)) {
    if (++n > (1u << 22)) { g_err = 1u; break; }
  }
}
__device__ __forceinline__ unsigned int ld_acquire(const unsigned int* p) {
  unsigned int v; asm volatile("ld.acquire.gpu.global.u32 %0, [%1];" : "=r"(v) : "l"(p) : "memory"); return v;
}
__device__ __forceinline__ void flag_add(unsigned int* p) {
  asm volatile("red.release.gpu.global.add.u32 [%0], 1;" ::"l"(p) : "memory");
}
__device__ __forceinline__ void flag_set(unsigned int* p, unsigned int v) {
  asm volatile("st.release.gpu.global.u32 [%0], %1;" ::"l"(p), "r"(v) : "memory");
}
template <int SLEEP>
__device__ __forceinline__ void src_wait(const unsigned int* f, unsigned int target, uint32_t need, uint32_t& ready, int lane) {
  uint32_t n = 0;
#pragma unroll 1
  while ((ready & need) != need) {
    const unsigned int v = ld_acquire(f + (lane & 15));
    ready = __ballot_sync(0xffffffffu, (int)(v - target) >= 0);
    if (SLEEP) { if ((ready & need) != need) __nanosleep(SLEEP); }
    if (++n > (1u << 20)) { g_err = 3u; break; }
  }
  __syncwarp();
}
__device__ __forceinline__ unsigned int ld_relaxed(const unsigned int* p) {
  unsigned int v; asm volatile("ld.relaxed.gpu.global.u32 %0, [%1];" : "=r"(v) : "l"(p) : "memory"); return v;
}
__device__ __forceinline__ bool src_wait_tma(const unsigned int* f, unsigned int target, uint32_t need, uint32_t& ready, int lane, uint32_t eb, uint32_t par) {
  uint32_t n = 0;
  bool fr = false;
#pragma unroll 1
  while ((ready & need) != need) {
    const unsigned int v = ld_acquire(f + (lane & 15));
    fr = __all_sync(0xffffffffu, mbar_test_wait(eb, par));
    ready = __ballot_sync(0xffffffffu, (int)(v - target) >= 0);
    if (++n > (1u << 20)) { g_err = 3u; break; }
  }
  return fr;
}
__device__ __forceinline__ uint4 ld_relaxed4(const uint4* p) {
  uint4 v; asm volatile("ld.relaxed.gpu.global.v4.u32 {%0,%1,%2,%3}, [%4];" : "=r"(v.x), "=r"(v.y), "=r"(v.z), "=r"(v.w) : "l"(p) : "memory"); return v;
}
__device__ __forceinline__ void st_relaxed4(uint4* p, uint32_t a, uint32_t b, uint32_t c, uint32_t d) {
  asm volatile("st.relaxed.gpu.global.v4.u32 [%0], {%1,%2,%3,%4};" ::"l"(p), "r"(a), "r"(b), "r"(c), "r"(d) : "memory");
}
template <int SLEEP>
__device__ __forceinline__ void flag_wait_t(const unsigned int* p, unsigned int target) {
  uint32_t n = 0;
#pragma unroll 1
  while ((int)(ld_acquire(p) - target) < 0) {
    if (SLEEP) __nanosleep(SLEEP);
    if (++n > (1u << 20)) { g_err = 2u; break; }
  }
}
__device__ __forceinline__ void flag_wait(const unsigned int* p, unsigned int target) { flag_wait_t<0>(p, target); }
__device__ __forceinline__ void flag_wait_slow(const unsigned int* p, unsigned int target) { flag_wait_t<256>(p, target); }
__device__ __forceinline__ void tma_load_2d(uint32_t dst, const CUtensorMap* tm, int c0, int c1, uint32_t bar) {
  asm volatile("cp.async.bulk.tensor.2d.shared::cluster.global.mbarrier::complete_tx::bytes [%0], [%1, {%2, %3}], [%4];"
               ::"r"(dst), "l"(tm), "r"(c0), "r"(c1), "r"(bar) : "memory");
}
__device__ __forceinline__ void tma_load_2d_mc(uint32_t dst, const CUtensorMap* tm, int c0, int c1, uint32_t bar, uint16_t mask) {
  asm volatile("cp.async.bulk.tensor.2d.shared::cluster.global.mbarrier::complete_tx::bytes.multicast::cluster [%0], [%1, {%2, %3}], [%4], %5;"
               ::"r"(dst), "l"(tm), "r"(c0), "r"(c1), "r"(bar), "h"(mask) : "memory");
}
__device__ __forceinline__ void mbar_wait_u(uint32_t bar, uint32_t parity) {
  uint32_t n = 0;
#pragma unroll 1
  while (!__all_sync(0xffffffffu, mbar_try_wait(bar, parity))) {
    if (++n > (1u << 22)) { g_err = 1u; break; }
  }
}
__device__ __forceinline__ void expect_tx_e(uint32_t bar, uint32_t bytes) {
  asm volatile("{\n.reg .pred p;\nelect.sync _|p, 0xffffffff;\n@p mbarrier.arrive.expect_tx.shared::cta.b64 _, [%0], %1;\n}\n" ::"r"(bar), "r"(bytes) : "memory");
}
__device__ __forceinline__ void tma_2d_e(uint32_t dst, const CUtensorMap* tm, int c0, int c1, uint32_t bar) {
  asm volatile("{\n.reg .pred p;\nelect.sync _|p, 0xffffffff;\n"
               "@p cp.async.bulk.tensor.2d.shared::cluster.global.mbarrier::complete_tx::bytes [%0], [%1, {%2, %3}], [%4];\n}\n"
               ::"r"(dst), "l"(tm), "r"(c0), "r"(c1), "r"(bar) : "memory");
}
__device__ __forceinline__ void tma_2d_mc_e(uint32_t dst, const CUtensorMap* tm, int c0, int c1, uint32_t bar) {
  asm volatile("{\n.reg .pred p;\nelect.sync _|p, 0xffffffff;\n"
               "@p cp.async.bulk.tensor.2d.shared::cluster.global.mbarrier::complete_tx::bytes.multicast::cluster [%0], [%1, {%2, %3}], [%4], %5;\n}\n"
               ::"r"(dst), "l"(tm), "r"(c0), "r"(c1), "r"(bar), "h"((uint16_t)3) : "memory");
}
__device__ __forceinline__ void tma_pf_e(const CUtensorMap* tm, int c0, int c1) {
  asm volatile("{\n.reg .pred p;\nelect.sync _|p, 0xffffffff;\n"
               "@p cp.async.bulk.prefetch.tensor.2d.L2.global.tile [%0, {%1, %2}];\n}\n" ::"l"(tm), "r"(c0), "r"(c1) : "memory");
}
__device__ __forceinline__ void tma_2d_to_e(uint32_t dst, const CUtensorMap* tm, int c0, int c1, uint32_t bar, uint32_t mask) {
  asm volatile("{\n.reg .pred p;\nelect.sync _|p, 0xffffffff;\n"
               "@p cp.async.bulk.tensor.2d.shared::cluster.global.mbarrier::complete_tx::bytes.multicast::cluster [%0], [%1, {%2, %3}], [%4], %5;\n}\n"
               ::"r"(dst), "l"(tm), "r"(c0), "r"(c1), "r"(bar), "h"((uint16_t)mask) : "memory");
}
__device__ __forceinline__ void tma_3d_mc_e(uint32_t dst, const CUtensorMap* tm, int c1, int c2, uint32_t bar) {
  asm volatile("{\n.reg .pred p;\nelect.sync _|p, 0xffffffff;\n"
               "@p cp.async.bulk.tensor.3d.shared::cluster.global.mbarrier::complete_tx::bytes.multicast::cluster [%0], [%1, {%6, %2, %3}], [%4], %5;\n}\n"
               ::"r"(dst), "l"(tm), "r"(c1), "r"(c2), "r"(bar), "h"((uint16_t)3), "r"(0) : "memory");
}
__device__ __forceinline__ uint32_t poll_flags(const unsigned int* f, unsigned int target, int lane) {
  const unsigned int v = ld_acquire(f + (lane & 15));
  const uint32_t r = __ballot_sync(0xffffffffu, (int)(v - target) >= 0);
  __syncwarp();
  return r;
}
__device__ __forceinline__ void mbar_arrive_cluster(uint32_t local_bar, uint32_t rank) {
  asm volatile("{\n.reg .b32 ra;\nmapa.shared::cluster.u32 ra, %0, %1;\nmbarrier.arrive.shared::cluster.b64 _, [ra];\n}\n"
               ::"r"(local_bar), "r"(rank) : "memory");
}
__device__ __forceinline__ void release2(uint32_t bar) { mbar_arrive_cluster(bar, 0); mbar_arrive_cluster(bar, 1); }
__device__ __forceinline__ void tma_store_2d(const CUtensorMap* tm, uint32_t src, int c0, int c1) {
  asm volatile("cp.async.bulk.tensor.2d.global.shared::cta.bulk_group [%0, {%2, %3}], [%1];"
               ::"l"(tm), "r"(src), "r"(c0), "r"(c1) : "memory");
}
__device__ __forceinline__ void bulk_store(void* dst, uint32_t src, uint32_t bytes) {
  asm volatile("cp.async.bulk.global.shared::cta.bulk_group [%0], [%1], %2;" ::"l"(dst), "r"(src), "r"(bytes) : "memory");
}
__device__ __forceinline__ void bulk_load(uint32_t dst, const void* src, uint32_t bytes, uint32_t bar) {
  asm volatile("cp.async.bulk.shared::cluster.global.mbarrier::complete_tx::bytes [%0], [%1], %2, [%3];" ::"r"(dst), "l"(src), "r"(bytes), "r"(bar) : "memory");
}
__device__ __forceinline__ void bulk_red_add(void* dst, uint32_t src, uint32_t bytes) {
  asm volatile("cp.reduce.async.bulk.global.shared::cta.bulk_group.add.f32 [%0], [%1], %2;" ::"l"(dst), "r"(src), "r"(bytes) : "memory");
}
__device__ __forceinline__ void bulk_red_add_e(void* dst, uint32_t src, uint32_t bytes) {
  asm volatile("{\n.reg .pred p;\nelect.sync _|p, 0xffffffff;\n@p cp.reduce.async.bulk.global.shared::cta.bulk_group.add.f32 [%0], [%1], %2;\n}\n" ::"l"(dst), "r"(src), "r"(bytes) : "memory");
}
__device__ __forceinline__ void bulk_commit() { asm volatile("cp.async.bulk.commit_group;" ::: "memory"); }
__device__ __forceinline__ void bulk_wait_read0() { asm volatile("cp.async.bulk.wait_group.read 0;" ::: "memory"); }
__device__ __forceinline__ void bulk_wait0() { asm volatile("cp.async.bulk.wait_group 0;" ::: "memory"); }
__device__ __forceinline__ void fence_async_smem() { asm volatile("fence.proxy.async.shared::cta;" ::: "memory"); }
__device__ __forceinline__ void fence_async_all() { asm volatile("fence.proxy.async.global;" ::: "memory"); }
__device__ __forceinline__ void wgmma_fence() { asm volatile("wgmma.fence.sync.aligned;" ::: "memory"); }
__device__ __forceinline__ void wgmma_commit() { asm volatile("wgmma.commit_group.sync.aligned;" ::: "memory"); }
template <int N> __device__ __forceinline__ void wgmma_wait() { asm volatile("wgmma.wait_group.sync.aligned %0;" ::"n"(N) : "memory"); }
__device__ __forceinline__ void cluster_arrive() { asm volatile("barrier.cluster.arrive.release.aligned;" ::: "memory"); }
__device__ __forceinline__ void cluster_wait() { asm volatile("barrier.cluster.wait.acquire.aligned;" ::: "memory"); }
template <int ID, int N> __device__ __forceinline__ void nbar() { asm volatile("bar.sync %0, %1;" ::"n"(ID), "n"(N) : "memory"); }
__device__ __forceinline__ uint64_t make_desc(uint32_t addr, uint32_t lbo_bytes, uint32_t sbo_bytes) {
  uint64_t d = 0;
  d |= (uint64_t)((addr & 0x3FFFF) >> 4);
  d |= (uint64_t)((lbo_bytes >> 4) & 0x3FFF) << 16;
  d |= (uint64_t)((sbo_bytes >> 4) & 0x3FFF) << 32;
  d |= (uint64_t)1 << 62;
  return d;
}
__device__ __forceinline__ uint64_t desc64(uint32_t lo, uint32_t hi) { return (uint64_t)lo | ((uint64_t)hi << 32); }
__device__ __forceinline__ uint32_t pack_bf16(float lo, float hi) {
  uint32_t r; asm("cvt.rn.bf16x2.f32 %0, %1, %2;" : "=r"(r) : "f"(hi), "f"(lo)); return r;
}
__device__ __forceinline__ uint32_t mul_bf16x2(uint32_t a, uint32_t s, bool hi) {
  __nv_bfloat162 x = *reinterpret_cast<__nv_bfloat162*>(&a), y = *reinterpret_cast<__nv_bfloat162*>(&s);
  x = __hmul2(x, hi ? __high2bfloat162(y) : __low2bfloat162(y));
  return *reinterpret_cast<uint32_t*>(&x);
}
__device__ __forceinline__ float bf16r(float x) { return __bfloat162float(__float2bfloat16_rn(x)); }
__device__ __forceinline__ float bf_lo(uint32_t u) { return __uint_as_float(u << 16); }
__device__ __forceinline__ float bf_hi(uint32_t u) { return __uint_as_float(u & 0xFFFF0000u); }
__device__ __forceinline__ float ex2(float x) { float r; asm("ex2.approx.ftz.f32 %0, %1;" : "=f"(r) : "f"(x)); return r; }
__device__ __forceinline__ float rcp(float x) { float r; asm("rcp.approx.ftz.f32 %0, %1;" : "=f"(r) : "f"(x)); return r; }
__device__ __forceinline__ void mma_bf16(float (&d)[4], uint32_t a0, uint32_t a1, uint32_t a2, uint32_t a3, uint32_t b0, uint32_t b1) {
  asm("mma.sync.aligned.m16n8k16.row.col.f32.bf16.bf16.f32 {%0,%1,%2,%3}, {%4,%5,%6,%7}, {%8,%9}, {%0,%1,%2,%3};"
               : "+f"(d[0]), "+f"(d[1]), "+f"(d[2]), "+f"(d[3]) : "r"(a0), "r"(a1), "r"(a2), "r"(a3), "r"(b0), "r"(b1));
}
__device__ __forceinline__ void ldsm_x4(uint32_t& r0, uint32_t& r1, uint32_t& r2, uint32_t& r3, uint32_t addr) {
  asm volatile("ldmatrix.sync.aligned.m8n8.x4.shared.b16 {%0,%1,%2,%3}, [%4];"
               : "=r"(r0), "=r"(r1), "=r"(r2), "=r"(r3) : "r"(addr) : "memory");
}
__device__ __forceinline__ void ldsm_x4_t(uint32_t& r0, uint32_t& r1, uint32_t& r2, uint32_t& r3, uint32_t addr) {
  asm volatile("ldmatrix.sync.aligned.m8n8.x4.trans.shared.b16 {%0,%1,%2,%3}, [%4];"
               : "=r"(r0), "=r"(r1), "=r"(r2), "=r"(r3) : "r"(addr) : "memory");
}
__device__ __forceinline__ void ldsm_x2_t(uint32_t& r0, uint32_t& r1, uint32_t addr) {
  asm volatile("ldmatrix.sync.aligned.m8n8.x2.trans.shared.b16 {%0,%1}, [%2];"
               : "=r"(r0), "=r"(r1) : "r"(addr) : "memory");
}
__device__ __forceinline__ void stsm_x4(uint32_t addr, uint32_t r0, uint32_t r1, uint32_t r2, uint32_t r3) {
  asm volatile("stmatrix.sync.aligned.m8n8.x4.shared.b16 [%0], {%1,%2,%3,%4};"
               ::"r"(addr), "r"(r0), "r"(r1), "r"(r2), "r"(r3) : "memory");
}
__device__ __forceinline__ void stsm_x4_p(bool on, uint32_t addr, uint32_t r0, uint32_t r1, uint32_t r2, uint32_t r3) {
  asm volatile("{\n.reg .pred p;\nsetp.ne.b32 p, %5, 0;\n@p stmatrix.sync.aligned.m8n8.x4.shared.b16 [%0], {%1,%2,%3,%4};\n}\n"
               ::"r"(addr), "r"(r0), "r"(r1), "r"(r2), "r"(r3), "r"((int)on) : "memory");
}
__device__ __forceinline__ float2 lds_f2(uint32_t addr) {
  float2 v; asm volatile("ld.shared.v2.f32 {%0,%1}, [%2];" : "=f"(v.x), "=f"(v.y) : "r"(addr) : "memory"); return v;
}
__device__ __forceinline__ uint4 lds128(uint32_t addr) {
  uint4 v; asm volatile("ld.shared.v4.b32 {%0,%1,%2,%3}, [%4];" : "=r"(v.x), "=r"(v.y), "=r"(v.z), "=r"(v.w) : "r"(addr) : "memory"); return v;
}
__device__ __forceinline__ void sts128(uint32_t addr, uint4 v) {
  asm volatile("st.shared.v4.b32 [%0], {%1,%2,%3,%4};" ::"r"(addr), "r"(v.x), "r"(v.y), "r"(v.z), "r"(v.w) : "memory");
}
__device__ __forceinline__ float lds_f(uint32_t addr) {
  float v; asm volatile("ld.shared.f32 %0, [%1];" : "=f"(v) : "r"(addr) : "memory"); return v;
}
__device__ __forceinline__ uint32_t lds_vol(uint32_t addr) {
  uint32_t v; asm volatile("ld.volatile.shared.u32 %0, [%1];" : "=r"(v) : "r"(addr) : "memory"); return v;
}
__device__ __forceinline__ void sts16(uint32_t addr, uint32_t v) {
  asm volatile("st.shared.u16 [%0], %1;" ::"r"(addr), "h"((unsigned short)v) : "memory");
}
__device__ __forceinline__ void nbar_dyn(int id, int n) { asm volatile("bar.sync %0, %1;" ::"r"(id), "r"(n) : "memory"); }
__device__ __forceinline__ uint64_t make_desc_ns(uint32_t addr, uint32_t lbo_bytes, uint32_t sbo_bytes) {
  return (uint64_t)((addr & 0x3FFFF) >> 4) | ((uint64_t)(lbo_bytes >> 4) << 16) | ((uint64_t)(sbo_bytes >> 4) << 32);
}
__device__ __forceinline__ void sts_f(uint32_t addr, float v) { asm volatile("st.shared.f32 [%0], %1;" ::"r"(addr), "f"(v) : "memory"); }
__device__ __forceinline__ void sts64(uint32_t addr, uint32_t a, uint32_t b) {
  asm volatile("st.shared.v2.b32 [%0], {%1,%2};" ::"r"(addr), "r"(a), "r"(b) : "memory");
}
__device__ __forceinline__ void sts_f2(uint32_t addr, float a, float b) {
  asm volatile("st.shared.v2.f32 [%0], {%1,%2};" ::"r"(addr), "f"(a), "f"(b) : "memory");
}
__device__ __forceinline__ void red_add2(float* p, float a, float b) {
  asm volatile("red.global.add.v2.f32 [%0], {%1,%2};" ::"l"(p), "f"(a), "f"(b) : "memory");
}
__device__ __forceinline__ void red_add4(float* p, float a, float b, float c, float d) {
  asm volatile("red.global.add.v4.f32 [%0], {%1,%2,%3,%4};" ::"l"(p), "f"(a), "f"(b), "f"(c), "f"(d) : "memory");
}
__device__ __forceinline__ void red_add1(float* p, float a) {
  asm volatile("red.global.add.f32 [%0], %1;" ::"l"(p), "f"(a) : "memory");
}
__device__ __forceinline__ void l2_prefetch(const void* p, uint32_t bytes) {
  asm volatile("cp.async.bulk.prefetch.L2.global [%0], %1;" ::"l"(p), "r"(bytes) : "memory");
}

__device__ __forceinline__ void wgmma_n256(float (&d)[192], uint64_t da, uint64_t db, int scale_d) {
  asm volatile("{\n.reg .pred p;\nsetp.ne.b32 p, %130, 0;\n"
    "wgmma.mma_async.sync.aligned.m64n256k16.f32.bf16.bf16 {%0, %1, %2, %3, %4, %5, %6, %7, %8, %9, %10, %11, %12, %13, %14, %15, %16, %17, %18, %19, %20, %21, %22, %23, %24, %25, %26, %27, %28, %29, %30, %31, %32, %33, %34, %35, %36, %37, %38, %39, %40, %41, %42, %43, %44, %45, %46, %47, %48, %49, %50, %51, %52, %53, %54, %55, %56, %57, %58, %59, %60, %61, %62, %63, %64, %65, %66, %67, %68, %69, %70, %71, %72, %73, %74, %75, %76, %77, %78, %79, %80, %81, %82, %83, %84, %85, %86, %87, %88, %89, %90, %91, %92, %93, %94, %95, %96, %97, %98, %99, %100, %101, %102, %103, %104, %105, %106, %107, %108, %109, %110, %111, %112, %113, %114, %115, %116, %117, %118, %119, %120, %121, %122, %123, %124, %125, %126, %127}, %128, %129, p, 1, 1, 0, 1;\n}\n"
    : "+f"(d[0]), "+f"(d[1]), "+f"(d[2]), "+f"(d[3]), "+f"(d[4]), "+f"(d[5]), "+f"(d[6]), "+f"(d[7]), "+f"(d[8]), "+f"(d[9]), "+f"(d[10]), "+f"(d[11]), "+f"(d[12]), "+f"(d[13]), "+f"(d[14]), "+f"(d[15]), "+f"(d[16]), "+f"(d[17]), "+f"(d[18]), "+f"(d[19]), "+f"(d[20]), "+f"(d[21]), "+f"(d[22]), "+f"(d[23]), "+f"(d[24]), "+f"(d[25]), "+f"(d[26]), "+f"(d[27]), "+f"(d[28]), "+f"(d[29]), "+f"(d[30]), "+f"(d[31]), "+f"(d[32]), "+f"(d[33]), "+f"(d[34]), "+f"(d[35]), "+f"(d[36]), "+f"(d[37]), "+f"(d[38]), "+f"(d[39]), "+f"(d[40]), "+f"(d[41]), "+f"(d[42]), "+f"(d[43]), "+f"(d[44]), "+f"(d[45]), "+f"(d[46]), "+f"(d[47]), "+f"(d[48]), "+f"(d[49]), "+f"(d[50]), "+f"(d[51]), "+f"(d[52]), "+f"(d[53]), "+f"(d[54]), "+f"(d[55]), "+f"(d[56]), "+f"(d[57]), "+f"(d[58]), "+f"(d[59]), "+f"(d[60]), "+f"(d[61]), "+f"(d[62]), "+f"(d[63]), "+f"(d[64]), "+f"(d[65]), "+f"(d[66]), "+f"(d[67]), "+f"(d[68]), "+f"(d[69]), "+f"(d[70]), "+f"(d[71]), "+f"(d[72]), "+f"(d[73]), "+f"(d[74]), "+f"(d[75]), "+f"(d[76]), "+f"(d[77]), "+f"(d[78]), "+f"(d[79]), "+f"(d[80]), "+f"(d[81]), "+f"(d[82]), "+f"(d[83]), "+f"(d[84]), "+f"(d[85]), "+f"(d[86]), "+f"(d[87]), "+f"(d[88]), "+f"(d[89]), "+f"(d[90]), "+f"(d[91]), "+f"(d[92]), "+f"(d[93]), "+f"(d[94]), "+f"(d[95]), "+f"(d[96]), "+f"(d[97]), "+f"(d[98]), "+f"(d[99]), "+f"(d[100]), "+f"(d[101]), "+f"(d[102]), "+f"(d[103]), "+f"(d[104]), "+f"(d[105]), "+f"(d[106]), "+f"(d[107]), "+f"(d[108]), "+f"(d[109]), "+f"(d[110]), "+f"(d[111]), "+f"(d[112]), "+f"(d[113]), "+f"(d[114]), "+f"(d[115]), "+f"(d[116]), "+f"(d[117]), "+f"(d[118]), "+f"(d[119]), "+f"(d[120]), "+f"(d[121]), "+f"(d[122]), "+f"(d[123]), "+f"(d[124]), "+f"(d[125]), "+f"(d[126]), "+f"(d[127])
    : "l"(da), "l"(db), "r"(scale_d));
}
__device__ __forceinline__ void wgmma_n128(float (&d)[192], uint64_t da, uint64_t db, int scale_d) {
  asm volatile("{\n.reg .pred p;\nsetp.ne.b32 p, %66, 0;\n"
    "wgmma.mma_async.sync.aligned.m64n128k16.f32.bf16.bf16 {%0, %1, %2, %3, %4, %5, %6, %7, %8, %9, %10, %11, %12, %13, %14, %15, %16, %17, %18, %19, %20, %21, %22, %23, %24, %25, %26, %27, %28, %29, %30, %31, %32, %33, %34, %35, %36, %37, %38, %39, %40, %41, %42, %43, %44, %45, %46, %47, %48, %49, %50, %51, %52, %53, %54, %55, %56, %57, %58, %59, %60, %61, %62, %63}, %64, %65, p, 1, 1, 0, 1;\n}\n"
    : "+f"(d[128]), "+f"(d[129]), "+f"(d[130]), "+f"(d[131]), "+f"(d[132]), "+f"(d[133]), "+f"(d[134]), "+f"(d[135]), "+f"(d[136]), "+f"(d[137]), "+f"(d[138]), "+f"(d[139]), "+f"(d[140]), "+f"(d[141]), "+f"(d[142]), "+f"(d[143]), "+f"(d[144]), "+f"(d[145]), "+f"(d[146]), "+f"(d[147]), "+f"(d[148]), "+f"(d[149]), "+f"(d[150]), "+f"(d[151]), "+f"(d[152]), "+f"(d[153]), "+f"(d[154]), "+f"(d[155]), "+f"(d[156]), "+f"(d[157]), "+f"(d[158]), "+f"(d[159]), "+f"(d[160]), "+f"(d[161]), "+f"(d[162]), "+f"(d[163]), "+f"(d[164]), "+f"(d[165]), "+f"(d[166]), "+f"(d[167]), "+f"(d[168]), "+f"(d[169]), "+f"(d[170]), "+f"(d[171]), "+f"(d[172]), "+f"(d[173]), "+f"(d[174]), "+f"(d[175]), "+f"(d[176]), "+f"(d[177]), "+f"(d[178]), "+f"(d[179]), "+f"(d[180]), "+f"(d[181]), "+f"(d[182]), "+f"(d[183]), "+f"(d[184]), "+f"(d[185]), "+f"(d[186]), "+f"(d[187]), "+f"(d[188]), "+f"(d[189]), "+f"(d[190]), "+f"(d[191])
    : "l"(da), "l"(db), "r"(scale_d));
}
__device__ __forceinline__ void wgmma_n256_k(float (&d)[192], uint64_t da, uint64_t db, int scale_d) {
  asm volatile("{\n.reg .pred p;\nsetp.ne.b32 p, %130, 0;\n"
    "wgmma.mma_async.sync.aligned.m64n256k16.f32.bf16.bf16 {%0, %1, %2, %3, %4, %5, %6, %7, %8, %9, %10, %11, %12, %13, %14, %15, %16, %17, %18, %19, %20, %21, %22, %23, %24, %25, %26, %27, %28, %29, %30, %31, %32, %33, %34, %35, %36, %37, %38, %39, %40, %41, %42, %43, %44, %45, %46, %47, %48, %49, %50, %51, %52, %53, %54, %55, %56, %57, %58, %59, %60, %61, %62, %63, %64, %65, %66, %67, %68, %69, %70, %71, %72, %73, %74, %75, %76, %77, %78, %79, %80, %81, %82, %83, %84, %85, %86, %87, %88, %89, %90, %91, %92, %93, %94, %95, %96, %97, %98, %99, %100, %101, %102, %103, %104, %105, %106, %107, %108, %109, %110, %111, %112, %113, %114, %115, %116, %117, %118, %119, %120, %121, %122, %123, %124, %125, %126, %127}, %128, %129, p, 1, 1, 0, 0;\n}\n"
    : "+f"(d[0]), "+f"(d[1]), "+f"(d[2]), "+f"(d[3]), "+f"(d[4]), "+f"(d[5]), "+f"(d[6]), "+f"(d[7]), "+f"(d[8]), "+f"(d[9]), "+f"(d[10]), "+f"(d[11]), "+f"(d[12]), "+f"(d[13]), "+f"(d[14]), "+f"(d[15]), "+f"(d[16]), "+f"(d[17]), "+f"(d[18]), "+f"(d[19]), "+f"(d[20]), "+f"(d[21]), "+f"(d[22]), "+f"(d[23]), "+f"(d[24]), "+f"(d[25]), "+f"(d[26]), "+f"(d[27]), "+f"(d[28]), "+f"(d[29]), "+f"(d[30]), "+f"(d[31]), "+f"(d[32]), "+f"(d[33]), "+f"(d[34]), "+f"(d[35]), "+f"(d[36]), "+f"(d[37]), "+f"(d[38]), "+f"(d[39]), "+f"(d[40]), "+f"(d[41]), "+f"(d[42]), "+f"(d[43]), "+f"(d[44]), "+f"(d[45]), "+f"(d[46]), "+f"(d[47]), "+f"(d[48]), "+f"(d[49]), "+f"(d[50]), "+f"(d[51]), "+f"(d[52]), "+f"(d[53]), "+f"(d[54]), "+f"(d[55]), "+f"(d[56]), "+f"(d[57]), "+f"(d[58]), "+f"(d[59]), "+f"(d[60]), "+f"(d[61]), "+f"(d[62]), "+f"(d[63]), "+f"(d[64]), "+f"(d[65]), "+f"(d[66]), "+f"(d[67]), "+f"(d[68]), "+f"(d[69]), "+f"(d[70]), "+f"(d[71]), "+f"(d[72]), "+f"(d[73]), "+f"(d[74]), "+f"(d[75]), "+f"(d[76]), "+f"(d[77]), "+f"(d[78]), "+f"(d[79]), "+f"(d[80]), "+f"(d[81]), "+f"(d[82]), "+f"(d[83]), "+f"(d[84]), "+f"(d[85]), "+f"(d[86]), "+f"(d[87]), "+f"(d[88]), "+f"(d[89]), "+f"(d[90]), "+f"(d[91]), "+f"(d[92]), "+f"(d[93]), "+f"(d[94]), "+f"(d[95]), "+f"(d[96]), "+f"(d[97]), "+f"(d[98]), "+f"(d[99]), "+f"(d[100]), "+f"(d[101]), "+f"(d[102]), "+f"(d[103]), "+f"(d[104]), "+f"(d[105]), "+f"(d[106]), "+f"(d[107]), "+f"(d[108]), "+f"(d[109]), "+f"(d[110]), "+f"(d[111]), "+f"(d[112]), "+f"(d[113]), "+f"(d[114]), "+f"(d[115]), "+f"(d[116]), "+f"(d[117]), "+f"(d[118]), "+f"(d[119]), "+f"(d[120]), "+f"(d[121]), "+f"(d[122]), "+f"(d[123]), "+f"(d[124]), "+f"(d[125]), "+f"(d[126]), "+f"(d[127])
    : "l"(da), "l"(db), "r"(scale_d));
}
__device__ __forceinline__ void wgmma_n128_k(float (&d)[192], uint64_t da, uint64_t db, int scale_d) {
  asm volatile("{\n.reg .pred p;\nsetp.ne.b32 p, %66, 0;\n"
    "wgmma.mma_async.sync.aligned.m64n128k16.f32.bf16.bf16 {%0, %1, %2, %3, %4, %5, %6, %7, %8, %9, %10, %11, %12, %13, %14, %15, %16, %17, %18, %19, %20, %21, %22, %23, %24, %25, %26, %27, %28, %29, %30, %31, %32, %33, %34, %35, %36, %37, %38, %39, %40, %41, %42, %43, %44, %45, %46, %47, %48, %49, %50, %51, %52, %53, %54, %55, %56, %57, %58, %59, %60, %61, %62, %63}, %64, %65, p, 1, 1, 0, 0;\n}\n"
    : "+f"(d[128]), "+f"(d[129]), "+f"(d[130]), "+f"(d[131]), "+f"(d[132]), "+f"(d[133]), "+f"(d[134]), "+f"(d[135]), "+f"(d[136]), "+f"(d[137]), "+f"(d[138]), "+f"(d[139]), "+f"(d[140]), "+f"(d[141]), "+f"(d[142]), "+f"(d[143]), "+f"(d[144]), "+f"(d[145]), "+f"(d[146]), "+f"(d[147]), "+f"(d[148]), "+f"(d[149]), "+f"(d[150]), "+f"(d[151]), "+f"(d[152]), "+f"(d[153]), "+f"(d[154]), "+f"(d[155]), "+f"(d[156]), "+f"(d[157]), "+f"(d[158]), "+f"(d[159]), "+f"(d[160]), "+f"(d[161]), "+f"(d[162]), "+f"(d[163]), "+f"(d[164]), "+f"(d[165]), "+f"(d[166]), "+f"(d[167]), "+f"(d[168]), "+f"(d[169]), "+f"(d[170]), "+f"(d[171]), "+f"(d[172]), "+f"(d[173]), "+f"(d[174]), "+f"(d[175]), "+f"(d[176]), "+f"(d[177]), "+f"(d[178]), "+f"(d[179]), "+f"(d[180]), "+f"(d[181]), "+f"(d[182]), "+f"(d[183]), "+f"(d[184]), "+f"(d[185]), "+f"(d[186]), "+f"(d[187]), "+f"(d[188]), "+f"(d[189]), "+f"(d[190]), "+f"(d[191])
    : "l"(da), "l"(db), "r"(scale_d));
}
__device__ __forceinline__ void wgmma_n40_tt(float (&d)[20], uint64_t da, uint64_t db, int scale_d) {
  asm volatile("{\n.reg .pred p;\nsetp.ne.b32 p, %22, 0;\n"
    "wgmma.mma_async.sync.aligned.m64n40k16.f32.bf16.bf16 {%0, %1, %2, %3, %4, %5, %6, %7, %8, %9, %10, %11, %12, %13, %14, %15, %16, %17, %18, %19}, %20, %21, p, 1, 1, 1, 1;\n}\n"
    : "+f"(d[0]), "+f"(d[1]), "+f"(d[2]), "+f"(d[3]), "+f"(d[4]), "+f"(d[5]), "+f"(d[6]), "+f"(d[7]), "+f"(d[8]), "+f"(d[9]), "+f"(d[10]), "+f"(d[11]), "+f"(d[12]), "+f"(d[13]), "+f"(d[14]), "+f"(d[15]), "+f"(d[16]), "+f"(d[17]), "+f"(d[18]), "+f"(d[19])
    : "l"(da), "l"(db), "r"(scale_d));
}
__device__ __forceinline__ void wgmma_n40_rs(float (&d)[20], const uint32_t (&a)[4], uint64_t db, int scale_d) {
  asm volatile("{\n.reg .pred p;\nsetp.ne.b32 p, %25, 0;\n"
    "wgmma.mma_async.sync.aligned.m64n40k16.f32.bf16.bf16 {%0, %1, %2, %3, %4, %5, %6, %7, %8, %9, %10, %11, %12, %13, %14, %15, %16, %17, %18, %19}, {%20, %21, %22, %23}, %24, p, 1, 1, 1;\n}\n"
    : "+f"(d[0]), "+f"(d[1]), "+f"(d[2]), "+f"(d[3]), "+f"(d[4]), "+f"(d[5]), "+f"(d[6]), "+f"(d[7]), "+f"(d[8]), "+f"(d[9]), "+f"(d[10]), "+f"(d[11]), "+f"(d[12]), "+f"(d[13]), "+f"(d[14]), "+f"(d[15]), "+f"(d[16]), "+f"(d[17]), "+f"(d[18]), "+f"(d[19])
    : "r"(a[0]), "r"(a[1]), "r"(a[2]), "r"(a[3]), "l"(db), "r"(scale_d));
}
__device__ __forceinline__ void wgmma_n256_0(float (&d)[192], uint64_t da, uint64_t db) {
  asm volatile("{\n.reg .pred p;\nsetp.ne.b32 p, 0, 0;\n"
    "wgmma.mma_async.sync.aligned.m64n256k16.f32.bf16.bf16 {%0, %1, %2, %3, %4, %5, %6, %7, %8, %9, %10, %11, %12, %13, %14, %15, %16, %17, %18, %19, %20, %21, %22, %23, %24, %25, %26, %27, %28, %29, %30, %31, %32, %33, %34, %35, %36, %37, %38, %39, %40, %41, %42, %43, %44, %45, %46, %47, %48, %49, %50, %51, %52, %53, %54, %55, %56, %57, %58, %59, %60, %61, %62, %63, %64, %65, %66, %67, %68, %69, %70, %71, %72, %73, %74, %75, %76, %77, %78, %79, %80, %81, %82, %83, %84, %85, %86, %87, %88, %89, %90, %91, %92, %93, %94, %95, %96, %97, %98, %99, %100, %101, %102, %103, %104, %105, %106, %107, %108, %109, %110, %111, %112, %113, %114, %115, %116, %117, %118, %119, %120, %121, %122, %123, %124, %125, %126, %127}, %128, %129, p, 1, 1, 0, 1;\n}\n"
    : "=f"(d[0]), "=f"(d[1]), "=f"(d[2]), "=f"(d[3]), "=f"(d[4]), "=f"(d[5]), "=f"(d[6]), "=f"(d[7]), "=f"(d[8]), "=f"(d[9]), "=f"(d[10]), "=f"(d[11]), "=f"(d[12]), "=f"(d[13]), "=f"(d[14]), "=f"(d[15]), "=f"(d[16]), "=f"(d[17]), "=f"(d[18]), "=f"(d[19]), "=f"(d[20]), "=f"(d[21]), "=f"(d[22]), "=f"(d[23]), "=f"(d[24]), "=f"(d[25]), "=f"(d[26]), "=f"(d[27]), "=f"(d[28]), "=f"(d[29]), "=f"(d[30]), "=f"(d[31]), "=f"(d[32]), "=f"(d[33]), "=f"(d[34]), "=f"(d[35]), "=f"(d[36]), "=f"(d[37]), "=f"(d[38]), "=f"(d[39]), "=f"(d[40]), "=f"(d[41]), "=f"(d[42]), "=f"(d[43]), "=f"(d[44]), "=f"(d[45]), "=f"(d[46]), "=f"(d[47]), "=f"(d[48]), "=f"(d[49]), "=f"(d[50]), "=f"(d[51]), "=f"(d[52]), "=f"(d[53]), "=f"(d[54]), "=f"(d[55]), "=f"(d[56]), "=f"(d[57]), "=f"(d[58]), "=f"(d[59]), "=f"(d[60]), "=f"(d[61]), "=f"(d[62]), "=f"(d[63]), "=f"(d[64]), "=f"(d[65]), "=f"(d[66]), "=f"(d[67]), "=f"(d[68]), "=f"(d[69]), "=f"(d[70]), "=f"(d[71]), "=f"(d[72]), "=f"(d[73]), "=f"(d[74]), "=f"(d[75]), "=f"(d[76]), "=f"(d[77]), "=f"(d[78]), "=f"(d[79]), "=f"(d[80]), "=f"(d[81]), "=f"(d[82]), "=f"(d[83]), "=f"(d[84]), "=f"(d[85]), "=f"(d[86]), "=f"(d[87]), "=f"(d[88]), "=f"(d[89]), "=f"(d[90]), "=f"(d[91]), "=f"(d[92]), "=f"(d[93]), "=f"(d[94]), "=f"(d[95]), "=f"(d[96]), "=f"(d[97]), "=f"(d[98]), "=f"(d[99]), "=f"(d[100]), "=f"(d[101]), "=f"(d[102]), "=f"(d[103]), "=f"(d[104]), "=f"(d[105]), "=f"(d[106]), "=f"(d[107]), "=f"(d[108]), "=f"(d[109]), "=f"(d[110]), "=f"(d[111]), "=f"(d[112]), "=f"(d[113]), "=f"(d[114]), "=f"(d[115]), "=f"(d[116]), "=f"(d[117]), "=f"(d[118]), "=f"(d[119]), "=f"(d[120]), "=f"(d[121]), "=f"(d[122]), "=f"(d[123]), "=f"(d[124]), "=f"(d[125]), "=f"(d[126]), "=f"(d[127])
    : "l"(da), "l"(db));
}
__device__ __forceinline__ void wgmma_n128_0(float (&d)[192], uint64_t da, uint64_t db) {
  asm volatile("{\n.reg .pred p;\nsetp.ne.b32 p, 0, 0;\n"
    "wgmma.mma_async.sync.aligned.m64n128k16.f32.bf16.bf16 {%0, %1, %2, %3, %4, %5, %6, %7, %8, %9, %10, %11, %12, %13, %14, %15, %16, %17, %18, %19, %20, %21, %22, %23, %24, %25, %26, %27, %28, %29, %30, %31, %32, %33, %34, %35, %36, %37, %38, %39, %40, %41, %42, %43, %44, %45, %46, %47, %48, %49, %50, %51, %52, %53, %54, %55, %56, %57, %58, %59, %60, %61, %62, %63}, %64, %65, p, 1, 1, 0, 1;\n}\n"
    : "=f"(d[128]), "=f"(d[129]), "=f"(d[130]), "=f"(d[131]), "=f"(d[132]), "=f"(d[133]), "=f"(d[134]), "=f"(d[135]), "=f"(d[136]), "=f"(d[137]), "=f"(d[138]), "=f"(d[139]), "=f"(d[140]), "=f"(d[141]), "=f"(d[142]), "=f"(d[143]), "=f"(d[144]), "=f"(d[145]), "=f"(d[146]), "=f"(d[147]), "=f"(d[148]), "=f"(d[149]), "=f"(d[150]), "=f"(d[151]), "=f"(d[152]), "=f"(d[153]), "=f"(d[154]), "=f"(d[155]), "=f"(d[156]), "=f"(d[157]), "=f"(d[158]), "=f"(d[159]), "=f"(d[160]), "=f"(d[161]), "=f"(d[162]), "=f"(d[163]), "=f"(d[164]), "=f"(d[165]), "=f"(d[166]), "=f"(d[167]), "=f"(d[168]), "=f"(d[169]), "=f"(d[170]), "=f"(d[171]), "=f"(d[172]), "=f"(d[173]), "=f"(d[174]), "=f"(d[175]), "=f"(d[176]), "=f"(d[177]), "=f"(d[178]), "=f"(d[179]), "=f"(d[180]), "=f"(d[181]), "=f"(d[182]), "=f"(d[183]), "=f"(d[184]), "=f"(d[185]), "=f"(d[186]), "=f"(d[187]), "=f"(d[188]), "=f"(d[189]), "=f"(d[190]), "=f"(d[191])
    : "l"(da), "l"(db));
}
__device__ __forceinline__ void wgmma_n64a(float (&d)[192], uint64_t da, uint64_t db, int scale_d) {
  asm volatile("{\n.reg .pred p;\nsetp.ne.b32 p, %34, 0;\n"
    "wgmma.mma_async.sync.aligned.m64n64k16.f32.bf16.bf16 {%0, %1, %2, %3, %4, %5, %6, %7, %8, %9, %10, %11, %12, %13, %14, %15, %16, %17, %18, %19, %20, %21, %22, %23, %24, %25, %26, %27, %28, %29, %30, %31}, %32, %33, p, 1, 1, 0, 1;\n}\n"
    : "+f"(d[128]), "+f"(d[129]), "+f"(d[130]), "+f"(d[131]), "+f"(d[132]), "+f"(d[133]), "+f"(d[134]), "+f"(d[135]), "+f"(d[136]), "+f"(d[137]), "+f"(d[138]), "+f"(d[139]), "+f"(d[140]), "+f"(d[141]), "+f"(d[142]), "+f"(d[143]), "+f"(d[144]), "+f"(d[145]), "+f"(d[146]), "+f"(d[147]), "+f"(d[148]), "+f"(d[149]), "+f"(d[150]), "+f"(d[151]), "+f"(d[152]), "+f"(d[153]), "+f"(d[154]), "+f"(d[155]), "+f"(d[156]), "+f"(d[157]), "+f"(d[158]), "+f"(d[159])
    : "l"(da), "l"(db), "r"(scale_d));
}
__device__ __forceinline__ void wgmma_n64b(float (&d)[192], uint64_t da, uint64_t db, int scale_d) {
  asm volatile("{\n.reg .pred p;\nsetp.ne.b32 p, %34, 0;\n"
    "wgmma.mma_async.sync.aligned.m64n64k16.f32.bf16.bf16 {%0, %1, %2, %3, %4, %5, %6, %7, %8, %9, %10, %11, %12, %13, %14, %15, %16, %17, %18, %19, %20, %21, %22, %23, %24, %25, %26, %27, %28, %29, %30, %31}, %32, %33, p, 1, 1, 0, 1;\n}\n"
    : "+f"(d[160]), "+f"(d[161]), "+f"(d[162]), "+f"(d[163]), "+f"(d[164]), "+f"(d[165]), "+f"(d[166]), "+f"(d[167]), "+f"(d[168]), "+f"(d[169]), "+f"(d[170]), "+f"(d[171]), "+f"(d[172]), "+f"(d[173]), "+f"(d[174]), "+f"(d[175]), "+f"(d[176]), "+f"(d[177]), "+f"(d[178]), "+f"(d[179]), "+f"(d[180]), "+f"(d[181]), "+f"(d[182]), "+f"(d[183]), "+f"(d[184]), "+f"(d[185]), "+f"(d[186]), "+f"(d[187]), "+f"(d[188]), "+f"(d[189]), "+f"(d[190]), "+f"(d[191])
    : "l"(da), "l"(db), "r"(scale_d));
}

constexpr int SLOT = 16384;
constexpr int KVT = 10240;
constexpr uint32_t QA = 0x0BAu, QK = 0x462u, QQ = 0x981u;
constexpr int SM_SD = 12 * SLOT;
constexpr int SM_BAR = SM_SD + 8192;
constexpr int SM_RS = SM_BAR + 512;
constexpr int SM_AP = SM_RS + 768;
constexpr int SM_BP = SM_AP + 2048;
constexpr int SM_WPHI = SM_BP + 12288;
constexpr int SM_EPOCH = SM_WPHI + 10240;
constexpr int SM_TOTAL = SM_EPOCH + 16 + 1024;
constexpr int B_FULLS = 0, B_XOLD = 24, B_STAT = 32, B_EMPTYS = 40, B_FULLT = 256  , B_CONS = 384  , B_E3 = 472, B_E0 = 480, B_E1 = 488, B_E2 = 496, B_EPI = 504, B_CS = 160,
              B_KVDONE = 168  , B_ODONE = 176, B_XDONE = 184, B_OH1 = 192, B_CS2 = 208, B_XH0 = 232, B_R0 = 240, B_CB = 144  , B_XOLD2 = 216, B_FLG = 64  ;
constexpr uint64_t BAR_CNT = 0x1c07fc0eac00a800ull;
constexpr uint64_t WO_A0 = 0xba76218762187643ull, WO_B0 = 0x9540395403ba9021ull, WO_A1 = 0xba713257132576abull, WO_B1 = 0x9506489064890132ull;
constexpr uint64_t WO_DA0 = 0xa9876543210edd00ull, WO_DB0 = 0xa987654321bbccccull, WO_DA1 = 0xa9876543210fff00ull, WO_DB1 = 0xa98765432bbcccddull;
constexpr int NX = 4;
constexpr int XS = 10;

#define PL 2
#define PROFX(i) PROFT(tid_ == 128 && layer == PL, 200 + (i))
#define PSL 20
#define EP 5
#define DRY 0
#define NCOM 3
#define CSLP 128
#define PFS 8
#define KVTH 0x41700000u
#define RL 3
#define ORD 1
#define XB2 2
#define PMOD 3
#define DB1 2
#define NLAYERS 4
constexpr float L2E = 1.4426950408889634f;
#define PHI_MAX 2147483648.f

#define D128(lo) desc64(lo, 0x40000040u)
struct Ctx { uint32_t sb; int g, rb, cu; bf16* out; };

__device__ __forceinline__ void colsum(const CUtensorMap* tm, float* cs, int rb, int g, int w0, int dw, int lane, uint32_t stg, uint32_t cb, uint32_t par) {
  const uint32_t src = stg + (lane >> 3) * 2048;
#pragma unroll 1
  for (int wi = w0 - dw; wi < 6; wi += dw) {
    float s[8] = {0.f, 0.f, 0.f, 0.f, 0.f, 0.f, 0.f, 0.f};
    if (wi >= 0) {
      mbar_wait_u(cb, par);
      par ^= 1;
#pragma unroll 4
      for (int r = 0; r < 16; ++r) {
        const uint4 v = lds128(src + r * 128 + (((lane ^ r) & 7) << 4));
        s[0] += bf_lo(v.x); s[1] += bf_hi(v.x); s[2] += bf_lo(v.y); s[3] += bf_hi(v.y);
        s[4] += bf_lo(v.z); s[5] += bf_hi(v.z); s[6] += bf_lo(v.w); s[7] += bf_hi(v.w);
      }
#pragma unroll
      for (int i = 0; i < 8; ++i) s[i] += __shfl_xor_sync(0xffffffffu, s[i], 8);
    }
    const int wn = wi + dw;
    if (wn < 6) {
      expect_tx_e(cb, 8192);
      tma_2d_e(stg, tm, (wn >= 4 ? 0 : 1024 + (wn >> 1) * 1024) + g * 128 + (wn & 1) * 64, rb * 64, cb);
    }
    if (wi >= 0) {
#pragma unroll
      for (int i = 0; i < 8; ++i) s[i] += __shfl_xor_sync(0xffffffffu, s[i], 16);
      if (lane < 8) {
        red_add4(cs + g * 384 + (wi * 8 + lane) * 8, s[0], s[1], s[2], s[3]);
        red_add4(cs + g * 384 + (wi * 8 + lane) * 8 + 4, s[4], s[5], s[6], s[7]);
      }
      __syncwarp();
    }
  }
}
#define PHASE_CTX() \
  uint32_t sb = c.sb; asm volatile("" : "+r"(sb)); \
  int tid_ = threadIdx.x; asm volatile("" : "+r"(tid_)); \
  const uint32_t bar = sb + SM_BAR; \
  const int lane = tid_ & 31, cw = (tid_ >> 5) - 4, wg = cw >> 2, wq = cw & 3, gq = lane >> 2, t = lane & 3, wrow0 = cw * 16; \
  const int lrow = (lane & 7) + ((lane >> 3) & 1) * 8, lchk = lane >> 4; \
  const bool elected = (tid_ & 127) == 0; \
  const uint32_t rowo = (wrow0 + lrow) * 128, X = (lchk ^ (lane & 7)) << 4; \
  (void)bar; (void)wq; (void)gq; (void)lrow; (void)lchk; (void)elected; (void)wrow0; (void)wg; (void)rowo; (void)X; (void)t;

__device__ __forceinline__ void slab_out_half(uint32_t slot, bf16* dst, int wrow0, int lane, bool FENCE = false) {
  const int r0 = lane >> 3, ch = lane & 7;
  const uint32_t src = slot + (wrow0 + r0) * 128;
  uint4 v[4];
#pragma unroll
  for (int i = 0; i < 4; ++i) v[i] = lds128(src + i * 512 + (((ch ^ (4 * i + r0)) & 7) << 4));
  if (FENCE) fence_async_smem();
  dst += (size_t)(wrow0 + r0) * D_ + ch * 8;
#pragma unroll
  for (int i = 0; i < 4; ++i)
    asm volatile("st.global.v4.u32 [%0], {%1,%2,%3,%4};" ::"l"(dst + (size_t)i * 4 * D_), "r"(v[i].x), "r"(v[i].y), "r"(v[i].z), "r"(v[i].w) : "memory");
}

template <int O>
__device__ __forceinline__ void phi_proj(float (&p)[2][4][4], const uint32_t (&kq)[64], uint32_t wa) {
#pragma unroll
  for (int h = 0; h < 2; ++h)
#pragma unroll
    for (int i = 0; i < 4; ++i) { p[h][i][0] = p[h][i][1] = p[h][i][2] = p[h][i][3] = 0.f; }
#pragma unroll
  for (int ks = 0; ks < 2; ++ks)
#pragma unroll
    for (int np = 0; np < 2; ++np)
#pragma unroll
      for (int h = 0; h < 2; ++h) {
        uint32_t b0, b1, b2, b3;
        ldsm_x4_t(b0, b1, b2, b3, wa + h * 2560 + ks * 1280 + np * 32);
        mma_bf16(p[h][2 * np], kq[O + 8 * h + 4 * ks], kq[O + 8 * h + 4 * ks + 1], kq[O + 8 * h + 4 * ks + 2], kq[O + 8 * h + 4 * ks + 3], b0, b1);
        mma_bf16(p[h][2 * np + 1], kq[O + 8 * h + 4 * ks], kq[O + 8 * h + 4 * ks + 1], kq[O + 8 * h + 4 * ks + 2], kq[O + 8 * h + 4 * ks + 3], b2, b3);
      }
}
__device__ __forceinline__ void phi_exp(uint32_t (&raw)[4][4], const float (&p)[4][4], float sc0, float sc1) {
#pragma unroll
  for (int i = 0; i < 4; ++i) {
    const float e0 = ex2(p[i][0] * sc0), e1 = ex2(p[i][1] * sc0), e2 = ex2(p[i][2] * sc1), e3 = ex2(p[i][3] * sc1);
    const float m0 = e0 * e1, m1 = e2 * e3, rr = rcp(m0 * m1), r0 = rr * m1, r1 = rr * m0;
    raw[i >> 1][(i & 1) * 2] = pack_bf16(e0, e1);
    raw[i >> 1][(i & 1) * 2 + 1] = pack_bf16(e2, e3);
    raw[2 + (i >> 1)][(i & 1) * 2] = pack_bf16(e1 * r0, e0 * r0);
    raw[2 + (i >> 1)][(i & 1) * 2 + 1] = pack_bf16(e3 * r1, e2 * r1);
  }
}
#define FENCE_P(h) _Pragma("unroll") for (int i_ = 0; i_ < 16; ++i_) asm volatile("" : "+f"(p[h][i_ >> 2][i_ & 3]) :: "memory")
#define FENCE_RAW(h) _Pragma("unroll") for (int i_ = 0; i_ < 16; ++i_) asm volatile("" : "+r"(raw[h][i_ >> 2][i_ & 3]) :: "memory")
template <int O>
__device__ __forceinline__ void phi_norm(uint32_t (&ph)[2][4][4], const uint32_t (&raw)[2][4][4], const uint32_t (&kq)[64], uint32_t wa,
                                         float sc0, float sc1, float mul0, float mul1) {
  bool bad = false;
#pragma unroll
  for (int h = 0; h < 2; ++h)
#pragma unroll
    for (int sg = 0; sg < 2; ++sg) {
      float ss[4] = {0.f, 0.f, 0.f, 0.f};
#pragma unroll
      for (int ks = 0; ks < 2; ++ks)
        mma_bf16(ss, raw[h][2 * sg + ks][0], raw[h][2 * sg + ks][1], raw[h][2 * sg + ks][2], raw[h][2 * sg + ks][3], 0x3F803F80u, 0x3F803F80u);
      bad = bad || !(ss[0] < PHI_MAX) || !(ss[2] < PHI_MAX);
      const uint32_t iv = pack_bf16(rcp(ss[0]) * mul0, rcp(ss[2]) * mul1);
#pragma unroll
      for (int ks = 0; ks < 2; ++ks)
#pragma unroll
        for (int j = 0; j < 4; ++j) ph[h][2 * sg + ks][j] = mul_bf16x2(raw[h][2 * sg + ks][j], iv, j & 1);
    }
  if (__builtin_expect(__any_sync(0xffffffffu, bad), 0)) {
#pragma unroll 1
    for (int it = 0; it < 4; ++it) {
      float q[4][4];
#pragma unroll
      for (int i = 0; i < 4; ++i) { q[i][0] = q[i][1] = q[i][2] = q[i][3] = 0.f; }
#pragma unroll
      for (int ks = 0; ks < 2; ++ks) {
        uint32_t a[4];
#pragma unroll
        for (int j = 0; j < 4; ++j) a[j] = (it & 2) ? kq[O + 8 + 4 * ks + j] : kq[O + 4 * ks + j];
#pragma unroll
        for (int np = 0; np < 2; ++np) {
          uint32_t b0, b1, b2, b3;
          ldsm_x4_t(b0, b1, b2, b3, wa + (it >> 1) * 2560 + ks * 1280 + np * 32);
          mma_bf16(q[2 * np], a[0], a[1], a[2], a[3], b0, b1);
          mma_bf16(q[2 * np + 1], a[0], a[1], a[2], a[3], b2, b3);
        }
      }
      float iv[2];
#pragma unroll
      for (int r = 0; r < 2; ++r) {
        const float sc = (it & 1) ? -(r ? sc1 : sc0) : (r ? sc1 : sc0);
        float mx = -INFINITY, sm = 0.f;
#pragma unroll
        for (int i = 0; i < 8; ++i) { float& v = q[i >> 1][2 * r + (i & 1)]; v *= sc; mx = fmaxf(mx, v); }
        mx = fmaxf(mx, __shfl_xor_sync(0xffffffffu, mx, 1));
        mx = fmaxf(mx, __shfl_xor_sync(0xffffffffu, mx, 2));
#pragma unroll
        for (int i = 0; i < 8; ++i) { float& v = q[i >> 1][2 * r + (i & 1)]; v = ex2(v - mx); sm += v; }
        sm += __shfl_xor_sync(0xffffffffu, sm, 1);
        sm += __shfl_xor_sync(0xffffffffu, sm, 2);
        iv[r] = rcp(sm) * (r ? mul1 : mul0);
      }
#pragma unroll
      for (int i = 0; i < 24; ++i) ph[i >> 4][(i >> 2) & 3][i & 3] = ph[(i + 8) >> 4][((i + 8) >> 2) & 3][i & 3];
#pragma unroll
      for (int i = 0; i < 4; ++i) {
        ph[1][2 + (i >> 1)][(i & 1) * 2] = pack_bf16(q[i][0] * iv[0], q[i][1] * iv[0]);
        ph[1][2 + (i >> 1)][(i & 1) * 2 + 1] = pack_bf16(q[i][2] * iv[1], q[i][3] * iv[1]);
      }
    }
  }
}

__device__ __forceinline__ void stats_out(float s0, float s1, float q0, float q1, float2* dst, int t) {
  const bool od = t & 1;
  float sa = od ? s1 : s0, qa = od ? q1 : q0;
  sa += __shfl_xor_sync(0xffffffffu, od ? s0 : s1, 1);
  qa += __shfl_xor_sync(0xffffffffu, od ? q0 : q1, 1);
  sa += __shfl_xor_sync(0xffffffffu, sa, 2);
  qa += __shfl_xor_sync(0xffffffffu, qa, 2);
  if (t < 2) red_add2(&dst[t * 8].x, sa, qa);
}

__device__ __forceinline__ void consumer(const Ctx& c) {
  const int g = c.g, m0 = c.rb * 128;
  float acc[192];
#define X_H1() \
      _Pragma("unroll") for (int jp = 4; jp < 8; ++jp) \
        stsm_x4(sb + (XS + 1) * SLOT + rowo + (X ^ ((jp & 3) << 5)), \
                pack_bf16(acc[128 + 8 * jp], acc[129 + 8 * jp]), pack_bf16(acc[130 + 8 * jp], acc[131 + 8 * jp]), \
                pack_bf16(acc[132 + 8 * jp], acc[133 + 8 * jp]), pack_bf16(acc[134 + 8 * jp], acc[135 + 8 * jp]));
#pragma unroll
  for (int i = 128; i < 192; ++i) acc[i] = 0.f;
#pragma unroll 1
  for (int layer = 0;; ++layer) {
    {
      PHASE_CTX();
      const uint32_t wu = c.cu >> 2;
      const uint32_t dA0 = (((sb + wu * 8192) & 0x3FFFF) >> 4) | (1u << 16), dB0 = ((sb & 0x3FFFF) >> 4) | (512u << 16);
      {
        PROFX(0);
        mbar_wait(bar + B_FULLS, 0);
        PROFX(1);
        wgmma_fence();
        wgmma_n256_0(acc, D128(dA0 + XS * 1024), D128(dB0 + 2048));
#pragma unroll
        for (int k = 1; k < 4; ++k) wgmma_n256(acc, D128(dA0 + XS * 1024 + k * 2), D128(dB0 + 2048 + k * 128), 1);
        wgmma_commit();
        wgmma_wait<1>();
        float s0 = 0.f, s1 = 0.f, q0 = 0.f, q1 = 0.f;
        if (layer) {
          X_H1();
#pragma unroll
          for (int i = 128; i < 192; i += 4) {
            s0 += acc[i] + acc[i + 1]; s1 += acc[i + 2] + acc[i + 3];
            q0 = fmaf(acc[i], acc[i], fmaf(acc[i + 1], acc[i + 1], q0)); q1 = fmaf(acc[i + 2], acc[i + 2], fmaf(acc[i + 3], acc[i + 3], q1));
          }
        }
        asm volatile("" : "+f"(s0), "+f"(s1), "+f"(q0), "+f"(q1) :: "memory");
        wgmma_fence();
        wgmma_n128_0(acc, D128(dA0 + XS * 1024), D128(dB0 + 1024));
#pragma unroll
        for (int k = 1; k < 4; ++k) wgmma_n128(acc, D128(dA0 + XS * 1024 + k * 2), D128(dB0 + 1024 + k * 128), 1);
        wgmma_commit();
        if (layer) {
          PHASE_CTX();
          fence_async_smem();
          nbar_dyn(3 + wu, 128);
          stats_out(s0, s1, q0, q1, g_stats + layer * S_ + m0 + wrow0 + gq, t);
          PROFT(tid_ == 128, layer * 16 + 8);
        }
      }
      uint32_t s = 1, u = 0, sp = 0;
      const int ix = layer ? 1 : 2 * min(g, NCOM) + 1;
#pragma unroll 1
      for (int i = 1; i < 14; ++i) {
        mbar_wait(bar + B_FULLS + s * 8, (u + (s ? layer : 0)) & 1);
        const uint32_t da = dA0 + ((QA >> (4 * s)) & 15) * 1024, dk = dB0 + ((QK >> (4 * s)) & 15) * 1024,
                       dq = dB0 + ((QQ >> (4 * s)) & 15) * 1024;
        wgmma_fence();
#pragma unroll
        for (int k = 0; k < 4; ++k) {
          wgmma_n256(acc, D128(da + k * 2), D128(dk + k * 128), 1);
          wgmma_n128(acc, D128(da + k * 2), D128(dq + k * 128), 1);
        }
        wgmma_commit();
        if (i == ix || (i == ix + 1 && !layer)) {
          PHASE_CTX();
          if (layer) {
            slab_out_half(sb + (XS + 1) * SLOT, g_x + (size_t)m0 * D_ + g * 128 + 64, wrow0, lane);
          } else {
            float s0 = 0.f, s1 = 0.f, q0 = 0.f, q1 = 0.f;
            const uint32_t xa = sb + ((QA >> (4 * sp)) & 15) * SLOT + rowo;
#pragma unroll
            for (int jp = 0; jp < 4; ++jp) {
              uint32_t x0, x1, x2, x3;
              ldsm_x4(x0, x1, x2, x3, xa + (X ^ (jp << 5)));
              s0 += (bf_lo(x0) + bf_hi(x0)) + (bf_lo(x2) + bf_hi(x2));
              s1 += (bf_lo(x1) + bf_hi(x1)) + (bf_lo(x3) + bf_hi(x3));
              q0 = fmaf(bf_lo(x0), bf_lo(x0), fmaf(bf_hi(x0), bf_hi(x0), fmaf(bf_lo(x2), bf_lo(x2), fmaf(bf_hi(x2), bf_hi(x2), q0))));
              q1 = fmaf(bf_lo(x1), bf_lo(x1), fmaf(bf_hi(x1), bf_hi(x1), fmaf(bf_lo(x3), bf_lo(x3), fmaf(bf_hi(x3), bf_hi(x3), q1))));
            }
            stats_out(s0, s1, q0, q1, g_stats + m0 + wrow0 + gq, t);
          }
          __syncwarp();
          if (lane == 0 && (layer || i != ix)) mbar_arrive(bar + B_XDONE);
          nbar_dyn(3 + wu, 128);
        }
        wgmma_wait<1>();
        if (elected) release2(bar + B_EMPTYS + sp * 8);
        sp = s;
        if (++s == 3) { s = 0; ++u; }
      }
      {
        const uint64_t dap = make_desc_ns(sb + SM_AP + wu * 1024, 0, 128), dbp = make_desc_ns(sb + SM_BP + (layer & 1) * 6144, 0, 128);
        if (wu == 0) {
          wgmma_wait<0>();
          if (elected) mbar_arrive(bar + B_R0);
          nbar<6, 256>();
        }
        if (layer < 2) mbar_wait(bar + (layer ? B_CS2 : B_CS), 0);
        mbar_wait(bar + B_STAT, layer & 1);
        mbar_wait(bar + B_FULLS + 16, layer & 1);
        wgmma_fence();
        wgmma_n256_k(acc, dap, dbp, 1);
#pragma unroll
        for (int k = 0; k < 4; ++k) wgmma_n256(acc, D128(dA0 + (QA >> 8) * 1024 + k * 2), D128(dB0 + (QK >> 8) * 1024 + k * 128), 1);
        mbar_wait(bar + B_FULLS, 1);
        PROFT(tid_ == 128, layer * 16 + 9);
        wgmma_fence();
#pragma unroll
        for (int k = 0; k < 4; ++k) wgmma_n256(acc, D128(dA0 + (QA & 15) * 1024 + k * 2), D128(dB0 + (QK & 15) * 1024 + k * 128), 1);
        wgmma_commit();
        if (wu) nbar<6, 256>();
#define Q_TAIL() \
        wgmma_n128_k(acc, dap, dbp + 256, 1); \
        _Pragma("unroll") for (int k = 0; k < 4; ++k) wgmma_n128(acc, D128(dA0 + (QA >> 8) * 1024 + k * 2), D128(dB0 + (QQ >> 8) * 1024 + k * 128), 1); \
        _Pragma("unroll") for (int k = 0; k < 4; ++k) wgmma_n128(acc, D128(dA0 + (QA & 15) * 1024 + k * 2), D128(dB0 + (QQ & 15) * 1024 + k * 128), 1);
        Q_TAIL();
        wgmma_commit();
        wgmma_wait<1>();
#pragma unroll
        for (int i = 0; i < 128; ++i) asm volatile("" : "+f"(acc[i]) :: "memory");
      }
    }
    uint32_t xo[32];
    {
      PHASE_CTX();
      PROFT(tid_ == 128, layer * 16 + 1);
      const bool isB = layer & 1;
      const int cu = c.cu;
      if (cu >= 4) asm volatile("bar.arrive 7, 256;" ::: "memory");
      if (elected && cu == 4) mbar_arrive(bar + B_R0);
      uint32_t kq[64];
      const uint32_t rowq = rowo & 8191;
      const float rs0 = lds_f(sb + SM_RS + (16 + wrow0 + gq) * 4), rs1 = lds_f(sb + SM_RS + (24 + wrow0 + gq) * 4);
#define Q_DONE() \
      wgmma_wait<0>(); \
      if (lane == 0) release2(bar + B_E0); \
      _Pragma("unroll") for (int i = 128; i < 192; ++i) asm volatile("" : "+f"(acc[i]) :: "memory"); \
      _Pragma("unroll") for (int i = 0; i < 32; ++i) kq[32 + i] = pack_bf16(acc[128 + 2 * i], acc[129 + 2 * i]);
      if (isB) {
        if (cu == 0) asm volatile("bar.arrive 10, 64;" ::: "memory");
        if (elected) release2(bar + B_E1);
        const int e = gq & 1;
        const bool sel = t > (gq >> 1);
        const uint32_t rja = sb + SM_RS + (wrow0 + 2 * t + e) * 4;
        const float rjA0 = lds_f(rja + 32), rjA1 = lds_f(rja + 64), rjB0 = lds_f(rja + (sel ? 0 : 64)), rjB1 = lds_f(rja + (sel ? 32 : 96));
        uint32_t vv[32];
#pragma unroll
        for (int i = 0; i < 16; ++i) { kq[i] = pack_bf16(acc[2 * i], acc[2 * i + 1]); vv[i] = pack_bf16(acc[64 + 2 * i], acc[65 + 2 * i]); }
        const uint32_t rB = sb + 4 * SLOT + wg * 4 * KVT + rowq;
        auto dump = [&](int hp) {
          const uint32_t kb = rB + 2048 + (hp ^ wg) * 2 * KVT;
#pragma unroll
          for (int jp = 0; jp < 4; ++jp) {
            stsm_x4(kb + (X ^ (jp << 5)), kq[16 * hp + 4 * jp], kq[16 * hp + 4 * jp + 1], kq[16 * hp + 4 * jp + 2], kq[16 * hp + 4 * jp + 3]);
            stsm_x4(kb + KVT + (X ^ (jp << 5)), vv[16 * hp + 4 * jp], vv[16 * hp + 4 * jp + 1], vv[16 * hp + 4 * jp + 2], vv[16 * hp + 4 * jp + 3]);
          }
          if (cu == 3) {
            const uint32_t kd = rB + 2048 + 32768 + (1 - hp) * 2 * KVT;
#pragma unroll
            for (int jp = 0; jp < 4; ++jp) {
              stsm_x4(kd + (X ^ (jp << 5)), kq[16 * hp + 4 * jp], kq[16 * hp + 4 * jp + 1], kq[16 * hp + 4 * jp + 2], kq[16 * hp + 4 * jp + 3]);
              stsm_x4(kd + KVT + (X ^ (jp << 5)), vv[16 * hp + 4 * jp], vv[16 * hp + 4 * jp + 1], vv[16 * hp + 4 * jp + 2], vv[16 * hp + 4 * jp + 3]);
            }
            if (hp) asm volatile("bar.arrive 15, 64;" ::: "memory"); else asm volatile("bar.arrive 9, 64;" ::: "memory");
          }
          asm volatile("bar.arrive %0, 224;" :: "r"(hp ? 13 + (cu >> 2) : 8 + (cu & 4)) : "memory");
        };
        uint4* const hbuf = g_halo + ((c.rb * 8 + g) * 2 + (layer >> 1)) * 512 + lane;
        if (cu < 4) {
          nbar<7, 256>();
          dump(0);
        }
#pragma unroll
        for (int i = 16; i < 32; ++i) { kq[i] = pack_bf16(acc[2 * i], acc[2 * i + 1]); vv[i] = pack_bf16(acc[64 + 2 * i], acc[65 + 2 * i]); }
        if (cu >= 4) {
          if (cu == 7) {
#pragma unroll
            for (int jp = 0; jp < 8; ++jp) {
              st_relaxed4(hbuf + jp * 32, ~kq[4 * jp], ~kq[4 * jp + 1], ~kq[4 * jp + 2], ~kq[4 * jp + 3]);
              st_relaxed4(hbuf + 256 + jp * 32, ~vv[4 * jp], ~vv[4 * jp + 1], ~vv[4 * jp + 2], ~vv[4 * jp + 3]);
            }
          }
          dump(0);
          dump(1);
        }
        PROFT(tid_ == 128, layer * 16 + 2);
        constexpr float SC = 0.17677669529663687f * L2E;
        const float fA0 = rjA0 * rs0 * SC, fB0 = rjB0 * rs0 * SC, fA1 = rjA1 * rs1 * SC, fB1 = rjB1 * rs1 * SC;
        const float bA0 = (m0 + wrow0) ? 0.f : -1e30f, bB = sel ? bA0 : 0.f;
        const uint32_t pA_ = e ? 0x1044u : 0x4410u, pB_ = e ? 0x3244u : 0x4432u, pLo = sel ? pB_ : 0x4444u, pHi = sel ? 0x4444u : pB_;
        const uint32_t KX = ((lane >> 3) ^ (lane & 7)) << 4;
        Q_DONE();
        if (cu == 0) {
          nbar<11, 64>();
        } else if (cu == 4) {
          uint4 hv[16];
          if (c.rb > 0) {
            uint32_t n = 0;
#pragma unroll 1
            while (true) {
              uint32_t mn = 0xFFFFFFFFu;
#pragma unroll
              for (int i = 0; i < 16; ++i) hv[i] = ld_relaxed4(hbuf - 16 * 512 + i * 32);
#pragma unroll
              for (int i = 0; i < 16; ++i) mn = __vimin3_u32(__vimin3_u32(mn, hv[i].x, hv[i].y), hv[i].z, hv[i].w);
              if (__all_sync(0xffffffffu, mn != 0u)) break;
              if (++n > (1u << 20)) { g_err = 4u; break; }
            }
          } else {
#pragma unroll
            for (int i = 0; i < 16; ++i) hv[i] = make_uint4(~0u, ~0u, ~0u, ~0u);
          }
          nbar<10, 64>();
#pragma unroll
          for (int i = 0; i < 16; ++i)
            stsm_x4(rB - 4 * KVT + (((i >> 2) & 1) * 2 + (i >> 3)) * KVT + (X ^ ((i & 3) << 5)), ~hv[i].x, ~hv[i].y, ~hv[i].z, ~hv[i].w);
          asm volatile("bar.arrive 11, 64;" ::: "memory");
          nbar<9, 64>();
        } else {
          nbar_dyn(8 + (cu & 4), 224);
        }
        PROFT(tid_ == 128, layer * 16 + 5);
        PROFT(lane == 0 && layer == PL, 136 + cw);
        auto attend = [&](int hp) {
          const uint32_t qad = sb + (XS + 1 - hp) * SLOT + rowo, kt = rB + 2 * (hp ^ wg) * KVT - (lane & 8) * 128, vt = rB + (2 * (hp ^ wg) + 1) * KVT;
          __syncwarp();
          uint32_t kb[2][2][4], vb[2][2][2][4];
#pragma unroll
          for (int h = 0; h < 2; ++h)
#pragma unroll
            for (int nt = 0; nt < 2; ++nt) ldsm_x4(kb[h][nt][0], kb[h][nt][1], kb[h][nt][2], kb[h][nt][3], kt + nt * 1024 + (KX ^ (h << 6)));
#pragma unroll
          for (int ks = 0; ks < 2; ++ks)
#pragma unroll
            for (int np = 0; np < 2; ++np)
#pragma unroll
              for (int h = 0; h < 2; ++h)
                ldsm_x4_t(vb[h][ks][np][0], vb[h][ks][np][1], vb[h][ks][np][2], vb[h][ks][np][3], vt + ks * 2048 + (X ^ (h << 6) ^ (np << 5)));
          if (hp == 0 && lane == 0) release2(bar + B_E3);
          if (DB1 == 1 && hp == 0 && cu < 4) dump(1);
          float la[2][2], lb[2][2], mx[2][2], sm[2][2];
#pragma unroll
          for (int h = 0; h < 2; ++h) {
            const int qo = 32 + 16 * hp + 8 * h, ko = 16 * hp + 8 * h;
            float sc[4][4];
#pragma unroll
            for (int nt = 0; nt < 4; ++nt) {
              sc[nt][0] = sc[nt][1] = sc[nt][2] = sc[nt][3] = 0.f;
#pragma unroll
              for (int ks = 0; ks < 2; ++ks)
                mma_bf16(sc[nt], kq[qo + 4 * ks], kq[qo + 4 * ks + 1], kq[qo + 4 * ks + 2], kq[qo + 4 * ks + 3],
                         nt < 2 ? kb[h][nt & 1][2 * ks] : kq[ko + 4 * ks + (nt & 1)], nt < 2 ? kb[h][nt & 1][2 * ks + 1] : kq[ko + 4 * ks + 2 + (nt & 1)]);
            }
            la[h][0] = fmaf(e ? sc[1][1] : sc[1][0], fA0, bA0);
            lb[h][0] = fmaf(sel ? (e ? sc[0][1] : sc[0][0]) : (e ? sc[2][1] : sc[2][0]), fB0, bB);
            la[h][1] = (e ? sc[2][3] : sc[2][2]) * fA1;
            lb[h][1] = fmaf(sel ? (e ? sc[1][3] : sc[1][2]) : (e ? sc[3][3] : sc[3][2]), fB1, bB);
            mx[h][0] = fmaxf(la[h][0], lb[h][0]); mx[h][1] = fmaxf(la[h][1], lb[h][1]);
          }
#pragma unroll
          for (int o = 1; o <= 2; o <<= 1)
#pragma unroll
            for (int h = 0; h < 2; ++h)
#pragma unroll
              for (int r = 0; r < 2; ++r) mx[h][r] = fmaxf(mx[h][r], __shfl_xor_sync(0xffffffffu, mx[h][r], o));
          float oa[2][4][4];
#pragma unroll
          for (int h = 0; h < 2; ++h) {
#pragma unroll
            for (int r = 0; r < 2; ++r) { la[h][r] = ex2(la[h][r] - mx[h][r]); lb[h][r] = ex2(lb[h][r] - mx[h][r]); sm[h][r] = la[h][r] + lb[h][r]; }
            const uint32_t p0 = pack_bf16(la[h][0] * rjA0, lb[h][0] * rjB0), p1 = pack_bf16(la[h][1] * rjA1, lb[h][1] * rjB1);
            const uint32_t a00 = __byte_perm(p0, 0u, pLo), a02 = __byte_perm(p0, 0u, pA_), a03 = __byte_perm(p1, 0u, pLo);
            const uint32_t a10 = __byte_perm(p0, 0u, pHi), a11 = __byte_perm(p1, 0u, pA_), a13 = __byte_perm(p1, 0u, pHi);
#pragma unroll
            for (int i = 0; i < 4; ++i) {
              oa[h][i][0] = oa[h][i][1] = oa[h][i][2] = oa[h][i][3] = 0.f;
              mma_bf16(oa[h][i], a00, 0u, a02, a03, vb[h][0][i >> 1][2 * (i & 1)], vb[h][0][i >> 1][2 * (i & 1) + 1]);
              mma_bf16(oa[h][i], a10, a11, 0u, a13, vb[h][1][i >> 1][2 * (i & 1)], vb[h][1][i >> 1][2 * (i & 1) + 1]);
            }
          }
#pragma unroll
          for (int o = 1; o <= 2; o <<= 1)
#pragma unroll
            for (int h = 0; h < 2; ++h)
#pragma unroll
              for (int r = 0; r < 2; ++r) sm[h][r] += __shfl_xor_sync(0xffffffffu, sm[h][r], o);
          mbar_wait(bar + (hp ? B_XOLD2 : B_XOLD), 1);
#pragma unroll
          for (int jp = 0; jp < 4; ++jp) ldsm_x4(xo[16 * hp + 4 * jp], xo[16 * hp + 4 * jp + 1], xo[16 * hp + 4 * jp + 2], xo[16 * hp + 4 * jp + 3], qad + (X ^ (jp << 5)));
#pragma unroll
          for (int h = 0; h < 2; ++h) {
            const float i0 = rcp(sm[h][0]), i1 = rcp(sm[h][1]);
#pragma unroll
            for (int np = 0; np < 2; ++np)
              stsm_x4(qad + (X ^ (h << 6) ^ (np << 5)),
                      pack_bf16(oa[h][2 * np][0] * i0, oa[h][2 * np][1] * i0), pack_bf16(oa[h][2 * np][2] * i1, oa[h][2 * np][3] * i1),
                      pack_bf16(oa[h][2 * np + 1][0] * i0, oa[h][2 * np + 1][1] * i0), pack_bf16(oa[h][2 * np + 1][2] * i1, oa[h][2 * np + 1][3] * i1));
          }
          __syncwarp();
          slab_out_half(sb + (XS + 1 - hp) * SLOT, g_o + (size_t)m0 * D_ + g * 128 + hp * 64, wrow0, lane, hp);
          __syncwarp();
          if (lane == 0) mbar_arrive(bar + (hp ? B_ODONE : B_OH1));
          PROFT(lane == 0 && layer == PL && hp == 0, 128 + cw);
        };
        attend(0);
        if (DB1 == 2 && cu < 4) dump(1);
        if (cu == 4) nbar<15, 64>();
        else if (cu != 0) nbar_dyn(13 + (cu >> 2), 224);
        attend(1);
      } else {
#pragma unroll
        for (int i = 0; i < 32; ++i) kq[i] = pack_bf16(acc[2 * i], acc[2 * i + 1]);
        if (cu < 4) nbar<7, 256>();
        {
          const uint32_t vb = sb + (5 + 3 * wg) * SLOT + (rowq >> 1) + ((lchk ^ ((lane & 7) >> 1)) << 4);
#pragma unroll
          for (int jp = 8; jp < 16; ++jp)
            stsm_x4((vb ^ ((jp & 1) << 5)) + ((jp >> 1) & 3) * 4096,
                    pack_bf16(acc[8 * jp], acc[8 * jp + 1]), pack_bf16(acc[8 * jp + 2], acc[8 * jp + 3]),
                    pack_bf16(acc[8 * jp + 4], acc[8 * jp + 5]), pack_bf16(acc[8 * jp + 6], acc[8 * jp + 7]));
        }
        PROFT(tid_ == 128, layer * 16 + 2);
        Q_DONE();
        const uint32_t pA = sb + (3 + 3 * wg) * SLOT + (rowo & 8191);
        float sc0 = rs0 * L2E, sc1 = rs1 * L2E;
        const uint32_t wa0 = sb + SM_WPHI + lrow * 80 + lchk * 16;
        const uint32_t wu = c.cu >> 2, par = (layer >> 1) & 1;
        float p[2][4][4];
        uint32_t raw[2][4][4], ph[2][4][4];
        float kva[20], oa[2][20];
        auto kv_start = [&](int hp) {
#pragma unroll
          for (int h = 0; h < 2; ++h)
#pragma unroll
            for (int cp = 0; cp < 4; ++cp)
              stsm_x4(pA + hp * 16384 + h * 8192 + (X ^ (cp << 5)), ph[h][cp][0], ph[h][cp][1], ph[h][cp][2], ph[h][cp][3]);
          PROFT(tid_ == 128, layer * 16 + 11);
          fence_async_smem();
          nbar<1, 256>();
          const uint32_t hu = 2 * hp + wu;
          const uint32_t dP = (((sb + 3 * SLOT + hu * 8192) & 0x3FFFF) >> 4) | (512u << 16);
          const uint32_t dV = (((sb + 5 * SLOT + hu * 4096) & 0x3FFFF) >> 4) | (((SM_SD - 5 * SLOT - hu * 4096) >> 4) << 16);
          wgmma_fence();
#pragma unroll
          for (int ks = 0; ks < 8; ++ks)
            wgmma_n40_tt(kva, desc64(dP + (ks >> 2) * 3072 + (ks & 3) * 128, 0x40000040u),
                         desc64(dV + (ks >> 2) * (3072u - (2816u << 16)) + (ks & 3) * 64, 0x80000020u), ks != 0);
          wgmma_commit();
        };
        auto kv_end = [&](int hp) {
          wgmma_wait<0>();
#pragma unroll
          for (int i = 0; i < 20; ++i) asm volatile("" : "+f"(kva[i]) :: "memory");
          nbar_dyn(3 + wu, 128);
          PROFT(tid_ == 128, layer * 16 + 12);
          const bool od = lane & 1;
#pragma unroll
          for (int i = 0; i < 4; ++i)
            sts128(sb + (3 + hp) * SLOT + (cw * 128 + i * 32 + lane) * 16,
                   make_uint4(__float_as_uint(kva[4 * i]), __float_as_uint(kva[4 * i + 1]), __float_as_uint(kva[4 * i + 2]),
                              __float_as_uint(od == (i >= 2) ? 1.f : kva[4 * i + 3])));
          sts128(sb + (6 + hp) * SLOT + wg * 8192 + (wq * 32 + lane) * 16,
                 make_uint4(__float_as_uint(od ? kva[11] : kva[3]), __float_as_uint(od ? kva[15] : kva[7]), __float_as_uint(od ? kva[18] : kva[16]), __float_as_uint(1.f)));
          fence_async_smem();
          __syncwarp();
          if (lane == 0) mbar_arrive(bar + B_KVDONE - hp * 32);
          PROFT(tid_ == 128, layer * 16 + 3);
        };
        const uint4* const kvg = g_kv + (g * 2 + (layer >> 1)) * 2560 + cw * 128 + lane;
        uint4 u[5];
        auto kv_load = [&](int hp) {
#pragma unroll
          for (int i = 0; i < 4; ++i) u[i] = ld_relaxed4(kvg + hp * 1280 + i * 32);
          u[4] = ld_relaxed4(kvg + hp * 1280 + 1024 - cw * 96);
        };
        auto o_start = [&](int hp, const uint32_t (&pq)[2][4][4]) {
          PROFT(tid_ == 128 && hp == 0, layer * 16 + 10);
          if (hp == 0) mbar_wait(bar + B_KVDONE - 32, par);
          const bool od = lane & 1;
          uint32_t n = 0;
#pragma unroll 1
          while (!__all_sync(0xffffffffu, (od ? u[2].w : u[0].w) == 0x41800000u && (od ? u[3].w : u[1].w) == 0x41800000u && u[4].w == 0x41800000u)) {
#pragma unroll 1
            while (__any_sync(0xffffffffu, u[4].w < KVTH) && ++n < (1u << 20)) u[4].w = ld_relaxed(&kvg[hp * 1280 + 1024 - cw * 96].w);
            if (++n > (1u << 20)) { g_err = 6u; break; }
            kv_load(hp);
          }
          PROFT(tid_ == 128 && hp == 0, layer * 16 + 5);
          if (!od) { u[0].w = u[4].x; u[1].w = u[4].y; } else { u[2].w = u[4].x; u[3].w = u[4].y; }
#pragma unroll
          for (int i = 0; i < 4; i += 2)
            stsm_x4(sb + (5 + 3 * hp) * SLOT + rowo + (X ^ ((i & 2) << 4)),
                    pack_bf16(__uint_as_float(u[i].x), __uint_as_float(u[i].y)), pack_bf16(__uint_as_float(u[i].z), __uint_as_float(u[i].w)),
                    pack_bf16(__uint_as_float(u[i + 1].x), __uint_as_float(u[i + 1].y)), pack_bf16(__uint_as_float(u[i + 1].z), __uint_as_float(u[i + 1].w)));
          const uint32_t z2 = pack_bf16(__uint_as_float(u[4].z), __uint_as_float(u[4].z));
          if (t < 2) sts128(sb + (5 + 3 * hp) * SLOT + (wrow0 + gq + 8 * t) * 128 + ((4 ^ gq) << 4), make_uint4(z2, z2, z2, z2));
          fence_async_smem();
          nbar<1, 256>();
          PROFT(tid_ == 128 && hp == 1, layer * 16 + 4);
          const uint32_t dK = (((sb + (5 + 3 * hp) * SLOT) & 0x3FFFF) >> 4) | (512u << 16);
          wgmma_fence();
#pragma unroll
          for (int ks = 0; ks < 4; ++ks) {
#pragma unroll
            for (int hh = 0; hh < 2; ++hh) wgmma_n40_rs(oa[hh], pq[hh][ks], D128(dK + hh * 512 + ks * 128), ks != 0);
          }
          wgmma_commit();
        };
        auto o_end = [&](int hp) {
          wgmma_wait<0>();
#pragma unroll
          for (int i = 0; i < 20; ++i) asm volatile("" : "+f"(oa[0][i]), "+f"(oa[1][i]) :: "memory");
#pragma unroll
          for (int hh = 0; hh < 2; ++hh) {
            const float i0 = rcp(oa[hh][16] + 1e-6f), i1 = rcp(oa[hh][18] + 1e-6f);
            const uint32_t qad = sb + (3 + hp) * SLOT + rowo, hx = hh << 6;
#pragma unroll
            for (int np = 0; np < 2; ++np)
              stsm_x4(qad + (X ^ hx ^ (np << 5)),
                      pack_bf16(oa[hh][8 * np] * i0, oa[hh][8 * np + 1] * i0), pack_bf16(oa[hh][8 * np + 2] * i1, oa[hh][8 * np + 3] * i1),
                      pack_bf16(oa[hh][8 * np + 4] * i0, oa[hh][8 * np + 5] * i0), pack_bf16(oa[hh][8 * np + 6] * i1, oa[hh][8 * np + 7] * i1));
          }
          __syncwarp();
          slab_out_half(sb + (3 + hp) * SLOT, g_o + (size_t)m0 * D_ + g * 128 + hp * 64, wrow0, lane, hp);
          __syncwarp();
          if (lane == 0) mbar_arrive(bar + (hp ? B_ODONE : B_OH1));
        };
#define XO_LOAD() \
        mbar_wait(bar + B_XOLD, 0); \
        mbar_wait(bar + B_XOLD2, 0); \
        _Pragma("unroll") for (int jp = 0; jp < 8; ++jp) \
          ldsm_x4(xo[4 * jp], xo[4 * jp + 1], xo[4 * jp + 2], xo[4 * jp + 3], sb + (XS + 1 - (jp >> 2)) * SLOT + rowo + (X ^ ((jp & 3) << 5)));
#define SC_RELOAD() \
        sc0 = __uint_as_float(lds_vol(sb + SM_RS + (16 + wrow0 + gq) * 4)) * L2E; sc1 = __uint_as_float(lds_vol(sb + SM_RS + (24 + wrow0 + gq) * 4)) * L2E;
        __syncwarp();
        phi_proj<0>(p, kq, wa0);
        phi_exp(raw[0], p[0], sc0, sc1);
        phi_exp(raw[1], p[1], sc0, sc1);
        phi_proj<16>(p, kq, wa0 + 5120);
        phi_norm<0>(ph, raw, kq, wa0, sc0, sc1, rs0, rs1);
        kv_start(0);
        phi_exp(raw[0], p[0], sc0, sc1);
        kv_end(0);
        if (RL & 1) { SC_RELOAD(); }
        XO_LOAD();
        phi_exp(raw[1], p[1], sc0, sc1);
        phi_proj<32>(p, kq, wa0);
        phi_norm<16>(ph, raw, kq, wa0 + 5120, sc0, sc1, rs0, rs1);
        kv_start(1);
        if (lane == 0) release2(bar + B_E3);
        phi_exp(raw[0], p[0], sc0, sc1);
        kv_end(1);
        if (RL & 2) { SC_RELOAD(); }
        kv_load(0);
        phi_exp(raw[1], p[1], sc0, sc1);
        phi_proj<48>(p, kq, wa0 + 5120);
        phi_norm<32>(ph, raw, kq, wa0, sc0, sc1, 1.f, 1.f);
        o_start(0, ph);
        phi_exp(raw[0], p[0], sc0, sc1);
        o_end(0);
        SC_RELOAD();
        kv_load(1);
        phi_exp(raw[1], p[1], sc0, sc1);
        phi_norm<48>(ph, raw, kq, wa0 + 5120, sc0, sc1, 1.f, 1.f);
        o_start(1, ph);
        o_end(1);
      }
      __syncwarp();
      PROFT(lane == 0 && layer == PL, 216 + cw);
      if (lane == 0) mbar_arrive(bar + B_EPI);
      PROFT(tid_ == 128, layer * 16 + 6);
    }
    {
      PHASE_CTX();
      const uint32_t wu = c.cu >> 2;
      const uint32_t dA0 = (((sb + wu * 8192) & 0x3FFFF) >> 4) | (1u << 16), dB0 = ((sb & 0x3FFFF) >> 4) | (512u << 16);
#pragma unroll
      for (int i = 0; i < 32; ++i) { acc[128 + 2 * i] = bf_lo(xo[i]); acc[129 + 2 * i] = bf_hi(xo[i]); }
      nbar_dyn(3 + wg, 128);
      uint64_t ta = (layer & 1) ? WO_A1 : WO_A0, tw = (layer & 1) ? WO_B1 : WO_B0;
#pragma unroll 1
      for (int i = 0; i < 16; ++i) {
        bool rel = i > 0 && i < 12;
        if (DRY && rel && !__all_sync(0xffffffffu, mbar_test_wait(bar + B_FULLT + i * 8, layer & 1))) {
          wgmma_wait<0>();
          if (elected) release2(bar + B_CONS + (i - 1) * 8);
          rel = false;
        }
        mbar_wait(bar + B_FULLT + i * 8, layer & 1);
        PROFT(tid_ == 128 && layer == PL, 160 + i);
        const uint32_t da = dA0 + ((uint32_t)ta & 15) * 1024, db = dB0 + ((uint32_t)tw & 15) * 1024;
        ta >>= 4; tw >>= 4;
        wgmma_fence();
#pragma unroll
        for (int k = 0; k < 4; ++k) wgmma_n128(acc, D128(da + k * 2), D128(db + k * 128), 1);
        wgmma_commit();
        if (i == 0) {
          if (elected) {
            release2(bar + B_E2);
          }
        } else {
          wgmma_wait<1>();
          if (elected && rel) release2(bar + B_CONS + (i - 1) * 8);
          if (elected && (unsigned)(i - 13) < 2u && layer + 1 < NLAYERS) release2(bar + B_EMPTYS + (i - 13) * 8);
        }
      }
      const bool last = layer == NLAYERS - 1;
      wgmma_wait<0>();
#pragma unroll
      for (int i = 128; i < 192; ++i) asm volatile("" : "+f"(acc[i]) :: "memory");
      if (elected && !last) release2(bar + B_EMPTYS + 16);
      PROFT(tid_ == 128, layer * 16 + 7);
#pragma unroll
      for (int jp = 0; jp < 4; ++jp)
        stsm_x4(sb + XS * SLOT + rowo + (X ^ (jp << 5)),
                pack_bf16(acc[128 + 8 * jp], acc[129 + 8 * jp]), pack_bf16(acc[130 + 8 * jp], acc[131 + 8 * jp]),
                pack_bf16(acc[132 + 8 * jp], acc[133 + 8 * jp]), pack_bf16(acc[134 + 8 * jp], acc[135 + 8 * jp]));
      if (last) {
        __syncwarp();
        slab_out_half(sb + XS * SLOT, c.out + (size_t)m0 * D_ + g * 128, wrow0, lane);
        X_H1();
        __syncwarp();
        slab_out_half(sb + (XS + 1) * SLOT, c.out + (size_t)m0 * D_ + g * 128 + 64, wrow0, lane);
        __syncwarp();
        if (lane == 0) mbar_arrive(bar + B_XDONE);
        PROFT(tid_ == 128, layer * 16 + 24);
        break;
      }
      __syncwarp();
      slab_out_half(sb + XS * SLOT, g_x + (size_t)m0 * D_ + g * 128, wrow0, lane, true);
      __syncwarp();
      if (lane == 0) mbar_arrive(bar + B_XH0);
      nbar_dyn(3 + wu, 128);
    }
  }
}

__device__ __forceinline__ void flag_fetch(uint32_t bar, uint32_t cp, const unsigned int* f) {
  asm volatile("{\n.reg .pred p;\nelect.sync _|p, 0xffffffff;\n@p mbarrier.expect_tx.relaxed.cta.shared::cta.b64 [%2], 64;\n"
               "@p cp.async.bulk.shared::cluster.global.mbarrier::complete_tx::bytes [%0], [%1], 64, [%2];\n}\n"
               ::"r"(cp), "l"(f), "r"(bar + 128) : "memory");
}
__device__ __forceinline__ void src_wait_async(uint32_t bar, uint32_t cp, const unsigned int* f, unsigned int target, int kb, uint32_t& ready, int lane) {
  uint32_t n = 0;
#pragma unroll 1
  while (true) {
    ready |= __ballot_sync(0xffffffffu, (int)(lds_vol(cp + (lane & 15) * 4) - target) >= 0);
    if ((ready >> kb) & 1) break;
    if (n > (1u << 20)) { g_err = 5u; break; }
    if ((n++ & PMOD) == 0) flag_fetch(bar, cp, f);
    __nanosleep(PSL);
  }
}

__device__ __forceinline__ int kblock0(int i, int g) {
  const int j = i >> 1, p = max(g, NCOM) + j - NCOM;
  return (j < NCOM ? j : p < 8 ? p : p - 8 + NCOM) * 2 + (i & 1);
}

#define WOORD 0xFDB9753ECA864210ull
__device__ __forceinline__ int wo_kblock(int m, int g) { return (2 * g + (int)((WOORD >> (4 * m)) & 15)) & 15; }

__global__ void __cluster_dims__(2, 1, 1) __launch_bounds__(384, 1)
mega_kernel(const __grid_constant__ CUtensorMap tm_x0, const __grid_constant__ CUtensorMap tm_x,
            const __grid_constant__ CUtensorMap tm_o,
            const __grid_constant__ CUtensorMap tm_wA, const __grid_constant__ CUtensorMap tm_wB,
            const __grid_constant__ CUtensorMap tm_woA, const __grid_constant__ CUtensorMap tm_woB,
                        const bf16* __restrict__ wB, const bf16* __restrict__ wphi, bf16* __restrict__ out) {
  extern __shared__ uint8_t smem_raw[];
  const uint32_t sb = (smem_u32(smem_raw) + 1023u) & ~1023u;
  const uint32_t bar = sb + SM_BAR;
  const int warp = __shfl_sync(0xffffffffu, threadIdx.x >> 5, 0), lane = threadIdx.x & 31;
  if (blockIdx.x >= 128) {
    const int xb = blockIdx.x - 128;
    const int ch = threadIdx.x % 96, rg = threadIdx.x / 96, gg = xb * 2 + ch / 48, sec = (ch % 48) >> 4;
    const uint4* src = reinterpret_cast<const uint4*>(wB + (size_t)rg * 3072 + (sec == 2 ? 0 : 1024 + sec * 1024) + gg * 128 + (ch & 15) * 8);
    float s[8] = {0.f, 0.f, 0.f, 0.f, 0.f, 0.f, 0.f, 0.f};
#pragma unroll 1
    for (int r0 = 0; r0 < 256; r0 += 32) {
      uint4 v[32];
#pragma unroll
      for (int r = 0; r < 32; ++r) v[r] = __ldg(src + (size_t)(r0 + r) * 1536);
#pragma unroll
      for (int r = 0; r < 32; ++r) {
        s[0] += bf_lo(v[r].x); s[1] += bf_hi(v[r].x); s[2] += bf_lo(v[r].y); s[3] += bf_hi(v[r].y);
        s[4] += bf_lo(v[r].z); s[5] += bf_hi(v[r].z); s[6] += bf_lo(v[r].w); s[7] += bf_hi(v[r].w);
      }
    }
    float* cd = g_cs + (ld_relaxed(&g_epoch) & 1) * 6144 + 3072 + xb * 768 + ch * 8;
    red_add4(cd, s[0], s[1], s[2], s[3]);
    red_add4(cd + 4, s[4], s[5], s[6], s[7]);
    nbar<1, 384>();
    if (threadIdx.x < 2) flag_add(&g_csflag[8 + xb * 2 + threadIdx.x].v);
    return;
  }
  const int bid = blockIdx.x;
  const int cr = bid & 1;
  const int g = (bid >> 1) & 7;
  const int rb = (bid >> 4) * 2 + cr;
  const int m0 = rb * 128;

  if (warp < 4) {
    asm volatile("setmaxnreg.dec.sync.aligned.u32 40;");
    asm volatile("barrier.cluster.arrive.relaxed.aligned;" ::: "memory");
    const unsigned int epoch = warp ? ld_relaxed(&g_epoch) : 0u;
    if (warp) cluster_wait();
    unsigned int xbase = epoch * NLAYERS;
    auto wo_a = [&](int layer) {
      uint64_t ts = ((layer & 1) ? WO_A1 : WO_A0) >> 8, td = ((layer & 1) ? WO_DA1 : WO_DA0) >> 8, tk = WOORD >> 8;
      uint32_t ready = 0u;
#pragma unroll 1
      for (int m = 2; m < 16; ++m) {
        const int kb = (2 * g + (uint32_t)tk) & 15;
        uint32_t dst = sb + ((uint32_t)ts & 15) * SLOT, fb = bar + B_FULLT + m * 8, eb = bar + B_CONS + ((uint32_t)td & 15) * 8;
        int kc = kb * 64;
        ts >>= 4; td >>= 4; tk >>= 4;
        asm volatile("" : "+r"(dst), "+r"(fb), "+r"(eb), "+r"(kc));
        bool fr = false;
        if (!((ready >> kb) & 1)) {
          PROFT(m == 2 && lane == 0, 64 + layer * 16 + 2);
          if (EP && m > EP) src_wait_async(bar, bar + B_FLG, g_of + rb * 32, xbase + layer + 1, kb, ready, lane);
          else fr = src_wait_tma(g_of + rb * 32, xbase + layer + 1, 1u << kb, ready, lane, eb, layer & 1);
          fence_async_all();
        }
        if (!fr) mbar_wait_u(eb, layer & 1);
        tma_2d_e(dst, &tm_o, kc, m0, fb);
        if (EP && m >= EP && (ready & 0xFFFFu) != 0xFFFFu) flag_fetch(bar, bar + B_FLG, g_of + rb * 32);
        PROFT(lane == 0 && layer == PL, 176 + m);
      }
    };
    auto wo_w = [&](int layer) {
      const CUtensorMap* tx = layer == 0 ? &tm_x0 : &tm_x;
      const CUtensorMap* two = (layer & 1) ? &tm_woB : &tm_woA;
      uint64_t ts = (layer & 1) ? WO_B1 : WO_B0, td = (layer & 1) ? WO_DB1 : WO_DB0, tk = WOORD;
      uint32_t pb = 0;
      fence_async_all();
      mbar_wait_u(bar + B_R0, layer & 1);
      expect_tx_e(bar + B_XOLD, 16384);
      tma_2d_e(sb + (XS + 1) * SLOT, tx, g * 128, m0, bar + B_XOLD);
#pragma unroll 1
      for (int m = 0; m < 16; ++m) {
        uint32_t dst = sb + ((uint32_t)ts & 15) * SLOT + cr * 8192, fb = bar + B_FULLT + m * 8, eb = bar + B_CONS + ((uint32_t)td & 15) * 8;
        int kc = ((2 * g + (uint32_t)tk) & 15) * 64;
        ts >>= 4; td >>= 4; tk >>= 4;
        asm volatile("" : "+r"(dst), "+r"(fb), "+r"(eb), "+r"(kc));
        if (eb != pb) mbar_wait_u(eb, layer & 1);
        pb = eb;
        tma_2d_mc_e(dst, two, g * 128 + cr * 64, kc, fb);
        expect_tx_e(fb, m < 2 ? 16384 : 32768);
        PROFT(lane == 0 && layer == PL, 144 + m);
        if (m == ((layer & 1) ? XB2 : 0)) {
          expect_tx_e(bar + B_XOLD2, 16384);
          tma_2d_e(sb + XS * SLOT, tx, g * 128 + 64, m0, bar + B_XOLD2);
        }
      }
    };
    if (warp == 0) {
      cluster_wait();
      PROFT(lane == 0, 125);
#pragma unroll 1
      for (int layer = 0; layer < NLAYERS; ++layer) {
        const CUtensorMap* tx = layer == 0 ? &tm_x0 : &tm_x;
        const CUtensorMap* tw = (layer & 1) ? &tm_wB : &tm_wA;
        uint32_t s = layer == 0, u = 0, ready = layer == 0 ? 0xFFFFu : 0u;
#pragma unroll 1
        for (int i = s; i < 16; ++i) {
          const int kb = layer == 0 ? kblock0(i, g) : wo_kblock(i, g), kc = kb * 64;
          const uint32_t fb = bar + B_FULLS + s * 8;
          const uint32_t kd = sb + (((QK >> (4 * s)) & 15) + cr) * SLOT, qd = sb + ((QQ >> (4 * s)) & 15) * SLOT + cr * 8192;
          const uint32_t need = 1u << kb;
          const bool ext = i >= 2 || layer == 0, early = ext && (ready & need) == need;
          mbar_wait_u(bar + B_EMPTYS + s * 8, (u + (s ? layer : 0) + 1) & 1);
          if (early) tma_2d_e(sb + ((QA >> (4 * s)) & 15) * SLOT, tx, kc, m0, fb);
          tma_2d_mc_e(kd, tw, 1024 + cr * 1024 + g * 128, kc, fb);
          tma_2d_mc_e(kd + 8192, tw, 1024 + cr * 1024 + g * 128 + 64, kc, fb);
          tma_2d_mc_e(qd, tw, g * 128 + cr * 64, kc, fb);
          expect_tx_e(fb, ext ? 65536 : 49152);
          PROFT(lane == 0 && layer == 0 && i == 1, 31);
          if (layer == 0 && i == 2) {
            mbar_wait_u(bar + B_FULLS, 0);
            tma_pf_e(&tm_x0, g * 128, m0);
            tma_pf_e(&tm_x0, g * 128 + 64, m0);
          }
          if (layer < 2 && i >= PFS) {
            const int j = i - PFS;
            if (j < 2) tma_pf_e(layer ? &tm_woB : &tm_woA, g * 128 + j * 64, rb * 64);
            else if (j < 8 && layer == 0) tma_pf_e(&tm_wB, ((j >> 1) - 1) * 1024 + g * 128 + (j & 1) * 64, rb * 64);
          }
          if (ext && !early) {
            PROFT(i == 2 && lane == 0, 64 + layer * 16 + 0);
            src_wait_tma(g_xf + rb * 32, xbase + layer + 1, need, ready, lane, fb, 0);
            PROFT(i == 2 && lane == 0, 64 + layer * 16 + 1);
            fence_async_all();
            tma_2d_e(sb + ((QA >> (4 * s)) & 15) * SLOT, tx, kc, m0, fb);
          }
          if (++s == 3) { s = 0; ++u; }
        }
        if (layer == 0) xbase = ld_relaxed(&g_epoch) * NLAYERS;
        wo_a(layer);
      }
    } else {
      if (warp >= 2) {
        const int h2 = threadIdx.x - 64;
        if (h2 < 16) sts_f(sb + SM_RS + h2 * 4, 0.f);
        if (h2 < 16) sts_f(bar + B_FLG + h2 * 4, __uint_as_float(xbase));
        mbar_wait_u(bar + B_FULLS, 0);
        colsum(&tm_wA, g_cs + (epoch & 1) * 6144, rb, g, warp - 2, 2, lane, warp == 2 ? sb + SM_SD : (sb + SM_BP + 1023u) & ~1023u, bar + B_CB + (warp - 2) * 8, 0);
#pragma unroll 1
        for (int i = h2; i < 320; i += 64) g_kv[(g * 16 + rb) * 320 + i] = make_uint4(0u, 0u, 0u, 0u);
        fence_async_all();
        nbar<5, 64>();
        if (h2 == 0) flag_add(&g_csflag[g].v);
        PROFT(h2 == 0, 242);
#pragma unroll 1
        for (int i = h2; i < 512; i += 256) {
          uint4 w[4];
#pragma unroll
          for (int j = 0; j < 4; ++j) w[j] = __ldg(reinterpret_cast<const uint4*>(wphi + (size_t)g * 4096) + i + j * 64);
#pragma unroll
          for (int j = 0; j < 4; ++j) sts128(sb + SM_WPHI + ((i >> 2) + j * 16) * 80 + (i & 3) * 16, w[j]);
        }
      }
      if (warp == 1) {
        if (lane >= 27) {
          const CUtensorMap* tm = lane == 27 ? &tm_o : lane == 28 ? &tm_wB : lane == 29 ? &tm_woA : lane == 30 ? &tm_woB : &tm_x;
          asm volatile("prefetch.tensormap [%0];" ::"l"(tm) : "memory");
        }
        __syncwarp();
        {
#pragma unroll 1
          for (int e = 0;; ++e) {
            if (e > 0 && e < NLAYERS) {
              mbar_wait_u(bar + B_XH0, (e - 1) & 1);
              flag_set(g_xf + rb * 32 + 2 * g, xbase + e + 1);
            }
            mbar_wait_u(bar + B_XDONE, e & 1);
            PROFT(e < 4, 64 + e * 16 + 4);
            if (e == NLAYERS) {
              if (bid == 0) g_epoch = epoch + 1;
              break;
            }
            PROFT(e < 4, 64 + e * 16 + 5);
            flag_set(g_xf + rb * 32 + 2 * g + 1, xbase + e + 1);
            PROFT(e < 4, 64 + e * 16 + 7);
            if ((e & 1) == 0) {
#pragma unroll 1
              for (int hp = 0; hp < 2; ++hp) {
                uint4* kvl = g_kv + ((g * 2 + (e >> 1)) * 2 + hp) * 1280;
                mbar_wait_u(bar + B_KVDONE - hp * 32, (e >> 1) & 1);
                PROFT(e == PL, 243 + hp * 4);
                bulk_red_add_e(kvl + rb * 64, sb + (3 + hp) * SLOT + rb * 1024, 16384 - rb * 1024);
                if (rb) bulk_red_add_e(kvl, sb + (3 + hp) * SLOT, rb * 1024);
                bulk_red_add_e(kvl + 1024, sb + (6 + hp) * SLOT, 2048);
                bulk_red_add_e(kvl + 1152, sb + (6 + hp) * SLOT + 8192, 2048);
                bulk_commit();
                PROFT(e < 4, 64 + e * 16 + 6);
              }
              bulk_wait_read0();
              __syncwarp();
              if (lane < 2) release2(bar + B_E1);
              __syncwarp();
            }
            mbar_wait_u(bar + B_OH1, e & 1);
            PROFT(e == PL, 251);
            flag_set(g_of + rb * 32 + 2 * g, xbase + e + 1);
            PROFT(e < 4, 64 + e * 16 + 9);
            mbar_wait_u(bar + B_ODONE, e & 1);
            PROFT(e < 4, 64 + e * 16 + 8);
            flag_set(g_of + rb * 32 + 2 * g + 1, xbase + e + 1);
            PROFT(e < 4, 64 + e * 16 + 11);
          }
        }
      } else {
        const int h2 = threadIdx.x - 64;
        const float* cs = g_cs + (epoch & 1) * 6144;
#pragma unroll 1
        for (int layer = 0; layer < NLAYERS; ++layer) {
          if (warp == 2 && layer < 2) {
            if (lane == 0) flag_wait_t<CSLP>(&g_csflag[layer * 8 + g].v, (epoch + 1) * (16u + layer));
            __syncwarp();
            float4 a[3];
#pragma unroll
            for (int i = 0; i < 3; ++i) a[i] = __ldcg(reinterpret_cast<const float4*>(cs + layer * 3072 + g * 384) + i * 32 + lane);
#pragma unroll 1
            for (int i = 0; i < 3; ++i) {
              const float av[4] = {a[0].x, a[0].y, a[0].z, a[0].w};
              a[0] = a[1]; a[1] = a[2];
#pragma unroll
              for (int j = 0; j < 4; ++j) {
                const float c1 = bf16r(av[j]), c2 = bf16r(av[j] - c1), c3 = (av[j] - c1) - c2;
                sts128(sb + SM_BP + layer * 6144 + ((i * 32 + lane) * 4 + j) * 16, make_uint4(pack_bf16(c1, c2), pack_bf16(c3, 0.f), 0u, 0u));
              }
            }
            fence_async_smem();
            __syncwarp();
            if (lane == 0) mbar_arrive(bar + (layer ? B_CS2 : B_CS));
            PROFT(lane == 0, 64 + layer * 16 + 12);
            if (layer == 0) {
              uint4* hz = g_halo + (rb * 8 + g) * 1024;
#pragma unroll 2
              for (int i = lane; i < 1024; i += 32) hz[i] = make_uint4(0u, 0u, 0u, 0u);
              if (lane < 12) reinterpret_cast<float4*>(g_cs + ((epoch & 1) ^ 1) * 6144 + bid * 48)[lane] = make_float4(0.f, 0.f, 0.f, 0.f);
              g_stats[(2 + (lane >> 4)) * S_ + m0 + g * 16 + (lane & 15)] = make_float2(0.f, 0.f);
              __syncwarp();
              if (lane == 0) flag_add(&g_csflag[8 + g].v);
            }
          }
          if (warp == 3) {
            const bool hal = (layer & 1) && rb > 0;
            {
              uint32_t rdy = 0u;
              src_wait<256>(g_xf + rb * 32, xbase + layer + 1, 0xAAAAu, rdy, lane);
              rdy = 0u;
              if (hal) src_wait<256>(g_xf + (rb - 1) * 32, xbase + layer + 1, 0xAAAAu, rdy, lane);
            }
            float2 u[5];
            const float2* sp = g_stats + layer * S_ + m0 + lane;
#pragma unroll
            for (int i = 0; i < 4; ++i) u[i] = __ldcg(sp + i * 32);
            u[4] = __ldcg(hal ? sp - 16 : sp);
            if (layer == 3) g_stats[(lane >> 4) * S_ + m0 + g * 16 + (lane & 15)] = make_float2(0.f, 0.f);
#pragma unroll 1
            for (int i = 0; i < (hal ? 5 : 4); ++i) {
              const int r = i < 4 ? 16 + i * 32 + lane : lane;
              const float sum = u[0].x, sq = u[0].y;
              u[0] = u[1]; u[1] = u[2]; u[2] = u[3]; u[3] = u[4];
              const float mean = sum * (1.f / D_);
              const float var = fmaxf(fmaf(-sum, mean, sq) * (1.f / D_), 0.f);
              const float sd = bf16r(sqrtf(bf16r(bf16r(var) + 1e-5f)));
              sts_f(sb + SM_RS + r * 4, 1.f / sd);
              if (i < 4) {
                const float hm = -0.5f * bf16r(mean);
                const uint32_t s2 = pack_bf16(sd, sd);
                if (!(layer & 1)) sts128(sb + SM_SD + (r - 16) * 64 + ((r >> 1) & 3) * 16, make_uint4(s2, s2, s2, s2));
                sts128(sb + SM_AP + (r - 16) * 16, make_uint4(pack_bf16(hm, hm), pack_bf16(hm, 0.f), 0u, 0u));
              }
            }
            fence_async_smem();
            __syncwarp();
            if (lane == 0) mbar_arrive(bar + B_STAT);
            PROFT(lane == 0, 64 + layer * 16 + 14);
            wo_w(__shfl_sync(0xffffffffu, layer, 0));
          }
        }
      }
    }
    __syncwarp();
    asm volatile("barrier.cluster.arrive.relaxed.aligned;\nbarrier.cluster.wait.aligned;\n" ::: "memory");
  } else {
    if (warp == 5) {
      if (lane == 0) {
        mbar_init(bar + B_FULLS, 1);
        asm volatile("fence.mbarrier_init.release.cluster;" ::: "memory");
      }
      __syncwarp();
      expect_tx_e(bar + B_FULLS, 65536);
      tma_2d_e(sb + XS * SLOT, &tm_x0, 0, m0, bar + B_FULLS);
#pragma unroll
      for (int j = 0; j < 6; ++j)
        tma_2d_e(sb + (j < 4 ? j + 4 : j - 2) * 8192, &tm_wA, (j < 4 ? 1024 + (j >> 1) * 1024 : 0) + g * 128 + (j & 1) * 64, 0, bar + B_FULLS);
      PROFT(lane == 0, 241);
    }
    if (lane < 8 && warp != 5 && threadIdx.x != 128) {
      const int i = (warp - 4) * 8 + lane;
      mbar_init(bar + i * 8, i < 32 ? 1u << ((BAR_CNT >> (2 * i)) & 3) : i < 48 ? 1u : (i == 59 || i == 60) ? 16u : i < 63 ? 4u : 8u);
      asm volatile("fence.mbarrier_init.release.cluster;" ::: "memory");
    }
    __syncwarp();
    asm volatile("barrier.cluster.arrive.relaxed.aligned;" ::: "memory");
    asm volatile("setmaxnreg.inc.sync.aligned.u32 232;");
    cluster_wait();
    PROFT(threadIdx.x == 128, 0);
    Ctx c; c.sb = sb; c.g = g; c.rb = rb; c.cu = warp - 4; c.out = out;
    consumer(c);
    asm volatile("bar.warp.sync 0xffffffff;\nbarrier.cluster.arrive.relaxed.aligned;\nbarrier.cluster.wait.aligned;\n" ::: "memory");
  }
}

typedef CUresult (*PFN_encodeTiled)(CUtensorMap*, CUtensorMapDataType, cuuint32_t, void*, const cuuint64_t*, const cuuint64_t*,
                                    const cuuint32_t*, const cuuint32_t*, CUtensorMapInterleave, CUtensorMapSwizzle,
                                    CUtensorMapL2promotion, CUtensorMapFloatOOBfill);

static CUtensorMap make_map(PFN_encodeTiled enc, const void* ptr, uint64_t cols, uint64_t rows, uint32_t box_c, uint32_t box_r, uint32_t nb = 1) {
  CUtensorMap m;
  cuuint64_t dims[3] = {nb > 1 ? box_c : cols, rows, cols / box_c};
  cuuint64_t strides[2] = {cols * 2, box_c * 2};
  cuuint32_t box[3] = {box_c, box_r, nb};
  cuuint32_t es[3] = {1, 1, 1};
  CUresult r = enc(&m, CU_TENSOR_MAP_DATA_TYPE_BFLOAT16, nb > 1 ? 3 : 2, const_cast<void*>(ptr), dims, strides, box, es, CU_TENSOR_MAP_INTERLEAVE_NONE,
      CU_TENSOR_MAP_SWIZZLE_128B, CU_TENSOR_MAP_L2_PROMOTION_L2_256B, CU_TENSOR_MAP_FLOAT_OOB_FILL_NONE);
  (void)r;
  return m;
}

extern "C" void kernel_launch(void* const* d_in, const int* in_sizes, int n_in, void* d_out, int out_size) {
  const bf16* A_x = (const bf16*)d_in[0];
  const bf16* A_wqkv = (const bf16*)d_in[1];
  const bf16* A_wphi = (const bf16*)d_in[2];
  const bf16* A_wo = (const bf16*)d_in[3];
  const bf16* B_wqkv = (const bf16*)d_in[5];
  const bf16* B_wo = (const bf16*)d_in[6];
  bf16* out = (bf16*)d_out;

  static PFN_encodeTiled enc = nullptr;
  static bf16 *p_x, *p_o;
  if (!enc) {
    void* fn = nullptr; cudaDriverEntryPointQueryResult qr;
    cudaGetDriverEntryPoint("cuTensorMapEncodeTiled", &fn, cudaEnableDefault, &qr);
    enc = (PFN_encodeTiled)fn;
    cudaGetSymbolAddress((void**)&p_x, g_x);
    cudaGetSymbolAddress((void**)&p_o, g_o);
    cudaFuncSetAttribute(mega_kernel, cudaFuncAttributeMaxDynamicSharedMemorySize, SM_TOTAL);
  }
  CUtensorMap tm_x0 = make_map(enc, A_x, 1024, 2048, 64, 128);
  CUtensorMap tm_x = make_map(enc, p_x, 1024, 2048, 64, 128);
  CUtensorMap tm_o = make_map(enc, p_o, 1024, 2048, 64, 128);
  CUtensorMap tm_wA = make_map(enc, A_wqkv, 3072, 1024, 64, 64);
  CUtensorMap tm_wB = make_map(enc, B_wqkv, 3072, 1024, 64, 64);
  CUtensorMap tm_woA = make_map(enc, A_wo, 1024, 1024, 64, 64);
  CUtensorMap tm_woB = make_map(enc, B_wo, 1024, 1024, 64, 64);
  mega_kernel<<<128 + NX, 384, SM_TOTAL, cudaStreamPerThread>>>(tm_x0, tm_x, tm_o, tm_wA, tm_wB, tm_woA, tm_woB,
                                                           B_wqkv, A_wphi, out);
}
```

```cpp
#include <cuda_runtime.h>
#include <cuda_bf16.h>
#include <cuda.h>
#include <stdint.h>

typedef __nv_bfloat16 bf16;

constexpr int S_ = 2048, D_ = 1024;

struct __align__(128) Flag { unsigned int v; unsigned int pad[31]; };
__device__ __align__(1024) bf16 g_x[S_ * D_];
__device__ __align__(1024) bf16 g_o[S_ * D_];
__device__ __align__(1024) uint4 g_halo[128 * 2 * 512];
__device__ __align__(1024) uint4 g_kv[8 * 2 * 2 * 1280];
__device__ __align__(1024) float2 g_stats[4 * S_];
__device__ __align__(1024) float g_cs[2 * 2 * 3072];
__device__ Flag g_csflag[16];
__device__ __align__(128) unsigned int g_xf[16 * 32], g_of[16 * 32];
__device__ unsigned int g_epoch, g_err;
#define PROFT(cond, idx) asm volatile("" ::: "memory")

__device__ __forceinline__ uint32_t smem_u32(const void* p) { return (uint32_t)__cvta_generic_to_shared(p); }
__device__ __forceinline__ void mbar_init(uint32_t bar, uint32_t count) {
  asm volatile("mbarrier.init.shared::cta.b64 [%0], %1;" ::"r"(bar), "r"(count) : "memory");
}
__device__ __forceinline__ void mbar_expect_tx(uint32_t bar, uint32_t bytes) {
  asm volatile("mbarrier.arrive.expect_tx.shared::cta.b64 _, [%0], %1;" ::"r"(bar), "r"(bytes) : "memory");
}
__device__ __forceinline__ void mbar_arrive(uint32_t bar) {
  asm volatile("mbarrier.arrive.shared::cta.b64 _, [%0];" ::"r"(bar) : "memory");
}
__device__ __forceinline__ bool mbar_try_wait(uint32_t bar, uint32_t parity) {
  uint32_t ok;
  asm volatile("{\n.reg .pred p;\nmbarrier.try_wait.parity.shared::cta.b64 p, [%1], %2;\nselp.b32 %0, 1, 0, p;\n}\n"
               : "=r"(ok) : "r"(bar), "r"(parity) : "memory");
  return ok != 0;
}
__device__ __forceinline__ bool mbar_test_wait(uint32_t bar, uint32_t parity) {
  uint32_t ok;
  asm volatile("{\n.reg .pred p;\nmbarrier.test_wait.parity.shared::cta.b64 p, [%1], %2;\nselp.b32 %0, 1, 0, p;\n}\n"
               : "=r"(ok) : "r"(bar), "r"(parity) : "memory");
  return ok != 0;
}
__device__ __forceinline__ uint64_t gtimer() {
  uint64_t t; asm volatile("mov.u64 %0, %globaltimer;" : "=l"(t)); return t;
}
__device__ __forceinline__ void mbar_wait(uint32_t bar, uint32_t parity) {
  uint32_t n = 0;
#pragma unroll 1
  while (!mbar_try_wait(bar, parity)) {
    if (++n > (1u << 22)) { g_err = 1u; break; }
  }
}
__device__ __forceinline__ unsigned int ld_acquire(const unsigned int* p) {
  unsigned int v; asm volatile("ld.acquire.gpu.global.u32 %0, [%1];" : "=r"(v) : "l"(p) : "memory"); return v;
}
__device__ __forceinline__ void flag_add(unsigned int* p) {
  asm volatile("red.release.gpu.global.add.u32 [%0], 1;" ::"l"(p) : "memory");
}
__device__ __forceinline__ void flag_set(unsigned int* p, unsigned int v) {
  asm volatile("st.release.gpu.global.u32 [%0], %1;" ::"l"(p), "r"(v) : "memory");
}
template <int SLEEP>
__device__ __forceinline__ void src_wait(const unsigned int* f, unsigned int target, uint32_t need, uint32_t& ready, int lane) {
  uint32_t n = 0;
#pragma unroll 1
  while ((ready & need) != need) {
    const unsigned int v = ld_acquire(f + (lane & 15));
    ready = __ballot_sync(0xffffffffu, (int)(v - target) >= 0);
    if (SLEEP) { if ((ready & need) != need) __nanosleep(SLEEP); }
    if (++n > (1u << 20)) { g_err = 3u; break; }
  }
  __syncwarp();
}
__device__ __forceinline__ unsigned int ld_relaxed(const unsigned int* p) {
  unsigned int v; asm volatile("ld.relaxed.gpu.global.u32 %0, [%1];" : "=r"(v) : "l"(p) : "memory"); return v;
}
__device__ __forceinline__ bool src_wait_tma(const unsigned int* f, unsigned int target, uint32_t need, uint32_t& ready, int lane, uint32_t eb, uint32_t par) {
  uint32_t n = 0;
  bool fr = false;
#pragma unroll 1
  while ((ready & need) != need) {
    const unsigned int v = ld_acquire(f + (lane & 15));
    fr = __all_sync(0xffffffffu, mbar_test_wait(eb, par));
    ready = __ballot_sync(0xffffffffu, (int)(v - target) >= 0);
    if (++n > (1u << 20)) { g_err = 3u; break; }
  }
  return fr;
}
__device__ __forceinline__ uint4 ld_relaxed4(const uint4* p) {
  uint4 v; asm volatile("ld.relaxed.gpu.global.v4.u32 {%0,%1,%2,%3}, [%4];" : "=r"(v.x), "=r"(v.y), "=r"(v.z), "=r"(v.w) : "l"(p) : "memory"); return v;
}
__device__ __forceinline__ void st_relaxed4(uint4* p, uint32_t a, uint32_t b, uint32_t c, uint32_t d) {
  asm volatile("st.relaxed.gpu.global.v4.u32 [%0], {%1,%2,%3,%4};" ::"l"(p), "r"(a), "r"(b), "r"(c), "r"(d) : "memory");
}
template <int SLEEP>
__device__ __forceinline__ void flag_wait_t(const unsigned int* p, unsigned int target) {
  uint32_t n = 0;
#pragma unroll 1
  while ((int)(ld_acquire(p) - target) < 0) {
    if (SLEEP) __nanosleep(SLEEP);
    if (++n > (1u << 20)) { g_err = 2u; break; }
  }
}
__device__ __forceinline__ void flag_wait(const unsigned int* p, unsigned int target) { flag_wait_t<0>(p, target); }
__device__ __forceinline__ void flag_wait_slow(const unsigned int* p, unsigned int target) { flag_wait_t<256>(p, target); }
__device__ __forceinline__ void tma_load_2d(uint32_t dst, const CUtensorMap* tm, int c0, int c1, uint32_t bar) {
  asm volatile("cp.async.bulk.tensor.2d.shared::cluster.global.mbarrier::complete_tx::bytes [%0], [%1, {%2, %3}], [%4];"
               ::"r"(dst), "l"(tm), "r"(c0), "r"(c1), "r"(bar) : "memory");
}
__device__ __forceinline__ void tma_load_2d_mc(uint32_t dst, const CUtensorMap* tm, int c0, int c1, uint32_t bar, uint16_t mask) {
  asm volatile("cp.async.bulk.tensor.2d.shared::cluster.global.mbarrier::complete_tx::bytes.multicast::cluster [%0], [%1, {%2, %3}], [%4], %5;"
               ::"r"(dst), "l"(tm), "r"(c0), "r"(c1), "r"(bar), "h"(mask) : "memory");
}
__device__ __forceinline__ void mbar_wait_u(uint32_t bar, uint32_t parity) {
  uint32_t n = 0;
#pragma unroll 1
  while (!__all_sync(0xffffffffu, mbar_try_wait(bar, parity))) {
    if (++n > (1u << 22)) { g_err = 1u; break; }
  }
}
__device__ __forceinline__ void expect_tx_e(uint32_t bar, uint32_t bytes) {
  asm volatile("{\n.reg .pred p;\nelect.sync _|p, 0xffffffff;\n@p mbarrier.arrive.expect_tx.shared::cta.b64 _, [%0], %1;\n}\n" ::"r"(bar), "r"(bytes) : "memory");
}
__device__ __forceinline__ void tma_2d_e(uint32_t dst, const CUtensorMap* tm, int c0, int c1, uint32_t bar) {
  asm volatile("{\n.reg .pred p;\nelect.sync _|p, 0xffffffff;\n"
               "@p cp.async.bulk.tensor.2d.shared::cluster.global.mbarrier::complete_tx::bytes [%0], [%1, {%2, %3}], [%4];\n}\n"
               ::"r"(dst), "l"(tm), "r"(c0), "r"(c1), "r"(bar) : "memory");
}
__device__ __forceinline__ void tma_2d_mc_e(uint32_t dst, const CUtensorMap* tm, int c0, int c1, uint32_t bar) {
  asm volatile("{\n.reg .pred p;\nelect.sync _|p, 0xffffffff;\n"
               "@p cp.async.bulk.tensor.2d.shared::cluster.global.mbarrier::complete_tx::bytes.multicast::cluster [%0], [%1, {%2, %3}], [%4], %5;\n}\n"
               ::"r"(dst), "l"(tm), "r"(c0), "r"(c1), "r"(bar), "h"((uint16_t)3) : "memory");
}
__device__ __forceinline__ void tma_pf_e(const CUtensorMap* tm, int c0, int c1) {
  asm volatile("{\n.reg .pred p;\nelect.sync _|p, 0xffffffff;\n"
               "@p cp.async.bulk.prefetch.tensor.2d.L2.global.tile [%0, {%1, %2}];\n}\n" ::"l"(tm), "r"(c0), "r"(c1) : "memory");
}
__device__ __forceinline__ void tma_2d_to_e(uint32_t dst, const CUtensorMap* tm, int c0, int c1, uint32_t bar, uint32_t mask) {
  asm volatile("{\n.reg .pred p;\nelect.sync _|p, 0xffffffff;\n"
               "@p cp.async.bulk.tensor.2d.shared::cluster.global.mbarrier::complete_tx::bytes.multicast::cluster [%0], [%1, {%2, %3}], [%4], %5;\n}\n"
               ::"r"(dst), "l"(tm), "r"(c0), "r"(c1), "r"(bar), "h"((uint16_t)mask) : "memory");
}
__device__ __forceinline__ void tma_3d_mc_e(uint32_t dst, const CUtensorMap* tm, int c1, int c2, uint32_t bar) {
  asm volatile("{\n.reg .pred p;\nelect.sync _|p, 0xffffffff;\n"
               "@p cp.async.bulk.tensor.3d.shared::cluster.global.mbarrier::complete_tx::bytes.multicast::cluster [%0], [%1, {%6, %2, %3}], [%4], %5;\n}\n"
               ::"r"(dst), "l"(tm), "r"(c1), "r"(c2), "r"(bar), "h"((uint16_t)3), "r"(0) : "memory");
}
__device__ __forceinline__ uint32_t poll_flags(const unsigned int* f, unsigned int target, int lane) {
  const unsigned int v = ld_acquire(f + (lane & 15));
  const uint32_t r = __ballot_sync(0xffffffffu, (int)(v - target) >= 0);
  __syncwarp();
  return r;
}
__device__ __forceinline__ void mbar_arrive_cluster(uint32_t local_bar, uint32_t rank) {
  asm volatile("{\n.reg .b32 ra;\nmapa.shared::cluster.u32 ra, %0, %1;\nmbarrier.arrive.shared::cluster.b64 _, [ra];\n}\n"
               ::"r"(local_bar), "r"(rank) : "memory");
}
__device__ __forceinline__ void release2(uint32_t bar) { mbar_arrive_cluster(bar, 0); mbar_arrive_cluster(bar, 1); }
__device__ __forceinline__ void tma_store_2d(const CUtensorMap* tm, uint32_t src, int c0, int c1) {
  asm volatile("cp.async.bulk.tensor.2d.global.shared::cta.bulk_group [%0, {%2, %3}], [%1];"
               ::"l"(tm), "r"(src), "r"(c0), "r"(c1) : "memory");
}
__device__ __forceinline__ void bulk_store(void* dst, uint32_t src, uint32_t bytes) {
  asm volatile("cp.async.bulk.global.shared::cta.bulk_group [%0], [%1], %2;" ::"l"(dst), "r"(src), "r"(bytes) : "memory");
}
__device__ __forceinline__ void bulk_load(uint32_t dst, const void* src, uint32_t bytes, uint32_t bar) {
  asm volatile("cp.async.bulk.shared::cluster.global.mbarrier::complete_tx::bytes [%0], [%1], %2, [%3];" ::"r"(dst), "l"(src), "r"(bytes), "r"(bar) : "memory");
}
__device__ __forceinline__ void bulk_red_add(void* dst, uint32_t src, uint32_t bytes) {
  asm volatile("cp.reduce.async.bulk.global.shared::cta.bulk_group.add.f32 [%0], [%1], %2;" ::"l"(dst), "r"(src), "r"(bytes) : "memory");
}
__device__ __forceinline__ void bulk_red_add_e(void* dst, uint32_t src, uint32_t bytes) {
  asm volatile("{\n.reg .pred p;\nelect.sync _|p, 0xffffffff;\n@p cp.reduce.async.bulk.global.shared::cta.bulk_group.add.f32 [%0], [%1], %2;\n}\n" ::"l"(dst), "r"(src), "r"(bytes) : "memory");
}
__device__ __forceinline__ void bulk_commit() { asm volatile("cp.async.bulk.commit_group;" ::: "memory"); }
__device__ __forceinline__ void bulk_wait_read0() { asm volatile("cp.async.bulk.wait_group.read 0;" ::: "memory"); }
__device__ __forceinline__ void bulk_wait0() { asm volatile("cp.async.bulk.wait_group 0;" ::: "memory"); }
__device__ __forceinline__ void fence_async_smem() { asm volatile("fence.proxy.async.shared::cta;" ::: "memory"); }
__device__ __forceinline__ void fence_async_all() { asm volatile("fence.proxy.async.global;" ::: "memory"); }
__device__ __forceinline__ void wgmma_fence() { asm volatile("wgmma.fence.sync.aligned;" ::: "memory"); }
__device__ __forceinline__ void wgmma_commit() { asm volatile("wgmma.commit_group.sync.aligned;" ::: "memory"); }
template <int N> __device__ __forceinline__ void wgmma_wait() { asm volatile("wgmma.wait_group.sync.aligned %0;" ::"n"(N) : "memory"); }
__device__ __forceinline__ void cluster_arrive() { asm volatile("barrier.cluster.arrive.release.aligned;" ::: "memory"); }
__device__ __forceinline__ void cluster_wait() { asm volatile("barrier.cluster.wait.acquire.aligned;" ::: "memory"); }
template <int ID, int N> __device__ __forceinline__ void nbar() { asm volatile("bar.sync %0, %1;" ::"n"(ID), "n"(N) : "memory"); }
__device__ __forceinline__ uint64_t make_desc(uint32_t addr, uint32_t lbo_bytes, uint32_t sbo_bytes) {
  uint64_t d = 0;
  d |= (uint64_t)((addr & 0x3FFFF) >> 4);
  d |= (uint64_t)((lbo_bytes >> 4) & 0x3FFF) << 16;
  d |= (uint64_t)((sbo_bytes >> 4) & 0x3FFF) << 32;
  d |= (uint64_t)1 << 62;
  return d;
}
__device__ __forceinline__ uint64_t desc64(uint32_t lo, uint32_t hi) { return (uint64_t)lo | ((uint64_t)hi << 32); }
__device__ __forceinline__ uint32_t pack_bf16(float lo, float hi) {
  uint32_t r; asm("cvt.rn.bf16x2.f32 %0, %1, %2;" : "=r"(r) : "f"(hi), "f"(lo)); return r;
}
__device__ __forceinline__ uint32_t mul_bf16x2(uint32_t a, uint32_t s, bool hi) {
  __nv_bfloat162 x = *reinterpret_cast<__nv_bfloat162*>(&a), y = *reinterpret_cast<__nv_bfloat162*>(&s);
  x = __hmul2(x, hi ? __high2bfloat162(y) : __low2bfloat162(y));
  return *reinterpret_cast<uint32_t*>(&x);
}
__device__ __forceinline__ float bf16r(float x) { return __bfloat162float(__float2bfloat16_rn(x)); }
__device__ __forceinline__ float bf_lo(uint32_t u) { return __uint_as_float(u << 16); }
__device__ __forceinline__ float bf_hi(uint32_t u) { return __uint_as_float(u & 0xFFFF0000u); }
__device__ __forceinline__ float ex2(float x) { float r; asm("ex2.approx.ftz.f32 %0, %1;" : "=f"(r) : "f"(x)); return r; }
__device__ __forceinline__ float rcp(float x) { float r; asm("rcp.approx.ftz.f32 %0, %1;" : "=f"(r) : "f"(x)); return r; }
__device__ __forceinline__ void mma_bf16(float (&d)[4], uint32_t a0, uint32_t a1, uint32_t a2, uint32_t a3, uint32_t b0, uint32_t b1) {
  asm("mma.sync.aligned.m16n8k16.row.col.f32.bf16.bf16.f32 {%0,%1,%2,%3}, {%4,%5,%6,%7}, {%8,%9}, {%0,%1,%2,%3};"
               : "+f"(d[0]), "+f"(d[1]), "+f"(d[2]), "+f"(d[3]) : "r"(a0), "r"(a1), "r"(a2), "r"(a3), "r"(b0), "r"(b1));
}
__device__ __forceinline__ void ldsm_x4(uint32_t& r0, uint32_t& r1, uint32_t& r2, uint32_t& r3, uint32_t addr) {
  asm volatile("ldmatrix.sync.aligned.m8n8.x4.shared.b16 {%0,%1,%2,%3}, [%4];"
               : "=r"(r0), "=r"(r1), "=r"(r2), "=r"(r3) : "r"(addr) : "memory");
}
__device__ __forceinline__ void ldsm_x4_t(uint32_t& r0, uint32_t& r1, uint32_t& r2, uint32_t& r3, uint32_t addr) {
  asm volatile("ldmatrix.sync.aligned.m8n8.x4.trans.shared.b16 {%0,%1,%2,%3}, [%4];"
               : "=r"(r0), "=r"(r1), "=r"(r2), "=r"(r3) : "r"(addr) : "memory");
}
__device__ __forceinline__ void ldsm_x2_t(uint32_t& r0, uint32_t& r1, uint32_t addr) {
  asm volatile("ldmatrix.sync.aligned.m8n8.x2.trans.shared.b16 {%0,%1}, [%2];"
               : "=r"(r0), "=r"(r1) : "r"(addr) : "memory");
}
__device__ __forceinline__ void stsm_x4(uint32_t addr, uint32_t r0, uint32_t r1, uint32_t r2, uint32_t r3) {
  asm volatile("stmatrix.sync.aligned.m8n8.x4.shared.b16 [%0], {%1,%2,%3,%4};"
               ::"r"(addr), "r"(r0), "r"(r1), "r"(r2), "r"(r3) : "memory");
}
__device__ __forceinline__ void stsm_x4_p(bool on, uint32_t addr, uint32_t r0, uint32_t r1, uint32_t r2, uint32_t r3) {
  asm volatile("{\n.reg .pred p;\nsetp.ne.b32 p, %5, 0;\n@p stmatrix.sync.aligned.m8n8.x4.shared.b16 [%0], {%1,%2,%3,%4};\n}\n"
               ::"r"(addr), "r"(r0), "r"(r1), "r"(r2), "r"(r3), "r"((int)on) : "memory");
}
__device__ __forceinline__ float2 lds_f2(uint32_t addr) {
  float2 v; asm volatile("ld.shared.v2.f32 {%0,%1}, [%2];" : "=f"(v.x), "=f"(v.y) : "r"(addr) : "memory"); return v;
}
__device__ __forceinline__ uint4 lds128(uint32_t addr) {
  uint4 v; asm volatile("ld.shared.v4.b32 {%0,%1,%2,%3}, [%4];" : "=r"(v.x), "=r"(v.y), "=r"(v.z), "=r"(v.w) : "r"(addr) : "memory"); return v;
}
__device__ __forceinline__ void sts128(uint32_t addr, uint4 v) {
  asm volatile("st.shared.v4.b32 [%0], {%1,%2,%3,%4};" ::"r"(addr), "r"(v.x), "r"(v.y), "r"(v.z), "r"(v.w) : "memory");
}
__device__ __forceinline__ float lds_f(uint32_t addr) {
  float v; asm volatile("ld.shared.f32 %0, [%1];" : "=f"(v) : "r"(addr) : "memory"); return v;
}
__device__ __forceinline__ uint32_t lds_vol(uint32_t addr) {
  uint32_t v; asm volatile("ld.volatile.shared.u32 %0, [%1];" : "=r"(v) : "r"(addr) : "memory"); return v;
}
__device__ __forceinline__ void sts16(uint32_t addr, uint32_t v) {
  asm volatile("st.shared.u16 [%0], %1;" ::"r"(addr), "h"((unsigned short)v) : "memory");
}
__device__ __forceinline__ void nbar_dyn(int id, int n) { asm volatile("bar.sync %0, %1;" ::"r"(id), "r"(n) : "memory"); }
__device__ __forceinline__ uint64_t make_desc_ns(uint32_t addr, uint32_t lbo_bytes, uint32_t sbo_bytes) {
  return (uint64_t)((addr & 0x3FFFF) >> 4) | ((uint64_t)(lbo_bytes >> 4) << 16) | ((uint64_t)(sbo_bytes >> 4) << 32);
}
__device__ __forceinline__ void sts_f(uint32_t addr, float v) { asm volatile("st.shared.f32 [%0], %1;" ::"r"(addr), "f"(v) : "memory"); }
__device__ __forceinline__ void sts64(uint32_t addr, uint32_t a, uint32_t b) {
  asm volatile("st.shared.v2.b32 [%0], {%1,%2};" ::"r"(addr), "r"(a), "r"(b) : "memory");
}
__device__ __forceinline__ void sts_f2(uint32_t addr, float a, float b) {
  asm volatile("st.shared.v2.f32 [%0], {%1,%2};" ::"r"(addr), "f"(a), "f"(b) : "memory");
}
__device__ __forceinline__ void red_add2(float* p, float a, float b) {
  asm volatile("red.global.add.v2.f32 [%0], {%1,%2};" ::"l"(p), "f"(a), "f"(b) : "memory");
}
__device__ __forceinline__ void red_add4(float* p, float a, float b, float c, float d) {
  asm volatile("red.global.add.v4.f32 [%0], {%1,%2,%3,%4};" ::"l"(p), "f"(a), "f"(b), "f"(c), "f"(d) : "memory");
}
__device__ __forceinline__ void red_add1(float* p, float a) {
  asm volatile("red.global.add.f32 [%0], %1;" ::"l"(p), "f"(a) : "memory");
}
__device__ __forceinline__ void l2_prefetch(const void* p, uint32_t bytes) {
  asm volatile("cp.async.bulk.prefetch.L2.global [%0], %1;" ::"l"(p), "r"(bytes) : "memory");
}

__device__ __forceinline__ void wgmma_n256(float (&d)[192], uint64_t da, uint64_t db, int scale_d) {
  asm volatile("{\n.reg .pred p;\nsetp.ne.b32 p, %130, 0;\n"
    "wgmma.mma_async.sync.aligned.m64n256k16.f32.bf16.bf16 {%0, %1, %2, %3, %4, %5, %6, %7, %8, %9, %10, %11, %12, %13, %14, %15, %16, %17, %18, %19, %20, %21, %22, %23, %24, %25, %26, %27, %28, %29, %30, %31, %32, %33, %34, %35, %36, %37, %38, %39, %40, %41, %42, %43, %44, %45, %46, %47, %48, %49, %50, %51, %52, %53, %54, %55, %56, %57, %58, %59, %60, %61, %62, %63, %64, %65, %66, %67, %68, %69, %70, %71, %72, %73, %74, %75, %76, %77, %78, %79, %80, %81, %82, %83, %84, %85, %86, %87, %88, %89, %90, %91, %92, %93, %94, %95, %96, %97, %98, %99, %100, %101, %102, %103, %104, %105, %106, %107, %108, %109, %110, %111, %112, %113, %114, %115, %116, %117, %118, %119, %120, %121, %122, %123, %124, %125, %126, %127}, %128, %129, p, 1, 1, 0, 1;\n}\n"
    : "+f"(d[0]), "+f"(d[1]), "+f"(d[2]), "+f"(d[3]), "+f"(d[4]), "+f"(d[5]), "+f"(d[6]), "+f"(d[7]), "+f"(d[8]), "+f"(d[9]), "+f"(d[10]), "+f"(d[11]), "+f"(d[12]), "+f"(d[13]), "+f"(d[14]), "+f"(d[15]), "+f"(d[16]), "+f"(d[17]), "+f"(d[18]), "+f"(d[19]), "+f"(d[20]), "+f"(d[21]), "+f"(d[22]), "+f"(d[23]), "+f"(d[24]), "+f"(d[25]), "+f"(d[26]), "+f"(d[27]), "+f"(d[28]), "+f"(d[29]), "+f"(d[30]), "+f"(d[31]), "+f"(d[32]), "+f"(d[33]), "+f"(d[34]), "+f"(d[35]), "+f"(d[36]), "+f"(d[37]), "+f"(d[38]), "+f"(d[39]), "+f"(d[40]), "+f"(d[41]), "+f"(d[42]), "+f"(d[43]), "+f"(d[44]), "+f"(d[45]), "+f"(d[46]), "+f"(d[47]), "+f"(d[48]), "+f"(d[49]), "+f"(d[50]), "+f"(d[51]), "+f"(d[52]), "+f"(d[53]), "+f"(d[54]), "+f"(d[55]), "+f"(d[56]), "+f"(d[57]), "+f"(d[58]), "+f"(d[59]), "+f"(d[60]), "+f"(d[61]), "+f"(d[62]), "+f"(d[63]), "+f"(d[64]), "+f"(d[65]), "+f"(d[66]), "+f"(d[67]), "+f"(d[68]), "+f"(d[69]), "+f"(d[70]), "+f"(d[71]), "+f"(d[72]), "+f"(d[73]), "+f"(d[74]), "+f"(d[75]), "+f"(d[76]), "+f"(d[77]), "+f"(d[78]), "+f"(d[79]), "+f"(d[80]), "+f"(d[81]), "+f"(d[82]), "+f"(d[83]), "+f"(d[84]), "+f"(d[85]), "+f"(d[86]), "+f"(d[87]), "+f"(d[88]), "+f"(d[89]), "+f"(d[90]), "+f"(d[91]), "+f"(d[92]), "+f"(d[93]), "+f"(d[94]), "+f"(d[95]), "+f"(d[96]), "+f"(d[97]), "+f"(d[98]), "+f"(d[99]), "+f"(d[100]), "+f"(d[101]), "+f"(d[102]), "+f"(d[103]), "+f"(d[104]), "+f"(d[105]), "+f"(d[106]), "+f"(d[107]), "+f"(d[108]), "+f"(d[109]), "+f"(d[110]), "+f"(d[111]), "+f"(d[112]), "+f"(d[113]), "+f"(d[114]), "+f"(d[115]), "+f"(d[116]), "+f"(d[117]), "+f"(d[118]), "+f"(d[119]), "+f"(d[120]), "+f"(d[121]), "+f"(d[122]), "+f"(d[123]), "+f"(d[124]), "+f"(d[125]), "+f"(d[126]), "+f"(d[127])
    : "l"(da), "l"(db), "r"(scale_d));
}
__device__ __forceinline__ void wgmma_n128(float (&d)[192], uint64_t da, uint64_t db, int scale_d) {
  asm volatile("{\n.reg .pred p;\nsetp.ne.b32 p, %66, 0;\n"
    "wgmma.mma_async.sync.aligned.m64n128k16.f32.bf16.bf16 {%0, %1, %2, %3, %4, %5, %6, %7, %8, %9, %10, %11, %12, %13, %14, %15, %16, %17, %18, %19, %20, %21, %22, %23, %24, %25, %26, %27, %28, %29, %30, %31, %32, %33, %34, %35, %36, %37, %38, %39, %40, %41, %42, %43, %44, %45, %46, %47, %48, %49, %50, %51, %52, %53, %54, %55, %56, %57, %58, %59, %60, %61, %62, %63}, %64, %65, p, 1, 1, 0, 1;\n}\n"
    : "+f"(d[128]), "+f"(d[129]), "+f"(d[130]), "+f"(d[131]), "+f"(d[132]), "+f"(d[133]), "+f"(d[134]), "+f"(d[135]), "+f"(d[136]), "+f"(d[137]), "+f"(d[138]), "+f"(d[139]), "+f"(d[140]), "+f"(d[141]), "+f"(d[142]), "+f"(d[143]), "+f"(d[144]), "+f"(d[145]), "+f"(d[146]), "+f"(d[147]), "+f"(d[148]), "+f"(d[149]), "+f"(d[150]), "+f"(d[151]), "+f"(d[152]), "+f"(d[153]), "+f"(d[154]), "+f"(d[155]), "+f"(d[156]), "+f"(d[157]), "+f"(d[158]), "+f"(d[159]), "+f"(d[160]), "+f"(d[161]), "+f"(d[162]), "+f"(d[163]), "+f"(d[164]), "+f"(d[165]), "+f"(d[166]), "+f"(d[167]), "+f"(d[168]), "+f"(d[169]), "+f"(d[170]), "+f"(d[171]), "+f"(d[172]), "+f"(d[173]), "+f"(d[174]), "+f"(d[175]), "+f"(d[176]), "+f"(d[177]), "+f"(d[178]), "+f"(d[179]), "+f"(d[180]), "+f"(d[181]), "+f"(d[182]), "+f"(d[183]), "+f"(d[184]), "+f"(d[185]), "+f"(d[186]), "+f"(d[187]), "+f"(d[188]), "+f"(d[189]), "+f"(d[190]), "+f"(d[191])
    : "l"(da), "l"(db), "r"(scale_d));
}
__device__ __forceinline__ void wgmma_n256_k(float (&d)[192], uint64_t da, uint64_t db, int scale_d) {
  asm volatile("{\n.reg .pred p;\nsetp.ne.b32 p, %130, 0;\n"
    "wgmma.mma_async.sync.aligned.m64n256k16.f32.bf16.bf16 {%0, %1, %2, %3, %4, %5, %6, %7, %8, %9, %10, %11, %12, %13, %14, %15, %16, %17, %18, %19, %20, %21, %22, %23, %24, %25, %26, %27, %28, %29, %30, %31, %32, %33, %34, %35, %36, %37, %38, %39, %40, %41, %42, %43, %44, %45, %46, %47, %48, %49, %50, %51, %52, %53, %54, %55, %56, %57, %58, %59, %60, %61, %62, %63, %64, %65, %66, %67, %68, %69, %70, %71, %72, %73, %74, %75, %76, %77, %78, %79, %80, %81, %82, %83, %84, %85, %86, %87, %88, %89, %90, %91, %92, %93, %94, %95, %96, %97, %98, %99, %100, %101, %102, %103, %104, %105, %106, %107, %108, %109, %110, %111, %112, %113, %114, %115, %116, %117, %118, %119, %120, %121, %122, %123, %124, %125, %126, %127}, %128, %129, p, 1, 1, 0, 0;\n}\n"
    : "+f"(d[0]), "+f"(d[1]), "+f"(d[2]), "+f"(d[3]), "+f"(d[4]), "+f"(d[5]), "+f"(d[6]), "+f"(d[7]), "+f"(d[8]), "+f"(d[9]), "+f"(d[10]), "+f"(d[11]), "+f"(d[12]), "+f"(d[13]), "+f"(d[14]), "+f"(d[15]), "+f"(d[16]), "+f"(d[17]), "+f"(d[18]), "+f"(d[19]), "+f"(d[20]), "+f"(d[21]), "+f"(d[22]), "+f"(d[23]), "+f"(d[24]), "+f"(d[25]), "+f"(d[26]), "+f"(d[27]), "+f"(d[28]), "+f"(d[29]), "+f"(d[30]), "+f"(d[31]), "+f"(d[32]), "+f"(d[33]), "+f"(d[34]), "+f"(d[35]), "+f"(d[36]), "+f"(d[37]), "+f"(d[38]), "+f"(d[39]), "+f"(d[40]), "+f"(d[41]), "+f"(d[42]), "+f"(d[43]), "+f"(d[44]), "+f"(d[45]), "+f"(d[46]), "+f"(d[47]), "+f"(d[48]), "+f"(d[49]), "+f"(d[50]), "+f"(d[51]), "+f"(d[52]), "+f"(d[53]), "+f"(d[54]), "+f"(d[55]), "+f"(d[56]), "+f"(d[57]), "+f"(d[58]), "+f"(d[59]), "+f"(d[60]), "+f"(d[61]), "+f"(d[62]), "+f"(d[63]), "+f"(d[64]), "+f"(d[65]), "+f"(d[66]), "+f"(d[67]), "+f"(d[68]), "+f"(d[69]), "+f"(d[70]), "+f"(d[71]), "+f"(d[72]), "+f"(d[73]), "+f"(d[74]), "+f"(d[75]), "+f"(d[76]), "+f"(d[77]), "+f"(d[78]), "+f"(d[79]), "+f"(d[80]), "+f"(d[81]), "+f"(d[82]), "+f"(d[83]), "+f"(d[84]), "+f"(d[85]), "+f"(d[86]), "+f"(d[87]), "+f"(d[88]), "+f"(d[89]), "+f"(d[90]), "+f"(d[91]), "+f"(d[92]), "+f"(d[93]), "+f"(d[94]), "+f"(d[95]), "+f"(d[96]), "+f"(d[97]), "+f"(d[98]), "+f"(d[99]), "+f"(d[100]), "+f"(d[101]), "+f"(d[102]), "+f"(d[103]), "+f"(d[104]), "+f"(d[105]), "+f"(d[106]), "+f"(d[107]), "+f"(d[108]), "+f"(d[109]), "+f"(d[110]), "+f"(d[111]), "+f"(d[112]), "+f"(d[113]), "+f"(d[114]), "+f"(d[115]), "+f"(d[116]), "+f"(d[117]), "+f"(d[118]), "+f"(d[119]), "+f"(d[120]), "+f"(d[121]), "+f"(d[122]), "+f"(d[123]), "+f"(d[124]), "+f"(d[125]), "+f"(d[126]), "+f"(d[127])
    : "l"(da), "l"(db), "r"(scale_d));
}
__device__ __forceinline__ void wgmma_n128_k(float (&d)[192], uint64_t da, uint64_t db, int scale_d) {
  asm volatile("{\n.reg .pred p;\nsetp.ne.b32 p, %66, 0;\n"
    "wgmma.mma_async.sync.aligned.m64n128k16.f32.bf16.bf16 {%0, %1, %2, %3, %4, %5, %6, %7, %8, %9, %10, %11, %12, %13, %14, %15, %16, %17, %18, %19, %20, %21, %22, %23, %24, %25, %26, %27, %28, %29, %30, %31, %32, %33, %34, %35, %36, %37, %38, %39, %40, %41, %42, %43, %44, %45, %46, %47, %48, %49, %50, %51, %52, %53, %54, %55, %56, %57, %58, %59, %60, %61, %62, %63}, %64, %65, p, 1, 1, 0, 0;\n}\n"
    : "+f"(d[128]), "+f"(d[129]), "+f"(d[130]), "+f"(d[131]), "+f"(d[132]), "+f"(d[133]), "+f"(d[134]), "+f"(d[135]), "+f"(d[136]), "+f"(d[137]), "+f"(d[138]), "+f"(d[139]), "+f"(d[140]), "+f"(d[141]), "+f"(d[142]), "+f"(d[143]), "+f"(d[144]), "+f"(d[145]), "+f"(d[146]), "+f"(d[147]), "+f"(d[148]), "+f"(d[149]), "+f"(d[150]), "+f"(d[151]), "+f"(d[152]), "+f"(d[153]), "+f"(d[154]), "+f"(d[155]), "+f"(d[156]), "+f"(d[157]), "+f"(d[158]), "+f"(d[159]), "+f"(d[160]), "+f"(d[161]), "+f"(d[162]), "+f"(d[163]), "+f"(d[164]), "+f"(d[165]), "+f"(d[166]), "+f"(d[167]), "+f"(d[168]), "+f"(d[169]), "+f"(d[170]), "+f"(d[171]), "+f"(d[172]), "+f"(d[173]), "+f"(d[174]), "+f"(d[175]), "+f"(d[176]), "+f"(d[177]), "+f"(d[178]), "+f"(d[179]), "+f"(d[180]), "+f"(d[181]), "+f"(d[182]), "+f"(d[183]), "+f"(d[184]), "+f"(d[185]), "+f"(d[186]), "+f"(d[187]), "+f"(d[188]), "+f"(d[189]), "+f"(d[190]), "+f"(d[191])
    : "l"(da), "l"(db), "r"(scale_d));
}
__device__ __forceinline__ void wgmma_n40_tt(float (&d)[20], uint64_t da, uint64_t db, int scale_d) {
  asm volatile("{\n.reg .pred p;\nsetp.ne.b32 p, %22, 0;\n"
    "wgmma.mma_async.sync.aligned.m64n40k16.f32.bf16.bf16 {%0, %1, %2, %3, %4, %5, %6, %7, %8, %9, %10, %11, %12, %13, %14, %15, %16, %17, %18, %19}, %20, %21, p, 1, 1, 1, 1;\n}\n"
    : "+f"(d[0]), "+f"(d[1]), "+f"(d[2]), "+f"(d[3]), "+f"(d[4]), "+f"(d[5]), "+f"(d[6]), "+f"(d[7]), "+f"(d[8]), "+f"(d[9]), "+f"(d[10]), "+f"(d[11]), "+f"(d[12]), "+f"(d[13]), "+f"(d[14]), "+f"(d[15]), "+f"(d[16]), "+f"(d[17]), "+f"(d[18]), "+f"(d[19])
    : "l"(da), "l"(db), "r"(scale_d));
}
__device__ __forceinline__ void wgmma_n40_rs(float (&d)[20], const uint32_t (&a)[4], uint64_t db, int scale_d) {
  asm volatile("{\n.reg .pred p;\nsetp.ne.b32 p, %25, 0;\n"
    "wgmma.mma_async.sync.aligned.m64n40k16.f32.bf16.bf16 {%0, %1, %2, %3, %4, %5, %6, %7, %8, %9, %10, %11, %12, %13, %14, %15, %16, %17, %18, %19}, {%20, %21, %22, %23}, %24, p, 1, 1, 1;\n}\n"
    : "+f"(d[0]), "+f"(d[1]), "+f"(d[2]), "+f"(d[3]), "+f"(d[4]), "+f"(d[5]), "+f"(d[6]), "+f"(d[7]), "+f"(d[8]), "+f"(d[9]), "+f"(d[10]), "+f"(d[11]), "+f"(d[12]), "+f"(d[13]), "+f"(d[14]), "+f"(d[15]), "+f"(d[16]), "+f"(d[17]), "+f"(d[18]), "+f"(d[19])
    : "r"(a[0]), "r"(a[1]), "r"(a[2]), "r"(a[3]), "l"(db), "r"(scale_d));
}
__device__ __forceinline__ void wgmma_n256_0(float (&d)[192], uint64_t da, uint64_t db) {
  asm volatile("{\n.reg .pred p;\nsetp.ne.b32 p, 0, 0;\n"
    "wgmma.mma_async.sync.aligned.m64n256k16.f32.bf16.bf16 {%0, %1, %2, %3, %4, %5, %6, %7, %8, %9, %10, %11, %12, %13, %14, %15, %16, %17, %18, %19, %20, %21, %22, %23, %24, %25, %26, %27, %28, %29, %30, %31, %32, %33, %34, %35, %36, %37, %38, %39, %40, %41, %42, %43, %44, %45, %46, %47, %48, %49, %50, %51, %52, %53, %54, %55, %56, %57, %58, %59, %60, %61, %62, %63, %64, %65, %66, %67, %68, %69, %70, %71, %72, %73, %74, %75, %76, %77, %78, %79, %80, %81, %82, %83, %84, %85, %86, %87, %88, %89, %90, %91, %92, %93, %94, %95, %96, %97, %98, %99, %100, %101, %102, %103, %104, %105, %106, %107, %108, %109, %110, %111, %112, %113, %114, %115, %116, %117, %118, %119, %120, %121, %122, %123, %124, %125, %126, %127}, %128, %129, p, 1, 1, 0, 1;\n}\n"
    : "=f"(d[0]), "=f"(d[1]), "=f"(d[2]), "=f"(d[3]), "=f"(d[4]), "=f"(d[5]), "=f"(d[6]), "=f"(d[7]), "=f"(d[8]), "=f"(d[9]), "=f"(d[10]), "=f"(d[11]), "=f"(d[12]), "=f"(d[13]), "=f"(d[14]), "=f"(d[15]), "=f"(d[16]), "=f"(d[17]), "=f"(d[18]), "=f"(d[19]), "=f"(d[20]), "=f"(d[21]), "=f"(d[22]), "=f"(d[23]), "=f"(d[24]), "=f"(d[25]), "=f"(d[26]), "=f"(d[27]), "=f"(d[28]), "=f"(d[29]), "=f"(d[30]), "=f"(d[31]), "=f"(d[32]), "=f"(d[33]), "=f"(d[34]), "=f"(d[35]), "=f"(d[36]), "=f"(d[37]), "=f"(d[38]), "=f"(d[39]), "=f"(d[40]), "=f"(d[41]), "=f"(d[42]), "=f"(d[43]), "=f"(d[44]), "=f"(d[45]), "=f"(d[46]), "=f"(d[47]), "=f"(d[48]), "=f"(d[49]), "=f"(d[50]), "=f"(d[51]), "=f"(d[52]), "=f"(d[53]), "=f"(d[54]), "=f"(d[55]), "=f"(d[56]), "=f"(d[57]), "=f"(d[58]), "=f"(d[59]), "=f"(d[60]), "=f"(d[61]), "=f"(d[62]), "=f"(d[63]), "=f"(d[64]), "=f"(d[65]), "=f"(d[66]), "=f"(d[67]), "=f"(d[68]), "=f"(d[69]), "=f"(d[70]), "=f"(d[71]), "=f"(d[72]), "=f"(d[73]), "=f"(d[74]), "=f"(d[75]), "=f"(d[76]), "=f"(d[77]), "=f"(d[78]), "=f"(d[79]), "=f"(d[80]), "=f"(d[81]), "=f"(d[82]), "=f"(d[83]), "=f"(d[84]), "=f"(d[85]), "=f"(d[86]), "=f"(d[87]), "=f"(d[88]), "=f"(d[89]), "=f"(d[90]), "=f"(d[91]), "=f"(d[92]), "=f"(d[93]), "=f"(d[94]), "=f"(d[95]), "=f"(d[96]), "=f"(d[97]), "=f"(d[98]), "=f"(d[99]), "=f"(d[100]), "=f"(d[101]), "=f"(d[102]), "=f"(d[103]), "=f"(d[104]), "=f"(d[105]), "=f"(d[106]), "=f"(d[107]), "=f"(d[108]), "=f"(d[109]), "=f"(d[110]), "=f"(d[111]), "=f"(d[112]), "=f"(d[113]), "=f"(d[114]), "=f"(d[115]), "=f"(d[116]), "=f"(d[117]), "=f"(d[118]), "=f"(d[119]), "=f"(d[120]), "=f"(d[121]), "=f"(d[122]), "=f"(d[123]), "=f"(d[124]), "=f"(d[125]), "=f"(d[126]), "=f"(d[127])
    : "l"(da), "l"(db));
}
__device__ __forceinline__ void wgmma_n128_0(float (&d)[192], uint64_t da, uint64_t db) {
  asm volatile("{\n.reg .pred p;\nsetp.ne.b32 p, 0, 0;\n"
    "wgmma.mma_async.sync.aligned.m64n128k16.f32.bf16.bf16 {%0, %1, %2, %3, %4, %5, %6, %7, %8, %9, %10, %11, %12, %13, %14, %15, %16, %17, %18, %19, %20, %21, %22, %23, %24, %25, %26, %27, %28, %29, %30, %31, %32, %33, %34, %35, %36, %37, %38, %39, %40, %41, %42, %43, %44, %45, %46, %47, %48, %49, %50, %51, %52, %53, %54, %55, %56, %57, %58, %59, %60, %61, %62, %63}, %64, %65, p, 1, 1, 0, 1;\n}\n"
    : "=f"(d[128]), "=f"(d[129]), "=f"(d[130]), "=f"(d[131]), "=f"(d[132]), "=f"(d[133]), "=f"(d[134]), "=f"(d[135]), "=f"(d[136]), "=f"(d[137]), "=f"(d[138]), "=f"(d[139]), "=f"(d[140]), "=f"(d[141]), "=f"(d[142]), "=f"(d[143]), "=f"(d[144]), "=f"(d[145]), "=f"(d[146]), "=f"(d[147]), "=f"(d[148]), "=f"(d[149]), "=f"(d[150]), "=f"(d[151]), "=f"(d[152]), "=f"(d[153]), "=f"(d[154]), "=f"(d[155]), "=f"(d[156]), "=f"(d[157]), "=f"(d[158]), "=f"(d[159]), "=f"(d[160]), "=f"(d[161]), "=f"(d[162]), "=f"(d[163]), "=f"(d[164]), "=f"(d[165]), "=f"(d[166]), "=f"(d[167]), "=f"(d[168]), "=f"(d[169]), "=f"(d[170]), "=f"(d[171]), "=f"(d[172]), "=f"(d[173]), "=f"(d[174]), "=f"(d[175]), "=f"(d[176]), "=f"(d[177]), "=f"(d[178]), "=f"(d[179]), "=f"(d[180]), "=f"(d[181]), "=f"(d[182]), "=f"(d[183]), "=f"(d[184]), "=f"(d[185]), "=f"(d[186]), "=f"(d[187]), "=f"(d[188]), "=f"(d[189]), "=f"(d[190]), "=f"(d[191])
    : "l"(da), "l"(db));
}
__device__ __forceinline__ void wgmma_n64a(float (&d)[192], uint64_t da, uint64_t db, int scale_d) {
  asm volatile("{\n.reg .pred p;\nsetp.ne.b32 p, %34, 0;\n"
    "wgmma.mma_async.sync.aligned.m64n64k16.f32.bf16.bf16 {%0, %1, %2, %3, %4, %5, %6, %7, %8, %9, %10, %11, %12, %13, %14, %15, %16, %17, %18, %19, %20, %21, %22, %23, %24, %25, %26, %27, %28, %29, %30, %31}, %32, %33, p, 1, 1, 0, 1;\n}\n"
    : "+f"(d[128]), "+f"(d[129]), "+f"(d[130]), "+f"(d[131]), "+f"(d[132]), "+f"(d[133]), "+f"(d[134]), "+f"(d[135]), "+f"(d[136]), "+f"(d[137]), "+f"(d[138]), "+f"(d[139]), "+f"(d[140]), "+f"(d[141]), "+f"(d[142]), "+f"(d[143]), "+f"(d[144]), "+f"(d[145]), "+f"(d[146]), "+f"(d[147]), "+f"(d[148]), "+f"(d[149]), "+f"(d[150]), "+f"(d[151]), "+f"(d[152]), "+f"(d[153]), "+f"(d[154]), "+f"(d[155]), "+f"(d[156]), "+f"(d[157]), "+f"(d[158]), "+f"(d[159])
    : "l"(da), "l"(db), "r"(scale_d));
}
__device__ __forceinline__ void wgmma_n64b(float (&d)[192], uint64_t da, uint64_t db, int scale_d) {
  asm volatile("{\n.reg .pred p;\nsetp.ne.b32 p, %34, 0;\n"
    "wgmma.mma_async.sync.aligned.m64n64k16.f32.bf16.bf16 {%0, %1, %2, %3, %4, %5, %6, %7, %8, %9, %10, %11, %12, %13, %14, %15, %16, %17, %18, %19, %20, %21, %22, %23, %24, %25, %26, %27, %28, %29, %30, %31}, %32, %33, p, 1, 1, 0, 1;\n}\n"
    : "+f"(d[160]), "+f"(d[161]), "+f"(d[162]), "+f"(d[163]), "+f"(d[164]), "+f"(d[165]), "+f"(d[166]), "+f"(d[167]), "+f"(d[168]), "+f"(d[169]), "+f"(d[170]), "+f"(d[171]), "+f"(d[172]), "+f"(d[173]), "+f"(d[174]), "+f"(d[175]), "+f"(d[176]), "+f"(d[177]), "+f"(d[178]), "+f"(d[179]), "+f"(d[180]), "+f"(d[181]), "+f"(d[182]), "+f"(d[183]), "+f"(d[184]), "+f"(d[185]), "+f"(d[186]), "+f"(d[187]), "+f"(d[188]), "+f"(d[189]), "+f"(d[190]), "+f"(d[191])
    : "l"(da), "l"(db), "r"(scale_d));
}

constexpr int SLOT = 16384;
constexpr int KVT = 10240;
constexpr uint32_t QA = 0x0BAu, QK = 0x462u, QQ = 0x981u;
constexpr int SM_SD = 12 * SLOT;
constexpr int SM_BAR = SM_SD + 8192;
constexpr int SM_RS = SM_BAR + 512;
constexpr int SM_AP = SM_RS + 768;
constexpr int SM_BP = SM_AP + 2048;
constexpr int SM_WPHI = SM_BP + 12288;
constexpr int SM_EPOCH = SM_WPHI + 10240;
constexpr int SM_TOTAL = SM_EPOCH + 16 + 1024;
constexpr int B_FULLS = 0, B_XOLD = 24, B_STAT = 32, B_EMPTYS = 40, B_FULLT = 256  , B_CONS = 384  , B_E3 = 472, B_E0 = 480, B_E1 = 488, B_E2 = 496, B_EPI = 504, B_CS = 160,
              B_KVDONE = 168  , B_ODONE = 176, B_XDONE = 184, B_OH1 = 192, B_CS2 = 208, B_XH0 = 232, B_R0 = 240, B_CB = 144  , B_XOLD2 = 216, B_FLG = 64  ;
constexpr uint64_t BAR_CNT = 0x1c07fc0eac00a800ull;
constexpr uint64_t WO_A0 = 0xba76218762187643ull, WO_B0 = 0x9540395403ba9021ull, WO_A1 = 0xba713257132576abull, WO_B1 = 0x9506489064890132ull;
constexpr uint64_t WO_DA0 = 0xa9876543210edd00ull, WO_DB0 = 0xa987654321bbccccull, WO_DA1 = 0xa9876543210fff00ull, WO_DB1 = 0xa98765432bbcccddull;
constexpr int NX = 4;
constexpr int XS = 10;

#define PL 2
#define PROFX(i) PROFT(tid_ == 128 && layer == PL, 200 + (i))
#define PSL 20
#define EP 5
#define DRY 0
#define NCOM 3
#define CSLP 128
#define PFS 8
#define KVTH 0x41700000u
#define RL 3
#define ORD 1
#define XB2 2
#define PMOD 3
#define DB1 2
#define XPF 2
#define XPM 0
#define AW 1
#define PG 0
#define NLAYERS 4
constexpr float L2E = 1.4426950408889634f;
#define PHI_MAX 2147483648.f

#define D128(lo) desc64(lo, 0x40000040u)
struct Ctx { uint32_t sb; int g, rb, cu; bf16* out; };

__device__ __forceinline__ void colsum(const CUtensorMap* tm, float* cs, int rb, int g, int w0, int dw, int lane, uint32_t stg, uint32_t cb, uint32_t par) {
  const uint32_t src = stg + (lane >> 3) * 2048;
#pragma unroll 1
  for (int wi = w0 - dw; wi < 6; wi += dw) {
    float s[8] = {0.f, 0.f, 0.f, 0.f, 0.f, 0.f, 0.f, 0.f};
    if (wi >= 0) {
      mbar_wait_u(cb, par);
      par ^= 1;
#pragma unroll 4
      for (int r = 0; r < 16; ++r) {
        const uint4 v = lds128(src + r * 128 + (((lane ^ r) & 7) << 4));
        s[0] += bf_lo(v.x); s[1] += bf_hi(v.x); s[2] += bf_lo(v.y); s[3] += bf_hi(v.y);
        s[4] += bf_lo(v.z); s[5] += bf_hi(v.z); s[6] += bf_lo(v.w); s[7] += bf_hi(v.w);
      }
#pragma unroll
      for (int i = 0; i < 8; ++i) s[i] += __shfl_xor_sync(0xffffffffu, s[i], 8);
    }
    const int wn = wi + dw;
    if (wn < 6) {
      expect_tx_e(cb, 8192);
      tma_2d_e(stg, tm, (wn >= 4 ? 0 : 1024 + (wn >> 1) * 1024) + g * 128 + (wn & 1) * 64, rb * 64, cb);
    }
    if (wi >= 0) {
#pragma unroll
      for (int i = 0; i < 8; ++i) s[i] += __shfl_xor_sync(0xffffffffu, s[i], 16);
      if (lane < 8) {
        red_add4(cs + g * 384 + (wi * 8 + lane) * 8, s[0], s[1], s[2], s[3]);
        red_add4(cs + g * 384 + (wi * 8 + lane) * 8 + 4, s[4], s[5], s[6], s[7]);
      }
      __syncwarp();
    }
  }
}
#define PHASE_CTX() \
  uint32_t sb = c.sb; asm volatile("" : "+r"(sb)); \
  int tid_ = threadIdx.x; asm volatile("" : "+r"(tid_)); \
  const uint32_t bar = sb + SM_BAR; \
  const int lane = tid_ & 31, cw = (tid_ >> 5) - 4, wg = cw >> 2, wq = cw & 3, gq = lane >> 2, t = lane & 3, wrow0 = cw * 16; \
  const int lrow = (lane & 7) + ((lane >> 3) & 1) * 8, lchk = lane >> 4; \
  const bool elected = (tid_ & 127) == 0; \
  const uint32_t rowo = (wrow0 + lrow) * 128, X = (lchk ^ (lane & 7)) << 4; \
  (void)bar; (void)wq; (void)gq; (void)lrow; (void)lchk; (void)elected; (void)wrow0; (void)wg; (void)rowo; (void)X; (void)t;

__device__ __forceinline__ void slab_out_half(uint32_t slot, bf16* dst, int wrow0, int lane, bool FENCE = false) {
  const int r0 = lane >> 3, ch = lane & 7;
  const uint32_t src = slot + (wrow0 + r0) * 128;
  uint4 v[4];
#pragma unroll
  for (int i = 0; i < 4; ++i) v[i] = lds128(src + i * 512 + (((ch ^ (4 * i + r0)) & 7) << 4));
  if (FENCE) fence_async_smem();
  dst += (size_t)(wrow0 + r0) * D_ + ch * 8;
#pragma unroll
  for (int i = 0; i < 4; ++i)
    asm volatile("st.global.v4.u32 [%0], {%1,%2,%3,%4};" ::"l"(dst + (size_t)i * 4 * D_), "r"(v[i].x), "r"(v[i].y), "r"(v[i].z), "r"(v[i].w) : "memory");
}

template <int O>
__device__ __forceinline__ void phi_proj(float (&p)[2][4][4], const uint32_t (&kq)[64], uint32_t wa) {
#pragma unroll
  for (int h = 0; h < 2; ++h)
#pragma unroll
    for (int i = 0; i < 4; ++i) { p[h][i][0] = p[h][i][1] = p[h][i][2] = p[h][i][3] = 0.f; }
#pragma unroll
  for (int ks = 0; ks < 2; ++ks)
#pragma unroll
    for (int np = 0; np < 2; ++np)
#pragma unroll
      for (int h = 0; h < 2; ++h) {
        uint32_t b0, b1, b2, b3;
        ldsm_x4_t(b0, b1, b2, b3, wa + h * 2560 + ks * 1280 + np * 32);
        mma_bf16(p[h][2 * np], kq[O + 8 * h + 4 * ks], kq[O + 8 * h + 4 * ks + 1], kq[O + 8 * h + 4 * ks + 2], kq[O + 8 * h + 4 * ks + 3], b0, b1);
        mma_bf16(p[h][2 * np + 1], kq[O + 8 * h + 4 * ks], kq[O + 8 * h + 4 * ks + 1], kq[O + 8 * h + 4 * ks + 2], kq[O + 8 * h + 4 * ks + 3], b2, b3);
      }
}
__device__ __forceinline__ void phi_exp(uint32_t (&raw)[4][4], const float (&p)[4][4], float sc0, float sc1) {
#pragma unroll
  for (int i = 0; i < 4; ++i) {
    const float e0 = ex2(p[i][0] * sc0), e1 = ex2(p[i][1] * sc0), e2 = ex2(p[i][2] * sc1), e3 = ex2(p[i][3] * sc1);
    const float m0 = e0 * e1, m1 = e2 * e3, rr = rcp(m0 * m1), r0 = rr * m1, r1 = rr * m0;
    raw[i >> 1][(i & 1) * 2] = pack_bf16(e0, e1);
    raw[i >> 1][(i & 1) * 2 + 1] = pack_bf16(e2, e3);
    raw[2 + (i >> 1)][(i & 1) * 2] = pack_bf16(e1 * r0, e0 * r0);
    raw[2 + (i >> 1)][(i & 1) * 2 + 1] = pack_bf16(e3 * r1, e2 * r1);
  }
}
#define FENCE_P(h) _Pragma("unroll") for (int i_ = 0; i_ < 16; ++i_) asm volatile("" : "+f"(p[h][i_ >> 2][i_ & 3]) :: "memory")
#define FENCE_RAW(h) _Pragma("unroll") for (int i_ = 0; i_ < 16; ++i_) asm volatile("" : "+r"(raw[h][i_ >> 2][i_ & 3]) :: "memory")
template <int O>
__device__ __forceinline__ void phi_norm(uint32_t (&ph)[2][4][4], const uint32_t (&raw)[2][4][4], const uint32_t (&kq)[64], uint32_t wa,
                                         float sc0, float sc1, float mul0, float mul1) {
  bool bad = false;
#pragma unroll
  for (int h = 0; h < 2; ++h)
#pragma unroll
    for (int sg = 0; sg < 2; ++sg) {
      float ss[4] = {0.f, 0.f, 0.f, 0.f};
#pragma unroll
      for (int ks = 0; ks < 2; ++ks)
        mma_bf16(ss, raw[h][2 * sg + ks][0], raw[h][2 * sg + ks][1], raw[h][2 * sg + ks][2], raw[h][2 * sg + ks][3], 0x3F803F80u, 0x3F803F80u);
      bad = bad || !(ss[0] < PHI_MAX) || !(ss[2] < PHI_MAX);
      const uint32_t iv = pack_bf16(rcp(ss[0]) * mul0, rcp(ss[2]) * mul1);
#pragma unroll
      for (int ks = 0; ks < 2; ++ks)
#pragma unroll
        for (int j = 0; j < 4; ++j) ph[h][2 * sg + ks][j] = mul_bf16x2(raw[h][2 * sg + ks][j], iv, j & 1);
    }
  if (__builtin_expect(__any_sync(0xffffffffu, bad), 0)) {
#pragma unroll 1
    for (int it = 0; it < 4; ++it) {
      float q[4][4];
#pragma unroll
      for (int i = 0; i < 4; ++i) { q[i][0] = q[i][1] = q[i][2] = q[i][3] = 0.f; }
#pragma unroll
      for (int ks = 0; ks < 2; ++ks) {
        uint32_t a[4];
#pragma unroll
        for (int j = 0; j < 4; ++j) a[j] = (it & 2) ? kq[O + 8 + 4 * ks + j] : kq[O + 4 * ks + j];
#pragma unroll
        for (int np = 0; np < 2; ++np) {
          uint32_t b0, b1, b2, b3;
          ldsm_x4_t(b0, b1, b2, b3, wa + (it >> 1) * 2560 + ks * 1280 + np * 32);
          mma_bf16(q[2 * np], a[0], a[1], a[2], a[3], b0, b1);
          mma_bf16(q[2 * np + 1], a[0], a[1], a[2], a[3], b2, b3);
        }
      }
      float iv[2];
#pragma unroll
      for (int r = 0; r < 2; ++r) {
        const float sc = (it & 1) ? -(r ? sc1 : sc0) : (r ? sc1 : sc0);
        float mx = -INFINITY, sm = 0.f;
#pragma unroll
        for (int i = 0; i < 8; ++i) { float& v = q[i >> 1][2 * r + (i & 1)]; v *= sc; mx = fmaxf(mx, v); }
        mx = fmaxf(mx, __shfl_xor_sync(0xffffffffu, mx, 1));
        mx = fmaxf(mx, __shfl_xor_sync(0xffffffffu, mx, 2));
#pragma unroll
        for (int i = 0; i < 8; ++i) { float& v = q[i >> 1][2 * r + (i & 1)]; v = ex2(v - mx); sm += v; }
        sm += __shfl_xor_sync(0xffffffffu, sm, 1);
        sm += __shfl_xor_sync(0xffffffffu, sm, 2);
        iv[r] = rcp(sm) * (r ? mul1 : mul0);
      }
#pragma unroll
      for (int i = 0; i < 24; ++i) ph[i >> 4][(i >> 2) & 3][i & 3] = ph[(i + 8) >> 4][((i + 8) >> 2) & 3][i & 3];
#pragma unroll
      for (int i = 0; i < 4; ++i) {
        ph[1][2 + (i >> 1)][(i & 1) * 2] = pack_bf16(q[i][0] * iv[0], q[i][1] * iv[0]);
        ph[1][2 + (i >> 1)][(i & 1) * 2 + 1] = pack_bf16(q[i][2] * iv[1], q[i][3] * iv[1]);
      }
    }
  }
}

__device__ __forceinline__ void stats_out(float s0, float s1, float q0, float q1, float2* dst, int t) {
  const bool od = t & 1;
  float sa = od ? s1 : s0, qa = od ? q1 : q0;
  sa += __shfl_xor_sync(0xffffffffu, od ? s0 : s1, 1);
  qa += __shfl_xor_sync(0xffffffffu, od ? q0 : q1, 1);
  sa += __shfl_xor_sync(0xffffffffu, sa, 2);
  qa += __shfl_xor_sync(0xffffffffu, qa, 2);
  if (t < 2) red_add2(&dst[t * 8].x, sa, qa);
}

__device__ __forceinline__ void consumer(const Ctx& c) {
  const int g = c.g, m0 = c.rb * 128;
  float acc[192];
#define X_H1() \
      _Pragma("unroll") for (int jp = 4; jp < 8; ++jp) \
        stsm_x4(sb + (XS + 1) * SLOT + rowo + (X ^ ((jp & 3) << 5)), \
                pack_bf16(acc[128 + 8 * jp], acc[129 + 8 * jp]), pack_bf16(acc[130 + 8 * jp], acc[131 + 8 * jp]), \
                pack_bf16(acc[132 + 8 * jp], acc[133 + 8 * jp]), pack_bf16(acc[134 + 8 * jp], acc[135 + 8 * jp]));
#pragma unroll
  for (int i = 128; i < 192; ++i) acc[i] = 0.f;
#pragma unroll 1
  for (int layer = 0;; ++layer) {
    {
      PHASE_CTX();
      const uint32_t wu = c.cu >> 2;
      const uint32_t dA0 = (((sb + wu * 8192) & 0x3FFFF) >> 4) | (1u << 16), dB0 = ((sb & 0x3FFFF) >> 4) | (512u << 16);
      {
        PROFX(0);
        mbar_wait(bar + B_FULLS, 0);
        PROFX(1);
        wgmma_fence();
        wgmma_n256_0(acc, D128(dA0 + XS * 1024), D128(dB0 + 2048));
#pragma unroll
        for (int k = 1; k < 4; ++k) wgmma_n256(acc, D128(dA0 + XS * 1024 + k * 2), D128(dB0 + 2048 + k * 128), 1);
        wgmma_commit();
        wgmma_wait<1>();
        float s0 = 0.f, s1 = 0.f, q0 = 0.f, q1 = 0.f;
        if (layer) {
          X_H1();
#pragma unroll
          for (int i = 128; i < 192; i += 4) {
            s0 += acc[i] + acc[i + 1]; s1 += acc[i + 2] + acc[i + 3];
            q0 = fmaf(acc[i], acc[i], fmaf(acc[i + 1], acc[i + 1], q0)); q1 = fmaf(acc[i + 2], acc[i + 2], fmaf(acc[i + 3], acc[i + 3], q1));
          }
        }
        asm volatile("" : "+f"(s0), "+f"(s1), "+f"(q0), "+f"(q1) :: "memory");
        wgmma_fence();
        wgmma_n128_0(acc, D128(dA0 + XS * 1024), D128(dB0 + 1024));
#pragma unroll
        for (int k = 1; k < 4; ++k) wgmma_n128(acc, D128(dA0 + XS * 1024 + k * 2), D128(dB0 + 1024 + k * 128), 1);
        wgmma_commit();
        if (layer) {
          PHASE_CTX();
          fence_async_smem();
          nbar_dyn(3 + wu, 128);
          stats_out(s0, s1, q0, q1, g_stats + layer * S_ + m0 + wrow0 + gq, t);
          PROFT(tid_ == 128, layer * 16 + 8);
        }
      }
      uint32_t s = 1, u = 0, sp = 0;
      const int ix = layer ? 1 : 2 * min(g, NCOM) + 1;
#pragma unroll 1
      for (int i = 1; i < 14; ++i) {
        mbar_wait(bar + B_FULLS + s * 8, (u + (s ? layer : 0)) & 1);
        const uint32_t da = dA0 + ((QA >> (4 * s)) & 15) * 1024, dk = dB0 + ((QK >> (4 * s)) & 15) * 1024,
                       dq = dB0 + ((QQ >> (4 * s)) & 15) * 1024;
        wgmma_fence();
#pragma unroll
        for (int k = 0; k < 4; ++k) {
          wgmma_n256(acc, D128(da + k * 2), D128(dk + k * 128), 1);
          wgmma_n128(acc, D128(da + k * 2), D128(dq + k * 128), 1);
        }
        wgmma_commit();
        if (i == ix || (i == ix + 1 && !layer)) {
          PHASE_CTX();
          if (layer) {
            slab_out_half(sb + (XS + 1) * SLOT, g_x + (size_t)m0 * D_ + g * 128 + 64, wrow0, lane);
          } else {
            float s0 = 0.f, s1 = 0.f, q0 = 0.f, q1 = 0.f;
            const uint32_t xa = sb + ((QA >> (4 * sp)) & 15) * SLOT + rowo;
#pragma unroll
            for (int jp = 0; jp < 4; ++jp) {
              uint32_t x0, x1, x2, x3;
              ldsm_x4(x0, x1, x2, x3, xa + (X ^ (jp << 5)));
              s0 += (bf_lo(x0) + bf_hi(x0)) + (bf_lo(x2) + bf_hi(x2));
              s1 += (bf_lo(x1) + bf_hi(x1)) + (bf_lo(x3) + bf_hi(x3));
              q0 = fmaf(bf_lo(x0), bf_lo(x0), fmaf(bf_hi(x0), bf_hi(x0), fmaf(bf_lo(x2), bf_lo(x2), fmaf(bf_hi(x2), bf_hi(x2), q0))));
              q1 = fmaf(bf_lo(x1), bf_lo(x1), fmaf(bf_hi(x1), bf_hi(x1), fmaf(bf_lo(x3), bf_lo(x3), fmaf(bf_hi(x3), bf_hi(x3), q1))));
            }
            stats_out(s0, s1, q0, q1, g_stats + m0 + wrow0 + gq, t);
          }
          __syncwarp();
          if (lane == 0 && (layer || i != ix)) mbar_arrive(bar + B_XDONE);
          nbar_dyn(3 + wu, 128);
        }
        wgmma_wait<1>();
        if (elected) release2(bar + B_EMPTYS + sp * 8);
        sp = s;
        if (++s == 3) { s = 0; ++u; }
      }
      {
        const uint64_t dap = make_desc_ns(sb + SM_AP + wu * 1024, 0, 128), dbp = make_desc_ns(sb + SM_BP + (layer & 1) * 6144, 0, 128);
        if (wu == 0) {
          wgmma_wait<0>();
          if (elected) mbar_arrive(bar + B_R0);
          nbar<6, 256>();
        }
        if (layer < 2) mbar_wait(bar + (layer ? B_CS2 : B_CS), 0);
        mbar_wait(bar + B_STAT, layer & 1);
        mbar_wait(bar + B_FULLS + 16, layer & 1);
        wgmma_fence();
        wgmma_n256_k(acc, dap, dbp, 1);
#pragma unroll
        for (int k = 0; k < 4; ++k) wgmma_n256(acc, D128(dA0 + (QA >> 8) * 1024 + k * 2), D128(dB0 + (QK >> 8) * 1024 + k * 128), 1);
        mbar_wait(bar + B_FULLS, 1);
        PROFT(tid_ == 128, layer * 16 + 9);
        wgmma_fence();
#pragma unroll
        for (int k = 0; k < 4; ++k) wgmma_n256(acc, D128(dA0 + (QA & 15) * 1024 + k * 2), D128(dB0 + (QK & 15) * 1024 + k * 128), 1);
        wgmma_commit();
        if (wu) nbar<6, 256>();
#define Q_TAIL() \
        wgmma_n128_k(acc, dap, dbp + 256, 1); \
        _Pragma("unroll") for (int k = 0; k < 4; ++k) wgmma_n128(acc, D128(dA0 + (QA >> 8) * 1024 + k * 2), D128(dB0 + (QQ >> 8) * 1024 + k * 128), 1); \
        _Pragma("unroll") for (int k = 0; k < 4; ++k) wgmma_n128(acc, D128(dA0 + (QA & 15) * 1024 + k * 2), D128(dB0 + (QQ & 15) * 1024 + k * 128), 1);
        Q_TAIL();
        wgmma_commit();
        wgmma_wait<1>();
#pragma unroll
        for (int i = 0; i < 128; ++i) asm volatile("" : "+f"(acc[i]) :: "memory");
      }
    }
    uint32_t xo[32];
    {
      PHASE_CTX();
      PROFT(tid_ == 128, layer * 16 + 1);
      const bool isB = layer & 1;
      const int cu = c.cu;
      if (cu >= 4) asm volatile("bar.arrive 7, 256;" ::: "memory");
      if (elected && cu == 4) mbar_arrive(bar + B_R0);
      uint32_t kq[64];
      const uint32_t rowq = rowo & 8191;
      const float rs0 = lds_f(sb + SM_RS + (16 + wrow0 + gq) * 4), rs1 = lds_f(sb + SM_RS + (24 + wrow0 + gq) * 4);
#define Q_DONE() \
      wgmma_wait<0>(); \
      if (lane == 0) release2(bar + B_E0); \
      _Pragma("unroll") for (int i = 128; i < 192; ++i) asm volatile("" : "+f"(acc[i]) :: "memory"); \
      _Pragma("unroll") for (int i = 0; i < 32; ++i) kq[32 + i] = pack_bf16(acc[128 + 2 * i], acc[129 + 2 * i]);
      if (isB) {
        if (cu == 0) asm volatile("bar.arrive 10, 64;" ::: "memory");
        if (elected) release2(bar + B_E1);
        const int e = gq & 1;
        const bool sel = t > (gq >> 1);
        const uint32_t rja = sb + SM_RS + (wrow0 + 2 * t + e) * 4;
        const float rjA0 = lds_f(rja + 32), rjA1 = lds_f(rja + 64), rjB0 = lds_f(rja + (sel ? 0 : 64)), rjB1 = lds_f(rja + (sel ? 32 : 96));
        uint32_t vv[32];
#pragma unroll
        for (int i = 0; i < 16; ++i) { kq[i] = pack_bf16(acc[2 * i], acc[2 * i + 1]); vv[i] = pack_bf16(acc[64 + 2 * i], acc[65 + 2 * i]); }
        const uint32_t rB = sb + 4 * SLOT + wg * 4 * KVT + rowq;
        auto dump = [&](int hp) {
          const uint32_t kb = rB + 2048 + (hp ^ wg) * 2 * KVT;
#pragma unroll
          for (int jp = 0; jp < 4; ++jp) {
            stsm_x4(kb + (X ^ (jp << 5)), kq[16 * hp + 4 * jp], kq[16 * hp + 4 * jp + 1], kq[16 * hp + 4 * jp + 2], kq[16 * hp + 4 * jp + 3]);
            stsm_x4(kb + KVT + (X ^ (jp << 5)), vv[16 * hp + 4 * jp], vv[16 * hp + 4 * jp + 1], vv[16 * hp + 4 * jp + 2], vv[16 * hp + 4 * jp + 3]);
          }
          if (cu == 3) {
            const uint32_t kd = rB + 2048 + 32768 + (1 - hp) * 2 * KVT;
#pragma unroll
            for (int jp = 0; jp < 4; ++jp) {
              stsm_x4(kd + (X ^ (jp << 5)), kq[16 * hp + 4 * jp], kq[16 * hp + 4 * jp + 1], kq[16 * hp + 4 * jp + 2], kq[16 * hp + 4 * jp + 3]);
              stsm_x4(kd + KVT + (X ^ (jp << 5)), vv[16 * hp + 4 * jp], vv[16 * hp + 4 * jp + 1], vv[16 * hp + 4 * jp + 2], vv[16 * hp + 4 * jp + 3]);
            }
            if (hp) asm volatile("bar.arrive 15, 64;" ::: "memory"); else asm volatile("bar.arrive 9, 64;" ::: "memory");
          }
          asm volatile("bar.arrive %0, 224;" :: "r"(hp ? 13 + (cu >> 2) : 8 + (cu & 4)) : "memory");
        };
        uint4* const hbuf = g_halo + ((c.rb * 8 + g) * 2 + (layer >> 1)) * 512 + lane;
        if (cu < 4) {
          nbar<7, 256>();
          dump(0);
        }
#pragma unroll
        for (int i = 16; i < 32; ++i) { kq[i] = pack_bf16(acc[2 * i], acc[2 * i + 1]); vv[i] = pack_bf16(acc[64 + 2 * i], acc[65 + 2 * i]); }
        if (cu >= 4) {
          if (cu == 7) {
#pragma unroll
            for (int jp = 0; jp < 8; ++jp) {
              st_relaxed4(hbuf + jp * 32, ~kq[4 * jp], ~kq[4 * jp + 1], ~kq[4 * jp + 2], ~kq[4 * jp + 3]);
              st_relaxed4(hbuf + 256 + jp * 32, ~vv[4 * jp], ~vv[4 * jp + 1], ~vv[4 * jp + 2], ~vv[4 * jp + 3]);
            }
          }
          dump(0);
          dump(1);
        }
        PROFT(tid_ == 128, layer * 16 + 2);
        constexpr float SC = 0.17677669529663687f * L2E;
        const float fA0 = rjA0 * rs0 * SC, fB0 = rjB0 * rs0 * SC, fA1 = rjA1 * rs1 * SC, fB1 = rjB1 * rs1 * SC;
        const float bA0 = (m0 + wrow0) ? 0.f : -1e30f, bB = sel ? bA0 : 0.f;
        const uint32_t pA_ = e ? 0x1044u : 0x4410u, pB_ = e ? 0x3244u : 0x4432u, pLo = sel ? pB_ : 0x4444u, pHi = sel ? 0x4444u : pB_;
        const uint32_t KX = ((lane >> 3) ^ (lane & 7)) << 4;
        Q_DONE();
        if (cu == 0) {
          nbar<11, 64>();
        } else if (cu == 4) {
          uint4 hv[16];
          if (c.rb > 0) {
            uint32_t n = 0;
#pragma unroll 1
            while (true) {
              uint32_t mn = 0xFFFFFFFFu;
#pragma unroll
              for (int i = 0; i < 16; ++i) hv[i] = ld_relaxed4(hbuf - 16 * 512 + i * 32);
#pragma unroll
              for (int i = 0; i < 16; ++i) mn = __vimin3_u32(__vimin3_u32(mn, hv[i].x, hv[i].y), hv[i].z, hv[i].w);
              if (__all_sync(0xffffffffu, mn != 0u)) break;
              if (++n > (1u << 20)) { g_err = 4u; break; }
            }
          } else {
#pragma unroll
            for (int i = 0; i < 16; ++i) hv[i] = make_uint4(~0u, ~0u, ~0u, ~0u);
          }
          nbar<10, 64>();
#pragma unroll
          for (int i = 0; i < 16; ++i)
            stsm_x4(rB - 4 * KVT + (((i >> 2) & 1) * 2 + (i >> 3)) * KVT + (X ^ ((i & 3) << 5)), ~hv[i].x, ~hv[i].y, ~hv[i].z, ~hv[i].w);
          asm volatile("bar.arrive 11, 64;" ::: "memory");
          nbar<9, 64>();
        } else {
          nbar_dyn(8 + (cu & 4), 224);
        }
        PROFT(tid_ == 128, layer * 16 + 5);
        PROFT(lane == 0 && layer == PL, 136 + cw);
        auto attend = [&](int hp) {
          const uint32_t qad = sb + (XS + 1 - hp) * SLOT + rowo, kt = rB + 2 * (hp ^ wg) * KVT - (lane & 8) * 128, vt = rB + (2 * (hp ^ wg) + 1) * KVT;
          __syncwarp();
          uint32_t kb[2][2][4], vb[2][2][2][4];
#pragma unroll
          for (int h = 0; h < 2; ++h)
#pragma unroll
            for (int nt = 0; nt < 2; ++nt) ldsm_x4(kb[h][nt][0], kb[h][nt][1], kb[h][nt][2], kb[h][nt][3], kt + nt * 1024 + (KX ^ (h << 6)));
#pragma unroll
          for (int ks = 0; ks < 2; ++ks)
#pragma unroll
            for (int np = 0; np < 2; ++np)
#pragma unroll
              for (int h = 0; h < 2; ++h)
                ldsm_x4_t(vb[h][ks][np][0], vb[h][ks][np][1], vb[h][ks][np][2], vb[h][ks][np][3], vt + ks * 2048 + (X ^ (h << 6) ^ (np << 5)));
          if (hp == 0 && lane == 0) release2(bar + B_E3);
          if (DB1 == 1 && hp == 0 && cu < 4) dump(1);
          float la[2][2], lb[2][2], mx[2][2], sm[2][2];
#pragma unroll
          for (int h = 0; h < 2; ++h) {
            const int qo = 32 + 16 * hp + 8 * h, ko = 16 * hp + 8 * h;
            float sc[4][4];
#pragma unroll
            for (int nt = 0; nt < 4; ++nt) {
              sc[nt][0] = sc[nt][1] = sc[nt][2] = sc[nt][3] = 0.f;
#pragma unroll
              for (int ks = 0; ks < 2; ++ks)
                mma_bf16(sc[nt], kq[qo + 4 * ks], kq[qo + 4 * ks + 1], kq[qo + 4 * ks + 2], kq[qo + 4 * ks + 3],
                         nt < 2 ? kb[h][nt & 1][2 * ks] : kq[ko + 4 * ks + (nt & 1)], nt < 2 ? kb[h][nt & 1][2 * ks + 1] : kq[ko + 4 * ks + 2 + (nt & 1)]);
            }
            la[h][0] = fmaf(e ? sc[1][1] : sc[1][0], fA0, bA0);
            lb[h][0] = fmaf(sel ? (e ? sc[0][1] : sc[0][0]) : (e ? sc[2][1] : sc[2][0]), fB0, bB);
            la[h][1] = (e ? sc[2][3] : sc[2][2]) * fA1;
            lb[h][1] = fmaf(sel ? (e ? sc[1][3] : sc[1][2]) : (e ? sc[3][3] : sc[3][2]), fB1, bB);
            mx[h][0] = fmaxf(la[h][0], lb[h][0]); mx[h][1] = fmaxf(la[h][1], lb[h][1]);
          }
#pragma unroll
          for (int o = 1; o <= 2; o <<= 1)
#pragma unroll
            for (int h = 0; h < 2; ++h)
#pragma unroll
              for (int r = 0; r < 2; ++r) mx[h][r] = fmaxf(mx[h][r], __shfl_xor_sync(0xffffffffu, mx[h][r], o));
          float oa[2][4][4];
#pragma unroll
          for (int h = 0; h < 2; ++h) {
#pragma unroll
            for (int r = 0; r < 2; ++r) { la[h][r] = ex2(la[h][r] - mx[h][r]); lb[h][r] = ex2(lb[h][r] - mx[h][r]); sm[h][r] = la[h][r] + lb[h][r]; }
            const uint32_t p0 = pack_bf16(la[h][0] * rjA0, lb[h][0] * rjB0), p1 = pack_bf16(la[h][1] * rjA1, lb[h][1] * rjB1);
            const uint32_t a00 = __byte_perm(p0, 0u, pLo), a02 = __byte_perm(p0, 0u, pA_), a03 = __byte_perm(p1, 0u, pLo);
            const uint32_t a10 = __byte_perm(p0, 0u, pHi), a11 = __byte_perm(p1, 0u, pA_), a13 = __byte_perm(p1, 0u, pHi);
#pragma unroll
            for (int i = 0; i < 4; ++i) {
              oa[h][i][0] = oa[h][i][1] = oa[h][i][2] = oa[h][i][3] = 0.f;
              mma_bf16(oa[h][i], a00, 0u, a02, a03, vb[h][0][i >> 1][2 * (i & 1)], vb[h][0][i >> 1][2 * (i & 1) + 1]);
              mma_bf16(oa[h][i], a10, a11, 0u, a13, vb[h][1][i >> 1][2 * (i & 1)], vb[h][1][i >> 1][2 * (i & 1) + 1]);
            }
          }
#pragma unroll
          for (int o = 1; o <= 2; o <<= 1)
#pragma unroll
            for (int h = 0; h < 2; ++h)
#pragma unroll
              for (int r = 0; r < 2; ++r) sm[h][r] += __shfl_xor_sync(0xffffffffu, sm[h][r], o);
          mbar_wait(bar + (hp ? B_XOLD2 : B_XOLD), 1);
#pragma unroll
          for (int jp = 0; jp < 4; ++jp) ldsm_x4(xo[16 * hp + 4 * jp], xo[16 * hp + 4 * jp + 1], xo[16 * hp + 4 * jp + 2], xo[16 * hp + 4 * jp + 3], qad + (X ^ (jp << 5)));
#pragma unroll
          for (int h = 0; h < 2; ++h) {
            const float i0 = rcp(sm[h][0]), i1 = rcp(sm[h][1]);
#pragma unroll
            for (int np = 0; np < 2; ++np)
              stsm_x4(qad + (X ^ (h << 6) ^ (np << 5)),
                      pack_bf16(oa[h][2 * np][0] * i0, oa[h][2 * np][1] * i0), pack_bf16(oa[h][2 * np][2] * i1, oa[h][2 * np][3] * i1),
                      pack_bf16(oa[h][2 * np + 1][0] * i0, oa[h][2 * np + 1][1] * i0), pack_bf16(oa[h][2 * np + 1][2] * i1, oa[h][2 * np + 1][3] * i1));
          }
          __syncwarp();
          slab_out_half(sb + (XS + 1 - hp) * SLOT, g_o + (size_t)m0 * D_ + g * 128 + hp * 64, wrow0, lane, hp);
          __syncwarp();
          if (lane == 0) mbar_arrive(bar + (hp ? B_ODONE : B_OH1));
          PROFT(lane == 0 && layer == PL && hp == 0, 128 + cw);
        };
        attend(0);
        if (DB1 == 2 && cu < 4) dump(1);
        if (cu == 4) nbar<15, 64>();
        else if (cu != 0) nbar_dyn(13 + (cu >> 2), 224);
        attend(1);
      } else {
#pragma unroll
        for (int i = 0; i < 32; ++i) kq[i] = pack_bf16(acc[2 * i], acc[2 * i + 1]);
        if (cu < 4) nbar<7, 256>();
        {
          const uint32_t vb = sb + (5 + 3 * wg) * SLOT + (rowq >> 1) + ((lchk ^ ((lane & 7) >> 1)) << 4);
#pragma unroll
          for (int jp = 8; jp < 16; ++jp)
            stsm_x4((vb ^ ((jp & 1) << 5)) + ((jp >> 1) & 3) * 4096,
                    pack_bf16(acc[8 * jp], acc[8 * jp + 1]), pack_bf16(acc[8 * jp + 2], acc[8 * jp + 3]),
                    pack_bf16(acc[8 * jp + 4], acc[8 * jp + 5]), pack_bf16(acc[8 * jp + 6], acc[8 * jp + 7]));
        }
        PROFT(tid_ == 128, layer * 16 + 2);
        Q_DONE();
        const uint32_t pA = sb + (3 + 3 * wg) * SLOT + (rowo & 8191);
        float sc0 = rs0 * L2E, sc1 = rs1 * L2E;
        const uint32_t wa0 = sb + SM_WPHI + lrow * 80 + lchk * 16;
        const uint32_t wu = c.cu >> 2, par = (layer >> 1) & 1;
        float p[2][4][4];
        uint32_t raw[2][4][4], ph[2][4][4];
        float kva[20], oa[2][20];
        auto kv_start = [&](int hp) {
#pragma unroll
          for (int h = 0; h < 2; ++h)
#pragma unroll
            for (int cp = 0; cp < 4; ++cp)
              stsm_x4(pA + hp * 16384 + h * 8192 + (X ^ (cp << 5)), ph[h][cp][0], ph[h][cp][1], ph[h][cp][2], ph[h][cp][3]);
          PROFT(tid_ == 128, layer * 16 + 11);
          fence_async_smem();
          nbar<1, 256>();
          const uint32_t hu = 2 * hp + wu;
          const uint32_t dP = (((sb + 3 * SLOT + hu * 8192) & 0x3FFFF) >> 4) | (512u << 16);
          const uint32_t dV = (((sb + 5 * SLOT + hu * 4096) & 0x3FFFF) >> 4) | (((SM_SD - 5 * SLOT - hu * 4096) >> 4) << 16);
          wgmma_fence();
#pragma unroll
          for (int ks = 0; ks < 8; ++ks)
            wgmma_n40_tt(kva, desc64(dP + (ks >> 2) * 3072 + (ks & 3) * 128, 0x40000040u),
                         desc64(dV + (ks >> 2) * (3072u - (2816u << 16)) + (ks & 3) * 64, 0x80000020u), ks != 0);
          wgmma_commit();
        };
        auto kv_end = [&](int hp) {
          wgmma_wait<0>();
#pragma unroll
          for (int i = 0; i < 20; ++i) asm volatile("" : "+f"(kva[i]) :: "memory");
          nbar_dyn(3 + wu, 128);
          PROFT(tid_ == 128, layer * 16 + 12);
          const bool od = lane & 1;
#pragma unroll
          for (int i = 0; i < 4; ++i)
            sts128(sb + (3 + hp) * SLOT + (cw * 128 + i * 32 + lane) * 16,
                   make_uint4(__float_as_uint(kva[4 * i]), __float_as_uint(kva[4 * i + 1]), __float_as_uint(kva[4 * i + 2]),
                              __float_as_uint(od == (i >= 2) ? 1.f : kva[4 * i + 3])));
          sts128(sb + (6 + hp) * SLOT + wg * 8192 + (wq * 32 + lane) * 16,
                 make_uint4(__float_as_uint(od ? kva[11] : kva[3]), __float_as_uint(od ? kva[15] : kva[7]), __float_as_uint(od ? kva[18] : kva[16]), __float_as_uint(1.f)));
          fence_async_smem();
          __syncwarp();
          if (lane == 0) mbar_arrive(bar + B_KVDONE - hp * 32);
          PROFT(tid_ == 128, layer * 16 + 3);
        };
        const uint4* const kvg = g_kv + (g * 2 + (layer >> 1)) * 2560 + cw * 128 + lane;
        uint4 u[5];
        auto kv_load = [&](int hp) {
#pragma unroll
          for (int i = 0; i < 4; ++i) u[i] = ld_relaxed4(kvg + hp * 1280 + i * 32);
          u[4] = ld_relaxed4(kvg + hp * 1280 + 1024 - cw * 96);
        };
        auto o_start = [&](int hp, const uint32_t (&pq)[2][4][4]) {
          PROFT(tid_ == 128 && hp == 0, layer * 16 + 10);
          if (hp == 0) mbar_wait(bar + B_KVDONE - 32, par);
          const bool od = lane & 1;
          uint32_t n = 0;
#pragma unroll 1
          while (!__all_sync(0xffffffffu, (od ? u[2].w : u[0].w) == 0x41800000u && (od ? u[3].w : u[1].w) == 0x41800000u && u[4].w == 0x41800000u)) {
#pragma unroll 1
            while (__any_sync(0xffffffffu, u[4].w < KVTH) && ++n < (1u << 20)) u[4].w = ld_relaxed(&kvg[hp * 1280 + 1024 - cw * 96].w);
            if (++n > (1u << 20)) { g_err = 6u; break; }
            kv_load(hp);
          }
          PROFT(tid_ == 128 && hp == 0, layer * 16 + 5);
          if (!od) { u[0].w = u[4].x; u[1].w = u[4].y; } else { u[2].w = u[4].x; u[3].w = u[4].y; }
#pragma unroll
          for (int i = 0; i < 4; i += 2)
            stsm_x4(sb + (5 + 3 * hp) * SLOT + rowo + (X ^ ((i & 2) << 4)),
                    pack_bf16(__uint_as_float(u[i].x), __uint_as_float(u[i].y)), pack_bf16(__uint_as_float(u[i].z), __uint_as_float(u[i].w)),
                    pack_bf16(__uint_as_float(u[i + 1].x), __uint_as_float(u[i + 1].y)), pack_bf16(__uint_as_float(u[i + 1].z), __uint_as_float(u[i + 1].w)));
          const uint32_t z2 = pack_bf16(__uint_as_float(u[4].z), __uint_as_float(u[4].z));
          if (t < 2) sts128(sb + (5 + 3 * hp) * SLOT + (wrow0 + gq + 8 * t) * 128 + ((4 ^ gq) << 4), make_uint4(z2, z2, z2, z2));
          fence_async_smem();
          nbar<1, 256>();
          PROFT(tid_ == 128 && hp == 1, layer * 16 + 4);
          const uint32_t dK = (((sb + (5 + 3 * hp) * SLOT) & 0x3FFFF) >> 4) | (512u << 16);
          wgmma_fence();
#pragma unroll
          for (int ks = 0; ks < 4; ++ks) {
#pragma unroll
            for (int hh = 0; hh < 2; ++hh) wgmma_n40_rs(oa[hh], pq[hh][ks], D128(dK + hh * 512 + ks * 128), ks != 0);
          }
          wgmma_commit();
        };
        auto o_end = [&](int hp) {
          wgmma_wait<0>();
#pragma unroll
          for (int i = 0; i < 20; ++i) asm volatile("" : "+f"(oa[0][i]), "+f"(oa[1][i]) :: "memory");
#pragma unroll
          for (int hh = 0; hh < 2; ++hh) {
            const float i0 = rcp(oa[hh][16] + 1e-6f), i1 = rcp(oa[hh][18] + 1e-6f);
            const uint32_t qad = sb + (3 + hp) * SLOT + rowo, hx = hh << 6;
#pragma unroll
            for (int np = 0; np < 2; ++np)
              stsm_x4(qad + (X ^ hx ^ (np << 5)),
                      pack_bf16(oa[hh][8 * np] * i0, oa[hh][8 * np + 1] * i0), pack_bf16(oa[hh][8 * np + 2] * i1, oa[hh][8 * np + 3] * i1),
                      pack_bf16(oa[hh][8 * np + 4] * i0, oa[hh][8 * np + 5] * i0), pack_bf16(oa[hh][8 * np + 6] * i1, oa[hh][8 * np + 7] * i1));
          }
          __syncwarp();
          slab_out_half(sb + (3 + hp) * SLOT, g_o + (size_t)m0 * D_ + g * 128 + hp * 64, wrow0, lane, hp);
          __syncwarp();
          if (lane == 0) mbar_arrive(bar + (hp ? B_ODONE : B_OH1));
        };
#define XO_LOAD() \
        mbar_wait(bar + B_XOLD, 0); \
        mbar_wait(bar + B_XOLD2, 0); \
        _Pragma("unroll") for (int jp = 0; jp < 8; ++jp) \
          ldsm_x4(xo[4 * jp], xo[4 * jp + 1], xo[4 * jp + 2], xo[4 * jp + 3], sb + (XS + 1 - (jp >> 2)) * SLOT + rowo + (X ^ ((jp & 3) << 5)));
#define SC_RELOAD() \
        sc0 = __uint_as_float(lds_vol(sb + SM_RS + (16 + wrow0 + gq) * 4)) * L2E; sc1 = __uint_as_float(lds_vol(sb + SM_RS + (24 + wrow0 + gq) * 4)) * L2E;
        __syncwarp();
        phi_proj<0>(p, kq, wa0);
        phi_exp(raw[0], p[0], sc0, sc1);
        phi_exp(raw[1], p[1], sc0, sc1);
        phi_proj<16>(p, kq, wa0 + 5120);
        phi_norm<0>(ph, raw, kq, wa0, sc0, sc1, rs0, rs1);
        kv_start(0);
        phi_exp(raw[0], p[0], sc0, sc1);
        kv_end(0);
        if (RL & 1) { SC_RELOAD(); }
        XO_LOAD();
        phi_exp(raw[1], p[1], sc0, sc1);
        phi_proj<32>(p, kq, wa0);
        phi_norm<16>(ph, raw, kq, wa0 + 5120, sc0, sc1, rs0, rs1);
        kv_start(1);
        if (lane == 0) release2(bar + B_E3);
        phi_exp(raw[0], p[0], sc0, sc1);
        kv_end(1);
        if (RL & 2) { SC_RELOAD(); }
        kv_load(0);
        phi_exp(raw[1], p[1], sc0, sc1);
        phi_proj<48>(p, kq, wa0 + 5120);
        phi_norm<32>(ph, raw, kq, wa0, sc0, sc1, 1.f, 1.f);
        o_start(0, ph);
        phi_exp(raw[0], p[0], sc0, sc1);
        o_end(0);
        SC_RELOAD();
        kv_load(1);
        phi_exp(raw[1], p[1], sc0, sc1);
        phi_norm<48>(ph, raw, kq, wa0 + 5120, sc0, sc1, 1.f, 1.f);
        o_start(1, ph);
        o_end(1);
      }
      __syncwarp();
      PROFT(lane == 0 && layer == PL, 216 + cw);
      if (lane == 0) mbar_arrive(bar + B_EPI);
      PROFT(tid_ == 128, layer * 16 + 6);
    }
    {
      PHASE_CTX();
      const uint32_t wu = c.cu >> 2;
      const uint32_t dA0 = (((sb + wu * 8192) & 0x3FFFF) >> 4) | (1u << 16), dB0 = ((sb & 0x3FFFF) >> 4) | (512u << 16);
#pragma unroll
      for (int i = 0; i < 32; ++i) { acc[128 + 2 * i] = bf_lo(xo[i]); acc[129 + 2 * i] = bf_hi(xo[i]); }
      nbar_dyn(3 + wg, 128);
      uint64_t ta = (layer & 1) ? WO_A1 : WO_A0, tw = (layer & 1) ? WO_B1 : WO_B0;
#pragma unroll 1
      for (int i = 0; i < 16; ++i) {
        bool rel = i > 0 && i < 12;
        if (DRY && rel && !__all_sync(0xffffffffu, mbar_test_wait(bar + B_FULLT + i * 8, layer & 1))) {
          wgmma_wait<0>();
          if (elected) release2(bar + B_CONS + (i - 1) * 8);
          rel = false;
        }
        mbar_wait(bar + B_FULLT + i * 8, layer & 1);
        PROFT(tid_ == 128 && layer == PL, 160 + i);
        const uint32_t da = dA0 + ((uint32_t)ta & 15) * 1024, db = dB0 + ((uint32_t)tw & 15) * 1024;
        ta >>= 4; tw >>= 4;
        wgmma_fence();
#pragma unroll
        for (int k = 0; k < 4; ++k) wgmma_n128(acc, D128(da + k * 2), D128(db + k * 128), 1);
        wgmma_commit();
        if (i == 0) {
          if (elected) {
            release2(bar + B_E2);
          }
        } else {
          wgmma_wait<1>();
          if (elected && rel) release2(bar + B_CONS + (i - 1) * 8);
          if (elected && (unsigned)(i - 13) < 2u && layer + 1 < NLAYERS) release2(bar + B_EMPTYS + (i - 13) * 8);
        }
      }
      const bool last = layer == NLAYERS - 1;
      wgmma_wait<0>();
#pragma unroll
      for (int i = 128; i < 192; ++i) asm volatile("" : "+f"(acc[i]) :: "memory");
      if (elected && !last) release2(bar + B_EMPTYS + 16);
      PROFT(tid_ == 128, layer * 16 + 7);
#pragma unroll
      for (int jp = 0; jp < 4; ++jp)
        stsm_x4(sb + XS * SLOT + rowo + (X ^ (jp << 5)),
                pack_bf16(acc[128 + 8 * jp], acc[129 + 8 * jp]), pack_bf16(acc[130 + 8 * jp], acc[131 + 8 * jp]),
                pack_bf16(acc[132 + 8 * jp], acc[133 + 8 * jp]), pack_bf16(acc[134 + 8 * jp], acc[135 + 8 * jp]));
      if (last) {
        __syncwarp();
        slab_out_half(sb + XS * SLOT, c.out + (size_t)m0 * D_ + g * 128, wrow0, lane);
        X_H1();
        __syncwarp();
        slab_out_half(sb + (XS + 1) * SLOT, c.out + (size_t)m0 * D_ + g * 128 + 64, wrow0, lane);
        __syncwarp();
        if (lane == 0) mbar_arrive(bar + B_XDONE);
        PROFT(tid_ == 128, layer * 16 + 24);
        break;
      }
      __syncwarp();
      slab_out_half(sb + XS * SLOT, g_x + (size_t)m0 * D_ + g * 128, wrow0, lane, true);
      __syncwarp();
      if (lane == 0) mbar_arrive(bar + B_XH0);
      nbar_dyn(3 + wu, 128);
    }
  }
}

__device__ __forceinline__ void flag_fetch(uint32_t bar, uint32_t cp, const unsigned int* f) {
  asm volatile("{\n.reg .pred p;\nelect.sync _|p, 0xffffffff;\n@p mbarrier.expect_tx.relaxed.cta.shared::cta.b64 [%2], 64;\n"
               "@p cp.async.bulk.shared::cluster.global.mbarrier::complete_tx::bytes [%0], [%1], 64, [%2];\n}\n"
               ::"r"(cp), "l"(f), "r"(bar + 128) : "memory");
}
__device__ __forceinline__ void src_wait_async(uint32_t bar, uint32_t cp, const unsigned int* f, unsigned int target, int kb, uint32_t& ready, int lane) {
  uint32_t n = 0;
#pragma unroll 1
  while (true) {
    ready |= __ballot_sync(0xffffffffu, (int)(lds_vol(cp + (lane & 15) * 4) - target) >= 0);
    if ((ready >> kb) & 1) break;
    if (n > (1u << 20)) { g_err = 5u; break; }
    if ((n++ & PMOD) == 0) flag_fetch(bar, cp, f);
    __nanosleep(PSL);
  }
}

__device__ __forceinline__ int kblock0(int i, int g) {
  const int j = i >> 1, p = max(g, NCOM) + j - NCOM;
  return (j < NCOM ? j : p < 8 ? p : p - 8 + NCOM) * 2 + (i & 1);
}

#define WOORD 0xFDB9753ECA864210ull
__device__ __forceinline__ int wo_kblock(int m, int g) { return (2 * g + (int)((WOORD >> (4 * m)) & 15)) & 15; }

__global__ void __cluster_dims__(2, 1, 1) __launch_bounds__(384, 1)
mega_kernel(const __grid_constant__ CUtensorMap tm_x0, const __grid_constant__ CUtensorMap tm_x,
            const __grid_constant__ CUtensorMap tm_o,
            const __grid_constant__ CUtensorMap tm_wA, const __grid_constant__ CUtensorMap tm_wB,
            const __grid_constant__ CUtensorMap tm_woA, const __grid_constant__ CUtensorMap tm_woB,
                        const bf16* __restrict__ wB, const bf16* __restrict__ wphi, bf16* __restrict__ out) {
  extern __shared__ uint8_t smem_raw[];
  const uint32_t sb = (smem_u32(smem_raw) + 1023u) & ~1023u;
  const uint32_t bar = sb + SM_BAR;
  const int warp = __shfl_sync(0xffffffffu, threadIdx.x >> 5, 0), lane = threadIdx.x & 31;
  if (blockIdx.x >= 128) {
    const int xb = blockIdx.x - 128;
    const int ch = threadIdx.x % 96, rg = threadIdx.x / 96, gg = xb * 2 + ch / 48, sec = (ch % 48) >> 4;
    const uint4* src = reinterpret_cast<const uint4*>(wB + (size_t)rg * 3072 + (sec == 2 ? 0 : 1024 + sec * 1024) + gg * 128 + (ch & 15) * 8);
    float s[8] = {0.f, 0.f, 0.f, 0.f, 0.f, 0.f, 0.f, 0.f};
#pragma unroll 1
    for (int r0 = 0; r0 < 256; r0 += 32) {
      uint4 v[32];
#pragma unroll
      for (int r = 0; r < 32; ++r) v[r] = __ldg(src + (size_t)(r0 + r) * 1536);
#pragma unroll
      for (int r = 0; r < 32; ++r) {
        s[0] += bf_lo(v[r].x); s[1] += bf_hi(v[r].x); s[2] += bf_lo(v[r].y); s[3] += bf_hi(v[r].y);
        s[4] += bf_lo(v[r].z); s[5] += bf_hi(v[r].z); s[6] += bf_lo(v[r].w); s[7] += bf_hi(v[r].w);
      }
    }
    float* cd = g_cs + (ld_relaxed(&g_epoch) & 1) * 6144 + 3072 + xb * 768 + ch * 8;
    red_add4(cd, s[0], s[1], s[2], s[3]);
    red_add4(cd + 4, s[4], s[5], s[6], s[7]);
    nbar<1, 384>();
    if (threadIdx.x < 2) flag_add(&g_csflag[8 + xb * 2 + threadIdx.x].v);
    return;
  }
  const int bid = blockIdx.x;
  const int cr = bid & 1;
  const int g = (bid >> 1) & 7;
  const int rb = (bid >> 4) * 2 + cr;
  const int m0 = rb * 128;

  if (warp < 4) {
    asm volatile("setmaxnreg.dec.sync.aligned.u32 40;");
    asm volatile("barrier.cluster.arrive.relaxed.aligned;" ::: "memory");
    const unsigned int epoch = warp ? ld_relaxed(&g_epoch) : 0u;
    if (warp) cluster_wait();
    unsigned int xbase = epoch * NLAYERS;
    auto wo_a = [&](int layer, int m1) {
      uint64_t ts = ((layer & 1) ? WO_A1 : WO_A0) >> (4 * m1), td = ((layer & 1) ? WO_DA1 : WO_DA0) >> (4 * m1), tk = WOORD >> (4 * m1);
      uint32_t ready = 0u;
#pragma unroll 1
      for (int m = m1; m < 16; m += AW) {
        const int kb = (2 * g + (uint32_t)tk) & 15;
        uint32_t dst = sb + ((uint32_t)ts & 15) * SLOT, fb = bar + B_FULLT + m * 8, eb = bar + B_CONS + ((uint32_t)td & 15) * 8;
        int kc = kb * 64;
        ts >>= 4 * AW; td >>= 4 * AW; tk >>= 4 * AW;
        asm volatile("" : "+r"(dst), "+r"(fb), "+r"(eb), "+r"(kc));
        bool fr = false;
        if (!((ready >> kb) & 1)) {
          PROFT(m == 2 && lane == 0, 64 + layer * 16 + 2);
          if (EP && m > EP) src_wait_async(bar, bar + B_FLG, g_of + rb * 32, xbase + layer + 1, kb, ready, lane);
          else fr = src_wait_tma(g_of + rb * 32, xbase + layer + 1, 1u << kb, ready, lane, eb, layer & 1);
          fence_async_all();
        }
        if (!fr) mbar_wait_u(eb, layer & 1);
        tma_2d_e(dst, &tm_o, kc, m0, fb);
        if (EP && m >= EP && (ready & 0xFFFFu) != 0xFFFFu) flag_fetch(bar, bar + B_FLG, g_of + rb * 32);
        PROFT(lane == 0 && layer == PL, 176 + m);
      }
    };
    auto wo_w = [&](int layer) {
      const CUtensorMap* tx = layer == 0 ? &tm_x0 : &tm_x;
      const CUtensorMap* two = (layer & 1) ? &tm_woB : &tm_woA;
      uint64_t ts = (layer & 1) ? WO_B1 : WO_B0, td = (layer & 1) ? WO_DB1 : WO_DB0, tk = WOORD;
      uint32_t pb = 0;
      fence_async_all();
      mbar_wait_u(bar + B_R0, layer & 1);
      expect_tx_e(bar + B_XOLD, 16384);
      tma_2d_e(sb + (XS + 1) * SLOT, tx, g * 128, m0, bar + B_XOLD);
#pragma unroll 1
      for (int m = 0; m < 16; ++m) {
        uint32_t dst = sb + ((uint32_t)ts & 15) * SLOT + cr * 8192, fb = bar + B_FULLT + m * 8, eb = bar + B_CONS + ((uint32_t)td & 15) * 8;
        int kc = ((2 * g + (uint32_t)tk) & 15) * 64;
        ts >>= 4; td >>= 4; tk >>= 4;
        asm volatile("" : "+r"(dst), "+r"(fb), "+r"(eb), "+r"(kc));
        if (eb != pb) mbar_wait_u(eb, layer & 1);
        pb = eb;
        tma_2d_mc_e(dst, two, g * 128 + cr * 64, kc, fb);
        expect_tx_e(fb, m < 2 ? 16384 : 32768);
        PROFT(lane == 0 && layer == PL, 144 + m);
        if (m == ((layer & 1) ? XB2 : 0)) {
          expect_tx_e(bar + B_XOLD2, 16384);
          tma_2d_e(sb + XS * SLOT, tx, g * 128 + 64, m0, bar + B_XOLD2);
        }
      }
    };
    if (warp == 0) {
      cluster_wait();
      PROFT(lane == 0, 125);
#pragma unroll 1
      for (int layer = 0; layer < NLAYERS; ++layer) {
        const CUtensorMap* tx = layer == 0 ? &tm_x0 : &tm_x;
        const CUtensorMap* tw = (layer & 1) ? &tm_wB : &tm_wA;
        uint32_t s = layer == 0, u = 0, ready = layer == 0 ? 0xFFFFu : 0u;
#pragma unroll 1
        for (int i = s; i < 16; ++i) {
          const int kb = layer == 0 ? kblock0(i, g) : wo_kblock(i, g), kc = kb * 64;
          const uint32_t fb = bar + B_FULLS + s * 8;
          const uint32_t kd = sb + (((QK >> (4 * s)) & 15) + cr) * SLOT, qd = sb + ((QQ >> (4 * s)) & 15) * SLOT + cr * 8192;
          const uint32_t need = 1u << kb;
          const bool ext = i >= 2 || layer == 0, early = ext && (ready & need) == need;
          mbar_wait_u(bar + B_EMPTYS + s * 8, (u + (s ? layer : 0) + 1) & 1);
          if (early) tma_2d_e(sb + ((QA >> (4 * s)) & 15) * SLOT, tx, kc, m0, fb);
          tma_2d_mc_e(kd, tw, 1024 + cr * 1024 + g * 128, kc, fb);
          tma_2d_mc_e(kd + 8192, tw, 1024 + cr * 1024 + g * 128 + 64, kc, fb);
          tma_2d_mc_e(qd, tw, g * 128 + cr * 64, kc, fb);
          expect_tx_e(fb, ext ? 65536 : 49152);
          PROFT(lane == 0 && layer == 0 && i == 1, 31);
          if (layer == 0 && g >= NCOM && i == XPF + (((g - NCOM) * XPM) >> 2)) {
            if (i <= 2) mbar_wait_u(bar + B_FULLS, 0);
            tma_pf_e(&tm_x0, g * 128, m0);
            tma_pf_e(&tm_x0, g * 128 + 64, m0);
          }
          if (layer < 2 && i >= PFS) {
            const int j = i - PFS;
            if (j < 2) tma_pf_e(layer ? &tm_woB : &tm_woA, g * 128 + j * 64, rb * 64);
            else if (j < 8 && layer == 0) tma_pf_e(&tm_wB, ((j >> 1) - 1) * 1024 + g * 128 + (j & 1) * 64, rb * 64);
          }
          if (ext && !early) {
            PROFT(i == 2 && lane == 0, 64 + layer * 16 + 0);
            src_wait_tma(g_xf + rb * 32, xbase + layer + 1, need, ready, lane, fb, 0);
            PROFT(i == 2 && lane == 0, 64 + layer * 16 + 1);
            fence_async_all();
            tma_2d_e(sb + ((QA >> (4 * s)) & 15) * SLOT, tx, kc, m0, fb);
          }
          if (++s == 3) { s = 0; ++u; }
        }
        if (layer == 0) xbase = ld_relaxed(&g_epoch) * NLAYERS;
        if (PG & 1) mbar_wait_u(bar + B_OH1, layer & 1);
        if (PG & 4) mbar_wait_u(bar + B_E3, layer & 1);
        wo_a(layer, 2);
      }
    } else {
      if (warp >= 2) {
        const int h2 = threadIdx.x - 64;
        if (h2 < 16) sts_f(sb + SM_RS + h2 * 4, 0.f);
        if (h2 < 16) sts_f(bar + B_FLG + h2 * 4, __uint_as_float(xbase));
        mbar_wait_u(bar + B_FULLS, 0);
        colsum(&tm_wA, g_cs + (epoch & 1) * 6144, rb, g, warp - 2, 2, lane, warp == 2 ? sb + SM_SD : (sb + SM_BP + 1023u) & ~1023u, bar + B_CB + (warp - 2) * 8, 0);
#pragma unroll 1
        for (int i = h2; i < 320; i += 64) g_kv[(g * 16 + rb) * 320 + i] = make_uint4(0u, 0u, 0u, 0u);
        fence_async_all();
        nbar<5, 64>();
        if (h2 == 0) flag_add(&g_csflag[g].v);
        PROFT(h2 == 0, 242);
#pragma unroll 1
        for (int i = h2; i < 512; i += 256) {
          uint4 w[4];
#pragma unroll
          for (int j = 0; j < 4; ++j) w[j] = __ldg(reinterpret_cast<const uint4*>(wphi + (size_t)g * 4096) + i + j * 64);
#pragma unroll
          for (int j = 0; j < 4; ++j) sts128(sb + SM_WPHI + ((i >> 2) + j * 16) * 80 + (i & 3) * 16, w[j]);
        }
      }
      if (warp == 1) {
        if (lane >= 27) {
          const CUtensorMap* tm = lane == 27 ? &tm_o : lane == 28 ? &tm_wB : lane == 29 ? &tm_woA : lane == 30 ? &tm_woB : &tm_x;
          asm volatile("prefetch.tensormap [%0];" ::"l"(tm) : "memory");
        }
        __syncwarp();
        {
#pragma unroll 1
          for (int e = 0;; ++e) {
            if (e > 0 && e < NLAYERS) {
              mbar_wait_u(bar + B_XH0, (e - 1) & 1);
              flag_set(g_xf + rb * 32 + 2 * g, xbase + e + 1);
            }
            mbar_wait_u(bar + B_XDONE, e & 1);
            PROFT(e < 4, 64 + e * 16 + 4);
            if (e == NLAYERS) {
              if (bid == 0) g_epoch = epoch + 1;
              break;
            }
            PROFT(e < 4, 64 + e * 16 + 5);
            flag_set(g_xf + rb * 32 + 2 * g + 1, xbase + e + 1);
            PROFT(e < 4, 64 + e * 16 + 7);
            if ((e & 1) == 0) {
#pragma unroll 1
              for (int hp = 0; hp < 2; ++hp) {
                uint4* kvl = g_kv + ((g * 2 + (e >> 1)) * 2 + hp) * 1280;
                mbar_wait_u(bar + B_KVDONE - hp * 32, (e >> 1) & 1);
                PROFT(e == PL, 243 + hp * 4);
                bulk_red_add_e(kvl + rb * 64, sb + (3 + hp) * SLOT + rb * 1024, 16384 - rb * 1024);
                if (rb) bulk_red_add_e(kvl, sb + (3 + hp) * SLOT, rb * 1024);
                bulk_red_add_e(kvl + 1024, sb + (6 + hp) * SLOT, 2048);
                bulk_red_add_e(kvl + 1152, sb + (6 + hp) * SLOT + 8192, 2048);
                bulk_commit();
                PROFT(e < 4, 64 + e * 16 + 6);
              }
              bulk_wait_read0();
              __syncwarp();
              if (lane < 2) release2(bar + B_E1);
              __syncwarp();
            }
            mbar_wait_u(bar + B_OH1, e & 1);
            PROFT(e == PL, 251);
            flag_set(g_of + rb * 32 + 2 * g, xbase + e + 1);
            PROFT(e < 4, 64 + e * 16 + 9);
            mbar_wait_u(bar + B_ODONE, e & 1);
            PROFT(e < 4, 64 + e * 16 + 8);
            flag_set(g_of + rb * 32 + 2 * g + 1, xbase + e + 1);
            PROFT(e < 4, 64 + e * 16 + 11);
          }
        }
      } else {
        const int h2 = threadIdx.x - 64;
        const float* cs = g_cs + (epoch & 1) * 6144;
#pragma unroll 1
        for (int layer = 0; layer < NLAYERS; ++layer) {
          if (warp == 2 && layer < 2) {
            if ((PG & 2) && layer) mbar_wait_u(bar + B_XH0, 0);
            if (lane == 0) flag_wait_t<CSLP>(&g_csflag[layer * 8 + g].v, (epoch + 1) * (16u + layer));
            __syncwarp();
            float4 a[3];
#pragma unroll
            for (int i = 0; i < 3; ++i) a[i] = __ldcg(reinterpret_cast<const float4*>(cs + layer * 3072 + g * 384) + i * 32 + lane);
#pragma unroll 1
            for (int i = 0; i < 3; ++i) {
              const float av[4] = {a[0].x, a[0].y, a[0].z, a[0].w};
              a[0] = a[1]; a[1] = a[2];
#pragma unroll
              for (int j = 0; j < 4; ++j) {
                const float c1 = bf16r(av[j]), c2 = bf16r(av[j] - c1), c3 = (av[j] - c1) - c2;
                sts128(sb + SM_BP + layer * 6144 + ((i * 32 + lane) * 4 + j) * 16, make_uint4(pack_bf16(c1, c2), pack_bf16(c3, 0.f), 0u, 0u));
              }
            }
            fence_async_smem();
            __syncwarp();
            if (lane == 0) mbar_arrive(bar + (layer ? B_CS2 : B_CS));
            PROFT(lane == 0, 64 + layer * 16 + 12);
            if (layer == 0) {
              uint4* hz = g_halo + (rb * 8 + g) * 1024;
#pragma unroll 2
              for (int i = lane; i < 1024; i += 32) hz[i] = make_uint4(0u, 0u, 0u, 0u);
              if (lane < 12) reinterpret_cast<float4*>(g_cs + ((epoch & 1) ^ 1) * 6144 + bid * 48)[lane] = make_float4(0.f, 0.f, 0.f, 0.f);
              g_stats[(2 + (lane >> 4)) * S_ + m0 + g * 16 + (lane & 15)] = make_float2(0.f, 0.f);
              __syncwarp();
              if (lane == 0) flag_add(&g_csflag[8 + g].v);
            }
          }
          if (warp == 3) {
            const bool hal = (layer & 1) && rb > 0;
            {
              uint32_t rdy = 0u;
              src_wait<256>(g_xf + rb * 32, xbase + layer + 1, 0xAAAAu, rdy, lane);
              rdy = 0u;
              if (hal) src_wait<256>(g_xf + (rb - 1) * 32, xbase + layer + 1, 0xAAAAu, rdy, lane);
            }
            float2 u[5];
            const float2* sp = g_stats + layer * S_ + m0 + lane;
#pragma unroll
            for (int i = 0; i < 4; ++i) u[i] = __ldcg(sp + i * 32);
            u[4] = __ldcg(hal ? sp - 16 : sp);
            if (layer == 3) g_stats[(lane >> 4) * S_ + m0 + g * 16 + (lane & 15)] = make_float2(0.f, 0.f);
#pragma unroll 1
            for (int i = 0; i < (hal ? 5 : 4); ++i) {
              const int r = i < 4 ? 16 + i * 32 + lane : lane;
              const float sum = u[0].x, sq = u[0].y;
              u[0] = u[1]; u[1] = u[2]; u[2] = u[3]; u[3] = u[4];
              const float mean = sum * (1.f / D_);
              const float var = fmaxf(fmaf(-sum, mean, sq) * (1.f / D_), 0.f);
              const float sd = bf16r(sqrtf(bf16r(bf16r(var) + 1e-5f)));
              sts_f(sb + SM_RS + r * 4, 1.f / sd);
              if (i < 4) {
                const float hm = -0.5f * bf16r(mean);
                const uint32_t s2 = pack_bf16(sd, sd);
                if (!(layer & 1)) sts128(sb + SM_SD + (r - 16) * 64 + ((r >> 1) & 3) * 16, make_uint4(s2, s2, s2, s2));
                sts128(sb + SM_AP + (r - 16) * 16, make_uint4(pack_bf16(hm, hm), pack_bf16(hm, 0.f), 0u, 0u));
              }
            }
            fence_async_smem();
            __syncwarp();
            if (lane == 0) mbar_arrive(bar + B_STAT);
            PROFT(lane == 0, 64 + layer * 16 + 14);
            wo_w(__shfl_sync(0xffffffffu, layer, 0));
          }
        }
      }
    }
    __syncwarp();
    asm volatile("barrier.cluster.arrive.relaxed.aligned;\nbarrier.cluster.wait.aligned;\n" ::: "memory");
  } else {
    if (warp == 5) {
      if (lane == 0) {
        mbar_init(bar + B_FULLS, 1);
        asm volatile("fence.mbarrier_init.release.cluster;" ::: "memory");
      }
      __syncwarp();
      expect_tx_e(bar + B_FULLS, 65536);
      tma_2d_e(sb + XS * SLOT, &tm_x0, 0, m0, bar + B_FULLS);
#pragma unroll
      for (int j = 0; j < 6; ++j)
        tma_2d_e(sb + (j < 4 ? j + 4 : j - 2) * 8192, &tm_wA, (j < 4 ? 1024 + (j >> 1) * 1024 : 0) + g * 128 + (j & 1) * 64, 0, bar + B_FULLS);
      PROFT(lane == 0, 241);
    }
    if (lane < 8 && warp != 5 && threadIdx.x != 128) {
      const int i = (warp - 4) * 8 + lane;
      mbar_init(bar + i * 8, i < 32 ? 1u << ((BAR_CNT >> (2 * i)) & 3) : i < 48 ? 1u : (i == 59 || i == 60) ? 16u : i < 63 ? 4u : 8u);
      asm volatile("fence.mbarrier_init.release.cluster;" ::: "memory");
    }
    __syncwarp();
    asm volatile("barrier.cluster.arrive.relaxed.aligned;" ::: "memory");
    asm volatile("setmaxnreg.inc.sync.aligned.u32 232;");
    cluster_wait();
    PROFT(threadIdx.x == 128, 0);
    Ctx c; c.sb = sb; c.g = g; c.rb = rb; c.cu = warp - 4; c.out = out;
    consumer(c);
    asm volatile("bar.warp.sync 0xffffffff;\nbarrier.cluster.arrive.relaxed.aligned;\nbarrier.cluster.wait.aligned;\n" ::: "memory");
  }
}

typedef CUresult (*PFN_encodeTiled)(CUtensorMap*, CUtensorMapDataType, cuuint32_t, void*, const cuuint64_t*, const cuuint64_t*,
                                    const cuuint32_t*, const cuuint32_t*, CUtensorMapInterleave, CUtensorMapSwizzle,
                                    CUtensorMapL2promotion, CUtensorMapFloatOOBfill);

static CUtensorMap make_map(PFN_encodeTiled enc, const void* ptr, uint64_t cols, uint64_t rows, uint32_t box_c, uint32_t box_r, uint32_t nb = 1) {
  CUtensorMap m;
  cuuint64_t dims[3] = {nb > 1 ? box_c : cols, rows, cols / box_c};
  cuuint64_t strides[2] = {cols * 2, box_c * 2};
  cuuint32_t box[3] = {box_c, box_r, nb};
  cuuint32_t es[3] = {1, 1, 1};
  CUresult r = enc(&m, CU_TENSOR_MAP_DATA_TYPE_BFLOAT16, nb > 1 ? 3 : 2, const_cast<void*>(ptr), dims, strides, box, es, CU_TENSOR_MAP_INTERLEAVE_NONE,
      CU_TENSOR_MAP_SWIZZLE_128B, CU_TENSOR_MAP_L2_PROMOTION_L2_256B, CU_TENSOR_MAP_FLOAT_OOB_FILL_NONE);
  (void)r;
  return m;
}

extern "C" void kernel_launch(void* const* d_in, const int* in_sizes, int n_in, void* d_out, int out_size) {
  const bf16* A_x = (const bf16*)d_in[0];
  const bf16* A_wqkv = (const bf16*)d_in[1];
  const bf16* A_wphi = (const bf16*)d_in[2];
  const bf16* A_wo = (const bf16*)d_in[3];
  const bf16* B_wqkv = (const bf16*)d_in[5];
  const bf16* B_wo = (const bf16*)d_in[6];
  bf16* out = (bf16*)d_out;

  static PFN_encodeTiled enc = nullptr;
  static bf16 *p_x, *p_o;
  if (!enc) {
    void* fn = nullptr; cudaDriverEntryPointQueryResult qr;
    cudaGetDriverEntryPoint("cuTensorMapEncodeTiled", &fn, cudaEnableDefault, &qr);
    enc = (PFN_encodeTiled)fn;
    cudaGetSymbolAddress((void**)&p_x, g_x);
    cudaGetSymbolAddress((void**)&p_o, g_o);
    cudaFuncSetAttribute(mega_kernel, cudaFuncAttributeMaxDynamicSharedMemorySize, SM_TOTAL);
  }
  CUtensorMap tm_x0 = make_map(enc, A_x, 1024, 2048, 64, 128);
  CUtensorMap tm_x = make_map(enc, p_x, 1024, 2048, 64, 128);
  CUtensorMap tm_o = make_map(enc, p_o, 1024, 2048, 64, 128);
  CUtensorMap tm_wA = make_map(enc, A_wqkv, 3072, 1024, 64, 64);
  CUtensorMap tm_wB = make_map(enc, B_wqkv, 3072, 1024, 64, 64);
  CUtensorMap tm_woA = make_map(enc, A_wo, 1024, 1024, 64, 64);
  CUtensorMap tm_woB = make_map(enc, B_wo, 1024, 1024, 64, 64);
  mega_kernel<<<128 + NX, 384, SM_TOTAL, cudaStreamPerThread>>>(tm_x0, tm_x, tm_o, tm_wA, tm_wB, tm_woA, tm_woB,
                                                           B_wqkv, A_wphi, out);
}
```

```cpp
#include <cuda_runtime.h>
#include <cuda_bf16.h>
#include <cuda.h>
#include <stdint.h>

typedef __nv_bfloat16 bf16;

constexpr int S_ = 2048, D_ = 1024;

struct __align__(128) Flag { unsigned int v; unsigned int pad[31]; };
__device__ __align__(1024) bf16 g_x[S_ * D_];
__device__ __align__(1024) bf16 g_o[S_ * D_];
__device__ __align__(1024) uint4 g_halo[128 * 2 * 512];
__device__ __align__(1024) uint4 g_kv[8 * 2 * 2 * 1280];
__device__ __align__(1024) float2 g_stats[4 * S_];
__device__ __align__(1024) float g_cs[2 * 2 * 3072];
__device__ Flag g_csflag[16];
__device__ __align__(128) unsigned int g_xf[16 * 32], g_of[16 * 32];
__device__ unsigned int g_epoch, g_err;
#define PROFT(cond, idx) asm volatile("" ::: "memory")

__device__ __forceinline__ uint32_t smem_u32(const void* p) { return (uint32_t)__cvta_generic_to_shared(p); }
__device__ __forceinline__ void mbar_init(uint32_t bar, uint32_t count) {
  asm volatile("mbarrier.init.shared::cta.b64 [%0], %1;" ::"r"(bar), "r"(count) : "memory");
}
__device__ __forceinline__ void mbar_expect_tx(uint32_t bar, uint32_t bytes) {
  asm volatile("mbarrier.arrive.expect_tx.shared::cta.b64 _, [%0], %1;" ::"r"(bar), "r"(bytes) : "memory");
}
__device__ __forceinline__ void mbar_arrive(uint32_t bar) {
  asm volatile("mbarrier.arrive.shared::cta.b64 _, [%0];" ::"r"(bar) : "memory");
}
__device__ __forceinline__ bool mbar_try_wait(uint32_t bar, uint32_t parity) {
  uint32_t ok;
  asm volatile("{\n.reg .pred p;\nmbarrier.try_wait.parity.shared::cta.b64 p, [%1], %2;\nselp.b32 %0, 1, 0, p;\n}\n"
               : "=r"(ok) : "r"(bar), "r"(parity) : "memory");
  return ok != 0;
}
__device__ __forceinline__ bool mbar_test_wait(uint32_t bar, uint32_t parity) {
  uint32_t ok;
  asm volatile("{\n.reg .pred p;\nmbarrier.test_wait.parity.shared::cta.b64 p, [%1], %2;\nselp.b32 %0, 1, 0, p;\n}\n"
               : "=r"(ok) : "r"(bar), "r"(parity) : "memory");
  return ok != 0;
}
__device__ __forceinline__ uint64_t gtimer() {
  uint64_t t; asm volatile("mov.u64 %0, %globaltimer;" : "=l"(t)); return t;
}
__device__ __forceinline__ void mbar_wait(uint32_t bar, uint32_t parity) {
  uint32_t n = 0;
#pragma unroll 1
  while (!mbar_try_wait(bar, parity)) {
    if (++n > (1u << 22)) { g_err = 1u; break; }
  }
}
__device__ __forceinline__ unsigned int ld_acquire(const unsigned int* p) {
  unsigned int v; asm volatile("ld.acquire.gpu.global.u32 %0, [%1];" : "=r"(v) : "l"(p) : "memory"); return v;
}
__device__ __forceinline__ void flag_add(unsigned int* p) {
  asm volatile("red.release.gpu.global.add.u32 [%0], 1;" ::"l"(p) : "memory");
}
__device__ __forceinline__ void flag_set(unsigned int* p, unsigned int v) {
  asm volatile("st.release.gpu.global.u32 [%0], %1;" ::"l"(p), "r"(v) : "memory");
}
__device__ __forceinline__ void flag_set_x(unsigned int* p, unsigned int v, bool rlx) {
  if (rlx) asm volatile("st.relaxed.gpu.global.u32 [%0], %1;" ::"l"(p), "r"(v) : "memory"); else flag_set(p, v);
}
template <int SLEEP>
__device__ __forceinline__ void src_wait(const unsigned int* f, unsigned int target, uint32_t need, uint32_t& ready, int lane) {
  uint32_t n = 0;
#pragma unroll 1
  while ((ready & need) != need) {
    const unsigned int v = ld_acquire(f + (lane & 15));
    ready = __ballot_sync(0xffffffffu, (int)(v - target) >= 0);
    if (SLEEP) { if ((ready & need) != need) __nanosleep(SLEEP); }
    if (++n > (1u << 20)) { g_err = 3u; break; }
  }
  __syncwarp();
}
__device__ __forceinline__ unsigned int ld_relaxed(const unsigned int* p) {
  unsigned int v; asm volatile("ld.relaxed.gpu.global.u32 %0, [%1];" : "=r"(v) : "l"(p) : "memory"); return v;
}
__device__ __forceinline__ bool src_wait_tma(const unsigned int* f, unsigned int target, uint32_t need, uint32_t& ready, int lane, uint32_t eb, uint32_t par) {
  uint32_t n = 0;
  bool fr = false;
#pragma unroll 1
  while ((ready & need) != need) {
    const unsigned int v = ld_acquire(f + (lane & 15));
    fr = __all_sync(0xffffffffu, mbar_test_wait(eb, par));
    ready = __ballot_sync(0xffffffffu, (int)(v - target) >= 0);
    if (++n > (1u << 20)) { g_err = 3u; break; }
  }
  return fr;
}
__device__ __forceinline__ uint4 ld_relaxed4(const uint4* p) {
  uint4 v; asm volatile("ld.relaxed.gpu.global.v4.u32 {%0,%1,%2,%3}, [%4];" : "=r"(v.x), "=r"(v.y), "=r"(v.z), "=r"(v.w) : "l"(p) : "memory"); return v;
}
__device__ __forceinline__ void st_relaxed4(uint4* p, uint32_t a, uint32_t b, uint32_t c, uint32_t d) {
  asm volatile("st.relaxed.gpu.global.v4.u32 [%0], {%1,%2,%3,%4};" ::"l"(p), "r"(a), "r"(b), "r"(c), "r"(d) : "memory");
}
template <int SLEEP>
__device__ __forceinline__ void flag_wait_t(const unsigned int* p, unsigned int target) {
  uint32_t n = 0;
#pragma unroll 1
  while ((int)(ld_acquire(p) - target) < 0) {
    if (SLEEP) __nanosleep(SLEEP);
    if (++n > (1u << 20)) { g_err = 2u; break; }
  }
}
__device__ __forceinline__ void flag_wait(const unsigned int* p, unsigned int target) { flag_wait_t<0>(p, target); }
__device__ __forceinline__ void flag_wait_slow(const unsigned int* p, unsigned int target) { flag_wait_t<256>(p, target); }
__device__ __forceinline__ void tma_load_2d(uint32_t dst, const CUtensorMap* tm, int c0, int c1, uint32_t bar) {
  asm volatile("cp.async.bulk.tensor.2d.shared::cluster.global.mbarrier::complete_tx::bytes [%0], [%1, {%2, %3}], [%4];"
               ::"r"(dst), "l"(tm), "r"(c0), "r"(c1), "r"(bar) : "memory");
}
__device__ __forceinline__ void tma_load_2d_mc(uint32_t dst, const CUtensorMap* tm, int c0, int c1, uint32_t bar, uint16_t mask) {
  asm volatile("cp.async.bulk.tensor.2d.shared::cluster.global.mbarrier::complete_tx::bytes.multicast::cluster [%0], [%1, {%2, %3}], [%4], %5;"
               ::"r"(dst), "l"(tm), "r"(c0), "r"(c1), "r"(bar), "h"(mask) : "memory");
}
__device__ __forceinline__ void mbar_wait_u(uint32_t bar, uint32_t parity) {
  uint32_t n = 0;
#pragma unroll 1
  while (!__all_sync(0xffffffffu, mbar_try_wait(bar, parity))) {
    if (++n > (1u << 22)) { g_err = 1u; break; }
  }
}
__device__ __forceinline__ void expect_tx_e(uint32_t bar, uint32_t bytes) {
  asm volatile("{\n.reg .pred p;\nelect.sync _|p, 0xffffffff;\n@p mbarrier.arrive.expect_tx.shared::cta.b64 _, [%0], %1;\n}\n" ::"r"(bar), "r"(bytes) : "memory");
}
__device__ __forceinline__ void tma_2d_e(uint32_t dst, const CUtensorMap* tm, int c0, int c1, uint32_t bar) {
  asm volatile("{\n.reg .pred p;\nelect.sync _|p, 0xffffffff;\n"
               "@p cp.async.bulk.tensor.2d.shared::cluster.global.mbarrier::complete_tx::bytes [%0], [%1, {%2, %3}], [%4];\n}\n"
               ::"r"(dst), "l"(tm), "r"(c0), "r"(c1), "r"(bar) : "memory");
}
__device__ __forceinline__ void tma_2d_mc_e(uint32_t dst, const CUtensorMap* tm, int c0, int c1, uint32_t bar) {
  asm volatile("{\n.reg .pred p;\nelect.sync _|p, 0xffffffff;\n"
               "@p cp.async.bulk.tensor.2d.shared::cluster.global.mbarrier::complete_tx::bytes.multicast::cluster [%0], [%1, {%2, %3}], [%4], %5;\n}\n"
               ::"r"(dst), "l"(tm), "r"(c0), "r"(c1), "r"(bar), "h"((uint16_t)3) : "memory");
}
__device__ __forceinline__ void tma_pf_e(const CUtensorMap* tm, int c0, int c1) {
  asm volatile("{\n.reg .pred p;\nelect.sync _|p, 0xffffffff;\n"
               "@p cp.async.bulk.prefetch.tensor.2d.L2.global.tile [%0, {%1, %2}];\n}\n" ::"l"(tm), "r"(c0), "r"(c1) : "memory");
}
__device__ __forceinline__ void tma_2d_to_e(uint32_t dst, const CUtensorMap* tm, int c0, int c1, uint32_t bar, uint32_t mask) {
  asm volatile("{\n.reg .pred p;\nelect.sync _|p, 0xffffffff;\n"
               "@p cp.async.bulk.tensor.2d.shared::cluster.global.mbarrier::complete_tx::bytes.multicast::cluster [%0], [%1, {%2, %3}], [%4], %5;\n}\n"
               ::"r"(dst), "l"(tm), "r"(c0), "r"(c1), "r"(bar), "h"((uint16_t)mask) : "memory");
}
__device__ __forceinline__ void tma_3d_mc_e(uint32_t dst, const CUtensorMap* tm, int c1, int c2, uint32_t bar) {
  asm volatile("{\n.reg .pred p;\nelect.sync _|p, 0xffffffff;\n"
               "@p cp.async.bulk.tensor.3d.shared::cluster.global.mbarrier::complete_tx::bytes.multicast::cluster [%0], [%1, {%6, %2, %3}], [%4], %5;\n}\n"
               ::"r"(dst), "l"(tm), "r"(c1), "r"(c2), "r"(bar), "h"((uint16_t)3), "r"(0) : "memory");
}
__device__ __forceinline__ uint32_t poll_flags(const unsigned int* f, unsigned int target, int lane) {
  const unsigned int v = ld_acquire(f + (lane & 15));
  const uint32_t r = __ballot_sync(0xffffffffu, (int)(v - target) >= 0);
  __syncwarp();
  return r;
}
__device__ __forceinline__ void mbar_arrive_cluster(uint32_t local_bar, uint32_t rank) {
  asm volatile("{\n.reg .b32 ra;\nmapa.shared::cluster.u32 ra, %0, %1;\nmbarrier.arrive.shared::cluster.b64 _, [ra];\n}\n"
               ::"r"(local_bar), "r"(rank) : "memory");
}
__device__ __forceinline__ void release2(uint32_t bar) { mbar_arrive_cluster(bar, 0); mbar_arrive_cluster(bar, 1); }
__device__ __forceinline__ void tma_store_2d(const CUtensorMap* tm, uint32_t src, int c0, int c1) {
  asm volatile("cp.async.bulk.tensor.2d.global.shared::cta.bulk_group [%0, {%2, %3}], [%1];"
               ::"l"(tm), "r"(src), "r"(c0), "r"(c1) : "memory");
}
__device__ __forceinline__ void bulk_store(void* dst, uint32_t src, uint32_t bytes) {
  asm volatile("cp.async.bulk.global.shared::cta.bulk_group [%0], [%1], %2;" ::"l"(dst), "r"(src), "r"(bytes) : "memory");
}
__device__ __forceinline__ void bulk_load(uint32_t dst, const void* src, uint32_t bytes, uint32_t bar) {
  asm volatile("cp.async.bulk.shared::cluster.global.mbarrier::complete_tx::bytes [%0], [%1], %2, [%3];" ::"r"(dst), "l"(src), "r"(bytes), "r"(bar) : "memory");
}
__device__ __forceinline__ void bulk_red_add(void* dst, uint32_t src, uint32_t bytes) {
  asm volatile("cp.reduce.async.bulk.global.shared::cta.bulk_group.add.f32 [%0], [%1], %2;" ::"l"(dst), "r"(src), "r"(bytes) : "memory");
}
__device__ __forceinline__ void bulk_red_add_e(void* dst, uint32_t src, uint32_t bytes) {
  asm volatile("{\n.reg .pred p;\nelect.sync _|p, 0xffffffff;\n@p cp.reduce.async.bulk.global.shared::cta.bulk_group.add.f32 [%0], [%1], %2;\n}\n" ::"l"(dst), "r"(src), "r"(bytes) : "memory");
}
__device__ __forceinline__ void bulk_commit() { asm volatile("cp.async.bulk.commit_group;" ::: "memory"); }
__device__ __forceinline__ void bulk_wait_read0() { asm volatile("cp.async.bulk.wait_group.read 0;" ::: "memory"); }
__device__ __forceinline__ void bulk_wait0() { asm volatile("cp.async.bulk.wait_group 0;" ::: "memory"); }
__device__ __forceinline__ void fence_async_smem() { asm volatile("fence.proxy.async.shared::cta;" ::: "memory"); }
__device__ __forceinline__ void fence_async_all() { asm volatile("fence.proxy.async.global;" ::: "memory"); }
__device__ __forceinline__ void wgmma_fence() { asm volatile("wgmma.fence.sync.aligned;" ::: "memory"); }
__device__ __forceinline__ void wgmma_commit() { asm volatile("wgmma.commit_group.sync.aligned;" ::: "memory"); }
template <int N> __device__ __forceinline__ void wgmma_wait() { asm volatile("wgmma.wait_group.sync.aligned %0;" ::"n"(N) : "memory"); }
__device__ __forceinline__ void cluster_arrive() { asm volatile("barrier.cluster.arrive.release.aligned;" ::: "memory"); }
__device__ __forceinline__ void cluster_wait() { asm volatile("barrier.cluster.wait.acquire.aligned;" ::: "memory"); }
template <int ID, int N> __device__ __forceinline__ void nbar() { asm volatile("bar.sync %0, %1;" ::"n"(ID), "n"(N) : "memory"); }
__device__ __forceinline__ uint64_t make_desc(uint32_t addr, uint32_t lbo_bytes, uint32_t sbo_bytes) {
  uint64_t d = 0;
  d |= (uint64_t)((addr & 0x3FFFF) >> 4);
  d |= (uint64_t)((lbo_bytes >> 4) & 0x3FFF) << 16;
  d |= (uint64_t)((sbo_bytes >> 4) & 0x3FFF) << 32;
  d |= (uint64_t)1 << 62;
  return d;
}
__device__ __forceinline__ uint64_t desc64(uint32_t lo, uint32_t hi) { return (uint64_t)lo | ((uint64_t)hi << 32); }
__device__ __forceinline__ uint32_t pack_bf16(float lo, float hi) {
  uint32_t r; asm("cvt.rn.bf16x2.f32 %0, %1, %2;" : "=r"(r) : "f"(hi), "f"(lo)); return r;
}
__device__ __forceinline__ uint32_t mul_bf16x2(uint32_t a, uint32_t s, bool hi) {
  __nv_bfloat162 x = *reinterpret_cast<__nv_bfloat162*>(&a), y = *reinterpret_cast<__nv_bfloat162*>(&s);
  x = __hmul2(x, hi ? __high2bfloat162(y) : __low2bfloat162(y));
  return *reinterpret_cast<uint32_t*>(&x);
}
__device__ __forceinline__ float bf16r(float x) { return __bfloat162float(__float2bfloat16_rn(x)); }
__device__ __forceinline__ float bf_lo(uint32_t u) { return __uint_as_float(u << 16); }
__device__ __forceinline__ float bf_hi(uint32_t u) { return __uint_as_float(u & 0xFFFF0000u); }
__device__ __forceinline__ float ex2(float x) { float r; asm("ex2.approx.ftz.f32 %0, %1;" : "=f"(r) : "f"(x)); return r; }
__device__ __forceinline__ float rcp(float x) { float r; asm("rcp.approx.ftz.f32 %0, %1;" : "=f"(r) : "f"(x)); return r; }
__device__ __forceinline__ void mma_bf16(float (&d)[4], uint32_t a0, uint32_t a1, uint32_t a2, uint32_t a3, uint32_t b0, uint32_t b1) {
  asm("mma.sync.aligned.m16n8k16.row.col.f32.bf16.bf16.f32 {%0,%1,%2,%3}, {%4,%5,%6,%7}, {%8,%9}, {%0,%1,%2,%3};"
               : "+f"(d[0]), "+f"(d[1]), "+f"(d[2]), "+f"(d[3]) : "r"(a0), "r"(a1), "r"(a2), "r"(a3), "r"(b0), "r"(b1));
}
__device__ __forceinline__ void ldsm_x4(uint32_t& r0, uint32_t& r1, uint32_t& r2, uint32_t& r3, uint32_t addr) {
  asm volatile("ldmatrix.sync.aligned.m8n8.x4.shared.b16 {%0,%1,%2,%3}, [%4];"
               : "=r"(r0), "=r"(r1), "=r"(r2), "=r"(r3) : "r"(addr) : "memory");
}
__device__ __forceinline__ void ldsm_x4_t(uint32_t& r0, uint32_t& r1, uint32_t& r2, uint32_t& r3, uint32_t addr) {
  asm volatile("ldmatrix.sync.aligned.m8n8.x4.trans.shared.b16 {%0,%1,%2,%3}, [%4];"
               : "=r"(r0), "=r"(r1), "=r"(r2), "=r"(r3) : "r"(addr) : "memory");
}
__device__ __forceinline__ void ldsm_x2_t(uint32_t& r0, uint32_t& r1, uint32_t addr) {
  asm volatile("ldmatrix.sync.aligned.m8n8.x2.trans.shared.b16 {%0,%1}, [%2];"
               : "=r"(r0), "=r"(r1) : "r"(addr) : "memory");
}
__device__ __forceinline__ void stsm_x4(uint32_t addr, uint32_t r0, uint32_t r1, uint32_t r2, uint32_t r3) {
  asm volatile("stmatrix.sync.aligned.m8n8.x4.shared.b16 [%0], {%1,%2,%3,%4};"
               ::"r"(addr), "r"(r0), "r"(r1), "r"(r2), "r"(r3) : "memory");
}
__device__ __forceinline__ void stsm_x4_p(bool on, uint32_t addr, uint32_t r0, uint32_t r1, uint32_t r2, uint32_t r3) {
  asm volatile("{\n.reg .pred p;\nsetp.ne.b32 p, %5, 0;\n@p stmatrix.sync.aligned.m8n8.x4.shared.b16 [%0], {%1,%2,%3,%4};\n}\n"
               ::"r"(addr), "r"(r0), "r"(r1), "r"(r2), "r"(r3), "r"((int)on) : "memory");
}
__device__ __forceinline__ float2 lds_f2(uint32_t addr) {
  float2 v; asm volatile("ld.shared.v2.f32 {%0,%1}, [%2];" : "=f"(v.x), "=f"(v.y) : "r"(addr) : "memory"); return v;
}
__device__ __forceinline__ uint4 lds128(uint32_t addr) {
  uint4 v; asm volatile("ld.shared.v4.b32 {%0,%1,%2,%3}, [%4];" : "=r"(v.x), "=r"(v.y), "=r"(v.z), "=r"(v.w) : "r"(addr) : "memory"); return v;
}
__device__ __forceinline__ void sts128(uint32_t addr, uint4 v) {
  asm volatile("st.shared.v4.b32 [%0], {%1,%2,%3,%4};" ::"r"(addr), "r"(v.x), "r"(v.y), "r"(v.z), "r"(v.w) : "memory");
}
__device__ __forceinline__ float lds_f(uint32_t addr) {
  float v; asm volatile("ld.shared.f32 %0, [%1];" : "=f"(v) : "r"(addr) : "memory"); return v;
}
__device__ __forceinline__ uint32_t lds_vol(uint32_t addr) {
  uint32_t v; asm volatile("ld.volatile.shared.u32 %0, [%1];" : "=r"(v) : "r"(addr) : "memory"); return v;
}
__device__ __forceinline__ void sts16(uint32_t addr, uint32_t v) {
  asm volatile("st.shared.u16 [%0], %1;" ::"r"(addr), "h"((unsigned short)v) : "memory");
}
__device__ __forceinline__ void nbar_dyn(int id, int n) { asm volatile("bar.sync %0, %1;" ::"r"(id), "r"(n) : "memory"); }
__device__ __forceinline__ uint64_t make_desc_ns(uint32_t addr, uint32_t lbo_bytes, uint32_t sbo_bytes) {
  return (uint64_t)((addr & 0x3FFFF) >> 4) | ((uint64_t)(lbo_bytes >> 4) << 16) | ((uint64_t)(sbo_bytes >> 4) << 32);
}
__device__ __forceinline__ void sts_f(uint32_t addr, float v) { asm volatile("st.shared.f32 [%0], %1;" ::"r"(addr), "f"(v) : "memory"); }
__device__ __forceinline__ void sts64(uint32_t addr, uint32_t a, uint32_t b) {
  asm volatile("st.shared.v2.b32 [%0], {%1,%2};" ::"r"(addr), "r"(a), "r"(b) : "memory");
}
__device__ __forceinline__ void sts_f2(uint32_t addr, float a, float b) {
  asm volatile("st.shared.v2.f32 [%0], {%1,%2};" ::"r"(addr), "f"(a), "f"(b) : "memory");
}
__device__ __forceinline__ void red_add2(float* p, float a, float b) {
  asm volatile("red.global.add.v2.f32 [%0], {%1,%2};" ::"l"(p), "f"(a), "f"(b) : "memory");
}
__device__ __forceinline__ void red_add4(float* p, float a, float b, float c, float d) {
  asm volatile("red.global.add.v4.f32 [%0], {%1,%2,%3,%4};" ::"l"(p), "f"(a), "f"(b), "f"(c), "f"(d) : "memory");
}
__device__ __forceinline__ void red_add1(float* p, float a) {
  asm volatile("red.global.add.f32 [%0], %1;" ::"l"(p), "f"(a) : "memory");
}
__device__ __forceinline__ void l2_prefetch(const void* p, uint32_t bytes) {
  asm volatile("cp.async.bulk.prefetch.L2.global [%0], %1;" ::"l"(p), "r"(bytes) : "memory");
}

__device__ __forceinline__ void wgmma_n256(float (&d)[192], uint64_t da, uint64_t db, int scale_d) {
  asm volatile("{\n.reg .pred p;\nsetp.ne.b32 p, %130, 0;\n"
    "wgmma.mma_async.sync.aligned.m64n256k16.f32.bf16.bf16 {%0, %1, %2, %3, %4, %5, %6, %7, %8, %9, %10, %11, %12, %13, %14, %15, %16, %17, %18, %19, %20, %21, %22, %23, %24, %25, %26, %27, %28, %29, %30, %31, %32, %33, %34, %35, %36, %37, %38, %39, %40, %41, %42, %43, %44, %45, %46, %47, %48, %49, %50, %51, %52, %53, %54, %55, %56, %57, %58, %59, %60, %61, %62, %63, %64, %65, %66, %67, %68, %69, %70, %71, %72, %73, %74, %75, %76, %77, %78, %79, %80, %81, %82, %83, %84, %85, %86, %87, %88, %89, %90, %91, %92, %93, %94, %95, %96, %97, %98, %99, %100, %101, %102, %103, %104, %105, %106, %107, %108, %109, %110, %111, %112, %113, %114, %115, %116, %117, %118, %119, %120, %121, %122, %123, %124, %125, %126, %127}, %128, %129, p, 1, 1, 0, 1;\n}\n"
    : "+f"(d[0]), "+f"(d[1]), "+f"(d[2]), "+f"(d[3]), "+f"(d[4]), "+f"(d[5]), "+f"(d[6]), "+f"(d[7]), "+f"(d[8]), "+f"(d[9]), "+f"(d[10]), "+f"(d[11]), "+f"(d[12]), "+f"(d[13]), "+f"(d[14]), "+f"(d[15]), "+f"(d[16]), "+f"(d[17]), "+f"(d[18]), "+f"(d[19]), "+f"(d[20]), "+f"(d[21]), "+f"(d[22]), "+f"(d[23]), "+f"(d[24]), "+f"(d[25]), "+f"(d[26]), "+f"(d[27]), "+f"(d[28]), "+f"(d[29]), "+f"(d[30]), "+f"(d[31]), "+f"(d[32]), "+f"(d[33]), "+f"(d[34]), "+f"(d[35]), "+f"(d[36]), "+f"(d[37]), "+f"(d[38]), "+f"(d[39]), "+f"(d[40]), "+f"(d[41]), "+f"(d[42]), "+f"(d[43]), "+f"(d[44]), "+f"(d[45]), "+f"(d[46]), "+f"(d[47]), "+f"(d[48]), "+f"(d[49]), "+f"(d[50]), "+f"(d[51]), "+f"(d[52]), "+f"(d[53]), "+f"(d[54]), "+f"(d[55]), "+f"(d[56]), "+f"(d[57]), "+f"(d[58]), "+f"(d[59]), "+f"(d[60]), "+f"(d[61]), "+f"(d[62]), "+f"(d[63]), "+f"(d[64]), "+f"(d[65]), "+f"(d[66]), "+f"(d[67]), "+f"(d[68]), "+f"(d[69]), "+f"(d[70]), "+f"(d[71]), "+f"(d[72]), "+f"(d[73]), "+f"(d[74]), "+f"(d[75]), "+f"(d[76]), "+f"(d[77]), "+f"(d[78]), "+f"(d[79]), "+f"(d[80]), "+f"(d[81]), "+f"(d[82]), "+f"(d[83]), "+f"(d[84]), "+f"(d[85]), "+f"(d[86]), "+f"(d[87]), "+f"(d[88]), "+f"(d[89]), "+f"(d[90]), "+f"(d[91]), "+f"(d[92]), "+f"(d[93]), "+f"(d[94]), "+f"(d[95]), "+f"(d[96]), "+f"(d[97]), "+f"(d[98]), "+f"(d[99]), "+f"(d[100]), "+f"(d[101]), "+f"(d[102]), "+f"(d[103]), "+f"(d[104]), "+f"(d[105]), "+f"(d[106]), "+f"(d[107]), "+f"(d[108]), "+f"(d[109]), "+f"(d[110]), "+f"(d[111]), "+f"(d[112]), "+f"(d[113]), "+f"(d[114]), "+f"(d[115]), "+f"(d[116]), "+f"(d[117]), "+f"(d[118]), "+f"(d[119]), "+f"(d[120]), "+f"(d[121]), "+f"(d[122]), "+f"(d[123]), "+f"(d[124]), "+f"(d[125]), "+f"(d[126]), "+f"(d[127])
    : "l"(da), "l"(db), "r"(scale_d));
}
__device__ __forceinline__ void wgmma_n128(float (&d)[192], uint64_t da, uint64_t db, int scale_d) {
  asm volatile("{\n.reg .pred p;\nsetp.ne.b32 p, %66, 0;\n"
    "wgmma.mma_async.sync.aligned.m64n128k16.f32.bf16.bf16 {%0, %1, %2, %3, %4, %5, %6, %7, %8, %9, %10, %11, %12, %13, %14, %15, %16, %17, %18, %19, %20, %21, %22, %23, %24, %25, %26, %27, %28, %29, %30, %31, %32, %33, %34, %35, %36, %37, %38, %39, %40, %41, %42, %43, %44, %45, %46, %47, %48, %49, %50, %51, %52, %53, %54, %55, %56, %57, %58, %59, %60, %61, %62, %63}, %64, %65, p, 1, 1, 0, 1;\n}\n"
    : "+f"(d[128]), "+f"(d[129]), "+f"(d[130]), "+f"(d[131]), "+f"(d[132]), "+f"(d[133]), "+f"(d[134]), "+f"(d[135]), "+f"(d[136]), "+f"(d[137]), "+f"(d[138]), "+f"(d[139]), "+f"(d[140]), "+f"(d[141]), "+f"(d[142]), "+f"(d[143]), "+f"(d[144]), "+f"(d[145]), "+f"(d[146]), "+f"(d[147]), "+f"(d[148]), "+f"(d[149]), "+f"(d[150]), "+f"(d[151]), "+f"(d[152]), "+f"(d[153]), "+f"(d[154]), "+f"(d[155]), "+f"(d[156]), "+f"(d[157]), "+f"(d[158]), "+f"(d[159]), "+f"(d[160]), "+f"(d[161]), "+f"(d[162]), "+f"(d[163]), "+f"(d[164]), "+f"(d[165]), "+f"(d[166]), "+f"(d[167]), "+f"(d[168]), "+f"(d[169]), "+f"(d[170]), "+f"(d[171]), "+f"(d[172]), "+f"(d[173]), "+f"(d[174]), "+f"(d[175]), "+f"(d[176]), "+f"(d[177]), "+f"(d[178]), "+f"(d[179]), "+f"(d[180]), "+f"(d[181]), "+f"(d[182]), "+f"(d[183]), "+f"(d[184]), "+f"(d[185]), "+f"(d[186]), "+f"(d[187]), "+f"(d[188]), "+f"(d[189]), "+f"(d[190]), "+f"(d[191])
    : "l"(da), "l"(db), "r"(scale_d));
}
__device__ __forceinline__ void wgmma_n256_k(float (&d)[192], uint64_t da, uint64_t db, int scale_d) {
  asm volatile("{\n.reg .pred p;\nsetp.ne.b32 p, %130, 0;\n"
    "wgmma.mma_async.sync.aligned.m64n256k16.f32.bf16.bf16 {%0, %1, %2, %3, %4, %5, %6, %7, %8, %9, %10, %11, %12, %13, %14, %15, %16, %17, %18, %19, %20, %21, %22, %23, %24, %25, %26, %27, %28, %29, %30, %31, %32, %33, %34, %35, %36, %37, %38, %39, %40, %41, %42, %43, %44, %45, %46, %47, %48, %49, %50, %51, %52, %53, %54, %55, %56, %57, %58, %59, %60, %61, %62, %63, %64, %65, %66, %67, %68, %69, %70, %71, %72, %73, %74, %75, %76, %77, %78, %79, %80, %81, %82, %83, %84, %85, %86, %87, %88, %89, %90, %91, %92, %93, %94, %95, %96, %97, %98, %99, %100, %101, %102, %103, %104, %105, %106, %107, %108, %109, %110, %111, %112, %113, %114, %115, %116, %117, %118, %119, %120, %121, %122, %123, %124, %125, %126, %127}, %128, %129, p, 1, 1, 0, 0;\n}\n"
    : "+f"(d[0]), "+f"(d[1]), "+f"(d[2]), "+f"(d[3]), "+f"(d[4]), "+f"(d[5]), "+f"(d[6]), "+f"(d[7]), "+f"(d[8]), "+f"(d[9]), "+f"(d[10]), "+f"(d[11]), "+f"(d[12]), "+f"(d[13]), "+f"(d[14]), "+f"(d[15]), "+f"(d[16]), "+f"(d[17]), "+f"(d[18]), "+f"(d[19]), "+f"(d[20]), "+f"(d[21]), "+f"(d[22]), "+f"(d[23]), "+f"(d[24]), "+f"(d[25]), "+f"(d[26]), "+f"(d[27]), "+f"(d[28]), "+f"(d[29]), "+f"(d[30]), "+f"(d[31]), "+f"(d[32]), "+f"(d[33]), "+f"(d[34]), "+f"(d[35]), "+f"(d[36]), "+f"(d[37]), "+f"(d[38]), "+f"(d[39]), "+f"(d[40]), "+f"(d[41]), "+f"(d[42]), "+f"(d[43]), "+f"(d[44]), "+f"(d[45]), "+f"(d[46]), "+f"(d[47]), "+f"(d[48]), "+f"(d[49]), "+f"(d[50]), "+f"(d[51]), "+f"(d[52]), "+f"(d[53]), "+f"(d[54]), "+f"(d[55]), "+f"(d[56]), "+f"(d[57]), "+f"(d[58]), "+f"(d[59]), "+f"(d[60]), "+f"(d[61]), "+f"(d[62]), "+f"(d[63]), "+f"(d[64]), "+f"(d[65]), "+f"(d[66]), "+f"(d[67]), "+f"(d[68]), "+f"(d[69]), "+f"(d[70]), "+f"(d[71]), "+f"(d[72]), "+f"(d[73]), "+f"(d[74]), "+f"(d[75]), "+f"(d[76]), "+f"(d[77]), "+f"(d[78]), "+f"(d[79]), "+f"(d[80]), "+f"(d[81]), "+f"(d[82]), "+f"(d[83]), "+f"(d[84]), "+f"(d[85]), "+f"(d[86]), "+f"(d[87]), "+f"(d[88]), "+f"(d[89]), "+f"(d[90]), "+f"(d[91]), "+f"(d[92]), "+f"(d[93]), "+f"(d[94]), "+f"(d[95]), "+f"(d[96]), "+f"(d[97]), "+f"(d[98]), "+f"(d[99]), "+f"(d[100]), "+f"(d[101]), "+f"(d[102]), "+f"(d[103]), "+f"(d[104]), "+f"(d[105]), "+f"(d[106]), "+f"(d[107]), "+f"(d[108]), "+f"(d[109]), "+f"(d[110]), "+f"(d[111]), "+f"(d[112]), "+f"(d[113]), "+f"(d[114]), "+f"(d[115]), "+f"(d[116]), "+f"(d[117]), "+f"(d[118]), "+f"(d[119]), "+f"(d[120]), "+f"(d[121]), "+f"(d[122]), "+f"(d[123]), "+f"(d[124]), "+f"(d[125]), "+f"(d[126]), "+f"(d[127])
    : "l"(da), "l"(db), "r"(scale_d));
}
__device__ __forceinline__ void wgmma_n128_k(float (&d)[192], uint64_t da, uint64_t db, int scale_d) {
  asm volatile("{\n.reg .pred p;\nsetp.ne.b32 p, %66, 0;\n"
    "wgmma.mma_async.sync.aligned.m64n128k16.f32.bf16.bf16 {%0, %1, %2, %3, %4, %5, %6, %7, %8, %9, %10, %11, %12, %13, %14, %15, %16, %17, %18, %19, %20, %21, %22, %23, %24, %25, %26, %27, %28, %29, %30, %31, %32, %33, %34, %35, %36, %37, %38, %39, %40, %41, %42, %43, %44, %45, %46, %47, %48, %49, %50, %51, %52, %53, %54, %55, %56, %57, %58, %59, %60, %61, %62, %63}, %64, %65, p, 1, 1, 0, 0;\n}\n"
    : "+f"(d[128]), "+f"(d[129]), "+f"(d[130]), "+f"(d[131]), "+f"(d[132]), "+f"(d[133]), "+f"(d[134]), "+f"(d[135]), "+f"(d[136]), "+f"(d[137]), "+f"(d[138]), "+f"(d[139]), "+f"(d[140]), "+f"(d[141]), "+f"(d[142]), "+f"(d[143]), "+f"(d[144]), "+f"(d[145]), "+f"(d[146]), "+f"(d[147]), "+f"(d[148]), "+f"(d[149]), "+f"(d[150]), "+f"(d[151]), "+f"(d[152]), "+f"(d[153]), "+f"(d[154]), "+f"(d[155]), "+f"(d[156]), "+f"(d[157]), "+f"(d[158]), "+f"(d[159]), "+f"(d[160]), "+f"(d[161]), "+f"(d[162]), "+f"(d[163]), "+f"(d[164]), "+f"(d[165]), "+f"(d[166]), "+f"(d[167]), "+f"(d[168]), "+f"(d[169]), "+f"(d[170]), "+f"(d[171]), "+f"(d[172]), "+f"(d[173]), "+f"(d[174]), "+f"(d[175]), "+f"(d[176]), "+f"(d[177]), "+f"(d[178]), "+f"(d[179]), "+f"(d[180]), "+f"(d[181]), "+f"(d[182]), "+f"(d[183]), "+f"(d[184]), "+f"(d[185]), "+f"(d[186]), "+f"(d[187]), "+f"(d[188]), "+f"(d[189]), "+f"(d[190]), "+f"(d[191])
    : "l"(da), "l"(db), "r"(scale_d));
}
__device__ __forceinline__ void wgmma_n40_tt(float (&d)[20], uint64_t da, uint64_t db, int scale_d) {
  asm volatile("{\n.reg .pred p;\nsetp.ne.b32 p, %22, 0;\n"
    "wgmma.mma_async.sync.aligned.m64n40k16.f32.bf16.bf16 {%0, %1, %2, %3, %4, %5, %6, %7, %8, %9, %10, %11, %12, %13, %14, %15, %16, %17, %18, %19}, %20, %21, p, 1, 1, 1, 1;\n}\n"
    : "+f"(d[0]), "+f"(d[1]), "+f"(d[2]), "+f"(d[3]), "+f"(d[4]), "+f"(d[5]), "+f"(d[6]), "+f"(d[7]), "+f"(d[8]), "+f"(d[9]), "+f"(d[10]), "+f"(d[11]), "+f"(d[12]), "+f"(d[13]), "+f"(d[14]), "+f"(d[15]), "+f"(d[16]), "+f"(d[17]), "+f"(d[18]), "+f"(d[19])
    : "l"(da), "l"(db), "r"(scale_d));
}
__device__ __forceinline__ void wgmma_n40_rs(float (&d)[20], const uint32_t (&a)[4], uint64_t db, int scale_d) {
  asm volatile("{\n.reg .pred p;\nsetp.ne.b32 p, %25, 0;\n"
    "wgmma.mma_async.sync.aligned.m64n40k16.f32.bf16.bf16 {%0, %1, %2, %3, %4, %5, %6, %7, %8, %9, %10, %11, %12, %13, %14, %15, %16, %17, %18, %19}, {%20, %21, %22, %23}, %24, p, 1, 1, 1;\n}\n"
    : "+f"(d[0]), "+f"(d[1]), "+f"(d[2]), "+f"(d[3]), "+f"(d[4]), "+f"(d[5]), "+f"(d[6]), "+f"(d[7]), "+f"(d[8]), "+f"(d[9]), "+f"(d[10]), "+f"(d[11]), "+f"(d[12]), "+f"(d[13]), "+f"(d[14]), "+f"(d[15]), "+f"(d[16]), "+f"(d[17]), "+f"(d[18]), "+f"(d[19])
    : "r"(a[0]), "r"(a[1]), "r"(a[2]), "r"(a[3]), "l"(db), "r"(scale_d));
}
__device__ __forceinline__ void wgmma_n256_0(float (&d)[192], uint64_t da, uint64_t db) {
  asm volatile("{\n.reg .pred p;\nsetp.ne.b32 p, 0, 0;\n"
    "wgmma.mma_async.sync.aligned.m64n256k16.f32.bf16.bf16 {%0, %1, %2, %3, %4, %5, %6, %7, %8, %9, %10, %11, %12, %13, %14, %15, %16, %17, %18, %19, %20, %21, %22, %23, %24, %25, %26, %27, %28, %29, %30, %31, %32, %33, %34, %35, %36, %37, %38, %39, %40, %41, %42, %43, %44, %45, %46, %47, %48, %49, %50, %51, %52, %53, %54, %55, %56, %57, %58, %59, %60, %61, %62, %63, %64, %65, %66, %67, %68, %69, %70, %71, %72, %73, %74, %75, %76, %77, %78, %79, %80, %81, %82, %83, %84, %85, %86, %87, %88, %89, %90, %91, %92, %93, %94, %95, %96, %97, %98, %99, %100, %101, %102, %103, %104, %105, %106, %107, %108, %109, %110, %111, %112, %113, %114, %115, %116, %117, %118, %119, %120, %121, %122, %123, %124, %125, %126, %127}, %128, %129, p, 1, 1, 0, 1;\n}\n"
    : "=f"(d[0]), "=f"(d[1]), "=f"(d[2]), "=f"(d[3]), "=f"(d[4]), "=f"(d[5]), "=f"(d[6]), "=f"(d[7]), "=f"(d[8]), "=f"(d[9]), "=f"(d[10]), "=f"(d[11]), "=f"(d[12]), "=f"(d[13]), "=f"(d[14]), "=f"(d[15]), "=f"(d[16]), "=f"(d[17]), "=f"(d[18]), "=f"(d[19]), "=f"(d[20]), "=f"(d[21]), "=f"(d[22]), "=f"(d[23]), "=f"(d[24]), "=f"(d[25]), "=f"(d[26]), "=f"(d[27]), "=f"(d[28]), "=f"(d[29]), "=f"(d[30]), "=f"(d[31]), "=f"(d[32]), "=f"(d[33]), "=f"(d[34]), "=f"(d[35]), "=f"(d[36]), "=f"(d[37]), "=f"(d[38]), "=f"(d[39]), "=f"(d[40]), "=f"(d[41]), "=f"(d[42]), "=f"(d[43]), "=f"(d[44]), "=f"(d[45]), "=f"(d[46]), "=f"(d[47]), "=f"(d[48]), "=f"(d[49]), "=f"(d[50]), "=f"(d[51]), "=f"(d[52]), "=f"(d[53]), "=f"(d[54]), "=f"(d[55]), "=f"(d[56]), "=f"(d[57]), "=f"(d[58]), "=f"(d[59]), "=f"(d[60]), "=f"(d[61]), "=f"(d[62]), "=f"(d[63]), "=f"(d[64]), "=f"(d[65]), "=f"(d[66]), "=f"(d[67]), "=f"(d[68]), "=f"(d[69]), "=f"(d[70]), "=f"(d[71]), "=f"(d[72]), "=f"(d[73]), "=f"(d[74]), "=f"(d[75]), "=f"(d[76]), "=f"(d[77]), "=f"(d[78]), "=f"(d[79]), "=f"(d[80]), "=f"(d[81]), "=f"(d[82]), "=f"(d[83]), "=f"(d[84]), "=f"(d[85]), "=f"(d[86]), "=f"(d[87]), "=f"(d[88]), "=f"(d[89]), "=f"(d[90]), "=f"(d[91]), "=f"(d[92]), "=f"(d[93]), "=f"(d[94]), "=f"(d[95]), "=f"(d[96]), "=f"(d[97]), "=f"(d[98]), "=f"(d[99]), "=f"(d[100]), "=f"(d[101]), "=f"(d[102]), "=f"(d[103]), "=f"(d[104]), "=f"(d[105]), "=f"(d[106]), "=f"(d[107]), "=f"(d[108]), "=f"(d[109]), "=f"(d[110]), "=f"(d[111]), "=f"(d[112]), "=f"(d[113]), "=f"(d[114]), "=f"(d[115]), "=f"(d[116]), "=f"(d[117]), "=f"(d[118]), "=f"(d[119]), "=f"(d[120]), "=f"(d[121]), "=f"(d[122]), "=f"(d[123]), "=f"(d[124]), "=f"(d[125]), "=f"(d[126]), "=f"(d[127])
    : "l"(da), "l"(db));
}
__device__ __forceinline__ void wgmma_n128_0(float (&d)[192], uint64_t da, uint64_t db) {
  asm volatile("{\n.reg .pred p;\nsetp.ne.b32 p, 0, 0;\n"
    "wgmma.mma_async.sync.aligned.m64n128k16.f32.bf16.bf16 {%0, %1, %2, %3, %4, %5, %6, %7, %8, %9, %10, %11, %12, %13, %14, %15, %16, %17, %18, %19, %20, %21, %22, %23, %24, %25, %26, %27, %28, %29, %30, %31, %32, %33, %34, %35, %36, %37, %38, %39, %40, %41, %42, %43, %44, %45, %46, %47, %48, %49, %50, %51, %52, %53, %54, %55, %56, %57, %58, %59, %60, %61, %62, %63}, %64, %65, p, 1, 1, 0, 1;\n}\n"
    : "=f"(d[128]), "=f"(d[129]), "=f"(d[130]), "=f"(d[131]), "=f"(d[132]), "=f"(d[133]), "=f"(d[134]), "=f"(d[135]), "=f"(d[136]), "=f"(d[137]), "=f"(d[138]), "=f"(d[139]), "=f"(d[140]), "=f"(d[141]), "=f"(d[142]), "=f"(d[143]), "=f"(d[144]), "=f"(d[145]), "=f"(d[146]), "=f"(d[147]), "=f"(d[148]), "=f"(d[149]), "=f"(d[150]), "=f"(d[151]), "=f"(d[152]), "=f"(d[153]), "=f"(d[154]), "=f"(d[155]), "=f"(d[156]), "=f"(d[157]), "=f"(d[158]), "=f"(d[159]), "=f"(d[160]), "=f"(d[161]), "=f"(d[162]), "=f"(d[163]), "=f"(d[164]), "=f"(d[165]), "=f"(d[166]), "=f"(d[167]), "=f"(d[168]), "=f"(d[169]), "=f"(d[170]), "=f"(d[171]), "=f"(d[172]), "=f"(d[173]), "=f"(d[174]), "=f"(d[175]), "=f"(d[176]), "=f"(d[177]), "=f"(d[178]), "=f"(d[179]), "=f"(d[180]), "=f"(d[181]), "=f"(d[182]), "=f"(d[183]), "=f"(d[184]), "=f"(d[185]), "=f"(d[186]), "=f"(d[187]), "=f"(d[188]), "=f"(d[189]), "=f"(d[190]), "=f"(d[191])
    : "l"(da), "l"(db));
}
__device__ __forceinline__ void wgmma_n64a(float (&d)[192], uint64_t da, uint64_t db, int scale_d) {
  asm volatile("{\n.reg .pred p;\nsetp.ne.b32 p, %34, 0;\n"
    "wgmma.mma_async.sync.aligned.m64n64k16.f32.bf16.bf16 {%0, %1, %2, %3, %4, %5, %6, %7, %8, %9, %10, %11, %12, %13, %14, %15, %16, %17, %18, %19, %20, %21, %22, %23, %24, %25, %26, %27, %28, %29, %30, %31}, %32, %33, p, 1, 1, 0, 1;\n}\n"
    : "+f"(d[128]), "+f"(d[129]), "+f"(d[130]), "+f"(d[131]), "+f"(d[132]), "+f"(d[133]), "+f"(d[134]), "+f"(d[135]), "+f"(d[136]), "+f"(d[137]), "+f"(d[138]), "+f"(d[139]), "+f"(d[140]), "+f"(d[141]), "+f"(d[142]), "+f"(d[143]), "+f"(d[144]), "+f"(d[145]), "+f"(d[146]), "+f"(d[147]), "+f"(d[148]), "+f"(d[149]), "+f"(d[150]), "+f"(d[151]), "+f"(d[152]), "+f"(d[153]), "+f"(d[154]), "+f"(d[155]), "+f"(d[156]), "+f"(d[157]), "+f"(d[158]), "+f"(d[159])
    : "l"(da), "l"(db), "r"(scale_d));
}
__device__ __forceinline__ void wgmma_n64b(float (&d)[192], uint64_t da, uint64_t db, int scale_d) {
  asm volatile("{\n.reg .pred p;\nsetp.ne.b32 p, %34, 0;\n"
    "wgmma.mma_async.sync.aligned.m64n64k16.f32.bf16.bf16 {%0, %1, %2, %3, %4, %5, %6, %7, %8, %9, %10, %11, %12, %13, %14, %15, %16, %17, %18, %19, %20, %21, %22, %23, %24, %25, %26, %27, %28, %29, %30, %31}, %32, %33, p, 1, 1, 0, 1;\n}\n"
    : "+f"(d[160]), "+f"(d[161]), "+f"(d[162]), "+f"(d[163]), "+f"(d[164]), "+f"(d[165]), "+f"(d[166]), "+f"(d[167]), "+f"(d[168]), "+f"(d[169]), "+f"(d[170]), "+f"(d[171]), "+f"(d[172]), "+f"(d[173]), "+f"(d[174]), "+f"(d[175]), "+f"(d[176]), "+f"(d[177]), "+f"(d[178]), "+f"(d[179]), "+f"(d[180]), "+f"(d[181]), "+f"(d[182]), "+f"(d[183]), "+f"(d[184]), "+f"(d[185]), "+f"(d[186]), "+f"(d[187]), "+f"(d[188]), "+f"(d[189]), "+f"(d[190]), "+f"(d[191])
    : "l"(da), "l"(db), "r"(scale_d));
}

constexpr int SLOT = 16384;
constexpr int KVT = 10240;
constexpr uint32_t QA = 0x0BAu, QK = 0x462u, QQ = 0x981u;
constexpr int SM_SD = 12 * SLOT;
constexpr int SM_BAR = SM_SD + 8192;
constexpr int SM_RS = SM_BAR + 512;
constexpr int SM_AP = SM_RS + 768;
constexpr int SM_BP = SM_AP + 2048;
constexpr int SM_WPHI = SM_BP + 12288;
constexpr int SM_EPOCH = SM_WPHI + 10240;
constexpr int SM_TOTAL = SM_EPOCH + 16 + 1024;
constexpr int B_FULLS = 0, B_XOLD = 24, B_STAT = 32, B_EMPTYS = 40, B_FULLT = 256  , B_CONS = 384  , B_E3 = 472, B_E0 = 480, B_E1 = 488, B_E2 = 496, B_EPI = 504, B_CS = 160,
              B_KVDONE = 168  , B_ODONE = 176, B_XDONE = 184, B_OH1 = 192, B_CS2 = 208, B_XH0 = 232, B_R0 = 240, B_CB = 144  , B_XOLD2 = 216, B_FLG = 64  ;
constexpr uint64_t BAR_CNT = 0x1c07fc0eac00a800ull;
constexpr uint64_t WO_A0 = 0xba76218762187643ull, WO_B0 = 0x9540395403ba9021ull, WO_A1 = 0xba713257132576abull, WO_B1 = 0x9506489064890132ull;
constexpr uint64_t WO_DA0 = 0xa9876543210edd00ull, WO_DB0 = 0xa987654321bbccccull, WO_DA1 = 0xa9876543210fff00ull, WO_DB1 = 0xa98765432bbcccddull;
#define WOORD 0xFDB9753ECA864210ull
constexpr int NX = 4;
constexpr int XS = 10;

#define PL 2
#define PROFX(i) PROFT(tid_ == 128 && layer == PL, 200 + (i))
#define PSL 20
#define EP 5
#define NCOM 3
#define CSLP 128
#define PFS 8
#define KVTH 0x41700000u
#define RL 3
#define ORD 1
#define XB2 2
#define PMOD 3
#define DB1 2
#define XPF 2
#define XPM 0
#define AW 1
#define PG 0
#define UNS 6
#define NLAYERS 4
constexpr float L2E = 1.4426950408889634f;
#define PHI_MAX 2147483648.f

#define D128(lo) desc64(lo, 0x40000040u)
struct Ctx { uint32_t sb; int g, rb, cu; bf16* out; };

__device__ __forceinline__ void colsum(const CUtensorMap* tm, float* cs, int rb, int g, int w0, int dw, int lane, uint32_t stg, uint32_t cb, uint32_t par) {
  const uint32_t src = stg + (lane >> 3) * 2048;
#pragma unroll 1
  for (int wi = w0 - dw; wi < 6; wi += dw) {
    float s[8] = {0.f, 0.f, 0.f, 0.f, 0.f, 0.f, 0.f, 0.f};
    if (wi >= 0) {
      mbar_wait_u(cb, par);
      par ^= 1;
#pragma unroll 4
      for (int r = 0; r < 16; ++r) {
        const uint4 v = lds128(src + r * 128 + (((lane ^ r) & 7) << 4));
        s[0] += bf_lo(v.x); s[1] += bf_hi(v.x); s[2] += bf_lo(v.y); s[3] += bf_hi(v.y);
        s[4] += bf_lo(v.z); s[5] += bf_hi(v.z); s[6] += bf_lo(v.w); s[7] += bf_hi(v.w);
      }
#pragma unroll
      for (int i = 0; i < 8; ++i) s[i] += __shfl_xor_sync(0xffffffffu, s[i], 8);
    }
    const int wn = wi + dw;
    if (wn < 6) {
      expect_tx_e(cb, 8192);
      tma_2d_e(stg, tm, (wn >= 4 ? 0 : 1024 + (wn >> 1) * 1024) + g * 128 + (wn & 1) * 64, rb * 64, cb);
    }
    if (wi >= 0) {
#pragma unroll
      for (int i = 0; i < 8; ++i) s[i] += __shfl_xor_sync(0xffffffffu, s[i], 16);
      if (lane < 8) {
        red_add4(cs + g * 384 + (wi * 8 + lane) * 8, s[0], s[1], s[2], s[3]);
        red_add4(cs + g * 384 + (wi * 8 + lane) * 8 + 4, s[4], s[5], s[6], s[7]);
      }
      __syncwarp();
    }
  }
}
#define PHASE_CTX() \
  uint32_t sb = c.sb; asm volatile("" : "+r"(sb)); \
  int tid_ = threadIdx.x; asm volatile("" : "+r"(tid_)); \
  const uint32_t bar = sb + SM_BAR; \
  const int lane = tid_ & 31, cw = (tid_ >> 5) - 4, wg = cw >> 2, wq = cw & 3, gq = lane >> 2, t = lane & 3, wrow0 = cw * 16; \
  const int lrow = (lane & 7) + ((lane >> 3) & 1) * 8, lchk = lane >> 4; \
  const bool elected = (tid_ & 127) == 0; \
  const uint32_t rowo = (wrow0 + lrow) * 128, X = (lchk ^ (lane & 7)) << 4; \
  (void)bar; (void)wq; (void)gq; (void)lrow; (void)lchk; (void)elected; (void)wrow0; (void)wg; (void)rowo; (void)X; (void)t;

__device__ __forceinline__ void slab_out_half(uint32_t slot, bf16* dst, int wrow0, int lane, bool FENCE = false) {
  const int r0 = lane >> 3, ch = lane & 7;
  const uint32_t src = slot + (wrow0 + r0) * 128;
  uint4 v[4];
#pragma unroll
  for (int i = 0; i < 4; ++i) v[i] = lds128(src + i * 512 + (((ch ^ (4 * i + r0)) & 7) << 4));
  if (FENCE) fence_async_smem();
  dst += (size_t)(wrow0 + r0) * D_ + ch * 8;
#pragma unroll
  for (int i = 0; i < 4; ++i)
    asm volatile("st.global.v4.u32 [%0], {%1,%2,%3,%4};" ::"l"(dst + (size_t)i * 4 * D_), "r"(v[i].x), "r"(v[i].y), "r"(v[i].z), "r"(v[i].w) : "memory");
}

struct Tag { uint32_t me, mo, tg; };
__device__ __forceinline__ Tag make_tag(int gq, int t, uint32_t tg) {
  const uint32_t on = t == (gq & 3), par = ((gq >> 2) ^ gq) & 1;
  return Tag{on & ~par, on & par, tg};
}
__device__ __forceinline__ void stsm_tag(uint32_t addr, uint32_t r0, uint32_t r1, uint32_t r2, uint32_t r3, const Tag& k) {
  stsm_x4(addr, (r0 & ~k.me) | (k.tg & k.me), (r1 & ~k.me) | (k.tg & k.me), (r2 & ~k.mo) | (k.tg & k.mo), (r3 & ~k.mo) | (k.tg & k.mo));
}
__device__ __forceinline__ void tile_check(uint32_t slot, const bf16* src, int wrow0, int lane, uint32_t tg) {
  const uint32_t va = slot + (wrow0 + (lane >> 2)) * 128 + (lane & 3) * 32 + (lane >> 2) * 4;
  if (__builtin_expect(__any_sync(0xffffffffu, ((lds_vol(va) ^ tg) | (lds_vol(va + 1024) ^ tg)) & 1), 0)) {
    const int r0 = lane >> 3, ch = lane & 7;
    uint32_t n = 0;
#pragma unroll 1
    do {
#pragma unroll 1
      for (int i = 0; i < 4; ++i)
        sts128(slot + (wrow0 + r0 + 4 * i) * 128 + (((ch ^ (4 * i + r0)) & 7) << 4),
               ld_relaxed4(reinterpret_cast<const uint4*>(src + (size_t)(wrow0 + r0 + 4 * i) * D_ + ch * 8)));
      __syncwarp();
      if (++n > (1u << 16)) { g_err = 8u; break; }
    } while (__any_sync(0xffffffffu, ((lds_vol(va) ^ tg) | (lds_vol(va + 1024) ^ tg)) & 1));
    fence_async_smem();
    __syncwarp();
  }
}

template <int O>
__device__ __forceinline__ void phi_proj(float (&p)[2][4][4], const uint32_t (&kq)[64], uint32_t wa) {
#pragma unroll
  for (int h = 0; h < 2; ++h)
#pragma unroll
    for (int i = 0; i < 4; ++i) { p[h][i][0] = p[h][i][1] = p[h][i][2] = p[h][i][3] = 0.f; }
#pragma unroll
  for (int ks = 0; ks < 2; ++ks)
#pragma unroll
    for (int np = 0; np < 2; ++np)
#pragma unroll
      for (int h = 0; h < 2; ++h) {
        uint32_t b0, b1, b2, b3;
        ldsm_x4_t(b0, b1, b2, b3, wa + h * 2560 + ks * 1280 + np * 32);
        mma_bf16(p[h][2 * np], kq[O + 8 * h + 4 * ks], kq[O + 8 * h + 4 * ks + 1], kq[O + 8 * h + 4 * ks + 2], kq[O + 8 * h + 4 * ks + 3], b0, b1);
        mma_bf16(p[h][2 * np + 1], kq[O + 8 * h + 4 * ks], kq[O + 8 * h + 4 * ks + 1], kq[O + 8 * h + 4 * ks + 2], kq[O + 8 * h + 4 * ks + 3], b2, b3);
      }
}
__device__ __forceinline__ void phi_exp(uint32_t (&raw)[4][4], const float (&p)[4][4], float sc0, float sc1) {
#pragma unroll
  for (int i = 0; i < 4; ++i) {
    const float e0 = ex2(p[i][0] * sc0), e1 = ex2(p[i][1] * sc0), e2 = ex2(p[i][2] * sc1), e3 = ex2(p[i][3] * sc1);
    const float m0 = e0 * e1, m1 = e2 * e3, rr = rcp(m0 * m1), r0 = rr * m1, r1 = rr * m0;
    raw[i >> 1][(i & 1) * 2] = pack_bf16(e0, e1);
    raw[i >> 1][(i & 1) * 2 + 1] = pack_bf16(e2, e3);
    raw[2 + (i >> 1)][(i & 1) * 2] = pack_bf16(e1 * r0, e0 * r0);
    raw[2 + (i >> 1)][(i & 1) * 2 + 1] = pack_bf16(e3 * r1, e2 * r1);
  }
}
#define FENCE_P(h) _Pragma("unroll") for (int i_ = 0; i_ < 16; ++i_) asm volatile("" : "+f"(p[h][i_ >> 2][i_ & 3]) :: "memory")
#define FENCE_RAW(h) _Pragma("unroll") for (int i_ = 0; i_ < 16; ++i_) asm volatile("" : "+r"(raw[h][i_ >> 2][i_ & 3]) :: "memory")
template <int O>
__device__ __forceinline__ void phi_norm(uint32_t (&ph)[2][4][4], const uint32_t (&raw)[2][4][4], const uint32_t (&kq)[64], uint32_t wa,
                                         float sc0, float sc1, float mul0, float mul1) {
  bool bad = false;
#pragma unroll
  for (int h = 0; h < 2; ++h)
#pragma unroll
    for (int sg = 0; sg < 2; ++sg) {
      float ss[4] = {0.f, 0.f, 0.f, 0.f};
#pragma unroll
      for (int ks = 0; ks < 2; ++ks)
        mma_bf16(ss, raw[h][2 * sg + ks][0], raw[h][2 * sg + ks][1], raw[h][2 * sg + ks][2], raw[h][2 * sg + ks][3], 0x3F803F80u, 0x3F803F80u);
      bad = bad || !(ss[0] < PHI_MAX) || !(ss[2] < PHI_MAX);
      const uint32_t iv = pack_bf16(rcp(ss[0]) * mul0, rcp(ss[2]) * mul1);
#pragma unroll
      for (int ks = 0; ks < 2; ++ks)
#pragma unroll
        for (int j = 0; j < 4; ++j) ph[h][2 * sg + ks][j] = mul_bf16x2(raw[h][2 * sg + ks][j], iv, j & 1);
    }
  if (__builtin_expect(__any_sync(0xffffffffu, bad), 0)) {
#pragma unroll 1
    for (int it = 0; it < 4; ++it) {
      float q[4][4];
#pragma unroll
      for (int i = 0; i < 4; ++i) { q[i][0] = q[i][1] = q[i][2] = q[i][3] = 0.f; }
#pragma unroll
      for (int ks = 0; ks < 2; ++ks) {
        uint32_t a[4];
#pragma unroll
        for (int j = 0; j < 4; ++j) a[j] = (it & 2) ? kq[O + 8 + 4 * ks + j] : kq[O + 4 * ks + j];
#pragma unroll
        for (int np = 0; np < 2; ++np) {
          uint32_t b0, b1, b2, b3;
          ldsm_x4_t(b0, b1, b2, b3, wa + (it >> 1) * 2560 + ks * 1280 + np * 32);
          mma_bf16(q[2 * np], a[0], a[1], a[2], a[3], b0, b1);
          mma_bf16(q[2 * np + 1], a[0], a[1], a[2], a[3], b2, b3);
        }
      }
      float iv[2];
#pragma unroll
      for (int r = 0; r < 2; ++r) {
        const float sc = (it & 1) ? -(r ? sc1 : sc0) : (r ? sc1 : sc0);
        float mx = -INFINITY, sm = 0.f;
#pragma unroll
        for (int i = 0; i < 8; ++i) { float& v = q[i >> 1][2 * r + (i & 1)]; v *= sc; mx = fmaxf(mx, v); }
        mx = fmaxf(mx, __shfl_xor_sync(0xffffffffu, mx, 1));
        mx = fmaxf(mx, __shfl_xor_sync(0xffffffffu, mx, 2));
#pragma unroll
        for (int i = 0; i < 8; ++i) { float& v = q[i >> 1][2 * r + (i & 1)]; v = ex2(v - mx); sm += v; }
        sm += __shfl_xor_sync(0xffffffffu, sm, 1);
        sm += __shfl_xor_sync(0xffffffffu, sm, 2);
        iv[r] = rcp(sm) * (r ? mul1 : mul0);
      }
#pragma unroll
      for (int i = 0; i < 24; ++i) ph[i >> 4][(i >> 2) & 3][i & 3] = ph[(i + 8) >> 4][((i + 8) >> 2) & 3][i & 3];
#pragma unroll
      for (int i = 0; i < 4; ++i) {
        ph[1][2 + (i >> 1)][(i & 1) * 2] = pack_bf16(q[i][0] * iv[0], q[i][1] * iv[0]);
        ph[1][2 + (i >> 1)][(i & 1) * 2 + 1] = pack_bf16(q[i][2] * iv[1], q[i][3] * iv[1]);
      }
    }
  }
}

__device__ __forceinline__ void stats_out(float s0, float s1, float q0, float q1, float2* dst, int t) {
  const bool od = t & 1;
  float sa = od ? s1 : s0, qa = od ? q1 : q0;
  sa += __shfl_xor_sync(0xffffffffu, od ? s0 : s1, 1);
  qa += __shfl_xor_sync(0xffffffffu, od ? q0 : q1, 1);
  sa += __shfl_xor_sync(0xffffffffu, sa, 2);
  qa += __shfl_xor_sync(0xffffffffu, qa, 2);
  if (t < 2) red_add2(&dst[t * 8].x, sa, qa);
}

__device__ __forceinline__ void consumer(const Ctx& c) {
  const int g = c.g, m0 = c.rb * 128;
  float acc[192];
#define X_H1() \
      _Pragma("unroll") for (int jp = 4; jp < 8; ++jp) \
        stsm_x4(sb + (XS + 1) * SLOT + rowo + (X ^ ((jp & 3) << 5)), \
                pack_bf16(acc[128 + 8 * jp], acc[129 + 8 * jp]), pack_bf16(acc[130 + 8 * jp], acc[131 + 8 * jp]), \
                pack_bf16(acc[132 + 8 * jp], acc[133 + 8 * jp]), pack_bf16(acc[134 + 8 * jp], acc[135 + 8 * jp]));
#pragma unroll
  for (int i = 128; i < 192; ++i) acc[i] = 0.f;
#pragma unroll 1
  for (int layer = 0;; ++layer) {
    {
      PHASE_CTX();
      const uint32_t wu = c.cu >> 2;
      const uint32_t dA0 = (((sb + wu * 8192) & 0x3FFFF) >> 4) | (1u << 16), dB0 = ((sb & 0x3FFFF) >> 4) | (512u << 16);
      {
        PROFX(0);
        mbar_wait(bar + B_FULLS, 0);
        PROFX(1);
        wgmma_fence();
        wgmma_n256_0(acc, D128(dA0 + XS * 1024), D128(dB0 + 2048));
#pragma unroll
        for (int k = 1; k < 4; ++k) wgmma_n256(acc, D128(dA0 + XS * 1024 + k * 2), D128(dB0 + 2048 + k * 128), 1);
        wgmma_commit();
        wgmma_wait<1>();
        float s0 = 0.f, s1 = 0.f, q0 = 0.f, q1 = 0.f;
        if (layer) {
          X_H1();
#pragma unroll
          for (int i = 128; i < 192; i += 4) {
            s0 += acc[i] + acc[i + 1]; s1 += acc[i + 2] + acc[i + 3];
            q0 = fmaf(acc[i], acc[i], fmaf(acc[i + 1], acc[i + 1], q0)); q1 = fmaf(acc[i + 2], acc[i + 2], fmaf(acc[i + 3], acc[i + 3], q1));
          }
        }
        asm volatile("" : "+f"(s0), "+f"(s1), "+f"(q0), "+f"(q1) :: "memory");
        wgmma_fence();
        wgmma_n128_0(acc, D128(dA0 + XS * 1024), D128(dB0 + 1024));
#pragma unroll
        for (int k = 1; k < 4; ++k) wgmma_n128(acc, D128(dA0 + XS * 1024 + k * 2), D128(dB0 + 1024 + k * 128), 1);
        wgmma_commit();
        if (layer) {
          PHASE_CTX();
          fence_async_smem();
          nbar_dyn(3 + wu, 128);
          stats_out(s0, s1, q0, q1, g_stats + layer * S_ + m0 + wrow0 + gq, t);
          PROFT(tid_ == 128, layer * 16 + 8);
        }
      }
      uint32_t s = 1, u = 0, sp = 0;
      const int ix = layer ? 1 : 2 * min(g, NCOM) + 1;
#pragma unroll 1
      for (int i = 1; i < 14; ++i) {
        mbar_wait(bar + B_FULLS + s * 8, (u + (s ? layer : 0)) & 1);
        const uint32_t da = dA0 + ((QA >> (4 * s)) & 15) * 1024, dk = dB0 + ((QK >> (4 * s)) & 15) * 1024,
                       dq = dB0 + ((QQ >> (4 * s)) & 15) * 1024;
        wgmma_fence();
#pragma unroll
        for (int k = 0; k < 4; ++k) {
          wgmma_n256(acc, D128(da + k * 2), D128(dk + k * 128), 1);
          wgmma_n128(acc, D128(da + k * 2), D128(dq + k * 128), 1);
        }
        wgmma_commit();
        if (i == ix || (i == ix + 1 && !layer)) {
          PHASE_CTX();
          if (layer) {
            slab_out_half(sb + (XS + 1) * SLOT, g_x + (size_t)m0 * D_ + g * 128 + 64, wrow0, lane);
          } else {
            float s0 = 0.f, s1 = 0.f, q0 = 0.f, q1 = 0.f;
            const uint32_t xa = sb + ((QA >> (4 * sp)) & 15) * SLOT + rowo;
#pragma unroll
            for (int jp = 0; jp < 4; ++jp) {
              uint32_t x0, x1, x2, x3;
              ldsm_x4(x0, x1, x2, x3, xa + (X ^ (jp << 5)));
              s0 += (bf_lo(x0) + bf_hi(x0)) + (bf_lo(x2) + bf_hi(x2));
              s1 += (bf_lo(x1) + bf_hi(x1)) + (bf_lo(x3) + bf_hi(x3));
              q0 = fmaf(bf_lo(x0), bf_lo(x0), fmaf(bf_hi(x0), bf_hi(x0), fmaf(bf_lo(x2), bf_lo(x2), fmaf(bf_hi(x2), bf_hi(x2), q0))));
              q1 = fmaf(bf_lo(x1), bf_lo(x1), fmaf(bf_hi(x1), bf_hi(x1), fmaf(bf_lo(x3), bf_lo(x3), fmaf(bf_hi(x3), bf_hi(x3), q1))));
            }
            stats_out(s0, s1, q0, q1, g_stats + m0 + wrow0 + gq, t);
          }
          __syncwarp();
          if (lane == 0 && (layer || i != ix)) mbar_arrive(bar + B_XDONE);
          nbar_dyn(3 + wu, 128);
        }
        wgmma_wait<1>();
        if (elected) release2(bar + B_EMPTYS + sp * 8);
        sp = s;
        if (++s == 3) { s = 0; ++u; }
      }
      {
        const uint64_t dap = make_desc_ns(sb + SM_AP + wu * 1024, 0, 128), dbp = make_desc_ns(sb + SM_BP + (layer & 1) * 6144, 0, 128);
        if (wu == 0) {
          wgmma_wait<0>();
          if (elected) mbar_arrive(bar + B_R0);
          nbar<6, 256>();
        }
        if (layer < 2) mbar_wait(bar + (layer ? B_CS2 : B_CS), 0);
        mbar_wait(bar + B_STAT, layer & 1);
        mbar_wait(bar + B_FULLS + 16, layer & 1);
        wgmma_fence();
        wgmma_n256_k(acc, dap, dbp, 1);
#pragma unroll
        for (int k = 0; k < 4; ++k) wgmma_n256(acc, D128(dA0 + (QA >> 8) * 1024 + k * 2), D128(dB0 + (QK >> 8) * 1024 + k * 128), 1);
        mbar_wait(bar + B_FULLS, 1);
        PROFT(tid_ == 128, layer * 16 + 9);
        wgmma_fence();
#pragma unroll
        for (int k = 0; k < 4; ++k) wgmma_n256(acc, D128(dA0 + (QA & 15) * 1024 + k * 2), D128(dB0 + (QK & 15) * 1024 + k * 128), 1);
        wgmma_commit();
        if (wu) nbar<6, 256>();
#define Q_TAIL() \
        wgmma_n128_k(acc, dap, dbp + 256, 1); \
        _Pragma("unroll") for (int k = 0; k < 4; ++k) wgmma_n128(acc, D128(dA0 + (QA >> 8) * 1024 + k * 2), D128(dB0 + (QQ >> 8) * 1024 + k * 128), 1); \
        _Pragma("unroll") for (int k = 0; k < 4; ++k) wgmma_n128(acc, D128(dA0 + (QA & 15) * 1024 + k * 2), D128(dB0 + (QQ & 15) * 1024 + k * 128), 1);
        Q_TAIL();
        wgmma_commit();
        wgmma_wait<1>();
#pragma unroll
        for (int i = 0; i < 128; ++i) asm volatile("" : "+f"(acc[i]) :: "memory");
      }
    }
    uint32_t xo[32];
    {
      PHASE_CTX();
      PROFT(tid_ == 128, layer * 16 + 1);
      const bool isB = layer & 1;
      const int cu = c.cu;
      if (cu >= 4) asm volatile("bar.arrive 7, 256;" ::: "memory");
      if (elected && cu == 4) mbar_arrive(bar + B_R0);
      uint32_t kq[64];
      const uint32_t rowq = rowo & 8191;
      const float rs0 = lds_f(sb + SM_RS + (16 + wrow0 + gq) * 4), rs1 = lds_f(sb + SM_RS + (24 + wrow0 + gq) * 4);
#define Q_DONE() \
      wgmma_wait<0>(); \
      if (lane == 0) release2(bar + B_E0); \
      _Pragma("unroll") for (int i = 128; i < 192; ++i) asm volatile("" : "+f"(acc[i]) :: "memory"); \
      _Pragma("unroll") for (int i = 0; i < 32; ++i) kq[32 + i] = pack_bf16(acc[128 + 2 * i], acc[129 + 2 * i]);
      if (isB) {
        if (cu == 0) asm volatile("bar.arrive 10, 64;" ::: "memory");
        if (elected) release2(bar + B_E1);
        const int e = gq & 1;
        const bool sel = t > (gq >> 1);
        const uint32_t rja = sb + SM_RS + (wrow0 + 2 * t + e) * 4;
        const float rjA0 = lds_f(rja + 32), rjA1 = lds_f(rja + 64), rjB0 = lds_f(rja + (sel ? 0 : 64)), rjB1 = lds_f(rja + (sel ? 32 : 96));
        uint32_t vv[32];
#pragma unroll
        for (int i = 0; i < 16; ++i) { kq[i] = pack_bf16(acc[2 * i], acc[2 * i + 1]); vv[i] = pack_bf16(acc[64 + 2 * i], acc[65 + 2 * i]); }
        const uint32_t rB = sb + 4 * SLOT + wg * 4 * KVT + rowq;
        auto dump = [&](int hp) {
          const uint32_t kb = rB + 2048 + (hp ^ wg) * 2 * KVT;
#pragma unroll
          for (int jp = 0; jp < 4; ++jp) {
            stsm_x4(kb + (X ^ (jp << 5)), kq[16 * hp + 4 * jp], kq[16 * hp + 4 * jp + 1], kq[16 * hp + 4 * jp + 2], kq[16 * hp + 4 * jp + 3]);
            stsm_x4(kb + KVT + (X ^ (jp << 5)), vv[16 * hp + 4 * jp], vv[16 * hp + 4 * jp + 1], vv[16 * hp + 4 * jp + 2], vv[16 * hp + 4 * jp + 3]);
          }
          if (cu == 3) {
            const uint32_t kd = rB + 2048 + 32768 + (1 - hp) * 2 * KVT;
#pragma unroll
            for (int jp = 0; jp < 4; ++jp) {
              stsm_x4(kd + (X ^ (jp << 5)), kq[16 * hp + 4 * jp], kq[16 * hp + 4 * jp + 1], kq[16 * hp + 4 * jp + 2], kq[16 * hp + 4 * jp + 3]);
              stsm_x4(kd + KVT + (X ^ (jp << 5)), vv[16 * hp + 4 * jp], vv[16 * hp + 4 * jp + 1], vv[16 * hp + 4 * jp + 2], vv[16 * hp + 4 * jp + 3]);
            }
            if (hp) asm volatile("bar.arrive 15, 64;" ::: "memory"); else asm volatile("bar.arrive 9, 64;" ::: "memory");
          }
          asm volatile("bar.arrive %0, 224;" :: "r"(hp ? 13 + (cu >> 2) : 8 + (cu & 4)) : "memory");
        };
        uint4* const hbuf = g_halo + ((c.rb * 8 + g) * 2 + (layer >> 1)) * 512 + lane;
        if (cu < 4) {
          nbar<7, 256>();
          dump(0);
        }
#pragma unroll
        for (int i = 16; i < 32; ++i) { kq[i] = pack_bf16(acc[2 * i], acc[2 * i + 1]); vv[i] = pack_bf16(acc[64 + 2 * i], acc[65 + 2 * i]); }
        if (cu >= 4) {
          if (cu == 7) {
#pragma unroll
            for (int jp = 0; jp < 8; ++jp) {
              st_relaxed4(hbuf + jp * 32, ~kq[4 * jp], ~kq[4 * jp + 1], ~kq[4 * jp + 2], ~kq[4 * jp + 3]);
              st_relaxed4(hbuf + 256 + jp * 32, ~vv[4 * jp], ~vv[4 * jp + 1], ~vv[4 * jp + 2], ~vv[4 * jp + 3]);
            }
          }
          dump(0);
          dump(1);
        }
        PROFT(tid_ == 128, layer * 16 + 2);
        constexpr float SC = 0.17677669529663687f * L2E;
        const float fA0 = rjA0 * rs0 * SC, fB0 = rjB0 * rs0 * SC, fA1 = rjA1 * rs1 * SC, fB1 = rjB1 * rs1 * SC;
        const float bA0 = (m0 + wrow0) ? 0.f : -1e30f, bB = sel ? bA0 : 0.f;
        const uint32_t pA_ = e ? 0x1044u : 0x4410u, pB_ = e ? 0x3244u : 0x4432u, pLo = sel ? pB_ : 0x4444u, pHi = sel ? 0x4444u : pB_;
        const uint32_t KX = ((lane >> 3) ^ (lane & 7)) << 4;
        Q_DONE();
        if (cu == 0) {
          nbar<11, 64>();
        } else if (cu == 4) {
          uint4 hv[16];
          if (c.rb > 0) {
            uint32_t n = 0;
#pragma unroll 1
            while (true) {
              uint32_t mn = 0xFFFFFFFFu;
#pragma unroll
              for (int i = 0; i < 16; ++i) hv[i] = ld_relaxed4(hbuf - 16 * 512 + i * 32);
#pragma unroll
              for (int i = 0; i < 16; ++i) mn = __vimin3_u32(__vimin3_u32(mn, hv[i].x, hv[i].y), hv[i].z, hv[i].w);
              if (__all_sync(0xffffffffu, mn != 0u)) break;
              if (++n > (1u << 20)) { g_err = 4u; break; }
            }
          } else {
#pragma unroll
            for (int i = 0; i < 16; ++i) hv[i] = make_uint4(~0u, ~0u, ~0u, ~0u);
          }
          nbar<10, 64>();
#pragma unroll
          for (int i = 0; i < 16; ++i)
            stsm_x4(rB - 4 * KVT + (((i >> 2) & 1) * 2 + (i >> 3)) * KVT + (X ^ ((i & 3) << 5)), ~hv[i].x, ~hv[i].y, ~hv[i].z, ~hv[i].w);
          asm volatile("bar.arrive 11, 64;" ::: "memory");
          nbar<9, 64>();
        } else {
          nbar_dyn(8 + (cu & 4), 224);
        }
        PROFT(tid_ == 128, layer * 16 + 5);
        PROFT(lane == 0 && layer == PL, 136 + cw);
        auto attend = [&](int hp) {
          const uint32_t qad = sb + (XS + 1 - hp) * SLOT + rowo, kt = rB + 2 * (hp ^ wg) * KVT - (lane & 8) * 128, vt = rB + (2 * (hp ^ wg) + 1) * KVT;
          __syncwarp();
          uint32_t kb[2][2][4], vb[2][2][2][4];
#pragma unroll
          for (int h = 0; h < 2; ++h)
#pragma unroll
            for (int nt = 0; nt < 2; ++nt) ldsm_x4(kb[h][nt][0], kb[h][nt][1], kb[h][nt][2], kb[h][nt][3], kt + nt * 1024 + (KX ^ (h << 6)));
#pragma unroll
          for (int ks = 0; ks < 2; ++ks)
#pragma unroll
            for (int np = 0; np < 2; ++np)
#pragma unroll
              for (int h = 0; h < 2; ++h)
                ldsm_x4_t(vb[h][ks][np][0], vb[h][ks][np][1], vb[h][ks][np][2], vb[h][ks][np][3], vt + ks * 2048 + (X ^ (h << 6) ^ (np << 5)));
          if (hp == 0 && lane == 0) release2(bar + B_E3);
          if (DB1 == 1 && hp == 0 && cu < 4) dump(1);
          float la[2][2], lb[2][2], mx[2][2], sm[2][2];
#pragma unroll
          for (int h = 0; h < 2; ++h) {
            const int qo = 32 + 16 * hp + 8 * h, ko = 16 * hp + 8 * h;
            float sc[4][4];
#pragma unroll
            for (int nt = 0; nt < 4; ++nt) {
              sc[nt][0] = sc[nt][1] = sc[nt][2] = sc[nt][3] = 0.f;
#pragma unroll
              for (int ks = 0; ks < 2; ++ks)
                mma_bf16(sc[nt], kq[qo + 4 * ks], kq[qo + 4 * ks + 1], kq[qo + 4 * ks + 2], kq[qo + 4 * ks + 3],
                         nt < 2 ? kb[h][nt & 1][2 * ks] : kq[ko + 4 * ks + (nt & 1)], nt < 2 ? kb[h][nt & 1][2 * ks + 1] : kq[ko + 4 * ks + 2 + (nt & 1)]);
            }
            la[h][0] = fmaf(e ? sc[1][1] : sc[1][0], fA0, bA0);
            lb[h][0] = fmaf(sel ? (e ? sc[0][1] : sc[0][0]) : (e ? sc[2][1] : sc[2][0]), fB0, bB);
            la[h][1] = (e ? sc[2][3] : sc[2][2]) * fA1;
            lb[h][1] = fmaf(sel ? (e ? sc[1][3] : sc[1][2]) : (e ? sc[3][3] : sc[3][2]), fB1, bB);
            mx[h][0] = fmaxf(la[h][0], lb[h][0]); mx[h][1] = fmaxf(la[h][1], lb[h][1]);
          }
#pragma unroll
          for (int o = 1; o <= 2; o <<= 1)
#pragma unroll
            for (int h = 0; h < 2; ++h)
#pragma unroll
              for (int r = 0; r < 2; ++r) mx[h][r] = fmaxf(mx[h][r], __shfl_xor_sync(0xffffffffu, mx[h][r], o));
          float oa[2][4][4];
#pragma unroll
          for (int h = 0; h < 2; ++h) {
#pragma unroll
            for (int r = 0; r < 2; ++r) { la[h][r] = ex2(la[h][r] - mx[h][r]); lb[h][r] = ex2(lb[h][r] - mx[h][r]); sm[h][r] = la[h][r] + lb[h][r]; }
            const uint32_t p0 = pack_bf16(la[h][0] * rjA0, lb[h][0] * rjB0), p1 = pack_bf16(la[h][1] * rjA1, lb[h][1] * rjB1);
            const uint32_t a00 = __byte_perm(p0, 0u, pLo), a02 = __byte_perm(p0, 0u, pA_), a03 = __byte_perm(p1, 0u, pLo);
            const uint32_t a10 = __byte_perm(p0, 0u, pHi), a11 = __byte_perm(p1, 0u, pA_), a13 = __byte_perm(p1, 0u, pHi);
#pragma unroll
            for (int i = 0; i < 4; ++i) {
              oa[h][i][0] = oa[h][i][1] = oa[h][i][2] = oa[h][i][3] = 0.f;
              mma_bf16(oa[h][i], a00, 0u, a02, a03, vb[h][0][i >> 1][2 * (i & 1)], vb[h][0][i >> 1][2 * (i & 1) + 1]);
              mma_bf16(oa[h][i], a10, a11, 0u, a13, vb[h][1][i >> 1][2 * (i & 1)], vb[h][1][i >> 1][2 * (i & 1) + 1]);
            }
          }
#pragma unroll
          for (int o = 1; o <= 2; o <<= 1)
#pragma unroll
            for (int h = 0; h < 2; ++h)
#pragma unroll
              for (int r = 0; r < 2; ++r) sm[h][r] += __shfl_xor_sync(0xffffffffu, sm[h][r], o);
          mbar_wait(bar + (hp ? B_XOLD2 : B_XOLD), 1);
#pragma unroll
          for (int jp = 0; jp < 4; ++jp) ldsm_x4(xo[16 * hp + 4 * jp], xo[16 * hp + 4 * jp + 1], xo[16 * hp + 4 * jp + 2], xo[16 * hp + 4 * jp + 3], qad + (X ^ (jp << 5)));
#pragma unroll
          for (int h = 0; h < 2; ++h) {
            const float i0 = rcp(sm[h][0]), i1 = rcp(sm[h][1]);
#pragma unroll
            for (int np = 0; np < 2; ++np)
              stsm_tag(qad + (X ^ (h << 6) ^ (np << 5)),
                       pack_bf16(oa[h][2 * np][0] * i0, oa[h][2 * np][1] * i0), pack_bf16(oa[h][2 * np][2] * i1, oa[h][2 * np][3] * i1),
                       pack_bf16(oa[h][2 * np + 1][0] * i0, oa[h][2 * np + 1][1] * i0), pack_bf16(oa[h][2 * np + 1][2] * i1, oa[h][2 * np + 1][3] * i1), make_tag(gq, t, 0u));
          }
          __syncwarp();
          slab_out_half(sb + (XS + 1 - hp) * SLOT, g_o + (size_t)m0 * D_ + g * 128 + hp * 64, wrow0, lane, hp);
          __syncwarp();
          if (lane == 0) mbar_arrive(bar + (hp ? B_ODONE : B_OH1));
          PROFT(lane == 0 && layer == PL && hp == 0, 128 + cw);
        };
        attend(0);
        if (DB1 == 2 && cu < 4) dump(1);
        if (cu == 4) nbar<15, 64>();
        else if (cu != 0) nbar_dyn(13 + (cu >> 2), 224);
        attend(1);
      } else {
#pragma unroll
        for (int i = 0; i < 32; ++i) kq[i] = pack_bf16(acc[2 * i], acc[2 * i + 1]);
        if (cu < 4) nbar<7, 256>();
        {
          const uint32_t vb = sb + (5 + 3 * wg) * SLOT + (rowq >> 1) + ((lchk ^ ((lane & 7) >> 1)) << 4);
#pragma unroll
          for (int jp = 8; jp < 16; ++jp)
            stsm_x4((vb ^ ((jp & 1) << 5)) + ((jp >> 1) & 3) * 4096,
                    pack_bf16(acc[8 * jp], acc[8 * jp + 1]), pack_bf16(acc[8 * jp + 2], acc[8 * jp + 3]),
                    pack_bf16(acc[8 * jp + 4], acc[8 * jp + 5]), pack_bf16(acc[8 * jp + 6], acc[8 * jp + 7]));
        }
        PROFT(tid_ == 128, layer * 16 + 2);
        Q_DONE();
        const uint32_t pA = sb + (3 + 3 * wg) * SLOT + (rowo & 8191);
        float sc0 = rs0 * L2E, sc1 = rs1 * L2E;
        const uint32_t wa0 = sb + SM_WPHI + lrow * 80 + lchk * 16;
        const uint32_t wu = c.cu >> 2, par = (layer >> 1) & 1;
        float p[2][4][4];
        uint32_t raw[2][4][4], ph[2][4][4];
        float kva[20], oa[2][20];
        auto kv_start = [&](int hp) {
#pragma unroll
          for (int h = 0; h < 2; ++h)
#pragma unroll
            for (int cp = 0; cp < 4; ++cp)
              stsm_x4(pA + hp * 16384 + h * 8192 + (X ^ (cp << 5)), ph[h][cp][0], ph[h][cp][1], ph[h][cp][2], ph[h][cp][3]);
          PROFT(tid_ == 128, layer * 16 + 11);
          fence_async_smem();
          nbar<1, 256>();
          const uint32_t hu = 2 * hp + wu;
          const uint32_t dP = (((sb + 3 * SLOT + hu * 8192) & 0x3FFFF) >> 4) | (512u << 16);
          const uint32_t dV = (((sb + 5 * SLOT + hu * 4096) & 0x3FFFF) >> 4) | (((SM_SD - 5 * SLOT - hu * 4096) >> 4) << 16);
          wgmma_fence();
#pragma unroll
          for (int ks = 0; ks < 8; ++ks)
            wgmma_n40_tt(kva, desc64(dP + (ks >> 2) * 3072 + (ks & 3) * 128, 0x40000040u),
                         desc64(dV + (ks >> 2) * (3072u - (2816u << 16)) + (ks & 3) * 64, 0x80000020u), ks != 0);
          wgmma_commit();
        };
        auto kv_end = [&](int hp) {
          wgmma_wait<0>();
#pragma unroll
          for (int i = 0; i < 20; ++i) asm volatile("" : "+f"(kva[i]) :: "memory");
          nbar_dyn(3 + wu, 128);
          PROFT(tid_ == 128, layer * 16 + 12);
          const bool od = lane & 1;
#pragma unroll
          for (int i = 0; i < 4; ++i)
            sts128(sb + (3 + hp) * SLOT + (cw * 128 + i * 32 + lane) * 16,
                   make_uint4(__float_as_uint(kva[4 * i]), __float_as_uint(kva[4 * i + 1]), __float_as_uint(kva[4 * i + 2]),
                              __float_as_uint(od == (i >= 2) ? 1.f : kva[4 * i + 3])));
          sts128(sb + (6 + hp) * SLOT + wg * 8192 + (wq * 32 + lane) * 16,
                 make_uint4(__float_as_uint(od ? kva[11] : kva[3]), __float_as_uint(od ? kva[15] : kva[7]), __float_as_uint(od ? kva[18] : kva[16]), __float_as_uint(1.f)));
          fence_async_smem();
          __syncwarp();
          if (lane == 0) mbar_arrive(bar + B_KVDONE - hp * 32);
          PROFT(tid_ == 128, layer * 16 + 3);
        };
        const uint4* const kvg = g_kv + (g * 2 + (layer >> 1)) * 2560 + cw * 128 + lane;
        uint4 u[5];
        auto kv_load = [&](int hp) {
#pragma unroll
          for (int i = 0; i < 4; ++i) u[i] = ld_relaxed4(kvg + hp * 1280 + i * 32);
          u[4] = ld_relaxed4(kvg + hp * 1280 + 1024 - cw * 96);
        };
        auto o_start = [&](int hp, const uint32_t (&pq)[2][4][4]) {
          PROFT(tid_ == 128 && hp == 0, layer * 16 + 10);
          if (hp == 0) mbar_wait(bar + B_KVDONE - 32, par);
          const bool od = lane & 1;
          uint32_t n = 0;
#pragma unroll 1
          while (!__all_sync(0xffffffffu, (od ? u[2].w : u[0].w) == 0x41800000u && (od ? u[3].w : u[1].w) == 0x41800000u && u[4].w == 0x41800000u)) {
#pragma unroll 1
            while (__any_sync(0xffffffffu, u[4].w < KVTH) && ++n < (1u << 20)) u[4].w = ld_relaxed(&kvg[hp * 1280 + 1024 - cw * 96].w);
            if (++n > (1u << 20)) { g_err = 6u; break; }
            kv_load(hp);
          }
          PROFT(tid_ == 128 && hp == 0, layer * 16 + 5);
          if (!od) { u[0].w = u[4].x; u[1].w = u[4].y; } else { u[2].w = u[4].x; u[3].w = u[4].y; }
#pragma unroll
          for (int i = 0; i < 4; i += 2)
            stsm_x4(sb + (5 + 3 * hp) * SLOT + rowo + (X ^ ((i & 2) << 4)),
                    pack_bf16(__uint_as_float(u[i].x), __uint_as_float(u[i].y)), pack_bf16(__uint_as_float(u[i].z), __uint_as_float(u[i].w)),
                    pack_bf16(__uint_as_float(u[i + 1].x), __uint_as_float(u[i + 1].y)), pack_bf16(__uint_as_float(u[i + 1].z), __uint_as_float(u[i + 1].w)));
          const uint32_t z2 = pack_bf16(__uint_as_float(u[4].z), __uint_as_float(u[4].z));
          if (t < 2) sts128(sb + (5 + 3 * hp) * SLOT + (wrow0 + gq + 8 * t) * 128 + ((4 ^ gq) << 4), make_uint4(z2, z2, z2, z2));
          fence_async_smem();
          nbar<1, 256>();
          PROFT(tid_ == 128 && hp == 1, layer * 16 + 4);
          const uint32_t dK = (((sb + (5 + 3 * hp) * SLOT) & 0x3FFFF) >> 4) | (512u << 16);
          wgmma_fence();
#pragma unroll
          for (int ks = 0; ks < 4; ++ks) {
#pragma unroll
            for (int hh = 0; hh < 2; ++hh) wgmma_n40_rs(oa[hh], pq[hh][ks], D128(dK + hh * 512 + ks * 128), ks != 0);
          }
          wgmma_commit();
        };
        auto o_end = [&](int hp) {
          wgmma_wait<0>();
#pragma unroll
          for (int i = 0; i < 20; ++i) asm volatile("" : "+f"(oa[0][i]), "+f"(oa[1][i]) :: "memory");
#pragma unroll
          for (int hh = 0; hh < 2; ++hh) {
            const float i0 = rcp(oa[hh][16] + 1e-6f), i1 = rcp(oa[hh][18] + 1e-6f);
            const uint32_t qad = sb + (3 + hp) * SLOT + rowo, hx = hh << 6;
#pragma unroll
            for (int np = 0; np < 2; ++np)
              stsm_tag(qad + (X ^ hx ^ (np << 5)),
                       pack_bf16(oa[hh][8 * np] * i0, oa[hh][8 * np + 1] * i0), pack_bf16(oa[hh][8 * np + 2] * i1, oa[hh][8 * np + 3] * i1),
                       pack_bf16(oa[hh][8 * np + 4] * i0, oa[hh][8 * np + 5] * i0), pack_bf16(oa[hh][8 * np + 6] * i1, oa[hh][8 * np + 7] * i1), make_tag(gq, t, 1u));
          }
          __syncwarp();
          slab_out_half(sb + (3 + hp) * SLOT, g_o + (size_t)m0 * D_ + g * 128 + hp * 64, wrow0, lane, hp);
          __syncwarp();
          if (lane == 0) mbar_arrive(bar + (hp ? B_ODONE : B_OH1));
        };
#define XO_LOAD() \
        mbar_wait(bar + B_XOLD, 0); \
        mbar_wait(bar + B_XOLD2, 0); \
        _Pragma("unroll") for (int jp = 0; jp < 8; ++jp) \
          ldsm_x4(xo[4 * jp], xo[4 * jp + 1], xo[4 * jp + 2], xo[4 * jp + 3], sb + (XS + 1 - (jp >> 2)) * SLOT + rowo + (X ^ ((jp & 3) << 5)));
#define SC_RELOAD() \
        sc0 = __uint_as_float(lds_vol(sb + SM_RS + (16 + wrow0 + gq) * 4)) * L2E; sc1 = __uint_as_float(lds_vol(sb + SM_RS + (24 + wrow0 + gq) * 4)) * L2E;
        __syncwarp();
        phi_proj<0>(p, kq, wa0);
        phi_exp(raw[0], p[0], sc0, sc1);
        phi_exp(raw[1], p[1], sc0, sc1);
        phi_proj<16>(p, kq, wa0 + 5120);
        phi_norm<0>(ph, raw, kq, wa0, sc0, sc1, rs0, rs1);
        kv_start(0);
        phi_exp(raw[0], p[0], sc0, sc1);
        kv_end(0);
        if (RL & 1) { SC_RELOAD(); }
        XO_LOAD();
        phi_exp(raw[1], p[1], sc0, sc1);
        phi_proj<32>(p, kq, wa0);
        phi_norm<16>(ph, raw, kq, wa0 + 5120, sc0, sc1, rs0, rs1);
        kv_start(1);
        if (lane == 0) release2(bar + B_E3);
        phi_exp(raw[0], p[0], sc0, sc1);
        kv_end(1);
        if (RL & 2) { SC_RELOAD(); }
        kv_load(0);
        phi_exp(raw[1], p[1], sc0, sc1);
        phi_proj<48>(p, kq, wa0 + 5120);
        phi_norm<32>(ph, raw, kq, wa0, sc0, sc1, 1.f, 1.f);
        o_start(0, ph);
        phi_exp(raw[0], p[0], sc0, sc1);
        o_end(0);
        SC_RELOAD();
        kv_load(1);
        phi_exp(raw[1], p[1], sc0, sc1);
        phi_norm<48>(ph, raw, kq, wa0 + 5120, sc0, sc1, 1.f, 1.f);
        o_start(1, ph);
        o_end(1);
      }
      __syncwarp();
      PROFT(lane == 0 && layer == PL, 216 + cw);
      if (lane == 0) mbar_arrive(bar + B_EPI);
      PROFT(tid_ == 128, layer * 16 + 6);
    }
    {
      PHASE_CTX();
      const uint32_t wu = c.cu >> 2;
      const uint32_t dA0 = (((sb + wu * 8192) & 0x3FFFF) >> 4) | (1u << 16), dB0 = ((sb & 0x3FFFF) >> 4) | (512u << 16);
#pragma unroll
      for (int i = 0; i < 32; ++i) { acc[128 + 2 * i] = bf_lo(xo[i]); acc[129 + 2 * i] = bf_hi(xo[i]); }
      nbar_dyn(3 + wg, 128);
      uint64_t ta = (layer & 1) ? WO_A1 : WO_A0, tw = (layer & 1) ? WO_B1 : WO_B0;
#pragma unroll 1
      for (int i = 0; i < 16; ++i) {
        mbar_wait(bar + B_FULLT + i * 8, layer & 1);
        PROFT(tid_ == 128 && layer == PL, 160 + i);
        if (i >= 2) tile_check(sb + ((uint32_t)ta & 15) * SLOT, g_o + (size_t)m0 * D_ + ((2 * g + (int)(WOORD >> (4 * i))) & 15) * 64, wrow0, lane, ~layer);
        const uint32_t da = dA0 + ((uint32_t)ta & 15) * 1024, db = dB0 + ((uint32_t)tw & 15) * 1024;
        ta >>= 4; tw >>= 4;
        wgmma_fence();
#pragma unroll
        for (int k = 0; k < 4; ++k) wgmma_n128(acc, D128(da + k * 2), D128(db + k * 128), 1);
        wgmma_commit();
        if (i == 0) {
          if (elected) {
            release2(bar + B_E2);
          }
        } else {
          wgmma_wait<1>();
          if (elected && i < 12) release2(bar + B_CONS + (i - 1) * 8);
          if (elected && (unsigned)(i - 13) < 2u && layer + 1 < NLAYERS) release2(bar + B_EMPTYS + (i - 13) * 8);
        }
      }
      const bool last = layer == NLAYERS - 1;
      wgmma_wait<0>();
#pragma unroll
      for (int i = 128; i < 192; ++i) asm volatile("" : "+f"(acc[i]) :: "memory");
      if (elected && !last) release2(bar + B_EMPTYS + 16);
      PROFT(tid_ == 128, layer * 16 + 7);
#pragma unroll
      for (int jp = 0; jp < 4; ++jp)
        stsm_x4(sb + XS * SLOT + rowo + (X ^ (jp << 5)),
                pack_bf16(acc[128 + 8 * jp], acc[129 + 8 * jp]), pack_bf16(acc[130 + 8 * jp], acc[131 + 8 * jp]),
                pack_bf16(acc[132 + 8 * jp], acc[133 + 8 * jp]), pack_bf16(acc[134 + 8 * jp], acc[135 + 8 * jp]));
      if (last) {
        __syncwarp();
        slab_out_half(sb + XS * SLOT, c.out + (size_t)m0 * D_ + g * 128, wrow0, lane);
        X_H1();
        __syncwarp();
        slab_out_half(sb + (XS + 1) * SLOT, c.out + (size_t)m0 * D_ + g * 128 + 64, wrow0, lane);
        __syncwarp();
        if (lane == 0) mbar_arrive(bar + B_XDONE);
        PROFT(tid_ == 128, layer * 16 + 24);
        break;
      }
      __syncwarp();
      slab_out_half(sb + XS * SLOT, g_x + (size_t)m0 * D_ + g * 128, wrow0, lane, true);
      __syncwarp();
      if (lane == 0) mbar_arrive(bar + B_XH0);
      nbar_dyn(3 + wu, 128);
    }
  }
}

__device__ __forceinline__ void flag_fetch(uint32_t bar, uint32_t cp, const unsigned int* f) {
  asm volatile("{\n.reg .pred p;\nelect.sync _|p, 0xffffffff;\n@p mbarrier.expect_tx.relaxed.cta.shared::cta.b64 [%2], 64;\n"
               "@p cp.async.bulk.shared::cluster.global.mbarrier::complete_tx::bytes [%0], [%1], 64, [%2];\n}\n"
               ::"r"(cp), "l"(f), "r"(bar + 128) : "memory");
}
__device__ __forceinline__ void src_wait_async(uint32_t bar, uint32_t cp, const unsigned int* f, unsigned int target, int kb, uint32_t& ready, int lane) {
  uint32_t n = 0;
#pragma unroll 1
  while (true) {
    ready |= __ballot_sync(0xffffffffu, (int)(lds_vol(cp + (lane & 15) * 4) - target) >= 0);
    if ((ready >> kb) & 1) break;
    if (n > (1u << 20)) { g_err = 5u; break; }
    if ((n++ & PMOD) == 0) flag_fetch(bar, cp, f);
    __nanosleep(PSL);
  }
}

__device__ __forceinline__ int kblock0(int i, int g) {
  const int j = i >> 1, p = max(g, NCOM) + j - NCOM;
  return (j < NCOM ? j : p < 8 ? p : p - 8 + NCOM) * 2 + (i & 1);
}

__device__ __forceinline__ int wo_kblock(int m, int g) { return (2 * g + (int)((WOORD >> (4 * m)) & 15)) & 15; }

__global__ void __cluster_dims__(2, 1, 1) __launch_bounds__(384, 1)
mega_kernel(const __grid_constant__ CUtensorMap tm_x0, const __grid_constant__ CUtensorMap tm_x,
            const __grid_constant__ CUtensorMap tm_o,
            const __grid_constant__ CUtensorMap tm_wA, const __grid_constant__ CUtensorMap tm_wB,
            const __grid_constant__ CUtensorMap tm_woA, const __grid_constant__ CUtensorMap tm_woB,
                        const bf16* __restrict__ wB, const bf16* __restrict__ wphi, bf16* __restrict__ out) {
  extern __shared__ uint8_t smem_raw[];
  const uint32_t sb = (smem_u32(smem_raw) + 1023u) & ~1023u;
  const uint32_t bar = sb + SM_BAR;
  const int warp = __shfl_sync(0xffffffffu, threadIdx.x >> 5, 0), lane = threadIdx.x & 31;
  if (blockIdx.x >= 128) {
    const int xb = blockIdx.x - 128;
    const int ch = threadIdx.x % 96, rg = threadIdx.x / 96, gg = xb * 2 + ch / 48, sec = (ch % 48) >> 4;
    const uint4* src = reinterpret_cast<const uint4*>(wB + (size_t)rg * 3072 + (sec == 2 ? 0 : 1024 + sec * 1024) + gg * 128 + (ch & 15) * 8);
    float s[8] = {0.f, 0.f, 0.f, 0.f, 0.f, 0.f, 0.f, 0.f};
#pragma unroll 1
    for (int r0 = 0; r0 < 256; r0 += 32) {
      uint4 v[32];
#pragma unroll
      for (int r = 0; r < 32; ++r) v[r] = __ldg(src + (size_t)(r0 + r) * 1536);
#pragma unroll
      for (int r = 0; r < 32; ++r) {
        s[0] += bf_lo(v[r].x); s[1] += bf_hi(v[r].x); s[2] += bf_lo(v[r].y); s[3] += bf_hi(v[r].y);
        s[4] += bf_lo(v[r].z); s[5] += bf_hi(v[r].z); s[6] += bf_lo(v[r].w); s[7] += bf_hi(v[r].w);
      }
    }
    float* cd = g_cs + (ld_relaxed(&g_epoch) & 1) * 6144 + 3072 + xb * 768 + ch * 8;
    red_add4(cd, s[0], s[1], s[2], s[3]);
    red_add4(cd + 4, s[4], s[5], s[6], s[7]);
    nbar<1, 384>();
    if (threadIdx.x < 2) flag_add(&g_csflag[8 + xb * 2 + threadIdx.x].v);
    return;
  }
  const int bid = blockIdx.x;
  const int cr = bid & 1;
  const int g = (bid >> 1) & 7;
  const int rb = (bid >> 4) * 2 + cr;
  const int m0 = rb * 128;

  if (warp < 4) {
    asm volatile("setmaxnreg.dec.sync.aligned.u32 40;");
    asm volatile("barrier.cluster.arrive.relaxed.aligned;" ::: "memory");
    const unsigned int epoch = warp ? ld_relaxed(&g_epoch) : 0u;
    if (warp) cluster_wait();
    unsigned int xbase = epoch * NLAYERS;
    auto wo_a = [&](int layer, int m1) {
      uint64_t ts = ((layer & 1) ? WO_A1 : WO_A0) >> (4 * m1), td = ((layer & 1) ? WO_DA1 : WO_DA0) >> (4 * m1), tk = WOORD >> (4 * m1);
      uint32_t ready = 0u;
#pragma unroll 1
      for (int m = m1; m < 16; m += AW) {
        const int kb = (2 * g + (uint32_t)tk) & 15;
        uint32_t dst = sb + ((uint32_t)ts & 15) * SLOT, fb = bar + B_FULLT + m * 8, eb = bar + B_CONS + ((uint32_t)td & 15) * 8;
        int kc = kb * 64;
        ts >>= 4 * AW; td >>= 4 * AW; tk >>= 4 * AW;
        asm volatile("" : "+r"(dst), "+r"(fb), "+r"(eb), "+r"(kc));
        bool fr = false;
        if (!((ready >> kb) & 1)) {
          PROFT(m == 2 && lane == 0, 64 + layer * 16 + 2);
          if (EP && m > EP) src_wait_async(bar, bar + B_FLG, g_of + rb * 32, xbase + layer + 1, kb, ready, lane);
          else fr = src_wait_tma(g_of + rb * 32, xbase + layer + 1, 1u << kb, ready, lane, eb, layer & 1);
          fence_async_all();
        }
        if (!fr) mbar_wait_u(eb, layer & 1);
        tma_2d_e(dst, &tm_o, kc, m0, fb);
        if (EP && m >= EP && (ready & 0xFFFFu) != 0xFFFFu) flag_fetch(bar, bar + B_FLG, g_of + rb * 32);
        PROFT(lane == 0 && layer == PL, 176 + m);
      }
    };
    auto wo_w = [&](int layer) {
      const CUtensorMap* tx = layer == 0 ? &tm_x0 : &tm_x;
      const CUtensorMap* two = (layer & 1) ? &tm_woB : &tm_woA;
      uint64_t ts = (layer & 1) ? WO_B1 : WO_B0, td = (layer & 1) ? WO_DB1 : WO_DB0, tk = WOORD;
      uint32_t pb = 0;
      fence_async_all();
      mbar_wait_u(bar + B_R0, layer & 1);
      expect_tx_e(bar + B_XOLD, 16384);
      tma_2d_e(sb + (XS + 1) * SLOT, tx, g * 128, m0, bar + B_XOLD);
#pragma unroll 1
      for (int m = 0; m < 16; ++m) {
        uint32_t dst = sb + ((uint32_t)ts & 15) * SLOT + cr * 8192, fb = bar + B_FULLT + m * 8, eb = bar + B_CONS + ((uint32_t)td & 15) * 8;
        int kc = ((2 * g + (uint32_t)tk) & 15) * 64;
        ts >>= 4; td >>= 4; tk >>= 4;
        asm volatile("" : "+r"(dst), "+r"(fb), "+r"(eb), "+r"(kc));
        if (eb != pb) mbar_wait_u(eb, layer & 1);
        pb = eb;
        tma_2d_mc_e(dst, two, g * 128 + cr * 64, kc, fb);
        expect_tx_e(fb, m < 2 ? 16384 : 32768);
        PROFT(lane == 0 && layer == PL, 144 + m);
        if (m == ((layer & 1) ? XB2 : 0)) {
          expect_tx_e(bar + B_XOLD2, 16384);
          tma_2d_e(sb + XS * SLOT, tx, g * 128 + 64, m0, bar + B_XOLD2);
        }
      }
    };
    if (warp == 0) {
      cluster_wait();
      PROFT(lane == 0, 125);
#pragma unroll 1
      for (int layer = 0; layer < NLAYERS; ++layer) {
        const CUtensorMap* tx = layer == 0 ? &tm_x0 : &tm_x;
        const CUtensorMap* tw = (layer & 1) ? &tm_wB : &tm_wA;
        uint32_t s = layer == 0, u = 0, ready = layer == 0 ? 0xFFFFu : 0u;
#pragma unroll 1
        for (int i = s; i < 16; ++i) {
          const int kb = layer == 0 ? kblock0(i, g) : wo_kblock(i, g), kc = kb * 64;
          const uint32_t fb = bar + B_FULLS + s * 8;
          const uint32_t kd = sb + (((QK >> (4 * s)) & 15) + cr) * SLOT, qd = sb + ((QQ >> (4 * s)) & 15) * SLOT + cr * 8192;
          const uint32_t need = 1u << kb;
          const bool ext = i >= 2 || layer == 0, early = ext && (ready & need) == need;
          mbar_wait_u(bar + B_EMPTYS + s * 8, (u + (s ? layer : 0) + 1) & 1);
          if (early) tma_2d_e(sb + ((QA >> (4 * s)) & 15) * SLOT, tx, kc, m0, fb);
          tma_2d_mc_e(kd, tw, 1024 + cr * 1024 + g * 128, kc, fb);
          tma_2d_mc_e(kd + 8192, tw, 1024 + cr * 1024 + g * 128 + 64, kc, fb);
          tma_2d_mc_e(qd, tw, g * 128 + cr * 64, kc, fb);
          expect_tx_e(fb, ext ? 65536 : 49152);
          PROFT(lane == 0 && layer == 0 && i == 1, 31);
          if (layer == 0 && g >= NCOM && i == XPF + (((g - NCOM) * XPM) >> 2)) {
            if (i <= 2) mbar_wait_u(bar + B_FULLS, 0);
            tma_pf_e(&tm_x0, g * 128, m0);
            tma_pf_e(&tm_x0, g * 128 + 64, m0);
          }
          if (layer < 2 && i >= PFS) {
            const int j = i - PFS;
            if (j < 2) tma_pf_e(layer ? &tm_woB : &tm_woA, g * 128 + j * 64, rb * 64);
            else if (j < 8 && layer == 0) tma_pf_e(&tm_wB, ((j >> 1) - 1) * 1024 + g * 128 + (j & 1) * 64, rb * 64);
          }
          if (ext && !early) {
            PROFT(i == 2 && lane == 0, 64 + layer * 16 + 0);
            src_wait_tma(g_xf + rb * 32, xbase + layer + 1, need, ready, lane, fb, 0);
            PROFT(i == 2 && lane == 0, 64 + layer * 16 + 1);
            fence_async_all();
            tma_2d_e(sb + ((QA >> (4 * s)) & 15) * SLOT, tx, kc, m0, fb);
          }
          if (++s == 3) { s = 0; ++u; }
        }
        if (layer == 0) xbase = ld_relaxed(&g_epoch) * NLAYERS;
        if (PG & 1) mbar_wait_u(bar + B_OH1, layer & 1);
        if (PG & 4) mbar_wait_u(bar + B_E3, layer & 1);
        wo_a(layer, 2);
      }
    } else {
      if (warp >= 2) {
        const int h2 = threadIdx.x - 64;
        if (h2 < 16) sts_f(sb + SM_RS + h2 * 4, 0.f);
        if (h2 < 16) sts_f(bar + B_FLG + h2 * 4, __uint_as_float(xbase));
        mbar_wait_u(bar + B_FULLS, 0);
        colsum(&tm_wA, g_cs + (epoch & 1) * 6144, rb, g, warp - 2, 2, lane, warp == 2 ? sb + SM_SD : (sb + SM_BP + 1023u) & ~1023u, bar + B_CB + (warp - 2) * 8, 0);
#pragma unroll 1
        for (int i = h2; i < 320; i += 64) g_kv[(g * 16 + rb) * 320 + i] = make_uint4(0u, 0u, 0u, 0u);
        fence_async_all();
        nbar<5, 64>();
        if (h2 == 0) flag_add(&g_csflag[g].v);
        PROFT(h2 == 0, 242);
#pragma unroll 1
        for (int i = h2; i < 512; i += 256) {
          uint4 w[4];
#pragma unroll
          for (int j = 0; j < 4; ++j) w[j] = __ldg(reinterpret_cast<const uint4*>(wphi + (size_t)g * 4096) + i + j * 64);
#pragma unroll
          for (int j = 0; j < 4; ++j) sts128(sb + SM_WPHI + ((i >> 2) + j * 16) * 80 + (i & 3) * 16, w[j]);
        }
      }
      if (warp == 1) {
        if (lane >= 27) {
          const CUtensorMap* tm = lane == 27 ? &tm_o : lane == 28 ? &tm_wB : lane == 29 ? &tm_woA : lane == 30 ? &tm_woB : &tm_x;
          asm volatile("prefetch.tensormap [%0];" ::"l"(tm) : "memory");
        }
        __syncwarp();
        {
#pragma unroll 1
          for (int e = 0;; ++e) {
            if (e > 0 && e < NLAYERS) {
              mbar_wait_u(bar + B_XH0, (e - 1) & 1);
              flag_set_x(g_xf + rb * 32 + 2 * g, xbase + e + 1, UNS & 1);
            }
            mbar_wait_u(bar + B_XDONE, e & 1);
            PROFT(e < 4, 64 + e * 16 + 4);
            if (e == NLAYERS) {
              if (bid == 0) g_epoch = epoch + 1;
              break;
            }
            PROFT(e < 4, 64 + e * 16 + 5);
            flag_set(g_xf + rb * 32 + 2 * g + 1, xbase + e + 1);
            PROFT(e < 4, 64 + e * 16 + 7);
            if ((e & 1) == 0) {
#pragma unroll 1
              for (int hp = 0; hp < 2; ++hp) {
                uint4* kvl = g_kv + ((g * 2 + (e >> 1)) * 2 + hp) * 1280;
                mbar_wait_u(bar + B_KVDONE - hp * 32, (e >> 1) & 1);
                PROFT(e == PL, 243 + hp * 4);
                bulk_red_add_e(kvl + rb * 64, sb + (3 + hp) * SLOT + rb * 1024, 16384 - rb * 1024);
                if (rb) bulk_red_add_e(kvl, sb + (3 + hp) * SLOT, rb * 1024);
                bulk_red_add_e(kvl + 1024, sb + (6 + hp) * SLOT, 2048);
                bulk_red_add_e(kvl + 1152, sb + (6 + hp) * SLOT + 8192, 2048);
                bulk_commit();
                PROFT(e < 4, 64 + e * 16 + 6);
              }
              bulk_wait_read0();
              __syncwarp();
              if (lane < 2) release2(bar + B_E1);
              __syncwarp();
            }
            mbar_wait_u(bar + B_OH1, e & 1);
            PROFT(e == PL, 251);
            flag_set_x(g_of + rb * 32 + 2 * g, xbase + e + 1, UNS & 2);
            PROFT(e < 4, 64 + e * 16 + 9);
            mbar_wait_u(bar + B_ODONE, e & 1);
            PROFT(e < 4, 64 + e * 16 + 8);
            flag_set_x(g_of + rb * 32 + 2 * g + 1, xbase + e + 1, UNS & 4);
            PROFT(e < 4, 64 + e * 16 + 11);
          }
        }
      } else {
        const int h2 = threadIdx.x - 64;
        const float* cs = g_cs + (epoch & 1) * 6144;
#pragma unroll 1
        for (int layer = 0; layer < NLAYERS; ++layer) {
          if (warp == 2 && layer < 2) {
            if ((PG & 2) && layer) mbar_wait_u(bar + B_XH0, 0);
            if (lane == 0) flag_wait_t<CSLP>(&g_csflag[layer * 8 + g].v, (epoch + 1) * (16u + layer));
            __syncwarp();
            float4 a[3];
#pragma unroll
            for (int i = 0; i < 3; ++i) a[i] = __ldcg(reinterpret_cast<const float4*>(cs + layer * 3072 + g * 384) + i * 32 + lane);
#pragma unroll 1
            for (int i = 0; i < 3; ++i) {
              const float av[4] = {a[0].x, a[0].y, a[0].z, a[0].w};
              a[0] = a[1]; a[1] = a[2];
#pragma unroll
              for (int j = 0; j < 4; ++j) {
                const float c1 = bf16r(av[j]), c2 = bf16r(av[j] - c1), c3 = (av[j] - c1) - c2;
                sts128(sb + SM_BP + layer * 6144 + ((i * 32 + lane) * 4 + j) * 16, make_uint4(pack_bf16(c1, c2), pack_bf16(c3, 0.f), 0u, 0u));
              }
            }
            fence_async_smem();
            __syncwarp();
            if (lane == 0) mbar_arrive(bar + (layer ? B_CS2 : B_CS));
            PROFT(lane == 0, 64 + layer * 16 + 12);
            if (layer == 0) {
              uint4* hz = g_halo + (rb * 8 + g) * 1024;
#pragma unroll 2
              for (int i = lane; i < 1024; i += 32) hz[i] = make_uint4(0u, 0u, 0u, 0u);
              if (lane < 12) reinterpret_cast<float4*>(g_cs + ((epoch & 1) ^ 1) * 6144 + bid * 48)[lane] = make_float4(0.f, 0.f, 0.f, 0.f);
              g_stats[(2 + (lane >> 4)) * S_ + m0 + g * 16 + (lane & 15)] = make_float2(0.f, 0.f);
              __syncwarp();
              if (lane == 0) flag_add(&g_csflag[8 + g].v);
            }
          }
          if (warp == 3) {
            const bool hal = (layer & 1) && rb > 0;
            {
              uint32_t rdy = 0u;
              src_wait<256>(g_xf + rb * 32, xbase + layer + 1, 0xAAAAu, rdy, lane);
              rdy = 0u;
              if (hal) src_wait<256>(g_xf + (rb - 1) * 32, xbase + layer + 1, 0xAAAAu, rdy, lane);
            }
            float2 u[5];
            const float2* sp = g_stats + layer * S_ + m0 + lane;
#pragma unroll
            for (int i = 0; i < 4; ++i) u[i] = __ldcg(sp + i * 32);
            u[4] = __ldcg(hal ? sp - 16 : sp);
            if (layer == 3) g_stats[(lane >> 4) * S_ + m0 + g * 16 + (lane & 15)] = make_float2(0.f, 0.f);
#pragma unroll 1
            for (int i = 0; i < (hal ? 5 : 4); ++i) {
              const int r = i < 4 ? 16 + i * 32 + lane : lane;
              const float sum = u[0].x, sq = u[0].y;
              u[0] = u[1]; u[1] = u[2]; u[2] = u[3]; u[3] = u[4];
              const float mean = sum * (1.f / D_);
              const float var = fmaxf(fmaf(-sum, mean, sq) * (1.f / D_), 0.f);
              const float sd = bf16r(sqrtf(bf16r(bf16r(var) + 1e-5f)));
              sts_f(sb + SM_RS + r * 4, 1.f / sd);
              if (i < 4) {
                const float hm = -0.5f * bf16r(mean);
                const uint32_t s2 = pack_bf16(sd, sd);
                if (!(layer & 1)) sts128(sb + SM_SD + (r - 16) * 64 + ((r >> 1) & 3) * 16, make_uint4(s2, s2, s2, s2));
                sts128(sb + SM_AP + (r - 16) * 16, make_uint4(pack_bf16(hm, hm), pack_bf16(hm, 0.f), 0u, 0u));
              }
            }
            fence_async_smem();
            __syncwarp();
            if (lane == 0) mbar_arrive(bar + B_STAT);
            PROFT(lane == 0, 64 + layer * 16 + 14);
            wo_w(__shfl_sync(0xffffffffu, layer, 0));
          }
        }
      }
    }
    __syncwarp();
    asm volatile("barrier.cluster.arrive.relaxed.aligned;\nbarrier.cluster.wait.aligned;\n" ::: "memory");
  } else {
    if (warp == 5) {
      if (lane == 0) {
        mbar_init(bar + B_FULLS, 1);
        asm volatile("fence.mbarrier_init.release.cluster;" ::: "memory");
      }
      __syncwarp();
      expect_tx_e(bar + B_FULLS, 65536);
      tma_2d_e(sb + XS * SLOT, &tm_x0, 0, m0, bar + B_FULLS);
#pragma unroll
      for (int j = 0; j < 6; ++j)
        tma_2d_e(sb + (j < 4 ? j + 4 : j - 2) * 8192, &tm_wA, (j < 4 ? 1024 + (j >> 1) * 1024 : 0) + g * 128 + (j & 1) * 64, 0, bar + B_FULLS);
      PROFT(lane == 0, 241);
    }
    if (lane < 8 && warp != 5 && threadIdx.x != 128) {
      const int i = (warp - 4) * 8 + lane;
      mbar_init(bar + i * 8, i < 32 ? 1u << ((BAR_CNT >> (2 * i)) & 3) : i < 48 ? 1u : (i == 59 || i == 60) ? 16u : i < 63 ? 4u : 8u);
      asm volatile("fence.mbarrier_init.release.cluster;" ::: "memory");
    }
    __syncwarp();
    asm volatile("barrier.cluster.arrive.relaxed.aligned;" ::: "memory");
    asm volatile("setmaxnreg.inc.sync.aligned.u32 232;");
    cluster_wait();
    PROFT(threadIdx.x == 128, 0);
    Ctx c; c.sb = sb; c.g = g; c.rb = rb; c.cu = warp - 4; c.out = out;
    consumer(c);
    asm volatile("bar.warp.sync 0xffffffff;\nbarrier.cluster.arrive.relaxed.aligned;\nbarrier.cluster.wait.aligned;\n" ::: "memory");
  }
}

typedef CUresult (*PFN_encodeTiled)(CUtensorMap*, CUtensorMapDataType, cuuint32_t, void*, const cuuint64_t*, const cuuint64_t*,
                                    const cuuint32_t*, const cuuint32_t*, CUtensorMapInterleave, CUtensorMapSwizzle,
                                    CUtensorMapL2promotion, CUtensorMapFloatOOBfill);

static CUtensorMap make_map(PFN_encodeTiled enc, const void* ptr, uint64_t cols, uint64_t rows, uint32_t box_c, uint32_t box_r, uint32_t nb = 1) {
  CUtensorMap m;
  cuuint64_t dims[3] = {nb > 1 ? box_c : cols, rows, cols / box_c};
  cuuint64_t strides[2] = {cols * 2, box_c * 2};
  cuuint32_t box[3] = {box_c, box_r, nb};
  cuuint32_t es[3] = {1, 1, 1};
  CUresult r = enc(&m, CU_TENSOR_MAP_DATA_TYPE_BFLOAT16, nb > 1 ? 3 : 2, const_cast<void*>(ptr), dims, strides, box, es, CU_TENSOR_MAP_INTERLEAVE_NONE,
      CU_TENSOR_MAP_SWIZZLE_128B, CU_TENSOR_MAP_L2_PROMOTION_L2_256B, CU_TENSOR_MAP_FLOAT_OOB_FILL_NONE);
  (void)r;
  return m;
}

extern "C" void kernel_launch(void* const* d_in, const int* in_sizes, int n_in, void* d_out, int out_size) {
  const bf16* A_x = (const bf16*)d_in[0];
  const bf16* A_wqkv = (const bf16*)d_in[1];
  const bf16* A_wphi = (const bf16*)d_in[2];
  const bf16* A_wo = (const bf16*)d_in[3];
  const bf16* B_wqkv = (const bf16*)d_in[5];
  const bf16* B_wo = (const bf16*)d_in[6];
  bf16* out = (bf16*)d_out;

  static PFN_encodeTiled enc = nullptr;
  static bf16 *p_x, *p_o;
  if (!enc) {
    void* fn = nullptr; cudaDriverEntryPointQueryResult qr;
    cudaGetDriverEntryPoint("cuTensorMapEncodeTiled", &fn, cudaEnableDefault, &qr);
    enc = (PFN_encodeTiled)fn;
    cudaGetSymbolAddress((void**)&p_x, g_x);
    cudaGetSymbolAddress((void**)&p_o, g_o);
    cudaFuncSetAttribute(mega_kernel, cudaFuncAttributeMaxDynamicSharedMemorySize, SM_TOTAL);
  }
  CUtensorMap tm_x0 = make_map(enc, A_x, 1024, 2048, 64, 128);
  CUtensorMap tm_x = make_map(enc, p_x, 1024, 2048, 64, 128);
  CUtensorMap tm_o = make_map(enc, p_o, 1024, 2048, 64, 128);
  CUtensorMap tm_wA = make_map(enc, A_wqkv, 3072, 1024, 64, 64);
  CUtensorMap tm_wB = make_map(enc, B_wqkv, 3072, 1024, 64, 64);
  CUtensorMap tm_woA = make_map(enc, A_wo, 1024, 1024, 64, 64);
  CUtensorMap tm_woB = make_map(enc, B_wo, 1024, 1024, 64, 64);
  mega_kernel<<<128 + NX, 384, SM_TOTAL, cudaStreamPerThread>>>(tm_x0, tm_x, tm_o, tm_wA, tm_wB, tm_woA, tm_woB,
                                                           B_wqkv, A_wphi, out);
}
```

```cpp
#include <cuda_runtime.h>
#include <cuda_bf16.h>
#include <cuda.h>
#include <stdint.h>

typedef __nv_bfloat16 bf16;

constexpr int S_ = 2048, D_ = 1024;

struct __align__(128) Flag { unsigned int v; unsigned int pad[31]; };
__device__ __align__(1024) bf16 g_x[S_ * D_];
__device__ __align__(1024) bf16 g_o[S_ * D_];
__device__ __align__(1024) uint4 g_halo[128 * 2 * 512];
__device__ __align__(1024) uint4 g_kv[8 * 2 * 2 * 1280];
__device__ __align__(1024) float2 g_stats[4 * S_];
__device__ __align__(1024) float g_cs[2 * 2 * 3072];
__device__ Flag g_csflag[16];
__device__ __align__(128) unsigned int g_xf[16 * 32], g_of[16 * 32];
__device__ unsigned int g_epoch, g_err;
#define PROFT(cond, idx) asm volatile("" ::: "memory")

__device__ __forceinline__ uint32_t smem_u32(const void* p) { return (uint32_t)__cvta_generic_to_shared(p); }
__device__ __forceinline__ void mbar_init(uint32_t bar, uint32_t count) {
  asm volatile("mbarrier.init.shared::cta.b64 [%0], %1;" ::"r"(bar), "r"(count) : "memory");
}
__device__ __forceinline__ void mbar_expect_tx(uint32_t bar, uint32_t bytes) {
  asm volatile("mbarrier.arrive.expect_tx.shared::cta.b64 _, [%0], %1;" ::"r"(bar), "r"(bytes) : "memory");
}
__device__ __forceinline__ void mbar_arrive(uint32_t bar) {
  asm volatile("mbarrier.arrive.shared::cta.b64 _, [%0];" ::"r"(bar) : "memory");
}
__device__ __forceinline__ bool mbar_try_wait(uint32_t bar, uint32_t parity) {
  uint32_t ok;
  asm volatile("{\n.reg .pred p;\nmbarrier.try_wait.parity.shared::cta.b64 p, [%1], %2;\nselp.b32 %0, 1, 0, p;\n}\n"
               : "=r"(ok) : "r"(bar), "r"(parity) : "memory");
  return ok != 0;
}
__device__ __forceinline__ bool mbar_test_wait(uint32_t bar, uint32_t parity) {
  uint32_t ok;
  asm volatile("{\n.reg .pred p;\nmbarrier.test_wait.parity.shared::cta.b64 p, [%1], %2;\nselp.b32 %0, 1, 0, p;\n}\n"
               : "=r"(ok) : "r"(bar), "r"(parity) : "memory");
  return ok != 0;
}
__device__ __forceinline__ uint64_t gtimer() {
  uint64_t t; asm volatile("mov.u64 %0, %globaltimer;" : "=l"(t)); return t;
}
__device__ __forceinline__ void mbar_wait(uint32_t bar, uint32_t parity) {
  uint32_t n = 0;
#pragma unroll 1
  while (!mbar_try_wait(bar, parity)) {
    if (++n > (1u << 22)) { g_err = 1u; break; }
  }
}
__device__ __forceinline__ unsigned int ld_acquire(const unsigned int* p) {
  unsigned int v; asm volatile("ld.acquire.gpu.global.u32 %0, [%1];" : "=r"(v) : "l"(p) : "memory"); return v;
}
__device__ __forceinline__ void flag_add(unsigned int* p) {
  asm volatile("red.release.gpu.global.add.u32 [%0], 1;" ::"l"(p) : "memory");
}
__device__ __forceinline__ void flag_set(unsigned int* p, unsigned int v) {
  asm volatile("st.release.gpu.global.u32 [%0], %1;" ::"l"(p), "r"(v) : "memory");
}
__device__ __forceinline__ void flag_set_x(unsigned int* p, unsigned int v, bool rlx) {
  if (rlx) asm volatile("st.relaxed.gpu.global.u32 [%0], %1;" ::"l"(p), "r"(v) : "memory"); else flag_set(p, v);
}
template <int SLEEP>
__device__ __forceinline__ void src_wait(const unsigned int* f, unsigned int target, uint32_t need, uint32_t& ready, int lane) {
  uint32_t n = 0;
#pragma unroll 1
  while ((ready & need) != need) {
    const unsigned int v = ld_acquire(f + (lane & 15));
    ready = __ballot_sync(0xffffffffu, (int)(v - target) >= 0);
    if (SLEEP) { if ((ready & need) != need) __nanosleep(SLEEP); }
    if (++n > (1u << 20)) { g_err = 3u; break; }
  }
  __syncwarp();
}
__device__ __forceinline__ unsigned int ld_relaxed(const unsigned int* p) {
  unsigned int v; asm volatile("ld.relaxed.gpu.global.u32 %0, [%1];" : "=r"(v) : "l"(p) : "memory"); return v;
}
__device__ __forceinline__ bool src_wait_tma(const unsigned int* f, unsigned int target, uint32_t need, uint32_t& ready, int lane, uint32_t eb, uint32_t par) {
  uint32_t n = 0;
  bool fr = false;
#pragma unroll 1
  while ((ready & need) != need) {
    const unsigned int v = ld_acquire(f + (lane & 15));
    fr = __all_sync(0xffffffffu, mbar_test_wait(eb, par));
    ready = __ballot_sync(0xffffffffu, (int)(v - target) >= 0);
    if (++n > (1u << 20)) { g_err = 3u; break; }
  }
  return fr;
}
__device__ __forceinline__ uint4 ld_relaxed4(const uint4* p) {
  uint4 v; asm volatile("ld.relaxed.gpu.global.v4.u32 {%0,%1,%2,%3}, [%4];" : "=r"(v.x), "=r"(v.y), "=r"(v.z), "=r"(v.w) : "l"(p) : "memory"); return v;
}
__device__ __forceinline__ void st_relaxed4(uint4* p, uint32_t a, uint32_t b, uint32_t c, uint32_t d) {
  asm volatile("st.relaxed.gpu.global.v4.u32 [%0], {%1,%2,%3,%4};" ::"l"(p), "r"(a), "r"(b), "r"(c), "r"(d) : "memory");
}
template <int SLEEP>
__device__ __forceinline__ void flag_wait_t(const unsigned int* p, unsigned int target) {
  uint32_t n = 0;
#pragma unroll 1
  while ((int)(ld_acquire(p) - target) < 0) {
    if (SLEEP) __nanosleep(SLEEP);
    if (++n > (1u << 20)) { g_err = 2u; break; }
  }
}
__device__ __forceinline__ void flag_wait(const unsigned int* p, unsigned int target) { flag_wait_t<0>(p, target); }
__device__ __forceinline__ void flag_wait_slow(const unsigned int* p, unsigned int target) { flag_wait_t<256>(p, target); }
__device__ __forceinline__ void tma_load_2d(uint32_t dst, const CUtensorMap* tm, int c0, int c1, uint32_t bar) {
  asm volatile("cp.async.bulk.tensor.2d.shared::cluster.global.mbarrier::complete_tx::bytes [%0], [%1, {%2, %3}], [%4];"
               ::"r"(dst), "l"(tm), "r"(c0), "r"(c1), "r"(bar) : "memory");
}
__device__ __forceinline__ void tma_load_2d_mc(uint32_t dst, const CUtensorMap* tm, int c0, int c1, uint32_t bar, uint16_t mask) {
  asm volatile("cp.async.bulk.tensor.2d.shared::cluster.global.mbarrier::complete_tx::bytes.multicast::cluster [%0], [%1, {%2, %3}], [%4], %5;"
               ::"r"(dst), "l"(tm), "r"(c0), "r"(c1), "r"(bar), "h"(mask) : "memory");
}
__device__ __forceinline__ void mbar_wait_u(uint32_t bar, uint32_t parity) {
  uint32_t n = 0;
#pragma unroll 1
  while (!__all_sync(0xffffffffu, mbar_try_wait(bar, parity))) {
    if (++n > (1u << 22)) { g_err = 1u; break; }
  }
}
__device__ __forceinline__ void expect_tx_e(uint32_t bar, uint32_t bytes) {
  asm volatile("{\n.reg .pred p;\nelect.sync _|p, 0xffffffff;\n@p mbarrier.arrive.expect_tx.shared::cta.b64 _, [%0], %1;\n}\n" ::"r"(bar), "r"(bytes) : "memory");
}
__device__ __forceinline__ void tma_2d_e(uint32_t dst, const CUtensorMap* tm, int c0, int c1, uint32_t bar) {
  asm volatile("{\n.reg .pred p;\nelect.sync _|p, 0xffffffff;\n"
               "@p cp.async.bulk.tensor.2d.shared::cluster.global.mbarrier::complete_tx::bytes [%0], [%1, {%2, %3}], [%4];\n}\n"
               ::"r"(dst), "l"(tm), "r"(c0), "r"(c1), "r"(bar) : "memory");
}
__device__ __forceinline__ void tma_2d_mc_e(uint32_t dst, const CUtensorMap* tm, int c0, int c1, uint32_t bar) {
  asm volatile("{\n.reg .pred p;\nelect.sync _|p, 0xffffffff;\n"
               "@p cp.async.bulk.tensor.2d.shared::cluster.global.mbarrier::complete_tx::bytes.multicast::cluster [%0], [%1, {%2, %3}], [%4], %5;\n}\n"
               ::"r"(dst), "l"(tm), "r"(c0), "r"(c1), "r"(bar), "h"((uint16_t)3) : "memory");
}
__device__ __forceinline__ void tma_pf_e(const CUtensorMap* tm, int c0, int c1) {
  asm volatile("{\n.reg .pred p;\nelect.sync _|p, 0xffffffff;\n"
               "@p cp.async.bulk.prefetch.tensor.2d.L2.global.tile [%0, {%1, %2}];\n}\n" ::"l"(tm), "r"(c0), "r"(c1) : "memory");
}
__device__ __forceinline__ void tma_2d_to_e(uint32_t dst, const CUtensorMap* tm, int c0, int c1, uint32_t bar, uint32_t mask) {
  asm volatile("{\n.reg .pred p;\nelect.sync _|p, 0xffffffff;\n"
               "@p cp.async.bulk.tensor.2d.shared::cluster.global.mbarrier::complete_tx::bytes.multicast::cluster [%0], [%1, {%2, %3}], [%4], %5;\n}\n"
               ::"r"(dst), "l"(tm), "r"(c0), "r"(c1), "r"(bar), "h"((uint16_t)mask) : "memory");
}
__device__ __forceinline__ void tma_3d_mc_e(uint32_t dst, const CUtensorMap* tm, int c1, int c2, uint32_t bar) {
  asm volatile("{\n.reg .pred p;\nelect.sync _|p, 0xffffffff;\n"
               "@p cp.async.bulk.tensor.3d.shared::cluster.global.mbarrier::complete_tx::bytes.multicast::cluster [%0], [%1, {%6, %2, %3}], [%4], %5;\n}\n"
               ::"r"(dst), "l"(tm), "r"(c1), "r"(c2), "r"(bar), "h"((uint16_t)3), "r"(0) : "memory");
}
__device__ __forceinline__ uint32_t poll_flags(const unsigned int* f, unsigned int target, int lane) {
  const unsigned int v = ld_acquire(f + (lane & 15));
  const uint32_t r = __ballot_sync(0xffffffffu, (int)(v - target) >= 0);
  __syncwarp();
  return r;
}
__device__ __forceinline__ void mbar_arrive_cluster(uint32_t local_bar, uint32_t rank) {
  asm volatile("{\n.reg .b32 ra;\nmapa.shared::cluster.u32 ra, %0, %1;\nmbarrier.arrive.shared::cluster.b64 _, [ra];\n}\n"
               ::"r"(local_bar), "r"(rank) : "memory");
}
__device__ __forceinline__ void release2(uint32_t bar) { mbar_arrive_cluster(bar, 0); mbar_arrive_cluster(bar, 1); }
__device__ __forceinline__ void tma_store_2d(const CUtensorMap* tm, uint32_t src, int c0, int c1) {
  asm volatile("cp.async.bulk.tensor.2d.global.shared::cta.bulk_group [%0, {%2, %3}], [%1];"
               ::"l"(tm), "r"(src), "r"(c0), "r"(c1) : "memory");
}
__device__ __forceinline__ void bulk_store(void* dst, uint32_t src, uint32_t bytes) {
  asm volatile("cp.async.bulk.global.shared::cta.bulk_group [%0], [%1], %2;" ::"l"(dst), "r"(src), "r"(bytes) : "memory");
}
__device__ __forceinline__ void bulk_load(uint32_t dst, const void* src, uint32_t bytes, uint32_t bar) {
  asm volatile("cp.async.bulk.shared::cluster.global.mbarrier::complete_tx::bytes [%0], [%1], %2, [%3];" ::"r"(dst), "l"(src), "r"(bytes), "r"(bar) : "memory");
}
__device__ __forceinline__ void bulk_red_add(void* dst, uint32_t src, uint32_t bytes) {
  asm volatile("cp.reduce.async.bulk.global.shared::cta.bulk_group.add.f32 [%0], [%1], %2;" ::"l"(dst), "r"(src), "r"(bytes) : "memory");
}
__device__ __forceinline__ void bulk_red_add_e(void* dst, uint32_t src, uint32_t bytes) {
  asm volatile("{\n.reg .pred p;\nelect.sync _|p, 0xffffffff;\n@p cp.reduce.async.bulk.global.shared::cta.bulk_group.add.f32 [%0], [%1], %2;\n}\n" ::"l"(dst), "r"(src), "r"(bytes) : "memory");
}
__device__ __forceinline__ void bulk_commit() { asm volatile("cp.async.bulk.commit_group;" ::: "memory"); }
__device__ __forceinline__ void bulk_wait_read0() { asm volatile("cp.async.bulk.wait_group.read 0;" ::: "memory"); }
__device__ __forceinline__ void bulk_wait0() { asm volatile("cp.async.bulk.wait_group 0;" ::: "memory"); }
__device__ __forceinline__ void fence_async_smem() { asm volatile("fence.proxy.async.shared::cta;" ::: "memory"); }
__device__ __forceinline__ void fence_async_all() { asm volatile("fence.proxy.async.global;" ::: "memory"); }
__device__ __forceinline__ void wgmma_fence() { asm volatile("wgmma.fence.sync.aligned;" ::: "memory"); }
__device__ __forceinline__ void wgmma_commit() { asm volatile("wgmma.commit_group.sync.aligned;" ::: "memory"); }
template <int N> __device__ __forceinline__ void wgmma_wait() { asm volatile("wgmma.wait_group.sync.aligned %0;" ::"n"(N) : "memory"); }
__device__ __forceinline__ void cluster_arrive() { asm volatile("barrier.cluster.arrive.release.aligned;" ::: "memory"); }
__device__ __forceinline__ void cluster_wait() { asm volatile("barrier.cluster.wait.acquire.aligned;" ::: "memory"); }
template <int ID, int N> __device__ __forceinline__ void nbar() { asm volatile("bar.sync %0, %1;" ::"n"(ID), "n"(N) : "memory"); }
__device__ __forceinline__ uint64_t make_desc(uint32_t addr, uint32_t lbo_bytes, uint32_t sbo_bytes) {
  uint64_t d = 0;
  d |= (uint64_t)((addr & 0x3FFFF) >> 4);
  d |= (uint64_t)((lbo_bytes >> 4) & 0x3FFF) << 16;
  d |= (uint64_t)((sbo_bytes >> 4) & 0x3FFF) << 32;
  d |= (uint64_t)1 << 62;
  return d;
}
__device__ __forceinline__ uint64_t desc64(uint32_t lo, uint32_t hi) { return (uint64_t)lo | ((uint64_t)hi << 32); }
__device__ __forceinline__ uint32_t pack_bf16(float lo, float hi) {
  uint32_t r; asm("cvt.rn.bf16x2.f32 %0, %1, %2;" : "=r"(r) : "f"(hi), "f"(lo)); return r;
}
__device__ __forceinline__ uint32_t mul_bf16x2(uint32_t a, uint32_t s, bool hi) {
  __nv_bfloat162 x = *reinterpret_cast<__nv_bfloat162*>(&a), y = *reinterpret_cast<__nv_bfloat162*>(&s);
  x = __hmul2(x, hi ? __high2bfloat162(y) : __low2bfloat162(y));
  return *reinterpret_cast<uint32_t*>(&x);
}
__device__ __forceinline__ float bf16r(float x) { return __bfloat162float(__float2bfloat16_rn(x)); }
__device__ __forceinline__ float bf_lo(uint32_t u) { return __uint_as_float(u << 16); }
__device__ __forceinline__ float bf_hi(uint32_t u) { return __uint_as_float(u & 0xFFFF0000u); }
__device__ __forceinline__ float ex2(float x) { float r; asm("ex2.approx.ftz.f32 %0, %1;" : "=f"(r) : "f"(x)); return r; }
__device__ __forceinline__ float rcp(float x) { float r; asm("rcp.approx.ftz.f32 %0, %1;" : "=f"(r) : "f"(x)); return r; }
__device__ __forceinline__ void mma_bf16(float (&d)[4], uint32_t a0, uint32_t a1, uint32_t a2, uint32_t a3, uint32_t b0, uint32_t b1) {
  asm("mma.sync.aligned.m16n8k16.row.col.f32.bf16.bf16.f32 {%0,%1,%2,%3}, {%4,%5,%6,%7}, {%8,%9}, {%0,%1,%2,%3};"
               : "+f"(d[0]), "+f"(d[1]), "+f"(d[2]), "+f"(d[3]) : "r"(a0), "r"(a1), "r"(a2), "r"(a3), "r"(b0), "r"(b1));
}
__device__ __forceinline__ void ldsm_x4(uint32_t& r0, uint32_t& r1, uint32_t& r2, uint32_t& r3, uint32_t addr) {
  asm volatile("ldmatrix.sync.aligned.m8n8.x4.shared.b16 {%0,%1,%2,%3}, [%4];"
               : "=r"(r0), "=r"(r1), "=r"(r2), "=r"(r3) : "r"(addr) : "memory");
}
__device__ __forceinline__ void ldsm_x4_t(uint32_t& r0, uint32_t& r1, uint32_t& r2, uint32_t& r3, uint32_t addr) {
  asm volatile("ldmatrix.sync.aligned.m8n8.x4.trans.shared.b16 {%0,%1,%2,%3}, [%4];"
               : "=r"(r0), "=r"(r1), "=r"(r2), "=r"(r3) : "r"(addr) : "memory");
}
__device__ __forceinline__ void ldsm_x2_t(uint32_t& r0, uint32_t& r1, uint32_t addr) {
  asm volatile("ldmatrix.sync.aligned.m8n8.x2.trans.shared.b16 {%0,%1}, [%2];"
               : "=r"(r0), "=r"(r1) : "r"(addr) : "memory");
}
__device__ __forceinline__ void stsm_x4(uint32_t addr, uint32_t r0, uint32_t r1, uint32_t r2, uint32_t r3) {
  asm volatile("stmatrix.sync.aligned.m8n8.x4.shared.b16 [%0], {%1,%2,%3,%4};"
               ::"r"(addr), "r"(r0), "r"(r1), "r"(r2), "r"(r3) : "memory");
}
__device__ __forceinline__ void stsm_x4_p(bool on, uint32_t addr, uint32_t r0, uint32_t r1, uint32_t r2, uint32_t r3) {
  asm volatile("{\n.reg .pred p;\nsetp.ne.b32 p, %5, 0;\n@p stmatrix.sync.aligned.m8n8.x4.shared.b16 [%0], {%1,%2,%3,%4};\n}\n"
               ::"r"(addr), "r"(r0), "r"(r1), "r"(r2), "r"(r3), "r"((int)on) : "memory");
}
__device__ __forceinline__ float2 lds_f2(uint32_t addr) {
  float2 v; asm volatile("ld.shared.v2.f32 {%0,%1}, [%2];" : "=f"(v.x), "=f"(v.y) : "r"(addr) : "memory"); return v;
}
__device__ __forceinline__ uint4 lds128(uint32_t addr) {
  uint4 v; asm volatile("ld.shared.v4.b32 {%0,%1,%2,%3}, [%4];" : "=r"(v.x), "=r"(v.y), "=r"(v.z), "=r"(v.w) : "r"(addr) : "memory"); return v;
}
__device__ __forceinline__ void sts128(uint32_t addr, uint4 v) {
  asm volatile("st.shared.v4.b32 [%0], {%1,%2,%3,%4};" ::"r"(addr), "r"(v.x), "r"(v.y), "r"(v.z), "r"(v.w) : "memory");
}
__device__ __forceinline__ float lds_f(uint32_t addr) {
  float v; asm volatile("ld.shared.f32 %0, [%1];" : "=f"(v) : "r"(addr) : "memory"); return v;
}
__device__ __forceinline__ uint32_t lds_vol(uint32_t addr) {
  uint32_t v; asm volatile("ld.volatile.shared.u32 %0, [%1];" : "=r"(v) : "r"(addr) : "memory"); return v;
}
__device__ __forceinline__ void sts16(uint32_t addr, uint32_t v) {
  asm volatile("st.shared.u16 [%0], %1;" ::"r"(addr), "h"((unsigned short)v) : "memory");
}
__device__ __forceinline__ void nbar_dyn(int id, int n) { asm volatile("bar.sync %0, %1;" ::"r"(id), "r"(n) : "memory"); }
__device__ __forceinline__ uint64_t make_desc_ns(uint32_t addr, uint32_t lbo_bytes, uint32_t sbo_bytes) {
  return (uint64_t)((addr & 0x3FFFF) >> 4) | ((uint64_t)(lbo_bytes >> 4) << 16) | ((uint64_t)(sbo_bytes >> 4) << 32);
}
__device__ __forceinline__ void sts_f(uint32_t addr, float v) { asm volatile("st.shared.f32 [%0], %1;" ::"r"(addr), "f"(v) : "memory"); }
__device__ __forceinline__ void sts64(uint32_t addr, uint32_t a, uint32_t b) {
  asm volatile("st.shared.v2.b32 [%0], {%1,%2};" ::"r"(addr), "r"(a), "r"(b) : "memory");
}
__device__ __forceinline__ void sts_f2(uint32_t addr, float a, float b) {
  asm volatile("st.shared.v2.f32 [%0], {%1,%2};" ::"r"(addr), "f"(a), "f"(b) : "memory");
}
__device__ __forceinline__ void red_add2(float* p, float a, float b) {
  asm volatile("red.global.add.v2.f32 [%0], {%1,%2};" ::"l"(p), "f"(a), "f"(b) : "memory");
}
__device__ __forceinline__ void red_add4(float* p, float a, float b, float c, float d) {
  asm volatile("red.global.add.v4.f32 [%0], {%1,%2,%3,%4};" ::"l"(p), "f"(a), "f"(b), "f"(c), "f"(d) : "memory");
}
__device__ __forceinline__ void red_add1(float* p, float a) {
  asm volatile("red.global.add.f32 [%0], %1;" ::"l"(p), "f"(a) : "memory");
}
__device__ __forceinline__ void l2_prefetch(const void* p, uint32_t bytes) {
  asm volatile("cp.async.bulk.prefetch.L2.global [%0], %1;" ::"l"(p), "r"(bytes) : "memory");
}

__device__ __forceinline__ void wgmma_n256(float (&d)[192], uint64_t da, uint64_t db, int scale_d) {
  asm volatile("{\n.reg .pred p;\nsetp.ne.b32 p, %130, 0;\n"
    "wgmma.mma_async.sync.aligned.m64n256k16.f32.bf16.bf16 {%0, %1, %2, %3, %4, %5, %6, %7, %8, %9, %10, %11, %12, %13, %14, %15, %16, %17, %18, %19, %20, %21, %22, %23, %24, %25, %26, %27, %28, %29, %30, %31, %32, %33, %34, %35, %36, %37, %38, %39, %40, %41, %42, %43, %44, %45, %46, %47, %48, %49, %50, %51, %52, %53, %54, %55, %56, %57, %58, %59, %60, %61, %62, %63, %64, %65, %66, %67, %68, %69, %70, %71, %72, %73, %74, %75, %76, %77, %78, %79, %80, %81, %82, %83, %84, %85, %86, %87, %88, %89, %90, %91, %92, %93, %94, %95, %96, %97, %98, %99, %100, %101, %102, %103, %104, %105, %106, %107, %108, %109, %110, %111, %112, %113, %114, %115, %116, %117, %118, %119, %120, %121, %122, %123, %124, %125, %126, %127}, %128, %129, p, 1, 1, 0, 1;\n}\n"
    : "+f"(d[0]), "+f"(d[1]), "+f"(d[2]), "+f"(d[3]), "+f"(d[4]), "+f"(d[5]), "+f"(d[6]), "+f"(d[7]), "+f"(d[8]), "+f"(d[9]), "+f"(d[10]), "+f"(d[11]), "+f"(d[12]), "+f"(d[13]), "+f"(d[14]), "+f"(d[15]), "+f"(d[16]), "+f"(d[17]), "+f"(d[18]), "+f"(d[19]), "+f"(d[20]), "+f"(d[21]), "+f"(d[22]), "+f"(d[23]), "+f"(d[24]), "+f"(d[25]), "+f"(d[26]), "+f"(d[27]), "+f"(d[28]), "+f"(d[29]), "+f"(d[30]), "+f"(d[31]), "+f"(d[32]), "+f"(d[33]), "+f"(d[34]), "+f"(d[35]), "+f"(d[36]), "+f"(d[37]), "+f"(d[38]), "+f"(d[39]), "+f"(d[40]), "+f"(d[41]), "+f"(d[42]), "+f"(d[43]), "+f"(d[44]), "+f"(d[45]), "+f"(d[46]), "+f"(d[47]), "+f"(d[48]), "+f"(d[49]), "+f"(d[50]), "+f"(d[51]), "+f"(d[52]), "+f"(d[53]), "+f"(d[54]), "+f"(d[55]), "+f"(d[56]), "+f"(d[57]), "+f"(d[58]), "+f"(d[59]), "+f"(d[60]), "+f"(d[61]), "+f"(d[62]), "+f"(d[63]), "+f"(d[64]), "+f"(d[65]), "+f"(d[66]), "+f"(d[67]), "+f"(d[68]), "+f"(d[69]), "+f"(d[70]), "+f"(d[71]), "+f"(d[72]), "+f"(d[73]), "+f"(d[74]), "+f"(d[75]), "+f"(d[76]), "+f"(d[77]), "+f"(d[78]), "+f"(d[79]), "+f"(d[80]), "+f"(d[81]), "+f"(d[82]), "+f"(d[83]), "+f"(d[84]), "+f"(d[85]), "+f"(d[86]), "+f"(d[87]), "+f"(d[88]), "+f"(d[89]), "+f"(d[90]), "+f"(d[91]), "+f"(d[92]), "+f"(d[93]), "+f"(d[94]), "+f"(d[95]), "+f"(d[96]), "+f"(d[97]), "+f"(d[98]), "+f"(d[99]), "+f"(d[100]), "+f"(d[101]), "+f"(d[102]), "+f"(d[103]), "+f"(d[104]), "+f"(d[105]), "+f"(d[106]), "+f"(d[107]), "+f"(d[108]), "+f"(d[109]), "+f"(d[110]), "+f"(d[111]), "+f"(d[112]), "+f"(d[113]), "+f"(d[114]), "+f"(d[115]), "+f"(d[116]), "+f"(d[117]), "+f"(d[118]), "+f"(d[119]), "+f"(d[120]), "+f"(d[121]), "+f"(d[122]), "+f"(d[123]), "+f"(d[124]), "+f"(d[125]), "+f"(d[126]), "+f"(d[127])
    : "l"(da), "l"(db), "r"(scale_d));
}
__device__ __forceinline__ void wgmma_n128(float (&d)[192], uint64_t da, uint64_t db, int scale_d) {
  asm volatile("{\n.reg .pred p;\nsetp.ne.b32 p, %66, 0;\n"
    "wgmma.mma_async.sync.aligned.m64n128k16.f32.bf16.bf16 {%0, %1, %2, %3, %4, %5, %6, %7, %8, %9, %10, %11, %12, %13, %14, %15, %16, %17, %18, %19, %20, %21, %22, %23, %24, %25, %26, %27, %28, %29, %30, %31, %32, %33, %34, %35, %36, %37, %38, %39, %40, %41, %42, %43, %44, %45, %46, %47, %48, %49, %50, %51, %52, %53, %54, %55, %56, %57, %58, %59, %60, %61, %62, %63}, %64, %65, p, 1, 1, 0, 1;\n}\n"
    : "+f"(d[128]), "+f"(d[129]), "+f"(d[130]), "+f"(d[131]), "+f"(d[132]), "+f"(d[133]), "+f"(d[134]), "+f"(d[135]), "+f"(d[136]), "+f"(d[137]), "+f"(d[138]), "+f"(d[139]), "+f"(d[140]), "+f"(d[141]), "+f"(d[142]), "+f"(d[143]), "+f"(d[144]), "+f"(d[145]), "+f"(d[146]), "+f"(d[147]), "+f"(d[148]), "+f"(d[149]), "+f"(d[150]), "+f"(d[151]), "+f"(d[152]), "+f"(d[153]), "+f"(d[154]), "+f"(d[155]), "+f"(d[156]), "+f"(d[157]), "+f"(d[158]), "+f"(d[159]), "+f"(d[160]), "+f"(d[161]), "+f"(d[162]), "+f"(d[163]), "+f"(d[164]), "+f"(d[165]), "+f"(d[166]), "+f"(d[167]), "+f"(d[168]), "+f"(d[169]), "+f"(d[170]), "+f"(d[171]), "+f"(d[172]), "+f"(d[173]), "+f"(d[174]), "+f"(d[175]), "+f"(d[176]), "+f"(d[177]), "+f"(d[178]), "+f"(d[179]), "+f"(d[180]), "+f"(d[181]), "+f"(d[182]), "+f"(d[183]), "+f"(d[184]), "+f"(d[185]), "+f"(d[186]), "+f"(d[187]), "+f"(d[188]), "+f"(d[189]), "+f"(d[190]), "+f"(d[191])
    : "l"(da), "l"(db), "r"(scale_d));
}
__device__ __forceinline__ void wgmma_n256_k(float (&d)[192], uint64_t da, uint64_t db, int scale_d) {
  asm volatile("{\n.reg .pred p;\nsetp.ne.b32 p, %130, 0;\n"
    "wgmma.mma_async.sync.aligned.m64n256k16.f32.bf16.bf16 {%0, %1, %2, %3, %4, %5, %6, %7, %8, %9, %10, %11, %12, %13, %14, %15, %16, %17, %18, %19, %20, %21, %22, %23, %24, %25, %26, %27, %28, %29, %30, %31, %32, %33, %34, %35, %36, %37, %38, %39, %40, %41, %42, %43, %44, %45, %46, %47, %48, %49, %50, %51, %52, %53, %54, %55, %56, %57, %58, %59, %60, %61, %62, %63, %64, %65, %66, %67, %68, %69, %70, %71, %72, %73, %74, %75, %76, %77, %78, %79, %80, %81, %82, %83, %84, %85, %86, %87, %88, %89, %90, %91, %92, %93, %94, %95, %96, %97, %98, %99, %100, %101, %102, %103, %104, %105, %106, %107, %108, %109, %110, %111, %112, %113, %114, %115, %116, %117, %118, %119, %120, %121, %122, %123, %124, %125, %126, %127}, %128, %129, p, 1, 1, 0, 0;\n}\n"
    : "+f"(d[0]), "+f"(d[1]), "+f"(d[2]), "+f"(d[3]), "+f"(d[4]), "+f"(d[5]), "+f"(d[6]), "+f"(d[7]), "+f"(d[8]), "+f"(d[9]), "+f"(d[10]), "+f"(d[11]), "+f"(d[12]), "+f"(d[13]), "+f"(d[14]), "+f"(d[15]), "+f"(d[16]), "+f"(d[17]), "+f"(d[18]), "+f"(d[19]), "+f"(d[20]), "+f"(d[21]), "+f"(d[22]), "+f"(d[23]), "+f"(d[24]), "+f"(d[25]), "+f"(d[26]), "+f"(d[27]), "+f"(d[28]), "+f"(d[29]), "+f"(d[30]), "+f"(d[31]), "+f"(d[32]), "+f"(d[33]), "+f"(d[34]), "+f"(d[35]), "+f"(d[36]), "+f"(d[37]), "+f"(d[38]), "+f"(d[39]), "+f"(d[40]), "+f"(d[41]), "+f"(d[42]), "+f"(d[43]), "+f"(d[44]), "+f"(d[45]), "+f"(d[46]), "+f"(d[47]), "+f"(d[48]), "+f"(d[49]), "+f"(d[50]), "+f"(d[51]), "+f"(d[52]), "+f"(d[53]), "+f"(d[54]), "+f"(d[55]), "+f"(d[56]), "+f"(d[57]), "+f"(d[58]), "+f"(d[59]), "+f"(d[60]), "+f"(d[61]), "+f"(d[62]), "+f"(d[63]), "+f"(d[64]), "+f"(d[65]), "+f"(d[66]), "+f"(d[67]), "+f"(d[68]), "+f"(d[69]), "+f"(d[70]), "+f"(d[71]), "+f"(d[72]), "+f"(d[73]), "+f"(d[74]), "+f"(d[75]), "+f"(d[76]), "+f"(d[77]), "+f"(d[78]), "+f"(d[79]), "+f"(d[80]), "+f"(d[81]), "+f"(d[82]), "+f"(d[83]), "+f"(d[84]), "+f"(d[85]), "+f"(d[86]), "+f"(d[87]), "+f"(d[88]), "+f"(d[89]), "+f"(d[90]), "+f"(d[91]), "+f"(d[92]), "+f"(d[93]), "+f"(d[94]), "+f"(d[95]), "+f"(d[96]), "+f"(d[97]), "+f"(d[98]), "+f"(d[99]), "+f"(d[100]), "+f"(d[101]), "+f"(d[102]), "+f"(d[103]), "+f"(d[104]), "+f"(d[105]), "+f"(d[106]), "+f"(d[107]), "+f"(d[108]), "+f"(d[109]), "+f"(d[110]), "+f"(d[111]), "+f"(d[112]), "+f"(d[113]), "+f"(d[114]), "+f"(d[115]), "+f"(d[116]), "+f"(d[117]), "+f"(d[118]), "+f"(d[119]), "+f"(d[120]), "+f"(d[121]), "+f"(d[122]), "+f"(d[123]), "+f"(d[124]), "+f"(d[125]), "+f"(d[126]), "+f"(d[127])
    : "l"(da), "l"(db), "r"(scale_d));
}
__device__ __forceinline__ void wgmma_n128_k(float (&d)[192], uint64_t da, uint64_t db, int scale_d) {
  asm volatile("{\n.reg .pred p;\nsetp.ne.b32 p, %66, 0;\n"
    "wgmma.mma_async.sync.aligned.m64n128k16.f32.bf16.bf16 {%0, %1, %2, %3, %4, %5, %6, %7, %8, %9, %10, %11, %12, %13, %14, %15, %16, %17, %18, %19, %20, %21, %22, %23, %24, %25, %26, %27, %28, %29, %30, %31, %32, %33, %34, %35, %36, %37, %38, %39, %40, %41, %42, %43, %44, %45, %46, %47, %48, %49, %50, %51, %52, %53, %54, %55, %56, %57, %58, %59, %60, %61, %62, %63}, %64, %65, p, 1, 1, 0, 0;\n}\n"
    : "+f"(d[128]), "+f"(d[129]), "+f"(d[130]), "+f"(d[131]), "+f"(d[132]), "+f"(d[133]), "+f"(d[134]), "+f"(d[135]), "+f"(d[136]), "+f"(d[137]), "+f"(d[138]), "+f"(d[139]), "+f"(d[140]), "+f"(d[141]), "+f"(d[142]), "+f"(d[143]), "+f"(d[144]), "+f"(d[145]), "+f"(d[146]), "+f"(d[147]), "+f"(d[148]), "+f"(d[149]), "+f"(d[150]), "+f"(d[151]), "+f"(d[152]), "+f"(d[153]), "+f"(d[154]), "+f"(d[155]), "+f"(d[156]), "+f"(d[157]), "+f"(d[158]), "+f"(d[159]), "+f"(d[160]), "+f"(d[161]), "+f"(d[162]), "+f"(d[163]), "+f"(d[164]), "+f"(d[165]), "+f"(d[166]), "+f"(d[167]), "+f"(d[168]), "+f"(d[169]), "+f"(d[170]), "+f"(d[171]), "+f"(d[172]), "+f"(d[173]), "+f"(d[174]), "+f"(d[175]), "+f"(d[176]), "+f"(d[177]), "+f"(d[178]), "+f"(d[179]), "+f"(d[180]), "+f"(d[181]), "+f"(d[182]), "+f"(d[183]), "+f"(d[184]), "+f"(d[185]), "+f"(d[186]), "+f"(d[187]), "+f"(d[188]), "+f"(d[189]), "+f"(d[190]), "+f"(d[191])
    : "l"(da), "l"(db), "r"(scale_d));
}
__device__ __forceinline__ void wgmma_n40_tt(float (&d)[20], uint64_t da, uint64_t db, int scale_d) {
  asm volatile("{\n.reg .pred p;\nsetp.ne.b32 p, %22, 0;\n"
    "wgmma.mma_async.sync.aligned.m64n40k16.f32.bf16.bf16 {%0, %1, %2, %3, %4, %5, %6, %7, %8, %9, %10, %11, %12, %13, %14, %15, %16, %17, %18, %19}, %20, %21, p, 1, 1, 1, 1;\n}\n"
    : "+f"(d[0]), "+f"(d[1]), "+f"(d[2]), "+f"(d[3]), "+f"(d[4]), "+f"(d[5]), "+f"(d[6]), "+f"(d[7]), "+f"(d[8]), "+f"(d[9]), "+f"(d[10]), "+f"(d[11]), "+f"(d[12]), "+f"(d[13]), "+f"(d[14]), "+f"(d[15]), "+f"(d[16]), "+f"(d[17]), "+f"(d[18]), "+f"(d[19])
    : "l"(da), "l"(db), "r"(scale_d));
}
__device__ __forceinline__ void wgmma_n40_rs(float (&d)[20], const uint32_t (&a)[4], uint64_t db, int scale_d) {
  asm volatile("{\n.reg .pred p;\nsetp.ne.b32 p, %25, 0;\n"
    "wgmma.mma_async.sync.aligned.m64n40k16.f32.bf16.bf16 {%0, %1, %2, %3, %4, %5, %6, %7, %8, %9, %10, %11, %12, %13, %14, %15, %16, %17, %18, %19}, {%20, %21, %22, %23}, %24, p, 1, 1, 1;\n}\n"
    : "+f"(d[0]), "+f"(d[1]), "+f"(d[2]), "+f"(d[3]), "+f"(d[4]), "+f"(d[5]), "+f"(d[6]), "+f"(d[7]), "+f"(d[8]), "+f"(d[9]), "+f"(d[10]), "+f"(d[11]), "+f"(d[12]), "+f"(d[13]), "+f"(d[14]), "+f"(d[15]), "+f"(d[16]), "+f"(d[17]), "+f"(d[18]), "+f"(d[19])
    : "r"(a[0]), "r"(a[1]), "r"(a[2]), "r"(a[3]), "l"(db), "r"(scale_d));
}
__device__ __forceinline__ void wgmma_n256_0(float (&d)[192], uint64_t da, uint64_t db) {
  asm volatile("{\n.reg .pred p;\nsetp.ne.b32 p, 0, 0;\n"
    "wgmma.mma_async.sync.aligned.m64n256k16.f32.bf16.bf16 {%0, %1, %2, %3, %4, %5, %6, %7, %8, %9, %10, %11, %12, %13, %14, %15, %16, %17, %18, %19, %20, %21, %22, %23, %24, %25, %26, %27, %28, %29, %30, %31, %32, %33, %34, %35, %36, %37, %38, %39, %40, %41, %42, %43, %44, %45, %46, %47, %48, %49, %50, %51, %52, %53, %54, %55, %56, %57, %58, %59, %60, %61, %62, %63, %64, %65, %66, %67, %68, %69, %70, %71, %72, %73, %74, %75, %76, %77, %78, %79, %80, %81, %82, %83, %84, %85, %86, %87, %88, %89, %90, %91, %92, %93, %94, %95, %96, %97, %98, %99, %100, %101, %102, %103, %104, %105, %106, %107, %108, %109, %110, %111, %112, %113, %114, %115, %116, %117, %118, %119, %120, %121, %122, %123, %124, %125, %126, %127}, %128, %129, p, 1, 1, 0, 1;\n}\n"
    : "=f"(d[0]), "=f"(d[1]), "=f"(d[2]), "=f"(d[3]), "=f"(d[4]), "=f"(d[5]), "=f"(d[6]), "=f"(d[7]), "=f"(d[8]), "=f"(d[9]), "=f"(d[10]), "=f"(d[11]), "=f"(d[12]), "=f"(d[13]), "=f"(d[14]), "=f"(d[15]), "=f"(d[16]), "=f"(d[17]), "=f"(d[18]), "=f"(d[19]), "=f"(d[20]), "=f"(d[21]), "=f"(d[22]), "=f"(d[23]), "=f"(d[24]), "=f"(d[25]), "=f"(d[26]), "=f"(d[27]), "=f"(d[28]), "=f"(d[29]), "=f"(d[30]), "=f"(d[31]), "=f"(d[32]), "=f"(d[33]), "=f"(d[34]), "=f"(d[35]), "=f"(d[36]), "=f"(d[37]), "=f"(d[38]), "=f"(d[39]), "=f"(d[40]), "=f"(d[41]), "=f"(d[42]), "=f"(d[43]), "=f"(d[44]), "=f"(d[45]), "=f"(d[46]), "=f"(d[47]), "=f"(d[48]), "=f"(d[49]), "=f"(d[50]), "=f"(d[51]), "=f"(d[52]), "=f"(d[53]), "=f"(d[54]), "=f"(d[55]), "=f"(d[56]), "=f"(d[57]), "=f"(d[58]), "=f"(d[59]), "=f"(d[60]), "=f"(d[61]), "=f"(d[62]), "=f"(d[63]), "=f"(d[64]), "=f"(d[65]), "=f"(d[66]), "=f"(d[67]), "=f"(d[68]), "=f"(d[69]), "=f"(d[70]), "=f"(d[71]), "=f"(d[72]), "=f"(d[73]), "=f"(d[74]), "=f"(d[75]), "=f"(d[76]), "=f"(d[77]), "=f"(d[78]), "=f"(d[79]), "=f"(d[80]), "=f"(d[81]), "=f"(d[82]), "=f"(d[83]), "=f"(d[84]), "=f"(d[85]), "=f"(d[86]), "=f"(d[87]), "=f"(d[88]), "=f"(d[89]), "=f"(d[90]), "=f"(d[91]), "=f"(d[92]), "=f"(d[93]), "=f"(d[94]), "=f"(d[95]), "=f"(d[96]), "=f"(d[97]), "=f"(d[98]), "=f"(d[99]), "=f"(d[100]), "=f"(d[101]), "=f"(d[102]), "=f"(d[103]), "=f"(d[104]), "=f"(d[105]), "=f"(d[106]), "=f"(d[107]), "=f"(d[108]), "=f"(d[109]), "=f"(d[110]), "=f"(d[111]), "=f"(d[112]), "=f"(d[113]), "=f"(d[114]), "=f"(d[115]), "=f"(d[116]), "=f"(d[117]), "=f"(d[118]), "=f"(d[119]), "=f"(d[120]), "=f"(d[121]), "=f"(d[122]), "=f"(d[123]), "=f"(d[124]), "=f"(d[125]), "=f"(d[126]), "=f"(d[127])
    : "l"(da), "l"(db));
}
__device__ __forceinline__ void wgmma_n128_0(float (&d)[192], uint64_t da, uint64_t db) {
  asm volatile("{\n.reg .pred p;\nsetp.ne.b32 p, 0, 0;\n"
    "wgmma.mma_async.sync.aligned.m64n128k16.f32.bf16.bf16 {%0, %1, %2, %3, %4, %5, %6, %7, %8, %9, %10, %11, %12, %13, %14, %15, %16, %17, %18, %19, %20, %21, %22, %23, %24, %25, %26, %27, %28, %29, %30, %31, %32, %33, %34, %35, %36, %37, %38, %39, %40, %41, %42, %43, %44, %45, %46, %47, %48, %49, %50, %51, %52, %53, %54, %55, %56, %57, %58, %59, %60, %61, %62, %63}, %64, %65, p, 1, 1, 0, 1;\n}\n"
    : "=f"(d[128]), "=f"(d[129]), "=f"(d[130]), "=f"(d[131]), "=f"(d[132]), "=f"(d[133]), "=f"(d[134]), "=f"(d[135]), "=f"(d[136]), "=f"(d[137]), "=f"(d[138]), "=f"(d[139]), "=f"(d[140]), "=f"(d[141]), "=f"(d[142]), "=f"(d[143]), "=f"(d[144]), "=f"(d[145]), "=f"(d[146]), "=f"(d[147]), "=f"(d[148]), "=f"(d[149]), "=f"(d[150]), "=f"(d[151]), "=f"(d[152]), "=f"(d[153]), "=f"(d[154]), "=f"(d[155]), "=f"(d[156]), "=f"(d[157]), "=f"(d[158]), "=f"(d[159]), "=f"(d[160]), "=f"(d[161]), "=f"(d[162]), "=f"(d[163]), "=f"(d[164]), "=f"(d[165]), "=f"(d[166]), "=f"(d[167]), "=f"(d[168]), "=f"(d[169]), "=f"(d[170]), "=f"(d[171]), "=f"(d[172]), "=f"(d[173]), "=f"(d[174]), "=f"(d[175]), "=f"(d[176]), "=f"(d[177]), "=f"(d[178]), "=f"(d[179]), "=f"(d[180]), "=f"(d[181]), "=f"(d[182]), "=f"(d[183]), "=f"(d[184]), "=f"(d[185]), "=f"(d[186]), "=f"(d[187]), "=f"(d[188]), "=f"(d[189]), "=f"(d[190]), "=f"(d[191])
    : "l"(da), "l"(db));
}
__device__ __forceinline__ void wgmma_n64a(float (&d)[192], uint64_t da, uint64_t db, int scale_d) {
  asm volatile("{\n.reg .pred p;\nsetp.ne.b32 p, %34, 0;\n"
    "wgmma.mma_async.sync.aligned.m64n64k16.f32.bf16.bf16 {%0, %1, %2, %3, %4, %5, %6, %7, %8, %9, %10, %11, %12, %13, %14, %15, %16, %17, %18, %19, %20, %21, %22, %23, %24, %25, %26, %27, %28, %29, %30, %31}, %32, %33, p, 1, 1, 0, 1;\n}\n"
    : "+f"(d[128]), "+f"(d[129]), "+f"(d[130]), "+f"(d[131]), "+f"(d[132]), "+f"(d[133]), "+f"(d[134]), "+f"(d[135]), "+f"(d[136]), "+f"(d[137]), "+f"(d[138]), "+f"(d[139]), "+f"(d[140]), "+f"(d[141]), "+f"(d[142]), "+f"(d[143]), "+f"(d[144]), "+f"(d[145]), "+f"(d[146]), "+f"(d[147]), "+f"(d[148]), "+f"(d[149]), "+f"(d[150]), "+f"(d[151]), "+f"(d[152]), "+f"(d[153]), "+f"(d[154]), "+f"(d[155]), "+f"(d[156]), "+f"(d[157]), "+f"(d[158]), "+f"(d[159])
    : "l"(da), "l"(db), "r"(scale_d));
}
__device__ __forceinline__ void wgmma_n64b(float (&d)[192], uint64_t da, uint64_t db, int scale_d) {
  asm volatile("{\n.reg .pred p;\nsetp.ne.b32 p, %34, 0;\n"
    "wgmma.mma_async.sync.aligned.m64n64k16.f32.bf16.bf16 {%0, %1, %2, %3, %4, %5, %6, %7, %8, %9, %10, %11, %12, %13, %14, %15, %16, %17, %18, %19, %20, %21, %22, %23, %24, %25, %26, %27, %28, %29, %30, %31}, %32, %33, p, 1, 1, 0, 1;\n}\n"
    : "+f"(d[160]), "+f"(d[161]), "+f"(d[162]), "+f"(d[163]), "+f"(d[164]), "+f"(d[165]), "+f"(d[166]), "+f"(d[167]), "+f"(d[168]), "+f"(d[169]), "+f"(d[170]), "+f"(d[171]), "+f"(d[172]), "+f"(d[173]), "+f"(d[174]), "+f"(d[175]), "+f"(d[176]), "+f"(d[177]), "+f"(d[178]), "+f"(d[179]), "+f"(d[180]), "+f"(d[181]), "+f"(d[182]), "+f"(d[183]), "+f"(d[184]), "+f"(d[185]), "+f"(d[186]), "+f"(d[187]), "+f"(d[188]), "+f"(d[189]), "+f"(d[190]), "+f"(d[191])
    : "l"(da), "l"(db), "r"(scale_d));
}

constexpr int SLOT = 16384;
constexpr int KVT = 10240;
constexpr uint32_t QA = 0x0BAu, QK = 0x462u, QQ = 0x981u;
constexpr int SM_SD = 12 * SLOT;
constexpr int SM_BAR = SM_SD + 8192;
constexpr int SM_RS = SM_BAR + 512;
constexpr int SM_AP = SM_RS + 768;
constexpr int SM_BP = SM_AP + 2048;
constexpr int SM_WPHI = SM_BP + 12288;
constexpr int SM_EPOCH = SM_WPHI + 10240;
constexpr int SM_TOTAL = SM_EPOCH + 16 + 1024;
constexpr int B_FULLS = 0, B_XOLD = 24, B_STAT = 32, B_EMPTYS = 40, B_FULLT = 256  , B_CONS = 384  , B_E3 = 472, B_E0 = 480, B_E1 = 488, B_E2 = 496, B_EPI = 504, B_CS = 160,
              B_KVDONE = 168  , B_ODONE = 176, B_XDONE = 184, B_OH1 = 192, B_CS2 = 208, B_XH0 = 232, B_R0 = 240, B_CB = 144  , B_XOLD2 = 216, B_FLG = 64  ;
constexpr uint64_t BAR_CNT = 0x1c07fc0eac00a800ull;
constexpr uint64_t WO_A0 = 0xba76218762187643ull, WO_B0 = 0x9540395403ba9021ull, WO_A1 = 0xba713257132576abull, WO_B1 = 0x9506489064890132ull;
constexpr uint64_t WO_DA0 = 0xa9876543210edd00ull, WO_DB0 = 0xa987654321bbccccull, WO_DA1 = 0xa9876543210fff00ull, WO_DB1 = 0xa98765432bbcccddull;
#define WOORD 0xFDB9753ECA864210ull
constexpr int NX = 4;
constexpr int XS = 10;

#define PL 2
#define PROFX(i) PROFT(tid_ == 128 && layer == PL, 200 + (i))
#define PSL 20
#define EP 5
#define NCOM 3
#define CSLP 128
#define PFS 8
#define KVTH 0x41700000u
#define RL 3
#define ORD 1
#define XB2 2
#define PMOD 3
#define DB1 2
#define XPF 2
#define XPM 0
#define AW 1
#define PG 0
#define UNS 7
#define TLINE 0
#define RORD 0
#define WSK 0
#define NLAYERS 4
constexpr float L2E = 1.4426950408889634f;
#define PHI_MAX 2147483648.f

#define D128(lo) desc64(lo, 0x40000040u)
struct Ctx { uint32_t sb; int g, rb, cu; bf16* out; };

__device__ __forceinline__ void colsum(const CUtensorMap* tm, float* cs, int rb, int g, int w0, int dw, int lane, uint32_t stg, uint32_t cb, uint32_t par) {
  const uint32_t src = stg + (lane >> 3) * 2048;
#pragma unroll 1
  for (int wi = w0 - dw; wi < 6; wi += dw) {
    float s[8] = {0.f, 0.f, 0.f, 0.f, 0.f, 0.f, 0.f, 0.f};
    if (wi >= 0) {
      mbar_wait_u(cb, par);
      par ^= 1;
#pragma unroll 4
      for (int r = 0; r < 16; ++r) {
        const uint4 v = lds128(src + r * 128 + (((lane ^ r) & 7) << 4));
        s[0] += bf_lo(v.x); s[1] += bf_hi(v.x); s[2] += bf_lo(v.y); s[3] += bf_hi(v.y);
        s[4] += bf_lo(v.z); s[5] += bf_hi(v.z); s[6] += bf_lo(v.w); s[7] += bf_hi(v.w);
      }
#pragma unroll
      for (int i = 0; i < 8; ++i) s[i] += __shfl_xor_sync(0xffffffffu, s[i], 8);
    }
    const int wn = wi + dw;
    if (wn < 6) {
      expect_tx_e(cb, 8192);
      tma_2d_e(stg, tm, (wn >= 4 ? 0 : 1024 + (wn >> 1) * 1024) + g * 128 + (wn & 1) * 64, rb * 64, cb);
    }
    if (wi >= 0) {
#pragma unroll
      for (int i = 0; i < 8; ++i) s[i] += __shfl_xor_sync(0xffffffffu, s[i], 16);
      if (lane < 8) {
        red_add4(cs + g * 384 + (wi * 8 + lane) * 8, s[0], s[1], s[2], s[3]);
        red_add4(cs + g * 384 + (wi * 8 + lane) * 8 + 4, s[4], s[5], s[6], s[7]);
      }
      __syncwarp();
    }
  }
}
#define PHASE_CTX() \
  uint32_t sb = c.sb; asm volatile("" : "+r"(sb)); \
  int tid_ = threadIdx.x; asm volatile("" : "+r"(tid_)); \
  const uint32_t bar = sb + SM_BAR; \
  const int lane = tid_ & 31, cw = (tid_ >> 5) - 4, wg = cw >> 2, wq = cw & 3, gq = lane >> 2, t = lane & 3, wrow0 = cw * 16; \
  const int lrow = (lane & 7) + ((lane >> 3) & 1) * 8, lchk = lane >> 4; \
  const bool elected = (tid_ & 127) == 0; \
  const uint32_t rowo = (wrow0 + lrow) * 128, X = (lchk ^ (lane & 7)) << 4; \
  (void)bar; (void)wq; (void)gq; (void)lrow; (void)lchk; (void)elected; (void)wrow0; (void)wg; (void)rowo; (void)X; (void)t;

__device__ __forceinline__ void slab_out_half(uint32_t slot, bf16* dst, int wrow0, int lane, bool FENCE = false) {
  const int r0 = lane >> 3, ch = lane & 7;
  const uint32_t src = slot + (wrow0 + r0) * 128;
  uint4 v[4];
#pragma unroll
  for (int i = 0; i < 4; ++i) v[i] = lds128(src + i * 512 + (((ch ^ (4 * i + r0)) & 7) << 4));
  if (FENCE) fence_async_smem();
  dst += (size_t)(wrow0 + r0) * D_ + ch * 8;
#pragma unroll
  for (int i = 0; i < 4; ++i)
    asm volatile("st.global.v4.u32 [%0], {%1,%2,%3,%4};" ::"l"(dst + (size_t)i * 4 * D_), "r"(v[i].x), "r"(v[i].y), "r"(v[i].z), "r"(v[i].w) : "memory");
}

struct Tag { uint32_t me, mo, tg; };
__device__ __forceinline__ Tag make_tag(int gq, int t, uint32_t tg) {
  const uint32_t on = t == (gq & 3), par = ((gq >> 2) ^ gq) & 1;
  return Tag{on & ~par, on & par, tg};
}
__device__ __forceinline__ void stsm_tag(uint32_t addr, uint32_t r0, uint32_t r1, uint32_t r2, uint32_t r3, const Tag& k, int jp) {
  stsm_x4(addr, (r0 & ~k.me) | (k.tg & k.me), (r1 & ~k.me) | (k.tg & k.me), (r2 & ~k.mo) | (k.tg & k.mo), (r3 & ~k.mo) | (k.tg & k.mo));
}
#define TILE_BAD() (((lds_vol(va) ^ tg) | (lds_vol(va + 1024) ^ tg)) & 1)
#define TILE_VA() (slot + (wrow0 + (lane >> 2)) * 128 + (lane & 3) * 32 + (lane >> 2) * 4)
__device__ __forceinline__ void tile_check(uint32_t slot, const bf16* src, int wrow0, int lane, uint32_t tg) {
  const uint32_t va = TILE_VA();
  if (__builtin_expect(__any_sync(0xffffffffu, TILE_BAD()), 0)) {
    const int r0 = lane >> 3, ch = lane & 7;
    uint32_t n = 0;
#pragma unroll 1
    do {
#pragma unroll 1
      for (int i = 0; i < 4; ++i)
        sts128(slot + (wrow0 + r0 + 4 * i) * 128 + (((ch ^ (4 * i + r0)) & 7) << 4),
               ld_relaxed4(reinterpret_cast<const uint4*>(src + (size_t)(wrow0 + r0 + 4 * i) * D_ + ch * 8)));
      __syncwarp();
      if (++n > (1u << 16)) { g_err = 8u; break; }
    } while (__any_sync(0xffffffffu, TILE_BAD()));
    fence_async_smem();
    __syncwarp();
  }
}

template <int O>
__device__ __forceinline__ void phi_proj(float (&p)[2][4][4], const uint32_t (&kq)[64], uint32_t wa) {
#pragma unroll
  for (int h = 0; h < 2; ++h)
#pragma unroll
    for (int i = 0; i < 4; ++i) { p[h][i][0] = p[h][i][1] = p[h][i][2] = p[h][i][3] = 0.f; }
#pragma unroll
  for (int ks = 0; ks < 2; ++ks)
#pragma unroll
    for (int np = 0; np < 2; ++np)
#pragma unroll
      for (int h = 0; h < 2; ++h) {
        uint32_t b0, b1, b2, b3;
        ldsm_x4_t(b0, b1, b2, b3, wa + h * 2560 + ks * 1280 + np * 32);
        mma_bf16(p[h][2 * np], kq[O + 8 * h + 4 * ks], kq[O + 8 * h + 4 * ks + 1], kq[O + 8 * h + 4 * ks + 2], kq[O + 8 * h + 4 * ks + 3], b0, b1);
        mma_bf16(p[h][2 * np + 1], kq[O + 8 * h + 4 * ks], kq[O + 8 * h + 4 * ks + 1], kq[O + 8 * h + 4 * ks + 2], kq[O + 8 * h + 4 * ks + 3], b2, b3);
      }
}
__device__ __forceinline__ void phi_exp(uint32_t (&raw)[4][4], const float (&p)[4][4], float sc0, float sc1) {
#pragma unroll
  for (int i = 0; i < 4; ++i) {
    const float e0 = ex2(p[i][0] * sc0), e1 = ex2(p[i][1] * sc0), e2 = ex2(p[i][2] * sc1), e3 = ex2(p[i][3] * sc1);
    const float m0 = e0 * e1, m1 = e2 * e3, rr = rcp(m0 * m1), r0 = rr * m1, r1 = rr * m0;
    raw[i >> 1][(i & 1) * 2] = pack_bf16(e0, e1);
    raw[i >> 1][(i & 1) * 2 + 1] = pack_bf16(e2, e3);
    raw[2 + (i >> 1)][(i & 1) * 2] = pack_bf16(e1 * r0, e0 * r0);
    raw[2 + (i >> 1)][(i & 1) * 2 + 1] = pack_bf16(e3 * r1, e2 * r1);
  }
}
#define FENCE_P(h) _Pragma("unroll") for (int i_ = 0; i_ < 16; ++i_) asm volatile("" : "+f"(p[h][i_ >> 2][i_ & 3]) :: "memory")
#define FENCE_RAW(h) _Pragma("unroll") for (int i_ = 0; i_ < 16; ++i_) asm volatile("" : "+r"(raw[h][i_ >> 2][i_ & 3]) :: "memory")
template <int O>
__device__ __forceinline__ void phi_norm(uint32_t (&ph)[2][4][4], const uint32_t (&raw)[2][4][4], const uint32_t (&kq)[64], uint32_t wa,
                                         float sc0, float sc1, float mul0, float mul1) {
  bool bad = false;
#pragma unroll
  for (int h = 0; h < 2; ++h)
#pragma unroll
    for (int sg = 0; sg < 2; ++sg) {
      float ss[4] = {0.f, 0.f, 0.f, 0.f};
#pragma unroll
      for (int ks = 0; ks < 2; ++ks)
        mma_bf16(ss, raw[h][2 * sg + ks][0], raw[h][2 * sg + ks][1], raw[h][2 * sg + ks][2], raw[h][2 * sg + ks][3], 0x3F803F80u, 0x3F803F80u);
      bad = bad || !(ss[0] < PHI_MAX) || !(ss[2] < PHI_MAX);
      const uint32_t iv = pack_bf16(rcp(ss[0]) * mul0, rcp(ss[2]) * mul1);
#pragma unroll
      for (int ks = 0; ks < 2; ++ks)
#pragma unroll
        for (int j = 0; j < 4; ++j) ph[h][2 * sg + ks][j] = mul_bf16x2(raw[h][2 * sg + ks][j], iv, j & 1);
    }
  if (__builtin_expect(__any_sync(0xffffffffu, bad), 0)) {
#pragma unroll 1
    for (int it = 0; it < 4; ++it) {
      float q[4][4];
#pragma unroll
      for (int i = 0; i < 4; ++i) { q[i][0] = q[i][1] = q[i][2] = q[i][3] = 0.f; }
#pragma unroll
      for (int ks = 0; ks < 2; ++ks) {
        uint32_t a[4];
#pragma unroll
        for (int j = 0; j < 4; ++j) a[j] = (it & 2) ? kq[O + 8 + 4 * ks + j] : kq[O + 4 * ks + j];
#pragma unroll
        for (int np = 0; np < 2; ++np) {
          uint32_t b0, b1, b2, b3;
          ldsm_x4_t(b0, b1, b2, b3, wa + (it >> 1) * 2560 + ks * 1280 + np * 32);
          mma_bf16(q[2 * np], a[0], a[1], a[2], a[3], b0, b1);
          mma_bf16(q[2 * np + 1], a[0], a[1], a[2], a[3], b2, b3);
        }
      }
      float iv[2];
#pragma unroll
      for (int r = 0; r < 2; ++r) {
        const float sc = (it & 1) ? -(r ? sc1 : sc0) : (r ? sc1 : sc0);
        float mx = -INFINITY, sm = 0.f;
#pragma unroll
        for (int i = 0; i < 8; ++i) { float& v = q[i >> 1][2 * r + (i & 1)]; v *= sc; mx = fmaxf(mx, v); }
        mx = fmaxf(mx, __shfl_xor_sync(0xffffffffu, mx, 1));
        mx = fmaxf(mx, __shfl_xor_sync(0xffffffffu, mx, 2));
#pragma unroll
        for (int i = 0; i < 8; ++i) { float& v = q[i >> 1][2 * r + (i & 1)]; v = ex2(v - mx); sm += v; }
        sm += __shfl_xor_sync(0xffffffffu, sm, 1);
        sm += __shfl_xor_sync(0xffffffffu, sm, 2);
        iv[r] = rcp(sm) * (r ? mul1 : mul0);
      }
#pragma unroll
      for (int i = 0; i < 24; ++i) ph[i >> 4][(i >> 2) & 3][i & 3] = ph[(i + 8) >> 4][((i + 8) >> 2) & 3][i & 3];
#pragma unroll
      for (int i = 0; i < 4; ++i) {
        ph[1][2 + (i >> 1)][(i & 1) * 2] = pack_bf16(q[i][0] * iv[0], q[i][1] * iv[0]);
        ph[1][2 + (i >> 1)][(i & 1) * 2 + 1] = pack_bf16(q[i][2] * iv[1], q[i][3] * iv[1]);
      }
    }
  }
}

__device__ __forceinline__ void stats_out(float s0, float s1, float q0, float q1, float2* dst, int t) {
  const bool od = t & 1;
  float sa = od ? s1 : s0, qa = od ? q1 : q0;
  sa += __shfl_xor_sync(0xffffffffu, od ? s0 : s1, 1);
  qa += __shfl_xor_sync(0xffffffffu, od ? q0 : q1, 1);
  sa += __shfl_xor_sync(0xffffffffu, sa, 2);
  qa += __shfl_xor_sync(0xffffffffu, qa, 2);
  if (t < 2) red_add2(&dst[t * 8].x, sa, qa);
}

__device__ __forceinline__ void consumer(const Ctx& c) {
  const int g = c.g, m0 = c.rb * 128;
  float acc[192];
#define X_HALF(hf, TG) \
      _Pragma("unroll") for (int jp = 4 * (hf); jp < 4 * (hf) + 4; ++jp) \
        stsm_tag(sb + (XS + (hf)) * SLOT + rowo + (X ^ ((jp & 3) << 5)), \
                 pack_bf16(acc[128 + 8 * jp], acc[129 + 8 * jp]), pack_bf16(acc[130 + 8 * jp], acc[131 + 8 * jp]), \
                 pack_bf16(acc[132 + 8 * jp], acc[133 + 8 * jp]), pack_bf16(acc[134 + 8 * jp], acc[135 + 8 * jp]), TG, jp & 3);
#pragma unroll
  for (int i = 128; i < 192; ++i) acc[i] = 0.f;
#pragma unroll 1
  for (int layer = 0;; ++layer) {
    {
      PHASE_CTX();
      const uint32_t wu = c.cu >> 2;
      const uint32_t dA0 = (((sb + wu * 8192) & 0x3FFFF) >> 4) | (1u << 16), dB0 = ((sb & 0x3FFFF) >> 4) | (512u << 16);
      {
        PROFX(0);
        mbar_wait(bar + B_FULLS, 0);
        PROFX(1);
        wgmma_fence();
        wgmma_n256_0(acc, D128(dA0 + XS * 1024), D128(dB0 + 2048));
#pragma unroll
        for (int k = 1; k < 4; ++k) wgmma_n256(acc, D128(dA0 + XS * 1024 + k * 2), D128(dB0 + 2048 + k * 128), 1);
        wgmma_commit();
        wgmma_wait<1>();
        float s0 = 0.f, s1 = 0.f, q0 = 0.f, q1 = 0.f;
        if (layer) {
          X_HALF(1, (Tag{0u, 0u, 0u}));
#pragma unroll
          for (int i = 128; i < 192; i += 4) {
            s0 += acc[i] + acc[i + 1]; s1 += acc[i + 2] + acc[i + 3];
            q0 = fmaf(acc[i], acc[i], fmaf(acc[i + 1], acc[i + 1], q0)); q1 = fmaf(acc[i + 2], acc[i + 2], fmaf(acc[i + 3], acc[i + 3], q1));
          }
        }
        asm volatile("" : "+f"(s0), "+f"(s1), "+f"(q0), "+f"(q1) :: "memory");
        wgmma_fence();
        wgmma_n128_0(acc, D128(dA0 + XS * 1024), D128(dB0 + 1024));
#pragma unroll
        for (int k = 1; k < 4; ++k) wgmma_n128(acc, D128(dA0 + XS * 1024 + k * 2), D128(dB0 + 1024 + k * 128), 1);
        wgmma_commit();
        if (layer) {
          PHASE_CTX();
          fence_async_smem();
          nbar_dyn(3 + wu, 128);
          stats_out(s0, s1, q0, q1, g_stats + layer * S_ + m0 + wrow0 + gq, t);
          PROFT(tid_ == 128, layer * 16 + 8);
        }
      }
      uint32_t s = 1, u = 0, sp = 0;
      const int ix = layer ? 99 : 2 * min(g, NCOM) + 1;
#pragma unroll 1
      for (int i = 1; i < 14; ++i) {
        mbar_wait(bar + B_FULLS + s * 8, (u + (s ? layer : 0)) & 1);
        if ((UNS & 1) && layer && (unsigned)(i - 2) < 7u) {
          PHASE_CTX();
          tile_check(sb + ((QA >> (4 * s)) & 15) * SLOT, g_x + (size_t)m0 * D_ + ((2 * g + 2 * i - 2) & 15) * 64, wrow0, lane, lds_vol(sb + SM_EPOCH) + layer);
        }
        const uint32_t da = dA0 + ((QA >> (4 * s)) & 15) * 1024, dk = dB0 + ((QK >> (4 * s)) & 15) * 1024,
                       dq = dB0 + ((QQ >> (4 * s)) & 15) * 1024;
        wgmma_fence();
#pragma unroll
        for (int k = 0; k < 4; ++k) {
          wgmma_n256(acc, D128(da + k * 2), D128(dk + k * 128), 1);
          wgmma_n128(acc, D128(da + k * 2), D128(dq + k * 128), 1);
        }
        wgmma_commit();
        if ((unsigned)(i - ix) < 2u) {
          PHASE_CTX();
          {
            float s0 = 0.f, s1 = 0.f, q0 = 0.f, q1 = 0.f;
            const uint32_t xa = sb + ((QA >> (4 * sp)) & 15) * SLOT + rowo;
#pragma unroll
            for (int jp = 0; jp < 4; ++jp) {
              uint32_t x0, x1, x2, x3;
              ldsm_x4(x0, x1, x2, x3, xa + (X ^ (jp << 5)));
              s0 += (bf_lo(x0) + bf_hi(x0)) + (bf_lo(x2) + bf_hi(x2));
              s1 += (bf_lo(x1) + bf_hi(x1)) + (bf_lo(x3) + bf_hi(x3));
              q0 = fmaf(bf_lo(x0), bf_lo(x0), fmaf(bf_hi(x0), bf_hi(x0), fmaf(bf_lo(x2), bf_lo(x2), fmaf(bf_hi(x2), bf_hi(x2), q0))));
              q1 = fmaf(bf_lo(x1), bf_lo(x1), fmaf(bf_hi(x1), bf_hi(x1), fmaf(bf_lo(x3), bf_lo(x3), fmaf(bf_hi(x3), bf_hi(x3), q1))));
            }
            stats_out(s0, s1, q0, q1, g_stats + m0 + wrow0 + gq, t);
          }
          __syncwarp();
          if (lane == 0 && i != ix) mbar_arrive(bar + B_XDONE);
          nbar_dyn(3 + wu, 128);
        }
        wgmma_wait<1>();
        if (elected) release2(bar + B_EMPTYS + sp * 8);
        if (i == 1 && layer) {
          PHASE_CTX();
          slab_out_half(sb + (XS + 1) * SLOT, g_x + (size_t)m0 * D_ + g * 128 + 64, wrow0, lane);
          __syncwarp();
          if (lane == 0) mbar_arrive(bar + B_XDONE);
          nbar_dyn(3 + wu, 128);
        }
        sp = s;
        if (++s == 3) { s = 0; ++u; }
      }
      {
        const uint64_t dap = make_desc_ns(sb + SM_AP + wu * 1024, 0, 128), dbp = make_desc_ns(sb + SM_BP + (layer & 1) * 6144, 0, 128);
        if (wu == 0) {
          wgmma_wait<0>();
          if (elected) mbar_arrive(bar + B_R0);
          nbar<6, 256>();
        }
        if (layer < 2) mbar_wait(bar + (layer ? B_CS2 : B_CS), 0);
        mbar_wait(bar + B_STAT, layer & 1);
        mbar_wait(bar + B_FULLS + 16, layer & 1);
        wgmma_fence();
        wgmma_n256_k(acc, dap, dbp, 1);
#pragma unroll
        for (int k = 0; k < 4; ++k) wgmma_n256(acc, D128(dA0 + (QA >> 8) * 1024 + k * 2), D128(dB0 + (QK >> 8) * 1024 + k * 128), 1);
        mbar_wait(bar + B_FULLS, 1);
        PROFT(tid_ == 128, layer * 16 + 9);
        wgmma_fence();
#pragma unroll
        for (int k = 0; k < 4; ++k) wgmma_n256(acc, D128(dA0 + (QA & 15) * 1024 + k * 2), D128(dB0 + (QK & 15) * 1024 + k * 128), 1);
        wgmma_commit();
        if (wu) nbar<6, 256>();
#define Q_TAIL() \
        wgmma_n128_k(acc, dap, dbp + 256, 1); \
        _Pragma("unroll") for (int k = 0; k < 4; ++k) wgmma_n128(acc, D128(dA0 + (QA >> 8) * 1024 + k * 2), D128(dB0 + (QQ >> 8) * 1024 + k * 128), 1); \
        _Pragma("unroll") for (int k = 0; k < 4; ++k) wgmma_n128(acc, D128(dA0 + (QA & 15) * 1024 + k * 2), D128(dB0 + (QQ & 15) * 1024 + k * 128), 1);
        Q_TAIL();
        wgmma_commit();
        wgmma_wait<1>();
#pragma unroll
        for (int i = 0; i < 128; ++i) asm volatile("" : "+f"(acc[i]) :: "memory");
      }
    }
    uint32_t xo[32];
    {
      PHASE_CTX();
      PROFT(tid_ == 128, layer * 16 + 1);
      const bool isB = layer & 1;
      const int cu = c.cu;
      if (cu >= 4) asm volatile("bar.arrive 7, 256;" ::: "memory");
      if (elected && cu == 4) mbar_arrive(bar + B_R0);
      uint32_t kq[64];
      const uint32_t rowq = rowo & 8191;
      const float rs0 = lds_f(sb + SM_RS + (16 + wrow0 + gq) * 4), rs1 = lds_f(sb + SM_RS + (24 + wrow0 + gq) * 4);
#define Q_DONE() \
      wgmma_wait<0>(); \
      if (lane == 0) release2(bar + B_E0); \
      _Pragma("unroll") for (int i = 128; i < 192; ++i) asm volatile("" : "+f"(acc[i]) :: "memory"); \
      _Pragma("unroll") for (int i = 0; i < 32; ++i) kq[32 + i] = pack_bf16(acc[128 + 2 * i], acc[129 + 2 * i]);
      if (isB) {
        if (cu == 0) asm volatile("bar.arrive 10, 64;" ::: "memory");
        if (elected) release2(bar + B_E1);
        const int e = gq & 1;
        const bool sel = t > (gq >> 1);
        const uint32_t rja = sb + SM_RS + (wrow0 + 2 * t + e) * 4;
        const float rjA0 = lds_f(rja + 32), rjA1 = lds_f(rja + 64), rjB0 = lds_f(rja + (sel ? 0 : 64)), rjB1 = lds_f(rja + (sel ? 32 : 96));
        uint32_t vv[32];
#pragma unroll
        for (int i = 0; i < 16; ++i) { kq[i] = pack_bf16(acc[2 * i], acc[2 * i + 1]); vv[i] = pack_bf16(acc[64 + 2 * i], acc[65 + 2 * i]); }
        const uint32_t rB = sb + 4 * SLOT + wg * 4 * KVT + rowq;
        auto dump = [&](int hp) {
          const uint32_t kb = rB + 2048 + (hp ^ wg) * 2 * KVT;
#pragma unroll
          for (int jp = 0; jp < 4; ++jp) {
            stsm_x4(kb + (X ^ (jp << 5)), kq[16 * hp + 4 * jp], kq[16 * hp + 4 * jp + 1], kq[16 * hp + 4 * jp + 2], kq[16 * hp + 4 * jp + 3]);
            stsm_x4(kb + KVT + (X ^ (jp << 5)), vv[16 * hp + 4 * jp], vv[16 * hp + 4 * jp + 1], vv[16 * hp + 4 * jp + 2], vv[16 * hp + 4 * jp + 3]);
          }
          if (cu == 3) {
            const uint32_t kd = rB + 2048 + 32768 + (1 - hp) * 2 * KVT;
#pragma unroll
            for (int jp = 0; jp < 4; ++jp) {
              stsm_x4(kd + (X ^ (jp << 5)), kq[16 * hp + 4 * jp], kq[16 * hp + 4 * jp + 1], kq[16 * hp + 4 * jp + 2], kq[16 * hp + 4 * jp + 3]);
              stsm_x4(kd + KVT + (X ^ (jp << 5)), vv[16 * hp + 4 * jp], vv[16 * hp + 4 * jp + 1], vv[16 * hp + 4 * jp + 2], vv[16 * hp + 4 * jp + 3]);
            }
            if (hp) asm volatile("bar.arrive 15, 64;" ::: "memory"); else asm volatile("bar.arrive 9, 64;" ::: "memory");
          }
          asm volatile("bar.arrive %0, 224;" :: "r"(hp ? 13 + (cu >> 2) : 8 + (cu & 4)) : "memory");
        };
        uint4* const hbuf = g_halo + ((c.rb * 8 + g) * 2 + (layer >> 1)) * 512 + lane;
        if (cu < 4) {
          nbar<7, 256>();
          dump(0);
        }
#pragma unroll
        for (int i = 16; i < 32; ++i) { kq[i] = pack_bf16(acc[2 * i], acc[2 * i + 1]); vv[i] = pack_bf16(acc[64 + 2 * i], acc[65 + 2 * i]); }
        if (cu >= 4) {
          if (cu == 7) {
#pragma unroll
            for (int jp = 0; jp < 8; ++jp) {
              st_relaxed4(hbuf + jp * 32, ~kq[4 * jp], ~kq[4 * jp + 1], ~kq[4 * jp + 2], ~kq[4 * jp + 3]);
              st_relaxed4(hbuf + 256 + jp * 32, ~vv[4 * jp], ~vv[4 * jp + 1], ~vv[4 * jp + 2], ~vv[4 * jp + 3]);
            }
          }
          dump(0);
          dump(1);
        }
        PROFT(tid_ == 128, layer * 16 + 2);
        constexpr float SC = 0.17677669529663687f * L2E;
        const float fA0 = rjA0 * rs0 * SC, fB0 = rjB0 * rs0 * SC, fA1 = rjA1 * rs1 * SC, fB1 = rjB1 * rs1 * SC;
        const float bA0 = (m0 + wrow0) ? 0.f : -1e30f, bB = sel ? bA0 : 0.f;
        const uint32_t pA_ = e ? 0x1044u : 0x4410u, pB_ = e ? 0x3244u : 0x4432u, pLo = sel ? pB_ : 0x4444u, pHi = sel ? 0x4444u : pB_;
        const uint32_t KX = ((lane >> 3) ^ (lane & 7)) << 4;
        Q_DONE();
        if (cu == 0) {
          nbar<11, 64>();
        } else if (cu == 4) {
          uint4 hv[16];
          if (c.rb > 0) {
            uint32_t n = 0;
#pragma unroll 1
            while (true) {
              uint32_t mn = 0xFFFFFFFFu;
#pragma unroll
              for (int i = 0; i < 16; ++i) hv[i] = ld_relaxed4(hbuf - 16 * 512 + i * 32);
#pragma unroll
              for (int i = 0; i < 16; ++i) mn = __vimin3_u32(__vimin3_u32(mn, hv[i].x, hv[i].y), hv[i].z, hv[i].w);
              if (__all_sync(0xffffffffu, mn != 0u)) break;
              if (++n > (1u << 20)) { g_err = 4u; break; }
            }
          } else {
#pragma unroll
            for (int i = 0; i < 16; ++i) hv[i] = make_uint4(~0u, ~0u, ~0u, ~0u);
          }
          nbar<10, 64>();
#pragma unroll
          for (int i = 0; i < 16; ++i)
            stsm_x4(rB - 4 * KVT + (((i >> 2) & 1) * 2 + (i >> 3)) * KVT + (X ^ ((i & 3) << 5)), ~hv[i].x, ~hv[i].y, ~hv[i].z, ~hv[i].w);
          asm volatile("bar.arrive 11, 64;" ::: "memory");
          nbar<9, 64>();
        } else {
          nbar_dyn(8 + (cu & 4), 224);
        }
        PROFT(tid_ == 128, layer * 16 + 5);
        PROFT(lane == 0 && layer == PL, 136 + cw);
        auto attend = [&](int hp) {
          const uint32_t qad = sb + (XS + 1 - hp) * SLOT + rowo, kt = rB + 2 * (hp ^ wg) * KVT - (lane & 8) * 128, vt = rB + (2 * (hp ^ wg) + 1) * KVT;
          __syncwarp();
          uint32_t kb[2][2][4], vb[2][2][2][4];
#pragma unroll
          for (int h = 0; h < 2; ++h)
#pragma unroll
            for (int nt = 0; nt < 2; ++nt) ldsm_x4(kb[h][nt][0], kb[h][nt][1], kb[h][nt][2], kb[h][nt][3], kt + nt * 1024 + (KX ^ (h << 6)));
#pragma unroll
          for (int ks = 0; ks < 2; ++ks)
#pragma unroll
            for (int np = 0; np < 2; ++np)
#pragma unroll
              for (int h = 0; h < 2; ++h)
                ldsm_x4_t(vb[h][ks][np][0], vb[h][ks][np][1], vb[h][ks][np][2], vb[h][ks][np][3], vt + ks * 2048 + (X ^ (h << 6) ^ (np << 5)));
          if (hp == 0 && lane == 0) release2(bar + B_E3);
          if (DB1 == 1 && hp == 0 && cu < 4) dump(1);
          float la[2][2], lb[2][2], mx[2][2], sm[2][2];
#pragma unroll
          for (int h = 0; h < 2; ++h) {
            const int qo = 32 + 16 * hp + 8 * h, ko = 16 * hp + 8 * h;
            float sc[4][4];
#pragma unroll
            for (int nt = 0; nt < 4; ++nt) {
              sc[nt][0] = sc[nt][1] = sc[nt][2] = sc[nt][3] = 0.f;
#pragma unroll
              for (int ks = 0; ks < 2; ++ks)
                mma_bf16(sc[nt], kq[qo + 4 * ks], kq[qo + 4 * ks + 1], kq[qo + 4 * ks + 2], kq[qo + 4 * ks + 3],
                         nt < 2 ? kb[h][nt & 1][2 * ks] : kq[ko + 4 * ks + (nt & 1)], nt < 2 ? kb[h][nt & 1][2 * ks + 1] : kq[ko + 4 * ks + 2 + (nt & 1)]);
            }
            la[h][0] = fmaf(e ? sc[1][1] : sc[1][0], fA0, bA0);
            lb[h][0] = fmaf(sel ? (e ? sc[0][1] : sc[0][0]) : (e ? sc[2][1] : sc[2][0]), fB0, bB);
            la[h][1] = (e ? sc[2][3] : sc[2][2]) * fA1;
            lb[h][1] = fmaf(sel ? (e ? sc[1][3] : sc[1][2]) : (e ? sc[3][3] : sc[3][2]), fB1, bB);
            mx[h][0] = fmaxf(la[h][0], lb[h][0]); mx[h][1] = fmaxf(la[h][1], lb[h][1]);
          }
#pragma unroll
          for (int o = 1; o <= 2; o <<= 1)
#pragma unroll
            for (int h = 0; h < 2; ++h)
#pragma unroll
              for (int r = 0; r < 2; ++r) mx[h][r] = fmaxf(mx[h][r], __shfl_xor_sync(0xffffffffu, mx[h][r], o));
          float oa[2][4][4];
#pragma unroll
          for (int h = 0; h < 2; ++h) {
#pragma unroll
            for (int r = 0; r < 2; ++r) { la[h][r] = ex2(la[h][r] - mx[h][r]); lb[h][r] = ex2(lb[h][r] - mx[h][r]); sm[h][r] = la[h][r] + lb[h][r]; }
            const uint32_t p0 = pack_bf16(la[h][0] * rjA0, lb[h][0] * rjB0), p1 = pack_bf16(la[h][1] * rjA1, lb[h][1] * rjB1);
            const uint32_t a00 = __byte_perm(p0, 0u, pLo), a02 = __byte_perm(p0, 0u, pA_), a03 = __byte_perm(p1, 0u, pLo);
            const uint32_t a10 = __byte_perm(p0, 0u, pHi), a11 = __byte_perm(p1, 0u, pA_), a13 = __byte_perm(p1, 0u, pHi);
#pragma unroll
            for (int i = 0; i < 4; ++i) {
              oa[h][i][0] = oa[h][i][1] = oa[h][i][2] = oa[h][i][3] = 0.f;
              mma_bf16(oa[h][i], a00, 0u, a02, a03, vb[h][0][i >> 1][2 * (i & 1)], vb[h][0][i >> 1][2 * (i & 1) + 1]);
              mma_bf16(oa[h][i], a10, a11, 0u, a13, vb[h][1][i >> 1][2 * (i & 1)], vb[h][1][i >> 1][2 * (i & 1) + 1]);
            }
          }
#pragma unroll
          for (int o = 1; o <= 2; o <<= 1)
#pragma unroll
            for (int h = 0; h < 2; ++h)
#pragma unroll
              for (int r = 0; r < 2; ++r) sm[h][r] += __shfl_xor_sync(0xffffffffu, sm[h][r], o);
          mbar_wait(bar + (hp ? B_XOLD2 : B_XOLD), 1);
#pragma unroll
          for (int jp = 0; jp < 4; ++jp) ldsm_x4(xo[16 * hp + 4 * jp], xo[16 * hp + 4 * jp + 1], xo[16 * hp + 4 * jp + 2], xo[16 * hp + 4 * jp + 3], qad + (X ^ (jp << 5)));
#pragma unroll
          for (int h = 0; h < 2; ++h) {
            const float i0 = rcp(sm[h][0]), i1 = rcp(sm[h][1]);
#pragma unroll
            for (int np = 0; np < 2; ++np)
              stsm_tag(qad + (X ^ (h << 6) ^ (np << 5)),
                       pack_bf16(oa[h][2 * np][0] * i0, oa[h][2 * np][1] * i0), pack_bf16(oa[h][2 * np][2] * i1, oa[h][2 * np][3] * i1),
                       pack_bf16(oa[h][2 * np + 1][0] * i0, oa[h][2 * np + 1][1] * i0), pack_bf16(oa[h][2 * np + 1][2] * i1, oa[h][2 * np + 1][3] * i1), make_tag(gq, t, 0u), 2 * h + np);
          }
          __syncwarp();
          slab_out_half(sb + (XS + 1 - hp) * SLOT, g_o + (size_t)m0 * D_ + g * 128 + hp * 64, wrow0, lane, hp);
          __syncwarp();
          if (lane == 0) mbar_arrive(bar + (hp ? B_ODONE : B_OH1));
          PROFT(lane == 0 && layer == PL && hp == 0, 128 + cw);
        };
        attend(0);
        if (DB1 == 2 && cu < 4) dump(1);
        if (cu == 4) nbar<15, 64>();
        else if (cu != 0) nbar_dyn(13 + (cu >> 2), 224);
        attend(1);
      } else {
#pragma unroll
        for (int i = 0; i < 32; ++i) kq[i] = pack_bf16(acc[2 * i], acc[2 * i + 1]);
        if (cu < 4) nbar<7, 256>();
        {
          const uint32_t vb = sb + (5 + 3 * wg) * SLOT + (rowq >> 1) + ((lchk ^ ((lane & 7) >> 1)) << 4);
#pragma unroll
          for (int jp = 8; jp < 16; ++jp)
            stsm_x4((vb ^ ((jp & 1) << 5)) + ((jp >> 1) & 3) * 4096,
                    pack_bf16(acc[8 * jp], acc[8 * jp + 1]), pack_bf16(acc[8 * jp + 2], acc[8 * jp + 3]),
                    pack_bf16(acc[8 * jp + 4], acc[8 * jp + 5]), pack_bf16(acc[8 * jp + 6], acc[8 * jp + 7]));
        }
        PROFT(tid_ == 128, layer * 16 + 2);
        Q_DONE();
        const uint32_t pA = sb + (3 + 3 * wg) * SLOT + (rowo & 8191);
        float sc0 = rs0 * L2E, sc1 = rs1 * L2E;
        const uint32_t wa0 = sb + SM_WPHI + lrow * 80 + lchk * 16;
        const uint32_t wu = c.cu >> 2, par = (layer >> 1) & 1;
        float p[2][4][4];
        uint32_t raw[2][4][4], ph[2][4][4];
        float kva[20], oa[2][20];
        auto kv_start = [&](int hp) {
#pragma unroll
          for (int h = 0; h < 2; ++h)
#pragma unroll
            for (int cp = 0; cp < 4; ++cp)
              stsm_x4(pA + hp * 16384 + h * 8192 + (X ^ (cp << 5)), ph[h][cp][0], ph[h][cp][1], ph[h][cp][2], ph[h][cp][3]);
          PROFT(tid_ == 128, layer * 16 + 11);
          fence_async_smem();
          nbar<1, 256>();
          const uint32_t hu = 2 * hp + wu;
          const uint32_t dP = (((sb + 3 * SLOT + hu * 8192) & 0x3FFFF) >> 4) | (512u << 16);
          const uint32_t dV = (((sb + 5 * SLOT + hu * 4096) & 0x3FFFF) >> 4) | (((SM_SD - 5 * SLOT - hu * 4096) >> 4) << 16);
          wgmma_fence();
#pragma unroll
          for (int ks = 0; ks < 8; ++ks)
            wgmma_n40_tt(kva, desc64(dP + (ks >> 2) * 3072 + (ks & 3) * 128, 0x40000040u),
                         desc64(dV + (ks >> 2) * (3072u - (2816u << 16)) + (ks & 3) * 64, 0x80000020u), ks != 0);
          wgmma_commit();
        };
        auto kv_end = [&](int hp) {
          wgmma_wait<0>();
#pragma unroll
          for (int i = 0; i < 20; ++i) asm volatile("" : "+f"(kva[i]) :: "memory");
          nbar_dyn(3 + wu, 128);
          PROFT(tid_ == 128, layer * 16 + 12);
          const bool od = lane & 1;
#pragma unroll
          for (int i = 0; i < 4; ++i)
            sts128(sb + (3 + hp) * SLOT + (cw * 128 + i * 32 + lane) * 16,
                   make_uint4(__float_as_uint(kva[4 * i]), __float_as_uint(kva[4 * i + 1]), __float_as_uint(kva[4 * i + 2]),
                              __float_as_uint(od == (i >= 2) ? 1.f : kva[4 * i + 3])));
          sts128(sb + (6 + hp) * SLOT + wg * 8192 + (wq * 32 + lane) * 16,
                 make_uint4(__float_as_uint(od ? kva[11] : kva[3]), __float_as_uint(od ? kva[15] : kva[7]), __float_as_uint(od ? kva[18] : kva[16]), __float_as_uint(1.f)));
          fence_async_smem();
          __syncwarp();
          if (lane == 0) mbar_arrive(bar + B_KVDONE - hp * 32);
          PROFT(tid_ == 128, layer * 16 + 3);
        };
        const uint4* const kvg = g_kv + (g * 2 + (layer >> 1)) * 2560 + cw * 128 + lane;
        uint4 u[5];
        auto kv_load = [&](int hp) {
#pragma unroll
          for (int i = 0; i < 4; ++i) u[i] = ld_relaxed4(kvg + hp * 1280 + i * 32);
          u[4] = ld_relaxed4(kvg + hp * 1280 + 1024 - cw * 96);
        };
        auto o_start = [&](int hp, const uint32_t (&pq)[2][4][4]) {
          PROFT(tid_ == 128 && hp == 0, layer * 16 + 10);
          if (hp == 0) mbar_wait(bar + B_KVDONE - 32, par);
          const bool od = lane & 1;
          uint32_t n = 0;
#pragma unroll 1
          while (!__all_sync(0xffffffffu, (od ? u[2].w : u[0].w) == 0x41800000u && (od ? u[3].w : u[1].w) == 0x41800000u && u[4].w == 0x41800000u)) {
#pragma unroll 1
            while (__any_sync(0xffffffffu, u[4].w < KVTH) && ++n < (1u << 20)) u[4].w = ld_relaxed(&kvg[hp * 1280 + 1024 - cw * 96].w);
            if (++n > (1u << 20)) { g_err = 6u; break; }
            kv_load(hp);
          }
          PROFT(tid_ == 128 && hp == 0, layer * 16 + 5);
          if (!od) { u[0].w = u[4].x; u[1].w = u[4].y; } else { u[2].w = u[4].x; u[3].w = u[4].y; }
#pragma unroll
          for (int i = 0; i < 4; i += 2)
            stsm_x4(sb + (5 + 3 * hp) * SLOT + rowo + (X ^ ((i & 2) << 4)),
                    pack_bf16(__uint_as_float(u[i].x), __uint_as_float(u[i].y)), pack_bf16(__uint_as_float(u[i].z), __uint_as_float(u[i].w)),
                    pack_bf16(__uint_as_float(u[i + 1].x), __uint_as_float(u[i + 1].y)), pack_bf16(__uint_as_float(u[i + 1].z), __uint_as_float(u[i + 1].w)));
          const uint32_t z2 = pack_bf16(__uint_as_float(u[4].z), __uint_as_float(u[4].z));
          if (t < 2) sts128(sb + (5 + 3 * hp) * SLOT + (wrow0 + gq + 8 * t) * 128 + ((4 ^ gq) << 4), make_uint4(z2, z2, z2, z2));
          fence_async_smem();
          nbar<1, 256>();
          PROFT(tid_ == 128 && hp == 1, layer * 16 + 4);
          const uint32_t dK = (((sb + (5 + 3 * hp) * SLOT) & 0x3FFFF) >> 4) | (512u << 16);
          wgmma_fence();
#pragma unroll
          for (int ks = 0; ks < 4; ++ks) {
#pragma unroll
            for (int hh = 0; hh < 2; ++hh) wgmma_n40_rs(oa[hh], pq[hh][ks], D128(dK + hh * 512 + ks * 128), ks != 0);
          }
          wgmma_commit();
        };
        auto o_end = [&](int hp) {
          wgmma_wait<0>();
#pragma unroll
          for (int i = 0; i < 20; ++i) asm volatile("" : "+f"(oa[0][i]), "+f"(oa[1][i]) :: "memory");
#pragma unroll
          for (int hh = 0; hh < 2; ++hh) {
            const float i0 = rcp(oa[hh][16] + 1e-6f), i1 = rcp(oa[hh][18] + 1e-6f);
            const uint32_t qad = sb + (3 + hp) * SLOT + rowo, hx = hh << 6;
#pragma unroll
            for (int np = 0; np < 2; ++np)
              stsm_tag(qad + (X ^ hx ^ (np << 5)),
                       pack_bf16(oa[hh][8 * np] * i0, oa[hh][8 * np + 1] * i0), pack_bf16(oa[hh][8 * np + 2] * i1, oa[hh][8 * np + 3] * i1),
                       pack_bf16(oa[hh][8 * np + 4] * i0, oa[hh][8 * np + 5] * i0), pack_bf16(oa[hh][8 * np + 6] * i1, oa[hh][8 * np + 7] * i1), make_tag(gq, t, 1u), 2 * hh + np);
          }
          __syncwarp();
          slab_out_half(sb + (3 + hp) * SLOT, g_o + (size_t)m0 * D_ + g * 128 + hp * 64, wrow0, lane, hp);
          __syncwarp();
          if (lane == 0) mbar_arrive(bar + (hp ? B_ODONE : B_OH1));
        };
#define XO_LOAD() \
        mbar_wait(bar + B_XOLD, 0); \
        mbar_wait(bar + B_XOLD2, 0); \
        _Pragma("unroll") for (int jp = 0; jp < 8; ++jp) \
          ldsm_x4(xo[4 * jp], xo[4 * jp + 1], xo[4 * jp + 2], xo[4 * jp + 3], sb + (XS + 1 - (jp >> 2)) * SLOT + rowo + (X ^ ((jp & 3) << 5)));
#define SC_RELOAD() \
        sc0 = __uint_as_float(lds_vol(sb + SM_RS + (16 + wrow0 + gq) * 4)) * L2E; sc1 = __uint_as_float(lds_vol(sb + SM_RS + (24 + wrow0 + gq) * 4)) * L2E;
        __syncwarp();
        phi_proj<0>(p, kq, wa0);
        phi_exp(raw[0], p[0], sc0, sc1);
        phi_exp(raw[1], p[1], sc0, sc1);
        phi_proj<16>(p, kq, wa0 + 5120);
        phi_norm<0>(ph, raw, kq, wa0, sc0, sc1, rs0, rs1);
        kv_start(0);
        phi_exp(raw[0], p[0], sc0, sc1);
        kv_end(0);
        if (RL & 1) { SC_RELOAD(); }
        XO_LOAD();
        phi_exp(raw[1], p[1], sc0, sc1);
        phi_proj<32>(p, kq, wa0);
        phi_norm<16>(ph, raw, kq, wa0 + 5120, sc0, sc1, rs0, rs1);
        kv_start(1);
        if (lane == 0) release2(bar + B_E3);
        phi_exp(raw[0], p[0], sc0, sc1);
        kv_end(1);
        if (RL & 2) { SC_RELOAD(); }
        kv_load(0);
        phi_exp(raw[1], p[1], sc0, sc1);
        phi_proj<48>(p, kq, wa0 + 5120);
        phi_norm<32>(ph, raw, kq, wa0, sc0, sc1, 1.f, 1.f);
        o_start(0, ph);
        phi_exp(raw[0], p[0], sc0, sc1);
        o_end(0);
        SC_RELOAD();
        kv_load(1);
        phi_exp(raw[1], p[1], sc0, sc1);
        phi_norm<48>(ph, raw, kq, wa0 + 5120, sc0, sc1, 1.f, 1.f);
        o_start(1, ph);
        o_end(1);
      }
      __syncwarp();
      PROFT(lane == 0 && layer == PL, 216 + cw);
      if (lane == 0) mbar_arrive(bar + B_EPI);
      PROFT(tid_ == 128, layer * 16 + 6);
    }
    {
      PHASE_CTX();
      const uint32_t wu = c.cu >> 2;
      const uint32_t dA0 = (((sb + wu * 8192) & 0x3FFFF) >> 4) | (1u << 16), dB0 = ((sb & 0x3FFFF) >> 4) | (512u << 16);
#pragma unroll
      for (int i = 0; i < 32; ++i) { acc[128 + 2 * i] = bf_lo(xo[i]); acc[129 + 2 * i] = bf_hi(xo[i]); }
      nbar_dyn(3 + wg, 128);
      uint64_t ta = (layer & 1) ? WO_A1 : WO_A0, tw = (layer & 1) ? WO_B1 : WO_B0;
#pragma unroll 1
      for (int i = 0; i < 16; ++i) {
        mbar_wait(bar + B_FULLT + i * 8, layer & 1);
        PROFT(tid_ == 128 && layer == PL, 160 + i);
        if (i >= 2) tile_check(sb + ((uint32_t)ta & 15) * SLOT, g_o + (size_t)m0 * D_ + ((2 * g + (int)(WOORD >> (4 * i))) & 15) * 64, wrow0, lane, ~layer);
        const uint32_t da = dA0 + ((uint32_t)ta & 15) * 1024, db = dB0 + ((uint32_t)tw & 15) * 1024;
        ta >>= 4; tw >>= 4;
        if (WSK && i == 16 - WSK && wu) nbar<6, 256>();
        wgmma_fence();
#pragma unroll
        for (int k = 0; k < 4; ++k) wgmma_n128(acc, D128(da + k * 2), D128(db + k * 128), 1);
        wgmma_commit();
        if (WSK && i == 15 && !wu) asm volatile("bar.arrive 6, 256;" ::: "memory");
        if (i == 0) {
          if (elected) {
            release2(bar + B_E2);
          }
        } else {
          wgmma_wait<1>();
          if (elected && i < 12) release2(bar + B_CONS + (i - 1) * 8);
          if (elected && (unsigned)(i - 13) < 2u && layer + 1 < NLAYERS) release2(bar + B_EMPTYS + (i - 13) * 8);
        }
      }
      const bool last = layer == NLAYERS - 1;
      Tag xt = make_tag(gq, (last || !(UNS & 1)) ? 4 : t, lds_vol(sb + SM_EPOCH) + layer + 1);
      asm volatile("" : "+r"(xt.me), "+r"(xt.mo), "+r"(xt.tg) :: "memory");
      wgmma_wait<0>();
#pragma unroll
      for (int i = 128; i < 192; ++i) asm volatile("" : "+f"(acc[i]) :: "memory");
      if (elected && !last) release2(bar + B_EMPTYS + 16);
      PROFT(tid_ == 128, layer * 16 + 7);
      X_HALF(0, xt);
      if (last) {
        __syncwarp();
        slab_out_half(sb + XS * SLOT, c.out + (size_t)m0 * D_ + g * 128, wrow0, lane);
        X_HALF(1, (Tag{0u, 0u, 0u}));
        __syncwarp();
        slab_out_half(sb + (XS + 1) * SLOT, c.out + (size_t)m0 * D_ + g * 128 + 64, wrow0, lane);
        __syncwarp();
        if (lane == 0) mbar_arrive(bar + B_XDONE);
        PROFT(tid_ == 128, layer * 16 + 24);
        break;
      }
      __syncwarp();
      slab_out_half(sb + XS * SLOT, g_x + (size_t)m0 * D_ + g * 128, wrow0, lane, true);
      __syncwarp();
      if (lane == 0) mbar_arrive(bar + B_XH0);
      nbar_dyn(3 + wu, 128);
    }
  }
}

__device__ __forceinline__ void flag_fetch(uint32_t bar, uint32_t cp, const unsigned int* f) {
  asm volatile("{\n.reg .pred p;\nelect.sync _|p, 0xffffffff;\n@p mbarrier.expect_tx.relaxed.cta.shared::cta.b64 [%2], 64;\n"
               "@p cp.async.bulk.shared::cluster.global.mbarrier::complete_tx::bytes [%0], [%1], 64, [%2];\n}\n"
               ::"r"(cp), "l"(f), "r"(bar + 128) : "memory");
}
__device__ __forceinline__ void src_wait_async(uint32_t bar, uint32_t cp, const unsigned int* f, unsigned int target, int kb, uint32_t& ready, int lane) {
  uint32_t n = 0;
#pragma unroll 1
  while (true) {
    ready |= __ballot_sync(0xffffffffu, (int)(lds_vol(cp + (lane & 15) * 4) - target) >= 0);
    if ((ready >> kb) & 1) break;
    if (n > (1u << 20)) { g_err = 5u; break; }
    if ((n++ & PMOD) == 0) flag_fetch(bar, cp, f);
    __nanosleep(PSL);
  }
}

__device__ __forceinline__ int kblock0(int i, int g) {
  const int j = i >> 1, p = max(g, NCOM) + j - NCOM;
  return (j < NCOM ? j : p < 8 ? p : p - 8 + NCOM) * 2 + (i & 1);
}

__device__ __forceinline__ int wo_kblock(int m, int g) { return (2 * g + (int)((WOORD >> (4 * m)) & 15)) & 15; }

__global__ void __cluster_dims__(2, 1, 1) __launch_bounds__(384, 1)
mega_kernel(const __grid_constant__ CUtensorMap tm_x0, const __grid_constant__ CUtensorMap tm_x,
            const __grid_constant__ CUtensorMap tm_o,
            const __grid_constant__ CUtensorMap tm_wA, const __grid_constant__ CUtensorMap tm_wB,
            const __grid_constant__ CUtensorMap tm_woA, const __grid_constant__ CUtensorMap tm_woB,
                        const bf16* __restrict__ wB, const bf16* __restrict__ wphi, bf16* __restrict__ out) {
  extern __shared__ uint8_t smem_raw[];
  const uint32_t sb = (smem_u32(smem_raw) + 1023u) & ~1023u;
  const uint32_t bar = sb + SM_BAR;
  const int warp = __shfl_sync(0xffffffffu, threadIdx.x >> 5, 0), lane = threadIdx.x & 31;
  if (blockIdx.x >= 128) {
    const int xb = blockIdx.x - 128;
    const int ch = threadIdx.x % 96, rg = threadIdx.x / 96, gg = xb * 2 + ch / 48, sec = (ch % 48) >> 4;
    const uint4* src = reinterpret_cast<const uint4*>(wB + (size_t)rg * 3072 + (sec == 2 ? 0 : 1024 + sec * 1024) + gg * 128 + (ch & 15) * 8);
    float s[8] = {0.f, 0.f, 0.f, 0.f, 0.f, 0.f, 0.f, 0.f};
#pragma unroll 1
    for (int r0 = 0; r0 < 256; r0 += 32) {
      uint4 v[32];
#pragma unroll
      for (int r = 0; r < 32; ++r) v[r] = __ldg(src + (size_t)(r0 + r) * 1536);
#pragma unroll
      for (int r = 0; r < 32; ++r) {
        s[0] += bf_lo(v[r].x); s[1] += bf_hi(v[r].x); s[2] += bf_lo(v[r].y); s[3] += bf_hi(v[r].y);
        s[4] += bf_lo(v[r].z); s[5] += bf_hi(v[r].z); s[6] += bf_lo(v[r].w); s[7] += bf_hi(v[r].w);
      }
    }
    float* cd = g_cs + (ld_relaxed(&g_epoch) & 1) * 6144 + 3072 + xb * 768 + ch * 8;
    red_add4(cd, s[0], s[1], s[2], s[3]);
    red_add4(cd + 4, s[4], s[5], s[6], s[7]);
    nbar<1, 384>();
    if (threadIdx.x < 2) flag_add(&g_csflag[8 + xb * 2 + threadIdx.x].v);
    return;
  }
  const int bid = blockIdx.x;
  const int cr = bid & 1;
  const int g = (bid >> 1) & 7;
  const int rb = (bid >> 4) * 2 + cr;
  const int m0 = rb * 128;

  if (warp < 4) {
    asm volatile("setmaxnreg.dec.sync.aligned.u32 40;");
    asm volatile("barrier.cluster.arrive.relaxed.aligned;" ::: "memory");
    const unsigned int epoch = warp ? ld_relaxed(&g_epoch) : 0u;
    if (warp) cluster_wait();
    unsigned int xbase = epoch * NLAYERS;
    auto wo_a = [&](int layer, int m1) {
      uint64_t ts = ((layer & 1) ? WO_A1 : WO_A0) >> (4 * m1), td = ((layer & 1) ? WO_DA1 : WO_DA0) >> (4 * m1), tk = WOORD >> (4 * m1);
      uint32_t ready = 0u;
#pragma unroll 1
      for (int m = m1; m < 16; m += AW) {
        const int kb = (2 * g + (uint32_t)tk) & 15;
        uint32_t dst = sb + ((uint32_t)ts & 15) * SLOT, fb = bar + B_FULLT + m * 8, eb = bar + B_CONS + ((uint32_t)td & 15) * 8;
        int kc = kb * 64;
        ts >>= 4 * AW; td >>= 4 * AW; tk >>= 4 * AW;
        asm volatile("" : "+r"(dst), "+r"(fb), "+r"(eb), "+r"(kc));
        bool fr = false;
        if (!((ready >> kb) & 1)) {
          PROFT(m == 2 && lane == 0, 64 + layer * 16 + 2);
          if (EP && m > EP) src_wait_async(bar, bar + B_FLG, g_of + rb * 32, xbase + layer + 1, kb, ready, lane);
          else fr = src_wait_tma(g_of + rb * 32, xbase + layer + 1, 1u << kb, ready, lane, eb, layer & 1);
          fence_async_all();
        }
        if (!fr) mbar_wait_u(eb, layer & 1);
        tma_2d_e(dst, &tm_o, kc, m0, fb);
        if (EP && m >= EP && (ready & 0xFFFFu) != 0xFFFFu) flag_fetch(bar, bar + B_FLG, g_of + rb * 32);
        PROFT(lane == 0 && layer == PL, 176 + m);
      }
    };
    auto wo_w = [&](int layer) {
      const CUtensorMap* tx = layer == 0 ? &tm_x0 : &tm_x;
      const CUtensorMap* two = (layer & 1) ? &tm_woB : &tm_woA;
      uint64_t ts = (layer & 1) ? WO_B1 : WO_B0, td = (layer & 1) ? WO_DB1 : WO_DB0, tk = WOORD;
      uint32_t pb = 0;
      fence_async_all();
      mbar_wait_u(bar + B_R0, layer & 1);
      expect_tx_e(bar + B_XOLD, 16384);
      tma_2d_e(sb + (XS + 1) * SLOT, tx, g * 128, m0, bar + B_XOLD);
#pragma unroll 1
      for (int m = 0; m < 16; ++m) {
        uint32_t dst = sb + ((uint32_t)ts & 15) * SLOT + cr * 8192, fb = bar + B_FULLT + m * 8, eb = bar + B_CONS + ((uint32_t)td & 15) * 8;
        int kc = ((2 * g + (uint32_t)tk) & 15) * 64;
        ts >>= 4; td >>= 4; tk >>= 4;
        asm volatile("" : "+r"(dst), "+r"(fb), "+r"(eb), "+r"(kc));
        if (eb != pb) mbar_wait_u(eb, layer & 1);
        pb = eb;
        tma_2d_mc_e(dst, two, g * 128 + cr * 64, kc, fb);
        expect_tx_e(fb, m < 2 ? 16384 : 32768);
        PROFT(lane == 0 && layer == PL, 144 + m);
        if (m == ((layer & 1) ? XB2 : 0)) {
          expect_tx_e(bar + B_XOLD2, 16384);
          tma_2d_e(sb + XS * SLOT, tx, g * 128 + 64, m0, bar + B_XOLD2);
        }
      }
    };
    if (warp == 0) {
      cluster_wait();
      PROFT(lane == 0, 125);
#pragma unroll 1
      for (int layer = 0; layer < NLAYERS; ++layer) {
        const CUtensorMap* tx = layer == 0 ? &tm_x0 : &tm_x;
        const CUtensorMap* tw = (layer & 1) ? &tm_wB : &tm_wA;
        uint32_t s = layer == 0, u = 0, ready = layer == 0 ? 0xFFFFu : 0u;
#pragma unroll 1
        for (int i = s; i < 16; ++i) {
          const int kb = layer == 0 ? kblock0(i, g) : wo_kblock(i, g), kc = kb * 64;
          const uint32_t fb = bar + B_FULLS + s * 8;
          const uint32_t kd = sb + (((QK >> (4 * s)) & 15) + cr) * SLOT, qd = sb + ((QQ >> (4 * s)) & 15) * SLOT + cr * 8192;
          const uint32_t need = 1u << kb;
          const bool ext = i >= 2 || layer == 0, early = ext && (ready & need) == need;
          mbar_wait_u(bar + B_EMPTYS + s * 8, (u + (s ? layer : 0) + 1) & 1);
          if (early) tma_2d_e(sb + ((QA >> (4 * s)) & 15) * SLOT, tx, kc, m0, fb);
          tma_2d_mc_e(kd, tw, 1024 + cr * 1024 + g * 128, kc, fb);
          tma_2d_mc_e(kd + 8192, tw, 1024 + cr * 1024 + g * 128 + 64, kc, fb);
          tma_2d_mc_e(qd, tw, g * 128 + cr * 64, kc, fb);
          expect_tx_e(fb, ext ? 65536 : 49152);
          PROFT(lane == 0 && layer == 0 && i == 1, 31);
          if (layer == 0 && g >= NCOM && i == XPF + (((g - NCOM) * XPM) >> 2)) {
            if (i <= 2) mbar_wait_u(bar + B_FULLS, 0);
            tma_pf_e(&tm_x0, g * 128, m0);
            tma_pf_e(&tm_x0, g * 128 + 64, m0);
          }
          if (layer < 2 && i >= PFS) {
            const int j = i - PFS;
            if (j < 2) tma_pf_e(layer ? &tm_woB : &tm_woA, g * 128 + j * 64, rb * 64);
            else if (j < 8 && layer == 0) tma_pf_e(&tm_wB, ((j >> 1) - 1) * 1024 + g * 128 + (j & 1) * 64, rb * 64);
          }
          if (ext && !early) {
            PROFT(i == 2 && lane == 0, 64 + layer * 16 + 0);
            src_wait_tma(g_xf + rb * 32, xbase + layer + 1, need, ready, lane, fb, 0);
            PROFT(i == 2 && lane == 0, 64 + layer * 16 + 1);
            fence_async_all();
            tma_2d_e(sb + ((QA >> (4 * s)) & 15) * SLOT, tx, kc, m0, fb);
          }
          if (++s == 3) { s = 0; ++u; }
        }
        if (layer == 0) xbase = ld_relaxed(&g_epoch) * NLAYERS;
        if (PG & 1) mbar_wait_u(bar + B_OH1, layer & 1);
        if (PG & 4) mbar_wait_u(bar + B_E3, layer & 1);
        wo_a(layer, 2);
      }
    } else {
      if (warp >= 2) {
        const int h2 = threadIdx.x - 64;
        if (h2 < 16) sts_f(sb + SM_RS + h2 * 4, 0.f);
        if (h2 == 0) sts_f(sb + SM_EPOCH, __uint_as_float(epoch));
        if (h2 < 16) sts_f(bar + B_FLG + h2 * 4, __uint_as_float(xbase));
        mbar_wait_u(bar + B_FULLS, 0);
        colsum(&tm_wA, g_cs + (epoch & 1) * 6144, rb, g, warp - 2, 2, lane, warp == 2 ? sb + SM_SD : (sb + SM_BP + 1023u) & ~1023u, bar + B_CB + (warp - 2) * 8, 0);
#pragma unroll 1
        for (int i = h2; i < 320; i += 64) g_kv[(g * 16 + rb) * 320 + i] = make_uint4(0u, 0u, 0u, 0u);
        fence_async_all();
        nbar<5, 64>();
        if (h2 == 0) flag_add(&g_csflag[g].v);
        PROFT(h2 == 0, 242);
#pragma unroll 1
        for (int i = h2; i < 512; i += 256) {
          uint4 w[4];
#pragma unroll
          for (int j = 0; j < 4; ++j) w[j] = __ldg(reinterpret_cast<const uint4*>(wphi + (size_t)g * 4096) + i + j * 64);
#pragma unroll
          for (int j = 0; j < 4; ++j) sts128(sb + SM_WPHI + ((i >> 2) + j * 16) * 80 + (i & 3) * 16, w[j]);
        }
      }
      if (warp == 1) {
        if (lane >= 27) {
          const CUtensorMap* tm = lane == 27 ? &tm_o : lane == 28 ? &tm_wB : lane == 29 ? &tm_woA : lane == 30 ? &tm_woB : &tm_x;
          asm volatile("prefetch.tensormap [%0];" ::"l"(tm) : "memory");
        }
        __syncwarp();
        {
#pragma unroll 1
          for (int e = 0;; ++e) {
            if (e > 0 && e < NLAYERS) {
              mbar_wait_u(bar + B_XH0, (e - 1) & 1);
              flag_set_x(g_xf + rb * 32 + 2 * g, xbase + e + 1, UNS & 1);
            }
            mbar_wait_u(bar + B_XDONE, e & 1);
            PROFT(e < 4, 64 + e * 16 + 4);
            if (e == NLAYERS) {
              if (bid == 0) g_epoch = epoch + 1;
              break;
            }
            PROFT(e < 4, 64 + e * 16 + 5);
            flag_set(g_xf + rb * 32 + 2 * g + 1, xbase + e + 1);
            PROFT(e < 4, 64 + e * 16 + 7);
            if ((e & 1) == 0) {
#pragma unroll 1
              for (int hp = 0; hp < 2; ++hp) {
                uint4* kvl = g_kv + ((g * 2 + (e >> 1)) * 2 + hp) * 1280;
                mbar_wait_u(bar + B_KVDONE - hp * 32, (e >> 1) & 1);
                PROFT(e == PL, 243 + hp * 4);
                bulk_red_add_e(kvl + rb * 64, sb + (3 + hp) * SLOT + rb * 1024, 16384 - rb * 1024);
                if (rb) bulk_red_add_e(kvl, sb + (3 + hp) * SLOT, rb * 1024);
                bulk_red_add_e(kvl + 1024, sb + (6 + hp) * SLOT, 2048);
                bulk_red_add_e(kvl + 1152, sb + (6 + hp) * SLOT + 8192, 2048);
                bulk_commit();
                PROFT(e < 4, 64 + e * 16 + 6);
              }
              bulk_wait_read0();
              __syncwarp();
              if (lane < 2) release2(bar + B_E1);
              __syncwarp();
            }
            mbar_wait_u(bar + B_OH1, e & 1);
            PROFT(e == PL, 251);
            flag_set_x(g_of + rb * 32 + 2 * g, xbase + e + 1, UNS & 2);
            PROFT(e < 4, 64 + e * 16 + 9);
            mbar_wait_u(bar + B_ODONE, e & 1);
            PROFT(e < 4, 64 + e * 16 + 8);
            flag_set_x(g_of + rb * 32 + 2 * g + 1, xbase + e + 1, UNS & 4);
            PROFT(e < 4, 64 + e * 16 + 11);
          }
        }
      } else {
        const int h2 = threadIdx.x - 64;
        const float* cs = g_cs + (epoch & 1) * 6144;
#pragma unroll 1
        for (int layer = 0; layer < NLAYERS; ++layer) {
          if (warp == 2 && layer < 2) {
            if ((PG & 2) && layer) mbar_wait_u(bar + B_XH0, 0);
            if (lane == 0) flag_wait_t<CSLP>(&g_csflag[layer * 8 + g].v, (epoch + 1) * (16u + layer));
            __syncwarp();
            float4 a[3];
#pragma unroll
            for (int i = 0; i < 3; ++i) a[i] = __ldcg(reinterpret_cast<const float4*>(cs + layer * 3072 + g * 384) + i * 32 + lane);
#pragma unroll 1
            for (int i = 0; i < 3; ++i) {
              const float av[4] = {a[0].x, a[0].y, a[0].z, a[0].w};
              a[0] = a[1]; a[1] = a[2];
#pragma unroll
              for (int j = 0; j < 4; ++j) {
                const float c1 = bf16r(av[j]), c2 = bf16r(av[j] - c1), c3 = (av[j] - c1) - c2;
                sts128(sb + SM_BP + layer * 6144 + ((i * 32 + lane) * 4 + j) * 16, make_uint4(pack_bf16(c1, c2), pack_bf16(c3, 0.f), 0u, 0u));
              }
            }
            fence_async_smem();
            __syncwarp();
            if (lane == 0) mbar_arrive(bar + (layer ? B_CS2 : B_CS));
            PROFT(lane == 0, 64 + layer * 16 + 12);
            if (layer == 0) {
              uint4* hz = g_halo + (rb * 8 + g) * 1024;
#pragma unroll 2
              for (int i = lane; i < 1024; i += 32) hz[i] = make_uint4(0u, 0u, 0u, 0u);
              if (lane < 12) reinterpret_cast<float4*>(g_cs + ((epoch & 1) ^ 1) * 6144 + bid * 48)[lane] = make_float4(0.f, 0.f, 0.f, 0.f);
              g_stats[(2 + (lane >> 4)) * S_ + m0 + g * 16 + (lane & 15)] = make_float2(0.f, 0.f);
              __syncwarp();
              if (lane == 0) flag_add(&g_csflag[8 + g].v);
            }
          }
          if (warp == 3) {
            const bool hal = (layer & 1) && rb > 0;
            {
              uint32_t rdy = 0u;
              src_wait<256>(g_xf + rb * 32, xbase + layer + 1, 0xAAAAu, rdy, lane);
              rdy = 0u;
              if (hal) src_wait<256>(g_xf + (rb - 1) * 32, xbase + layer + 1, 0xAAAAu, rdy, lane);
            }
            float2 u[5];
            const float2* sp = g_stats + layer * S_ + m0 + lane;
#pragma unroll
            for (int i = 0; i < 4; ++i) u[i] = __ldcg(sp + i * 32);
            u[4] = __ldcg(hal ? sp - 16 : sp);
            if (layer == 3) g_stats[(lane >> 4) * S_ + m0 + g * 16 + (lane & 15)] = make_float2(0.f, 0.f);
#pragma unroll 1
            for (int i = 0; i < (hal ? 5 : 4); ++i) {
              const int r = i < 4 ? 16 + i * 32 + lane : lane;
              const float sum = u[0].x, sq = u[0].y;
              u[0] = u[1]; u[1] = u[2]; u[2] = u[3]; u[3] = u[4];
              const float mean = sum * (1.f / D_);
              const float var = fmaxf(fmaf(-sum, mean, sq) * (1.f / D_), 0.f);
              const float sd = bf16r(sqrtf(bf16r(bf16r(var) + 1e-5f)));
              sts_f(sb + SM_RS + r * 4, 1.f / sd);
              if (i < 4) {
                const float hm = -0.5f * bf16r(mean);
                const uint32_t s2 = pack_bf16(sd, sd);
                if (!(layer & 1)) sts128(sb + SM_SD + (r - 16) * 64 + ((r >> 1) & 3) * 16, make_uint4(s2, s2, s2, s2));
                sts128(sb + SM_AP + (r - 16) * 16, make_uint4(pack_bf16(hm, hm), pack_bf16(hm, 0.f), 0u, 0u));
              }
            }
            fence_async_smem();
            __syncwarp();
            if (lane == 0) mbar_arrive(bar + B_STAT);
            PROFT(lane == 0, 64 + layer * 16 + 14);
            wo_w(__shfl_sync(0xffffffffu, layer, 0));
          }
        }
      }
    }
    __syncwarp();
    asm volatile("barrier.cluster.arrive.relaxed.aligned;\nbarrier.cluster.wait.aligned;\n" ::: "memory");
  } else {
    if (warp == 5) {
      if (lane == 0) {
        mbar_init(bar + B_FULLS, 1);
        asm volatile("fence.mbarrier_init.release.cluster;" ::: "memory");
      }
      __syncwarp();
      expect_tx_e(bar + B_FULLS, 65536);
      tma_2d_e(sb + XS * SLOT, &tm_x0, 0, m0, bar + B_FULLS);
#pragma unroll
      for (int j = 0; j < 6; ++j)
        tma_2d_e(sb + (j < 4 ? j + 4 : j - 2) * 8192, &tm_wA, (j < 4 ? 1024 + (j >> 1) * 1024 : 0) + g * 128 + (j & 1) * 64, 0, bar + B_FULLS);
      PROFT(lane == 0, 241);
    }
    if (lane < 8 && warp != 5 && threadIdx.x != 128) {
      const int i = (warp - 4) * 8 + lane;
      mbar_init(bar + i * 8, i < 32 ? 1u << ((BAR_CNT >> (2 * i)) & 3) : i < 48 ? 1u : (i == 59 || i == 60) ? 16u : i < 63 ? 4u : 8u);
      asm volatile("fence.mbarrier_init.release.cluster;" ::: "memory");
    }
    __syncwarp();
    asm volatile("barrier.cluster.arrive.relaxed.aligned;" ::: "memory");
    asm volatile("setmaxnreg.inc.sync.aligned.u32 232;");
    cluster_wait();
    PROFT(threadIdx.x == 128, 0);
    Ctx c; c.sb = sb; c.g = g; c.rb = rb; c.cu = warp - 4; c.out = out;
    consumer(c);
    asm volatile("bar.warp.sync 0xffffffff;\nbarrier.cluster.arrive.relaxed.aligned;\nbarrier.cluster.wait.aligned;\n" ::: "memory");
  }
}

typedef CUresult (*PFN_encodeTiled)(CUtensorMap*, CUtensorMapDataType, cuuint32_t, void*, const cuuint64_t*, const cuuint64_t*,
                                    const cuuint32_t*, const cuuint32_t*, CUtensorMapInterleave, CUtensorMapSwizzle,
                                    CUtensorMapL2promotion, CUtensorMapFloatOOBfill);

static CUtensorMap make_map(PFN_encodeTiled enc, const void* ptr, uint64_t cols, uint64_t rows, uint32_t box_c, uint32_t box_r, uint32_t nb = 1) {
  CUtensorMap m;
  cuuint64_t dims[3] = {nb > 1 ? box_c : cols, rows, cols / box_c};
  cuuint64_t strides[2] = {cols * 2, box_c * 2};
  cuuint32_t box[3] = {box_c, box_r, nb};
  cuuint32_t es[3] = {1, 1, 1};
  CUresult r = enc(&m, CU_TENSOR_MAP_DATA_TYPE_BFLOAT16, nb > 1 ? 3 : 2, const_cast<void*>(ptr), dims, strides, box, es, CU_TENSOR_MAP_INTERLEAVE_NONE,
      CU_TENSOR_MAP_SWIZZLE_128B, CU_TENSOR_MAP_L2_PROMOTION_L2_256B, CU_TENSOR_MAP_FLOAT_OOB_FILL_NONE);
  (void)r;
  return m;
}

extern "C" void kernel_launch(void* const* d_in, const int* in_sizes, int n_in, void* d_out, int out_size) {
  const bf16* A_x = (const bf16*)d_in[0];
  const bf16* A_wqkv = (const bf16*)d_in[1];
  const bf16* A_wphi = (const bf16*)d_in[2];
  const bf16* A_wo = (const bf16*)d_in[3];
  const bf16* B_wqkv = (const bf16*)d_in[5];
  const bf16* B_wo = (const bf16*)d_in[6];
  bf16* out = (bf16*)d_out;

  static PFN_encodeTiled enc = nullptr;
  static bf16 *p_x, *p_o;
  if (!enc) {
    void* fn = nullptr; cudaDriverEntryPointQueryResult qr;
    cudaGetDriverEntryPoint("cuTensorMapEncodeTiled", &fn, cudaEnableDefault, &qr);
    enc = (PFN_encodeTiled)fn;
    cudaGetSymbolAddress((void**)&p_x, g_x);
    cudaGetSymbolAddress((void**)&p_o, g_o);
    cudaFuncSetAttribute(mega_kernel, cudaFuncAttributeMaxDynamicSharedMemorySize, SM_TOTAL);
  }
  CUtensorMap tm_x0 = make_map(enc, A_x, 1024, 2048, 64, 128);
  CUtensorMap tm_x = make_map(enc, p_x, 1024, 2048, 64, 128);
  CUtensorMap tm_o = make_map(enc, p_o, 1024, 2048, 64, 128);
  CUtensorMap tm_wA = make_map(enc, A_wqkv, 3072, 1024, 64, 64);
  CUtensorMap tm_wB = make_map(enc, B_wqkv, 3072, 1024, 64, 64);
  CUtensorMap tm_woA = make_map(enc, A_wo, 1024, 1024, 64, 64);
  CUtensorMap tm_woB = make_map(enc, B_wo, 1024, 1024, 64, 64);
  mega_kernel<<<128 + NX, 384, SM_TOTAL, cudaStreamPerThread>>>(tm_x0, tm_x, tm_o, tm_wA, tm_wB, tm_woA, tm_woB,
                                                           B_wqkv, A_wphi, out);
}
```

```cpp
#include <cuda_runtime.h>
#include <cuda_bf16.h>
#include <cuda.h>
#include <stdint.h>

typedef __nv_bfloat16 bf16;

constexpr int S_ = 2048, D_ = 1024;

struct __align__(128) Flag { unsigned int v; unsigned int pad[31]; };
__device__ __align__(1024) bf16 g_x[S_ * D_];
__device__ __align__(1024) bf16 g_o[S_ * D_];
__device__ __align__(1024) uint4 g_halo[128 * 2 * 512];
__device__ __align__(1024) uint4 g_kv[8 * 2 * 2 * 1280];
__device__ __align__(1024) float2 g_stats[4 * S_];
__device__ __align__(1024) float g_cs[2 * 2 * 3072];
__device__ Flag g_csflag[16];
__device__ __align__(128) unsigned int g_xf[16 * 32], g_of[16 * 32];
__device__ unsigned int g_epoch, g_err;
#define PROFT(cond, idx) asm volatile("" ::: "memory")

__device__ __forceinline__ uint32_t smem_u32(const void* p) { return (uint32_t)__cvta_generic_to_shared(p); }
__device__ __forceinline__ void mbar_init(uint32_t bar, uint32_t count) {
  asm volatile("mbarrier.init.shared::cta.b64 [%0], %1;" ::"r"(bar), "r"(count) : "memory");
}
__device__ __forceinline__ void mbar_expect_tx(uint32_t bar, uint32_t bytes) {
  asm volatile("mbarrier.arrive.expect_tx.shared::cta.b64 _, [%0], %1;" ::"r"(bar), "r"(bytes) : "memory");
}
__device__ __forceinline__ void mbar_arrive(uint32_t bar) {
  asm volatile("mbarrier.arrive.shared::cta.b64 _, [%0];" ::"r"(bar) : "memory");
}
__device__ __forceinline__ bool mbar_try_wait(uint32_t bar, uint32_t parity) {
  uint32_t ok;
  asm volatile("{\n.reg .pred p;\nmbarrier.try_wait.parity.shared::cta.b64 p, [%1], %2;\nselp.b32 %0, 1, 0, p;\n}\n"
               : "=r"(ok) : "r"(bar), "r"(parity) : "memory");
  return ok != 0;
}
__device__ __forceinline__ bool mbar_test_wait(uint32_t bar, uint32_t parity) {
  uint32_t ok;
  asm volatile("{\n.reg .pred p;\nmbarrier.test_wait.parity.shared::cta.b64 p, [%1], %2;\nselp.b32 %0, 1, 0, p;\n}\n"
               : "=r"(ok) : "r"(bar), "r"(parity) : "memory");
  return ok != 0;
}
__device__ __forceinline__ uint64_t gtimer() {
  uint64_t t; asm volatile("mov.u64 %0, %globaltimer;" : "=l"(t)); return t;
}
__device__ __forceinline__ void mbar_wait(uint32_t bar, uint32_t parity) {
  uint32_t n = 0;
#pragma unroll 1
  while (!mbar_try_wait(bar, parity)) {
    if (++n > (1u << 22)) { g_err = 1u; break; }
  }
}
__device__ __forceinline__ unsigned int ld_acquire(const unsigned int* p) {
  unsigned int v; asm volatile("ld.acquire.gpu.global.u32 %0, [%1];" : "=r"(v) : "l"(p) : "memory"); return v;
}
__device__ __forceinline__ void flag_add(unsigned int* p) {
  asm volatile("red.release.gpu.global.add.u32 [%0], 1;" ::"l"(p) : "memory");
}
__device__ __forceinline__ void flag_set(unsigned int* p, unsigned int v) {
  asm volatile("st.release.gpu.global.u32 [%0], %1;" ::"l"(p), "r"(v) : "memory");
}
__device__ __forceinline__ void flag_set_x(unsigned int* p, unsigned int v, bool rlx) {
  if (rlx) asm volatile("st.relaxed.gpu.global.u32 [%0], %1;" ::"l"(p), "r"(v) : "memory"); else flag_set(p, v);
}
template <int SLEEP>
__device__ __forceinline__ void src_wait(const unsigned int* f, unsigned int target, uint32_t need, uint32_t& ready, int lane) {
  uint32_t n = 0;
#pragma unroll 1
  while ((ready & need) != need) {
    const unsigned int v = ld_acquire(f + (lane & 15));
    ready = __ballot_sync(0xffffffffu, (int)(v - target) >= 0);
    if (SLEEP) { if ((ready & need) != need) __nanosleep(SLEEP); }
    if (++n > (1u << 20)) { g_err = 3u; break; }
  }
  __syncwarp();
}
__device__ __forceinline__ unsigned int ld_relaxed(const unsigned int* p) {
  unsigned int v; asm volatile("ld.relaxed.gpu.global.u32 %0, [%1];" : "=r"(v) : "l"(p) : "memory"); return v;
}
__device__ __forceinline__ bool src_wait_tma(const unsigned int* f, unsigned int target, uint32_t need, uint32_t& ready, int lane, uint32_t eb, uint32_t par) {
  uint32_t n = 0;
  bool fr = false;
#pragma unroll 1
  while ((ready & need) != need) {
    const unsigned int v = ld_acquire(f + (lane & 15));
    fr = __all_sync(0xffffffffu, mbar_test_wait(eb, par));
    ready = __ballot_sync(0xffffffffu, (int)(v - target) >= 0);
    if (++n > (1u << 20)) { g_err = 3u; break; }
  }
  return fr;
}
__device__ __forceinline__ uint4 ld_relaxed4(const uint4* p) {
  uint4 v; asm volatile("ld.relaxed.gpu.global.v4.u32 {%0,%1,%2,%3}, [%4];" : "=r"(v.x), "=r"(v.y), "=r"(v.z), "=r"(v.w) : "l"(p) : "memory"); return v;
}
__device__ __forceinline__ void st_relaxed4(uint4* p, uint32_t a, uint32_t b, uint32_t c, uint32_t d) {
  asm volatile("st.relaxed.gpu.global.v4.u32 [%0], {%1,%2,%3,%4};" ::"l"(p), "r"(a), "r"(b), "r"(c), "r"(d) : "memory");
}
template <int SLEEP>
__device__ __forceinline__ void flag_wait_t(const unsigned int* p, unsigned int target) {
  uint32_t n = 0;
#pragma unroll 1
  while ((int)(ld_acquire(p) - target) < 0) {
    if (SLEEP) __nanosleep(SLEEP);
    if (++n > (1u << 20)) { g_err = 2u; break; }
  }
}
__device__ __forceinline__ void flag_wait(const unsigned int* p, unsigned int target) { flag_wait_t<0>(p, target); }
__device__ __forceinline__ void flag_wait_slow(const unsigned int* p, unsigned int target) { flag_wait_t<256>(p, target); }
__device__ __forceinline__ void tma_load_2d(uint32_t dst, const CUtensorMap* tm, int c0, int c1, uint32_t bar) {
  asm volatile("cp.async.bulk.tensor.2d.shared::cluster.global.mbarrier::complete_tx::bytes [%0], [%1, {%2, %3}], [%4];"
               ::"r"(dst), "l"(tm), "r"(c0), "r"(c1), "r"(bar) : "memory");
}
__device__ __forceinline__ void tma_load_2d_mc(uint32_t dst, const CUtensorMap* tm, int c0, int c1, uint32_t bar, uint16_t mask) {
  asm volatile("cp.async.bulk.tensor.2d.shared::cluster.global.mbarrier::complete_tx::bytes.multicast::cluster [%0], [%1, {%2, %3}], [%4], %5;"
               ::"r"(dst), "l"(tm), "r"(c0), "r"(c1), "r"(bar), "h"(mask) : "memory");
}
__device__ __forceinline__ void mbar_wait_u(uint32_t bar, uint32_t parity) {
  uint32_t n = 0;
#pragma unroll 1
  while (!__all_sync(0xffffffffu, mbar_try_wait(bar, parity))) {
    if (++n > (1u << 22)) { g_err = 1u; break; }
  }
}
__device__ __forceinline__ void expect_tx_e(uint32_t bar, uint32_t bytes) {
  asm volatile("{\n.reg .pred p;\nelect.sync _|p, 0xffffffff;\n@p mbarrier.arrive.expect_tx.shared::cta.b64 _, [%0], %1;\n}\n" ::"r"(bar), "r"(bytes) : "memory");
}
__device__ __forceinline__ void tma_2d_e(uint32_t dst, const CUtensorMap* tm, int c0, int c1, uint32_t bar) {
  asm volatile("{\n.reg .pred p;\nelect.sync _|p, 0xffffffff;\n"
               "@p cp.async.bulk.tensor.2d.shared::cluster.global.mbarrier::complete_tx::bytes [%0], [%1, {%2, %3}], [%4];\n}\n"
               ::"r"(dst), "l"(tm), "r"(c0), "r"(c1), "r"(bar) : "memory");
}
__device__ __forceinline__ void tma_2d_mc_e(uint32_t dst, const CUtensorMap* tm, int c0, int c1, uint32_t bar) {
  asm volatile("{\n.reg .pred p;\nelect.sync _|p, 0xffffffff;\n"
               "@p cp.async.bulk.tensor.2d.shared::cluster.global.mbarrier::complete_tx::bytes.multicast::cluster [%0], [%1, {%2, %3}], [%4], %5;\n}\n"
               ::"r"(dst), "l"(tm), "r"(c0), "r"(c1), "r"(bar), "h"((uint16_t)3) : "memory");
}
__device__ __forceinline__ void tma_pf_e(const CUtensorMap* tm, int c0, int c1) {
  asm volatile("{\n.reg .pred p;\nelect.sync _|p, 0xffffffff;\n"
               "@p cp.async.bulk.prefetch.tensor.2d.L2.global.tile [%0, {%1, %2}];\n}\n" ::"l"(tm), "r"(c0), "r"(c1) : "memory");
}
__device__ __forceinline__ void tma_2d_to_e(uint32_t dst, const CUtensorMap* tm, int c0, int c1, uint32_t bar, uint32_t mask) {
  asm volatile("{\n.reg .pred p;\nelect.sync _|p, 0xffffffff;\n"
               "@p cp.async.bulk.tensor.2d.shared::cluster.global.mbarrier::complete_tx::bytes.multicast::cluster [%0], [%1, {%2, %3}], [%4], %5;\n}\n"
               ::"r"(dst), "l"(tm), "r"(c0), "r"(c1), "r"(bar), "h"((uint16_t)mask) : "memory");
}
__device__ __forceinline__ void tma_3d_mc_e(uint32_t dst, const CUtensorMap* tm, int c1, int c2, uint32_t bar) {
  asm volatile("{\n.reg .pred p;\nelect.sync _|p, 0xffffffff;\n"
               "@p cp.async.bulk.tensor.3d.shared::cluster.global.mbarrier::complete_tx::bytes.multicast::cluster [%0], [%1, {%6, %2, %3}], [%4], %5;\n}\n"
               ::"r"(dst), "l"(tm), "r"(c1), "r"(c2), "r"(bar), "h"((uint16_t)3), "r"(0) : "memory");
}
__device__ __forceinline__ uint32_t poll_flags(const unsigned int* f, unsigned int target, int lane) {
  const unsigned int v = ld_acquire(f + (lane & 15));
  const uint32_t r = __ballot_sync(0xffffffffu, (int)(v - target) >= 0);
  __syncwarp();
  return r;
}
__device__ __forceinline__ void mbar_arrive_cluster(uint32_t local_bar, uint32_t rank) {
  asm volatile("{\n.reg .b32 ra;\nmapa.shared::cluster.u32 ra, %0, %1;\nmbarrier.arrive.shared::cluster.b64 _, [ra];\n}\n"
               ::"r"(local_bar), "r"(rank) : "memory");
}
__device__ __forceinline__ void release2(uint32_t bar) { mbar_arrive_cluster(bar, 0); mbar_arrive_cluster(bar, 1); }
__device__ __forceinline__ void tma_store_2d(const CUtensorMap* tm, uint32_t src, int c0, int c1) {
  asm volatile("cp.async.bulk.tensor.2d.global.shared::cta.bulk_group [%0, {%2, %3}], [%1];"
               ::"l"(tm), "r"(src), "r"(c0), "r"(c1) : "memory");
}
__device__ __forceinline__ void bulk_store(void* dst, uint32_t src, uint32_t bytes) {
  asm volatile("cp.async.bulk.global.shared::cta.bulk_group [%0], [%1], %2;" ::"l"(dst), "r"(src), "r"(bytes) : "memory");
}
__device__ __forceinline__ void bulk_load(uint32_t dst, const void* src, uint32_t bytes, uint32_t bar) {
  asm volatile("cp.async.bulk.shared::cluster.global.mbarrier::complete_tx::bytes [%0], [%1], %2, [%3];" ::"r"(dst), "l"(src), "r"(bytes), "r"(bar) : "memory");
}
__device__ __forceinline__ void bulk_red_add(void* dst, uint32_t src, uint32_t bytes) {
  asm volatile("cp.reduce.async.bulk.global.shared::cta.bulk_group.add.f32 [%0], [%1], %2;" ::"l"(dst), "r"(src), "r"(bytes) : "memory");
}
__device__ __forceinline__ void bulk_red_add_e(void* dst, uint32_t src, uint32_t bytes) {
  asm volatile("{\n.reg .pred p;\nelect.sync _|p, 0xffffffff;\n@p cp.reduce.async.bulk.global.shared::cta.bulk_group.add.f32 [%0], [%1], %2;\n}\n" ::"l"(dst), "r"(src), "r"(bytes) : "memory");
}
__device__ __forceinline__ void bulk_commit() { asm volatile("cp.async.bulk.commit_group;" ::: "memory"); }
__device__ __forceinline__ void bulk_wait_read0() { asm volatile("cp.async.bulk.wait_group.read 0;" ::: "memory"); }
__device__ __forceinline__ void bulk_wait0() { asm volatile("cp.async.bulk.wait_group 0;" ::: "memory"); }
__device__ __forceinline__ void fence_async_smem() { asm volatile("fence.proxy.async.shared::cta;" ::: "memory"); }
__device__ __forceinline__ void fence_async_all() { asm volatile("fence.proxy.async.global;" ::: "memory"); }
__device__ __forceinline__ void wgmma_fence() { asm volatile("wgmma.fence.sync.aligned;" ::: "memory"); }
__device__ __forceinline__ void wgmma_commit() { asm volatile("wgmma.commit_group.sync.aligned;" ::: "memory"); }
template <int N> __device__ __forceinline__ void wgmma_wait() { asm volatile("wgmma.wait_group.sync.aligned %0;" ::"n"(N) : "memory"); }
__device__ __forceinline__ void cluster_arrive() { asm volatile("barrier.cluster.arrive.release.aligned;" ::: "memory"); }
__device__ __forceinline__ void cluster_wait() { asm volatile("barrier.cluster.wait.acquire.aligned;" ::: "memory"); }
template <int ID, int N> __device__ __forceinline__ void nbar() { asm volatile("bar.sync %0, %1;" ::"n"(ID), "n"(N) : "memory"); }
__device__ __forceinline__ uint64_t make_desc(uint32_t addr, uint32_t lbo_bytes, uint32_t sbo_bytes) {
  uint64_t d = 0;
  d |= (uint64_t)((addr & 0x3FFFF) >> 4);
  d |= (uint64_t)((lbo_bytes >> 4) & 0x3FFF) << 16;
  d |= (uint64_t)((sbo_bytes >> 4) & 0x3FFF) << 32;
  d |= (uint64_t)1 << 62;
  return d;
}
__device__ __forceinline__ uint64_t desc64(uint32_t lo, uint32_t hi) { return (uint64_t)lo | ((uint64_t)hi << 32); }
__device__ __forceinline__ uint32_t pack_bf16(float lo, float hi) {
  uint32_t r; asm("cvt.rn.bf16x2.f32 %0, %1, %2;" : "=r"(r) : "f"(hi), "f"(lo)); return r;
}
__device__ __forceinline__ uint32_t mul_bf16x2(uint32_t a, uint32_t s, bool hi) {
  __nv_bfloat162 x = *reinterpret_cast<__nv_bfloat162*>(&a), y = *reinterpret_cast<__nv_bfloat162*>(&s);
  x = __hmul2(x, hi ? __high2bfloat162(y) : __low2bfloat162(y));
  return *reinterpret_cast<uint32_t*>(&x);
}
__device__ __forceinline__ float bf16r(float x) { return __bfloat162float(__float2bfloat16_rn(x)); }
__device__ __forceinline__ float bf_lo(uint32_t u) { return __uint_as_float(u << 16); }
__device__ __forceinline__ float bf_hi(uint32_t u) { return __uint_as_float(u & 0xFFFF0000u); }
__device__ __forceinline__ float ex2(float x) { float r; asm("ex2.approx.ftz.f32 %0, %1;" : "=f"(r) : "f"(x)); return r; }
__device__ __forceinline__ float rcp(float x) { float r; asm("rcp.approx.ftz.f32 %0, %1;" : "=f"(r) : "f"(x)); return r; }
__device__ __forceinline__ void mma_bf16(float (&d)[4], uint32_t a0, uint32_t a1, uint32_t a2, uint32_t a3, uint32_t b0, uint32_t b1) {
  asm("mma.sync.aligned.m16n8k16.row.col.f32.bf16.bf16.f32 {%0,%1,%2,%3}, {%4,%5,%6,%7}, {%8,%9}, {%0,%1,%2,%3};"
               : "+f"(d[0]), "+f"(d[1]), "+f"(d[2]), "+f"(d[3]) : "r"(a0), "r"(a1), "r"(a2), "r"(a3), "r"(b0), "r"(b1));
}
__device__ __forceinline__ void ldsm_x4(uint32_t& r0, uint32_t& r1, uint32_t& r2, uint32_t& r3, uint32_t addr) {
  asm volatile("ldmatrix.sync.aligned.m8n8.x4.shared.b16 {%0,%1,%2,%3}, [%4];"
               : "=r"(r0), "=r"(r1), "=r"(r2), "=r"(r3) : "r"(addr) : "memory");
}
__device__ __forceinline__ void ldsm_x4_t(uint32_t& r0, uint32_t& r1, uint32_t& r2, uint32_t& r3, uint32_t addr) {
  asm volatile("ldmatrix.sync.aligned.m8n8.x4.trans.shared.b16 {%0,%1,%2,%3}, [%4];"
               : "=r"(r0), "=r"(r1), "=r"(r2), "=r"(r3) : "r"(addr) : "memory");
}
__device__ __forceinline__ void ldsm_x2_t(uint32_t& r0, uint32_t& r1, uint32_t addr) {
  asm volatile("ldmatrix.sync.aligned.m8n8.x2.trans.shared.b16 {%0,%1}, [%2];"
               : "=r"(r0), "=r"(r1) : "r"(addr) : "memory");
}
__device__ __forceinline__ void stsm_x4(uint32_t addr, uint32_t r0, uint32_t r1, uint32_t r2, uint32_t r3) {
  asm volatile("stmatrix.sync.aligned.m8n8.x4.shared.b16 [%0], {%1,%2,%3,%4};"
               ::"r"(addr), "r"(r0), "r"(r1), "r"(r2), "r"(r3) : "memory");
}
__device__ __forceinline__ void stsm_x4_p(bool on, uint32_t addr, uint32_t r0, uint32_t r1, uint32_t r2, uint32_t r3) {
  asm volatile("{\n.reg .pred p;\nsetp.ne.b32 p, %5, 0;\n@p stmatrix.sync.aligned.m8n8.x4.shared.b16 [%0], {%1,%2,%3,%4};\n}\n"
               ::"r"(addr), "r"(r0), "r"(r1), "r"(r2), "r"(r3), "r"((int)on) : "memory");
}
__device__ __forceinline__ float2 lds_f2(uint32_t addr) {
  float2 v; asm volatile("ld.shared.v2.f32 {%0,%1}, [%2];" : "=f"(v.x), "=f"(v.y) : "r"(addr) : "memory"); return v;
}
__device__ __forceinline__ uint4 lds128(uint32_t addr) {
  uint4 v; asm volatile("ld.shared.v4.b32 {%0,%1,%2,%3}, [%4];" : "=r"(v.x), "=r"(v.y), "=r"(v.z), "=r"(v.w) : "r"(addr) : "memory"); return v;
}
__device__ __forceinline__ void sts128(uint32_t addr, uint4 v) {
  asm volatile("st.shared.v4.b32 [%0], {%1,%2,%3,%4};" ::"r"(addr), "r"(v.x), "r"(v.y), "r"(v.z), "r"(v.w) : "memory");
}
__device__ __forceinline__ float lds_f(uint32_t addr) {
  float v; asm volatile("ld.shared.f32 %0, [%1];" : "=f"(v) : "r"(addr) : "memory"); return v;
}
__device__ __forceinline__ uint32_t lds_vol(uint32_t addr) {
  uint32_t v; asm volatile("ld.volatile.shared.u32 %0, [%1];" : "=r"(v) : "r"(addr) : "memory"); return v;
}
__device__ __forceinline__ void sts16(uint32_t addr, uint32_t v) {
  asm volatile("st.shared.u16 [%0], %1;" ::"r"(addr), "h"((unsigned short)v) : "memory");
}
__device__ __forceinline__ void nbar_dyn(int id, int n) { asm volatile("bar.sync %0, %1;" ::"r"(id), "r"(n) : "memory"); }
__device__ __forceinline__ uint64_t make_desc_ns(uint32_t addr, uint32_t lbo_bytes, uint32_t sbo_bytes) {
  return (uint64_t)((addr & 0x3FFFF) >> 4) | ((uint64_t)(lbo_bytes >> 4) << 16) | ((uint64_t)(sbo_bytes >> 4) << 32);
}
__device__ __forceinline__ void sts_f(uint32_t addr, float v) { asm volatile("st.shared.f32 [%0], %1;" ::"r"(addr), "f"(v) : "memory"); }
__device__ __forceinline__ void sts64(uint32_t addr, uint32_t a, uint32_t b) {
  asm volatile("st.shared.v2.b32 [%0], {%1,%2};" ::"r"(addr), "r"(a), "r"(b) : "memory");
}
__device__ __forceinline__ void sts_f2(uint32_t addr, float a, float b) {
  asm volatile("st.shared.v2.f32 [%0], {%1,%2};" ::"r"(addr), "f"(a), "f"(b) : "memory");
}
__device__ __forceinline__ void red_add2(float* p, float a, float b) {
  asm volatile("red.global.add.v2.f32 [%0], {%1,%2};" ::"l"(p), "f"(a), "f"(b) : "memory");
}
__device__ __forceinline__ void red_add4(float* p, float a, float b, float c, float d) {
  asm volatile("red.global.add.v4.f32 [%0], {%1,%2,%3,%4};" ::"l"(p), "f"(a), "f"(b), "f"(c), "f"(d) : "memory");
}
__device__ __forceinline__ void red_add1(float* p, float a) {
  asm volatile("red.global.add.f32 [%0], %1;" ::"l"(p), "f"(a) : "memory");
}
__device__ __forceinline__ void l2_prefetch(const void* p, uint32_t bytes) {
  asm volatile("cp.async.bulk.prefetch.L2.global [%0], %1;" ::"l"(p), "r"(bytes) : "memory");
}

__device__ __forceinline__ void wgmma_n256(float (&d)[192], uint64_t da, uint64_t db, int scale_d) {
  asm volatile("{\n.reg .pred p;\nsetp.ne.b32 p, %130, 0;\n"
    "wgmma.mma_async.sync.aligned.m64n256k16.f32.bf16.bf16 {%0, %1, %2, %3, %4, %5, %6, %7, %8, %9, %10, %11, %12, %13, %14, %15, %16, %17, %18, %19, %20, %21, %22, %23, %24, %25, %26, %27, %28, %29, %30, %31, %32, %33, %34, %35, %36, %37, %38, %39, %40, %41, %42, %43, %44, %45, %46, %47, %48, %49, %50, %51, %52, %53, %54, %55, %56, %57, %58, %59, %60, %61, %62, %63, %64, %65, %66, %67, %68, %69, %70, %71, %72, %73, %74, %75, %76, %77, %78, %79, %80, %81, %82, %83, %84, %85, %86, %87, %88, %89, %90, %91, %92, %93, %94, %95, %96, %97, %98, %99, %100, %101, %102, %103, %104, %105, %106, %107, %108, %109, %110, %111, %112, %113, %114, %115, %116, %117, %118, %119, %120, %121, %122, %123, %124, %125, %126, %127}, %128, %129, p, 1, 1, 0, 1;\n}\n"
    : "+f"(d[0]), "+f"(d[1]), "+f"(d[2]), "+f"(d[3]), "+f"(d[4]), "+f"(d[5]), "+f"(d[6]), "+f"(d[7]), "+f"(d[8]), "+f"(d[9]), "+f"(d[10]), "+f"(d[11]), "+f"(d[12]), "+f"(d[13]), "+f"(d[14]), "+f"(d[15]), "+f"(d[16]), "+f"(d[17]), "+f"(d[18]), "+f"(d[19]), "+f"(d[20]), "+f"(d[21]), "+f"(d[22]), "+f"(d[23]), "+f"(d[24]), "+f"(d[25]), "+f"(d[26]), "+f"(d[27]), "+f"(d[28]), "+f"(d[29]), "+f"(d[30]), "+f"(d[31]), "+f"(d[32]), "+f"(d[33]), "+f"(d[34]), "+f"(d[35]), "+f"(d[36]), "+f"(d[37]), "+f"(d[38]), "+f"(d[39]), "+f"(d[40]), "+f"(d[41]), "+f"(d[42]), "+f"(d[43]), "+f"(d[44]), "+f"(d[45]), "+f"(d[46]), "+f"(d[47]), "+f"(d[48]), "+f"(d[49]), "+f"(d[50]), "+f"(d[51]), "+f"(d[52]), "+f"(d[53]), "+f"(d[54]), "+f"(d[55]), "+f"(d[56]), "+f"(d[57]), "+f"(d[58]), "+f"(d[59]), "+f"(d[60]), "+f"(d[61]), "+f"(d[62]), "+f"(d[63]), "+f"(d[64]), "+f"(d[65]), "+f"(d[66]), "+f"(d[67]), "+f"(d[68]), "+f"(d[69]), "+f"(d[70]), "+f"(d[71]), "+f"(d[72]), "+f"(d[73]), "+f"(d[74]), "+f"(d[75]), "+f"(d[76]), "+f"(d[77]), "+f"(d[78]), "+f"(d[79]), "+f"(d[80]), "+f"(d[81]), "+f"(d[82]), "+f"(d[83]), "+f"(d[84]), "+f"(d[85]), "+f"(d[86]), "+f"(d[87]), "+f"(d[88]), "+f"(d[89]), "+f"(d[90]), "+f"(d[91]), "+f"(d[92]), "+f"(d[93]), "+f"(d[94]), "+f"(d[95]), "+f"(d[96]), "+f"(d[97]), "+f"(d[98]), "+f"(d[99]), "+f"(d[100]), "+f"(d[101]), "+f"(d[102]), "+f"(d[103]), "+f"(d[104]), "+f"(d[105]), "+f"(d[106]), "+f"(d[107]), "+f"(d[108]), "+f"(d[109]), "+f"(d[110]), "+f"(d[111]), "+f"(d[112]), "+f"(d[113]), "+f"(d[114]), "+f"(d[115]), "+f"(d[116]), "+f"(d[117]), "+f"(d[118]), "+f"(d[119]), "+f"(d[120]), "+f"(d[121]), "+f"(d[122]), "+f"(d[123]), "+f"(d[124]), "+f"(d[125]), "+f"(d[126]), "+f"(d[127])
    : "l"(da), "l"(db), "r"(scale_d));
}
__device__ __forceinline__ void wgmma_n128(float (&d)[192], uint64_t da, uint64_t db, int scale_d) {
  asm volatile("{\n.reg .pred p;\nsetp.ne.b32 p, %66, 0;\n"
    "wgmma.mma_async.sync.aligned.m64n128k16.f32.bf16.bf16 {%0, %1, %2, %3, %4, %5, %6, %7, %8, %9, %10, %11, %12, %13, %14, %15, %16, %17, %18, %19, %20, %21, %22, %23, %24, %25, %26, %27, %28, %29, %30, %31, %32, %33, %34, %35, %36, %37, %38, %39, %40, %41, %42, %43, %44, %45, %46, %47, %48, %49, %50, %51, %52, %53, %54, %55, %56, %57, %58, %59, %60, %61, %62, %63}, %64, %65, p, 1, 1, 0, 1;\n}\n"
    : "+f"(d[128]), "+f"(d[129]), "+f"(d[130]), "+f"(d[131]), "+f"(d[132]), "+f"(d[133]), "+f"(d[134]), "+f"(d[135]), "+f"(d[136]), "+f"(d[137]), "+f"(d[138]), "+f"(d[139]), "+f"(d[140]), "+f"(d[141]), "+f"(d[142]), "+f"(d[143]), "+f"(d[144]), "+f"(d[145]), "+f"(d[146]), "+f"(d[147]), "+f"(d[148]), "+f"(d[149]), "+f"(d[150]), "+f"(d[151]), "+f"(d[152]), "+f"(d[153]), "+f"(d[154]), "+f"(d[155]), "+f"(d[156]), "+f"(d[157]), "+f"(d[158]), "+f"(d[159]), "+f"(d[160]), "+f"(d[161]), "+f"(d[162]), "+f"(d[163]), "+f"(d[164]), "+f"(d[165]), "+f"(d[166]), "+f"(d[167]), "+f"(d[168]), "+f"(d[169]), "+f"(d[170]), "+f"(d[171]), "+f"(d[172]), "+f"(d[173]), "+f"(d[174]), "+f"(d[175]), "+f"(d[176]), "+f"(d[177]), "+f"(d[178]), "+f"(d[179]), "+f"(d[180]), "+f"(d[181]), "+f"(d[182]), "+f"(d[183]), "+f"(d[184]), "+f"(d[185]), "+f"(d[186]), "+f"(d[187]), "+f"(d[188]), "+f"(d[189]), "+f"(d[190]), "+f"(d[191])
    : "l"(da), "l"(db), "r"(scale_d));
}
__device__ __forceinline__ void wgmma_n256_k(float (&d)[192], uint64_t da, uint64_t db, int scale_d) {
  asm volatile("{\n.reg .pred p;\nsetp.ne.b32 p, %130, 0;\n"
    "wgmma.mma_async.sync.aligned.m64n256k16.f32.bf16.bf16 {%0, %1, %2, %3, %4, %5, %6, %7, %8, %9, %10, %11, %12, %13, %14, %15, %16, %17, %18, %19, %20, %21, %22, %23, %24, %25, %26, %27, %28, %29, %30, %31, %32, %33, %34, %35, %36, %37, %38, %39, %40, %41, %42, %43, %44, %45, %46, %47, %48, %49, %50, %51, %52, %53, %54, %55, %56, %57, %58, %59, %60, %61, %62, %63, %64, %65, %66, %67, %68, %69, %70, %71, %72, %73, %74, %75, %76, %77, %78, %79, %80, %81, %82, %83, %84, %85, %86, %87, %88, %89, %90, %91, %92, %93, %94, %95, %96, %97, %98, %99, %100, %101, %102, %103, %104, %105, %106, %107, %108, %109, %110, %111, %112, %113, %114, %115, %116, %117, %118, %119, %120, %121, %122, %123, %124, %125, %126, %127}, %128, %129, p, 1, 1, 0, 0;\n}\n"
    : "+f"(d[0]), "+f"(d[1]), "+f"(d[2]), "+f"(d[3]), "+f"(d[4]), "+f"(d[5]), "+f"(d[6]), "+f"(d[7]), "+f"(d[8]), "+f"(d[9]), "+f"(d[10]), "+f"(d[11]), "+f"(d[12]), "+f"(d[13]), "+f"(d[14]), "+f"(d[15]), "+f"(d[16]), "+f"(d[17]), "+f"(d[18]), "+f"(d[19]), "+f"(d[20]), "+f"(d[21]), "+f"(d[22]), "+f"(d[23]), "+f"(d[24]), "+f"(d[25]), "+f"(d[26]), "+f"(d[27]), "+f"(d[28]), "+f"(d[29]), "+f"(d[30]), "+f"(d[31]), "+f"(d[32]), "+f"(d[33]), "+f"(d[34]), "+f"(d[35]), "+f"(d[36]), "+f"(d[37]), "+f"(d[38]), "+f"(d[39]), "+f"(d[40]), "+f"(d[41]), "+f"(d[42]), "+f"(d[43]), "+f"(d[44]), "+f"(d[45]), "+f"(d[46]), "+f"(d[47]), "+f"(d[48]), "+f"(d[49]), "+f"(d[50]), "+f"(d[51]), "+f"(d[52]), "+f"(d[53]), "+f"(d[54]), "+f"(d[55]), "+f"(d[56]), "+f"(d[57]), "+f"(d[58]), "+f"(d[59]), "+f"(d[60]), "+f"(d[61]), "+f"(d[62]), "+f"(d[63]), "+f"(d[64]), "+f"(d[65]), "+f"(d[66]), "+f"(d[67]), "+f"(d[68]), "+f"(d[69]), "+f"(d[70]), "+f"(d[71]), "+f"(d[72]), "+f"(d[73]), "+f"(d[74]), "+f"(d[75]), "+f"(d[76]), "+f"(d[77]), "+f"(d[78]), "+f"(d[79]), "+f"(d[80]), "+f"(d[81]), "+f"(d[82]), "+f"(d[83]), "+f"(d[84]), "+f"(d[85]), "+f"(d[86]), "+f"(d[87]), "+f"(d[88]), "+f"(d[89]), "+f"(d[90]), "+f"(d[91]), "+f"(d[92]), "+f"(d[93]), "+f"(d[94]), "+f"(d[95]), "+f"(d[96]), "+f"(d[97]), "+f"(d[98]), "+f"(d[99]), "+f"(d[100]), "+f"(d[101]), "+f"(d[102]), "+f"(d[103]), "+f"(d[104]), "+f"(d[105]), "+f"(d[106]), "+f"(d[107]), "+f"(d[108]), "+f"(d[109]), "+f"(d[110]), "+f"(d[111]), "+f"(d[112]), "+f"(d[113]), "+f"(d[114]), "+f"(d[115]), "+f"(d[116]), "+f"(d[117]), "+f"(d[118]), "+f"(d[119]), "+f"(d[120]), "+f"(d[121]), "+f"(d[122]), "+f"(d[123]), "+f"(d[124]), "+f"(d[125]), "+f"(d[126]), "+f"(d[127])
    : "l"(da), "l"(db), "r"(scale_d));
}
__device__ __forceinline__ void wgmma_n128_k(float (&d)[192], uint64_t da, uint64_t db, int scale_d) {
  asm volatile("{\n.reg .pred p;\nsetp.ne.b32 p, %66, 0;\n"
    "wgmma.mma_async.sync.aligned.m64n128k16.f32.bf16.bf16 {%0, %1, %2, %3, %4, %5, %6, %7, %8, %9, %10, %11, %12, %13, %14, %15, %16, %17, %18, %19, %20, %21, %22, %23, %24, %25, %26, %27, %28, %29, %30, %31, %32, %33, %34, %35, %36, %37, %38, %39, %40, %41, %42, %43, %44, %45, %46, %47, %48, %49, %50, %51, %52, %53, %54, %55, %56, %57, %58, %59, %60, %61, %62, %63}, %64, %65, p, 1, 1, 0, 0;\n}\n"
    : "+f"(d[128]), "+f"(d[129]), "+f"(d[130]), "+f"(d[131]), "+f"(d[132]), "+f"(d[133]), "+f"(d[134]), "+f"(d[135]), "+f"(d[136]), "+f"(d[137]), "+f"(d[138]), "+f"(d[139]), "+f"(d[140]), "+f"(d[141]), "+f"(d[142]), "+f"(d[143]), "+f"(d[144]), "+f"(d[145]), "+f"(d[146]), "+f"(d[147]), "+f"(d[148]), "+f"(d[149]), "+f"(d[150]), "+f"(d[151]), "+f"(d[152]), "+f"(d[153]), "+f"(d[154]), "+f"(d[155]), "+f"(d[156]), "+f"(d[157]), "+f"(d[158]), "+f"(d[159]), "+f"(d[160]), "+f"(d[161]), "+f"(d[162]), "+f"(d[163]), "+f"(d[164]), "+f"(d[165]), "+f"(d[166]), "+f"(d[167]), "+f"(d[168]), "+f"(d[169]), "+f"(d[170]), "+f"(d[171]), "+f"(d[172]), "+f"(d[173]), "+f"(d[174]), "+f"(d[175]), "+f"(d[176]), "+f"(d[177]), "+f"(d[178]), "+f"(d[179]), "+f"(d[180]), "+f"(d[181]), "+f"(d[182]), "+f"(d[183]), "+f"(d[184]), "+f"(d[185]), "+f"(d[186]), "+f"(d[187]), "+f"(d[188]), "+f"(d[189]), "+f"(d[190]), "+f"(d[191])
    : "l"(da), "l"(db), "r"(scale_d));
}
__device__ __forceinline__ void wgmma_n40_tt(float (&d)[20], uint64_t da, uint64_t db, int scale_d) {
  asm volatile("{\n.reg .pred p;\nsetp.ne.b32 p, %22, 0;\n"
    "wgmma.mma_async.sync.aligned.m64n40k16.f32.bf16.bf16 {%0, %1, %2, %3, %4, %5, %6, %7, %8, %9, %10, %11, %12, %13, %14, %15, %16, %17, %18, %19}, %20, %21, p, 1, 1, 1, 1;\n}\n"
    : "+f"(d[0]), "+f"(d[1]), "+f"(d[2]), "+f"(d[3]), "+f"(d[4]), "+f"(d[5]), "+f"(d[6]), "+f"(d[7]), "+f"(d[8]), "+f"(d[9]), "+f"(d[10]), "+f"(d[11]), "+f"(d[12]), "+f"(d[13]), "+f"(d[14]), "+f"(d[15]), "+f"(d[16]), "+f"(d[17]), "+f"(d[18]), "+f"(d[19])
    : "l"(da), "l"(db), "r"(scale_d));
}
__device__ __forceinline__ void wgmma_n40_rs(float (&d)[20], const uint32_t (&a)[4], uint64_t db, int scale_d) {
  asm volatile("{\n.reg .pred p;\nsetp.ne.b32 p, %25, 0;\n"
    "wgmma.mma_async.sync.aligned.m64n40k16.f32.bf16.bf16 {%0, %1, %2, %3, %4, %5, %6, %7, %8, %9, %10, %11, %12, %13, %14, %15, %16, %17, %18, %19}, {%20, %21, %22, %23}, %24, p, 1, 1, 1;\n}\n"
    : "+f"(d[0]), "+f"(d[1]), "+f"(d[2]), "+f"(d[3]), "+f"(d[4]), "+f"(d[5]), "+f"(d[6]), "+f"(d[7]), "+f"(d[8]), "+f"(d[9]), "+f"(d[10]), "+f"(d[11]), "+f"(d[12]), "+f"(d[13]), "+f"(d[14]), "+f"(d[15]), "+f"(d[16]), "+f"(d[17]), "+f"(d[18]), "+f"(d[19])
    : "r"(a[0]), "r"(a[1]), "r"(a[2]), "r"(a[3]), "l"(db), "r"(scale_d));
}
__device__ __forceinline__ void wgmma_n256_0(float (&d)[192], uint64_t da, uint64_t db) {
  asm volatile("{\n.reg .pred p;\nsetp.ne.b32 p, 0, 0;\n"
    "wgmma.mma_async.sync.aligned.m64n256k16.f32.bf16.bf16 {%0, %1, %2, %3, %4, %5, %6, %7, %8, %9, %10, %11, %12, %13, %14, %15, %16, %17, %18, %19, %20, %21, %22, %23, %24, %25, %26, %27, %28, %29, %30, %31, %32, %33, %34, %35, %36, %37, %38, %39, %40, %41, %42, %43, %44, %45, %46, %47, %48, %49, %50, %51, %52, %53, %54, %55, %56, %57, %58, %59, %60, %61, %62, %63, %64, %65, %66, %67, %68, %69, %70, %71, %72, %73, %74, %75, %76, %77, %78, %79, %80, %81, %82, %83, %84, %85, %86, %87, %88, %89, %90, %91, %92, %93, %94, %95, %96, %97, %98, %99, %100, %101, %102, %103, %104, %105, %106, %107, %108, %109, %110, %111, %112, %113, %114, %115, %116, %117, %118, %119, %120, %121, %122, %123, %124, %125, %126, %127}, %128, %129, p, 1, 1, 0, 1;\n}\n"
    : "=f"(d[0]), "=f"(d[1]), "=f"(d[2]), "=f"(d[3]), "=f"(d[4]), "=f"(d[5]), "=f"(d[6]), "=f"(d[7]), "=f"(d[8]), "=f"(d[9]), "=f"(d[10]), "=f"(d[11]), "=f"(d[12]), "=f"(d[13]), "=f"(d[14]), "=f"(d[15]), "=f"(d[16]), "=f"(d[17]), "=f"(d[18]), "=f"(d[19]), "=f"(d[20]), "=f"(d[21]), "=f"(d[22]), "=f"(d[23]), "=f"(d[24]), "=f"(d[25]), "=f"(d[26]), "=f"(d[27]), "=f"(d[28]), "=f"(d[29]), "=f"(d[30]), "=f"(d[31]), "=f"(d[32]), "=f"(d[33]), "=f"(d[34]), "=f"(d[35]), "=f"(d[36]), "=f"(d[37]), "=f"(d[38]), "=f"(d[39]), "=f"(d[40]), "=f"(d[41]), "=f"(d[42]), "=f"(d[43]), "=f"(d[44]), "=f"(d[45]), "=f"(d[46]), "=f"(d[47]), "=f"(d[48]), "=f"(d[49]), "=f"(d[50]), "=f"(d[51]), "=f"(d[52]), "=f"(d[53]), "=f"(d[54]), "=f"(d[55]), "=f"(d[56]), "=f"(d[57]), "=f"(d[58]), "=f"(d[59]), "=f"(d[60]), "=f"(d[61]), "=f"(d[62]), "=f"(d[63]), "=f"(d[64]), "=f"(d[65]), "=f"(d[66]), "=f"(d[67]), "=f"(d[68]), "=f"(d[69]), "=f"(d[70]), "=f"(d[71]), "=f"(d[72]), "=f"(d[73]), "=f"(d[74]), "=f"(d[75]), "=f"(d[76]), "=f"(d[77]), "=f"(d[78]), "=f"(d[79]), "=f"(d[80]), "=f"(d[81]), "=f"(d[82]), "=f"(d[83]), "=f"(d[84]), "=f"(d[85]), "=f"(d[86]), "=f"(d[87]), "=f"(d[88]), "=f"(d[89]), "=f"(d[90]), "=f"(d[91]), "=f"(d[92]), "=f"(d[93]), "=f"(d[94]), "=f"(d[95]), "=f"(d[96]), "=f"(d[97]), "=f"(d[98]), "=f"(d[99]), "=f"(d[100]), "=f"(d[101]), "=f"(d[102]), "=f"(d[103]), "=f"(d[104]), "=f"(d[105]), "=f"(d[106]), "=f"(d[107]), "=f"(d[108]), "=f"(d[109]), "=f"(d[110]), "=f"(d[111]), "=f"(d[112]), "=f"(d[113]), "=f"(d[114]), "=f"(d[115]), "=f"(d[116]), "=f"(d[117]), "=f"(d[118]), "=f"(d[119]), "=f"(d[120]), "=f"(d[121]), "=f"(d[122]), "=f"(d[123]), "=f"(d[124]), "=f"(d[125]), "=f"(d[126]), "=f"(d[127])
    : "l"(da), "l"(db));
}
__device__ __forceinline__ void wgmma_n128_0(float (&d)[192], uint64_t da, uint64_t db) {
  asm volatile("{\n.reg .pred p;\nsetp.ne.b32 p, 0, 0;\n"
    "wgmma.mma_async.sync.aligned.m64n128k16.f32.bf16.bf16 {%0, %1, %2, %3, %4, %5, %6, %7, %8, %9, %10, %11, %12, %13, %14, %15, %16, %17, %18, %19, %20, %21, %22, %23, %24, %25, %26, %27, %28, %29, %30, %31, %32, %33, %34, %35, %36, %37, %38, %39, %40, %41, %42, %43, %44, %45, %46, %47, %48, %49, %50, %51, %52, %53, %54, %55, %56, %57, %58, %59, %60, %61, %62, %63}, %64, %65, p, 1, 1, 0, 1;\n}\n"
    : "=f"(d[128]), "=f"(d[129]), "=f"(d[130]), "=f"(d[131]), "=f"(d[132]), "=f"(d[133]), "=f"(d[134]), "=f"(d[135]), "=f"(d[136]), "=f"(d[137]), "=f"(d[138]), "=f"(d[139]), "=f"(d[140]), "=f"(d[141]), "=f"(d[142]), "=f"(d[143]), "=f"(d[144]), "=f"(d[145]), "=f"(d[146]), "=f"(d[147]), "=f"(d[148]), "=f"(d[149]), "=f"(d[150]), "=f"(d[151]), "=f"(d[152]), "=f"(d[153]), "=f"(d[154]), "=f"(d[155]), "=f"(d[156]), "=f"(d[157]), "=f"(d[158]), "=f"(d[159]), "=f"(d[160]), "=f"(d[161]), "=f"(d[162]), "=f"(d[163]), "=f"(d[164]), "=f"(d[165]), "=f"(d[166]), "=f"(d[167]), "=f"(d[168]), "=f"(d[169]), "=f"(d[170]), "=f"(d[171]), "=f"(d[172]), "=f"(d[173]), "=f"(d[174]), "=f"(d[175]), "=f"(d[176]), "=f"(d[177]), "=f"(d[178]), "=f"(d[179]), "=f"(d[180]), "=f"(d[181]), "=f"(d[182]), "=f"(d[183]), "=f"(d[184]), "=f"(d[185]), "=f"(d[186]), "=f"(d[187]), "=f"(d[188]), "=f"(d[189]), "=f"(d[190]), "=f"(d[191])
    : "l"(da), "l"(db));
}
__device__ __forceinline__ void wgmma_n64a(float (&d)[192], uint64_t da, uint64_t db, int scale_d) {
  asm volatile("{\n.reg .pred p;\nsetp.ne.b32 p, %34, 0;\n"
    "wgmma.mma_async.sync.aligned.m64n64k16.f32.bf16.bf16 {%0, %1, %2, %3, %4, %5, %6, %7, %8, %9, %10, %11, %12, %13, %14, %15, %16, %17, %18, %19, %20, %21, %22, %23, %24, %25, %26, %27, %28, %29, %30, %31}, %32, %33, p, 1, 1, 0, 1;\n}\n"
    : "+f"(d[128]), "+f"(d[129]), "+f"(d[130]), "+f"(d[131]), "+f"(d[132]), "+f"(d[133]), "+f"(d[134]), "+f"(d[135]), "+f"(d[136]), "+f"(d[137]), "+f"(d[138]), "+f"(d[139]), "+f"(d[140]), "+f"(d[141]), "+f"(d[142]), "+f"(d[143]), "+f"(d[144]), "+f"(d[145]), "+f"(d[146]), "+f"(d[147]), "+f"(d[148]), "+f"(d[149]), "+f"(d[150]), "+f"(d[151]), "+f"(d[152]), "+f"(d[153]), "+f"(d[154]), "+f"(d[155]), "+f"(d[156]), "+f"(d[157]), "+f"(d[158]), "+f"(d[159])
    : "l"(da), "l"(db), "r"(scale_d));
}
__device__ __forceinline__ void wgmma_n64b(float (&d)[192], uint64_t da, uint64_t db, int scale_d) {
  asm volatile("{\n.reg .pred p;\nsetp.ne.b32 p, %34, 0;\n"
    "wgmma.mma_async.sync.aligned.m64n64k16.f32.bf16.bf16 {%0, %1, %2, %3, %4, %5, %6, %7, %8, %9, %10, %11, %12, %13, %14, %15, %16, %17, %18, %19, %20, %21, %22, %23, %24, %25, %26, %27, %28, %29, %30, %31}, %32, %33, p, 1, 1, 0, 1;\n}\n"
    : "+f"(d[160]), "+f"(d[161]), "+f"(d[162]), "+f"(d[163]), "+f"(d[164]), "+f"(d[165]), "+f"(d[166]), "+f"(d[167]), "+f"(d[168]), "+f"(d[169]), "+f"(d[170]), "+f"(d[171]), "+f"(d[172]), "+f"(d[173]), "+f"(d[174]), "+f"(d[175]), "+f"(d[176]), "+f"(d[177]), "+f"(d[178]), "+f"(d[179]), "+f"(d[180]), "+f"(d[181]), "+f"(d[182]), "+f"(d[183]), "+f"(d[184]), "+f"(d[185]), "+f"(d[186]), "+f"(d[187]), "+f"(d[188]), "+f"(d[189]), "+f"(d[190]), "+f"(d[191])
    : "l"(da), "l"(db), "r"(scale_d));
}

constexpr int SLOT = 16384;
constexpr int KVT = 10240;
constexpr uint32_t QA = 0x0BAu, QK = 0x462u, QQ = 0x981u;
constexpr int SM_SD = 12 * SLOT;
constexpr int SM_BAR = SM_SD + 8192;
constexpr int SM_RS = SM_BAR + 512;
constexpr int SM_AP = SM_RS + 768;
constexpr int SM_BP = SM_AP + 2048;
constexpr int SM_WPHI = SM_BP + 12288;
constexpr int SM_EPOCH = SM_WPHI + 10240;
constexpr int SM_TOTAL = SM_EPOCH + 16 + 1024;
constexpr int B_FULLS = 0, B_XOLD = 24, B_STAT = 32, B_EMPTYS = 40, B_FULLT = 256  , B_CONS = 384  , B_E3 = 472, B_E0 = 480, B_E1 = 488, B_E2 = 496, B_EPI = 504, B_CS = 160,
              B_KVDONE = 168  , B_ODONE = 176, B_XDONE = 184, B_OH1 = 192, B_CS2 = 208, B_XH0 = 232, B_R0 = 240, B_CB = 144  , B_XOLD2 = 216, B_FLG = 64  ;
constexpr uint64_t BAR_CNT = 0x1c07fc0eac00a800ull;
constexpr uint64_t WO_A0 = 0xba76218762187643ull, WO_B0 = 0x9540395403ba9021ull, WO_A1 = 0xba713257132576abull, WO_B1 = 0x9506489064890132ull;
constexpr uint64_t WO_DA0 = 0xa9876543210edd00ull, WO_DB0 = 0xa987654321bbccccull, WO_DA1 = 0xa9876543210fff00ull, WO_DB1 = 0xa98765432bbcccddull;
#define WOORD 0xFDB9753ECA864210ull
constexpr int NX = 4;
constexpr int XS = 10;

#define PL 2
#define PROFX(i) PROFT(tid_ == 128 && layer == PL, 200 + (i))
#define PSL 20
#define EP 5
#define NCOM 3
#define CSLP 128
#define PFS 8
#define KVTH 0x41700000u
#define RL 3
#define ORD 1
#define XB2 2
#define PMOD 3
#define DB1 2
#define XPF 2
#define XPM 0
#define AW 1
#define PG 0
#define UNS 7
#define TLINE 0
#define RORD 0
#define WSK 1
#define HE 0
#define NLAYERS 4
constexpr float L2E = 1.4426950408889634f;
#define PHI_MAX 2147483648.f

#define D128(lo) desc64(lo, 0x40000040u)
struct Ctx { uint32_t sb; int g, rb, cu; bf16* out; };

__device__ __forceinline__ void colsum(const CUtensorMap* tm, float* cs, int rb, int g, int w0, int dw, int lane, uint32_t stg, uint32_t cb, uint32_t par) {
  const uint32_t src = stg + (lane >> 3) * 2048;
#pragma unroll 1
  for (int wi = w0 - dw; wi < 6; wi += dw) {
    float s[8] = {0.f, 0.f, 0.f, 0.f, 0.f, 0.f, 0.f, 0.f};
    if (wi >= 0) {
      mbar_wait_u(cb, par);
      par ^= 1;
#pragma unroll 4
      for (int r = 0; r < 16; ++r) {
        const uint4 v = lds128(src + r * 128 + (((lane ^ r) & 7) << 4));
        s[0] += bf_lo(v.x); s[1] += bf_hi(v.x); s[2] += bf_lo(v.y); s[3] += bf_hi(v.y);
        s[4] += bf_lo(v.z); s[5] += bf_hi(v.z); s[6] += bf_lo(v.w); s[7] += bf_hi(v.w);
      }
#pragma unroll
      for (int i = 0; i < 8; ++i) s[i] += __shfl_xor_sync(0xffffffffu, s[i], 8);
    }
    const int wn = wi + dw;
    if (wn < 6) {
      expect_tx_e(cb, 8192);
      tma_2d_e(stg, tm, (wn >= 4 ? 0 : 1024 + (wn >> 1) * 1024) + g * 128 + (wn & 1) * 64, rb * 64, cb);
    }
    if (wi >= 0) {
#pragma unroll
      for (int i = 0; i < 8; ++i) s[i] += __shfl_xor_sync(0xffffffffu, s[i], 16);
      if (lane < 8) {
        red_add4(cs + g * 384 + (wi * 8 + lane) * 8, s[0], s[1], s[2], s[3]);
        red_add4(cs + g * 384 + (wi * 8 + lane) * 8 + 4, s[4], s[5], s[6], s[7]);
      }
      __syncwarp();
    }
  }
}
#define PHASE_CTX() \
  uint32_t sb = c.sb; asm volatile("" : "+r"(sb)); \
  int tid_ = threadIdx.x; asm volatile("" : "+r"(tid_)); \
  const uint32_t bar = sb + SM_BAR; \
  const int lane = tid_ & 31, cw = (tid_ >> 5) - 4, wg = cw >> 2, wq = cw & 3, gq = lane >> 2, t = lane & 3, wrow0 = cw * 16; \
  const int lrow = (lane & 7) + ((lane >> 3) & 1) * 8, lchk = lane >> 4; \
  const bool elected = (tid_ & 127) == 0; \
  const uint32_t rowo = (wrow0 + lrow) * 128, X = (lchk ^ (lane & 7)) << 4; \
  (void)bar; (void)wq; (void)gq; (void)lrow; (void)lchk; (void)elected; (void)wrow0; (void)wg; (void)rowo; (void)X; (void)t;

__device__ __forceinline__ void slab_out_half(uint32_t slot, bf16* dst, int wrow0, int lane, bool FENCE = false) {
  const int r0 = lane >> 3, ch = lane & 7;
  const uint32_t src = slot + (wrow0 + r0) * 128;
  uint4 v[4];
#pragma unroll
  for (int i = 0; i < 4; ++i) v[i] = lds128(src + i * 512 + (((ch ^ (4 * i + r0)) & 7) << 4));
  if (FENCE) fence_async_smem();
  dst += (size_t)(wrow0 + r0) * D_ + ch * 8;
#pragma unroll
  for (int i = 0; i < 4; ++i)
    asm volatile("st.global.v4.u32 [%0], {%1,%2,%3,%4};" ::"l"(dst + (size_t)i * 4 * D_), "r"(v[i].x), "r"(v[i].y), "r"(v[i].z), "r"(v[i].w) : "memory");
}

struct Tag { uint32_t me, mo, tg; };
__device__ __forceinline__ Tag make_tag(int gq, int t, uint32_t tg) {
  const uint32_t on = t == (gq & 3), par = ((gq >> 2) ^ gq) & 1;
  return Tag{on & ~par, on & par, tg};
}
__device__ __forceinline__ void stsm_tag(uint32_t addr, uint32_t r0, uint32_t r1, uint32_t r2, uint32_t r3, const Tag& k, int jp) {
  stsm_x4(addr, (r0 & ~k.me) | (k.tg & k.me), (r1 & ~k.me) | (k.tg & k.me), (r2 & ~k.mo) | (k.tg & k.mo), (r3 & ~k.mo) | (k.tg & k.mo));
}
#define TILE_BAD() (((lds_vol(va) ^ tg) | (lds_vol(va + 1024) ^ tg)) & 1)
#define TILE_VA() (slot + (wrow0 + (lane >> 2)) * 128 + (lane & 3) * 32 + (lane >> 2) * 4)
__device__ __forceinline__ void tile_check(uint32_t slot, const bf16* src, int wrow0, int lane, uint32_t tg) {
  const uint32_t va = TILE_VA();
  if (__builtin_expect(__any_sync(0xffffffffu, TILE_BAD()), 0)) {
    const int r0 = lane >> 3, ch = lane & 7;
    uint32_t n = 0;
#pragma unroll 1
    do {
      uint4 v[4];
#pragma unroll
      for (int i = 0; i < 4; ++i) v[i] = ld_relaxed4(reinterpret_cast<const uint4*>(src + (size_t)(wrow0 + r0 + 4 * i) * D_ + ch * 8));
#pragma unroll
      for (int i = 0; i < 4; ++i) sts128(slot + (wrow0 + r0 + 4 * i) * 128 + (((ch ^ (4 * i + r0)) & 7) << 4), v[i]);
      __syncwarp();
      if (++n > (1u << 16)) { g_err = 8u; break; }
    } while (__any_sync(0xffffffffu, TILE_BAD()));
    fence_async_smem();
    __syncwarp();
  }
}

template <int O>
__device__ __forceinline__ void phi_proj(float (&p)[2][4][4], const uint32_t (&kq)[64], uint32_t wa) {
#pragma unroll
  for (int h = 0; h < 2; ++h)
#pragma unroll
    for (int i = 0; i < 4; ++i) { p[h][i][0] = p[h][i][1] = p[h][i][2] = p[h][i][3] = 0.f; }
#pragma unroll
  for (int ks = 0; ks < 2; ++ks)
#pragma unroll
    for (int np = 0; np < 2; ++np)
#pragma unroll
      for (int h = 0; h < 2; ++h) {
        uint32_t b0, b1, b2, b3;
        ldsm_x4_t(b0, b1, b2, b3, wa + h * 2560 + ks * 1280 + np * 32);
        mma_bf16(p[h][2 * np], kq[O + 8 * h + 4 * ks], kq[O + 8 * h + 4 * ks + 1], kq[O + 8 * h + 4 * ks + 2], kq[O + 8 * h + 4 * ks + 3], b0, b1);
        mma_bf16(p[h][2 * np + 1], kq[O + 8 * h + 4 * ks], kq[O + 8 * h + 4 * ks + 1], kq[O + 8 * h + 4 * ks + 2], kq[O + 8 * h + 4 * ks + 3], b2, b3);
      }
}
__device__ __forceinline__ void phi_exp(uint32_t (&raw)[4][4], const float (&p)[4][4], float sc0, float sc1) {
#pragma unroll
  for (int i = 0; i < 4; ++i) {
    const float e0 = ex2(p[i][0] * sc0), e1 = ex2(p[i][1] * sc0), e2 = ex2(p[i][2] * sc1), e3 = ex2(p[i][3] * sc1);
    const float m0 = e0 * e1, m1 = e2 * e3, rr = rcp(m0 * m1), r0 = rr * m1, r1 = rr * m0;
    raw[i >> 1][(i & 1) * 2] = pack_bf16(e0, e1);
    raw[i >> 1][(i & 1) * 2 + 1] = pack_bf16(e2, e3);
    raw[2 + (i >> 1)][(i & 1) * 2] = pack_bf16(e1 * r0, e0 * r0);
    raw[2 + (i >> 1)][(i & 1) * 2 + 1] = pack_bf16(e3 * r1, e2 * r1);
  }
}
#define FENCE_P(h) _Pragma("unroll") for (int i_ = 0; i_ < 16; ++i_) asm volatile("" : "+f"(p[h][i_ >> 2][i_ & 3]) :: "memory")
#define FENCE_RAW(h) _Pragma("unroll") for (int i_ = 0; i_ < 16; ++i_) asm volatile("" : "+r"(raw[h][i_ >> 2][i_ & 3]) :: "memory")
template <int O>
__device__ __forceinline__ void phi_norm(uint32_t (&ph)[2][4][4], const uint32_t (&raw)[2][4][4], const uint32_t (&kq)[64], uint32_t wa,
                                         float sc0, float sc1, float mul0, float mul1) {
  bool bad = false;
#pragma unroll
  for (int h = 0; h < 2; ++h)
#pragma unroll
    for (int sg = 0; sg < 2; ++sg) {
      float ss[4] = {0.f, 0.f, 0.f, 0.f};
#pragma unroll
      for (int ks = 0; ks < 2; ++ks)
        mma_bf16(ss, raw[h][2 * sg + ks][0], raw[h][2 * sg + ks][1], raw[h][2 * sg + ks][2], raw[h][2 * sg + ks][3], 0x3F803F80u, 0x3F803F80u);
      bad = bad || !(ss[0] < PHI_MAX) || !(ss[2] < PHI_MAX);
      const uint32_t iv = pack_bf16(rcp(ss[0]) * mul0, rcp(ss[2]) * mul1);
#pragma unroll
      for (int ks = 0; ks < 2; ++ks)
#pragma unroll
        for (int j = 0; j < 4; ++j) ph[h][2 * sg + ks][j] = mul_bf16x2(raw[h][2 * sg + ks][j], iv, j & 1);
    }
  if (__builtin_expect(__any_sync(0xffffffffu, bad), 0)) {
#pragma unroll 1
    for (int it = 0; it < 4; ++it) {
      float q[4][4];
#pragma unroll
      for (int i = 0; i < 4; ++i) { q[i][0] = q[i][1] = q[i][2] = q[i][3] = 0.f; }
#pragma unroll
      for (int ks = 0; ks < 2; ++ks) {
        uint32_t a[4];
#pragma unroll
        for (int j = 0; j < 4; ++j) a[j] = (it & 2) ? kq[O + 8 + 4 * ks + j] : kq[O + 4 * ks + j];
#pragma unroll
        for (int np = 0; np < 2; ++np) {
          uint32_t b0, b1, b2, b3;
          ldsm_x4_t(b0, b1, b2, b3, wa + (it >> 1) * 2560 + ks * 1280 + np * 32);
          mma_bf16(q[2 * np], a[0], a[1], a[2], a[3], b0, b1);
          mma_bf16(q[2 * np + 1], a[0], a[1], a[2], a[3], b2, b3);
        }
      }
      float iv[2];
#pragma unroll
      for (int r = 0; r < 2; ++r) {
        const float sc = (it & 1) ? -(r ? sc1 : sc0) : (r ? sc1 : sc0);
        float mx = -INFINITY, sm = 0.f;
#pragma unroll
        for (int i = 0; i < 8; ++i) { float& v = q[i >> 1][2 * r + (i & 1)]; v *= sc; mx = fmaxf(mx, v); }
        mx = fmaxf(mx, __shfl_xor_sync(0xffffffffu, mx, 1));
        mx = fmaxf(mx, __shfl_xor_sync(0xffffffffu, mx, 2));
#pragma unroll
        for (int i = 0; i < 8; ++i) { float& v = q[i >> 1][2 * r + (i & 1)]; v = ex2(v - mx); sm += v; }
        sm += __shfl_xor_sync(0xffffffffu, sm, 1);
        sm += __shfl_xor_sync(0xffffffffu, sm, 2);
        iv[r] = rcp(sm) * (r ? mul1 : mul0);
      }
#pragma unroll
      for (int i = 0; i < 24; ++i) ph[i >> 4][(i >> 2) & 3][i & 3] = ph[(i + 8) >> 4][((i + 8) >> 2) & 3][i & 3];
#pragma unroll
      for (int i = 0; i < 4; ++i) {
        ph[1][2 + (i >> 1)][(i & 1) * 2] = pack_bf16(q[i][0] * iv[0], q[i][1] * iv[0]);
        ph[1][2 + (i >> 1)][(i & 1) * 2 + 1] = pack_bf16(q[i][2] * iv[1], q[i][3] * iv[1]);
      }
    }
  }
}

__device__ __forceinline__ void stats_out(float s0, float s1, float q0, float q1, float2* dst, int t) {
  const bool od = t & 1;
  float sa = od ? s1 : s0, qa = od ? q1 : q0;
  sa += __shfl_xor_sync(0xffffffffu, od ? s0 : s1, 1);
  qa += __shfl_xor_sync(0xffffffffu, od ? q0 : q1, 1);
  sa += __shfl_xor_sync(0xffffffffu, sa, 2);
  qa += __shfl_xor_sync(0xffffffffu, qa, 2);
  if (t < 2) red_add2(&dst[t * 8].x, sa, qa);
}

__device__ __forceinline__ void consumer(const Ctx& c) {
  const int g = c.g, m0 = c.rb * 128;
  float acc[192];
#define X_HALF(hf, TG) \
      _Pragma("unroll") for (int jp = 4 * (hf); jp < 4 * (hf) + 4; ++jp) \
        stsm_tag(sb + (XS + (hf)) * SLOT + rowo + (X ^ ((jp & 3) << 5)), \
                 pack_bf16(acc[128 + 8 * jp], acc[129 + 8 * jp]), pack_bf16(acc[130 + 8 * jp], acc[131 + 8 * jp]), \
                 pack_bf16(acc[132 + 8 * jp], acc[133 + 8 * jp]), pack_bf16(acc[134 + 8 * jp], acc[135 + 8 * jp]), TG, jp & 3);
#pragma unroll
  for (int i = 128; i < 192; ++i) acc[i] = 0.f;
#pragma unroll 1
  for (int layer = 0;; ++layer) {
    {
      PHASE_CTX();
      const uint32_t wu = c.cu >> 2;
      const uint32_t dA0 = (((sb + wu * 8192) & 0x3FFFF) >> 4) | (1u << 16), dB0 = ((sb & 0x3FFFF) >> 4) | (512u << 16);
      {
        PROFX(0);
        mbar_wait(bar + B_FULLS, 0);
        PROFX(1);
        wgmma_fence();
        wgmma_n256_0(acc, D128(dA0 + XS * 1024), D128(dB0 + 2048));
#pragma unroll
        for (int k = 1; k < 4; ++k) wgmma_n256(acc, D128(dA0 + XS * 1024 + k * 2), D128(dB0 + 2048 + k * 128), 1);
        wgmma_commit();
        wgmma_wait<1>();
        float s0 = 0.f, s1 = 0.f, q0 = 0.f, q1 = 0.f;
        if (layer) {
          X_HALF(1, (Tag{0u, 0u, 0u}));
#pragma unroll
          for (int i = 128; i < 192; i += 4) {
            s0 += acc[i] + acc[i + 1]; s1 += acc[i + 2] + acc[i + 3];
            q0 = fmaf(acc[i], acc[i], fmaf(acc[i + 1], acc[i + 1], q0)); q1 = fmaf(acc[i + 2], acc[i + 2], fmaf(acc[i + 3], acc[i + 3], q1));
          }
        }
        asm volatile("" : "+f"(s0), "+f"(s1), "+f"(q0), "+f"(q1) :: "memory");
        wgmma_fence();
        wgmma_n128_0(acc, D128(dA0 + XS * 1024), D128(dB0 + 1024));
#pragma unroll
        for (int k = 1; k < 4; ++k) wgmma_n128(acc, D128(dA0 + XS * 1024 + k * 2), D128(dB0 + 1024 + k * 128), 1);
        wgmma_commit();
        if (layer) {
          PHASE_CTX();
          fence_async_smem();
          nbar_dyn(3 + wu, 128);
          stats_out(s0, s1, q0, q1, g_stats + layer * S_ + m0 + wrow0 + gq, t);
          PROFT(tid_ == 128, layer * 16 + 8);
        }
      }
      uint32_t s = 1, u = 0, sp = 0;
      const int ix = layer ? 99 : 2 * min(g, NCOM) + 1;
#pragma unroll 1
      for (int i = 1; i < 14; ++i) {
        mbar_wait(bar + B_FULLS + s * 8, (u + (s ? layer : 0)) & 1);
        if ((UNS & 1) && layer && (unsigned)(i - 2) < 7u) {
          PHASE_CTX();
          tile_check(sb + ((QA >> (4 * s)) & 15) * SLOT, g_x + (size_t)m0 * D_ + ((2 * g + 2 * i - 2) & 15) * 64, wrow0, lane, lds_vol(sb + SM_EPOCH) + layer);
        }
        const uint32_t da = dA0 + ((QA >> (4 * s)) & 15) * 1024, dk = dB0 + ((QK >> (4 * s)) & 15) * 1024,
                       dq = dB0 + ((QQ >> (4 * s)) & 15) * 1024;
        wgmma_fence();
#pragma unroll
        for (int k = 0; k < 4; ++k) {
          wgmma_n256(acc, D128(da + k * 2), D128(dk + k * 128), 1);
          wgmma_n128(acc, D128(da + k * 2), D128(dq + k * 128), 1);
        }
        wgmma_commit();
        if ((unsigned)(i - ix) < 2u) {
          PHASE_CTX();
          {
            float s0 = 0.f, s1 = 0.f, q0 = 0.f, q1 = 0.f;
            const uint32_t xa = sb + ((QA >> (4 * sp)) & 15) * SLOT + rowo;
#pragma unroll
            for (int jp = 0; jp < 4; ++jp) {
              uint32_t x0, x1, x2, x3;
              ldsm_x4(x0, x1, x2, x3, xa + (X ^ (jp << 5)));
              s0 += (bf_lo(x0) + bf_hi(x0)) + (bf_lo(x2) + bf_hi(x2));
              s1 += (bf_lo(x1) + bf_hi(x1)) + (bf_lo(x3) + bf_hi(x3));
              q0 = fmaf(bf_lo(x0), bf_lo(x0), fmaf(bf_hi(x0), bf_hi(x0), fmaf(bf_lo(x2), bf_lo(x2), fmaf(bf_hi(x2), bf_hi(x2), q0))));
              q1 = fmaf(bf_lo(x1), bf_lo(x1), fmaf(bf_hi(x1), bf_hi(x1), fmaf(bf_lo(x3), bf_lo(x3), fmaf(bf_hi(x3), bf_hi(x3), q1))));
            }
            stats_out(s0, s1, q0, q1, g_stats + m0 + wrow0 + gq, t);
          }
          __syncwarp();
          if (lane == 0 && i != ix) mbar_arrive(bar + B_XDONE);
          nbar_dyn(3 + wu, 128);
        }
        wgmma_wait<1>();
        if (elected) release2(bar + B_EMPTYS + sp * 8);
        if (i == 1 && layer) {
          PHASE_CTX();
          slab_out_half(sb + (XS + 1) * SLOT, g_x + (size_t)m0 * D_ + g * 128 + 64, wrow0, lane);
          __syncwarp();
          if (lane == 0) mbar_arrive(bar + B_XDONE);
          nbar_dyn(3 + wu, 128);
        }
        sp = s;
        if (++s == 3) { s = 0; ++u; }
      }
      {
        const uint64_t dap = make_desc_ns(sb + SM_AP + wu * 1024, 0, 128), dbp = make_desc_ns(sb + SM_BP + (layer & 1) * 6144, 0, 128);
        if (wu == 0) {
          wgmma_wait<0>();
          if (elected) mbar_arrive(bar + B_R0);
          nbar<6, 256>();
        }
        if (layer < 2) mbar_wait(bar + (layer ? B_CS2 : B_CS), 0);
        mbar_wait(bar + B_STAT, layer & 1);
        mbar_wait(bar + B_FULLS + 16, layer & 1);
        wgmma_fence();
        wgmma_n256_k(acc, dap, dbp, 1);
#pragma unroll
        for (int k = 0; k < 4; ++k) wgmma_n256(acc, D128(dA0 + (QA >> 8) * 1024 + k * 2), D128(dB0 + (QK >> 8) * 1024 + k * 128), 1);
        mbar_wait(bar + B_FULLS, 1);
        PROFT(tid_ == 128, layer * 16 + 9);
        wgmma_fence();
#pragma unroll
        for (int k = 0; k < 4; ++k) wgmma_n256(acc, D128(dA0 + (QA & 15) * 1024 + k * 2), D128(dB0 + (QK & 15) * 1024 + k * 128), 1);
        wgmma_commit();
        if (wu) nbar<6, 256>();
#define Q_TAIL() \
        wgmma_n128_k(acc, dap, dbp + 256, 1); \
        _Pragma("unroll") for (int k = 0; k < 4; ++k) wgmma_n128(acc, D128(dA0 + (QA >> 8) * 1024 + k * 2), D128(dB0 + (QQ >> 8) * 1024 + k * 128), 1); \
        _Pragma("unroll") for (int k = 0; k < 4; ++k) wgmma_n128(acc, D128(dA0 + (QA & 15) * 1024 + k * 2), D128(dB0 + (QQ & 15) * 1024 + k * 128), 1);
        Q_TAIL();
        wgmma_commit();
        wgmma_wait<1>();
#pragma unroll
        for (int i = 0; i < 128; ++i) asm volatile("" : "+f"(acc[i]) :: "memory");
      }
    }
    uint32_t xo[32];
    {
      PHASE_CTX();
      PROFT(tid_ == 128, layer * 16 + 1);
      const bool isB = layer & 1;
      const int cu = c.cu;
      if (cu >= 4) asm volatile("bar.arrive 7, 256;" ::: "memory");
      if (elected && cu == 4) mbar_arrive(bar + B_R0);
      uint32_t kq[64];
      const uint32_t rowq = rowo & 8191;
      const float rs0 = lds_f(sb + SM_RS + (16 + wrow0 + gq) * 4), rs1 = lds_f(sb + SM_RS + (24 + wrow0 + gq) * 4);
#define Q_DONE() \
      wgmma_wait<0>(); \
      if (lane == 0) release2(bar + B_E0); \
      _Pragma("unroll") for (int i = 128; i < 192; ++i) asm volatile("" : "+f"(acc[i]) :: "memory"); \
      _Pragma("unroll") for (int i = 0; i < 32; ++i) kq[32 + i] = pack_bf16(acc[128 + 2 * i], acc[129 + 2 * i]);
      if (isB) {
        if (cu == 0) asm volatile("bar.arrive 10, 64;" ::: "memory");
        if (elected) release2(bar + B_E1);
        const int e = gq & 1;
        const bool sel = t > (gq >> 1);
        const uint32_t rja = sb + SM_RS + (wrow0 + 2 * t + e) * 4;
        const float rjA0 = lds_f(rja + 32), rjA1 = lds_f(rja + 64), rjB0 = lds_f(rja + (sel ? 0 : 64)), rjB1 = lds_f(rja + (sel ? 32 : 96));
        uint32_t vv[32];
#pragma unroll
        for (int i = 0; i < 16; ++i) { kq[i] = pack_bf16(acc[2 * i], acc[2 * i + 1]); vv[i] = pack_bf16(acc[64 + 2 * i], acc[65 + 2 * i]); }
        const uint32_t rB = sb + 4 * SLOT + wg * 4 * KVT + rowq;
        auto dump = [&](int hp) {
          const uint32_t kb = rB + 2048 + (hp ^ wg) * 2 * KVT;
#pragma unroll
          for (int jp = 0; jp < 4; ++jp) {
            stsm_x4(kb + (X ^ (jp << 5)), kq[16 * hp + 4 * jp], kq[16 * hp + 4 * jp + 1], kq[16 * hp + 4 * jp + 2], kq[16 * hp + 4 * jp + 3]);
            stsm_x4(kb + KVT + (X ^ (jp << 5)), vv[16 * hp + 4 * jp], vv[16 * hp + 4 * jp + 1], vv[16 * hp + 4 * jp + 2], vv[16 * hp + 4 * jp + 3]);
          }
          if (cu == 3) {
            const uint32_t kd = rB + 2048 + 32768 + (1 - hp) * 2 * KVT;
#pragma unroll
            for (int jp = 0; jp < 4; ++jp) {
              stsm_x4(kd + (X ^ (jp << 5)), kq[16 * hp + 4 * jp], kq[16 * hp + 4 * jp + 1], kq[16 * hp + 4 * jp + 2], kq[16 * hp + 4 * jp + 3]);
              stsm_x4(kd + KVT + (X ^ (jp << 5)), vv[16 * hp + 4 * jp], vv[16 * hp + 4 * jp + 1], vv[16 * hp + 4 * jp + 2], vv[16 * hp + 4 * jp + 3]);
            }
            if (hp) asm volatile("bar.arrive 15, 64;" ::: "memory"); else asm volatile("bar.arrive 9, 64;" ::: "memory");
          }
          asm volatile("bar.arrive %0, 224;" :: "r"(hp ? 13 + (cu >> 2) : 8 + (cu & 4)) : "memory");
        };
        uint4* const hbuf = g_halo + ((c.rb * 8 + g) * 2 + (layer >> 1)) * 512 + lane;
        if (cu < 4) {
          nbar<7, 256>();
          dump(0);
        }
#pragma unroll
        for (int i = 16; i < 32; ++i) { kq[i] = pack_bf16(acc[2 * i], acc[2 * i + 1]); vv[i] = pack_bf16(acc[64 + 2 * i], acc[65 + 2 * i]); }
        if (cu >= 4) {
          if (cu == 7) {
#pragma unroll
            for (int jp = 0; jp < 8; ++jp) {
              st_relaxed4(hbuf + jp * 32, ~kq[4 * jp], ~kq[4 * jp + 1], ~kq[4 * jp + 2], ~kq[4 * jp + 3]);
              st_relaxed4(hbuf + 256 + jp * 32, ~vv[4 * jp], ~vv[4 * jp + 1], ~vv[4 * jp + 2], ~vv[4 * jp + 3]);
            }
          }
          dump(0);
          dump(1);
        }
        PROFT(tid_ == 128, layer * 16 + 2);
        constexpr float SC = 0.17677669529663687f * L2E;
        const float fA0 = rjA0 * rs0 * SC, fB0 = rjB0 * rs0 * SC, fA1 = rjA1 * rs1 * SC, fB1 = rjB1 * rs1 * SC;
        const float bA0 = (m0 + wrow0) ? 0.f : -1e30f, bB = sel ? bA0 : 0.f;
        const uint32_t pA_ = e ? 0x1044u : 0x4410u, pB_ = e ? 0x3244u : 0x4432u, pLo = sel ? pB_ : 0x4444u, pHi = sel ? 0x4444u : pB_;
        const uint32_t KX = ((lane >> 3) ^ (lane & 7)) << 4;
        Q_DONE();
        if (cu == 0) {
          nbar<11, 64>();
        } else if (cu == 4) {
          uint4 hv[16];
          if (c.rb > 0) {
            uint32_t n = 0;
#pragma unroll 1
            while (true) {
              uint32_t mn = 0xFFFFFFFFu;
#pragma unroll
              for (int i = 0; i < 16; ++i) hv[i] = ld_relaxed4(hbuf - 16 * 512 + i * 32);
#pragma unroll
              for (int i = 0; i < 16; ++i) mn = __vimin3_u32(__vimin3_u32(mn, hv[i].x, hv[i].y), hv[i].z, hv[i].w);
              if (__all_sync(0xffffffffu, mn != 0u)) break;
              if (++n > (1u << 20)) { g_err = 4u; break; }
            }
          } else {
#pragma unroll
            for (int i = 0; i < 16; ++i) hv[i] = make_uint4(~0u, ~0u, ~0u, ~0u);
          }
          nbar<10, 64>();
#pragma unroll
          for (int i = 0; i < 16; ++i)
            stsm_x4(rB - 4 * KVT + (((i >> 2) & 1) * 2 + (i >> 3)) * KVT + (X ^ ((i & 3) << 5)), ~hv[i].x, ~hv[i].y, ~hv[i].z, ~hv[i].w);
          asm volatile("bar.arrive 11, 64;" ::: "memory");
          nbar<9, 64>();
        } else {
          nbar_dyn(8 + (cu & 4), 224);
        }
        PROFT(tid_ == 128, layer * 16 + 5);
        PROFT(lane == 0 && layer == PL, 136 + cw);
        auto attend = [&](int hp) {
          const uint32_t qad = sb + (XS + 1 - hp) * SLOT + rowo, kt = rB + 2 * (hp ^ wg) * KVT - (lane & 8) * 128, vt = rB + (2 * (hp ^ wg) + 1) * KVT;
          __syncwarp();
          uint32_t kb[2][2][4], vb[2][2][2][4];
#pragma unroll
          for (int h = 0; h < 2; ++h)
#pragma unroll
            for (int nt = 0; nt < 2; ++nt) ldsm_x4(kb[h][nt][0], kb[h][nt][1], kb[h][nt][2], kb[h][nt][3], kt + nt * 1024 + (KX ^ (h << 6)));
#pragma unroll
          for (int ks = 0; ks < 2; ++ks)
#pragma unroll
            for (int np = 0; np < 2; ++np)
#pragma unroll
              for (int h = 0; h < 2; ++h)
                ldsm_x4_t(vb[h][ks][np][0], vb[h][ks][np][1], vb[h][ks][np][2], vb[h][ks][np][3], vt + ks * 2048 + (X ^ (h << 6) ^ (np << 5)));
          if (hp == 0 && lane == 0) release2(bar + B_E3);
          if (DB1 == 1 && hp == 0 && cu < 4) dump(1);
          float la[2][2], lb[2][2], mx[2][2], sm[2][2];
#pragma unroll
          for (int h = 0; h < 2; ++h) {
            const int qo = 32 + 16 * hp + 8 * h, ko = 16 * hp + 8 * h;
            float sc[4][4];
#pragma unroll
            for (int nt = 0; nt < 4; ++nt) {
              sc[nt][0] = sc[nt][1] = sc[nt][2] = sc[nt][3] = 0.f;
#pragma unroll
              for (int ks = 0; ks < 2; ++ks)
                mma_bf16(sc[nt], kq[qo + 4 * ks], kq[qo + 4 * ks + 1], kq[qo + 4 * ks + 2], kq[qo + 4 * ks + 3],
                         nt < 2 ? kb[h][nt & 1][2 * ks] : kq[ko + 4 * ks + (nt & 1)], nt < 2 ? kb[h][nt & 1][2 * ks + 1] : kq[ko + 4 * ks + 2 + (nt & 1)]);
            }
            la[h][0] = fmaf(e ? sc[1][1] : sc[1][0], fA0, bA0);
            lb[h][0] = fmaf(sel ? (e ? sc[0][1] : sc[0][0]) : (e ? sc[2][1] : sc[2][0]), fB0, bB);
            la[h][1] = (e ? sc[2][3] : sc[2][2]) * fA1;
            lb[h][1] = fmaf(sel ? (e ? sc[1][3] : sc[1][2]) : (e ? sc[3][3] : sc[3][2]), fB1, bB);
            mx[h][0] = fmaxf(la[h][0], lb[h][0]); mx[h][1] = fmaxf(la[h][1], lb[h][1]);
          }
#pragma unroll
          for (int o = 1; o <= 2; o <<= 1)
#pragma unroll
            for (int h = 0; h < 2; ++h)
#pragma unroll
              for (int r = 0; r < 2; ++r) mx[h][r] = fmaxf(mx[h][r], __shfl_xor_sync(0xffffffffu, mx[h][r], o));
          float oa[2][4][4];
#pragma unroll
          for (int h = 0; h < 2; ++h) {
#pragma unroll
            for (int r = 0; r < 2; ++r) { la[h][r] = ex2(la[h][r] - mx[h][r]); lb[h][r] = ex2(lb[h][r] - mx[h][r]); sm[h][r] = la[h][r] + lb[h][r]; }
            const uint32_t p0 = pack_bf16(la[h][0] * rjA0, lb[h][0] * rjB0), p1 = pack_bf16(la[h][1] * rjA1, lb[h][1] * rjB1);
            const uint32_t a00 = __byte_perm(p0, 0u, pLo), a02 = __byte_perm(p0, 0u, pA_), a03 = __byte_perm(p1, 0u, pLo);
            const uint32_t a10 = __byte_perm(p0, 0u, pHi), a11 = __byte_perm(p1, 0u, pA_), a13 = __byte_perm(p1, 0u, pHi);
#pragma unroll
            for (int i = 0; i < 4; ++i) {
              oa[h][i][0] = oa[h][i][1] = oa[h][i][2] = oa[h][i][3] = 0.f;
              mma_bf16(oa[h][i], a00, 0u, a02, a03, vb[h][0][i >> 1][2 * (i & 1)], vb[h][0][i >> 1][2 * (i & 1) + 1]);
              mma_bf16(oa[h][i], a10, a11, 0u, a13, vb[h][1][i >> 1][2 * (i & 1)], vb[h][1][i >> 1][2 * (i & 1) + 1]);
            }
          }
#pragma unroll
          for (int o = 1; o <= 2; o <<= 1)
#pragma unroll
            for (int h = 0; h < 2; ++h)
#pragma unroll
              for (int r = 0; r < 2; ++r) sm[h][r] += __shfl_xor_sync(0xffffffffu, sm[h][r], o);
          if (HE == 2 && lane == 0) mbar_arrive(bar + (hp ? B_ODONE : B_OH1));
          mbar_wait(bar + (hp ? B_XOLD2 : B_XOLD), 1);
#pragma unroll
          for (int jp = 0; jp < 4; ++jp) ldsm_x4(xo[16 * hp + 4 * jp], xo[16 * hp + 4 * jp + 1], xo[16 * hp + 4 * jp + 2], xo[16 * hp + 4 * jp + 3], qad + (X ^ (jp << 5)));
#pragma unroll
          for (int h = 0; h < 2; ++h) {
            const float i0 = rcp(sm[h][0]), i1 = rcp(sm[h][1]);
#pragma unroll
            for (int np = 0; np < 2; ++np)
              stsm_tag(qad + (X ^ (h << 6) ^ (np << 5)),
                       pack_bf16(oa[h][2 * np][0] * i0, oa[h][2 * np][1] * i0), pack_bf16(oa[h][2 * np][2] * i1, oa[h][2 * np][3] * i1),
                       pack_bf16(oa[h][2 * np + 1][0] * i0, oa[h][2 * np + 1][1] * i0), pack_bf16(oa[h][2 * np + 1][2] * i1, oa[h][2 * np + 1][3] * i1), make_tag(gq, t, 0u), 2 * h + np);
          }
          __syncwarp();
          if (HE == 1 && lane == 0) mbar_arrive(bar + (hp ? B_ODONE : B_OH1));
          slab_out_half(sb + (XS + 1 - hp) * SLOT, g_o + (size_t)m0 * D_ + g * 128 + hp * 64, wrow0, lane, hp);
          if (HE == 0 && lane == 0) mbar_arrive(bar + (hp ? B_ODONE : B_OH1));
          PROFT(lane == 0 && layer == PL && hp == 0, 128 + cw);
        };
        attend(0);
        if (DB1 == 2 && cu < 4) dump(1);
        if (cu == 4) nbar<15, 64>();
        else if (cu != 0) nbar_dyn(13 + (cu >> 2), 224);
        attend(1);
      } else {
#pragma unroll
        for (int i = 0; i < 32; ++i) kq[i] = pack_bf16(acc[2 * i], acc[2 * i + 1]);
        if (cu < 4) nbar<7, 256>();
        {
          const uint32_t vb = sb + (5 + 3 * wg) * SLOT + (rowq >> 1) + ((lchk ^ ((lane & 7) >> 1)) << 4);
#pragma unroll
          for (int jp = 8; jp < 16; ++jp)
            stsm_x4((vb ^ ((jp & 1) << 5)) + ((jp >> 1) & 3) * 4096,
                    pack_bf16(acc[8 * jp], acc[8 * jp + 1]), pack_bf16(acc[8 * jp + 2], acc[8 * jp + 3]),
                    pack_bf16(acc[8 * jp + 4], acc[8 * jp + 5]), pack_bf16(acc[8 * jp + 6], acc[8 * jp + 7]));
        }
        PROFT(tid_ == 128, layer * 16 + 2);
        Q_DONE();
        const uint32_t pA = sb + (3 + 3 * wg) * SLOT + (rowo & 8191);
        float sc0 = rs0 * L2E, sc1 = rs1 * L2E;
        const uint32_t wa0 = sb + SM_WPHI + lrow * 80 + lchk * 16;
        const uint32_t wu = c.cu >> 2, par = (layer >> 1) & 1;
        float p[2][4][4];
        uint32_t raw[2][4][4], ph[2][4][4];
        float kva[20], oa[2][20];
        auto kv_start = [&](int hp) {
#pragma unroll
          for (int h = 0; h < 2; ++h)
#pragma unroll
            for (int cp = 0; cp < 4; ++cp)
              stsm_x4(pA + hp * 16384 + h * 8192 + (X ^ (cp << 5)), ph[h][cp][0], ph[h][cp][1], ph[h][cp][2], ph[h][cp][3]);
          PROFT(tid_ == 128, layer * 16 + 11);
          fence_async_smem();
          nbar<1, 256>();
          const uint32_t hu = 2 * hp + wu;
          const uint32_t dP = (((sb + 3 * SLOT + hu * 8192) & 0x3FFFF) >> 4) | (512u << 16);
          const uint32_t dV = (((sb + 5 * SLOT + hu * 4096) & 0x3FFFF) >> 4) | (((SM_SD - 5 * SLOT - hu * 4096) >> 4) << 16);
          wgmma_fence();
#pragma unroll
          for (int ks = 0; ks < 8; ++ks)
            wgmma_n40_tt(kva, desc64(dP + (ks >> 2) * 3072 + (ks & 3) * 128, 0x40000040u),
                         desc64(dV + (ks >> 2) * (3072u - (2816u << 16)) + (ks & 3) * 64, 0x80000020u), ks != 0);
          wgmma_commit();
        };
        auto kv_end = [&](int hp) {
          wgmma_wait<0>();
#pragma unroll
          for (int i = 0; i < 20; ++i) asm volatile("" : "+f"(kva[i]) :: "memory");
          nbar_dyn(3 + wu, 128);
          PROFT(tid_ == 128, layer * 16 + 12);
          const bool od = lane & 1;
#pragma unroll
          for (int i = 0; i < 4; ++i)
            sts128(sb + (3 + hp) * SLOT + (cw * 128 + i * 32 + lane) * 16,
                   make_uint4(__float_as_uint(kva[4 * i]), __float_as_uint(kva[4 * i + 1]), __float_as_uint(kva[4 * i + 2]),
                              __float_as_uint(od == (i >= 2) ? 1.f : kva[4 * i + 3])));
          sts128(sb + (6 + hp) * SLOT + wg * 8192 + (wq * 32 + lane) * 16,
                 make_uint4(__float_as_uint(od ? kva[11] : kva[3]), __float_as_uint(od ? kva[15] : kva[7]), __float_as_uint(od ? kva[18] : kva[16]), __float_as_uint(1.f)));
          fence_async_smem();
          __syncwarp();
          if (lane == 0) mbar_arrive(bar + B_KVDONE - hp * 32);
          PROFT(tid_ == 128, layer * 16 + 3);
        };
        const uint4* const kvg = g_kv + (g * 2 + (layer >> 1)) * 2560 + cw * 128 + lane;
        uint4 u[5];
        auto kv_load = [&](int hp) {
#pragma unroll
          for (int i = 0; i < 4; ++i) u[i] = ld_relaxed4(kvg + hp * 1280 + i * 32);
          u[4] = ld_relaxed4(kvg + hp * 1280 + 1024 - cw * 96);
        };
        auto o_start = [&](int hp, const uint32_t (&pq)[2][4][4]) {
          PROFT(tid_ == 128 && hp == 0, layer * 16 + 10);
          if (hp == 0) mbar_wait(bar + B_KVDONE - 32, par);
          const bool od = lane & 1;
          uint32_t n = 0;
#pragma unroll 1
          while (!__all_sync(0xffffffffu, (od ? u[2].w : u[0].w) == 0x41800000u && (od ? u[3].w : u[1].w) == 0x41800000u && u[4].w == 0x41800000u)) {
#pragma unroll 1
            while (__any_sync(0xffffffffu, u[4].w < KVTH) && ++n < (1u << 20)) u[4].w = ld_relaxed(&kvg[hp * 1280 + 1024 - cw * 96].w);
            if (++n > (1u << 20)) { g_err = 6u; break; }
            kv_load(hp);
          }
          PROFT(tid_ == 128 && hp == 0, layer * 16 + 5);
          if (!od) { u[0].w = u[4].x; u[1].w = u[4].y; } else { u[2].w = u[4].x; u[3].w = u[4].y; }
#pragma unroll
          for (int i = 0; i < 4; i += 2)
            stsm_x4(sb + (5 + 3 * hp) * SLOT + rowo + (X ^ ((i & 2) << 4)),
                    pack_bf16(__uint_as_float(u[i].x), __uint_as_float(u[i].y)), pack_bf16(__uint_as_float(u[i].z), __uint_as_float(u[i].w)),
                    pack_bf16(__uint_as_float(u[i + 1].x), __uint_as_float(u[i + 1].y)), pack_bf16(__uint_as_float(u[i + 1].z), __uint_as_float(u[i + 1].w)));
          const uint32_t z2 = pack_bf16(__uint_as_float(u[4].z), __uint_as_float(u[4].z));
          if (t < 2) sts128(sb + (5 + 3 * hp) * SLOT + (wrow0 + gq + 8 * t) * 128 + ((4 ^ gq) << 4), make_uint4(z2, z2, z2, z2));
          fence_async_smem();
          nbar<1, 256>();
          PROFT(tid_ == 128 && hp == 1, layer * 16 + 4);
          const uint32_t dK = (((sb + (5 + 3 * hp) * SLOT) & 0x3FFFF) >> 4) | (512u << 16);
          wgmma_fence();
#pragma unroll
          for (int ks = 0; ks < 4; ++ks) {
#pragma unroll
            for (int hh = 0; hh < 2; ++hh) wgmma_n40_rs(oa[hh], pq[hh][ks], D128(dK + hh * 512 + ks * 128), ks != 0);
          }
          wgmma_commit();
        };
        auto o_end = [&](int hp) {
          wgmma_wait<0>();
          if (HE == 2 && lane == 0) mbar_arrive(bar + (hp ? B_ODONE : B_OH1));
#pragma unroll
          for (int i = 0; i < 20; ++i) asm volatile("" : "+f"(oa[0][i]), "+f"(oa[1][i]) :: "memory");
#pragma unroll
          for (int hh = 0; hh < 2; ++hh) {
            const float i0 = rcp(oa[hh][16] + 1e-6f), i1 = rcp(oa[hh][18] + 1e-6f);
            const uint32_t qad = sb + (3 + hp) * SLOT + rowo, hx = hh << 6;
#pragma unroll
            for (int np = 0; np < 2; ++np)
              stsm_tag(qad + (X ^ hx ^ (np << 5)),
                       pack_bf16(oa[hh][8 * np] * i0, oa[hh][8 * np + 1] * i0), pack_bf16(oa[hh][8 * np + 2] * i1, oa[hh][8 * np + 3] * i1),
                       pack_bf16(oa[hh][8 * np + 4] * i0, oa[hh][8 * np + 5] * i0), pack_bf16(oa[hh][8 * np + 6] * i1, oa[hh][8 * np + 7] * i1), make_tag(gq, t, 1u), 2 * hh + np);
          }
          __syncwarp();
          if (HE == 1 && lane == 0) mbar_arrive(bar + (hp ? B_ODONE : B_OH1));
          slab_out_half(sb + (3 + hp) * SLOT, g_o + (size_t)m0 * D_ + g * 128 + hp * 64, wrow0, lane, hp);
          if (HE == 0 && lane == 0) mbar_arrive(bar + (hp ? B_ODONE : B_OH1));
        };
#define XO_LOAD() \
        mbar_wait(bar + B_XOLD, 0); \
        mbar_wait(bar + B_XOLD2, 0); \
        _Pragma("unroll") for (int jp = 0; jp < 8; ++jp) \
          ldsm_x4(xo[4 * jp], xo[4 * jp + 1], xo[4 * jp + 2], xo[4 * jp + 3], sb + (XS + 1 - (jp >> 2)) * SLOT + rowo + (X ^ ((jp & 3) << 5)));
#define SC_RELOAD() \
        sc0 = __uint_as_float(lds_vol(sb + SM_RS + (16 + wrow0 + gq) * 4)) * L2E; sc1 = __uint_as_float(lds_vol(sb + SM_RS + (24 + wrow0 + gq) * 4)) * L2E;
        __syncwarp();
        phi_proj<0>(p, kq, wa0);
        phi_exp(raw[0], p[0], sc0, sc1);
        phi_exp(raw[1], p[1], sc0, sc1);
        phi_proj<16>(p, kq, wa0 + 5120);
        phi_norm<0>(ph, raw, kq, wa0, sc0, sc1, rs0, rs1);
        kv_start(0);
        phi_exp(raw[0], p[0], sc0, sc1);
        kv_end(0);
        if (RL & 1) { SC_RELOAD(); }
        XO_LOAD();
        phi_exp(raw[1], p[1], sc0, sc1);
        phi_proj<32>(p, kq, wa0);
        phi_norm<16>(ph, raw, kq, wa0 + 5120, sc0, sc1, rs0, rs1);
        kv_start(1);
        if (lane == 0) release2(bar + B_E3);
        phi_exp(raw[0], p[0], sc0, sc1);
        kv_end(1);
        if (RL & 2) { SC_RELOAD(); }
        kv_load(0);
        phi_exp(raw[1], p[1], sc0, sc1);
        phi_proj<48>(p, kq, wa0 + 5120);
        phi_norm<32>(ph, raw, kq, wa0, sc0, sc1, 1.f, 1.f);
        o_start(0, ph);
        phi_exp(raw[0], p[0], sc0, sc1);
        o_end(0);
        SC_RELOAD();
        kv_load(1);
        phi_exp(raw[1], p[1], sc0, sc1);
        phi_norm<48>(ph, raw, kq, wa0 + 5120, sc0, sc1, 1.f, 1.f);
        o_start(1, ph);
        o_end(1);
      }
      __syncwarp();
      PROFT(lane == 0 && layer == PL, 216 + cw);
      if (lane == 0) mbar_arrive(bar + B_EPI);
      PROFT(tid_ == 128, layer * 16 + 6);
    }
    {
      PHASE_CTX();
      const uint32_t wu = c.cu >> 2;
      const uint32_t dA0 = (((sb + wu * 8192) & 0x3FFFF) >> 4) | (1u << 16), dB0 = ((sb & 0x3FFFF) >> 4) | (512u << 16);
#pragma unroll
      for (int i = 0; i < 32; ++i) { acc[128 + 2 * i] = bf_lo(xo[i]); acc[129 + 2 * i] = bf_hi(xo[i]); }
      nbar_dyn(3 + wg, 128);
      uint64_t ta = (layer & 1) ? WO_A1 : WO_A0, tw = (layer & 1) ? WO_B1 : WO_B0;
#pragma unroll 1
      for (int i = 0; i < 16; ++i) {
        mbar_wait(bar + B_FULLT + i * 8, layer & 1);
        PROFT(tid_ == 128 && layer == PL, 160 + i);
        if (i >= 2) tile_check(sb + ((uint32_t)ta & 15) * SLOT, g_o + (size_t)m0 * D_ + ((2 * g + (int)(WOORD >> (4 * i))) & 15) * 64, wrow0, lane, ~layer);
        const uint32_t da = dA0 + ((uint32_t)ta & 15) * 1024, db = dB0 + ((uint32_t)tw & 15) * 1024;
        ta >>= 4; tw >>= 4;
        if (WSK && i == 16 - WSK && wu) nbar<6, 256>();
        wgmma_fence();
#pragma unroll
        for (int k = 0; k < 4; ++k) wgmma_n128(acc, D128(da + k * 2), D128(db + k * 128), 1);
        wgmma_commit();
        if (WSK && i == 15 && !wu) asm volatile("bar.arrive 6, 256;" ::: "memory");
        if (i == 0) {
          if (elected) {
            release2(bar + B_E2);
          }
        } else {
          wgmma_wait<1>();
          if (elected && i < 12) release2(bar + B_CONS + (i - 1) * 8);
          if (elected && (unsigned)(i - 13) < 2u && layer + 1 < NLAYERS) release2(bar + B_EMPTYS + (i - 13) * 8);
        }
      }
      const bool last = layer == NLAYERS - 1;
      Tag xt = make_tag(gq, (last || !(UNS & 1)) ? 4 : t, lds_vol(sb + SM_EPOCH) + layer + 1);
      asm volatile("" : "+r"(xt.me), "+r"(xt.mo), "+r"(xt.tg) :: "memory");
      wgmma_wait<0>();
#pragma unroll
      for (int i = 128; i < 192; ++i) asm volatile("" : "+f"(acc[i]) :: "memory");
      if (elected && !last) release2(bar + B_EMPTYS + 16);
      PROFT(tid_ == 128, layer * 16 + 7);
      X_HALF(0, xt);
      if (last) {
        __syncwarp();
        slab_out_half(sb + XS * SLOT, c.out + (size_t)m0 * D_ + g * 128, wrow0, lane);
        X_HALF(1, (Tag{0u, 0u, 0u}));
        __syncwarp();
        slab_out_half(sb + (XS + 1) * SLOT, c.out + (size_t)m0 * D_ + g * 128 + 64, wrow0, lane);
        __syncwarp();
        if (lane == 0) mbar_arrive(bar + B_XDONE);
        PROFT(tid_ == 128, layer * 16 + 24);
        break;
      }
      __syncwarp();
      slab_out_half(sb + XS * SLOT, g_x + (size_t)m0 * D_ + g * 128, wrow0, lane, true);
      __syncwarp();
      if (lane == 0) mbar_arrive(bar + B_XH0);
      nbar_dyn(3 + wu, 128);
    }
  }
}

__device__ __forceinline__ void flag_fetch(uint32_t bar, uint32_t cp, const unsigned int* f) {
  asm volatile("{\n.reg .pred p;\nelect.sync _|p, 0xffffffff;\n@p mbarrier.expect_tx.relaxed.cta.shared::cta.b64 [%2], 64;\n"
               "@p cp.async.bulk.shared::cluster.global.mbarrier::complete_tx::bytes [%0], [%1], 64, [%2];\n}\n"
               ::"r"(cp), "l"(f), "r"(bar + 128) : "memory");
}
__device__ __forceinline__ void src_wait_async(uint32_t bar, uint32_t cp, const unsigned int* f, unsigned int target, int kb, uint32_t& ready, int lane) {
  uint32_t n = 0;
#pragma unroll 1
  while (true) {
    ready |= __ballot_sync(0xffffffffu, (int)(lds_vol(cp + (lane & 15) * 4) - target) >= 0);
    if ((ready >> kb) & 1) break;
    if (n > (1u << 20)) { g_err = 5u; break; }
    if ((n++ & PMOD) == 0) flag_fetch(bar, cp, f);
    __nanosleep(PSL);
  }
}

__device__ __forceinline__ int kblock0(int i, int g) {
  const int j = i >> 1, p = max(g, NCOM) + j - NCOM;
  return (j < NCOM ? j : p < 8 ? p : p - 8 + NCOM) * 2 + (i & 1);
}

__device__ __forceinline__ int wo_kblock(int m, int g) { return (2 * g + (int)((WOORD >> (4 * m)) & 15)) & 15; }

__global__ void __cluster_dims__(2, 1, 1) __launch_bounds__(384, 1)
mega_kernel(const __grid_constant__ CUtensorMap tm_x0, const __grid_constant__ CUtensorMap tm_x,
            const __grid_constant__ CUtensorMap tm_o,
            const __grid_constant__ CUtensorMap tm_wA, const __grid_constant__ CUtensorMap tm_wB,
            const __grid_constant__ CUtensorMap tm_woA, const __grid_constant__ CUtensorMap tm_woB,
                        const bf16* __restrict__ wB, const bf16* __restrict__ wphi, bf16* __restrict__ out) {
  extern __shared__ uint8_t smem_raw[];
  const uint32_t sb = (smem_u32(smem_raw) + 1023u) & ~1023u;
  const uint32_t bar = sb + SM_BAR;
  const int warp = __shfl_sync(0xffffffffu, threadIdx.x >> 5, 0), lane = threadIdx.x & 31;
  if (blockIdx.x >= 128) {
    const int xb = blockIdx.x - 128;
    const int ch = threadIdx.x % 96, rg = threadIdx.x / 96, gg = xb * 2 + ch / 48, sec = (ch % 48) >> 4;
    const uint4* src = reinterpret_cast<const uint4*>(wB + (size_t)rg * 3072 + (sec == 2 ? 0 : 1024 + sec * 1024) + gg * 128 + (ch & 15) * 8);
    float s[8] = {0.f, 0.f, 0.f, 0.f, 0.f, 0.f, 0.f, 0.f};
#pragma unroll 1
    for (int r0 = 0; r0 < 256; r0 += 32) {
      uint4 v[32];
#pragma unroll
      for (int r = 0; r < 32; ++r) v[r] = __ldg(src + (size_t)(r0 + r) * 1536);
#pragma unroll
      for (int r = 0; r < 32; ++r) {
        s[0] += bf_lo(v[r].x); s[1] += bf_hi(v[r].x); s[2] += bf_lo(v[r].y); s[3] += bf_hi(v[r].y);
        s[4] += bf_lo(v[r].z); s[5] += bf_hi(v[r].z); s[6] += bf_lo(v[r].w); s[7] += bf_hi(v[r].w);
      }
    }
    float* cd = g_cs + (ld_relaxed(&g_epoch) & 1) * 6144 + 3072 + xb * 768 + ch * 8;
    red_add4(cd, s[0], s[1], s[2], s[3]);
    red_add4(cd + 4, s[4], s[5], s[6], s[7]);
    nbar<1, 384>();
    if (threadIdx.x < 2) flag_add(&g_csflag[8 + xb * 2 + threadIdx.x].v);
    return;
  }
  const int bid = blockIdx.x;
  const int cr = bid & 1;
  const int g = (bid >> 1) & 7;
  const int rb = (bid >> 4) * 2 + cr;
  const int m0 = rb * 128;

  if (warp < 4) {
    asm volatile("setmaxnreg.dec.sync.aligned.u32 40;");
    asm volatile("barrier.cluster.arrive.relaxed.aligned;" ::: "memory");
    const unsigned int epoch = warp ? ld_relaxed(&g_epoch) : 0u;
    if (warp) cluster_wait();
    unsigned int xbase = epoch * NLAYERS;
    auto wo_a = [&](int layer, int m1) {
      uint64_t ts = ((layer & 1) ? WO_A1 : WO_A0) >> (4 * m1), td = ((layer & 1) ? WO_DA1 : WO_DA0) >> (4 * m1), tk = WOORD >> (4 * m1);
      uint32_t ready = 0u;
#pragma unroll 1
      for (int m = m1; m < 16; m += AW) {
        const int kb = (2 * g + (uint32_t)tk) & 15;
        uint32_t dst = sb + ((uint32_t)ts & 15) * SLOT, fb = bar + B_FULLT + m * 8, eb = bar + B_CONS + ((uint32_t)td & 15) * 8;
        int kc = kb * 64;
        ts >>= 4 * AW; td >>= 4 * AW; tk >>= 4 * AW;
        asm volatile("" : "+r"(dst), "+r"(fb), "+r"(eb), "+r"(kc));
        bool fr = false;
        if (!((ready >> kb) & 1)) {
          PROFT(m == 2 && lane == 0, 64 + layer * 16 + 2);
          if (EP && m > EP) src_wait_async(bar, bar + B_FLG, g_of + rb * 32, xbase + layer + 1, kb, ready, lane);
          else fr = src_wait_tma(g_of + rb * 32, xbase + layer + 1, 1u << kb, ready, lane, eb, layer & 1);
          fence_async_all();
        }
        if (!fr) mbar_wait_u(eb, layer & 1);
        tma_2d_e(dst, &tm_o, kc, m0, fb);
        if (EP && m >= EP && (ready & 0xFFFFu) != 0xFFFFu) flag_fetch(bar, bar + B_FLG, g_of + rb * 32);
        PROFT(lane == 0 && layer == PL, 176 + m);
      }
    };
    auto wo_w = [&](int layer) {
      const CUtensorMap* tx = layer == 0 ? &tm_x0 : &tm_x;
      const CUtensorMap* two = (layer & 1) ? &tm_woB : &tm_woA;
      uint64_t ts = (layer & 1) ? WO_B1 : WO_B0, td = (layer & 1) ? WO_DB1 : WO_DB0, tk = WOORD;
      uint32_t pb = 0;
      fence_async_all();
      mbar_wait_u(bar + B_R0, layer & 1);
      expect_tx_e(bar + B_XOLD, 16384);
      tma_2d_e(sb + (XS + 1) * SLOT, tx, g * 128, m0, bar + B_XOLD);
#pragma unroll 1
      for (int m = 0; m < 16; ++m) {
        uint32_t dst = sb + ((uint32_t)ts & 15) * SLOT + cr * 8192, fb = bar + B_FULLT + m * 8, eb = bar + B_CONS + ((uint32_t)td & 15) * 8;
        int kc = ((2 * g + (uint32_t)tk) & 15) * 64;
        ts >>= 4; td >>= 4; tk >>= 4;
        asm volatile("" : "+r"(dst), "+r"(fb), "+r"(eb), "+r"(kc));
        if (eb != pb) mbar_wait_u(eb, layer & 1);
        pb = eb;
        tma_2d_mc_e(dst, two, g * 128 + cr * 64, kc, fb);
        expect_tx_e(fb, m < 2 ? 16384 : 32768);
        PROFT(lane == 0 && layer == PL, 144 + m);
        if (m == ((layer & 1) ? XB2 : 0)) {
          expect_tx_e(bar + B_XOLD2, 16384);
          tma_2d_e(sb + XS * SLOT, tx, g * 128 + 64, m0, bar + B_XOLD2);
        }
      }
    };
    if (warp == 0) {
      cluster_wait();
      PROFT(lane == 0, 125);
#pragma unroll 1
      for (int layer = 0; layer < NLAYERS; ++layer) {
        const CUtensorMap* tx = layer == 0 ? &tm_x0 : &tm_x;
        const CUtensorMap* tw = (layer & 1) ? &tm_wB : &tm_wA;
        uint32_t s = layer == 0, u = 0, ready = layer == 0 ? 0xFFFFu : 0u;
#pragma unroll 1
        for (int i = s; i < 16; ++i) {
          const int kb = layer == 0 ? kblock0(i, g) : wo_kblock(i, g), kc = kb * 64;
          const uint32_t fb = bar + B_FULLS + s * 8;
          const uint32_t kd = sb + (((QK >> (4 * s)) & 15) + cr) * SLOT, qd = sb + ((QQ >> (4 * s)) & 15) * SLOT + cr * 8192;
          const uint32_t need = 1u << kb;
          const bool ext = i >= 2 || layer == 0, early = ext && (ready & need) == need;
          mbar_wait_u(bar + B_EMPTYS + s * 8, (u + (s ? layer : 0) + 1) & 1);
          if (early) tma_2d_e(sb + ((QA >> (4 * s)) & 15) * SLOT, tx, kc, m0, fb);
          tma_2d_mc_e(kd, tw, 1024 + cr * 1024 + g * 128, kc, fb);
          tma_2d_mc_e(kd + 8192, tw, 1024 + cr * 1024 + g * 128 + 64, kc, fb);
          tma_2d_mc_e(qd, tw, g * 128 + cr * 64, kc, fb);
          expect_tx_e(fb, ext ? 65536 : 49152);
          PROFT(lane == 0 && layer == 0 && i == 1, 31);
          if (layer == 0 && g >= NCOM && i == XPF + (((g - NCOM) * XPM) >> 2)) {
            if (i <= 2) mbar_wait_u(bar + B_FULLS, 0);
            tma_pf_e(&tm_x0, g * 128, m0);
            tma_pf_e(&tm_x0, g * 128 + 64, m0);
          }
          if (layer < 2 && i >= PFS) {
            const int j = i - PFS;
            if (j < 2) tma_pf_e(layer ? &tm_woB : &tm_woA, g * 128 + j * 64, rb * 64);
            else if (j < 8 && layer == 0) tma_pf_e(&tm_wB, ((j >> 1) - 1) * 1024 + g * 128 + (j & 1) * 64, rb * 64);
          }
          if (ext && !early) {
            PROFT(i == 2 && lane == 0, 64 + layer * 16 + 0);
            src_wait_tma(g_xf + rb * 32, xbase + layer + 1, need, ready, lane, fb, 0);
            PROFT(i == 2 && lane == 0, 64 + layer * 16 + 1);
            fence_async_all();
            tma_2d_e(sb + ((QA >> (4 * s)) & 15) * SLOT, tx, kc, m0, fb);
          }
          if (++s == 3) { s = 0; ++u; }
        }
        if (layer == 0) xbase = ld_relaxed(&g_epoch) * NLAYERS;
        if (PG & 1) mbar_wait_u(bar + B_OH1, layer & 1);
        if (PG & 4) mbar_wait_u(bar + B_E3, layer & 1);
        wo_a(layer, 2);
      }
    } else {
      if (warp >= 2) {
        const int h2 = threadIdx.x - 64;
        if (h2 < 16) sts_f(sb + SM_RS + h2 * 4, 0.f);
        if (h2 == 0) sts_f(sb + SM_EPOCH, __uint_as_float(epoch));
        if (h2 < 16) sts_f(bar + B_FLG + h2 * 4, __uint_as_float(xbase));
        mbar_wait_u(bar + B_FULLS, 0);
        colsum(&tm_wA, g_cs + (epoch & 1) * 6144, rb, g, warp - 2, 2, lane, warp == 2 ? sb + SM_SD : (sb + SM_BP + 1023u) & ~1023u, bar + B_CB + (warp - 2) * 8, 0);
#pragma unroll 1
        for (int i = h2; i < 320; i += 64) g_kv[(g * 16 + rb) * 320 + i] = make_uint4(0u, 0u, 0u, 0u);
        fence_async_all();
        nbar<5, 64>();
        if (h2 == 0) flag_add(&g_csflag[g].v);
        PROFT(h2 == 0, 242);
#pragma unroll 1
        for (int i = h2; i < 512; i += 256) {
          uint4 w[4];
#pragma unroll
          for (int j = 0; j < 4; ++j) w[j] = __ldg(reinterpret_cast<const uint4*>(wphi + (size_t)g * 4096) + i + j * 64);
#pragma unroll
          for (int j = 0; j < 4; ++j) sts128(sb + SM_WPHI + ((i >> 2) + j * 16) * 80 + (i & 3) * 16, w[j]);
        }
      }
      if (warp == 1) {
        if (lane >= 27) {
          const CUtensorMap* tm = lane == 27 ? &tm_o : lane == 28 ? &tm_wB : lane == 29 ? &tm_woA : lane == 30 ? &tm_woB : &tm_x;
          asm volatile("prefetch.tensormap [%0];" ::"l"(tm) : "memory");
        }
        __syncwarp();
        {
#pragma unroll 1
          for (int e = 0;; ++e) {
            if (e > 0 && e < NLAYERS) {
              mbar_wait_u(bar + B_XH0, (e - 1) & 1);
              flag_set_x(g_xf + rb * 32 + 2 * g, xbase + e + 1, UNS & 1);
            }
            mbar_wait_u(bar + B_XDONE, e & 1);
            PROFT(e < 4, 64 + e * 16 + 4);
            if (e == NLAYERS) {
              if (bid == 0) g_epoch = epoch + 1;
              break;
            }
            PROFT(e < 4, 64 + e * 16 + 5);
            flag_set(g_xf + rb * 32 + 2 * g + 1, xbase + e + 1);
            PROFT(e < 4, 64 + e * 16 + 7);
            if ((e & 1) == 0) {
#pragma unroll 1
              for (int hp = 0; hp < 2; ++hp) {
                uint4* kvl = g_kv + ((g * 2 + (e >> 1)) * 2 + hp) * 1280;
                mbar_wait_u(bar + B_KVDONE - hp * 32, (e >> 1) & 1);
                PROFT(e == PL, 243 + hp * 4);
                bulk_red_add_e(kvl + rb * 64, sb + (3 + hp) * SLOT + rb * 1024, 16384 - rb * 1024);
                if (rb) bulk_red_add_e(kvl, sb + (3 + hp) * SLOT, rb * 1024);
                bulk_red_add_e(kvl + 1024, sb + (6 + hp) * SLOT, 2048);
                bulk_red_add_e(kvl + 1152, sb + (6 + hp) * SLOT + 8192, 2048);
                bulk_commit();
                PROFT(e < 4, 64 + e * 16 + 6);
              }
              bulk_wait_read0();
              __syncwarp();
              if (lane < 2) release2(bar + B_E1);
              __syncwarp();
            }
            mbar_wait_u(bar + B_OH1, e & 1);
            PROFT(e == PL, 251);
            flag_set_x(g_of + rb * 32 + 2 * g, xbase + e + 1, UNS & 2);
            PROFT(e < 4, 64 + e * 16 + 9);
            mbar_wait_u(bar + B_ODONE, e & 1);
            PROFT(e < 4, 64 + e * 16 + 8);
            flag_set_x(g_of + rb * 32 + 2 * g + 1, xbase + e + 1, UNS & 4);
            PROFT(e < 4, 64 + e * 16 + 11);
          }
        }
      } else {
        const int h2 = threadIdx.x - 64;
        const float* cs = g_cs + (epoch & 1) * 6144;
#pragma unroll 1
        for (int layer = 0; layer < NLAYERS; ++layer) {
          if (warp == 2 && layer < 2) {
            if ((PG & 2) && layer) mbar_wait_u(bar + B_XH0, 0);
            if (lane == 0) flag_wait_t<CSLP>(&g_csflag[layer * 8 + g].v, (epoch + 1) * (16u + layer));
            __syncwarp();
            float4 a[3];
#pragma unroll
            for (int i = 0; i < 3; ++i) a[i] = __ldcg(reinterpret_cast<const float4*>(cs + layer * 3072 + g * 384) + i * 32 + lane);
#pragma unroll 1
            for (int i = 0; i < 3; ++i) {
              const float av[4] = {a[0].x, a[0].y, a[0].z, a[0].w};
              a[0] = a[1]; a[1] = a[2];
#pragma unroll
              for (int j = 0; j < 4; ++j) {
                const float c1 = bf16r(av[j]), c2 = bf16r(av[j] - c1), c3 = (av[j] - c1) - c2;
                sts128(sb + SM_BP + layer * 6144 + ((i * 32 + lane) * 4 + j) * 16, make_uint4(pack_bf16(c1, c2), pack_bf16(c3, 0.f), 0u, 0u));
              }
            }
            fence_async_smem();
            __syncwarp();
            if (lane == 0) mbar_arrive(bar + (layer ? B_CS2 : B_CS));
            PROFT(lane == 0, 64 + layer * 16 + 12);
            if (layer == 0) {
              uint4* hz = g_halo + (rb * 8 + g) * 1024;
#pragma unroll 2
              for (int i = lane; i < 1024; i += 32) hz[i] = make_uint4(0u, 0u, 0u, 0u);
              if (lane < 12) reinterpret_cast<float4*>(g_cs + ((epoch & 1) ^ 1) * 6144 + bid * 48)[lane] = make_float4(0.f, 0.f, 0.f, 0.f);
              g_stats[(2 + (lane >> 4)) * S_ + m0 + g * 16 + (lane & 15)] = make_float2(0.f, 0.f);
              __syncwarp();
              if (lane == 0) flag_add(&g_csflag[8 + g].v);
            }
          }
          if (warp == 3) {
            const bool hal = (layer & 1) && rb > 0;
            {
              uint32_t rdy = 0u;
              src_wait<256>(g_xf + rb * 32, xbase + layer + 1, 0xAAAAu, rdy, lane);
              rdy = 0u;
              if (hal) src_wait<256>(g_xf + (rb - 1) * 32, xbase + layer + 1, 0xAAAAu, rdy, lane);
            }
            float2 u[5];
            const float2* sp = g_stats + layer * S_ + m0 + lane;
#pragma unroll
            for (int i = 0; i < 4; ++i) u[i] = __ldcg(sp + i * 32);
            u[4] = __ldcg(hal ? sp - 16 : sp);
            if (layer == 3) g_stats[(lane >> 4) * S_ + m0 + g * 16 + (lane & 15)] = make_float2(0.f, 0.f);
#pragma unroll 1
            for (int i = 0; i < (hal ? 5 : 4); ++i) {
              const int r = i < 4 ? 16 + i * 32 + lane : lane;
              const float sum = u[0].x, sq = u[0].y;
              u[0] = u[1]; u[1] = u[2]; u[2] = u[3]; u[3] = u[4];
              const float mean = sum * (1.f / D_);
              const float var = fmaxf(fmaf(-sum, mean, sq) * (1.f / D_), 0.f);
              const float sd = bf16r(sqrtf(bf16r(bf16r(var) + 1e-5f)));
              sts_f(sb + SM_RS + r * 4, 1.f / sd);
              if (i < 4) {
                const float hm = -0.5f * bf16r(mean);
                const uint32_t s2 = pack_bf16(sd, sd);
                if (!(layer & 1)) sts128(sb + SM_SD + (r - 16) * 64 + ((r >> 1) & 3) * 16, make_uint4(s2, s2, s2, s2));
                sts128(sb + SM_AP + (r - 16) * 16, make_uint4(pack_bf16(hm, hm), pack_bf16(hm, 0.f), 0u, 0u));
              }
            }
            fence_async_smem();
            __syncwarp();
            if (lane == 0) mbar_arrive(bar + B_STAT);
            PROFT(lane == 0, 64 + layer * 16 + 14);
            wo_w(__shfl_sync(0xffffffffu, layer, 0));
          }
        }
      }
    }
    __syncwarp();
    asm volatile("barrier.cluster.arrive.relaxed.aligned;\nbarrier.cluster.wait.aligned;\n" ::: "memory");
  } else {
    if (warp == 5) {
      if (lane == 0) {
        mbar_init(bar + B_FULLS, 1);
        asm volatile("fence.mbarrier_init.release.cluster;" ::: "memory");
      }
      __syncwarp();
      expect_tx_e(bar + B_FULLS, 65536);
      tma_2d_e(sb + XS * SLOT, &tm_x0, 0, m0, bar + B_FULLS);
#pragma unroll
      for (int j = 0; j < 6; ++j)
        tma_2d_e(sb + (j < 4 ? j + 4 : j - 2) * 8192, &tm_wA, (j < 4 ? 1024 + (j >> 1) * 1024 : 0) + g * 128 + (j & 1) * 64, 0, bar + B_FULLS);
      PROFT(lane == 0, 241);
    }
    if (lane < 8 && warp != 5 && threadIdx.x != 128) {
      const int i = (warp - 4) * 8 + lane;
      mbar_init(bar + i * 8, i < 32 ? 1u << ((BAR_CNT >> (2 * i)) & 3) : i < 48 ? 1u : (i == 59 || i == 60) ? 16u : i < 63 ? 4u : 8u);
      asm volatile("fence.mbarrier_init.release.cluster;" ::: "memory");
    }
    __syncwarp();
    asm volatile("barrier.cluster.arrive.relaxed.aligned;" ::: "memory");
    asm volatile("setmaxnreg.inc.sync.aligned.u32 232;");
    cluster_wait();
    PROFT(threadIdx.x == 128, 0);
    Ctx c; c.sb = sb; c.g = g; c.rb = rb; c.cu = warp - 4; c.out = out;
    consumer(c);
    asm volatile("bar.warp.sync 0xffffffff;\nbarrier.cluster.arrive.relaxed.aligned;\nbarrier.cluster.wait.aligned;\n" ::: "memory");
  }
}

typedef CUresult (*PFN_encodeTiled)(CUtensorMap*, CUtensorMapDataType, cuuint32_t, void*, const cuuint64_t*, const cuuint64_t*,
                                    const cuuint32_t*, const cuuint32_t*, CUtensorMapInterleave, CUtensorMapSwizzle,
                                    CUtensorMapL2promotion, CUtensorMapFloatOOBfill);

static CUtensorMap make_map(PFN_encodeTiled enc, const void* ptr, uint64_t cols, uint64_t rows, uint32_t box_c, uint32_t box_r, uint32_t nb = 1) {
  CUtensorMap m;
  cuuint64_t dims[3] = {nb > 1 ? box_c : cols, rows, cols / box_c};
  cuuint64_t strides[2] = {cols * 2, box_c * 2};
  cuuint32_t box[3] = {box_c, box_r, nb};
  cuuint32_t es[3] = {1, 1, 1};
  CUresult r = enc(&m, CU_TENSOR_MAP_DATA_TYPE_BFLOAT16, nb > 1 ? 3 : 2, const_cast<void*>(ptr), dims, strides, box, es, CU_TENSOR_MAP_INTERLEAVE_NONE,
      CU_TENSOR_MAP_SWIZZLE_128B, CU_TENSOR_MAP_L2_PROMOTION_L2_256B, CU_TENSOR_MAP_FLOAT_OOB_FILL_NONE);
  (void)r;
  return m;
}

extern "C" void kernel_launch(void* const* d_in, const int* in_sizes, int n_in, void* d_out, int out_size) {
  const bf16* A_x = (const bf16*)d_in[0];
  const bf16* A_wqkv = (const bf16*)d_in[1];
  const bf16* A_wphi = (const bf16*)d_in[2];
  const bf16* A_wo = (const bf16*)d_in[3];
  const bf16* B_wqkv = (const bf16*)d_in[5];
  const bf16* B_wo = (const bf16*)d_in[6];
  bf16* out = (bf16*)d_out;

  static PFN_encodeTiled enc = nullptr;
  static bf16 *p_x, *p_o;
  if (!enc) {
    void* fn = nullptr; cudaDriverEntryPointQueryResult qr;
    cudaGetDriverEntryPoint("cuTensorMapEncodeTiled", &fn, cudaEnableDefault, &qr);
    enc = (PFN_encodeTiled)fn;
    cudaGetSymbolAddress((void**)&p_x, g_x);
    cudaGetSymbolAddress((void**)&p_o, g_o);
    cudaFuncSetAttribute(mega_kernel, cudaFuncAttributeMaxDynamicSharedMemorySize, SM_TOTAL);
  }
  CUtensorMap tm_x0 = make_map(enc, A_x, 1024, 2048, 64, 128);
  CUtensorMap tm_x = make_map(enc, p_x, 1024, 2048, 64, 128);
  CUtensorMap tm_o = make_map(enc, p_o, 1024, 2048, 64, 128);
  CUtensorMap tm_wA = make_map(enc, A_wqkv, 3072, 1024, 64, 64);
  CUtensorMap tm_wB = make_map(enc, B_wqkv, 3072, 1024, 64, 64);
  CUtensorMap tm_woA = make_map(enc, A_wo, 1024, 1024, 64, 64);
  CUtensorMap tm_woB = make_map(enc, B_wo, 1024, 1024, 64, 64);
  mega_kernel<<<128 + NX, 384, SM_TOTAL, cudaStreamPerThread>>>(tm_x0, tm_x, tm_o, tm_wA, tm_wB, tm_woA, tm_woB,
                                                           B_wqkv, A_wphi, out);
}
```

```cpp
#include <cuda_runtime.h>
#include <cuda_bf16.h>
#include <cuda.h>
#include <stdint.h>

typedef __nv_bfloat16 bf16;

constexpr int S_ = 2048, D_ = 1024;

struct __align__(128) Flag { unsigned int v; unsigned int pad[31]; };
__device__ __align__(1024) bf16 g_x[S_ * D_];
__device__ __align__(1024) bf16 g_o[S_ * D_];
__device__ __align__(1024) uint4 g_halo[128 * 2 * 512];
__device__ __align__(1024) uint4 g_kv[8 * 2 * 2 * 1280];
__device__ __align__(1024) float2 g_stats[4 * S_];
__device__ __align__(1024) float g_cs[2 * 2 * 3072];
__device__ Flag g_csflag[16];
__device__ __align__(128) unsigned int g_xf[16 * 32], g_of[16 * 32];
__device__ unsigned int g_epoch, g_err;
#define PROFT(cond, idx) asm volatile("" ::: "memory")

__device__ __forceinline__ uint32_t smem_u32(const void* p) { return (uint32_t)__cvta_generic_to_shared(p); }
__device__ __forceinline__ void mbar_init(uint32_t bar, uint32_t count) {
  asm volatile("mbarrier.init.shared::cta.b64 [%0], %1;" ::"r"(bar), "r"(count) : "memory");
}
__device__ __forceinline__ void mbar_expect_tx(uint32_t bar, uint32_t bytes) {
  asm volatile("mbarrier.arrive.expect_tx.shared::cta.b64 _, [%0], %1;" ::"r"(bar), "r"(bytes) : "memory");
}
__device__ __forceinline__ void mbar_arrive(uint32_t bar) {
  asm volatile("mbarrier.arrive.shared::cta.b64 _, [%0];" ::"r"(bar) : "memory");
}
__device__ __forceinline__ bool mbar_try_wait(uint32_t bar, uint32_t parity) {
  uint32_t ok;
  asm volatile("{\n.reg .pred p;\nmbarrier.try_wait.parity.shared::cta.b64 p, [%1], %2;\nselp.b32 %0, 1, 0, p;\n}\n"
               : "=r"(ok) : "r"(bar), "r"(parity) : "memory");
  return ok != 0;
}
__device__ __forceinline__ bool mbar_test_wait(uint32_t bar, uint32_t parity) {
  uint32_t ok;
  asm volatile("{\n.reg .pred p;\nmbarrier.test_wait.parity.shared::cta.b64 p, [%1], %2;\nselp.b32 %0, 1, 0, p;\n}\n"
               : "=r"(ok) : "r"(bar), "r"(parity) : "memory");
  return ok != 0;
}
__device__ __forceinline__ uint64_t gtimer() {
  uint64_t t; asm volatile("mov.u64 %0, %globaltimer;" : "=l"(t)); return t;
}
__device__ __forceinline__ void mbar_wait(uint32_t bar, uint32_t parity) {
  uint32_t n = 0;
#pragma unroll 1
  while (!mbar_try_wait(bar, parity)) {
    if (++n > (1u << 22)) { g_err = 1u; break; }
  }
}
__device__ __forceinline__ unsigned int ld_acquire(const unsigned int* p) {
  unsigned int v; asm volatile("ld.acquire.gpu.global.u32 %0, [%1];" : "=r"(v) : "l"(p) : "memory"); return v;
}
__device__ __forceinline__ void flag_add(unsigned int* p) {
  asm volatile("red.release.gpu.global.add.u32 [%0], 1;" ::"l"(p) : "memory");
}
__device__ __forceinline__ void flag_set(unsigned int* p, unsigned int v) {
  asm volatile("st.release.gpu.global.u32 [%0], %1;" ::"l"(p), "r"(v) : "memory");
}
__device__ __forceinline__ void flag_set_x(unsigned int* p, unsigned int v, bool rlx) {
  if (rlx) asm volatile("st.relaxed.gpu.global.u32 [%0], %1;" ::"l"(p), "r"(v) : "memory"); else flag_set(p, v);
}
template <int SLEEP>
__device__ __forceinline__ void src_wait(const unsigned int* f, unsigned int target, uint32_t need, uint32_t& ready, int lane) {
  uint32_t n = 0;
#pragma unroll 1
  while ((ready & need) != need) {
    const unsigned int v = ld_acquire(f + (lane & 15));
    ready = __ballot_sync(0xffffffffu, (int)(v - target) >= 0);
    if (SLEEP) { if ((ready & need) != need) __nanosleep(SLEEP); }
    if (++n > (1u << 20)) { g_err = 3u; break; }
  }
  __syncwarp();
}
__device__ __forceinline__ unsigned int ld_relaxed(const unsigned int* p) {
  unsigned int v; asm volatile("ld.relaxed.gpu.global.u32 %0, [%1];" : "=r"(v) : "l"(p) : "memory"); return v;
}
__device__ __forceinline__ bool src_wait_tma(const unsigned int* f, unsigned int target, uint32_t need, uint32_t& ready, int lane, uint32_t eb, uint32_t par) {
  uint32_t n = 0;
  bool fr = false;
#pragma unroll 1
  while ((ready & need) != need) {
    const unsigned int v = ld_acquire(f + (lane & 15));
    fr = __all_sync(0xffffffffu, mbar_test_wait(eb, par));
    ready = __ballot_sync(0xffffffffu, (int)(v - target) >= 0);
    if (++n > (1u << 20)) { g_err = 3u; break; }
  }
  return fr;
}
__device__ __forceinline__ uint4 ld_relaxed4(const uint4* p) {
  uint4 v; asm volatile("ld.relaxed.gpu.global.v4.u32 {%0,%1,%2,%3}, [%4];" : "=r"(v.x), "=r"(v.y), "=r"(v.z), "=r"(v.w) : "l"(p) : "memory"); return v;
}
__device__ __forceinline__ void st_relaxed4(uint4* p, uint32_t a, uint32_t b, uint32_t c, uint32_t d) {
  asm volatile("st.relaxed.gpu.global.v4.u32 [%0], {%1,%2,%3,%4};" ::"l"(p), "r"(a), "r"(b), "r"(c), "r"(d) : "memory");
}
template <int SLEEP>
__device__ __forceinline__ void flag_wait_t(const unsigned int* p, unsigned int target) {
  uint32_t n = 0;
#pragma unroll 1
  while ((int)(ld_acquire(p) - target) < 0) {
    if (SLEEP) __nanosleep(SLEEP);
    if (++n > (1u << 20)) { g_err = 2u; break; }
  }
}
__device__ __forceinline__ void flag_wait(const unsigned int* p, unsigned int target) { flag_wait_t<0>(p, target); }
__device__ __forceinline__ void flag_wait_slow(const unsigned int* p, unsigned int target) { flag_wait_t<256>(p, target); }
__device__ __forceinline__ void tma_load_2d(uint32_t dst, const CUtensorMap* tm, int c0, int c1, uint32_t bar) {
  asm volatile("cp.async.bulk.tensor.2d.shared::cluster.global.mbarrier::complete_tx::bytes [%0], [%1, {%2, %3}], [%4];"
               ::"r"(dst), "l"(tm), "r"(c0), "r"(c1), "r"(bar) : "memory");
}
__device__ __forceinline__ void tma_load_2d_mc(uint32_t dst, const CUtensorMap* tm, int c0, int c1, uint32_t bar, uint16_t mask) {
  asm volatile("cp.async.bulk.tensor.2d.shared::cluster.global.mbarrier::complete_tx::bytes.multicast::cluster [%0], [%1, {%2, %3}], [%4], %5;"
               ::"r"(dst), "l"(tm), "r"(c0), "r"(c1), "r"(bar), "h"(mask) : "memory");
}
__device__ __forceinline__ void mbar_wait_u(uint32_t bar, uint32_t parity) {
  uint32_t n = 0;
#pragma unroll 1
  while (!__all_sync(0xffffffffu, mbar_try_wait(bar, parity))) {
    if (++n > (1u << 22)) { g_err = 1u; break; }
  }
}
__device__ __forceinline__ void expect_tx_e(uint32_t bar, uint32_t bytes) {
  asm volatile("{\n.reg .pred p;\nelect.sync _|p, 0xffffffff;\n@p mbarrier.arrive.expect_tx.shared::cta.b64 _, [%0], %1;\n}\n" ::"r"(bar), "r"(bytes) : "memory");
}
__device__ __forceinline__ void tma_2d_e(uint32_t dst, const CUtensorMap* tm, int c0, int c1, uint32_t bar) {
  asm volatile("{\n.reg .pred p;\nelect.sync _|p, 0xffffffff;\n"
               "@p cp.async.bulk.tensor.2d.shared::cluster.global.mbarrier::complete_tx::bytes [%0], [%1, {%2, %3}], [%4];\n}\n"
               ::"r"(dst), "l"(tm), "r"(c0), "r"(c1), "r"(bar) : "memory");
}
__device__ __forceinline__ void tma_2d_mc_e(uint32_t dst, const CUtensorMap* tm, int c0, int c1, uint32_t bar) {
  asm volatile("{\n.reg .pred p;\nelect.sync _|p, 0xffffffff;\n"
               "@p cp.async.bulk.tensor.2d.shared::cluster.global.mbarrier::complete_tx::bytes.multicast::cluster [%0], [%1, {%2, %3}], [%4], %5;\n}\n"
               ::"r"(dst), "l"(tm), "r"(c0), "r"(c1), "r"(bar), "h"((uint16_t)3) : "memory");
}
__device__ __forceinline__ void tma_pf_e(const CUtensorMap* tm, int c0, int c1) {
  asm volatile("{\n.reg .pred p;\nelect.sync _|p, 0xffffffff;\n"
               "@p cp.async.bulk.prefetch.tensor.2d.L2.global.tile [%0, {%1, %2}];\n}\n" ::"l"(tm), "r"(c0), "r"(c1) : "memory");
}
__device__ __forceinline__ void tma_2d_to_e(uint32_t dst, const CUtensorMap* tm, int c0, int c1, uint32_t bar, uint32_t mask) {
  asm volatile("{\n.reg .pred p;\nelect.sync _|p, 0xffffffff;\n"
               "@p cp.async.bulk.tensor.2d.shared::cluster.global.mbarrier::complete_tx::bytes.multicast::cluster [%0], [%1, {%2, %3}], [%4], %5;\n}\n"
               ::"r"(dst), "l"(tm), "r"(c0), "r"(c1), "r"(bar), "h"((uint16_t)mask) : "memory");
}
__device__ __forceinline__ void tma_3d_mc_e(uint32_t dst, const CUtensorMap* tm, int c1, int c2, uint32_t bar) {
  asm volatile("{\n.reg .pred p;\nelect.sync _|p, 0xffffffff;\n"
               "@p cp.async.bulk.tensor.3d.shared::cluster.global.mbarrier::complete_tx::bytes.multicast::cluster [%0], [%1, {%6, %2, %3}], [%4], %5;\n}\n"
               ::"r"(dst), "l"(tm), "r"(c1), "r"(c2), "r"(bar), "h"((uint16_t)3), "r"(0) : "memory");
}
__device__ __forceinline__ uint32_t poll_flags(const unsigned int* f, unsigned int target, int lane) {
  const unsigned int v = ld_acquire(f + (lane & 15));
  const uint32_t r = __ballot_sync(0xffffffffu, (int)(v - target) >= 0);
  __syncwarp();
  return r;
}
__device__ __forceinline__ void mbar_arrive_cluster(uint32_t local_bar, uint32_t rank) {
  asm volatile("{\n.reg .b32 ra;\nmapa.shared::cluster.u32 ra, %0, %1;\nmbarrier.arrive.shared::cluster.b64 _, [ra];\n}\n"
               ::"r"(local_bar), "r"(rank) : "memory");
}
__device__ __forceinline__ void release2(uint32_t bar) { mbar_arrive_cluster(bar, 0); mbar_arrive_cluster(bar, 1); }
__device__ __forceinline__ void tma_store_2d(const CUtensorMap* tm, uint32_t src, int c0, int c1) {
  asm volatile("cp.async.bulk.tensor.2d.global.shared::cta.bulk_group [%0, {%2, %3}], [%1];"
               ::"l"(tm), "r"(src), "r"(c0), "r"(c1) : "memory");
}
__device__ __forceinline__ void bulk_store(void* dst, uint32_t src, uint32_t bytes) {
  asm volatile("cp.async.bulk.global.shared::cta.bulk_group [%0], [%1], %2;" ::"l"(dst), "r"(src), "r"(bytes) : "memory");
}
__device__ __forceinline__ void bulk_load(uint32_t dst, const void* src, uint32_t bytes, uint32_t bar) {
  asm volatile("cp.async.bulk.shared::cluster.global.mbarrier::complete_tx::bytes [%0], [%1], %2, [%3];" ::"r"(dst), "l"(src), "r"(bytes), "r"(bar) : "memory");
}
__device__ __forceinline__ void bulk_red_add(void* dst, uint32_t src, uint32_t bytes) {
  asm volatile("cp.reduce.async.bulk.global.shared::cta.bulk_group.add.f32 [%0], [%1], %2;" ::"l"(dst), "r"(src), "r"(bytes) : "memory");
}
__device__ __forceinline__ void bulk_red_add_e(void* dst, uint32_t src, uint32_t bytes) {
  asm volatile("{\n.reg .pred p;\nelect.sync _|p, 0xffffffff;\n@p cp.reduce.async.bulk.global.shared::cta.bulk_group.add.f32 [%0], [%1], %2;\n}\n" ::"l"(dst), "r"(src), "r"(bytes) : "memory");
}
__device__ __forceinline__ void bulk_commit() { asm volatile("cp.async.bulk.commit_group;" ::: "memory"); }
__device__ __forceinline__ void bulk_wait_read0() { asm volatile("cp.async.bulk.wait_group.read 0;" ::: "memory"); }
__device__ __forceinline__ void bulk_wait0() { asm volatile("cp.async.bulk.wait_group 0;" ::: "memory"); }
__device__ __forceinline__ void fence_async_smem() { asm volatile("fence.proxy.async.shared::cta;" ::: "memory"); }
__device__ __forceinline__ void fence_async_all() { asm volatile("fence.proxy.async.global;" ::: "memory"); }
__device__ __forceinline__ void wgmma_fence() { asm volatile("wgmma.fence.sync.aligned;" ::: "memory"); }
__device__ __forceinline__ void wgmma_commit() { asm volatile("wgmma.commit_group.sync.aligned;" ::: "memory"); }
template <int N> __device__ __forceinline__ void wgmma_wait() { asm volatile("wgmma.wait_group.sync.aligned %0;" ::"n"(N) : "memory"); }
__device__ __forceinline__ void cluster_arrive() { asm volatile("barrier.cluster.arrive.release.aligned;" ::: "memory"); }
__device__ __forceinline__ void cluster_wait() { asm volatile("barrier.cluster.wait.acquire.aligned;" ::: "memory"); }
template <int ID, int N> __device__ __forceinline__ void nbar() { asm volatile("bar.sync %0, %1;" ::"n"(ID), "n"(N) : "memory"); }
__device__ __forceinline__ uint64_t make_desc(uint32_t addr, uint32_t lbo_bytes, uint32_t sbo_bytes) {
  uint64_t d = 0;
  d |= (uint64_t)((addr & 0x3FFFF) >> 4);
  d |= (uint64_t)((lbo_bytes >> 4) & 0x3FFF) << 16;
  d |= (uint64_t)((sbo_bytes >> 4) & 0x3FFF) << 32;
  d |= (uint64_t)1 << 62;
  return d;
}
__device__ __forceinline__ uint64_t desc64(uint32_t lo, uint32_t hi) { return (uint64_t)lo | ((uint64_t)hi << 32); }
__device__ __forceinline__ uint32_t pack_bf16(float lo, float hi) {
  uint32_t r; asm("cvt.rn.bf16x2.f32 %0, %1, %2;" : "=r"(r) : "f"(hi), "f"(lo)); return r;
}
__device__ __forceinline__ uint32_t mul_bf16x2(uint32_t a, uint32_t s, bool hi) {
  __nv_bfloat162 x = *reinterpret_cast<__nv_bfloat162*>(&a), y = *reinterpret_cast<__nv_bfloat162*>(&s);
  x = __hmul2(x, hi ? __high2bfloat162(y) : __low2bfloat162(y));
  return *reinterpret_cast<uint32_t*>(&x);
}
__device__ __forceinline__ float bf16r(float x) { return __bfloat162float(__float2bfloat16_rn(x)); }
__device__ __forceinline__ float bf_lo(uint32_t u) { return __uint_as_float(u << 16); }
__device__ __forceinline__ float bf_hi(uint32_t u) { return __uint_as_float(u & 0xFFFF0000u); }
__device__ __forceinline__ float ex2(float x) { float r; asm("ex2.approx.ftz.f32 %0, %1;" : "=f"(r) : "f"(x)); return r; }
__device__ __forceinline__ float rcp(float x) { float r; asm("rcp.approx.ftz.f32 %0, %1;" : "=f"(r) : "f"(x)); return r; }
__device__ __forceinline__ void mma_bf16(float (&d)[4], uint32_t a0, uint32_t a1, uint32_t a2, uint32_t a3, uint32_t b0, uint32_t b1) {
  asm("mma.sync.aligned.m16n8k16.row.col.f32.bf16.bf16.f32 {%0,%1,%2,%3}, {%4,%5,%6,%7}, {%8,%9}, {%0,%1,%2,%3};"
               : "+f"(d[0]), "+f"(d[1]), "+f"(d[2]), "+f"(d[3]) : "r"(a0), "r"(a1), "r"(a2), "r"(a3), "r"(b0), "r"(b1));
}
__device__ __forceinline__ void ldsm_x4(uint32_t& r0, uint32_t& r1, uint32_t& r2, uint32_t& r3, uint32_t addr) {
  asm volatile("ldmatrix.sync.aligned.m8n8.x4.shared.b16 {%0,%1,%2,%3}, [%4];"
               : "=r"(r0), "=r"(r1), "=r"(r2), "=r"(r3) : "r"(addr) : "memory");
}
__device__ __forceinline__ void ldsm_x4_t(uint32_t& r0, uint32_t& r1, uint32_t& r2, uint32_t& r3, uint32_t addr) {
  asm volatile("ldmatrix.sync.aligned.m8n8.x4.trans.shared.b16 {%0,%1,%2,%3}, [%4];"
               : "=r"(r0), "=r"(r1), "=r"(r2), "=r"(r3) : "r"(addr) : "memory");
}
__device__ __forceinline__ void ldsm_x2_t(uint32_t& r0, uint32_t& r1, uint32_t addr) {
  asm volatile("ldmatrix.sync.aligned.m8n8.x2.trans.shared.b16 {%0,%1}, [%2];"
               : "=r"(r0), "=r"(r1) : "r"(addr) : "memory");
}
__device__ __forceinline__ void stsm_x4(uint32_t addr, uint32_t r0, uint32_t r1, uint32_t r2, uint32_t r3) {
  asm volatile("stmatrix.sync.aligned.m8n8.x4.shared.b16 [%0], {%1,%2,%3,%4};"
               ::"r"(addr), "r"(r0), "r"(r1), "r"(r2), "r"(r3) : "memory");
}
__device__ __forceinline__ void stsm_x4_p(bool on, uint32_t addr, uint32_t r0, uint32_t r1, uint32_t r2, uint32_t r3) {
  asm volatile("{\n.reg .pred p;\nsetp.ne.b32 p, %5, 0;\n@p stmatrix.sync.aligned.m8n8.x4.shared.b16 [%0], {%1,%2,%3,%4};\n}\n"
               ::"r"(addr), "r"(r0), "r"(r1), "r"(r2), "r"(r3), "r"((int)on) : "memory");
}
__device__ __forceinline__ float2 lds_f2(uint32_t addr) {
  float2 v; asm volatile("ld.shared.v2.f32 {%0,%1}, [%2];" : "=f"(v.x), "=f"(v.y) : "r"(addr) : "memory"); return v;
}
__device__ __forceinline__ uint4 lds128(uint32_t addr) {
  uint4 v; asm volatile("ld.shared.v4.b32 {%0,%1,%2,%3}, [%4];" : "=r"(v.x), "=r"(v.y), "=r"(v.z), "=r"(v.w) : "r"(addr) : "memory"); return v;
}
__device__ __forceinline__ void sts128(uint32_t addr, uint4 v) {
  asm volatile("st.shared.v4.b32 [%0], {%1,%2,%3,%4};" ::"r"(addr), "r"(v.x), "r"(v.y), "r"(v.z), "r"(v.w) : "memory");
}
__device__ __forceinline__ float lds_f(uint32_t addr) {
  float v; asm volatile("ld.shared.f32 %0, [%1];" : "=f"(v) : "r"(addr) : "memory"); return v;
}
__device__ __forceinline__ uint32_t lds_vol(uint32_t addr) {
  uint32_t v; asm volatile("ld.volatile.shared.u32 %0, [%1];" : "=r"(v) : "r"(addr) : "memory"); return v;
}
__device__ __forceinline__ void sts16(uint32_t addr, uint32_t v) {
  asm volatile("st.shared.u16 [%0], %1;" ::"r"(addr), "h"((unsigned short)v) : "memory");
}
__device__ __forceinline__ void nbar_dyn(int id, int n) { asm volatile("bar.sync %0, %1;" ::"r"(id), "r"(n) : "memory"); }
__device__ __forceinline__ uint64_t make_desc_ns(uint32_t addr, uint32_t lbo_bytes, uint32_t sbo_bytes) {
  return (uint64_t)((addr & 0x3FFFF) >> 4) | ((uint64_t)(lbo_bytes >> 4) << 16) | ((uint64_t)(sbo_bytes >> 4) << 32);
}
__device__ __forceinline__ void sts_f(uint32_t addr, float v) { asm volatile("st.shared.f32 [%0], %1;" ::"r"(addr), "f"(v) : "memory"); }
__device__ __forceinline__ void sts64(uint32_t addr, uint32_t a, uint32_t b) {
  asm volatile("st.shared.v2.b32 [%0], {%1,%2};" ::"r"(addr), "r"(a), "r"(b) : "memory");
}
__device__ __forceinline__ void sts_f2(uint32_t addr, float a, float b) {
  asm volatile("st.shared.v2.f32 [%0], {%1,%2};" ::"r"(addr), "f"(a), "f"(b) : "memory");
}
__device__ __forceinline__ void red_add2(float* p, float a, float b) {
  asm volatile("red.global.add.v2.f32 [%0], {%1,%2};" ::"l"(p), "f"(a), "f"(b) : "memory");
}
__device__ __forceinline__ void red_add4(float* p, float a, float b, float c, float d) {
  asm volatile("red.global.add.v4.f32 [%0], {%1,%2,%3,%4};" ::"l"(p), "f"(a), "f"(b), "f"(c), "f"(d) : "memory");
}
__device__ __forceinline__ void red_add1(float* p, float a) {
  asm volatile("red.global.add.f32 [%0], %1;" ::"l"(p), "f"(a) : "memory");
}
__device__ __forceinline__ void l2_prefetch(const void* p, uint32_t bytes) {
  asm volatile("cp.async.bulk.prefetch.L2.global [%0], %1;" ::"l"(p), "r"(bytes) : "memory");
}

__device__ __forceinline__ void wgmma_n256(float (&d)[192], uint64_t da, uint64_t db, int scale_d) {
  asm volatile("{\n.reg .pred p;\nsetp.ne.b32 p, %130, 0;\n"
    "wgmma.mma_async.sync.aligned.m64n256k16.f32.bf16.bf16 {%0, %1, %2, %3, %4, %5, %6, %7, %8, %9, %10, %11, %12, %13, %14, %15, %16, %17, %18, %19, %20, %21, %22, %23, %24, %25, %26, %27, %28, %29, %30, %31, %32, %33, %34, %35, %36, %37, %38, %39, %40, %41, %42, %43, %44, %45, %46, %47, %48, %49, %50, %51, %52, %53, %54, %55, %56, %57, %58, %59, %60, %61, %62, %63, %64, %65, %66, %67, %68, %69, %70, %71, %72, %73, %74, %75, %76, %77, %78, %79, %80, %81, %82, %83, %84, %85, %86, %87, %88, %89, %90, %91, %92, %93, %94, %95, %96, %97, %98, %99, %100, %101, %102, %103, %104, %105, %106, %107, %108, %109, %110, %111, %112, %113, %114, %115, %116, %117, %118, %119, %120, %121, %122, %123, %124, %125, %126, %127}, %128, %129, p, 1, 1, 0, 1;\n}\n"
    : "+f"(d[0]), "+f"(d[1]), "+f"(d[2]), "+f"(d[3]), "+f"(d[4]), "+f"(d[5]), "+f"(d[6]), "+f"(d[7]), "+f"(d[8]), "+f"(d[9]), "+f"(d[10]), "+f"(d[11]), "+f"(d[12]), "+f"(d[13]), "+f"(d[14]), "+f"(d[15]), "+f"(d[16]), "+f"(d[17]), "+f"(d[18]), "+f"(d[19]), "+f"(d[20]), "+f"(d[21]), "+f"(d[22]), "+f"(d[23]), "+f"(d[24]), "+f"(d[25]), "+f"(d[26]), "+f"(d[27]), "+f"(d[28]), "+f"(d[29]), "+f"(d[30]), "+f"(d[31]), "+f"(d[32]), "+f"(d[33]), "+f"(d[34]), "+f"(d[35]), "+f"(d[36]), "+f"(d[37]), "+f"(d[38]), "+f"(d[39]), "+f"(d[40]), "+f"(d[41]), "+f"(d[42]), "+f"(d[43]), "+f"(d[44]), "+f"(d[45]), "+f"(d[46]), "+f"(d[47]), "+f"(d[48]), "+f"(d[49]), "+f"(d[50]), "+f"(d[51]), "+f"(d[52]), "+f"(d[53]), "+f"(d[54]), "+f"(d[55]), "+f"(d[56]), "+f"(d[57]), "+f"(d[58]), "+f"(d[59]), "+f"(d[60]), "+f"(d[61]), "+f"(d[62]), "+f"(d[63]), "+f"(d[64]), "+f"(d[65]), "+f"(d[66]), "+f"(d[67]), "+f"(d[68]), "+f"(d[69]), "+f"(d[70]), "+f"(d[71]), "+f"(d[72]), "+f"(d[73]), "+f"(d[74]), "+f"(d[75]), "+f"(d[76]), "+f"(d[77]), "+f"(d[78]), "+f"(d[79]), "+f"(d[80]), "+f"(d[81]), "+f"(d[82]), "+f"(d[83]), "+f"(d[84]), "+f"(d[85]), "+f"(d[86]), "+f"(d[87]), "+f"(d[88]), "+f"(d[89]), "+f"(d[90]), "+f"(d[91]), "+f"(d[92]), "+f"(d[93]), "+f"(d[94]), "+f"(d[95]), "+f"(d[96]), "+f"(d[97]), "+f"(d[98]), "+f"(d[99]), "+f"(d[100]), "+f"(d[101]), "+f"(d[102]), "+f"(d[103]), "+f"(d[104]), "+f"(d[105]), "+f"(d[106]), "+f"(d[107]), "+f"(d[108]), "+f"(d[109]), "+f"(d[110]), "+f"(d[111]), "+f"(d[112]), "+f"(d[113]), "+f"(d[114]), "+f"(d[115]), "+f"(d[116]), "+f"(d[117]), "+f"(d[118]), "+f"(d[119]), "+f"(d[120]), "+f"(d[121]), "+f"(d[122]), "+f"(d[123]), "+f"(d[124]), "+f"(d[125]), "+f"(d[126]), "+f"(d[127])
    : "l"(da), "l"(db), "r"(scale_d));
}
__device__ __forceinline__ void wgmma_n128(float (&d)[192], uint64_t da, uint64_t db, int scale_d) {
  asm volatile("{\n.reg .pred p;\nsetp.ne.b32 p, %66, 0;\n"
    "wgmma.mma_async.sync.aligned.m64n128k16.f32.bf16.bf16 {%0, %1, %2, %3, %4, %5, %6, %7, %8, %9, %10, %11, %12, %13, %14, %15, %16, %17, %18, %19, %20, %21, %22, %23, %24, %25, %26, %27, %28, %29, %30, %31, %32, %33, %34, %35, %36, %37, %38, %39, %40, %41, %42, %43, %44, %45, %46, %47, %48, %49, %50, %51, %52, %53, %54, %55, %56, %57, %58, %59, %60, %61, %62, %63}, %64, %65, p, 1, 1, 0, 1;\n}\n"
    : "+f"(d[128]), "+f"(d[129]), "+f"(d[130]), "+f"(d[131]), "+f"(d[132]), "+f"(d[133]), "+f"(d[134]), "+f"(d[135]), "+f"(d[136]), "+f"(d[137]), "+f"(d[138]), "+f"(d[139]), "+f"(d[140]), "+f"(d[141]), "+f"(d[142]), "+f"(d[143]), "+f"(d[144]), "+f"(d[145]), "+f"(d[146]), "+f"(d[147]), "+f"(d[148]), "+f"(d[149]), "+f"(d[150]), "+f"(d[151]), "+f"(d[152]), "+f"(d[153]), "+f"(d[154]), "+f"(d[155]), "+f"(d[156]), "+f"(d[157]), "+f"(d[158]), "+f"(d[159]), "+f"(d[160]), "+f"(d[161]), "+f"(d[162]), "+f"(d[163]), "+f"(d[164]), "+f"(d[165]), "+f"(d[166]), "+f"(d[167]), "+f"(d[168]), "+f"(d[169]), "+f"(d[170]), "+f"(d[171]), "+f"(d[172]), "+f"(d[173]), "+f"(d[174]), "+f"(d[175]), "+f"(d[176]), "+f"(d[177]), "+f"(d[178]), "+f"(d[179]), "+f"(d[180]), "+f"(d[181]), "+f"(d[182]), "+f"(d[183]), "+f"(d[184]), "+f"(d[185]), "+f"(d[186]), "+f"(d[187]), "+f"(d[188]), "+f"(d[189]), "+f"(d[190]), "+f"(d[191])
    : "l"(da), "l"(db), "r"(scale_d));
}
__device__ __forceinline__ void wgmma_n256_k(float (&d)[192], uint64_t da, uint64_t db, int scale_d) {
  asm volatile("{\n.reg .pred p;\nsetp.ne.b32 p, %130, 0;\n"
    "wgmma.mma_async.sync.aligned.m64n256k16.f32.bf16.bf16 {%0, %1, %2, %3, %4, %5, %6, %7, %8, %9, %10, %11, %12, %13, %14, %15, %16, %17, %18, %19, %20, %21, %22, %23, %24, %25, %26, %27, %28, %29, %30, %31, %32, %33, %34, %35, %36, %37, %38, %39, %40, %41, %42, %43, %44, %45, %46, %47, %48, %49, %50, %51, %52, %53, %54, %55, %56, %57, %58, %59, %60, %61, %62, %63, %64, %65, %66, %67, %68, %69, %70, %71, %72, %73, %74, %75, %76, %77, %78, %79, %80, %81, %82, %83, %84, %85, %86, %87, %88, %89, %90, %91, %92, %93, %94, %95, %96, %97, %98, %99, %100, %101, %102, %103, %104, %105, %106, %107, %108, %109, %110, %111, %112, %113, %114, %115, %116, %117, %118, %119, %120, %121, %122, %123, %124, %125, %126, %127}, %128, %129, p, 1, 1, 0, 0;\n}\n"
    : "+f"(d[0]), "+f"(d[1]), "+f"(d[2]), "+f"(d[3]), "+f"(d[4]), "+f"(d[5]), "+f"(d[6]), "+f"(d[7]), "+f"(d[8]), "+f"(d[9]), "+f"(d[10]), "+f"(d[11]), "+f"(d[12]), "+f"(d[13]), "+f"(d[14]), "+f"(d[15]), "+f"(d[16]), "+f"(d[17]), "+f"(d[18]), "+f"(d[19]), "+f"(d[20]), "+f"(d[21]), "+f"(d[22]), "+f"(d[23]), "+f"(d[24]), "+f"(d[25]), "+f"(d[26]), "+f"(d[27]), "+f"(d[28]), "+f"(d[29]), "+f"(d[30]), "+f"(d[31]), "+f"(d[32]), "+f"(d[33]), "+f"(d[34]), "+f"(d[35]), "+f"(d[36]), "+f"(d[37]), "+f"(d[38]), "+f"(d[39]), "+f"(d[40]), "+f"(d[41]), "+f"(d[42]), "+f"(d[43]), "+f"(d[44]), "+f"(d[45]), "+f"(d[46]), "+f"(d[47]), "+f"(d[48]), "+f"(d[49]), "+f"(d[50]), "+f"(d[51]), "+f"(d[52]), "+f"(d[53]), "+f"(d[54]), "+f"(d[55]), "+f"(d[56]), "+f"(d[57]), "+f"(d[58]), "+f"(d[59]), "+f"(d[60]), "+f"(d[61]), "+f"(d[62]), "+f"(d[63]), "+f"(d[64]), "+f"(d[65]), "+f"(d[66]), "+f"(d[67]), "+f"(d[68]), "+f"(d[69]), "+f"(d[70]), "+f"(d[71]), "+f"(d[72]), "+f"(d[73]), "+f"(d[74]), "+f"(d[75]), "+f"(d[76]), "+f"(d[77]), "+f"(d[78]), "+f"(d[79]), "+f"(d[80]), "+f"(d[81]), "+f"(d[82]), "+f"(d[83]), "+f"(d[84]), "+f"(d[85]), "+f"(d[86]), "+f"(d[87]), "+f"(d[88]), "+f"(d[89]), "+f"(d[90]), "+f"(d[91]), "+f"(d[92]), "+f"(d[93]), "+f"(d[94]), "+f"(d[95]), "+f"(d[96]), "+f"(d[97]), "+f"(d[98]), "+f"(d[99]), "+f"(d[100]), "+f"(d[101]), "+f"(d[102]), "+f"(d[103]), "+f"(d[104]), "+f"(d[105]), "+f"(d[106]), "+f"(d[107]), "+f"(d[108]), "+f"(d[109]), "+f"(d[110]), "+f"(d[111]), "+f"(d[112]), "+f"(d[113]), "+f"(d[114]), "+f"(d[115]), "+f"(d[116]), "+f"(d[117]), "+f"(d[118]), "+f"(d[119]), "+f"(d[120]), "+f"(d[121]), "+f"(d[122]), "+f"(d[123]), "+f"(d[124]), "+f"(d[125]), "+f"(d[126]), "+f"(d[127])
    : "l"(da), "l"(db), "r"(scale_d));
}
__device__ __forceinline__ void wgmma_n128_k(float (&d)[192], uint64_t da, uint64_t db, int scale_d) {
  asm volatile("{\n.reg .pred p;\nsetp.ne.b32 p, %66, 0;\n"
    "wgmma.mma_async.sync.aligned.m64n128k16.f32.bf16.bf16 {%0, %1, %2, %3, %4, %5, %6, %7, %8, %9, %10, %11, %12, %13, %14, %15, %16, %17, %18, %19, %20, %21, %22, %23, %24, %25, %26, %27, %28, %29, %30, %31, %32, %33, %34, %35, %36, %37, %38, %39, %40, %41, %42, %43, %44, %45, %46, %47, %48, %49, %50, %51, %52, %53, %54, %55, %56, %57, %58, %59, %60, %61, %62, %63}, %64, %65, p, 1, 1, 0, 0;\n}\n"
    : "+f"(d[128]), "+f"(d[129]), "+f"(d[130]), "+f"(d[131]), "+f"(d[132]), "+f"(d[133]), "+f"(d[134]), "+f"(d[135]), "+f"(d[136]), "+f"(d[137]), "+f"(d[138]), "+f"(d[139]), "+f"(d[140]), "+f"(d[141]), "+f"(d[142]), "+f"(d[143]), "+f"(d[144]), "+f"(d[145]), "+f"(d[146]), "+f"(d[147]), "+f"(d[148]), "+f"(d[149]), "+f"(d[150]), "+f"(d[151]), "+f"(d[152]), "+f"(d[153]), "+f"(d[154]), "+f"(d[155]), "+f"(d[156]), "+f"(d[157]), "+f"(d[158]), "+f"(d[159]), "+f"(d[160]), "+f"(d[161]), "+f"(d[162]), "+f"(d[163]), "+f"(d[164]), "+f"(d[165]), "+f"(d[166]), "+f"(d[167]), "+f"(d[168]), "+f"(d[169]), "+f"(d[170]), "+f"(d[171]), "+f"(d[172]), "+f"(d[173]), "+f"(d[174]), "+f"(d[175]), "+f"(d[176]), "+f"(d[177]), "+f"(d[178]), "+f"(d[179]), "+f"(d[180]), "+f"(d[181]), "+f"(d[182]), "+f"(d[183]), "+f"(d[184]), "+f"(d[185]), "+f"(d[186]), "+f"(d[187]), "+f"(d[188]), "+f"(d[189]), "+f"(d[190]), "+f"(d[191])
    : "l"(da), "l"(db), "r"(scale_d));
}
__device__ __forceinline__ void wgmma_n40_tt(float (&d)[20], uint64_t da, uint64_t db, int scale_d) {
  asm volatile("{\n.reg .pred p;\nsetp.ne.b32 p, %22, 0;\n"
    "wgmma.mma_async.sync.aligned.m64n40k16.f32.bf16.bf16 {%0, %1, %2, %3, %4, %5, %6, %7, %8, %9, %10, %11, %12, %13, %14, %15, %16, %17, %18, %19}, %20, %21, p, 1, 1, 1, 1;\n}\n"
    : "+f"(d[0]), "+f"(d[1]), "+f"(d[2]), "+f"(d[3]), "+f"(d[4]), "+f"(d[5]), "+f"(d[6]), "+f"(d[7]), "+f"(d[8]), "+f"(d[9]), "+f"(d[10]), "+f"(d[11]), "+f"(d[12]), "+f"(d[13]), "+f"(d[14]), "+f"(d[15]), "+f"(d[16]), "+f"(d[17]), "+f"(d[18]), "+f"(d[19])
    : "l"(da), "l"(db), "r"(scale_d));
}
__device__ __forceinline__ void wgmma_n40_rs(float (&d)[20], const uint32_t (&a)[4], uint64_t db, int scale_d) {
  asm volatile("{\n.reg .pred p;\nsetp.ne.b32 p, %25, 0;\n"
    "wgmma.mma_async.sync.aligned.m64n40k16.f32.bf16.bf16 {%0, %1, %2, %3, %4, %5, %6, %7, %8, %9, %10, %11, %12, %13, %14, %15, %16, %17, %18, %19}, {%20, %21, %22, %23}, %24, p, 1, 1, 1;\n}\n"
    : "+f"(d[0]), "+f"(d[1]), "+f"(d[2]), "+f"(d[3]), "+f"(d[4]), "+f"(d[5]), "+f"(d[6]), "+f"(d[7]), "+f"(d[8]), "+f"(d[9]), "+f"(d[10]), "+f"(d[11]), "+f"(d[12]), "+f"(d[13]), "+f"(d[14]), "+f"(d[15]), "+f"(d[16]), "+f"(d[17]), "+f"(d[18]), "+f"(d[19])
    : "r"(a[0]), "r"(a[1]), "r"(a[2]), "r"(a[3]), "l"(db), "r"(scale_d));
}
__device__ __forceinline__ void wgmma_n256_0(float (&d)[192], uint64_t da, uint64_t db) {
  asm volatile("{\n.reg .pred p;\nsetp.ne.b32 p, 0, 0;\n"
    "wgmma.mma_async.sync.aligned.m64n256k16.f32.bf16.bf16 {%0, %1, %2, %3, %4, %5, %6, %7, %8, %9, %10, %11, %12, %13, %14, %15, %16, %17, %18, %19, %20, %21, %22, %23, %24, %25, %26, %27, %28, %29, %30, %31, %32, %33, %34, %35, %36, %37, %38, %39, %40, %41, %42, %43, %44, %45, %46, %47, %48, %49, %50, %51, %52, %53, %54, %55, %56, %57, %58, %59, %60, %61, %62, %63, %64, %65, %66, %67, %68, %69, %70, %71, %72, %73, %74, %75, %76, %77, %78, %79, %80, %81, %82, %83, %84, %85, %86, %87, %88, %89, %90, %91, %92, %93, %94, %95, %96, %97, %98, %99, %100, %101, %102, %103, %104, %105, %106, %107, %108, %109, %110, %111, %112, %113, %114, %115, %116, %117, %118, %119, %120, %121, %122, %123, %124, %125, %126, %127}, %128, %129, p, 1, 1, 0, 1;\n}\n"
    : "=f"(d[0]), "=f"(d[1]), "=f"(d[2]), "=f"(d[3]), "=f"(d[4]), "=f"(d[5]), "=f"(d[6]), "=f"(d[7]), "=f"(d[8]), "=f"(d[9]), "=f"(d[10]), "=f"(d[11]), "=f"(d[12]), "=f"(d[13]), "=f"(d[14]), "=f"(d[15]), "=f"(d[16]), "=f"(d[17]), "=f"(d[18]), "=f"(d[19]), "=f"(d[20]), "=f"(d[21]), "=f"(d[22]), "=f"(d[23]), "=f"(d[24]), "=f"(d[25]), "=f"(d[26]), "=f"(d[27]), "=f"(d[28]), "=f"(d[29]), "=f"(d[30]), "=f"(d[31]), "=f"(d[32]), "=f"(d[33]), "=f"(d[34]), "=f"(d[35]), "=f"(d[36]), "=f"(d[37]), "=f"(d[38]), "=f"(d[39]), "=f"(d[40]), "=f"(d[41]), "=f"(d[42]), "=f"(d[43]), "=f"(d[44]), "=f"(d[45]), "=f"(d[46]), "=f"(d[47]), "=f"(d[48]), "=f"(d[49]), "=f"(d[50]), "=f"(d[51]), "=f"(d[52]), "=f"(d[53]), "=f"(d[54]), "=f"(d[55]), "=f"(d[56]), "=f"(d[57]), "=f"(d[58]), "=f"(d[59]), "=f"(d[60]), "=f"(d[61]), "=f"(d[62]), "=f"(d[63]), "=f"(d[64]), "=f"(d[65]), "=f"(d[66]), "=f"(d[67]), "=f"(d[68]), "=f"(d[69]), "=f"(d[70]), "=f"(d[71]), "=f"(d[72]), "=f"(d[73]), "=f"(d[74]), "=f"(d[75]), "=f"(d[76]), "=f"(d[77]), "=f"(d[78]), "=f"(d[79]), "=f"(d[80]), "=f"(d[81]), "=f"(d[82]), "=f"(d[83]), "=f"(d[84]), "=f"(d[85]), "=f"(d[86]), "=f"(d[87]), "=f"(d[88]), "=f"(d[89]), "=f"(d[90]), "=f"(d[91]), "=f"(d[92]), "=f"(d[93]), "=f"(d[94]), "=f"(d[95]), "=f"(d[96]), "=f"(d[97]), "=f"(d[98]), "=f"(d[99]), "=f"(d[100]), "=f"(d[101]), "=f"(d[102]), "=f"(d[103]), "=f"(d[104]), "=f"(d[105]), "=f"(d[106]), "=f"(d[107]), "=f"(d[108]), "=f"(d[109]), "=f"(d[110]), "=f"(d[111]), "=f"(d[112]), "=f"(d[113]), "=f"(d[114]), "=f"(d[115]), "=f"(d[116]), "=f"(d[117]), "=f"(d[118]), "=f"(d[119]), "=f"(d[120]), "=f"(d[121]), "=f"(d[122]), "=f"(d[123]), "=f"(d[124]), "=f"(d[125]), "=f"(d[126]), "=f"(d[127])
    : "l"(da), "l"(db));
}
__device__ __forceinline__ void wgmma_n128_0(float (&d)[192], uint64_t da, uint64_t db) {
  asm volatile("{\n.reg .pred p;\nsetp.ne.b32 p, 0, 0;\n"
    "wgmma.mma_async.sync.aligned.m64n128k16.f32.bf16.bf16 {%0, %1, %2, %3, %4, %5, %6, %7, %8, %9, %10, %11, %12, %13, %14, %15, %16, %17, %18, %19, %20, %21, %22, %23, %24, %25, %26, %27, %28, %29, %30, %31, %32, %33, %34, %35, %36, %37, %38, %39, %40, %41, %42, %43, %44, %45, %46, %47, %48, %49, %50, %51, %52, %53, %54, %55, %56, %57, %58, %59, %60, %61, %62, %63}, %64, %65, p, 1, 1, 0, 1;\n}\n"
    : "=f"(d[128]), "=f"(d[129]), "=f"(d[130]), "=f"(d[131]), "=f"(d[132]), "=f"(d[133]), "=f"(d[134]), "=f"(d[135]), "=f"(d[136]), "=f"(d[137]), "=f"(d[138]), "=f"(d[139]), "=f"(d[140]), "=f"(d[141]), "=f"(d[142]), "=f"(d[143]), "=f"(d[144]), "=f"(d[145]), "=f"(d[146]), "=f"(d[147]), "=f"(d[148]), "=f"(d[149]), "=f"(d[150]), "=f"(d[151]), "=f"(d[152]), "=f"(d[153]), "=f"(d[154]), "=f"(d[155]), "=f"(d[156]), "=f"(d[157]), "=f"(d[158]), "=f"(d[159]), "=f"(d[160]), "=f"(d[161]), "=f"(d[162]), "=f"(d[163]), "=f"(d[164]), "=f"(d[165]), "=f"(d[166]), "=f"(d[167]), "=f"(d[168]), "=f"(d[169]), "=f"(d[170]), "=f"(d[171]), "=f"(d[172]), "=f"(d[173]), "=f"(d[174]), "=f"(d[175]), "=f"(d[176]), "=f"(d[177]), "=f"(d[178]), "=f"(d[179]), "=f"(d[180]), "=f"(d[181]), "=f"(d[182]), "=f"(d[183]), "=f"(d[184]), "=f"(d[185]), "=f"(d[186]), "=f"(d[187]), "=f"(d[188]), "=f"(d[189]), "=f"(d[190]), "=f"(d[191])
    : "l"(da), "l"(db));
}
__device__ __forceinline__ void wgmma_n128_rs(float (&d)[192], const uint32_t (&a)[4], uint64_t db, int scale_d) {
  asm volatile("{\n.reg .pred p;\nsetp.ne.b32 p, %69, 0;\n"
    "wgmma.mma_async.sync.aligned.m64n128k16.f32.bf16.bf16 {%0, %1, %2, %3, %4, %5, %6, %7, %8, %9, %10, %11, %12, %13, %14, %15, %16, %17, %18, %19, %20, %21, %22, %23, %24, %25, %26, %27, %28, %29, %30, %31, %32, %33, %34, %35, %36, %37, %38, %39, %40, %41, %42, %43, %44, %45, %46, %47, %48, %49, %50, %51, %52, %53, %54, %55, %56, %57, %58, %59, %60, %61, %62, %63}, {%64, %65, %66, %67}, %68, p, 1, 1, 1;\n}\n"
    : "+f"(d[128]), "+f"(d[129]), "+f"(d[130]), "+f"(d[131]), "+f"(d[132]), "+f"(d[133]), "+f"(d[134]), "+f"(d[135]), "+f"(d[136]), "+f"(d[137]), "+f"(d[138]), "+f"(d[139]), "+f"(d[140]), "+f"(d[141]), "+f"(d[142]), "+f"(d[143]), "+f"(d[144]), "+f"(d[145]), "+f"(d[146]), "+f"(d[147]), "+f"(d[148]), "+f"(d[149]), "+f"(d[150]), "+f"(d[151]), "+f"(d[152]), "+f"(d[153]), "+f"(d[154]), "+f"(d[155]), "+f"(d[156]), "+f"(d[157]), "+f"(d[158]), "+f"(d[159]), "+f"(d[160]), "+f"(d[161]), "+f"(d[162]), "+f"(d[163]), "+f"(d[164]), "+f"(d[165]), "+f"(d[166]), "+f"(d[167]), "+f"(d[168]), "+f"(d[169]), "+f"(d[170]), "+f"(d[171]), "+f"(d[172]), "+f"(d[173]), "+f"(d[174]), "+f"(d[175]), "+f"(d[176]), "+f"(d[177]), "+f"(d[178]), "+f"(d[179]), "+f"(d[180]), "+f"(d[181]), "+f"(d[182]), "+f"(d[183]), "+f"(d[184]), "+f"(d[185]), "+f"(d[186]), "+f"(d[187]), "+f"(d[188]), "+f"(d[189]), "+f"(d[190]), "+f"(d[191])
    : "r"(a[0]), "r"(a[1]), "r"(a[2]), "r"(a[3]), "l"(db), "r"(scale_d));
}

constexpr int SLOT = 16384;
constexpr int KVT = 10240;
constexpr uint32_t QA = 0x0BAu, QK = 0x462u, QQ = 0x981u;
constexpr int SM_SD = 12 * SLOT;
constexpr int SM_BAR = SM_SD + 8192;
constexpr int SM_RS = SM_BAR + 512;
constexpr int SM_AP = SM_RS + 768;
constexpr int SM_BP = SM_AP + 2048;
constexpr int SM_WPHI = SM_BP + 12288;
constexpr int SM_EPOCH = SM_WPHI + 10240;
constexpr int SM_TOTAL = SM_EPOCH + 16 + 1024;
constexpr int B_FULLS = 0, B_XOLD = 24, B_STAT = 32, B_EMPTYS = 40, B_FULLT = 256  , B_CONS = 384  , B_E3 = 472, B_E0 = 480, B_E1 = 488, B_E2 = 496, B_EPI = 504, B_CS = 160,
              B_KVDONE = 168  , B_ODONE = 176, B_XDONE = 184, B_OH1 = B_CONS, B_CS2 = 208, B_XH0 = 232, B_R0 = 240, B_CB = 144  , B_XOLD2 = 216, B_FLG = 64  ;
constexpr uint64_t BAR_CNT = 0x1c07fc0eac00a800ull;
constexpr uint64_t WO_A0 = 0xa461b57648357643ull, WO_B0 = 0x59083a9021ba9021ull, WO_A1 = 0xa0b76901276a5babull, WO_B1 = 0x95428a5b34890132ull;
constexpr uint64_t WO_DA0 = 0xa9865432ff00dd00ull, WO_DB0 = 0xa986543211bbccccull, WO_DA1 = 0xa98654321ffff000ull, WO_DB1 = 0xa98754321bbcccddull;
#define WOORD 0xFDB9753ECA864210ull
constexpr int NX = 4;
constexpr int XS = 10;

#define PL 2
#define PROFX(i) PROFT(tid_ == 128 && layer == PL, 200 + (i))
#define PSL 20
#define EP 5
#define NCOM 3
#define CSLP 128
#define PFS 8
#define KVTH 0x41700000u
#define RL 3
#define ORD 1
#define XB2 2
#define PMOD 3
#define DB1 2
#define XPF 2
#define XPM 0
#define AW 1
#define PG 0
#define UNS 7
#define TLINE 0
#define RORD 0
#define WSK 1
#define NLAYERS 4
constexpr float L2E = 1.4426950408889634f;
#define PHI_MAX 2147483648.f

#define D128(lo) desc64(lo, 0x40000040u)
struct Ctx { uint32_t sb; int g, rb, cu; bf16* out; };

__device__ __forceinline__ void colsum(const CUtensorMap* tm, float* cs, int rb, int g, int w0, int dw, int lane, uint32_t stg, uint32_t cb, uint32_t par) {
  const uint32_t src = stg + (lane >> 3) * 2048;
#pragma unroll 1
  for (int wi = w0 - dw; wi < 6; wi += dw) {
    float s[8] = {0.f, 0.f, 0.f, 0.f, 0.f, 0.f, 0.f, 0.f};
    if (wi >= 0) {
      mbar_wait_u(cb, par);
      par ^= 1;
#pragma unroll 4
      for (int r = 0; r < 16; ++r) {
        const uint4 v = lds128(src + r * 128 + (((lane ^ r) & 7) << 4));
        s[0] += bf_lo(v.x); s[1] += bf_hi(v.x); s[2] += bf_lo(v.y); s[3] += bf_hi(v.y);
        s[4] += bf_lo(v.z); s[5] += bf_hi(v.z); s[6] += bf_lo(v.w); s[7] += bf_hi(v.w);
      }
#pragma unroll
      for (int i = 0; i < 8; ++i) s[i] += __shfl_xor_sync(0xffffffffu, s[i], 8);
    }
    const int wn = wi + dw;
    if (wn < 6) {
      expect_tx_e(cb, 8192);
      tma_2d_e(stg, tm, (wn >= 4 ? 0 : 1024 + (wn >> 1) * 1024) + g * 128 + (wn & 1) * 64, rb * 64, cb);
    }
    if (wi >= 0) {
#pragma unroll
      for (int i = 0; i < 8; ++i) s[i] += __shfl_xor_sync(0xffffffffu, s[i], 16);
      if (lane < 8) {
        red_add4(cs + g * 384 + (wi * 8 + lane) * 8, s[0], s[1], s[2], s[3]);
        red_add4(cs + g * 384 + (wi * 8 + lane) * 8 + 4, s[4], s[5], s[6], s[7]);
      }
      __syncwarp();
    }
  }
}
#define PHASE_CTX() \
  uint32_t sb = c.sb; asm volatile("" : "+r"(sb)); \
  int tid_ = threadIdx.x; asm volatile("" : "+r"(tid_)); \
  const uint32_t bar = sb + SM_BAR; \
  const int lane = tid_ & 31, cw = (tid_ >> 5) - 4, wg = cw >> 2, wq = cw & 3, gq = lane >> 2, t = lane & 3, wrow0 = cw * 16; \
  const int lrow = (lane & 7) + ((lane >> 3) & 1) * 8, lchk = lane >> 4; \
  const bool elected = (tid_ & 127) == 0; \
  const uint32_t rowo = (wrow0 + lrow) * 128, X = (lchk ^ (lane & 7)) << 4; \
  (void)bar; (void)wq; (void)gq; (void)lrow; (void)lchk; (void)elected; (void)wrow0; (void)wg; (void)rowo; (void)X; (void)t;

__device__ __forceinline__ void slab_out_half(uint32_t slot, bf16* dst, int wrow0, int lane, bool FENCE = false) {
  const int r0 = lane >> 3, ch = lane & 7;
  const uint32_t src = slot + (wrow0 + r0) * 128;
  uint4 v[4];
#pragma unroll
  for (int i = 0; i < 4; ++i) v[i] = lds128(src + i * 512 + (((ch ^ (4 * i + r0)) & 7) << 4));
  if (FENCE) fence_async_smem();
  dst += (size_t)(wrow0 + r0) * D_ + ch * 8;
#pragma unroll
  for (int i = 0; i < 4; ++i)
    asm volatile("st.global.v4.u32 [%0], {%1,%2,%3,%4};" ::"l"(dst + (size_t)i * 4 * D_), "r"(v[i].x), "r"(v[i].y), "r"(v[i].z), "r"(v[i].w) : "memory");
}

struct Tag { uint32_t me, mo, tg; };
__device__ __forceinline__ Tag make_tag(int gq, int t, uint32_t tg) {
  const uint32_t on = t == (gq & 3), par = ((gq >> 2) ^ gq) & 1;
  return Tag{on & ~par, on & par, tg};
}
__device__ __forceinline__ void stsm_tag(uint32_t addr, uint32_t r0, uint32_t r1, uint32_t r2, uint32_t r3, const Tag& k, int jp) {
  stsm_x4(addr, (r0 & ~k.me) | (k.tg & k.me), (r1 & ~k.me) | (k.tg & k.me), (r2 & ~k.mo) | (k.tg & k.mo), (r3 & ~k.mo) | (k.tg & k.mo));
}
#define TILE_BAD() (((lds_vol(va) ^ tg) | (lds_vol(va + 1024) ^ tg)) & 1)
#define TILE_VA() (slot + (wrow0 + (lane >> 2)) * 128 + (lane & 3) * 32 + (lane >> 2) * 4)
__device__ __forceinline__ void tile_check(uint32_t slot, const bf16* src, int wrow0, int lane, uint32_t tg) {
  const uint32_t va = TILE_VA();
  if (__builtin_expect(__any_sync(0xffffffffu, TILE_BAD()), 0)) {
    const int r0 = lane >> 3, ch = lane & 7;
    uint32_t n = 0;
#pragma unroll 1
    do {
      uint4 v[4];
#pragma unroll
      for (int i = 0; i < 4; ++i) v[i] = ld_relaxed4(reinterpret_cast<const uint4*>(src + (size_t)(wrow0 + r0 + 4 * i) * D_ + ch * 8));
#pragma unroll
      for (int i = 0; i < 4; ++i) sts128(slot + (wrow0 + r0 + 4 * i) * 128 + (((ch ^ (4 * i + r0)) & 7) << 4), v[i]);
      __syncwarp();
      if (++n > (1u << 16)) { g_err = 8u; break; }
    } while (__any_sync(0xffffffffu, TILE_BAD()));
    fence_async_smem();
    __syncwarp();
  }
}

template <int O>
__device__ __forceinline__ void phi_proj(float (&p)[2][4][4], const uint32_t (&kq)[64], uint32_t wa) {
#pragma unroll
  for (int h = 0; h < 2; ++h)
#pragma unroll
    for (int i = 0; i < 4; ++i) { p[h][i][0] = p[h][i][1] = p[h][i][2] = p[h][i][3] = 0.f; }
#pragma unroll
  for (int ks = 0; ks < 2; ++ks)
#pragma unroll
    for (int np = 0; np < 2; ++np)
#pragma unroll
      for (int h = 0; h < 2; ++h) {
        uint32_t b0, b1, b2, b3;
        ldsm_x4_t(b0, b1, b2, b3, wa + h * 2560 + ks * 1280 + np * 32);
        mma_bf16(p[h][2 * np], kq[O + 8 * h + 4 * ks], kq[O + 8 * h + 4 * ks + 1], kq[O + 8 * h + 4 * ks + 2], kq[O + 8 * h + 4 * ks + 3], b0, b1);
        mma_bf16(p[h][2 * np + 1], kq[O + 8 * h + 4 * ks], kq[O + 8 * h + 4 * ks + 1], kq[O + 8 * h + 4 * ks + 2], kq[O + 8 * h + 4 * ks + 3], b2, b3);
      }
}
__device__ __forceinline__ void phi_exp(uint32_t (&raw)[4][4], const float (&p)[4][4], float sc0, float sc1) {
#pragma unroll
  for (int i = 0; i < 4; ++i) {
    const float e0 = ex2(p[i][0] * sc0), e1 = ex2(p[i][1] * sc0), e2 = ex2(p[i][2] * sc1), e3 = ex2(p[i][3] * sc1);
    const float m0 = e0 * e1, m1 = e2 * e3, rr = rcp(m0 * m1), r0 = rr * m1, r1 = rr * m0;
    raw[i >> 1][(i & 1) * 2] = pack_bf16(e0, e1);
    raw[i >> 1][(i & 1) * 2 + 1] = pack_bf16(e2, e3);
    raw[2 + (i >> 1)][(i & 1) * 2] = pack_bf16(e1 * r0, e0 * r0);
    raw[2 + (i >> 1)][(i & 1) * 2 + 1] = pack_bf16(e3 * r1, e2 * r1);
  }
}
#define FENCE_P(h) _Pragma("unroll") for (int i_ = 0; i_ < 16; ++i_) asm volatile("" : "+f"(p[h][i_ >> 2][i_ & 3]) :: "memory")
#define FENCE_RAW(h) _Pragma("unroll") for (int i_ = 0; i_ < 16; ++i_) asm volatile("" : "+r"(raw[h][i_ >> 2][i_ & 3]) :: "memory")
template <int O>
__device__ __forceinline__ void phi_norm(uint32_t (&ph)[2][4][4], const uint32_t (&raw)[2][4][4], const uint32_t (&kq)[64], uint32_t wa,
                                         float sc0, float sc1, float mul0, float mul1) {
  bool bad = false;
#pragma unroll
  for (int h = 0; h < 2; ++h)
#pragma unroll
    for (int sg = 0; sg < 2; ++sg) {
      float ss[4] = {0.f, 0.f, 0.f, 0.f};
#pragma unroll
      for (int ks = 0; ks < 2; ++ks)
        mma_bf16(ss, raw[h][2 * sg + ks][0], raw[h][2 * sg + ks][1], raw[h][2 * sg + ks][2], raw[h][2 * sg + ks][3], 0x3F803F80u, 0x3F803F80u);
      bad = bad || !(ss[0] < PHI_MAX) || !(ss[2] < PHI_MAX);
      const uint32_t iv = pack_bf16(rcp(ss[0]) * mul0, rcp(ss[2]) * mul1);
#pragma unroll
      for (int ks = 0; ks < 2; ++ks)
#pragma unroll
        for (int j = 0; j < 4; ++j) ph[h][2 * sg + ks][j] = mul_bf16x2(raw[h][2 * sg + ks][j], iv, j & 1);
    }
  if (__builtin_expect(__any_sync(0xffffffffu, bad), 0)) {
#pragma unroll 1
    for (int it = 0; it < 4; ++it) {
      float q[4][4];
#pragma unroll
      for (int i = 0; i < 4; ++i) { q[i][0] = q[i][1] = q[i][2] = q[i][3] = 0.f; }
#pragma unroll
      for (int ks = 0; ks < 2; ++ks) {
        uint32_t a[4];
#pragma unroll
        for (int j = 0; j < 4; ++j) a[j] = (it & 2) ? kq[O + 8 + 4 * ks + j] : kq[O + 4 * ks + j];
#pragma unroll
        for (int np = 0; np < 2; ++np) {
          uint32_t b0, b1, b2, b3;
          ldsm_x4_t(b0, b1, b2, b3, wa + (it >> 1) * 2560 + ks * 1280 + np * 32);
          mma_bf16(q[2 * np], a[0], a[1], a[2], a[3], b0, b1);
          mma_bf16(q[2 * np + 1], a[0], a[1], a[2], a[3], b2, b3);
        }
      }
      float iv[2];
#pragma unroll
      for (int r = 0; r < 2; ++r) {
        const float sc = (it & 1) ? -(r ? sc1 : sc0) : (r ? sc1 : sc0);
        float mx = -INFINITY, sm = 0.f;
#pragma unroll
        for (int i = 0; i < 8; ++i) { float& v = q[i >> 1][2 * r + (i & 1)]; v *= sc; mx = fmaxf(mx, v); }
        mx = fmaxf(mx, __shfl_xor_sync(0xffffffffu, mx, 1));
        mx = fmaxf(mx, __shfl_xor_sync(0xffffffffu, mx, 2));
#pragma unroll
        for (int i = 0; i < 8; ++i) { float& v = q[i >> 1][2 * r + (i & 1)]; v = ex2(v - mx); sm += v; }
        sm += __shfl_xor_sync(0xffffffffu, sm, 1);
        sm += __shfl_xor_sync(0xffffffffu, sm, 2);
        iv[r] = rcp(sm) * (r ? mul1 : mul0);
      }
#pragma unroll
      for (int i = 0; i < 24; ++i) ph[i >> 4][(i >> 2) & 3][i & 3] = ph[(i + 8) >> 4][((i + 8) >> 2) & 3][i & 3];
#pragma unroll
      for (int i = 0; i < 4; ++i) {
        ph[1][2 + (i >> 1)][(i & 1) * 2] = pack_bf16(q[i][0] * iv[0], q[i][1] * iv[0]);
        ph[1][2 + (i >> 1)][(i & 1) * 2 + 1] = pack_bf16(q[i][2] * iv[1], q[i][3] * iv[1]);
      }
    }
  }
}

__device__ __forceinline__ void stats_out(float s0, float s1, float q0, float q1, float2* dst, int t) {
  const bool od = t & 1;
  float sa = od ? s1 : s0, qa = od ? q1 : q0;
  sa += __shfl_xor_sync(0xffffffffu, od ? s0 : s1, 1);
  qa += __shfl_xor_sync(0xffffffffu, od ? q0 : q1, 1);
  sa += __shfl_xor_sync(0xffffffffu, sa, 2);
  qa += __shfl_xor_sync(0xffffffffu, qa, 2);
  if (t < 2) red_add2(&dst[t * 8].x, sa, qa);
}

__device__ __forceinline__ void consumer(const Ctx& c) {
  const int g = c.g, m0 = c.rb * 128;
  float acc[192];
#define X_HALF(hf, TG) \
      _Pragma("unroll") for (int jp = 4 * (hf); jp < 4 * (hf) + 4; ++jp) \
        stsm_tag(sb + (XS + (hf)) * SLOT + rowo + (X ^ ((jp & 3) << 5)), \
                 pack_bf16(acc[128 + 8 * jp], acc[129 + 8 * jp]), pack_bf16(acc[130 + 8 * jp], acc[131 + 8 * jp]), \
                 pack_bf16(acc[132 + 8 * jp], acc[133 + 8 * jp]), pack_bf16(acc[134 + 8 * jp], acc[135 + 8 * jp]), TG, jp & 3);
#pragma unroll
  for (int i = 128; i < 192; ++i) acc[i] = 0.f;
#pragma unroll 1
  for (int layer = 0;; ++layer) {
    {
      PHASE_CTX();
      const uint32_t wu = c.cu >> 2;
      const uint32_t dA0 = (((sb + wu * 8192) & 0x3FFFF) >> 4) | (1u << 16), dB0 = ((sb & 0x3FFFF) >> 4) | (512u << 16);
      {
        PROFX(0);
        mbar_wait(bar + B_FULLS, 0);
        PROFX(1);
        wgmma_fence();
        wgmma_n256_0(acc, D128(dA0 + XS * 1024), D128(dB0 + 2048));
#pragma unroll
        for (int k = 1; k < 4; ++k) wgmma_n256(acc, D128(dA0 + XS * 1024 + k * 2), D128(dB0 + 2048 + k * 128), 1);
        wgmma_commit();
        wgmma_wait<1>();
        float s0 = 0.f, s1 = 0.f, q0 = 0.f, q1 = 0.f;
        if (layer) {
          X_HALF(1, (Tag{0u, 0u, 0u}));
#pragma unroll
          for (int i = 128; i < 192; i += 4) {
            s0 += acc[i] + acc[i + 1]; s1 += acc[i + 2] + acc[i + 3];
            q0 = fmaf(acc[i], acc[i], fmaf(acc[i + 1], acc[i + 1], q0)); q1 = fmaf(acc[i + 2], acc[i + 2], fmaf(acc[i + 3], acc[i + 3], q1));
          }
        }
        asm volatile("" : "+f"(s0), "+f"(s1), "+f"(q0), "+f"(q1) :: "memory");
        wgmma_fence();
        wgmma_n128_0(acc, D128(dA0 + XS * 1024), D128(dB0 + 1024));
#pragma unroll
        for (int k = 1; k < 4; ++k) wgmma_n128(acc, D128(dA0 + XS * 1024 + k * 2), D128(dB0 + 1024 + k * 128), 1);
        wgmma_commit();
        if (layer) {
          PHASE_CTX();
          fence_async_smem();
          nbar_dyn(3 + wu, 128);
          stats_out(s0, s1, q0, q1, g_stats + layer * S_ + m0 + wrow0 + gq, t);
          PROFT(tid_ == 128, layer * 16 + 8);
        }
      }
      uint32_t s = 1, u = 0, sp = 0;
      const int ix = layer ? 99 : 2 * min(g, NCOM) + 1;
#pragma unroll 1
      for (int i = 1; i < 14; ++i) {
        mbar_wait(bar + B_FULLS + s * 8, (u + (s ? layer : 0)) & 1);
        if ((UNS & 1) && layer && (unsigned)(i - 2) < 7u) {
          PHASE_CTX();
          tile_check(sb + ((QA >> (4 * s)) & 15) * SLOT, g_x + (size_t)m0 * D_ + ((2 * g + 2 * i - 2) & 15) * 64, wrow0, lane, lds_vol(sb + SM_EPOCH) + layer);
        }
        const uint32_t da = dA0 + ((QA >> (4 * s)) & 15) * 1024, dk = dB0 + ((QK >> (4 * s)) & 15) * 1024,
                       dq = dB0 + ((QQ >> (4 * s)) & 15) * 1024;
        wgmma_fence();
#pragma unroll
        for (int k = 0; k < 4; ++k) {
          wgmma_n256(acc, D128(da + k * 2), D128(dk + k * 128), 1);
          wgmma_n128(acc, D128(da + k * 2), D128(dq + k * 128), 1);
        }
        wgmma_commit();
        if ((unsigned)(i - ix) < 2u) {
          PHASE_CTX();
          {
            float s0 = 0.f, s1 = 0.f, q0 = 0.f, q1 = 0.f;
            const uint32_t xa = sb + ((QA >> (4 * sp)) & 15) * SLOT + rowo;
#pragma unroll
            for (int jp = 0; jp < 4; ++jp) {
              uint32_t x0, x1, x2, x3;
              ldsm_x4(x0, x1, x2, x3, xa + (X ^ (jp << 5)));
              s0 += (bf_lo(x0) + bf_hi(x0)) + (bf_lo(x2) + bf_hi(x2));
              s1 += (bf_lo(x1) + bf_hi(x1)) + (bf_lo(x3) + bf_hi(x3));
              q0 = fmaf(bf_lo(x0), bf_lo(x0), fmaf(bf_hi(x0), bf_hi(x0), fmaf(bf_lo(x2), bf_lo(x2), fmaf(bf_hi(x2), bf_hi(x2), q0))));
              q1 = fmaf(bf_lo(x1), bf_lo(x1), fmaf(bf_hi(x1), bf_hi(x1), fmaf(bf_lo(x3), bf_lo(x3), fmaf(bf_hi(x3), bf_hi(x3), q1))));
            }
            stats_out(s0, s1, q0, q1, g_stats + m0 + wrow0 + gq, t);
          }
          __syncwarp();
          if (lane == 0 && i != ix) mbar_arrive(bar + B_XDONE);
          nbar_dyn(3 + wu, 128);
        }
        wgmma_wait<1>();
        if (elected) release2(bar + B_EMPTYS + sp * 8);
        if (i == 1 && layer) {
          PHASE_CTX();
          slab_out_half(sb + (XS + 1) * SLOT, g_x + (size_t)m0 * D_ + g * 128 + 64, wrow0, lane);
          __syncwarp();
          if (lane == 0) mbar_arrive(bar + B_XDONE);
          nbar_dyn(3 + wu, 128);
        }
        sp = s;
        if (++s == 3) { s = 0; ++u; }
      }
      {
        const uint64_t dap = make_desc_ns(sb + SM_AP + wu * 1024, 0, 128), dbp = make_desc_ns(sb + SM_BP + (layer & 1) * 6144, 0, 128);
        if (wu == 0) {
          wgmma_wait<0>();
          if (elected) mbar_arrive(bar + B_R0);
          nbar<6, 256>();
        }
        if (layer < 2) mbar_wait(bar + (layer ? B_CS2 : B_CS), 0);
        mbar_wait(bar + B_STAT, layer & 1);
        mbar_wait(bar + B_FULLS + 16, layer & 1);
        wgmma_fence();
        wgmma_n256_k(acc, dap, dbp, 1);
#pragma unroll
        for (int k = 0; k < 4; ++k) wgmma_n256(acc, D128(dA0 + (QA >> 8) * 1024 + k * 2), D128(dB0 + (QK >> 8) * 1024 + k * 128), 1);
        mbar_wait(bar + B_FULLS, 1);
        PROFT(tid_ == 128, layer * 16 + 9);
        wgmma_fence();
#pragma unroll
        for (int k = 0; k < 4; ++k) wgmma_n256(acc, D128(dA0 + (QA & 15) * 1024 + k * 2), D128(dB0 + (QK & 15) * 1024 + k * 128), 1);
        wgmma_commit();
        if (wu) nbar<6, 256>();
#define Q_TAIL() \
        wgmma_n128_k(acc, dap, dbp + 256, 1); \
        _Pragma("unroll") for (int k = 0; k < 4; ++k) wgmma_n128(acc, D128(dA0 + (QA >> 8) * 1024 + k * 2), D128(dB0 + (QQ >> 8) * 1024 + k * 128), 1); \
        _Pragma("unroll") for (int k = 0; k < 4; ++k) wgmma_n128(acc, D128(dA0 + (QA & 15) * 1024 + k * 2), D128(dB0 + (QQ & 15) * 1024 + k * 128), 1);
        Q_TAIL();
        wgmma_commit();
        wgmma_wait<1>();
#pragma unroll
        for (int i = 0; i < 128; ++i) asm volatile("" : "+f"(acc[i]) :: "memory");
      }
    }
    uint32_t xo[32];
    uint32_t oq[8][4];
    {
      PHASE_CTX();
      PROFT(tid_ == 128, layer * 16 + 1);
      const bool isB = layer & 1;
      const int cu = c.cu;
      if (cu >= 4) asm volatile("bar.arrive 7, 256;" ::: "memory");
      if (elected && cu == 4) mbar_arrive(bar + B_R0);
      uint32_t kq[64];
      const uint32_t rowq = rowo & 8191;
      const float rs0 = lds_f(sb + SM_RS + (16 + wrow0 + gq) * 4), rs1 = lds_f(sb + SM_RS + (24 + wrow0 + gq) * 4);
#define Q_DONE() \
      wgmma_wait<0>(); \
      if (lane == 0) release2(bar + B_E0); \
      _Pragma("unroll") for (int i = 128; i < 192; ++i) asm volatile("" : "+f"(acc[i]) :: "memory"); \
      _Pragma("unroll") for (int i = 0; i < 32; ++i) kq[32 + i] = pack_bf16(acc[128 + 2 * i], acc[129 + 2 * i]);
      if (isB) {
        if (cu == 0) asm volatile("bar.arrive 10, 64;" ::: "memory");
        if (elected) release2(bar + B_E1);
        const int e = gq & 1;
        const bool sel = t > (gq >> 1);
        const uint32_t rja = sb + SM_RS + (wrow0 + 2 * t + e) * 4;
        const float rjA0 = lds_f(rja + 32), rjA1 = lds_f(rja + 64), rjB0 = lds_f(rja + (sel ? 0 : 64)), rjB1 = lds_f(rja + (sel ? 32 : 96));
        uint32_t vv[32];
#pragma unroll
        for (int i = 0; i < 16; ++i) { kq[i] = pack_bf16(acc[2 * i], acc[2 * i + 1]); vv[i] = pack_bf16(acc[64 + 2 * i], acc[65 + 2 * i]); }
        const uint32_t rB = sb + 4 * SLOT + wg * 4 * KVT + rowq;
        auto dump = [&](int hp) {
          const uint32_t kb = rB + 2048 + (hp ^ wg) * 2 * KVT;
#pragma unroll
          for (int jp = 0; jp < 4; ++jp) {
            stsm_x4(kb + (X ^ (jp << 5)), kq[16 * hp + 4 * jp], kq[16 * hp + 4 * jp + 1], kq[16 * hp + 4 * jp + 2], kq[16 * hp + 4 * jp + 3]);
            stsm_x4(kb + KVT + (X ^ (jp << 5)), vv[16 * hp + 4 * jp], vv[16 * hp + 4 * jp + 1], vv[16 * hp + 4 * jp + 2], vv[16 * hp + 4 * jp + 3]);
          }
          if (cu == 3) {
            const uint32_t kd = rB + 2048 + 32768 + (1 - hp) * 2 * KVT;
#pragma unroll
            for (int jp = 0; jp < 4; ++jp) {
              stsm_x4(kd + (X ^ (jp << 5)), kq[16 * hp + 4 * jp], kq[16 * hp + 4 * jp + 1], kq[16 * hp + 4 * jp + 2], kq[16 * hp + 4 * jp + 3]);
              stsm_x4(kd + KVT + (X ^ (jp << 5)), vv[16 * hp + 4 * jp], vv[16 * hp + 4 * jp + 1], vv[16 * hp + 4 * jp + 2], vv[16 * hp + 4 * jp + 3]);
            }
            if (hp) asm volatile("bar.arrive 15, 64;" ::: "memory"); else asm volatile("bar.arrive 9, 64;" ::: "memory");
          }
          asm volatile("bar.arrive %0, 224;" :: "r"(hp ? 13 + (cu >> 2) : 8 + (cu & 4)) : "memory");
        };
        uint4* const hbuf = g_halo + ((c.rb * 8 + g) * 2 + (layer >> 1)) * 512 + lane;
        if (cu < 4) {
          nbar<7, 256>();
          dump(0);
        }
#pragma unroll
        for (int i = 16; i < 32; ++i) { kq[i] = pack_bf16(acc[2 * i], acc[2 * i + 1]); vv[i] = pack_bf16(acc[64 + 2 * i], acc[65 + 2 * i]); }
        if (cu >= 4) {
          if (cu == 7) {
#pragma unroll
            for (int jp = 0; jp < 8; ++jp) {
              st_relaxed4(hbuf + jp * 32, ~kq[4 * jp], ~kq[4 * jp + 1], ~kq[4 * jp + 2], ~kq[4 * jp + 3]);
              st_relaxed4(hbuf + 256 + jp * 32, ~vv[4 * jp], ~vv[4 * jp + 1], ~vv[4 * jp + 2], ~vv[4 * jp + 3]);
            }
          }
          dump(0);
          dump(1);
        }
        PROFT(tid_ == 128, layer * 16 + 2);
        constexpr float SC = 0.17677669529663687f * L2E;
        const float fA0 = rjA0 * rs0 * SC, fB0 = rjB0 * rs0 * SC, fA1 = rjA1 * rs1 * SC, fB1 = rjB1 * rs1 * SC;
        const float bA0 = (m0 + wrow0) ? 0.f : -1e30f, bB = sel ? bA0 : 0.f;
        const uint32_t pA_ = e ? 0x1044u : 0x4410u, pB_ = e ? 0x3244u : 0x4432u, pLo = sel ? pB_ : 0x4444u, pHi = sel ? 0x4444u : pB_;
        const uint32_t KX = ((lane >> 3) ^ (lane & 7)) << 4;
        Q_DONE();
        if (cu == 0) {
          nbar<11, 64>();
        } else if (cu == 4) {
          uint4 hv[16];
          if (c.rb > 0) {
            uint32_t n = 0;
#pragma unroll 1
            while (true) {
              uint32_t mn = 0xFFFFFFFFu;
#pragma unroll
              for (int i = 0; i < 16; ++i) hv[i] = ld_relaxed4(hbuf - 16 * 512 + i * 32);
#pragma unroll
              for (int i = 0; i < 16; ++i) mn = __vimin3_u32(__vimin3_u32(mn, hv[i].x, hv[i].y), hv[i].z, hv[i].w);
              if (__all_sync(0xffffffffu, mn != 0u)) break;
              if (++n > (1u << 20)) { g_err = 4u; break; }
            }
          } else {
#pragma unroll
            for (int i = 0; i < 16; ++i) hv[i] = make_uint4(~0u, ~0u, ~0u, ~0u);
          }
          nbar<10, 64>();
#pragma unroll
          for (int i = 0; i < 16; ++i)
            stsm_x4(rB - 4 * KVT + (((i >> 2) & 1) * 2 + (i >> 3)) * KVT + (X ^ ((i & 3) << 5)), ~hv[i].x, ~hv[i].y, ~hv[i].z, ~hv[i].w);
          asm volatile("bar.arrive 11, 64;" ::: "memory");
          nbar<9, 64>();
        } else {
          nbar_dyn(8 + (cu & 4), 224);
        }
        PROFT(tid_ == 128, layer * 16 + 5);
        PROFT(lane == 0 && layer == PL, 136 + cw);
        auto attend = [&](int hp) {
          const uint32_t qad = sb + (XS + 1 - hp) * SLOT + rowo, kt = rB + 2 * (hp ^ wg) * KVT - (lane & 8) * 128, vt = rB + (2 * (hp ^ wg) + 1) * KVT;
          __syncwarp();
          uint32_t kb[2][2][4], vb[2][2][2][4];
#pragma unroll
          for (int h = 0; h < 2; ++h)
#pragma unroll
            for (int nt = 0; nt < 2; ++nt) ldsm_x4(kb[h][nt][0], kb[h][nt][1], kb[h][nt][2], kb[h][nt][3], kt + nt * 1024 + (KX ^ (h << 6)));
#pragma unroll
          for (int ks = 0; ks < 2; ++ks)
#pragma unroll
            for (int np = 0; np < 2; ++np)
#pragma unroll
              for (int h = 0; h < 2; ++h)
                ldsm_x4_t(vb[h][ks][np][0], vb[h][ks][np][1], vb[h][ks][np][2], vb[h][ks][np][3], vt + ks * 2048 + (X ^ (h << 6) ^ (np << 5)));
          if (hp == 0 && lane == 0) release2(bar + B_E3);
          if (DB1 == 1 && hp == 0 && cu < 4) dump(1);
          float la[2][2], lb[2][2], mx[2][2], sm[2][2];
#pragma unroll
          for (int h = 0; h < 2; ++h) {
            const int qo = 32 + 16 * hp + 8 * h, ko = 16 * hp + 8 * h;
            float sc[4][4];
#pragma unroll
            for (int nt = 0; nt < 4; ++nt) {
              sc[nt][0] = sc[nt][1] = sc[nt][2] = sc[nt][3] = 0.f;
#pragma unroll
              for (int ks = 0; ks < 2; ++ks)
                mma_bf16(sc[nt], kq[qo + 4 * ks], kq[qo + 4 * ks + 1], kq[qo + 4 * ks + 2], kq[qo + 4 * ks + 3],
                         nt < 2 ? kb[h][nt & 1][2 * ks] : kq[ko + 4 * ks + (nt & 1)], nt < 2 ? kb[h][nt & 1][2 * ks + 1] : kq[ko + 4 * ks + 2 + (nt & 1)]);
            }
            la[h][0] = fmaf(e ? sc[1][1] : sc[1][0], fA0, bA0);
            lb[h][0] = fmaf(sel ? (e ? sc[0][1] : sc[0][0]) : (e ? sc[2][1] : sc[2][0]), fB0, bB);
            la[h][1] = (e ? sc[2][3] : sc[2][2]) * fA1;
            lb[h][1] = fmaf(sel ? (e ? sc[1][3] : sc[1][2]) : (e ? sc[3][3] : sc[3][2]), fB1, bB);
            mx[h][0] = fmaxf(la[h][0], lb[h][0]); mx[h][1] = fmaxf(la[h][1], lb[h][1]);
          }
#pragma unroll
          for (int o = 1; o <= 2; o <<= 1)
#pragma unroll
            for (int h = 0; h < 2; ++h)
#pragma unroll
              for (int r = 0; r < 2; ++r) mx[h][r] = fmaxf(mx[h][r], __shfl_xor_sync(0xffffffffu, mx[h][r], o));
          float oa[2][4][4];
#pragma unroll
          for (int h = 0; h < 2; ++h) {
#pragma unroll
            for (int r = 0; r < 2; ++r) { la[h][r] = ex2(la[h][r] - mx[h][r]); lb[h][r] = ex2(lb[h][r] - mx[h][r]); sm[h][r] = la[h][r] + lb[h][r]; }
            const uint32_t p0 = pack_bf16(la[h][0] * rjA0, lb[h][0] * rjB0), p1 = pack_bf16(la[h][1] * rjA1, lb[h][1] * rjB1);
            const uint32_t a00 = __byte_perm(p0, 0u, pLo), a02 = __byte_perm(p0, 0u, pA_), a03 = __byte_perm(p1, 0u, pLo);
            const uint32_t a10 = __byte_perm(p0, 0u, pHi), a11 = __byte_perm(p1, 0u, pA_), a13 = __byte_perm(p1, 0u, pHi);
#pragma unroll
            for (int i = 0; i < 4; ++i) {
              oa[h][i][0] = oa[h][i][1] = oa[h][i][2] = oa[h][i][3] = 0.f;
              mma_bf16(oa[h][i], a00, 0u, a02, a03, vb[h][0][i >> 1][2 * (i & 1)], vb[h][0][i >> 1][2 * (i & 1) + 1]);
              mma_bf16(oa[h][i], a10, a11, 0u, a13, vb[h][1][i >> 1][2 * (i & 1)], vb[h][1][i >> 1][2 * (i & 1) + 1]);
            }
          }
#pragma unroll
          for (int o = 1; o <= 2; o <<= 1)
#pragma unroll
            for (int h = 0; h < 2; ++h)
#pragma unroll
              for (int r = 0; r < 2; ++r) sm[h][r] += __shfl_xor_sync(0xffffffffu, sm[h][r], o);
          mbar_wait(bar + (hp ? B_XOLD2 : B_XOLD), 1);
#pragma unroll
          for (int jp = 0; jp < 4; ++jp) ldsm_x4(xo[16 * hp + 4 * jp], xo[16 * hp + 4 * jp + 1], xo[16 * hp + 4 * jp + 2], xo[16 * hp + 4 * jp + 3], qad + (X ^ (jp << 5)));
#pragma unroll
          for (int h = 0; h < 2; ++h) {
            const float i0 = rcp(sm[h][0]), i1 = rcp(sm[h][1]);
#pragma unroll
            for (int np = 0; np < 2; ++np)
            {
              uint32_t (&o)[4] = oq[4 * hp + 2 * h + np];
              o[0] = pack_bf16(oa[h][2 * np][0] * i0, oa[h][2 * np][1] * i0); o[1] = pack_bf16(oa[h][2 * np][2] * i1, oa[h][2 * np][3] * i1);
              o[2] = pack_bf16(oa[h][2 * np + 1][0] * i0, oa[h][2 * np + 1][1] * i0); o[3] = pack_bf16(oa[h][2 * np + 1][2] * i1, oa[h][2 * np + 1][3] * i1);
              stsm_tag(qad + (X ^ (h << 6) ^ (np << 5)), o[0], o[1], o[2], o[3], make_tag(gq, t, 0u), 2 * h + np);
            }
          }
          __syncwarp();
          slab_out_half(sb + (XS + 1 - hp) * SLOT, g_o + (size_t)m0 * D_ + g * 128 + hp * 64, wrow0, lane);
          __syncwarp();
          if (lane == 0) mbar_arrive(bar + (hp ? B_ODONE : B_OH1));
          PROFT(lane == 0 && layer == PL && hp == 0, 128 + cw);
        };
        attend(0);
        if (DB1 == 2 && cu < 4) dump(1);
        if (cu == 4) nbar<15, 64>();
        else if (cu != 0) nbar_dyn(13 + (cu >> 2), 224);
        attend(1);
      } else {
#pragma unroll
        for (int i = 0; i < 32; ++i) kq[i] = pack_bf16(acc[2 * i], acc[2 * i + 1]);
        if (cu < 4) nbar<7, 256>();
        {
          const uint32_t vb = sb + (5 + 3 * wg) * SLOT + (rowq >> 1) + ((lchk ^ ((lane & 7) >> 1)) << 4);
#pragma unroll
          for (int jp = 8; jp < 16; ++jp)
            stsm_x4((vb ^ ((jp & 1) << 5)) + ((jp >> 1) & 3) * 4096,
                    pack_bf16(acc[8 * jp], acc[8 * jp + 1]), pack_bf16(acc[8 * jp + 2], acc[8 * jp + 3]),
                    pack_bf16(acc[8 * jp + 4], acc[8 * jp + 5]), pack_bf16(acc[8 * jp + 6], acc[8 * jp + 7]));
        }
        PROFT(tid_ == 128, layer * 16 + 2);
        Q_DONE();
        const uint32_t pA = sb + (3 + 3 * wg) * SLOT + (rowo & 8191);
        float sc0 = rs0 * L2E, sc1 = rs1 * L2E;
        const uint32_t wa0 = sb + SM_WPHI + lrow * 80 + lchk * 16;
        const uint32_t wu = c.cu >> 2, par = (layer >> 1) & 1;
        float p[2][4][4];
        uint32_t raw[2][4][4], ph[2][4][4];
        float kva[20], oa[2][20];
        auto kv_start = [&](int hp) {
#pragma unroll
          for (int h = 0; h < 2; ++h)
#pragma unroll
            for (int cp = 0; cp < 4; ++cp)
              stsm_x4(pA + hp * 16384 + h * 8192 + (X ^ (cp << 5)), ph[h][cp][0], ph[h][cp][1], ph[h][cp][2], ph[h][cp][3]);
          PROFT(tid_ == 128, layer * 16 + 11);
          fence_async_smem();
          nbar<1, 256>();
          const uint32_t hu = 2 * hp + wu;
          const uint32_t dP = (((sb + 3 * SLOT + hu * 8192) & 0x3FFFF) >> 4) | (512u << 16);
          const uint32_t dV = (((sb + 5 * SLOT + hu * 4096) & 0x3FFFF) >> 4) | (((SM_SD - 5 * SLOT - hu * 4096) >> 4) << 16);
          wgmma_fence();
#pragma unroll
          for (int ks = 0; ks < 8; ++ks)
            wgmma_n40_tt(kva, desc64(dP + (ks >> 2) * 3072 + (ks & 3) * 128, 0x40000040u),
                         desc64(dV + (ks >> 2) * (3072u - (2816u << 16)) + (ks & 3) * 64, 0x80000020u), ks != 0);
          wgmma_commit();
        };
        auto kv_end = [&](int hp) {
          wgmma_wait<0>();
#pragma unroll
          for (int i = 0; i < 20; ++i) asm volatile("" : "+f"(kva[i]) :: "memory");
          nbar_dyn(3 + wu, 128);
          PROFT(tid_ == 128, layer * 16 + 12);
          const bool od = lane & 1;
#pragma unroll
          for (int i = 0; i < 4; ++i)
            sts128(sb + (3 + hp) * SLOT + (cw * 128 + i * 32 + lane) * 16,
                   make_uint4(__float_as_uint(kva[4 * i]), __float_as_uint(kva[4 * i + 1]), __float_as_uint(kva[4 * i + 2]),
                              __float_as_uint(od == (i >= 2) ? 1.f : kva[4 * i + 3])));
          sts128(sb + (6 + hp) * SLOT + wg * 8192 + (wq * 32 + lane) * 16,
                 make_uint4(__float_as_uint(od ? kva[11] : kva[3]), __float_as_uint(od ? kva[15] : kva[7]), __float_as_uint(od ? kva[18] : kva[16]), __float_as_uint(1.f)));
          fence_async_smem();
          __syncwarp();
          if (lane == 0) mbar_arrive(bar + B_KVDONE - hp * 32);
          PROFT(tid_ == 128, layer * 16 + 3);
        };
        const uint4* const kvg = g_kv + (g * 2 + (layer >> 1)) * 2560 + cw * 128 + lane;
        uint4 u[5];
        auto kv_load = [&](int hp) {
#pragma unroll
          for (int i = 0; i < 4; ++i) u[i] = ld_relaxed4(kvg + hp * 1280 + i * 32);
          u[4] = ld_relaxed4(kvg + hp * 1280 + 1024 - cw * 96);
        };
        auto o_start = [&](int hp, const uint32_t (&pq)[2][4][4]) {
          PROFT(tid_ == 128 && hp == 0, layer * 16 + 10);
          if (hp == 0) mbar_wait(bar + B_KVDONE - 32, par);
          const bool od = lane & 1;
          uint32_t n = 0;
#pragma unroll 1
          while (!__all_sync(0xffffffffu, (od ? u[2].w : u[0].w) == 0x41800000u && (od ? u[3].w : u[1].w) == 0x41800000u && u[4].w == 0x41800000u)) {
#pragma unroll 1
            while (__any_sync(0xffffffffu, u[4].w < KVTH) && ++n < (1u << 20)) u[4].w = ld_relaxed(&kvg[hp * 1280 + 1024 - cw * 96].w);
            if (++n > (1u << 20)) { g_err = 6u; break; }
            kv_load(hp);
          }
          PROFT(tid_ == 128 && hp == 0, layer * 16 + 5);
          if (!od) { u[0].w = u[4].x; u[1].w = u[4].y; } else { u[2].w = u[4].x; u[3].w = u[4].y; }
#pragma unroll
          for (int i = 0; i < 4; i += 2)
            stsm_x4(sb + (5 + 3 * hp) * SLOT + rowo + (X ^ ((i & 2) << 4)),
                    pack_bf16(__uint_as_float(u[i].x), __uint_as_float(u[i].y)), pack_bf16(__uint_as_float(u[i].z), __uint_as_float(u[i].w)),
                    pack_bf16(__uint_as_float(u[i + 1].x), __uint_as_float(u[i + 1].y)), pack_bf16(__uint_as_float(u[i + 1].z), __uint_as_float(u[i + 1].w)));
          const uint32_t z2 = pack_bf16(__uint_as_float(u[4].z), __uint_as_float(u[4].z));
          if (t < 2) sts128(sb + (5 + 3 * hp) * SLOT + (wrow0 + gq + 8 * t) * 128 + ((4 ^ gq) << 4), make_uint4(z2, z2, z2, z2));
          fence_async_smem();
          nbar<1, 256>();
          PROFT(tid_ == 128 && hp == 1, layer * 16 + 4);
          const uint32_t dK = (((sb + (5 + 3 * hp) * SLOT) & 0x3FFFF) >> 4) | (512u << 16);
          wgmma_fence();
#pragma unroll
          for (int ks = 0; ks < 4; ++ks) {
#pragma unroll
            for (int hh = 0; hh < 2; ++hh) wgmma_n40_rs(oa[hh], pq[hh][ks], D128(dK + hh * 512 + ks * 128), ks != 0);
          }
          wgmma_commit();
        };
        auto o_end = [&](int hp) {
          wgmma_wait<0>();
#pragma unroll
          for (int i = 0; i < 20; ++i) asm volatile("" : "+f"(oa[0][i]), "+f"(oa[1][i]) :: "memory");
#pragma unroll
          for (int hh = 0; hh < 2; ++hh) {
            const float i0 = rcp(oa[hh][16] + 1e-6f), i1 = rcp(oa[hh][18] + 1e-6f);
            const uint32_t qad = sb + (3 + hp) * SLOT + rowo, hx = hh << 6;
#pragma unroll
            for (int np = 0; np < 2; ++np)
            {
              uint32_t (&o)[4] = oq[4 * hp + 2 * hh + np];
              o[0] = pack_bf16(oa[hh][8 * np] * i0, oa[hh][8 * np + 1] * i0); o[1] = pack_bf16(oa[hh][8 * np + 2] * i1, oa[hh][8 * np + 3] * i1);
              o[2] = pack_bf16(oa[hh][8 * np + 4] * i0, oa[hh][8 * np + 5] * i0); o[3] = pack_bf16(oa[hh][8 * np + 6] * i1, oa[hh][8 * np + 7] * i1);
              stsm_tag(qad + (X ^ hx ^ (np << 5)), o[0], o[1], o[2], o[3], make_tag(gq, t, 1u), 2 * hh + np);
            }
          }
          __syncwarp();
          slab_out_half(sb + (3 + hp) * SLOT, g_o + (size_t)m0 * D_ + g * 128 + hp * 64, wrow0, lane);
          __syncwarp();
          if (lane == 0) mbar_arrive(bar + (hp ? B_ODONE : B_OH1));
        };
#define XO_LOAD() \
        mbar_wait(bar + B_XOLD, 0); \
        mbar_wait(bar + B_XOLD2, 0); \
        _Pragma("unroll") for (int jp = 0; jp < 8; ++jp) \
          ldsm_x4(xo[4 * jp], xo[4 * jp + 1], xo[4 * jp + 2], xo[4 * jp + 3], sb + (XS + 1 - (jp >> 2)) * SLOT + rowo + (X ^ ((jp & 3) << 5)));
#define SC_RELOAD() \
        sc0 = __uint_as_float(lds_vol(sb + SM_RS + (16 + wrow0 + gq) * 4)) * L2E; sc1 = __uint_as_float(lds_vol(sb + SM_RS + (24 + wrow0 + gq) * 4)) * L2E;
        __syncwarp();
        phi_proj<0>(p, kq, wa0);
        phi_exp(raw[0], p[0], sc0, sc1);
        phi_exp(raw[1], p[1], sc0, sc1);
        phi_proj<16>(p, kq, wa0 + 5120);
        phi_norm<0>(ph, raw, kq, wa0, sc0, sc1, rs0, rs1);
        kv_start(0);
        phi_exp(raw[0], p[0], sc0, sc1);
        kv_end(0);
        if (RL & 1) { SC_RELOAD(); }
        XO_LOAD();
        phi_exp(raw[1], p[1], sc0, sc1);
        phi_proj<32>(p, kq, wa0);
        phi_norm<16>(ph, raw, kq, wa0 + 5120, sc0, sc1, rs0, rs1);
        kv_start(1);
        if (lane == 0) release2(bar + B_E3);
        phi_exp(raw[0], p[0], sc0, sc1);
        kv_end(1);
        if (RL & 2) { SC_RELOAD(); }
        kv_load(0);
        phi_exp(raw[1], p[1], sc0, sc1);
        phi_proj<48>(p, kq, wa0 + 5120);
        phi_norm<32>(ph, raw, kq, wa0, sc0, sc1, 1.f, 1.f);
        o_start(0, ph);
        phi_exp(raw[0], p[0], sc0, sc1);
        o_end(0);
        SC_RELOAD();
        kv_load(1);
        phi_exp(raw[1], p[1], sc0, sc1);
        phi_norm<48>(ph, raw, kq, wa0 + 5120, sc0, sc1, 1.f, 1.f);
        o_start(1, ph);
        o_end(1);
      }
      __syncwarp();
      PROFT(lane == 0 && layer == PL, 216 + cw);
      if (lane == 0) mbar_arrive(bar + B_EPI);
      PROFT(tid_ == 128, layer * 16 + 6);
    }
    {
      PHASE_CTX();
      const uint32_t wu = c.cu >> 2;
      const uint32_t dA0 = (((sb + wu * 8192) & 0x3FFFF) >> 4) | (1u << 16), dB0 = ((sb & 0x3FFFF) >> 4) | (512u << 16);
#pragma unroll
      for (int i = 0; i < 32; ++i) { acc[128 + 2 * i] = bf_lo(xo[i]); acc[129 + 2 * i] = bf_hi(xo[i]); }
      uint64_t ta = ((layer & 1) ? WO_A1 : WO_A0) >> 8, tw = (layer & 1) ? WO_B1 : WO_B0;
      mbar_wait(bar + B_FULLT, layer & 1);
      mbar_wait(bar + B_FULLT + 8, layer & 1);
      PROFT(tid_ == 128 && layer == PL, 160);
      wgmma_fence();
#pragma unroll
      for (int k = 0; k < 8; ++k) wgmma_n128_rs(acc, oq[k], D128(dB0 + ((uint32_t)(tw >> (k & 4)) & 15) * 1024 + (k & 3) * 128), 1);
      wgmma_commit();
      tw >>= 8;
      if (lane == 0) release2(bar + B_E2);
#pragma unroll 1
      for (int i = 2; i < 16; ++i) {
        mbar_wait(bar + B_FULLT + i * 8, layer & 1);
        PROFT(tid_ == 128 && layer == PL, 160 + i);
        tile_check(sb + ((uint32_t)ta & 15) * SLOT, g_o + (size_t)m0 * D_ + ((2 * g + (int)(WOORD >> (4 * i))) & 15) * 64, wrow0, lane, ~layer);
        const uint32_t da = dA0 + ((uint32_t)ta & 15) * 1024, db = dB0 + ((uint32_t)tw & 15) * 1024;
        ta >>= 4; tw >>= 4;
        if (WSK && i == 16 - WSK && wu) nbar<6, 256>();
        wgmma_fence();
#pragma unroll
        for (int k = 0; k < 4; ++k) wgmma_n128(acc, D128(da + k * 2), D128(db + k * 128), 1);
        wgmma_commit();
        if (WSK && i == 15 && !wu) asm volatile("bar.arrive 6, 256;" ::: "memory");
        wgmma_wait<1>();
        if (elected && i < 12) release2(bar + B_CONS + (i - 1) * 8);
        if (elected && (unsigned)(i - 13) < 2u && layer + 1 < NLAYERS) release2(bar + B_EMPTYS + (i - 13) * 8);
      }
      const bool last = layer == NLAYERS - 1;
      Tag xt = make_tag(gq, (last || !(UNS & 1)) ? 4 : t, lds_vol(sb + SM_EPOCH) + layer + 1);
      asm volatile("" : "+r"(xt.me), "+r"(xt.mo), "+r"(xt.tg) :: "memory");
      wgmma_wait<0>();
#pragma unroll
      for (int i = 128; i < 192; ++i) asm volatile("" : "+f"(acc[i]) :: "memory");
      if (elected && !last) release2(bar + B_EMPTYS + 16);
      PROFT(tid_ == 128, layer * 16 + 7);
      X_HALF(0, xt);
      if (last) {
        __syncwarp();
        slab_out_half(sb + XS * SLOT, c.out + (size_t)m0 * D_ + g * 128, wrow0, lane);
        X_HALF(1, (Tag{0u, 0u, 0u}));
        __syncwarp();
        slab_out_half(sb + (XS + 1) * SLOT, c.out + (size_t)m0 * D_ + g * 128 + 64, wrow0, lane);
        __syncwarp();
        if (lane == 0) mbar_arrive(bar + B_XDONE);
        PROFT(tid_ == 128, layer * 16 + 24);
        break;
      }
      __syncwarp();
      slab_out_half(sb + XS * SLOT, g_x + (size_t)m0 * D_ + g * 128, wrow0, lane, true);
      __syncwarp();
      if (lane == 0) mbar_arrive(bar + B_XH0);
      nbar_dyn(3 + wu, 128);
    }
  }
}

__device__ __forceinline__ void flag_fetch(uint32_t bar, uint32_t cp, const unsigned int* f) {
  asm volatile("{\n.reg .pred p;\nelect.sync _|p, 0xffffffff;\n@p mbarrier.expect_tx.relaxed.cta.shared::cta.b64 [%2], 64;\n"
               "@p cp.async.bulk.shared::cluster.global.mbarrier::complete_tx::bytes [%0], [%1], 64, [%2];\n}\n"
               ::"r"(cp), "l"(f), "r"(bar + 128) : "memory");
}
__device__ __forceinline__ void src_wait_async(uint32_t bar, uint32_t cp, const unsigned int* f, unsigned int target, int kb, uint32_t& ready, int lane) {
  uint32_t n = 0;
#pragma unroll 1
  while (true) {
    ready |= __ballot_sync(0xffffffffu, (int)(lds_vol(cp + (lane & 15) * 4) - target) >= 0);
    if ((ready >> kb) & 1) break;
    if (n > (1u << 20)) { g_err = 5u; break; }
    if ((n++ & PMOD) == 0) flag_fetch(bar, cp, f);
    __nanosleep(PSL);
  }
}

__device__ __forceinline__ int kblock0(int i, int g) {
  const int j = i >> 1, p = max(g, NCOM) + j - NCOM;
  return (j < NCOM ? j : p < 8 ? p : p - 8 + NCOM) * 2 + (i & 1);
}

__device__ __forceinline__ int wo_kblock(int m, int g) { return (2 * g + (int)((WOORD >> (4 * m)) & 15)) & 15; }

__global__ void __cluster_dims__(2, 1, 1) __launch_bounds__(384, 1)
mega_kernel(const __grid_constant__ CUtensorMap tm_x0, const __grid_constant__ CUtensorMap tm_x,
            const __grid_constant__ CUtensorMap tm_o,
            const __grid_constant__ CUtensorMap tm_wA, const __grid_constant__ CUtensorMap tm_wB,
            const __grid_constant__ CUtensorMap tm_woA, const __grid_constant__ CUtensorMap tm_woB,
                        const bf16* __restrict__ wB, const bf16* __restrict__ wphi, bf16* __restrict__ out) {
  extern __shared__ uint8_t smem_raw[];
  const uint32_t sb = (smem_u32(smem_raw) + 1023u) & ~1023u;
  const uint32_t bar = sb + SM_BAR;
  const int warp = __shfl_sync(0xffffffffu, threadIdx.x >> 5, 0), lane = threadIdx.x & 31;
  if (blockIdx.x >= 128) {
    const int xb = blockIdx.x - 128;
    const int ch = threadIdx.x % 96, rg = threadIdx.x / 96, gg = xb * 2 + ch / 48, sec = (ch % 48) >> 4;
    const uint4* src = reinterpret_cast<const uint4*>(wB + (size_t)rg * 3072 + (sec == 2 ? 0 : 1024 + sec * 1024) + gg * 128 + (ch & 15) * 8);
    float s[8] = {0.f, 0.f, 0.f, 0.f, 0.f, 0.f, 0.f, 0.f};
#pragma unroll 1
    for (int r0 = 0; r0 < 256; r0 += 32) {
      uint4 v[32];
#pragma unroll
      for (int r = 0; r < 32; ++r) v[r] = __ldg(src + (size_t)(r0 + r) * 1536);
#pragma unroll
      for (int r = 0; r < 32; ++r) {
        s[0] += bf_lo(v[r].x); s[1] += bf_hi(v[r].x); s[2] += bf_lo(v[r].y); s[3] += bf_hi(v[r].y);
        s[4] += bf_lo(v[r].z); s[5] += bf_hi(v[r].z); s[6] += bf_lo(v[r].w); s[7] += bf_hi(v[r].w);
      }
    }
    float* cd = g_cs + (ld_relaxed(&g_epoch) & 1) * 6144 + 3072 + xb * 768 + ch * 8;
    red_add4(cd, s[0], s[1], s[2], s[3]);
    red_add4(cd + 4, s[4], s[5], s[6], s[7]);
    nbar<1, 384>();
    if (threadIdx.x < 2) flag_add(&g_csflag[8 + xb * 2 + threadIdx.x].v);
    return;
  }
  const int bid = blockIdx.x;
  const int cr = bid & 1;
  const int g = (bid >> 1) & 7;
  const int rb = (bid >> 4) * 2 + cr;
  const int m0 = rb * 128;

  if (warp < 4) {
    asm volatile("setmaxnreg.dec.sync.aligned.u32 40;");
    asm volatile("barrier.cluster.arrive.relaxed.aligned;" ::: "memory");
    const unsigned int epoch = warp ? ld_relaxed(&g_epoch) : 0u;
    if (warp) cluster_wait();
    unsigned int xbase = epoch * NLAYERS;
    auto wo_a = [&](int layer, int m1) {
      uint64_t ts = ((layer & 1) ? WO_A1 : WO_A0) >> (4 * m1), td = ((layer & 1) ? WO_DA1 : WO_DA0) >> (4 * m1), tk = WOORD >> (4 * m1);
      uint32_t ready = 0u;
#pragma unroll 1
      for (int m = m1; m < 16; m += AW) {
        const int kb = (2 * g + (uint32_t)tk) & 15;
        uint32_t dst = sb + ((uint32_t)ts & 15) * SLOT, fb = bar + B_FULLT + m * 8, eb = bar + B_CONS + ((uint32_t)td & 15) * 8;
        int kc = kb * 64;
        ts >>= 4 * AW; td >>= 4 * AW; tk >>= 4 * AW;
        asm volatile("" : "+r"(dst), "+r"(fb), "+r"(eb), "+r"(kc));
        bool fr = false;
        if (!((ready >> kb) & 1)) {
          PROFT(m == 2 && lane == 0, 64 + layer * 16 + 2);
          if (EP && m > EP) src_wait_async(bar, bar + B_FLG, g_of + rb * 32, xbase + layer + 1, kb, ready, lane);
          else fr = src_wait_tma(g_of + rb * 32, xbase + layer + 1, 1u << kb, ready, lane, eb, layer & 1);
          fence_async_all();
        }
        if (m == 6) mbar_wait_u(bar + B_EPI, layer & 1);
        if (!fr) mbar_wait_u(eb, layer & 1);
        tma_2d_e(dst, &tm_o, kc, m0, fb);
        if (EP && m >= EP && (ready & 0xFFFFu) != 0xFFFFu) flag_fetch(bar, bar + B_FLG, g_of + rb * 32);
        PROFT(lane == 0 && layer == PL, 176 + m);
      }
    };
    auto wo_w = [&](int layer) {
      const CUtensorMap* tx = layer == 0 ? &tm_x0 : &tm_x;
      const CUtensorMap* two = (layer & 1) ? &tm_woB : &tm_woA;
      uint64_t ts = (layer & 1) ? WO_B1 : WO_B0, td = (layer & 1) ? WO_DB1 : WO_DB0, tk = WOORD;
      uint32_t pb = 0;
      fence_async_all();
      mbar_wait_u(bar + B_R0, layer & 1);
      expect_tx_e(bar + B_XOLD, 16384);
      tma_2d_e(sb + (XS + 1) * SLOT, tx, g * 128, m0, bar + B_XOLD);
#pragma unroll 1
      for (int m = 0; m < 16; ++m) {
        uint32_t dst = sb + ((uint32_t)ts & 15) * SLOT + cr * 8192, fb = bar + B_FULLT + m * 8, eb = bar + B_CONS + ((uint32_t)td & 15) * 8;
        int kc = ((2 * g + (uint32_t)tk) & 15) * 64;
        ts >>= 4; td >>= 4; tk >>= 4;
        asm volatile("" : "+r"(dst), "+r"(fb), "+r"(eb), "+r"(kc));
        if (eb < bar + B_E3 && pb >= bar + B_E3) mbar_wait_u(bar + B_E2, layer & 1);
        if (eb != pb) mbar_wait_u(eb, layer & 1);
        pb = eb;
        tma_2d_mc_e(dst, two, g * 128 + cr * 64, kc, fb);
        expect_tx_e(fb, m < 2 ? 16384 : 32768);
        PROFT(lane == 0 && layer == PL, 144 + m);
        if (m == ((layer & 1) ? XB2 : 0)) {
          expect_tx_e(bar + B_XOLD2, 16384);
          tma_2d_e(sb + XS * SLOT, tx, g * 128 + 64, m0, bar + B_XOLD2);
        }
      }
    };
    if (warp == 0) {
      cluster_wait();
      PROFT(lane == 0, 125);
#pragma unroll 1
      for (int layer = 0; layer < NLAYERS; ++layer) {
        const CUtensorMap* tx = layer == 0 ? &tm_x0 : &tm_x;
        const CUtensorMap* tw = (layer & 1) ? &tm_wB : &tm_wA;
        uint32_t s = layer == 0, u = 0, ready = layer == 0 ? 0xFFFFu : 0u;
#pragma unroll 1
        for (int i = s; i < 16; ++i) {
          const int kb = layer == 0 ? kblock0(i, g) : wo_kblock(i, g), kc = kb * 64;
          const uint32_t fb = bar + B_FULLS + s * 8;
          const uint32_t kd = sb + (((QK >> (4 * s)) & 15) + cr) * SLOT, qd = sb + ((QQ >> (4 * s)) & 15) * SLOT + cr * 8192;
          const uint32_t need = 1u << kb;
          const bool ext = i >= 2 || layer == 0, early = ext && (ready & need) == need;
          mbar_wait_u(bar + B_EMPTYS + s * 8, (u + (s ? layer : 0) + 1) & 1);
          if (early) tma_2d_e(sb + ((QA >> (4 * s)) & 15) * SLOT, tx, kc, m0, fb);
          tma_2d_mc_e(kd, tw, 1024 + cr * 1024 + g * 128, kc, fb);
          tma_2d_mc_e(kd + 8192, tw, 1024 + cr * 1024 + g * 128 + 64, kc, fb);
          tma_2d_mc_e(qd, tw, g * 128 + cr * 64, kc, fb);
          expect_tx_e(fb, ext ? 65536 : 49152);
          PROFT(lane == 0 && layer == 0 && i == 1, 31);
          if (layer == 0 && g >= NCOM && i == XPF + (((g - NCOM) * XPM) >> 2)) {
            if (i <= 2) mbar_wait_u(bar + B_FULLS, 0);
            tma_pf_e(&tm_x0, g * 128, m0);
            tma_pf_e(&tm_x0, g * 128 + 64, m0);
          }
          if (layer < 2 && i >= PFS) {
            const int j = i - PFS;
            if (j < 2) tma_pf_e(layer ? &tm_woB : &tm_woA, g * 128 + j * 64, rb * 64);
            else if (j < 8 && layer == 0) tma_pf_e(&tm_wB, ((j >> 1) - 1) * 1024 + g * 128 + (j & 1) * 64, rb * 64);
          }
          if (ext && !early) {
            PROFT(i == 2 && lane == 0, 64 + layer * 16 + 0);
            src_wait_tma(g_xf + rb * 32, xbase + layer + 1, need, ready, lane, fb, 0);
            PROFT(i == 2 && lane == 0, 64 + layer * 16 + 1);
            fence_async_all();
            tma_2d_e(sb + ((QA >> (4 * s)) & 15) * SLOT, tx, kc, m0, fb);
          }
          if (++s == 3) { s = 0; ++u; }
        }
        if (layer == 0) xbase = ld_relaxed(&g_epoch) * NLAYERS;
        if (PG & 1) mbar_wait_u(bar + B_OH1, layer & 1);
        if (PG & 4) mbar_wait_u(bar + B_E3, layer & 1);
        wo_a(layer, 2);
      }
    } else {
      if (warp >= 2) {
        const int h2 = threadIdx.x - 64;
        if (h2 < 16) sts_f(sb + SM_RS + h2 * 4, 0.f);
        if (h2 == 0) sts_f(sb + SM_EPOCH, __uint_as_float(epoch));
        if (h2 < 16) sts_f(bar + B_FLG + h2 * 4, __uint_as_float(xbase));
        mbar_wait_u(bar + B_FULLS, 0);
        colsum(&tm_wA, g_cs + (epoch & 1) * 6144, rb, g, warp - 2, 2, lane, warp == 2 ? sb + SM_SD : (sb + SM_BP + 1023u) & ~1023u, bar + B_CB + (warp - 2) * 8, 0);
#pragma unroll 1
        for (int i = h2; i < 320; i += 64) g_kv[(g * 16 + rb) * 320 + i] = make_uint4(0u, 0u, 0u, 0u);
        fence_async_all();
        nbar<5, 64>();
        if (h2 == 0) flag_add(&g_csflag[g].v);
        PROFT(h2 == 0, 242);
#pragma unroll 1
        for (int i = h2; i < 512; i += 256) {
          uint4 w[4];
#pragma unroll
          for (int j = 0; j < 4; ++j) w[j] = __ldg(reinterpret_cast<const uint4*>(wphi + (size_t)g * 4096) + i + j * 64);
#pragma unroll
          for (int j = 0; j < 4; ++j) sts128(sb + SM_WPHI + ((i >> 2) + j * 16) * 80 + (i & 3) * 16, w[j]);
        }
      }
      if (warp == 1) {
        if (lane >= 27) {
          const CUtensorMap* tm = lane == 27 ? &tm_o : lane == 28 ? &tm_wB : lane == 29 ? &tm_woA : lane == 30 ? &tm_woB : &tm_x;
          asm volatile("prefetch.tensormap [%0];" ::"l"(tm) : "memory");
        }
        __syncwarp();
        {
#pragma unroll 1
          for (int e = 0;; ++e) {
            if (e > 0 && e < NLAYERS) {
              mbar_wait_u(bar + B_XH0, (e - 1) & 1);
              flag_set_x(g_xf + rb * 32 + 2 * g, xbase + e + 1, UNS & 1);
            }
            mbar_wait_u(bar + B_XDONE, e & 1);
            PROFT(e < 4, 64 + e * 16 + 4);
            if (e == NLAYERS) {
              if (bid == 0) g_epoch = epoch + 1;
              break;
            }
            PROFT(e < 4, 64 + e * 16 + 5);
            flag_set(g_xf + rb * 32 + 2 * g + 1, xbase + e + 1);
            PROFT(e < 4, 64 + e * 16 + 7);
            if ((e & 1) == 0) {
#pragma unroll 1
              for (int hp = 0; hp < 2; ++hp) {
                uint4* kvl = g_kv + ((g * 2 + (e >> 1)) * 2 + hp) * 1280;
                mbar_wait_u(bar + B_KVDONE - hp * 32, (e >> 1) & 1);
                PROFT(e == PL, 243 + hp * 4);
                bulk_red_add_e(kvl + rb * 64, sb + (3 + hp) * SLOT + rb * 1024, 16384 - rb * 1024);
                if (rb) bulk_red_add_e(kvl, sb + (3 + hp) * SLOT, rb * 1024);
                bulk_red_add_e(kvl + 1024, sb + (6 + hp) * SLOT, 2048);
                bulk_red_add_e(kvl + 1152, sb + (6 + hp) * SLOT + 8192, 2048);
                bulk_commit();
                PROFT(e < 4, 64 + e * 16 + 6);
              }
              bulk_wait_read0();
              __syncwarp();
              if (lane < 2) release2(bar + B_E1);
              __syncwarp();
            }
            mbar_wait_u(bar + B_OH1, e & 1);
            PROFT(e == PL, 251);
            flag_set_x(g_of + rb * 32 + 2 * g, xbase + e + 1, UNS & 2);
            PROFT(e < 4, 64 + e * 16 + 9);
            mbar_wait_u(bar + B_ODONE, e & 1);
            PROFT(e < 4, 64 + e * 16 + 8);
            flag_set_x(g_of + rb * 32 + 2 * g + 1, xbase + e + 1, UNS & 4);
            PROFT(e < 4, 64 + e * 16 + 11);
          }
        }
      } else {
        const int h2 = threadIdx.x - 64;
        const float* cs = g_cs + (epoch & 1) * 6144;
#pragma unroll 1
        for (int layer = 0; layer < NLAYERS; ++layer) {
          if (warp == 2 && layer < 2) {
            if ((PG & 2) && layer) mbar_wait_u(bar + B_XH0, 0);
            if (lane == 0) flag_wait_t<CSLP>(&g_csflag[layer * 8 + g].v, (epoch + 1) * (16u + layer));
            __syncwarp();
            float4 a[3];
#pragma unroll
            for (int i = 0; i < 3; ++i) a[i] = __ldcg(reinterpret_cast<const float4*>(cs + layer * 3072 + g * 384) + i * 32 + lane);
#pragma unroll 1
            for (int i = 0; i < 3; ++i) {
              const float av[4] = {a[0].x, a[0].y, a[0].z, a[0].w};
              a[0] = a[1]; a[1] = a[2];
#pragma unroll
              for (int j = 0; j < 4; ++j) {
                const float c1 = bf16r(av[j]), c2 = bf16r(av[j] - c1), c3 = (av[j] - c1) - c2;
                sts128(sb + SM_BP + layer * 6144 + ((i * 32 + lane) * 4 + j) * 16, make_uint4(pack_bf16(c1, c2), pack_bf16(c3, 0.f), 0u, 0u));
              }
            }
            fence_async_smem();
            __syncwarp();
            if (lane == 0) mbar_arrive(bar + (layer ? B_CS2 : B_CS));
            PROFT(lane == 0, 64 + layer * 16 + 12);
            if (layer == 0) {
              uint4* hz = g_halo + (rb * 8 + g) * 1024;
#pragma unroll 2
              for (int i = lane; i < 1024; i += 32) hz[i] = make_uint4(0u, 0u, 0u, 0u);
              if (lane < 12) reinterpret_cast<float4*>(g_cs + ((epoch & 1) ^ 1) * 6144 + bid * 48)[lane] = make_float4(0.f, 0.f, 0.f, 0.f);
              g_stats[(2 + (lane >> 4)) * S_ + m0 + g * 16 + (lane & 15)] = make_float2(0.f, 0.f);
              __syncwarp();
              if (lane == 0) flag_add(&g_csflag[8 + g].v);
            }
          }
          if (warp == 3) {
            const bool hal = (layer & 1) && rb > 0;
            {
              uint32_t rdy = 0u;
              src_wait<256>(g_xf + rb * 32, xbase + layer + 1, 0xAAAAu, rdy, lane);
              rdy = 0u;
              if (hal) src_wait<256>(g_xf + (rb - 1) * 32, xbase + layer + 1, 0xAAAAu, rdy, lane);
            }
            float2 u[5];
            const float2* sp = g_stats + layer * S_ + m0 + lane;
#pragma unroll
            for (int i = 0; i < 4; ++i) u[i] = __ldcg(sp + i * 32);
            u[4] = __ldcg(hal ? sp - 16 : sp);
            if (layer == 3) g_stats[(lane >> 4) * S_ + m0 + g * 16 + (lane & 15)] = make_float2(0.f, 0.f);
#pragma unroll 1
            for (int i = 0; i < (hal ? 5 : 4); ++i) {
              const int r = i < 4 ? 16 + i * 32 + lane : lane;
              const float sum = u[0].x, sq = u[0].y;
              u[0] = u[1]; u[1] = u[2]; u[2] = u[3]; u[3] = u[4];
              const float mean = sum * (1.f / D_);
              const float var = fmaxf(fmaf(-sum, mean, sq) * (1.f / D_), 0.f);
              const float sd = bf16r(sqrtf(bf16r(bf16r(var) + 1e-5f)));
              sts_f(sb + SM_RS + r * 4, 1.f / sd);
              if (i < 4) {
                const float hm = -0.5f * bf16r(mean);
                const uint32_t s2 = pack_bf16(sd, sd);
                if (!(layer & 1)) sts128(sb + SM_SD + (r - 16) * 64 + ((r >> 1) & 3) * 16, make_uint4(s2, s2, s2, s2));
                sts128(sb + SM_AP + (r - 16) * 16, make_uint4(pack_bf16(hm, hm), pack_bf16(hm, 0.f), 0u, 0u));
              }
            }
            fence_async_smem();
            __syncwarp();
            if (lane == 0) mbar_arrive(bar + B_STAT);
            PROFT(lane == 0, 64 + layer * 16 + 14);
            wo_w(__shfl_sync(0xffffffffu, layer, 0));
          }
        }
      }
    }
    __syncwarp();
    asm volatile("barrier.cluster.arrive.relaxed.aligned;\nbarrier.cluster.wait.aligned;\n" ::: "memory");
  } else {
    if (warp == 5) {
      if (lane == 0) {
        mbar_init(bar + B_FULLS, 1);
        asm volatile("fence.mbarrier_init.release.cluster;" ::: "memory");
      }
      __syncwarp();
      expect_tx_e(bar + B_FULLS, 65536);
      tma_2d_e(sb + XS * SLOT, &tm_x0, 0, m0, bar + B_FULLS);
#pragma unroll
      for (int j = 0; j < 6; ++j)
        tma_2d_e(sb + (j < 4 ? j + 4 : j - 2) * 8192, &tm_wA, (j < 4 ? 1024 + (j >> 1) * 1024 : 0) + g * 128 + (j & 1) * 64, 0, bar + B_FULLS);
      PROFT(lane == 0, 241);
    }
    if (lane < 8 && warp != 5 && threadIdx.x != 128) {
      const int i = (warp - 4) * 8 + lane;
      mbar_init(bar + i * 8, i < 32 ? 1u << ((BAR_CNT >> (2 * i)) & 3) : i < 48 ? 1u : (i == 59 || i == 60 || i == 62) ? 16u : (i == 48 || i == 63) ? 8u : 4u);
      asm volatile("fence.mbarrier_init.release.cluster;" ::: "memory");
    }
    __syncwarp();
    asm volatile("barrier.cluster.arrive.relaxed.aligned;" ::: "memory");
    asm volatile("setmaxnreg.inc.sync.aligned.u32 232;");
    cluster_wait();
    PROFT(threadIdx.x == 128, 0);
    Ctx c; c.sb = sb; c.g = g; c.rb = rb; c.cu = warp - 4; c.out = out;
    consumer(c);
    asm volatile("bar.warp.sync 0xffffffff;\nbarrier.cluster.arrive.relaxed.aligned;\nbarrier.cluster.wait.aligned;\n" ::: "memory");
  }
}

typedef CUresult (*PFN_encodeTiled)(CUtensorMap*, CUtensorMapDataType, cuuint32_t, void*, const cuuint64_t*, const cuuint64_t*,
                                    const cuuint32_t*, const cuuint32_t*, CUtensorMapInterleave, CUtensorMapSwizzle,
                                    CUtensorMapL2promotion, CUtensorMapFloatOOBfill);

static CUtensorMap make_map(PFN_encodeTiled enc, const void* ptr, uint64_t cols, uint64_t rows, uint32_t box_c, uint32_t box_r, uint32_t nb = 1) {
  CUtensorMap m;
  cuuint64_t dims[3] = {nb > 1 ? box_c : cols, rows, cols / box_c};
  cuuint64_t strides[2] = {cols * 2, box_c * 2};
  cuuint32_t box[3] = {box_c, box_r, nb};
  cuuint32_t es[3] = {1, 1, 1};
  CUresult r = enc(&m, CU_TENSOR_MAP_DATA_TYPE_BFLOAT16, nb > 1 ? 3 : 2, const_cast<void*>(ptr), dims, strides, box, es, CU_TENSOR_MAP_INTERLEAVE_NONE,
      CU_TENSOR_MAP_SWIZZLE_128B, CU_TENSOR_MAP_L2_PROMOTION_L2_256B, CU_TENSOR_MAP_FLOAT_OOB_FILL_NONE);
  (void)r;
  return m;
}

extern "C" void kernel_launch(void* const* d_in, const int* in_sizes, int n_in, void* d_out, int out_size) {
  const bf16* A_x = (const bf16*)d_in[0];
  const bf16* A_wqkv = (const bf16*)d_in[1];
  const bf16* A_wphi = (const bf16*)d_in[2];
  const bf16* A_wo = (const bf16*)d_in[3];
  const bf16* B_wqkv = (const bf16*)d_in[5];
  const bf16* B_wo = (const bf16*)d_in[6];
  bf16* out = (bf16*)d_out;

  static PFN_encodeTiled enc = nullptr;
  static bf16 *p_x, *p_o;
  if (!enc) {
    void* fn = nullptr; cudaDriverEntryPointQueryResult qr;
    cudaGetDriverEntryPoint("cuTensorMapEncodeTiled", &fn, cudaEnableDefault, &qr);
    enc = (PFN_encodeTiled)fn;
    cudaGetSymbolAddress((void**)&p_x, g_x);
    cudaGetSymbolAddress((void**)&p_o, g_o);
    cudaFuncSetAttribute(mega_kernel, cudaFuncAttributeMaxDynamicSharedMemorySize, SM_TOTAL);
  }
  CUtensorMap tm_x0 = make_map(enc, A_x, 1024, 2048, 64, 128);
  CUtensorMap tm_x = make_map(enc, p_x, 1024, 2048, 64, 128);
  CUtensorMap tm_o = make_map(enc, p_o, 1024, 2048, 64, 128);
  CUtensorMap tm_wA = make_map(enc, A_wqkv, 3072, 1024, 64, 64);
  CUtensorMap tm_wB = make_map(enc, B_wqkv, 3072, 1024, 64, 64);
  CUtensorMap tm_woA = make_map(enc, A_wo, 1024, 1024, 64, 64);
  CUtensorMap tm_woB = make_map(enc, B_wo, 1024, 1024, 64, 64);
  mega_kernel<<<128 + NX, 384, SM_TOTAL, cudaStreamPerThread>>>(tm_x0, tm_x, tm_o, tm_wA, tm_wB, tm_woA, tm_woB,
                                                           B_wqkv, A_wphi, out);
}
```

```cpp
#include <cuda_runtime.h>
#include <cuda_bf16.h>
#include <cuda.h>
#include <stdint.h>

typedef __nv_bfloat16 bf16;

constexpr int S_ = 2048, D_ = 1024;

struct __align__(128) Flag { unsigned int v; unsigned int pad[31]; };
__device__ __align__(1024) bf16 g_x[S_ * D_];
__device__ __align__(1024) bf16 g_o[S_ * D_];
__device__ __align__(1024) uint4 g_halo[128 * 2 * 512];
__device__ __align__(1024) uint4 g_kv[8 * 2 * 2 * 1280];
__device__ __align__(1024) float2 g_stats[4 * S_];
__device__ __align__(1024) float g_cs[2 * 2 * 3072];
__device__ Flag g_csflag[16];
__device__ __align__(128) unsigned int g_xf[16 * 32], g_of[16 * 32];
__device__ unsigned int g_epoch, g_err;
#define PROFT(cond, idx) asm volatile("" ::: "memory")

__device__ __forceinline__ uint32_t smem_u32(const void* p) { return (uint32_t)__cvta_generic_to_shared(p); }
__device__ __forceinline__ void mbar_init(uint32_t bar, uint32_t count) {
  asm volatile("mbarrier.init.shared::cta.b64 [%0], %1;" ::"r"(bar), "r"(count) : "memory");
}
__device__ __forceinline__ void mbar_expect_tx(uint32_t bar, uint32_t bytes) {
  asm volatile("mbarrier.arrive.expect_tx.shared::cta.b64 _, [%0], %1;" ::"r"(bar), "r"(bytes) : "memory");
}
__device__ __forceinline__ void mbar_arrive(uint32_t bar) {
  asm volatile("mbarrier.arrive.shared::cta.b64 _, [%0];" ::"r"(bar) : "memory");
}
__device__ __forceinline__ bool mbar_try_wait(uint32_t bar, uint32_t parity) {
  uint32_t ok;
  asm volatile("{\n.reg .pred p;\nmbarrier.try_wait.parity.shared::cta.b64 p, [%1], %2;\nselp.b32 %0, 1, 0, p;\n}\n"
               : "=r"(ok) : "r"(bar), "r"(parity) : "memory");
  return ok != 0;
}
__device__ __forceinline__ bool mbar_test_wait(uint32_t bar, uint32_t parity) {
  uint32_t ok;
  asm volatile("{\n.reg .pred p;\nmbarrier.test_wait.parity.shared::cta.b64 p, [%1], %2;\nselp.b32 %0, 1, 0, p;\n}\n"
               : "=r"(ok) : "r"(bar), "r"(parity) : "memory");
  return ok != 0;
}
__device__ __forceinline__ uint64_t gtimer() {
  uint64_t t; asm volatile("mov.u64 %0, %globaltimer;" : "=l"(t)); return t;
}
__device__ __forceinline__ void mbar_wait(uint32_t bar, uint32_t parity) {
  uint32_t n = 0;
#pragma unroll 1
  while (!mbar_try_wait(bar, parity)) {
    if (++n > (1u << 22)) { g_err = 1u; break; }
  }
}
__device__ __forceinline__ unsigned int ld_acquire(const unsigned int* p) {
  unsigned int v; asm volatile("ld.acquire.gpu.global.u32 %0, [%1];" : "=r"(v) : "l"(p) : "memory"); return v;
}
__device__ __forceinline__ void flag_add(unsigned int* p) {
  asm volatile("red.release.gpu.global.add.u32 [%0], 1;" ::"l"(p) : "memory");
}
__device__ __forceinline__ void flag_set(unsigned int* p, unsigned int v) {
  asm volatile("st.release.gpu.global.u32 [%0], %1;" ::"l"(p), "r"(v) : "memory");
}
__device__ __forceinline__ void flag_set_x(unsigned int* p, unsigned int v, bool rlx) {
  if (rlx) asm volatile("st.relaxed.gpu.global.u32 [%0], %1;" ::"l"(p), "r"(v) : "memory"); else flag_set(p, v);
}
template <int SLEEP>
__device__ __forceinline__ void src_wait(const unsigned int* f, unsigned int target, uint32_t need, uint32_t& ready, int lane) {
  uint32_t n = 0;
#pragma unroll 1
  while ((ready & need) != need) {
    const unsigned int v = ld_acquire(f + (lane & 15));
    ready = __ballot_sync(0xffffffffu, (int)(v - target) >= 0);
    if (SLEEP) { if ((ready & need) != need) __nanosleep(SLEEP); }
    if (++n > (1u << 20)) { g_err = 3u; break; }
  }
  __syncwarp();
}
__device__ __forceinline__ unsigned int ld_relaxed(const unsigned int* p) {
  unsigned int v; asm volatile("ld.relaxed.gpu.global.u32 %0, [%1];" : "=r"(v) : "l"(p) : "memory"); return v;
}
__device__ __forceinline__ bool src_wait_tma(const unsigned int* f, unsigned int target, uint32_t need, uint32_t& ready, int lane, uint32_t eb, uint32_t par) {
  uint32_t n = 0;
  bool fr = false;
#pragma unroll 1
  while ((ready & need) != need) {
    const unsigned int v = ld_acquire(f + (lane & 15));
    fr = __all_sync(0xffffffffu, mbar_test_wait(eb, par));
    ready = __ballot_sync(0xffffffffu, (int)(v - target) >= 0);
    if (++n > (1u << 20)) { g_err = 3u; break; }
  }
  return fr;
}
__device__ __forceinline__ uint4 ld_relaxed4(const uint4* p) {
  uint4 v; asm volatile("ld.relaxed.gpu.global.v4.u32 {%0,%1,%2,%3}, [%4];" : "=r"(v.x), "=r"(v.y), "=r"(v.z), "=r"(v.w) : "l"(p) : "memory"); return v;
}
__device__ __forceinline__ void st_relaxed4(uint4* p, uint32_t a, uint32_t b, uint32_t c, uint32_t d) {
  asm volatile("st.relaxed.gpu.global.v4.u32 [%0], {%1,%2,%3,%4};" ::"l"(p), "r"(a), "r"(b), "r"(c), "r"(d) : "memory");
}
template <int SLEEP>
__device__ __forceinline__ void flag_wait_t(const unsigned int* p, unsigned int target) {
  uint32_t n = 0;
#pragma unroll 1
  while ((int)(ld_acquire(p) - target) < 0) {
    if (SLEEP) __nanosleep(SLEEP);
    if (++n > (1u << 20)) { g_err = 2u; break; }
  }
}
__device__ __forceinline__ void flag_wait(const unsigned int* p, unsigned int target) { flag_wait_t<0>(p, target); }
__device__ __forceinline__ void flag_wait_slow(const unsigned int* p, unsigned int target) { flag_wait_t<256>(p, target); }
__device__ __forceinline__ void tma_load_2d(uint32_t dst, const CUtensorMap* tm, int c0, int c1, uint32_t bar) {
  asm volatile("cp.async.bulk.tensor.2d.shared::cluster.global.mbarrier::complete_tx::bytes [%0], [%1, {%2, %3}], [%4];"
               ::"r"(dst), "l"(tm), "r"(c0), "r"(c1), "r"(bar) : "memory");
}
__device__ __forceinline__ void tma_load_2d_mc(uint32_t dst, const CUtensorMap* tm, int c0, int c1, uint32_t bar, uint16_t mask) {
  asm volatile("cp.async.bulk.tensor.2d.shared::cluster.global.mbarrier::complete_tx::bytes.multicast::cluster [%0], [%1, {%2, %3}], [%4], %5;"
               ::"r"(dst), "l"(tm), "r"(c0), "r"(c1), "r"(bar), "h"(mask) : "memory");
}
__device__ __forceinline__ void mbar_wait_u(uint32_t bar, uint32_t parity) {
  uint32_t n = 0;
#pragma unroll 1
  while (!__all_sync(0xffffffffu, mbar_try_wait(bar, parity))) {
    if (++n > (1u << 22)) { g_err = 1u; break; }
  }
}
__device__ __forceinline__ void expect_tx_e(uint32_t bar, uint32_t bytes) {
  asm volatile("{\n.reg .pred p;\nelect.sync _|p, 0xffffffff;\n@p mbarrier.arrive.expect_tx.shared::cta.b64 _, [%0], %1;\n}\n" ::"r"(bar), "r"(bytes) : "memory");
}
__device__ __forceinline__ void tma_2d_e(uint32_t dst, const CUtensorMap* tm, int c0, int c1, uint32_t bar) {
  asm volatile("{\n.reg .pred p;\nelect.sync _|p, 0xffffffff;\n"
               "@p cp.async.bulk.tensor.2d.shared::cluster.global.mbarrier::complete_tx::bytes [%0], [%1, {%2, %3}], [%4];\n}\n"
               ::"r"(dst), "l"(tm), "r"(c0), "r"(c1), "r"(bar) : "memory");
}
__device__ __forceinline__ void tma_2d_mc_e(uint32_t dst, const CUtensorMap* tm, int c0, int c1, uint32_t bar) {
  asm volatile("{\n.reg .pred p;\nelect.sync _|p, 0xffffffff;\n"
               "@p cp.async.bulk.tensor.2d.shared::cluster.global.mbarrier::complete_tx::bytes.multicast::cluster [%0], [%1, {%2, %3}], [%4], %5;\n}\n"
               ::"r"(dst), "l"(tm), "r"(c0), "r"(c1), "r"(bar), "h"((uint16_t)3) : "memory");
}
__device__ __forceinline__ void tma_pf_e(const CUtensorMap* tm, int c0, int c1) {
  asm volatile("{\n.reg .pred p;\nelect.sync _|p, 0xffffffff;\n"
               "@p cp.async.bulk.prefetch.tensor.2d.L2.global.tile [%0, {%1, %2}];\n}\n" ::"l"(tm), "r"(c0), "r"(c1) : "memory");
}
__device__ __forceinline__ void tma_2d_to_e(uint32_t dst, const CUtensorMap* tm, int c0, int c1, uint32_t bar, uint32_t mask) {
  asm volatile("{\n.reg .pred p;\nelect.sync _|p, 0xffffffff;\n"
               "@p cp.async.bulk.tensor.2d.shared::cluster.global.mbarrier::complete_tx::bytes.multicast::cluster [%0], [%1, {%2, %3}], [%4], %5;\n}\n"
               ::"r"(dst), "l"(tm), "r"(c0), "r"(c1), "r"(bar), "h"((uint16_t)mask) : "memory");
}
__device__ __forceinline__ void tma_3d_mc_e(uint32_t dst, const CUtensorMap* tm, int c1, int c2, uint32_t bar) {
  asm volatile("{\n.reg .pred p;\nelect.sync _|p, 0xffffffff;\n"
               "@p cp.async.bulk.tensor.3d.shared::cluster.global.mbarrier::complete_tx::bytes.multicast::cluster [%0], [%1, {%6, %2, %3}], [%4], %5;\n}\n"
               ::"r"(dst), "l"(tm), "r"(c1), "r"(c2), "r"(bar), "h"((uint16_t)3), "r"(0) : "memory");
}
__device__ __forceinline__ uint32_t poll_flags(const unsigned int* f, unsigned int target, int lane) {
  const unsigned int v = ld_acquire(f + (lane & 15));
  const uint32_t r = __ballot_sync(0xffffffffu, (int)(v - target) >= 0);
  __syncwarp();
  return r;
}
__device__ __forceinline__ void mbar_arrive_cluster(uint32_t local_bar, uint32_t rank) {
  asm volatile("{\n.reg .b32 ra;\nmapa.shared::cluster.u32 ra, %0, %1;\nmbarrier.arrive.shared::cluster.b64 _, [ra];\n}\n"
               ::"r"(local_bar), "r"(rank) : "memory");
}
__device__ __forceinline__ void release2(uint32_t bar) { mbar_arrive_cluster(bar, 0); mbar_arrive_cluster(bar, 1); }
__device__ __forceinline__ void tma_store_2d(const CUtensorMap* tm, uint32_t src, int c0, int c1) {
  asm volatile("cp.async.bulk.tensor.2d.global.shared::cta.bulk_group [%0, {%2, %3}], [%1];"
               ::"l"(tm), "r"(src), "r"(c0), "r"(c1) : "memory");
}
__device__ __forceinline__ void bulk_store(void* dst, uint32_t src, uint32_t bytes) {
  asm volatile("cp.async.bulk.global.shared::cta.bulk_group [%0], [%1], %2;" ::"l"(dst), "r"(src), "r"(bytes) : "memory");
}
__device__ __forceinline__ void bulk_load(uint32_t dst, const void* src, uint32_t bytes, uint32_t bar) {
  asm volatile("cp.async.bulk.shared::cluster.global.mbarrier::complete_tx::bytes [%0], [%1], %2, [%3];" ::"r"(dst), "l"(src), "r"(bytes), "r"(bar) : "memory");
}
__device__ __forceinline__ void bulk_red_add(void* dst, uint32_t src, uint32_t bytes) {
  asm volatile("cp.reduce.async.bulk.global.shared::cta.bulk_group.add.f32 [%0], [%1], %2;" ::"l"(dst), "r"(src), "r"(bytes) : "memory");
}
__device__ __forceinline__ void bulk_red_add_e(void* dst, uint32_t src, uint32_t bytes) {
  asm volatile("{\n.reg .pred p;\nelect.sync _|p, 0xffffffff;\n@p cp.reduce.async.bulk.global.shared::cta.bulk_group.add.f32 [%0], [%1], %2;\n}\n" ::"l"(dst), "r"(src), "r"(bytes) : "memory");
}
__device__ __forceinline__ void bulk_commit() { asm volatile("cp.async.bulk.commit_group;" ::: "memory"); }
__device__ __forceinline__ void bulk_wait_read0() { asm volatile("cp.async.bulk.wait_group.read 0;" ::: "memory"); }
__device__ __forceinline__ void bulk_wait0() { asm volatile("cp.async.bulk.wait_group 0;" ::: "memory"); }
__device__ __forceinline__ void fence_async_smem() { asm volatile("fence.proxy.async.shared::cta;" ::: "memory"); }
__device__ __forceinline__ void fence_async_all() { asm volatile("fence.proxy.async.global;" ::: "memory"); }
__device__ __forceinline__ void wgmma_fence() { asm volatile("wgmma.fence.sync.aligned;" ::: "memory"); }
__device__ __forceinline__ void wgmma_commit() { asm volatile("wgmma.commit_group.sync.aligned;" ::: "memory"); }
template <int N> __device__ __forceinline__ void wgmma_wait() { asm volatile("wgmma.wait_group.sync.aligned %0;" ::"n"(N) : "memory"); }
__device__ __forceinline__ void cluster_arrive() { asm volatile("barrier.cluster.arrive.release.aligned;" ::: "memory"); }
__device__ __forceinline__ void cluster_wait() { asm volatile("barrier.cluster.wait.acquire.aligned;" ::: "memory"); }
template <int ID, int N> __device__ __forceinline__ void nbar() { asm volatile("bar.sync %0, %1;" ::"n"(ID), "n"(N) : "memory"); }
__device__ __forceinline__ uint64_t make_desc(uint32_t addr, uint32_t lbo_bytes, uint32_t sbo_bytes) {
  uint64_t d = 0;
  d |= (uint64_t)((addr & 0x3FFFF) >> 4);
  d |= (uint64_t)((lbo_bytes >> 4) & 0x3FFF) << 16;
  d |= (uint64_t)((sbo_bytes >> 4) & 0x3FFF) << 32;
  d |= (uint64_t)1 << 62;
  return d;
}
__device__ __forceinline__ uint64_t desc64(uint32_t lo, uint32_t hi) { return (uint64_t)lo | ((uint64_t)hi << 32); }
__device__ __forceinline__ uint32_t pack_bf16(float lo, float hi) {
  uint32_t r; asm("cvt.rn.bf16x2.f32 %0, %1, %2;" : "=r"(r) : "f"(hi), "f"(lo)); return r;
}
__device__ __forceinline__ uint32_t mul_bf16x2(uint32_t a, uint32_t s, bool hi) {
  __nv_bfloat162 x = *reinterpret_cast<__nv_bfloat162*>(&a), y = *reinterpret_cast<__nv_bfloat162*>(&s);
  x = __hmul2(x, hi ? __high2bfloat162(y) : __low2bfloat162(y));
  return *reinterpret_cast<uint32_t*>(&x);
}
__device__ __forceinline__ float bf16r(float x) { return __bfloat162float(__float2bfloat16_rn(x)); }
__device__ __forceinline__ float bf_lo(uint32_t u) { return __uint_as_float(u << 16); }
__device__ __forceinline__ float bf_hi(uint32_t u) { return __uint_as_float(u & 0xFFFF0000u); }
__device__ __forceinline__ float ex2(float x) { float r; asm("ex2.approx.ftz.f32 %0, %1;" : "=f"(r) : "f"(x)); return r; }
__device__ __forceinline__ float rcp(float x) { float r; asm("rcp.approx.ftz.f32 %0, %1;" : "=f"(r) : "f"(x)); return r; }
__device__ __forceinline__ void mma_bf16(float (&d)[4], uint32_t a0, uint32_t a1, uint32_t a2, uint32_t a3, uint32_t b0, uint32_t b1) {
  asm("mma.sync.aligned.m16n8k16.row.col.f32.bf16.bf16.f32 {%0,%1,%2,%3}, {%4,%5,%6,%7}, {%8,%9}, {%0,%1,%2,%3};"
               : "+f"(d[0]), "+f"(d[1]), "+f"(d[2]), "+f"(d[3]) : "r"(a0), "r"(a1), "r"(a2), "r"(a3), "r"(b0), "r"(b1));
}
__device__ __forceinline__ void ldsm_x4(uint32_t& r0, uint32_t& r1, uint32_t& r2, uint32_t& r3, uint32_t addr) {
  asm volatile("ldmatrix.sync.aligned.m8n8.x4.shared.b16 {%0,%1,%2,%3}, [%4];"
               : "=r"(r0), "=r"(r1), "=r"(r2), "=r"(r3) : "r"(addr) : "memory");
}
__device__ __forceinline__ void ldsm_x4_t(uint32_t& r0, uint32_t& r1, uint32_t& r2, uint32_t& r3, uint32_t addr) {
  asm volatile("ldmatrix.sync.aligned.m8n8.x4.trans.shared.b16 {%0,%1,%2,%3}, [%4];"
               : "=r"(r0), "=r"(r1), "=r"(r2), "=r"(r3) : "r"(addr) : "memory");
}
__device__ __forceinline__ void ldsm_x2_t(uint32_t& r0, uint32_t& r1, uint32_t addr) {
  asm volatile("ldmatrix.sync.aligned.m8n8.x2.trans.shared.b16 {%0,%1}, [%2];"
               : "=r"(r0), "=r"(r1) : "r"(addr) : "memory");
}
__device__ __forceinline__ void stsm_x4(uint32_t addr, uint32_t r0, uint32_t r1, uint32_t r2, uint32_t r3) {
  asm volatile("stmatrix.sync.aligned.m8n8.x4.shared.b16 [%0], {%1,%2,%3,%4};"
               ::"r"(addr), "r"(r0), "r"(r1), "r"(r2), "r"(r3) : "memory");
}
__device__ __forceinline__ void stsm_x4_p(bool on, uint32_t addr, uint32_t r0, uint32_t r1, uint32_t r2, uint32_t r3) {
  asm volatile("{\n.reg .pred p;\nsetp.ne.b32 p, %5, 0;\n@p stmatrix.sync.aligned.m8n8.x4.shared.b16 [%0], {%1,%2,%3,%4};\n}\n"
               ::"r"(addr), "r"(r0), "r"(r1), "r"(r2), "r"(r3), "r"((int)on) : "memory");
}
__device__ __forceinline__ float2 lds_f2(uint32_t addr) {
  float2 v; asm volatile("ld.shared.v2.f32 {%0,%1}, [%2];" : "=f"(v.x), "=f"(v.y) : "r"(addr) : "memory"); return v;
}
__device__ __forceinline__ uint4 lds128(uint32_t addr) {
  uint4 v; asm volatile("ld.shared.v4.b32 {%0,%1,%2,%3}, [%4];" : "=r"(v.x), "=r"(v.y), "=r"(v.z), "=r"(v.w) : "r"(addr) : "memory"); return v;
}
__device__ __forceinline__ void sts128(uint32_t addr, uint4 v) {
  asm volatile("st.shared.v4.b32 [%0], {%1,%2,%3,%4};" ::"r"(addr), "r"(v.x), "r"(v.y), "r"(v.z), "r"(v.w) : "memory");
}
__device__ __forceinline__ float lds_f(uint32_t addr) {
  float v; asm volatile("ld.shared.f32 %0, [%1];" : "=f"(v) : "r"(addr) : "memory"); return v;
}
__device__ __forceinline__ uint32_t lds_vol(uint32_t addr) {
  uint32_t v; asm volatile("ld.volatile.shared.u32 %0, [%1];" : "=r"(v) : "r"(addr) : "memory"); return v;
}
__device__ __forceinline__ void sts16(uint32_t addr, uint32_t v) {
  asm volatile("st.shared.u16 [%0], %1;" ::"r"(addr), "h"((unsigned short)v) : "memory");
}
__device__ __forceinline__ void nbar_dyn(int id, int n) { asm volatile("bar.sync %0, %1;" ::"r"(id), "r"(n) : "memory"); }
__device__ __forceinline__ uint64_t make_desc_ns(uint32_t addr, uint32_t lbo_bytes, uint32_t sbo_bytes) {
  return (uint64_t)((addr & 0x3FFFF) >> 4) | ((uint64_t)(lbo_bytes >> 4) << 16) | ((uint64_t)(sbo_bytes >> 4) << 32);
}
__device__ __forceinline__ void sts_f(uint32_t addr, float v) { asm volatile("st.shared.f32 [%0], %1;" ::"r"(addr), "f"(v) : "memory"); }
__device__ __forceinline__ void sts64(uint32_t addr, uint32_t a, uint32_t b) {
  asm volatile("st.shared.v2.b32 [%0], {%1,%2};" ::"r"(addr), "r"(a), "r"(b) : "memory");
}
__device__ __forceinline__ void sts_f2(uint32_t addr, float a, float b) {
  asm volatile("st.shared.v2.f32 [%0], {%1,%2};" ::"r"(addr), "f"(a), "f"(b) : "memory");
}
__device__ __forceinline__ void red_add2(float* p, float a, float b) {
  asm volatile("red.global.add.v2.f32 [%0], {%1,%2};" ::"l"(p), "f"(a), "f"(b) : "memory");
}
__device__ __forceinline__ void red_add4(float* p, float a, float b, float c, float d) {
  asm volatile("red.global.add.v4.f32 [%0], {%1,%2,%3,%4};" ::"l"(p), "f"(a), "f"(b), "f"(c), "f"(d) : "memory");
}
__device__ __forceinline__ void red_add1(float* p, float a) {
  asm volatile("red.global.add.f32 [%0], %1;" ::"l"(p), "f"(a) : "memory");
}
__device__ __forceinline__ void l2_prefetch(const void* p, uint32_t bytes) {
  asm volatile("cp.async.bulk.prefetch.L2.global [%0], %1;" ::"l"(p), "r"(bytes) : "memory");
}

__device__ __forceinline__ void wgmma_n256(float (&d)[192], uint64_t da, uint64_t db, int scale_d) {
  asm volatile("{\n.reg .pred p;\nsetp.ne.b32 p, %130, 0;\n"
    "wgmma.mma_async.sync.aligned.m64n256k16.f32.bf16.bf16 {%0, %1, %2, %3, %4, %5, %6, %7, %8, %9, %10, %11, %12, %13, %14, %15, %16, %17, %18, %19, %20, %21, %22, %23, %24, %25, %26, %27, %28, %29, %30, %31, %32, %33, %34, %35, %36, %37, %38, %39, %40, %41, %42, %43, %44, %45, %46, %47, %48, %49, %50, %51, %52, %53, %54, %55, %56, %57, %58, %59, %60, %61, %62, %63, %64, %65, %66, %67, %68, %69, %70, %71, %72, %73, %74, %75, %76, %77, %78, %79, %80, %81, %82, %83, %84, %85, %86, %87, %88, %89, %90, %91, %92, %93, %94, %95, %96, %97, %98, %99, %100, %101, %102, %103, %104, %105, %106, %107, %108, %109, %110, %111, %112, %113, %114, %115, %116, %117, %118, %119, %120, %121, %122, %123, %124, %125, %126, %127}, %128, %129, p, 1, 1, 0, 1;\n}\n"
    : "+f"(d[0]), "+f"(d[1]), "+f"(d[2]), "+f"(d[3]), "+f"(d[4]), "+f"(d[5]), "+f"(d[6]), "+f"(d[7]), "+f"(d[8]), "+f"(d[9]), "+f"(d[10]), "+f"(d[11]), "+f"(d[12]), "+f"(d[13]), "+f"(d[14]), "+f"(d[15]), "+f"(d[16]), "+f"(d[17]), "+f"(d[18]), "+f"(d[19]), "+f"(d[20]), "+f"(d[21]), "+f"(d[22]), "+f"(d[23]), "+f"(d[24]), "+f"(d[25]), "+f"(d[26]), "+f"(d[27]), "+f"(d[28]), "+f"(d[29]), "+f"(d[30]), "+f"(d[31]), "+f"(d[32]), "+f"(d[33]), "+f"(d[34]), "+f"(d[35]), "+f"(d[36]), "+f"(d[37]), "+f"(d[38]), "+f"(d[39]), "+f"(d[40]), "+f"(d[41]), "+f"(d[42]), "+f"(d[43]), "+f"(d[44]), "+f"(d[45]), "+f"(d[46]), "+f"(d[47]), "+f"(d[48]), "+f"(d[49]), "+f"(d[50]), "+f"(d[51]), "+f"(d[52]), "+f"(d[53]), "+f"(d[54]), "+f"(d[55]), "+f"(d[56]), "+f"(d[57]), "+f"(d[58]), "+f"(d[59]), "+f"(d[60]), "+f"(d[61]), "+f"(d[62]), "+f"(d[63]), "+f"(d[64]), "+f"(d[65]), "+f"(d[66]), "+f"(d[67]), "+f"(d[68]), "+f"(d[69]), "+f"(d[70]), "+f"(d[71]), "+f"(d[72]), "+f"(d[73]), "+f"(d[74]), "+f"(d[75]), "+f"(d[76]), "+f"(d[77]), "+f"(d[78]), "+f"(d[79]), "+f"(d[80]), "+f"(d[81]), "+f"(d[82]), "+f"(d[83]), "+f"(d[84]), "+f"(d[85]), "+f"(d[86]), "+f"(d[87]), "+f"(d[88]), "+f"(d[89]), "+f"(d[90]), "+f"(d[91]), "+f"(d[92]), "+f"(d[93]), "+f"(d[94]), "+f"(d[95]), "+f"(d[96]), "+f"(d[97]), "+f"(d[98]), "+f"(d[99]), "+f"(d[100]), "+f"(d[101]), "+f"(d[102]), "+f"(d[103]), "+f"(d[104]), "+f"(d[105]), "+f"(d[106]), "+f"(d[107]), "+f"(d[108]), "+f"(d[109]), "+f"(d[110]), "+f"(d[111]), "+f"(d[112]), "+f"(d[113]), "+f"(d[114]), "+f"(d[115]), "+f"(d[116]), "+f"(d[117]), "+f"(d[118]), "+f"(d[119]), "+f"(d[120]), "+f"(d[121]), "+f"(d[122]), "+f"(d[123]), "+f"(d[124]), "+f"(d[125]), "+f"(d[126]), "+f"(d[127])
    : "l"(da), "l"(db), "r"(scale_d));
}
__device__ __forceinline__ void wgmma_n128(float (&d)[192], uint64_t da, uint64_t db, int scale_d) {
  asm volatile("{\n.reg .pred p;\nsetp.ne.b32 p, %66, 0;\n"
    "wgmma.mma_async.sync.aligned.m64n128k16.f32.bf16.bf16 {%0, %1, %2, %3, %4, %5, %6, %7, %8, %9, %10, %11, %12, %13, %14, %15, %16, %17, %18, %19, %20, %21, %22, %23, %24, %25, %26, %27, %28, %29, %30, %31, %32, %33, %34, %35, %36, %37, %38, %39, %40, %41, %42, %43, %44, %45, %46, %47, %48, %49, %50, %51, %52, %53, %54, %55, %56, %57, %58, %59, %60, %61, %62, %63}, %64, %65, p, 1, 1, 0, 1;\n}\n"
    : "+f"(d[128]), "+f"(d[129]), "+f"(d[130]), "+f"(d[131]), "+f"(d[132]), "+f"(d[133]), "+f"(d[134]), "+f"(d[135]), "+f"(d[136]), "+f"(d[137]), "+f"(d[138]), "+f"(d[139]), "+f"(d[140]), "+f"(d[141]), "+f"(d[142]), "+f"(d[143]), "+f"(d[144]), "+f"(d[145]), "+f"(d[146]), "+f"(d[147]), "+f"(d[148]), "+f"(d[149]), "+f"(d[150]), "+f"(d[151]), "+f"(d[152]), "+f"(d[153]), "+f"(d[154]), "+f"(d[155]), "+f"(d[156]), "+f"(d[157]), "+f"(d[158]), "+f"(d[159]), "+f"(d[160]), "+f"(d[161]), "+f"(d[162]), "+f"(d[163]), "+f"(d[164]), "+f"(d[165]), "+f"(d[166]), "+f"(d[167]), "+f"(d[168]), "+f"(d[169]), "+f"(d[170]), "+f"(d[171]), "+f"(d[172]), "+f"(d[173]), "+f"(d[174]), "+f"(d[175]), "+f"(d[176]), "+f"(d[177]), "+f"(d[178]), "+f"(d[179]), "+f"(d[180]), "+f"(d[181]), "+f"(d[182]), "+f"(d[183]), "+f"(d[184]), "+f"(d[185]), "+f"(d[186]), "+f"(d[187]), "+f"(d[188]), "+f"(d[189]), "+f"(d[190]), "+f"(d[191])
    : "l"(da), "l"(db), "r"(scale_d));
}
__device__ __forceinline__ void wgmma_n256_k(float (&d)[192], uint64_t da, uint64_t db, int scale_d) {
  asm volatile("{\n.reg .pred p;\nsetp.ne.b32 p, %130, 0;\n"
    "wgmma.mma_async.sync.aligned.m64n256k16.f32.bf16.bf16 {%0, %1, %2, %3, %4, %5, %6, %7, %8, %9, %10, %11, %12, %13, %14, %15, %16, %17, %18, %19, %20, %21, %22, %23, %24, %25, %26, %27, %28, %29, %30, %31, %32, %33, %34, %35, %36, %37, %38, %39, %40, %41, %42, %43, %44, %45, %46, %47, %48, %49, %50, %51, %52, %53, %54, %55, %56, %57, %58, %59, %60, %61, %62, %63, %64, %65, %66, %67, %68, %69, %70, %71, %72, %73, %74, %75, %76, %77, %78, %79, %80, %81, %82, %83, %84, %85, %86, %87, %88, %89, %90, %91, %92, %93, %94, %95, %96, %97, %98, %99, %100, %101, %102, %103, %104, %105, %106, %107, %108, %109, %110, %111, %112, %113, %114, %115, %116, %117, %118, %119, %120, %121, %122, %123, %124, %125, %126, %127}, %128, %129, p, 1, 1, 0, 0;\n}\n"
    : "+f"(d[0]), "+f"(d[1]), "+f"(d[2]), "+f"(d[3]), "+f"(d[4]), "+f"(d[5]), "+f"(d[6]), "+f"(d[7]), "+f"(d[8]), "+f"(d[9]), "+f"(d[10]), "+f"(d[11]), "+f"(d[12]), "+f"(d[13]), "+f"(d[14]), "+f"(d[15]), "+f"(d[16]), "+f"(d[17]), "+f"(d[18]), "+f"(d[19]), "+f"(d[20]), "+f"(d[21]), "+f"(d[22]), "+f"(d[23]), "+f"(d[24]), "+f"(d[25]), "+f"(d[26]), "+f"(d[27]), "+f"(d[28]), "+f"(d[29]), "+f"(d[30]), "+f"(d[31]), "+f"(d[32]), "+f"(d[33]), "+f"(d[34]), "+f"(d[35]), "+f"(d[36]), "+f"(d[37]), "+f"(d[38]), "+f"(d[39]), "+f"(d[40]), "+f"(d[41]), "+f"(d[42]), "+f"(d[43]), "+f"(d[44]), "+f"(d[45]), "+f"(d[46]), "+f"(d[47]), "+f"(d[48]), "+f"(d[49]), "+f"(d[50]), "+f"(d[51]), "+f"(d[52]), "+f"(d[53]), "+f"(d[54]), "+f"(d[55]), "+f"(d[56]), "+f"(d[57]), "+f"(d[58]), "+f"(d[59]), "+f"(d[60]), "+f"(d[61]), "+f"(d[62]), "+f"(d[63]), "+f"(d[64]), "+f"(d[65]), "+f"(d[66]), "+f"(d[67]), "+f"(d[68]), "+f"(d[69]), "+f"(d[70]), "+f"(d[71]), "+f"(d[72]), "+f"(d[73]), "+f"(d[74]), "+f"(d[75]), "+f"(d[76]), "+f"(d[77]), "+f"(d[78]), "+f"(d[79]), "+f"(d[80]), "+f"(d[81]), "+f"(d[82]), "+f"(d[83]), "+f"(d[84]), "+f"(d[85]), "+f"(d[86]), "+f"(d[87]), "+f"(d[88]), "+f"(d[89]), "+f"(d[90]), "+f"(d[91]), "+f"(d[92]), "+f"(d[93]), "+f"(d[94]), "+f"(d[95]), "+f"(d[96]), "+f"(d[97]), "+f"(d[98]), "+f"(d[99]), "+f"(d[100]), "+f"(d[101]), "+f"(d[102]), "+f"(d[103]), "+f"(d[104]), "+f"(d[105]), "+f"(d[106]), "+f"(d[107]), "+f"(d[108]), "+f"(d[109]), "+f"(d[110]), "+f"(d[111]), "+f"(d[112]), "+f"(d[113]), "+f"(d[114]), "+f"(d[115]), "+f"(d[116]), "+f"(d[117]), "+f"(d[118]), "+f"(d[119]), "+f"(d[120]), "+f"(d[121]), "+f"(d[122]), "+f"(d[123]), "+f"(d[124]), "+f"(d[125]), "+f"(d[126]), "+f"(d[127])
    : "l"(da), "l"(db), "r"(scale_d));
}
__device__ __forceinline__ void wgmma_n128_k(float (&d)[192], uint64_t da, uint64_t db, int scale_d) {
  asm volatile("{\n.reg .pred p;\nsetp.ne.b32 p, %66, 0;\n"
    "wgmma.mma_async.sync.aligned.m64n128k16.f32.bf16.bf16 {%0, %1, %2, %3, %4, %5, %6, %7, %8, %9, %10, %11, %12, %13, %14, %15, %16, %17, %18, %19, %20, %21, %22, %23, %24, %25, %26, %27, %28, %29, %30, %31, %32, %33, %34, %35, %36, %37, %38, %39, %40, %41, %42, %43, %44, %45, %46, %47, %48, %49, %50, %51, %52, %53, %54, %55, %56, %57, %58, %59, %60, %61, %62, %63}, %64, %65, p, 1, 1, 0, 0;\n}\n"
    : "+f"(d[128]), "+f"(d[129]), "+f"(d[130]), "+f"(d[131]), "+f"(d[132]), "+f"(d[133]), "+f"(d[134]), "+f"(d[135]), "+f"(d[136]), "+f"(d[137]), "+f"(d[138]), "+f"(d[139]), "+f"(d[140]), "+f"(d[141]), "+f"(d[142]), "+f"(d[143]), "+f"(d[144]), "+f"(d[145]), "+f"(d[146]), "+f"(d[147]), "+f"(d[148]), "+f"(d[149]), "+f"(d[150]), "+f"(d[151]), "+f"(d[152]), "+f"(d[153]), "+f"(d[154]), "+f"(d[155]), "+f"(d[156]), "+f"(d[157]), "+f"(d[158]), "+f"(d[159]), "+f"(d[160]), "+f"(d[161]), "+f"(d[162]), "+f"(d[163]), "+f"(d[164]), "+f"(d[165]), "+f"(d[166]), "+f"(d[167]), "+f"(d[168]), "+f"(d[169]), "+f"(d[170]), "+f"(d[171]), "+f"(d[172]), "+f"(d[173]), "+f"(d[174]), "+f"(d[175]), "+f"(d[176]), "+f"(d[177]), "+f"(d[178]), "+f"(d[179]), "+f"(d[180]), "+f"(d[181]), "+f"(d[182]), "+f"(d[183]), "+f"(d[184]), "+f"(d[185]), "+f"(d[186]), "+f"(d[187]), "+f"(d[188]), "+f"(d[189]), "+f"(d[190]), "+f"(d[191])
    : "l"(da), "l"(db), "r"(scale_d));
}
__device__ __forceinline__ void wgmma_n40_tt(float (&d)[20], uint64_t da, uint64_t db, int scale_d) {
  asm volatile("{\n.reg .pred p;\nsetp.ne.b32 p, %22, 0;\n"
    "wgmma.mma_async.sync.aligned.m64n40k16.f32.bf16.bf16 {%0, %1, %2, %3, %4, %5, %6, %7, %8, %9, %10, %11, %12, %13, %14, %15, %16, %17, %18, %19}, %20, %21, p, 1, 1, 1, 1;\n}\n"
    : "+f"(d[0]), "+f"(d[1]), "+f"(d[2]), "+f"(d[3]), "+f"(d[4]), "+f"(d[5]), "+f"(d[6]), "+f"(d[7]), "+f"(d[8]), "+f"(d[9]), "+f"(d[10]), "+f"(d[11]), "+f"(d[12]), "+f"(d[13]), "+f"(d[14]), "+f"(d[15]), "+f"(d[16]), "+f"(d[17]), "+f"(d[18]), "+f"(d[19])
    : "l"(da), "l"(db), "r"(scale_d));
}
__device__ __forceinline__ void wgmma_n40_rs(float (&d)[20], const uint32_t (&a)[4], uint64_t db, int scale_d) {
  asm volatile("{\n.reg .pred p;\nsetp.ne.b32 p, %25, 0;\n"
    "wgmma.mma_async.sync.aligned.m64n40k16.f32.bf16.bf16 {%0, %1, %2, %3, %4, %5, %6, %7, %8, %9, %10, %11, %12, %13, %14, %15, %16, %17, %18, %19}, {%20, %21, %22, %23}, %24, p, 1, 1, 1;\n}\n"
    : "+f"(d[0]), "+f"(d[1]), "+f"(d[2]), "+f"(d[3]), "+f"(d[4]), "+f"(d[5]), "+f"(d[6]), "+f"(d[7]), "+f"(d[8]), "+f"(d[9]), "+f"(d[10]), "+f"(d[11]), "+f"(d[12]), "+f"(d[13]), "+f"(d[14]), "+f"(d[15]), "+f"(d[16]), "+f"(d[17]), "+f"(d[18]), "+f"(d[19])
    : "r"(a[0]), "r"(a[1]), "r"(a[2]), "r"(a[3]), "l"(db), "r"(scale_d));
}
__device__ __forceinline__ void wgmma_n256_0(float (&d)[192], uint64_t da, uint64_t db) {
  asm volatile("{\n.reg .pred p;\nsetp.ne.b32 p, 0, 0;\n"
    "wgmma.mma_async.sync.aligned.m64n256k16.f32.bf16.bf16 {%0, %1, %2, %3, %4, %5, %6, %7, %8, %9, %10, %11, %12, %13, %14, %15, %16, %17, %18, %19, %20, %21, %22, %23, %24, %25, %26, %27, %28, %29, %30, %31, %32, %33, %34, %35, %36, %37, %38, %39, %40, %41, %42, %43, %44, %45, %46, %47, %48, %49, %50, %51, %52, %53, %54, %55, %56, %57, %58, %59, %60, %61, %62, %63, %64, %65, %66, %67, %68, %69, %70, %71, %72, %73, %74, %75, %76, %77, %78, %79, %80, %81, %82, %83, %84, %85, %86, %87, %88, %89, %90, %91, %92, %93, %94, %95, %96, %97, %98, %99, %100, %101, %102, %103, %104, %105, %106, %107, %108, %109, %110, %111, %112, %113, %114, %115, %116, %117, %118, %119, %120, %121, %122, %123, %124, %125, %126, %127}, %128, %129, p, 1, 1, 0, 1;\n}\n"
    : "=f"(d[0]), "=f"(d[1]), "=f"(d[2]), "=f"(d[3]), "=f"(d[4]), "=f"(d[5]), "=f"(d[6]), "=f"(d[7]), "=f"(d[8]), "=f"(d[9]), "=f"(d[10]), "=f"(d[11]), "=f"(d[12]), "=f"(d[13]), "=f"(d[14]), "=f"(d[15]), "=f"(d[16]), "=f"(d[17]), "=f"(d[18]), "=f"(d[19]), "=f"(d[20]), "=f"(d[21]), "=f"(d[22]), "=f"(d[23]), "=f"(d[24]), "=f"(d[25]), "=f"(d[26]), "=f"(d[27]), "=f"(d[28]), "=f"(d[29]), "=f"(d[30]), "=f"(d[31]), "=f"(d[32]), "=f"(d[33]), "=f"(d[34]), "=f"(d[35]), "=f"(d[36]), "=f"(d[37]), "=f"(d[38]), "=f"(d[39]), "=f"(d[40]), "=f"(d[41]), "=f"(d[42]), "=f"(d[43]), "=f"(d[44]), "=f"(d[45]), "=f"(d[46]), "=f"(d[47]), "=f"(d[48]), "=f"(d[49]), "=f"(d[50]), "=f"(d[51]), "=f"(d[52]), "=f"(d[53]), "=f"(d[54]), "=f"(d[55]), "=f"(d[56]), "=f"(d[57]), "=f"(d[58]), "=f"(d[59]), "=f"(d[60]), "=f"(d[61]), "=f"(d[62]), "=f"(d[63]), "=f"(d[64]), "=f"(d[65]), "=f"(d[66]), "=f"(d[67]), "=f"(d[68]), "=f"(d[69]), "=f"(d[70]), "=f"(d[71]), "=f"(d[72]), "=f"(d[73]), "=f"(d[74]), "=f"(d[75]), "=f"(d[76]), "=f"(d[77]), "=f"(d[78]), "=f"(d[79]), "=f"(d[80]), "=f"(d[81]), "=f"(d[82]), "=f"(d[83]), "=f"(d[84]), "=f"(d[85]), "=f"(d[86]), "=f"(d[87]), "=f"(d[88]), "=f"(d[89]), "=f"(d[90]), "=f"(d[91]), "=f"(d[92]), "=f"(d[93]), "=f"(d[94]), "=f"(d[95]), "=f"(d[96]), "=f"(d[97]), "=f"(d[98]), "=f"(d[99]), "=f"(d[100]), "=f"(d[101]), "=f"(d[102]), "=f"(d[103]), "=f"(d[104]), "=f"(d[105]), "=f"(d[106]), "=f"(d[107]), "=f"(d[108]), "=f"(d[109]), "=f"(d[110]), "=f"(d[111]), "=f"(d[112]), "=f"(d[113]), "=f"(d[114]), "=f"(d[115]), "=f"(d[116]), "=f"(d[117]), "=f"(d[118]), "=f"(d[119]), "=f"(d[120]), "=f"(d[121]), "=f"(d[122]), "=f"(d[123]), "=f"(d[124]), "=f"(d[125]), "=f"(d[126]), "=f"(d[127])
    : "l"(da), "l"(db));
}
__device__ __forceinline__ void wgmma_n128_0(float (&d)[192], uint64_t da, uint64_t db) {
  asm volatile("{\n.reg .pred p;\nsetp.ne.b32 p, 0, 0;\n"
    "wgmma.mma_async.sync.aligned.m64n128k16.f32.bf16.bf16 {%0, %1, %2, %3, %4, %5, %6, %7, %8, %9, %10, %11, %12, %13, %14, %15, %16, %17, %18, %19, %20, %21, %22, %23, %24, %25, %26, %27, %28, %29, %30, %31, %32, %33, %34, %35, %36, %37, %38, %39, %40, %41, %42, %43, %44, %45, %46, %47, %48, %49, %50, %51, %52, %53, %54, %55, %56, %57, %58, %59, %60, %61, %62, %63}, %64, %65, p, 1, 1, 0, 1;\n}\n"
    : "=f"(d[128]), "=f"(d[129]), "=f"(d[130]), "=f"(d[131]), "=f"(d[132]), "=f"(d[133]), "=f"(d[134]), "=f"(d[135]), "=f"(d[136]), "=f"(d[137]), "=f"(d[138]), "=f"(d[139]), "=f"(d[140]), "=f"(d[141]), "=f"(d[142]), "=f"(d[143]), "=f"(d[144]), "=f"(d[145]), "=f"(d[146]), "=f"(d[147]), "=f"(d[148]), "=f"(d[149]), "=f"(d[150]), "=f"(d[151]), "=f"(d[152]), "=f"(d[153]), "=f"(d[154]), "=f"(d[155]), "=f"(d[156]), "=f"(d[157]), "=f"(d[158]), "=f"(d[159]), "=f"(d[160]), "=f"(d[161]), "=f"(d[162]), "=f"(d[163]), "=f"(d[164]), "=f"(d[165]), "=f"(d[166]), "=f"(d[167]), "=f"(d[168]), "=f"(d[169]), "=f"(d[170]), "=f"(d[171]), "=f"(d[172]), "=f"(d[173]), "=f"(d[174]), "=f"(d[175]), "=f"(d[176]), "=f"(d[177]), "=f"(d[178]), "=f"(d[179]), "=f"(d[180]), "=f"(d[181]), "=f"(d[182]), "=f"(d[183]), "=f"(d[184]), "=f"(d[185]), "=f"(d[186]), "=f"(d[187]), "=f"(d[188]), "=f"(d[189]), "=f"(d[190]), "=f"(d[191])
    : "l"(da), "l"(db));
}
__device__ __forceinline__ void wgmma_n128_rs(float (&d)[192], const uint32_t (&a)[4], uint64_t db, int scale_d) {
  asm volatile("{\n.reg .pred p;\nsetp.ne.b32 p, %69, 0;\n"
    "wgmma.mma_async.sync.aligned.m64n128k16.f32.bf16.bf16 {%0, %1, %2, %3, %4, %5, %6, %7, %8, %9, %10, %11, %12, %13, %14, %15, %16, %17, %18, %19, %20, %21, %22, %23, %24, %25, %26, %27, %28, %29, %30, %31, %32, %33, %34, %35, %36, %37, %38, %39, %40, %41, %42, %43, %44, %45, %46, %47, %48, %49, %50, %51, %52, %53, %54, %55, %56, %57, %58, %59, %60, %61, %62, %63}, {%64, %65, %66, %67}, %68, p, 1, 1, 1;\n}\n"
    : "+f"(d[128]), "+f"(d[129]), "+f"(d[130]), "+f"(d[131]), "+f"(d[132]), "+f"(d[133]), "+f"(d[134]), "+f"(d[135]), "+f"(d[136]), "+f"(d[137]), "+f"(d[138]), "+f"(d[139]), "+f"(d[140]), "+f"(d[141]), "+f"(d[142]), "+f"(d[143]), "+f"(d[144]), "+f"(d[145]), "+f"(d[146]), "+f"(d[147]), "+f"(d[148]), "+f"(d[149]), "+f"(d[150]), "+f"(d[151]), "+f"(d[152]), "+f"(d[153]), "+f"(d[154]), "+f"(d[155]), "+f"(d[156]), "+f"(d[157]), "+f"(d[158]), "+f"(d[159]), "+f"(d[160]), "+f"(d[161]), "+f"(d[162]), "+f"(d[163]), "+f"(d[164]), "+f"(d[165]), "+f"(d[166]), "+f"(d[167]), "+f"(d[168]), "+f"(d[169]), "+f"(d[170]), "+f"(d[171]), "+f"(d[172]), "+f"(d[173]), "+f"(d[174]), "+f"(d[175]), "+f"(d[176]), "+f"(d[177]), "+f"(d[178]), "+f"(d[179]), "+f"(d[180]), "+f"(d[181]), "+f"(d[182]), "+f"(d[183]), "+f"(d[184]), "+f"(d[185]), "+f"(d[186]), "+f"(d[187]), "+f"(d[188]), "+f"(d[189]), "+f"(d[190]), "+f"(d[191])
    : "r"(a[0]), "r"(a[1]), "r"(a[2]), "r"(a[3]), "l"(db), "r"(scale_d));
}

constexpr int SLOT = 16384;
constexpr int KVT = 10240;
constexpr uint32_t QA = 0x0BAu, QK = 0x462u, QQ = 0x981u;
constexpr int SM_SD = 12 * SLOT;
constexpr int SM_BAR = SM_SD + 8192;
constexpr int SM_RS = SM_BAR + 512;
constexpr int SM_AP = SM_RS + 768;
constexpr int SM_BP = SM_AP + 2048;
constexpr int SM_WPHI = SM_BP + 12288;
constexpr int SM_EPOCH = SM_WPHI + 10240;
constexpr int SM_TOTAL = SM_EPOCH + 16 + 1024;
constexpr int B_FULLS = 0, B_XOLD = 24, B_STAT = 32, B_EMPTYS = 40, B_FULLT = 256  , B_CONS = 384  , B_E3 = 472, B_E0 = 480, B_E1 = 488, B_E2 = 496, B_EPI = 504, B_CS = 160,
              B_KVDONE = 168  , B_ODONE = 176, B_XDONE = 184, B_OH1 = B_CONS, B_CS2 = 208, B_XH0 = 232, B_R0 = 240, B_CB = 144  , B_XOLD2 = 216, B_FLG = 64  ;
constexpr uint64_t BAR_CNT = 0x1c07fc0eac00a800ull;
constexpr uint64_t WO_A0 = 0xa461b57648357643ull, WO_B0 = 0x59083a9021ba9021ull, WO_A1 = 0xa0b76901276a5babull, WO_B1 = 0x95428a5b34890132ull;
constexpr uint64_t WO_DA0 = 0xa9865432ff00dd00ull, WO_DB0 = 0xa986543211bbccccull, WO_DA1 = 0xa98654321ffff000ull, WO_DB1 = 0xa98754321bbcccddull;
#define WOORD 0xFDB9753ECA864210ull
constexpr int NX = 4;
constexpr int XS = 10;

#define PL 2
#define PROFX(i) PROFT(tid_ == 128 && layer == PL, 200 + (i))
#define PSL 20
#define EP 5
#define NCOM 3
#define CSLP 128
#define PFS 8
#define KVTH 0x41700000u
#define RL 3
#define ORD 1
#define XB2 2
#define PMOD 3
#define DB1 2
#define XPF 2
#define XPM 0
#define AW 1
#define PG 0
#define UNS 7
#define TLINE 0
#define RORD 0
#define WSK 1
#define ER 1
#define NLAYERS 4
constexpr float L2E = 1.4426950408889634f;
#define PHI_MAX 2147483648.f

#define D128(lo) desc64(lo, 0x40000040u)
struct Ctx { uint32_t sb; int g, rb, cu; bf16* out; };

__device__ __forceinline__ void colsum(const CUtensorMap* tm, float* cs, int rb, int g, int w0, int dw, int lane, uint32_t stg, uint32_t cb, uint32_t par) {
  const uint32_t src = stg + (lane >> 3) * 2048;
#pragma unroll 1
  for (int wi = w0 - dw; wi < 6; wi += dw) {
    float s[8] = {0.f, 0.f, 0.f, 0.f, 0.f, 0.f, 0.f, 0.f};
    if (wi >= 0) {
      mbar_wait_u(cb, par);
      par ^= 1;
#pragma unroll 4
      for (int r = 0; r < 16; ++r) {
        const uint4 v = lds128(src + r * 128 + (((lane ^ r) & 7) << 4));
        s[0] += bf_lo(v.x); s[1] += bf_hi(v.x); s[2] += bf_lo(v.y); s[3] += bf_hi(v.y);
        s[4] += bf_lo(v.z); s[5] += bf_hi(v.z); s[6] += bf_lo(v.w); s[7] += bf_hi(v.w);
      }
#pragma unroll
      for (int i = 0; i < 8; ++i) s[i] += __shfl_xor_sync(0xffffffffu, s[i], 8);
    }
    const int wn = wi + dw;
    if (wn < 6) {
      expect_tx_e(cb, 8192);
      tma_2d_e(stg, tm, (wn >= 4 ? 0 : 1024 + (wn >> 1) * 1024) + g * 128 + (wn & 1) * 64, rb * 64, cb);
    }
    if (wi >= 0) {
#pragma unroll
      for (int i = 0; i < 8; ++i) s[i] += __shfl_xor_sync(0xffffffffu, s[i], 16);
      if (lane < 8) {
        red_add4(cs + g * 384 + (wi * 8 + lane) * 8, s[0], s[1], s[2], s[3]);
        red_add4(cs + g * 384 + (wi * 8 + lane) * 8 + 4, s[4], s[5], s[6], s[7]);
      }
      __syncwarp();
    }
  }
}
#define PHASE_CTX() \
  uint32_t sb = c.sb; asm volatile("" : "+r"(sb)); \
  int tid_ = threadIdx.x; asm volatile("" : "+r"(tid_)); \
  const uint32_t bar = sb + SM_BAR; \
  const int lane = tid_ & 31, cw = (tid_ >> 5) - 4, wg = cw >> 2, wq = cw & 3, gq = lane >> 2, t = lane & 3, wrow0 = cw * 16; \
  const int lrow = (lane & 7) + ((lane >> 3) & 1) * 8, lchk = lane >> 4; \
  const bool elected = (tid_ & 127) == 0; \
  const uint32_t rowo = (wrow0 + lrow) * 128, X = (lchk ^ (lane & 7)) << 4; \
  (void)bar; (void)wq; (void)gq; (void)lrow; (void)lchk; (void)elected; (void)wrow0; (void)wg; (void)rowo; (void)X; (void)t;

__device__ __forceinline__ void slab_out_half(uint32_t slot, bf16* dst, int wrow0, int lane, bool FENCE = false) {
  const int r0 = lane >> 3, ch = lane & 7;
  const uint32_t src = slot + (wrow0 + r0) * 128;
  uint4 v[4];
#pragma unroll
  for (int i = 0; i < 4; ++i) v[i] = lds128(src + i * 512 + (((ch ^ (4 * i + r0)) & 7) << 4));
  if (FENCE) fence_async_smem();
  dst += (size_t)(wrow0 + r0) * D_ + ch * 8;
#pragma unroll
  for (int i = 0; i < 4; ++i)
    asm volatile("st.global.v4.u32 [%0], {%1,%2,%3,%4};" ::"l"(dst + (size_t)i * 4 * D_), "r"(v[i].x), "r"(v[i].y), "r"(v[i].z), "r"(v[i].w) : "memory");
}

struct Tag { uint32_t me, mo, tg; };
__device__ __forceinline__ Tag make_tag(int gq, int t, uint32_t tg) {
  const uint32_t on = t == (gq & 3), par = ((gq >> 2) ^ gq) & 1;
  return Tag{on & ~par, on & par, tg};
}
__device__ __forceinline__ void stsm_tag(uint32_t addr, uint32_t r0, uint32_t r1, uint32_t r2, uint32_t r3, const Tag& k, int jp) {
  stsm_x4(addr, (r0 & ~k.me) | (k.tg & k.me), (r1 & ~k.me) | (k.tg & k.me), (r2 & ~k.mo) | (k.tg & k.mo), (r3 & ~k.mo) | (k.tg & k.mo));
}
#define TILE_BAD() (((lds_vol(va) ^ tg) | (lds_vol(va + 1024) ^ tg)) & 1)
#define TILE_VA() (slot + (wrow0 + (lane >> 2)) * 128 + (lane & 3) * 32 + (lane >> 2) * 4)
__device__ __forceinline__ void tile_check(uint32_t slot, const bf16* src, int wrow0, int lane, uint32_t tg) {
  const uint32_t va = TILE_VA();
  if (__builtin_expect(__any_sync(0xffffffffu, TILE_BAD()), 0)) {
    const int r0 = lane >> 3, ch = lane & 7;
    uint32_t n = 0;
#pragma unroll 1
    do {
      uint4 v[4];
#pragma unroll
      for (int i = 0; i < 4; ++i) v[i] = ld_relaxed4(reinterpret_cast<const uint4*>(src + (size_t)(wrow0 + r0 + 4 * i) * D_ + ch * 8));
#pragma unroll
      for (int i = 0; i < 4; ++i) sts128(slot + (wrow0 + r0 + 4 * i) * 128 + (((ch ^ (4 * i + r0)) & 7) << 4), v[i]);
      __syncwarp();
      if (++n > (1u << 16)) { g_err = 8u; break; }
    } while (__any_sync(0xffffffffu, TILE_BAD()));
    fence_async_smem();
    __syncwarp();
  }
}

template <int O>
__device__ __forceinline__ void phi_proj(float (&p)[2][4][4], const uint32_t (&kq)[64], uint32_t wa) {
#pragma unroll
  for (int h = 0; h < 2; ++h)
#pragma unroll
    for (int i = 0; i < 4; ++i) { p[h][i][0] = p[h][i][1] = p[h][i][2] = p[h][i][3] = 0.f; }
#pragma unroll
  for (int ks = 0; ks < 2; ++ks)
#pragma unroll
    for (int np = 0; np < 2; ++np)
#pragma unroll
      for (int h = 0; h < 2; ++h) {
        uint32_t b0, b1, b2, b3;
        ldsm_x4_t(b0, b1, b2, b3, wa + h * 2560 + ks * 1280 + np * 32);
        mma_bf16(p[h][2 * np], kq[O + 8 * h + 4 * ks], kq[O + 8 * h + 4 * ks + 1], kq[O + 8 * h + 4 * ks + 2], kq[O + 8 * h + 4 * ks + 3], b0, b1);
        mma_bf16(p[h][2 * np + 1], kq[O + 8 * h + 4 * ks], kq[O + 8 * h + 4 * ks + 1], kq[O + 8 * h + 4 * ks + 2], kq[O + 8 * h + 4 * ks + 3], b2, b3);
      }
}
__device__ __forceinline__ void phi_exp(uint32_t (&raw)[4][4], const float (&p)[4][4], float sc0, float sc1) {
#pragma unroll
  for (int i = 0; i < 4; ++i) {
    const float e0 = ex2(p[i][0] * sc0), e1 = ex2(p[i][1] * sc0), e2 = ex2(p[i][2] * sc1), e3 = ex2(p[i][3] * sc1);
    const float m0 = e0 * e1, m1 = e2 * e3, rr = rcp(m0 * m1), r0 = rr * m1, r1 = rr * m0;
    raw[i >> 1][(i & 1) * 2] = pack_bf16(e0, e1);
    raw[i >> 1][(i & 1) * 2 + 1] = pack_bf16(e2, e3);
    raw[2 + (i >> 1)][(i & 1) * 2] = pack_bf16(e1 * r0, e0 * r0);
    raw[2 + (i >> 1)][(i & 1) * 2 + 1] = pack_bf16(e3 * r1, e2 * r1);
  }
}
#define FENCE_P(h) _Pragma("unroll") for (int i_ = 0; i_ < 16; ++i_) asm volatile("" : "+f"(p[h][i_ >> 2][i_ & 3]) :: "memory")
#define FENCE_RAW(h) _Pragma("unroll") for (int i_ = 0; i_ < 16; ++i_) asm volatile("" : "+r"(raw[h][i_ >> 2][i_ & 3]) :: "memory")
template <int O>
__device__ __forceinline__ void phi_norm(uint32_t (&ph)[2][4][4], const uint32_t (&raw)[2][4][4], const uint32_t (&kq)[64], uint32_t wa,
                                         float sc0, float sc1, float mul0, float mul1) {
  bool bad = false;
#pragma unroll
  for (int h = 0; h < 2; ++h)
#pragma unroll
    for (int sg = 0; sg < 2; ++sg) {
      float ss[4] = {0.f, 0.f, 0.f, 0.f};
#pragma unroll
      for (int ks = 0; ks < 2; ++ks)
        mma_bf16(ss, raw[h][2 * sg + ks][0], raw[h][2 * sg + ks][1], raw[h][2 * sg + ks][2], raw[h][2 * sg + ks][3], 0x3F803F80u, 0x3F803F80u);
      bad = bad || !(ss[0] < PHI_MAX) || !(ss[2] < PHI_MAX);
      const uint32_t iv = pack_bf16(rcp(ss[0]) * mul0, rcp(ss[2]) * mul1);
#pragma unroll
      for (int ks = 0; ks < 2; ++ks)
#pragma unroll
        for (int j = 0; j < 4; ++j) ph[h][2 * sg + ks][j] = mul_bf16x2(raw[h][2 * sg + ks][j], iv, j & 1);
    }
  if (__builtin_expect(__any_sync(0xffffffffu, bad), 0)) {
#pragma unroll 1
    for (int it = 0; it < 4; ++it) {
      float q[4][4];
#pragma unroll
      for (int i = 0; i < 4; ++i) { q[i][0] = q[i][1] = q[i][2] = q[i][3] = 0.f; }
#pragma unroll
      for (int ks = 0; ks < 2; ++ks) {
        uint32_t a[4];
#pragma unroll
        for (int j = 0; j < 4; ++j) a[j] = (it & 2) ? kq[O + 8 + 4 * ks + j] : kq[O + 4 * ks + j];
#pragma unroll
        for (int np = 0; np < 2; ++np) {
          uint32_t b0, b1, b2, b3;
          ldsm_x4_t(b0, b1, b2, b3, wa + (it >> 1) * 2560 + ks * 1280 + np * 32);
          mma_bf16(q[2 * np], a[0], a[1], a[2], a[3], b0, b1);
          mma_bf16(q[2 * np + 1], a[0], a[1], a[2], a[3], b2, b3);
        }
      }
      float iv[2];
#pragma unroll
      for (int r = 0; r < 2; ++r) {
        const float sc = (it & 1) ? -(r ? sc1 : sc0) : (r ? sc1 : sc0);
        float mx = -INFINITY, sm = 0.f;
#pragma unroll
        for (int i = 0; i < 8; ++i) { float& v = q[i >> 1][2 * r + (i & 1)]; v *= sc; mx = fmaxf(mx, v); }
        mx = fmaxf(mx, __shfl_xor_sync(0xffffffffu, mx, 1));
        mx = fmaxf(mx, __shfl_xor_sync(0xffffffffu, mx, 2));
#pragma unroll
        for (int i = 0; i < 8; ++i) { float& v = q[i >> 1][2 * r + (i & 1)]; v = ex2(v - mx); sm += v; }
        sm += __shfl_xor_sync(0xffffffffu, sm, 1);
        sm += __shfl_xor_sync(0xffffffffu, sm, 2);
        iv[r] = rcp(sm) * (r ? mul1 : mul0);
      }
#pragma unroll
      for (int i = 0; i < 24; ++i) ph[i >> 4][(i >> 2) & 3][i & 3] = ph[(i + 8) >> 4][((i + 8) >> 2) & 3][i & 3];
#pragma unroll
      for (int i = 0; i < 4; ++i) {
        ph[1][2 + (i >> 1)][(i & 1) * 2] = pack_bf16(q[i][0] * iv[0], q[i][1] * iv[0]);
        ph[1][2 + (i >> 1)][(i & 1) * 2 + 1] = pack_bf16(q[i][2] * iv[1], q[i][3] * iv[1]);
      }
    }
  }
}

__device__ __forceinline__ void stats_out(float s0, float s1, float q0, float q1, float2* dst, int t) {
  const bool od = t & 1;
  float sa = od ? s1 : s0, qa = od ? q1 : q0;
  sa += __shfl_xor_sync(0xffffffffu, od ? s0 : s1, 1);
  qa += __shfl_xor_sync(0xffffffffu, od ? q0 : q1, 1);
  sa += __shfl_xor_sync(0xffffffffu, sa, 2);
  qa += __shfl_xor_sync(0xffffffffu, qa, 2);
  if (t < 2) red_add2(&dst[t * 8].x, sa, qa);
}

__device__ __forceinline__ void consumer(const Ctx& c) {
  const int g = c.g, m0 = c.rb * 128;
  float acc[192];
#define X_HALF(hf, TG) \
      _Pragma("unroll") for (int jp = 4 * (hf); jp < 4 * (hf) + 4; ++jp) \
        stsm_tag(sb + (XS + (hf)) * SLOT + rowo + (X ^ ((jp & 3) << 5)), \
                 pack_bf16(acc[128 + 8 * jp], acc[129 + 8 * jp]), pack_bf16(acc[130 + 8 * jp], acc[131 + 8 * jp]), \
                 pack_bf16(acc[132 + 8 * jp], acc[133 + 8 * jp]), pack_bf16(acc[134 + 8 * jp], acc[135 + 8 * jp]), TG, jp & 3);
#pragma unroll
  for (int i = 128; i < 192; ++i) acc[i] = 0.f;
#pragma unroll 1
  for (int layer = 0;; ++layer) {
    {
      PHASE_CTX();
      const uint32_t wu = c.cu >> 2;
      const uint32_t dA0 = (((sb + wu * 8192) & 0x3FFFF) >> 4) | (1u << 16), dB0 = ((sb & 0x3FFFF) >> 4) | (512u << 16);
      {
        PROFX(0);
        mbar_wait(bar + B_FULLS, 0);
        PROFX(1);
        wgmma_fence();
        wgmma_n256_0(acc, D128(dA0 + XS * 1024), D128(dB0 + 2048));
#pragma unroll
        for (int k = 1; k < 4; ++k) wgmma_n256(acc, D128(dA0 + XS * 1024 + k * 2), D128(dB0 + 2048 + k * 128), 1);
        wgmma_commit();
        wgmma_wait<1>();
        float s0 = 0.f, s1 = 0.f, q0 = 0.f, q1 = 0.f;
        if (layer) {
          X_HALF(1, (Tag{0u, 0u, 0u}));
#pragma unroll
          for (int i = 128; i < 192; i += 4) {
            s0 += acc[i] + acc[i + 1]; s1 += acc[i + 2] + acc[i + 3];
            q0 = fmaf(acc[i], acc[i], fmaf(acc[i + 1], acc[i + 1], q0)); q1 = fmaf(acc[i + 2], acc[i + 2], fmaf(acc[i + 3], acc[i + 3], q1));
          }
        }
        asm volatile("" : "+f"(s0), "+f"(s1), "+f"(q0), "+f"(q1) :: "memory");
        wgmma_fence();
        wgmma_n128_0(acc, D128(dA0 + XS * 1024), D128(dB0 + 1024));
#pragma unroll
        for (int k = 1; k < 4; ++k) wgmma_n128(acc, D128(dA0 + XS * 1024 + k * 2), D128(dB0 + 1024 + k * 128), 1);
        wgmma_commit();
        if (layer) {
          PHASE_CTX();
          fence_async_smem();
          nbar_dyn(3 + wu, 128);
          stats_out(s0, s1, q0, q1, g_stats + layer * S_ + m0 + wrow0 + gq, t);
          PROFT(tid_ == 128, layer * 16 + 8);
        }
      }
      uint32_t s = 1, u = 0, sp = 0;
      const int ix = layer ? 99 : 2 * min(g, NCOM) + 1;
#pragma unroll 1
      for (int i = 1; i < 14; ++i) {
        mbar_wait(bar + B_FULLS + s * 8, (u + (s ? layer : 0)) & 1);
        if ((UNS & 1) && layer && (unsigned)(i - 2) < 7u) {
          PHASE_CTX();
          tile_check(sb + ((QA >> (4 * s)) & 15) * SLOT, g_x + (size_t)m0 * D_ + ((2 * g + 2 * i - 2) & 15) * 64, wrow0, lane, lds_vol(sb + SM_EPOCH) + layer);
        }
        const uint32_t da = dA0 + ((QA >> (4 * s)) & 15) * 1024, dk = dB0 + ((QK >> (4 * s)) & 15) * 1024,
                       dq = dB0 + ((QQ >> (4 * s)) & 15) * 1024;
        wgmma_fence();
#pragma unroll
        for (int k = 0; k < 4; ++k) {
          wgmma_n256(acc, D128(da + k * 2), D128(dk + k * 128), 1);
          wgmma_n128(acc, D128(da + k * 2), D128(dq + k * 128), 1);
          if (k == ER - 1) {
            wgmma_commit();
            wgmma_wait<1>();
            if (elected && (unsigned)(i - ix) >= 2u) release2(bar + B_EMPTYS + sp * 8);
          }
        }
        wgmma_commit();
        if ((unsigned)(i - ix) < 2u) {
          PHASE_CTX();
          {
            float s0 = 0.f, s1 = 0.f, q0 = 0.f, q1 = 0.f;
            const uint32_t xa = sb + ((QA >> (4 * sp)) & 15) * SLOT + rowo;
#pragma unroll
            for (int jp = 0; jp < 4; ++jp) {
              uint32_t x0, x1, x2, x3;
              ldsm_x4(x0, x1, x2, x3, xa + (X ^ (jp << 5)));
              s0 += (bf_lo(x0) + bf_hi(x0)) + (bf_lo(x2) + bf_hi(x2));
              s1 += (bf_lo(x1) + bf_hi(x1)) + (bf_lo(x3) + bf_hi(x3));
              q0 = fmaf(bf_lo(x0), bf_lo(x0), fmaf(bf_hi(x0), bf_hi(x0), fmaf(bf_lo(x2), bf_lo(x2), fmaf(bf_hi(x2), bf_hi(x2), q0))));
              q1 = fmaf(bf_lo(x1), bf_lo(x1), fmaf(bf_hi(x1), bf_hi(x1), fmaf(bf_lo(x3), bf_lo(x3), fmaf(bf_hi(x3), bf_hi(x3), q1))));
            }
            stats_out(s0, s1, q0, q1, g_stats + m0 + wrow0 + gq, t);
          }
          __syncwarp();
          if (lane == 0 && i != ix) mbar_arrive(bar + B_XDONE);
          nbar_dyn(3 + wu, 128);
          if (ER && elected) release2(bar + B_EMPTYS + sp * 8);
        }
        if (!ER) {
          wgmma_wait<1>();
          if (elected) release2(bar + B_EMPTYS + sp * 8);
        }
        if (i == 1 && layer) {
          PHASE_CTX();
          slab_out_half(sb + (XS + 1) * SLOT, g_x + (size_t)m0 * D_ + g * 128 + 64, wrow0, lane);
          __syncwarp();
          if (lane == 0) mbar_arrive(bar + B_XDONE);
          nbar_dyn(3 + wu, 128);
        }
        sp = s;
        if (++s == 3) { s = 0; ++u; }
      }
      {
        const uint64_t dap = make_desc_ns(sb + SM_AP + wu * 1024, 0, 128), dbp = make_desc_ns(sb + SM_BP + (layer & 1) * 6144, 0, 128);
        if (wu == 0) {
          wgmma_wait<0>();
          if (elected) mbar_arrive(bar + B_R0);
          nbar<6, 256>();
        }
        if (layer < 2) mbar_wait(bar + (layer ? B_CS2 : B_CS), 0);
        mbar_wait(bar + B_STAT, layer & 1);
        mbar_wait(bar + B_FULLS + 16, layer & 1);
        wgmma_fence();
        wgmma_n256_k(acc, dap, dbp, 1);
#pragma unroll
        for (int k = 0; k < 4; ++k) wgmma_n256(acc, D128(dA0 + (QA >> 8) * 1024 + k * 2), D128(dB0 + (QK >> 8) * 1024 + k * 128), 1);
        mbar_wait(bar + B_FULLS, 1);
        PROFT(tid_ == 128, layer * 16 + 9);
        wgmma_fence();
#pragma unroll
        for (int k = 0; k < 4; ++k) wgmma_n256(acc, D128(dA0 + (QA & 15) * 1024 + k * 2), D128(dB0 + (QK & 15) * 1024 + k * 128), 1);
        wgmma_commit();
        if (wu) nbar<6, 256>();
#define Q_TAIL() \
        wgmma_n128_k(acc, dap, dbp + 256, 1); \
        _Pragma("unroll") for (int k = 0; k < 4; ++k) wgmma_n128(acc, D128(dA0 + (QA >> 8) * 1024 + k * 2), D128(dB0 + (QQ >> 8) * 1024 + k * 128), 1); \
        _Pragma("unroll") for (int k = 0; k < 4; ++k) wgmma_n128(acc, D128(dA0 + (QA & 15) * 1024 + k * 2), D128(dB0 + (QQ & 15) * 1024 + k * 128), 1);
        Q_TAIL();
        wgmma_commit();
        wgmma_wait<1>();
#pragma unroll
        for (int i = 0; i < 128; ++i) asm volatile("" : "+f"(acc[i]) :: "memory");
      }
    }
    uint32_t xo[32];
    uint32_t oq[8][4];
    {
      PHASE_CTX();
      PROFT(tid_ == 128, layer * 16 + 1);
      const bool isB = layer & 1;
      const int cu = c.cu;
      if (cu >= 4) asm volatile("bar.arrive 7, 256;" ::: "memory");
      if (elected && cu == 4) mbar_arrive(bar + B_R0);
      uint32_t kq[64];
      const uint32_t rowq = rowo & 8191;
      const float rs0 = lds_f(sb + SM_RS + (16 + wrow0 + gq) * 4), rs1 = lds_f(sb + SM_RS + (24 + wrow0 + gq) * 4);
#define Q_DONE() \
      wgmma_wait<0>(); \
      if (lane == 0) release2(bar + B_E0); \
      _Pragma("unroll") for (int i = 128; i < 192; ++i) asm volatile("" : "+f"(acc[i]) :: "memory"); \
      _Pragma("unroll") for (int i = 0; i < 32; ++i) kq[32 + i] = pack_bf16(acc[128 + 2 * i], acc[129 + 2 * i]);
      if (isB) {
        if (cu == 0) asm volatile("bar.arrive 10, 64;" ::: "memory");
        if (elected) release2(bar + B_E1);
        const int e = gq & 1;
        const bool sel = t > (gq >> 1);
        const uint32_t rja = sb + SM_RS + (wrow0 + 2 * t + e) * 4;
        const float rjA0 = lds_f(rja + 32), rjA1 = lds_f(rja + 64), rjB0 = lds_f(rja + (sel ? 0 : 64)), rjB1 = lds_f(rja + (sel ? 32 : 96));
        uint32_t vv[32];
#pragma unroll
        for (int i = 0; i < 16; ++i) { kq[i] = pack_bf16(acc[2 * i], acc[2 * i + 1]); vv[i] = pack_bf16(acc[64 + 2 * i], acc[65 + 2 * i]); }
        const uint32_t rB = sb + 4 * SLOT + wg * 4 * KVT + rowq;
        auto dump = [&](int hp) {
          const uint32_t kb = rB + 2048 + (hp ^ wg) * 2 * KVT;
#pragma unroll
          for (int jp = 0; jp < 4; ++jp) {
            stsm_x4(kb + (X ^ (jp << 5)), kq[16 * hp + 4 * jp], kq[16 * hp + 4 * jp + 1], kq[16 * hp + 4 * jp + 2], kq[16 * hp + 4 * jp + 3]);
            stsm_x4(kb + KVT + (X ^ (jp << 5)), vv[16 * hp + 4 * jp], vv[16 * hp + 4 * jp + 1], vv[16 * hp + 4 * jp + 2], vv[16 * hp + 4 * jp + 3]);
          }
          if (cu == 3) {
            const uint32_t kd = rB + 2048 + 32768 + (1 - hp) * 2 * KVT;
#pragma unroll
            for (int jp = 0; jp < 4; ++jp) {
              stsm_x4(kd + (X ^ (jp << 5)), kq[16 * hp + 4 * jp], kq[16 * hp + 4 * jp + 1], kq[16 * hp + 4 * jp + 2], kq[16 * hp + 4 * jp + 3]);
              stsm_x4(kd + KVT + (X ^ (jp << 5)), vv[16 * hp + 4 * jp], vv[16 * hp + 4 * jp + 1], vv[16 * hp + 4 * jp + 2], vv[16 * hp + 4 * jp + 3]);
            }
            if (hp) asm volatile("bar.arrive 15, 64;" ::: "memory"); else asm volatile("bar.arrive 9, 64;" ::: "memory");
          }
          asm volatile("bar.arrive %0, 224;" :: "r"(hp ? 13 + (cu >> 2) : 8 + (cu & 4)) : "memory");
        };
        uint4* const hbuf = g_halo + ((c.rb * 8 + g) * 2 + (layer >> 1)) * 512 + lane;
        if (cu < 4) {
          nbar<7, 256>();
          dump(0);
        }
#pragma unroll
        for (int i = 16; i < 32; ++i) { kq[i] = pack_bf16(acc[2 * i], acc[2 * i + 1]); vv[i] = pack_bf16(acc[64 + 2 * i], acc[65 + 2 * i]); }
        if (cu >= 4) {
          if (cu == 7) {
#pragma unroll
            for (int jp = 0; jp < 8; ++jp) {
              st_relaxed4(hbuf + jp * 32, ~kq[4 * jp], ~kq[4 * jp + 1], ~kq[4 * jp + 2], ~kq[4 * jp + 3]);
              st_relaxed4(hbuf + 256 + jp * 32, ~vv[4 * jp], ~vv[4 * jp + 1], ~vv[4 * jp + 2], ~vv[4 * jp + 3]);
            }
          }
          dump(0);
          dump(1);
        }
        PROFT(tid_ == 128, layer * 16 + 2);
        constexpr float SC = 0.17677669529663687f * L2E;
        const float fA0 = rjA0 * rs0 * SC, fB0 = rjB0 * rs0 * SC, fA1 = rjA1 * rs1 * SC, fB1 = rjB1 * rs1 * SC;
        const float bA0 = (m0 + wrow0) ? 0.f : -1e30f, bB = sel ? bA0 : 0.f;
        const uint32_t pA_ = e ? 0x1044u : 0x4410u, pB_ = e ? 0x3244u : 0x4432u, pLo = sel ? pB_ : 0x4444u, pHi = sel ? 0x4444u : pB_;
        const uint32_t KX = ((lane >> 3) ^ (lane & 7)) << 4;
        Q_DONE();
        if (cu == 0) {
          nbar<11, 64>();
        } else if (cu == 4) {
          uint4 hv[16];
          if (c.rb > 0) {
            uint32_t n = 0;
#pragma unroll 1
            while (true) {
              uint32_t mn = 0xFFFFFFFFu;
#pragma unroll
              for (int i = 0; i < 16; ++i) hv[i] = ld_relaxed4(hbuf - 16 * 512 + i * 32);
#pragma unroll
              for (int i = 0; i < 16; ++i) mn = __vimin3_u32(__vimin3_u32(mn, hv[i].x, hv[i].y), hv[i].z, hv[i].w);
              if (__all_sync(0xffffffffu, mn != 0u)) break;
              if (++n > (1u << 20)) { g_err = 4u; break; }
            }
          } else {
#pragma unroll
            for (int i = 0; i < 16; ++i) hv[i] = make_uint4(~0u, ~0u, ~0u, ~0u);
          }
          nbar<10, 64>();
#pragma unroll
          for (int i = 0; i < 16; ++i)
            stsm_x4(rB - 4 * KVT + (((i >> 2) & 1) * 2 + (i >> 3)) * KVT + (X ^ ((i & 3) << 5)), ~hv[i].x, ~hv[i].y, ~hv[i].z, ~hv[i].w);
          asm volatile("bar.arrive 11, 64;" ::: "memory");
          nbar<9, 64>();
        } else {
          nbar_dyn(8 + (cu & 4), 224);
        }
        PROFT(tid_ == 128, layer * 16 + 5);
        PROFT(lane == 0 && layer == PL, 136 + cw);
        auto attend = [&](int hp) {
          const uint32_t qad = sb + (XS + 1 - hp) * SLOT + rowo, kt = rB + 2 * (hp ^ wg) * KVT - (lane & 8) * 128, vt = rB + (2 * (hp ^ wg) + 1) * KVT;
          __syncwarp();
          uint32_t kb[2][2][4], vb[2][2][2][4];
#pragma unroll
          for (int h = 0; h < 2; ++h)
#pragma unroll
            for (int nt = 0; nt < 2; ++nt) ldsm_x4(kb[h][nt][0], kb[h][nt][1], kb[h][nt][2], kb[h][nt][3], kt + nt * 1024 + (KX ^ (h << 6)));
#pragma unroll
          for (int ks = 0; ks < 2; ++ks)
#pragma unroll
            for (int np = 0; np < 2; ++np)
#pragma unroll
              for (int h = 0; h < 2; ++h)
                ldsm_x4_t(vb[h][ks][np][0], vb[h][ks][np][1], vb[h][ks][np][2], vb[h][ks][np][3], vt + ks * 2048 + (X ^ (h << 6) ^ (np << 5)));
          if (hp == 0 && lane == 0) release2(bar + B_E3);
          if (DB1 == 1 && hp == 0 && cu < 4) dump(1);
          float la[2][2], lb[2][2], mx[2][2], sm[2][2];
#pragma unroll
          for (int h = 0; h < 2; ++h) {
            const int qo = 32 + 16 * hp + 8 * h, ko = 16 * hp + 8 * h;
            float sc[4][4];
#pragma unroll
            for (int nt = 0; nt < 4; ++nt) {
              sc[nt][0] = sc[nt][1] = sc[nt][2] = sc[nt][3] = 0.f;
#pragma unroll
              for (int ks = 0; ks < 2; ++ks)
                mma_bf16(sc[nt], kq[qo + 4 * ks], kq[qo + 4 * ks + 1], kq[qo + 4 * ks + 2], kq[qo + 4 * ks + 3],
                         nt < 2 ? kb[h][nt & 1][2 * ks] : kq[ko + 4 * ks + (nt & 1)], nt < 2 ? kb[h][nt & 1][2 * ks + 1] : kq[ko + 4 * ks + 2 + (nt & 1)]);
            }
            la[h][0] = fmaf(e ? sc[1][1] : sc[1][0], fA0, bA0);
            lb[h][0] = fmaf(sel ? (e ? sc[0][1] : sc[0][0]) : (e ? sc[2][1] : sc[2][0]), fB0, bB);
            la[h][1] = (e ? sc[2][3] : sc[2][2]) * fA1;
            lb[h][1] = fmaf(sel ? (e ? sc[1][3] : sc[1][2]) : (e ? sc[3][3] : sc[3][2]), fB1, bB);
            mx[h][0] = fmaxf(la[h][0], lb[h][0]); mx[h][1] = fmaxf(la[h][1], lb[h][1]);
          }
#pragma unroll
          for (int o = 1; o <= 2; o <<= 1)
#pragma unroll
            for (int h = 0; h < 2; ++h)
#pragma unroll
              for (int r = 0; r < 2; ++r) mx[h][r] = fmaxf(mx[h][r], __shfl_xor_sync(0xffffffffu, mx[h][r], o));
          float oa[2][4][4];
#pragma unroll
          for (int h = 0; h < 2; ++h) {
#pragma unroll
            for (int r = 0; r < 2; ++r) { la[h][r] = ex2(la[h][r] - mx[h][r]); lb[h][r] = ex2(lb[h][r] - mx[h][r]); sm[h][r] = la[h][r] + lb[h][r]; }
            const uint32_t p0 = pack_bf16(la[h][0] * rjA0, lb[h][0] * rjB0), p1 = pack_bf16(la[h][1] * rjA1, lb[h][1] * rjB1);
            const uint32_t a00 = __byte_perm(p0, 0u, pLo), a02 = __byte_perm(p0, 0u, pA_), a03 = __byte_perm(p1, 0u, pLo);
            const uint32_t a10 = __byte_perm(p0, 0u, pHi), a11 = __byte_perm(p1, 0u, pA_), a13 = __byte_perm(p1, 0u, pHi);
#pragma unroll
            for (int i = 0; i < 4; ++i) {
              oa[h][i][0] = oa[h][i][1] = oa[h][i][2] = oa[h][i][3] = 0.f;
              mma_bf16(oa[h][i], a00, 0u, a02, a03, vb[h][0][i >> 1][2 * (i & 1)], vb[h][0][i >> 1][2 * (i & 1) + 1]);
              mma_bf16(oa[h][i], a10, a11, 0u, a13, vb[h][1][i >> 1][2 * (i & 1)], vb[h][1][i >> 1][2 * (i & 1) + 1]);
            }
          }
#pragma unroll
          for (int o = 1; o <= 2; o <<= 1)
#pragma unroll
            for (int h = 0; h < 2; ++h)
#pragma unroll
              for (int r = 0; r < 2; ++r) sm[h][r] += __shfl_xor_sync(0xffffffffu, sm[h][r], o);
          mbar_wait(bar + (hp ? B_XOLD2 : B_XOLD), 1);
#pragma unroll
          for (int jp = 0; jp < 4; ++jp) ldsm_x4(xo[16 * hp + 4 * jp], xo[16 * hp + 4 * jp + 1], xo[16 * hp + 4 * jp + 2], xo[16 * hp + 4 * jp + 3], qad + (X ^ (jp << 5)));
#pragma unroll
          for (int h = 0; h < 2; ++h) {
            const float i0 = rcp(sm[h][0]), i1 = rcp(sm[h][1]);
#pragma unroll
            for (int np = 0; np < 2; ++np)
            {
              uint32_t (&o)[4] = oq[4 * hp + 2 * h + np];
              o[0] = pack_bf16(oa[h][2 * np][0] * i0, oa[h][2 * np][1] * i0); o[1] = pack_bf16(oa[h][2 * np][2] * i1, oa[h][2 * np][3] * i1);
              o[2] = pack_bf16(oa[h][2 * np + 1][0] * i0, oa[h][2 * np + 1][1] * i0); o[3] = pack_bf16(oa[h][2 * np + 1][2] * i1, oa[h][2 * np + 1][3] * i1);
              stsm_tag(qad + (X ^ (h << 6) ^ (np << 5)), o[0], o[1], o[2], o[3], make_tag(gq, t, 0u), 2 * h + np);
            }
          }
          __syncwarp();
          slab_out_half(sb + (XS + 1 - hp) * SLOT, g_o + (size_t)m0 * D_ + g * 128 + hp * 64, wrow0, lane);
          __syncwarp();
          if (lane == 0) mbar_arrive(bar + (hp ? B_ODONE : B_OH1));
          PROFT(lane == 0 && layer == PL && hp == 0, 128 + cw);
        };
        attend(0);
        if (DB1 == 2 && cu < 4) dump(1);
        if (cu == 4) nbar<15, 64>();
        else if (cu != 0) nbar_dyn(13 + (cu >> 2), 224);
        attend(1);
      } else {
#pragma unroll
        for (int i = 0; i < 32; ++i) kq[i] = pack_bf16(acc[2 * i], acc[2 * i + 1]);
        if (cu < 4) nbar<7, 256>();
        {
          const uint32_t vb = sb + (5 + 3 * wg) * SLOT + (rowq >> 1) + ((lchk ^ ((lane & 7) >> 1)) << 4);
#pragma unroll
          for (int jp = 8; jp < 16; ++jp)
            stsm_x4((vb ^ ((jp & 1) << 5)) + ((jp >> 1) & 3) * 4096,
                    pack_bf16(acc[8 * jp], acc[8 * jp + 1]), pack_bf16(acc[8 * jp + 2], acc[8 * jp + 3]),
                    pack_bf16(acc[8 * jp + 4], acc[8 * jp + 5]), pack_bf16(acc[8 * jp + 6], acc[8 * jp + 7]));
        }
        PROFT(tid_ == 128, layer * 16 + 2);
        Q_DONE();
        const uint32_t pA = sb + (3 + 3 * wg) * SLOT + (rowo & 8191);
        float sc0 = rs0 * L2E, sc1 = rs1 * L2E;
        const uint32_t wa0 = sb + SM_WPHI + lrow * 80 + lchk * 16;
        const uint32_t wu = c.cu >> 2, par = (layer >> 1) & 1;
        float p[2][4][4];
        uint32_t raw[2][4][4], ph[2][4][4];
        float kva[20], oa[2][20];
        auto kv_start = [&](int hp) {
#pragma unroll
          for (int h = 0; h < 2; ++h)
#pragma unroll
            for (int cp = 0; cp < 4; ++cp)
              stsm_x4(pA + hp * 16384 + h * 8192 + (X ^ (cp << 5)), ph[h][cp][0], ph[h][cp][1], ph[h][cp][2], ph[h][cp][3]);
          PROFT(tid_ == 128, layer * 16 + 11);
          fence_async_smem();
          nbar<1, 256>();
          const uint32_t hu = 2 * hp + wu;
          const uint32_t dP = (((sb + 3 * SLOT + hu * 8192) & 0x3FFFF) >> 4) | (512u << 16);
          const uint32_t dV = (((sb + 5 * SLOT + hu * 4096) & 0x3FFFF) >> 4) | (((SM_SD - 5 * SLOT - hu * 4096) >> 4) << 16);
          wgmma_fence();
#pragma unroll
          for (int ks = 0; ks < 8; ++ks)
            wgmma_n40_tt(kva, desc64(dP + (ks >> 2) * 3072 + (ks & 3) * 128, 0x40000040u),
                         desc64(dV + (ks >> 2) * (3072u - (2816u << 16)) + (ks & 3) * 64, 0x80000020u), ks != 0);
          wgmma_commit();
        };
        auto kv_end = [&](int hp) {
          wgmma_wait<0>();
#pragma unroll
          for (int i = 0; i < 20; ++i) asm volatile("" : "+f"(kva[i]) :: "memory");
          nbar_dyn(3 + wu, 128);
          PROFT(tid_ == 128, layer * 16 + 12);
          const bool od = lane & 1;
#pragma unroll
          for (int i = 0; i < 4; ++i)
            sts128(sb + (3 + hp) * SLOT + (cw * 128 + i * 32 + lane) * 16,
                   make_uint4(__float_as_uint(kva[4 * i]), __float_as_uint(kva[4 * i + 1]), __float_as_uint(kva[4 * i + 2]),
                              __float_as_uint(od == (i >= 2) ? 1.f : kva[4 * i + 3])));
          sts128(sb + (6 + hp) * SLOT + wg * 8192 + (wq * 32 + lane) * 16,
                 make_uint4(__float_as_uint(od ? kva[11] : kva[3]), __float_as_uint(od ? kva[15] : kva[7]), __float_as_uint(od ? kva[18] : kva[16]), __float_as_uint(1.f)));
          fence_async_smem();
          __syncwarp();
          if (lane == 0) mbar_arrive(bar + B_KVDONE - hp * 32);
          PROFT(tid_ == 128, layer * 16 + 3);
        };
        const uint4* const kvg = g_kv + (g * 2 + (layer >> 1)) * 2560 + cw * 128 + lane;
        uint4 u[5];
        auto kv_load = [&](int hp) {
#pragma unroll
          for (int i = 0; i < 4; ++i) u[i] = ld_relaxed4(kvg + hp * 1280 + i * 32);
          u[4] = ld_relaxed4(kvg + hp * 1280 + 1024 - cw * 96);
        };
        auto o_start = [&](int hp, const uint32_t (&pq)[2][4][4]) {
          PROFT(tid_ == 128 && hp == 0, layer * 16 + 10);
          if (hp == 0) mbar_wait(bar + B_KVDONE - 32, par);
          const bool od = lane & 1;
          uint32_t n = 0;
#pragma unroll 1
          while (!__all_sync(0xffffffffu, (od ? u[2].w : u[0].w) == 0x41800000u && (od ? u[3].w : u[1].w) == 0x41800000u && u[4].w == 0x41800000u)) {
#pragma unroll 1
            while (__any_sync(0xffffffffu, u[4].w < KVTH) && ++n < (1u << 20)) u[4].w = ld_relaxed(&kvg[hp * 1280 + 1024 - cw * 96].w);
            if (++n > (1u << 20)) { g_err = 6u; break; }
            kv_load(hp);
          }
          PROFT(tid_ == 128 && hp == 0, layer * 16 + 5);
          if (!od) { u[0].w = u[4].x; u[1].w = u[4].y; } else { u[2].w = u[4].x; u[3].w = u[4].y; }
#pragma unroll
          for (int i = 0; i < 4; i += 2)
            stsm_x4(sb + (5 + 3 * hp) * SLOT + rowo + (X ^ ((i & 2) << 4)),
                    pack_bf16(__uint_as_float(u[i].x), __uint_as_float(u[i].y)), pack_bf16(__uint_as_float(u[i].z), __uint_as_float(u[i].w)),
                    pack_bf16(__uint_as_float(u[i + 1].x), __uint_as_float(u[i + 1].y)), pack_bf16(__uint_as_float(u[i + 1].z), __uint_as_float(u[i + 1].w)));
          const uint32_t z2 = pack_bf16(__uint_as_float(u[4].z), __uint_as_float(u[4].z));
          if (t < 2) sts128(sb + (5 + 3 * hp) * SLOT + (wrow0 + gq + 8 * t) * 128 + ((4 ^ gq) << 4), make_uint4(z2, z2, z2, z2));
          fence_async_smem();
          nbar<1, 256>();
          PROFT(tid_ == 128 && hp == 1, layer * 16 + 4);
          const uint32_t dK = (((sb + (5 + 3 * hp) * SLOT) & 0x3FFFF) >> 4) | (512u << 16);
          wgmma_fence();
#pragma unroll
          for (int ks = 0; ks < 4; ++ks) {
#pragma unroll
            for (int hh = 0; hh < 2; ++hh) wgmma_n40_rs(oa[hh], pq[hh][ks], D128(dK + hh * 512 + ks * 128), ks != 0);
          }
          wgmma_commit();
        };
        auto o_end = [&](int hp) {
          wgmma_wait<0>();
#pragma unroll
          for (int i = 0; i < 20; ++i) asm volatile("" : "+f"(oa[0][i]), "+f"(oa[1][i]) :: "memory");
#pragma unroll
          for (int hh = 0; hh < 2; ++hh) {
            const float i0 = rcp(oa[hh][16] + 1e-6f), i1 = rcp(oa[hh][18] + 1e-6f);
            const uint32_t qad = sb + (3 + hp) * SLOT + rowo, hx = hh << 6;
#pragma unroll
            for (int np = 0; np < 2; ++np)
            {
              uint32_t (&o)[4] = oq[4 * hp + 2 * hh + np];
              o[0] = pack_bf16(oa[hh][8 * np] * i0, oa[hh][8 * np + 1] * i0); o[1] = pack_bf16(oa[hh][8 * np + 2] * i1, oa[hh][8 * np + 3] * i1);
              o[2] = pack_bf16(oa[hh][8 * np + 4] * i0, oa[hh][8 * np + 5] * i0); o[3] = pack_bf16(oa[hh][8 * np + 6] * i1, oa[hh][8 * np + 7] * i1);
              stsm_tag(qad + (X ^ hx ^ (np << 5)), o[0], o[1], o[2], o[3], make_tag(gq, t, 1u), 2 * hh + np);
            }
          }
          __syncwarp();
          slab_out_half(sb + (3 + hp) * SLOT, g_o + (size_t)m0 * D_ + g * 128 + hp * 64, wrow0, lane);
          __syncwarp();
          if (lane == 0) mbar_arrive(bar + (hp ? B_ODONE : B_OH1));
        };
#define XO_LOAD() \
        mbar_wait(bar + B_XOLD, 0); \
        mbar_wait(bar + B_XOLD2, 0); \
        _Pragma("unroll") for (int jp = 0; jp < 8; ++jp) \
          ldsm_x4(xo[4 * jp], xo[4 * jp + 1], xo[4 * jp + 2], xo[4 * jp + 3], sb + (XS + 1 - (jp >> 2)) * SLOT + rowo + (X ^ ((jp & 3) << 5)));
#define SC_RELOAD() \
        sc0 = __uint_as_float(lds_vol(sb + SM_RS + (16 + wrow0 + gq) * 4)) * L2E; sc1 = __uint_as_float(lds_vol(sb + SM_RS + (24 + wrow0 + gq) * 4)) * L2E;
        __syncwarp();
        phi_proj<0>(p, kq, wa0);
        phi_exp(raw[0], p[0], sc0, sc1);
        phi_exp(raw[1], p[1], sc0, sc1);
        phi_proj<16>(p, kq, wa0 + 5120);
        phi_norm<0>(ph, raw, kq, wa0, sc0, sc1, rs0, rs1);
        kv_start(0);
        phi_exp(raw[0], p[0], sc0, sc1);
        kv_end(0);
        if (RL & 1) { SC_RELOAD(); }
        XO_LOAD();
        phi_exp(raw[1], p[1], sc0, sc1);
        phi_proj<32>(p, kq, wa0);
        phi_norm<16>(ph, raw, kq, wa0 + 5120, sc0, sc1, rs0, rs1);
        kv_start(1);
        if (lane == 0) release2(bar + B_E3);
        phi_exp(raw[0], p[0], sc0, sc1);
        kv_end(1);
        if (RL & 2) { SC_RELOAD(); }
        kv_load(0);
        phi_exp(raw[1], p[1], sc0, sc1);
        phi_proj<48>(p, kq, wa0 + 5120);
        phi_norm<32>(ph, raw, kq, wa0, sc0, sc1, 1.f, 1.f);
        o_start(0, ph);
        phi_exp(raw[0], p[0], sc0, sc1);
        o_end(0);
        SC_RELOAD();
        kv_load(1);
        phi_exp(raw[1], p[1], sc0, sc1);
        phi_norm<48>(ph, raw, kq, wa0 + 5120, sc0, sc1, 1.f, 1.f);
        o_start(1, ph);
        o_end(1);
      }
      __syncwarp();
      PROFT(lane == 0 && layer == PL, 216 + cw);
      if (lane == 0) mbar_arrive(bar + B_EPI);
      PROFT(tid_ == 128, layer * 16 + 6);
    }
    {
      PHASE_CTX();
      const uint32_t wu = c.cu >> 2;
      const uint32_t dA0 = (((sb + wu * 8192) & 0x3FFFF) >> 4) | (1u << 16), dB0 = ((sb & 0x3FFFF) >> 4) | (512u << 16);
#pragma unroll
      for (int i = 0; i < 32; ++i) { acc[128 + 2 * i] = bf_lo(xo[i]); acc[129 + 2 * i] = bf_hi(xo[i]); }
      uint64_t ta = ((layer & 1) ? WO_A1 : WO_A0) >> 8, tw = (layer & 1) ? WO_B1 : WO_B0;
      mbar_wait(bar + B_FULLT, layer & 1);
      mbar_wait(bar + B_FULLT + 8, layer & 1);
      PROFT(tid_ == 128 && layer == PL, 160);
      wgmma_fence();
#pragma unroll
      for (int k = 0; k < 8; ++k) wgmma_n128_rs(acc, oq[k], D128(dB0 + ((uint32_t)(tw >> (k & 4)) & 15) * 1024 + (k & 3) * 128), 1);
      wgmma_commit();
      tw >>= 8;
      if (lane == 0) release2(bar + B_E2);
#pragma unroll 1
      for (int i = 2; i < 16; ++i) {
        mbar_wait(bar + B_FULLT + i * 8, layer & 1);
        PROFT(tid_ == 128 && layer == PL, 160 + i);
        tile_check(sb + ((uint32_t)ta & 15) * SLOT, g_o + (size_t)m0 * D_ + ((2 * g + (int)(WOORD >> (4 * i))) & 15) * 64, wrow0, lane, ~layer);
        const uint32_t da = dA0 + ((uint32_t)ta & 15) * 1024, db = dB0 + ((uint32_t)tw & 15) * 1024;
        ta >>= 4; tw >>= 4;
        if (WSK && i == 16 - WSK && wu) nbar<6, 256>();
        wgmma_fence();
#pragma unroll
        for (int k = 0; k < 4; ++k) wgmma_n128(acc, D128(da + k * 2), D128(db + k * 128), 1);
        wgmma_commit();
        if (WSK && i == 15 && !wu) asm volatile("bar.arrive 6, 256;" ::: "memory");
        wgmma_wait<1>();
        if (elected && i < 12) release2(bar + B_CONS + (i - 1) * 8);
        if (elected && (unsigned)(i - 13) < 2u && layer + 1 < NLAYERS) release2(bar + B_EMPTYS + (i - 13) * 8);
      }
      const bool last = layer == NLAYERS - 1;
      Tag xt = make_tag(gq, (last || !(UNS & 1)) ? 4 : t, lds_vol(sb + SM_EPOCH) + layer + 1);
      asm volatile("" : "+r"(xt.me), "+r"(xt.mo), "+r"(xt.tg) :: "memory");
      wgmma_wait<0>();
#pragma unroll
      for (int i = 128; i < 192; ++i) asm volatile("" : "+f"(acc[i]) :: "memory");
      if (elected && !last) release2(bar + B_EMPTYS + 16);
      PROFT(tid_ == 128, layer * 16 + 7);
      X_HALF(0, xt);
      if (last) {
        __syncwarp();
        slab_out_half(sb + XS * SLOT, c.out + (size_t)m0 * D_ + g * 128, wrow0, lane);
        X_HALF(1, (Tag{0u, 0u, 0u}));
        __syncwarp();
        slab_out_half(sb + (XS + 1) * SLOT, c.out + (size_t)m0 * D_ + g * 128 + 64, wrow0, lane);
        __syncwarp();
        if (lane == 0) mbar_arrive(bar + B_XDONE);
        PROFT(tid_ == 128, layer * 16 + 24);
        break;
      }
      __syncwarp();
      slab_out_half(sb + XS * SLOT, g_x + (size_t)m0 * D_ + g * 128, wrow0, lane, true);
      __syncwarp();
      if (lane == 0) mbar_arrive(bar + B_XH0);
      nbar_dyn(3 + wu, 128);
    }
  }
}

__device__ __forceinline__ void flag_fetch(uint32_t bar, uint32_t cp, const unsigned int* f) {
  asm volatile("{\n.reg .pred p;\nelect.sync _|p, 0xffffffff;\n@p mbarrier.expect_tx.relaxed.cta.shared::cta.b64 [%2], 64;\n"
               "@p cp.async.bulk.shared::cluster.global.mbarrier::complete_tx::bytes [%0], [%1], 64, [%2];\n}\n"
               ::"r"(cp), "l"(f), "r"(bar + 128) : "memory");
}
__device__ __forceinline__ void src_wait_async(uint32_t bar, uint32_t cp, const unsigned int* f, unsigned int target, int kb, uint32_t& ready, int lane) {
  uint32_t n = 0;
#pragma unroll 1
  while (true) {
    ready |= __ballot_sync(0xffffffffu, (int)(lds_vol(cp + (lane & 15) * 4) - target) >= 0);
    if ((ready >> kb) & 1) break;
    if (n > (1u << 20)) { g_err = 5u; break; }
    if ((n++ & PMOD) == 0) flag_fetch(bar, cp, f);
    __nanosleep(PSL);
  }
}

__device__ __forceinline__ int kblock0(int i, int g) {
  const int j = i >> 1, p = max(g, NCOM) + j - NCOM;
  return (j < NCOM ? j : p < 8 ? p : p - 8 + NCOM) * 2 + (i & 1);
}

__device__ __forceinline__ int wo_kblock(int m, int g) { return (2 * g + (int)((WOORD >> (4 * m)) & 15)) & 15; }

__global__ void __cluster_dims__(2, 1, 1) __launch_bounds__(384, 1)
mega_kernel(const __grid_constant__ CUtensorMap tm_x0, const __grid_constant__ CUtensorMap tm_x,
            const __grid_constant__ CUtensorMap tm_o,
            const __grid_constant__ CUtensorMap tm_wA, const __grid_constant__ CUtensorMap tm_wB,
            const __grid_constant__ CUtensorMap tm_woA, const __grid_constant__ CUtensorMap tm_woB,
                        const bf16* __restrict__ wB, const bf16* __restrict__ wphi, bf16* __restrict__ out) {
  extern __shared__ uint8_t smem_raw[];
  const uint32_t sb = (smem_u32(smem_raw) + 1023u) & ~1023u;
  const uint32_t bar = sb + SM_BAR;
  const int warp = __shfl_sync(0xffffffffu, threadIdx.x >> 5, 0), lane = threadIdx.x & 31;
  if (blockIdx.x >= 128) {
    const int xb = blockIdx.x - 128;
    const int ch = threadIdx.x % 96, rg = threadIdx.x / 96, gg = xb * 2 + ch / 48, sec = (ch % 48) >> 4;
    const uint4* src = reinterpret_cast<const uint4*>(wB + (size_t)rg * 3072 + (sec == 2 ? 0 : 1024 + sec * 1024) + gg * 128 + (ch & 15) * 8);
    float s[8] = {0.f, 0.f, 0.f, 0.f, 0.f, 0.f, 0.f, 0.f};
#pragma unroll 1
    for (int r0 = 0; r0 < 256; r0 += 32) {
      uint4 v[32];
#pragma unroll
      for (int r = 0; r < 32; ++r) v[r] = __ldg(src + (size_t)(r0 + r) * 1536);
#pragma unroll
      for (int r = 0; r < 32; ++r) {
        s[0] += bf_lo(v[r].x); s[1] += bf_hi(v[r].x); s[2] += bf_lo(v[r].y); s[3] += bf_hi(v[r].y);
        s[4] += bf_lo(v[r].z); s[5] += bf_hi(v[r].z); s[6] += bf_lo(v[r].w); s[7] += bf_hi(v[r].w);
      }
    }
    float* cd = g_cs + (ld_relaxed(&g_epoch) & 1) * 6144 + 3072 + xb * 768 + ch * 8;
    red_add4(cd, s[0], s[1], s[2], s[3]);
    red_add4(cd + 4, s[4], s[5], s[6], s[7]);
    nbar<1, 384>();
    if (threadIdx.x < 2) flag_add(&g_csflag[8 + xb * 2 + threadIdx.x].v);
    return;
  }
  const int bid = blockIdx.x;
  const int cr = bid & 1;
  const int g = (bid >> 1) & 7;
  const int rb = (bid >> 4) * 2 + cr;
  const int m0 = rb * 128;

  if (warp < 4) {
    asm volatile("setmaxnreg.dec.sync.aligned.u32 40;");
    asm volatile("barrier.cluster.arrive.relaxed.aligned;" ::: "memory");
    const unsigned int epoch = warp ? ld_relaxed(&g_epoch) : 0u;
    if (warp) cluster_wait();
    unsigned int xbase = epoch * NLAYERS;
    auto wo_a = [&](int layer, int m1) {
      uint64_t ts = ((layer & 1) ? WO_A1 : WO_A0) >> (4 * m1), td = ((layer & 1) ? WO_DA1 : WO_DA0) >> (4 * m1), tk = WOORD >> (4 * m1);
      uint32_t ready = 0u;
#pragma unroll 1
      for (int m = m1; m < 16; m += AW) {
        const int kb = (2 * g + (uint32_t)tk) & 15;
        uint32_t dst = sb + ((uint32_t)ts & 15) * SLOT, fb = bar + B_FULLT + m * 8, eb = bar + B_CONS + ((uint32_t)td & 15) * 8;
        int kc = kb * 64;
        ts >>= 4 * AW; td >>= 4 * AW; tk >>= 4 * AW;
        asm volatile("" : "+r"(dst), "+r"(fb), "+r"(eb), "+r"(kc));
        bool fr = false;
        if (!((ready >> kb) & 1)) {
          PROFT(m == 2 && lane == 0, 64 + layer * 16 + 2);
          if (EP && m > EP) src_wait_async(bar, bar + B_FLG, g_of + rb * 32, xbase + layer + 1, kb, ready, lane);
          else fr = src_wait_tma(g_of + rb * 32, xbase + layer + 1, 1u << kb, ready, lane, eb, layer & 1);
          fence_async_all();
        }
        if (m == 6) mbar_wait_u(bar + B_EPI, layer & 1);
        if (!fr) mbar_wait_u(eb, layer & 1);
        tma_2d_e(dst, &tm_o, kc, m0, fb);
        if (EP && m >= EP && (ready & 0xFFFFu) != 0xFFFFu) flag_fetch(bar, bar + B_FLG, g_of + rb * 32);
        PROFT(lane == 0 && layer == PL, 176 + m);
      }
    };
    auto wo_w = [&](int layer) {
      const CUtensorMap* tx = layer == 0 ? &tm_x0 : &tm_x;
      const CUtensorMap* two = (layer & 1) ? &tm_woB : &tm_woA;
      uint64_t ts = (layer & 1) ? WO_B1 : WO_B0, td = (layer & 1) ? WO_DB1 : WO_DB0, tk = WOORD;
      uint32_t pb = 0;
      fence_async_all();
      mbar_wait_u(bar + B_R0, layer & 1);
      expect_tx_e(bar + B_XOLD, 16384);
      tma_2d_e(sb + (XS + 1) * SLOT, tx, g * 128, m0, bar + B_XOLD);
#pragma unroll 1
      for (int m = 0; m < 16; ++m) {
        uint32_t dst = sb + ((uint32_t)ts & 15) * SLOT + cr * 8192, fb = bar + B_FULLT + m * 8, eb = bar + B_CONS + ((uint32_t)td & 15) * 8;
        int kc = ((2 * g + (uint32_t)tk) & 15) * 64;
        ts >>= 4; td >>= 4; tk >>= 4;
        asm volatile("" : "+r"(dst), "+r"(fb), "+r"(eb), "+r"(kc));
        if (eb < bar + B_E3 && pb >= bar + B_E3) mbar_wait_u(bar + B_E2, layer & 1);
        if (eb != pb) mbar_wait_u(eb, layer & 1);
        pb = eb;
        tma_2d_mc_e(dst, two, g * 128 + cr * 64, kc, fb);
        expect_tx_e(fb, m < 2 ? 16384 : 32768);
        PROFT(lane == 0 && layer == PL, 144 + m);
        if (m == ((layer & 1) ? XB2 : 0)) {
          expect_tx_e(bar + B_XOLD2, 16384);
          tma_2d_e(sb + XS * SLOT, tx, g * 128 + 64, m0, bar + B_XOLD2);
        }
      }
    };
    if (warp == 0) {
      cluster_wait();
      PROFT(lane == 0, 125);
#pragma unroll 1
      for (int layer = 0; layer < NLAYERS; ++layer) {
        const CUtensorMap* tx = layer == 0 ? &tm_x0 : &tm_x;
        const CUtensorMap* tw = (layer & 1) ? &tm_wB : &tm_wA;
        uint32_t s = layer == 0, u = 0, ready = layer == 0 ? 0xFFFFu : 0u;
#pragma unroll 1
        for (int i = s; i < 16; ++i) {
          const int kb = layer == 0 ? kblock0(i, g) : wo_kblock(i, g), kc = kb * 64;
          const uint32_t fb = bar + B_FULLS + s * 8;
          const uint32_t kd = sb + (((QK >> (4 * s)) & 15) + cr) * SLOT, qd = sb + ((QQ >> (4 * s)) & 15) * SLOT + cr * 8192;
          const uint32_t need = 1u << kb;
          const bool ext = i >= 2 || layer == 0, early = ext && (ready & need) == need;
          mbar_wait_u(bar + B_EMPTYS + s * 8, (u + (s ? layer : 0) + 1) & 1);
          if (early) tma_2d_e(sb + ((QA >> (4 * s)) & 15) * SLOT, tx, kc, m0, fb);
          tma_2d_mc_e(kd, tw, 1024 + cr * 1024 + g * 128, kc, fb);
          tma_2d_mc_e(kd + 8192, tw, 1024 + cr * 1024 + g * 128 + 64, kc, fb);
          tma_2d_mc_e(qd, tw, g * 128 + cr * 64, kc, fb);
          expect_tx_e(fb, ext ? 65536 : 49152);
          PROFT(lane == 0 && layer == 0 && i == 1, 31);
          if (layer == 0 && g >= NCOM && i == XPF + (((g - NCOM) * XPM) >> 2)) {
            if (i <= 2) mbar_wait_u(bar + B_FULLS, 0);
            tma_pf_e(&tm_x0, g * 128, m0);
            tma_pf_e(&tm_x0, g * 128 + 64, m0);
          }
          if (layer < 2 && i >= PFS) {
            const int j = i - PFS;
            if (j < 2) tma_pf_e(layer ? &tm_woB : &tm_woA, g * 128 + j * 64, rb * 64);
            else if (j < 8 && layer == 0) tma_pf_e(&tm_wB, ((j >> 1) - 1) * 1024 + g * 128 + (j & 1) * 64, rb * 64);
          }
          if (ext && !early) {
            PROFT(i == 2 && lane == 0, 64 + layer * 16 + 0);
            src_wait_tma(g_xf + rb * 32, xbase + layer + 1, need, ready, lane, fb, 0);
            PROFT(i == 2 && lane == 0, 64 + layer * 16 + 1);
            fence_async_all();
            tma_2d_e(sb + ((QA >> (4 * s)) & 15) * SLOT, tx, kc, m0, fb);
          }
          if (++s == 3) { s = 0; ++u; }
        }
        if (layer == 0) xbase = ld_relaxed(&g_epoch) * NLAYERS;
        if (PG & 1) mbar_wait_u(bar + B_OH1, layer & 1);
        if (PG & 4) mbar_wait_u(bar + B_E3, layer & 1);
        wo_a(layer, 2);
      }
    } else {
      if (warp >= 2) {
        const int h2 = threadIdx.x - 64;
        if (h2 < 16) sts_f(sb + SM_RS + h2 * 4, 0.f);
        if (h2 == 0) sts_f(sb + SM_EPOCH, __uint_as_float(epoch));
        if (h2 < 16) sts_f(bar + B_FLG + h2 * 4, __uint_as_float(xbase));
        mbar_wait_u(bar + B_FULLS, 0);
        colsum(&tm_wA, g_cs + (epoch & 1) * 6144, rb, g, warp - 2, 2, lane, warp == 2 ? sb + SM_SD : (sb + SM_BP + 1023u) & ~1023u, bar + B_CB + (warp - 2) * 8, 0);
#pragma unroll 1
        for (int i = h2; i < 320; i += 64) g_kv[(g * 16 + rb) * 320 + i] = make_uint4(0u, 0u, 0u, 0u);
        fence_async_all();
        nbar<5, 64>();
        if (h2 == 0) flag_add(&g_csflag[g].v);
        PROFT(h2 == 0, 242);
#pragma unroll 1
        for (int i = h2; i < 512; i += 256) {
          uint4 w[4];
#pragma unroll
          for (int j = 0; j < 4; ++j) w[j] = __ldg(reinterpret_cast<const uint4*>(wphi + (size_t)g * 4096) + i + j * 64);
#pragma unroll
          for (int j = 0; j < 4; ++j) sts128(sb + SM_WPHI + ((i >> 2) + j * 16) * 80 + (i & 3) * 16, w[j]);
        }
      }
      if (warp == 1) {
        if (lane >= 27) {
          const CUtensorMap* tm = lane == 27 ? &tm_o : lane == 28 ? &tm_wB : lane == 29 ? &tm_woA : lane == 30 ? &tm_woB : &tm_x;
          asm volatile("prefetch.tensormap [%0];" ::"l"(tm) : "memory");
        }
        __syncwarp();
        {
#pragma unroll 1
          for (int e = 0;; ++e) {
            if (e > 0 && e < NLAYERS) {
              mbar_wait_u(bar + B_XH0, (e - 1) & 1);
              flag_set_x(g_xf + rb * 32 + 2 * g, xbase + e + 1, UNS & 1);
            }
            mbar_wait_u(bar + B_XDONE, e & 1);
            PROFT(e < 4, 64 + e * 16 + 4);
            if (e == NLAYERS) {
              if (bid == 0) g_epoch = epoch + 1;
              break;
            }
            PROFT(e < 4, 64 + e * 16 + 5);
            flag_set(g_xf + rb * 32 + 2 * g + 1, xbase + e + 1);
            PROFT(e < 4, 64 + e * 16 + 7);
            if ((e & 1) == 0) {
#pragma unroll 1
              for (int hp = 0; hp < 2; ++hp) {
                uint4* kvl = g_kv + ((g * 2 + (e >> 1)) * 2 + hp) * 1280;
                mbar_wait_u(bar + B_KVDONE - hp * 32, (e >> 1) & 1);
                PROFT(e == PL, 243 + hp * 4);
                bulk_red_add_e(kvl + rb * 64, sb + (3 + hp) * SLOT + rb * 1024, 16384 - rb * 1024);
                if (rb) bulk_red_add_e(kvl, sb + (3 + hp) * SLOT, rb * 1024);
                bulk_red_add_e(kvl + 1024, sb + (6 + hp) * SLOT, 2048);
                bulk_red_add_e(kvl + 1152, sb + (6 + hp) * SLOT + 8192, 2048);
                bulk_commit();
                PROFT(e < 4, 64 + e * 16 + 6);
              }
              bulk_wait_read0();
              __syncwarp();
              if (lane < 2) release2(bar + B_E1);
              __syncwarp();
            }
            mbar_wait_u(bar + B_OH1, e & 1);
            PROFT(e == PL, 251);
            flag_set_x(g_of + rb * 32 + 2 * g, xbase + e + 1, UNS & 2);
            PROFT(e < 4, 64 + e * 16 + 9);
            mbar_wait_u(bar + B_ODONE, e & 1);
            PROFT(e < 4, 64 + e * 16 + 8);
            flag_set_x(g_of + rb * 32 + 2 * g + 1, xbase + e + 1, UNS & 4);
            PROFT(e < 4, 64 + e * 16 + 11);
          }
        }
      } else {
        const int h2 = threadIdx.x - 64;
        const float* cs = g_cs + (epoch & 1) * 6144;
#pragma unroll 1
        for (int layer = 0; layer < NLAYERS; ++layer) {
          if (warp == 2 && layer < 2) {
            if ((PG & 2) && layer) mbar_wait_u(bar + B_XH0, 0);
            if (lane == 0) flag_wait_t<CSLP>(&g_csflag[layer * 8 + g].v, (epoch + 1) * (16u + layer));
            __syncwarp();
            float4 a[3];
#pragma unroll
            for (int i = 0; i < 3; ++i) a[i] = __ldcg(reinterpret_cast<const float4*>(cs + layer * 3072 + g * 384) + i * 32 + lane);
#pragma unroll 1
            for (int i = 0; i < 3; ++i) {
              const float av[4] = {a[0].x, a[0].y, a[0].z, a[0].w};
              a[0] = a[1]; a[1] = a[2];
#pragma unroll
              for (int j = 0; j < 4; ++j) {
                const float c1 = bf16r(av[j]), c2 = bf16r(av[j] - c1), c3 = (av[j] - c1) - c2;
                sts128(sb + SM_BP + layer * 6144 + ((i * 32 + lane) * 4 + j) * 16, make_uint4(pack_bf16(c1, c2), pack_bf16(c3, 0.f), 0u, 0u));
              }
            }
            fence_async_smem();
            __syncwarp();
            if (lane == 0) mbar_arrive(bar + (layer ? B_CS2 : B_CS));
            PROFT(lane == 0, 64 + layer * 16 + 12);
            if (layer == 0) {
              uint4* hz = g_halo + (rb * 8 + g) * 1024;
#pragma unroll 2
              for (int i = lane; i < 1024; i += 32) hz[i] = make_uint4(0u, 0u, 0u, 0u);
              if (lane < 12) reinterpret_cast<float4*>(g_cs + ((epoch & 1) ^ 1) * 6144 + bid * 48)[lane] = make_float4(0.f, 0.f, 0.f, 0.f);
              g_stats[(2 + (lane >> 4)) * S_ + m0 + g * 16 + (lane & 15)] = make_float2(0.f, 0.f);
              __syncwarp();
              if (lane == 0) flag_add(&g_csflag[8 + g].v);
            }
          }
          if (warp == 3) {
            const bool hal = (layer & 1) && rb > 0;
            {
              uint32_t rdy = 0u;
              src_wait<256>(g_xf + rb * 32, xbase + layer + 1, 0xAAAAu, rdy, lane);
              rdy = 0u;
              if (hal) src_wait<256>(g_xf + (rb - 1) * 32, xbase + layer + 1, 0xAAAAu, rdy, lane);
            }
            float2 u[5];
            const float2* sp = g_stats + layer * S_ + m0 + lane;
#pragma unroll
            for (int i = 0; i < 4; ++i) u[i] = __ldcg(sp + i * 32);
            u[4] = __ldcg(hal ? sp - 16 : sp);
            if (layer == 3) g_stats[(lane >> 4) * S_ + m0 + g * 16 + (lane & 15)] = make_float2(0.f, 0.f);
#pragma unroll 1
            for (int i = 0; i < (hal ? 5 : 4); ++i) {
              const int r = i < 4 ? 16 + i * 32 + lane : lane;
              const float sum = u[0].x, sq = u[0].y;
              u[0] = u[1]; u[1] = u[2]; u[2] = u[3]; u[3] = u[4];
              const float mean = sum * (1.f / D_);
              const float var = fmaxf(fmaf(-sum, mean, sq) * (1.f / D_), 0.f);
              const float sd = bf16r(sqrtf(bf16r(bf16r(var) + 1e-5f)));
              sts_f(sb + SM_RS + r * 4, 1.f / sd);
              if (i < 4) {
                const float hm = -0.5f * bf16r(mean);
                const uint32_t s2 = pack_bf16(sd, sd);
                if (!(layer & 1)) sts128(sb + SM_SD + (r - 16) * 64 + ((r >> 1) & 3) * 16, make_uint4(s2, s2, s2, s2));
                sts128(sb + SM_AP + (r - 16) * 16, make_uint4(pack_bf16(hm, hm), pack_bf16(hm, 0.f), 0u, 0u));
              }
            }
            fence_async_smem();
            __syncwarp();
            if (lane == 0) mbar_arrive(bar + B_STAT);
            PROFT(lane == 0, 64 + layer * 16 + 14);
            wo_w(__shfl_sync(0xffffffffu, layer, 0));
          }
        }
      }
    }
    __syncwarp();
    asm volatile("barrier.cluster.arrive.relaxed.aligned;\nbarrier.cluster.wait.aligned;\n" ::: "memory");
  } else {
    if (warp == 5) {
      if (lane == 0) {
        mbar_init(bar + B_FULLS, 1);
        asm volatile("fence.mbarrier_init.release.cluster;" ::: "memory");
      }
      __syncwarp();
      expect_tx_e(bar + B_FULLS, 65536);
      tma_2d_e(sb + XS * SLOT, &tm_x0, 0, m0, bar + B_FULLS);
#pragma unroll
      for (int j = 0; j < 6; ++j)
        tma_2d_e(sb + (j < 4 ? j + 4 : j - 2) * 8192, &tm_wA, (j < 4 ? 1024 + (j >> 1) * 1024 : 0) + g * 128 + (j & 1) * 64, 0, bar + B_FULLS);
      PROFT(lane == 0, 241);
    }
    if (lane < 8 && warp != 5 && threadIdx.x != 128) {
      const int i = (warp - 4) * 8 + lane;
      mbar_init(bar + i * 8, i < 32 ? 1u << ((BAR_CNT >> (2 * i)) & 3) : i < 48 ? 1u : (i == 59 || i == 60 || i == 62) ? 16u : (i == 48 || i == 63) ? 8u : 4u);
      asm volatile("fence.mbarrier_init.release.cluster;" ::: "memory");
    }
    __syncwarp();
    asm volatile("barrier.cluster.arrive.relaxed.aligned;" ::: "memory");
    asm volatile("setmaxnreg.inc.sync.aligned.u32 232;");
    cluster_wait();
    PROFT(threadIdx.x == 128, 0);
    Ctx c; c.sb = sb; c.g = g; c.rb = rb; c.cu = warp - 4; c.out = out;
    consumer(c);
    asm volatile("bar.warp.sync 0xffffffff;\nbarrier.cluster.arrive.relaxed.aligned;\nbarrier.cluster.wait.aligned;\n" ::: "memory");
  }
}

typedef CUresult (*PFN_encodeTiled)(CUtensorMap*, CUtensorMapDataType, cuuint32_t, void*, const cuuint64_t*, const cuuint64_t*,
                                    const cuuint32_t*, const cuuint32_t*, CUtensorMapInterleave, CUtensorMapSwizzle,
                                    CUtensorMapL2promotion, CUtensorMapFloatOOBfill);

static CUtensorMap make_map(PFN_encodeTiled enc, const void* ptr, uint64_t cols, uint64_t rows, uint32_t box_c, uint32_t box_r, uint32_t nb = 1) {
  CUtensorMap m;
  cuuint64_t dims[3] = {nb > 1 ? box_c : cols, rows, cols / box_c};
  cuuint64_t strides[2] = {cols * 2, box_c * 2};
  cuuint32_t box[3] = {box_c, box_r, nb};
  cuuint32_t es[3] = {1, 1, 1};
  CUresult r = enc(&m, CU_TENSOR_MAP_DATA_TYPE_BFLOAT16, nb > 1 ? 3 : 2, const_cast<void*>(ptr), dims, strides, box, es, CU_TENSOR_MAP_INTERLEAVE_NONE,
      CU_TENSOR_MAP_SWIZZLE_128B, CU_TENSOR_MAP_L2_PROMOTION_L2_256B, CU_TENSOR_MAP_FLOAT_OOB_FILL_NONE);
  (void)r;
  return m;
}

extern "C" void kernel_launch(void* const* d_in, const int* in_sizes, int n_in, void* d_out, int out_size) {
  const bf16* A_x = (const bf16*)d_in[0];
  const bf16* A_wqkv = (const bf16*)d_in[1];
  const bf16* A_wphi = (const bf16*)d_in[2];
  const bf16* A_wo = (const bf16*)d_in[3];
  const bf16* B_wqkv = (const bf16*)d_in[5];
  const bf16* B_wo = (const bf16*)d_in[6];
  bf16* out = (bf16*)d_out;

  static PFN_encodeTiled enc = nullptr;
  static bf16 *p_x, *p_o;
  if (!enc) {
    void* fn = nullptr; cudaDriverEntryPointQueryResult qr;
    cudaGetDriverEntryPoint("cuTensorMapEncodeTiled", &fn, cudaEnableDefault, &qr);
    enc = (PFN_encodeTiled)fn;
    cudaGetSymbolAddress((void**)&p_x, g_x);
    cudaGetSymbolAddress((void**)&p_o, g_o);
    cudaFuncSetAttribute(mega_kernel, cudaFuncAttributeMaxDynamicSharedMemorySize, SM_TOTAL);
  }
  CUtensorMap tm_x0 = make_map(enc, A_x, 1024, 2048, 64, 128);
  CUtensorMap tm_x = make_map(enc, p_x, 1024, 2048, 64, 128);
  CUtensorMap tm_o = make_map(enc, p_o, 1024, 2048, 64, 128);
  CUtensorMap tm_wA = make_map(enc, A_wqkv, 3072, 1024, 64, 64);
  CUtensorMap tm_wB = make_map(enc, B_wqkv, 3072, 1024, 64, 64);
  CUtensorMap tm_woA = make_map(enc, A_wo, 1024, 1024, 64, 64);
  CUtensorMap tm_woB = make_map(enc, B_wo, 1024, 1024, 64, 64);
  mega_kernel<<<128 + NX, 384, SM_TOTAL, cudaStreamPerThread>>>(tm_x0, tm_x, tm_o, tm_wA, tm_wB, tm_woA, tm_woB,
                                                           B_wqkv, A_wphi, out);
}
```

```cpp
#include <cuda_runtime.h>
#include <cuda_bf16.h>
#include <cuda.h>
#include <stdint.h>

typedef __nv_bfloat16 bf16;

constexpr int S_ = 2048, D_ = 1024;

struct __align__(128) Flag { unsigned int v; unsigned int pad[31]; };
__device__ __align__(1024) bf16 g_x[S_ * D_];
__device__ __align__(1024) bf16 g_o[S_ * D_];
__device__ __align__(1024) uint4 g_halo[128 * 2 * 512];
__device__ __align__(1024) uint4 g_kv[8 * 2 * 2 * 1280];
__device__ __align__(1024) float2 g_stats[4 * S_];
__device__ __align__(1024) float g_cs[2 * 2 * 3072];
__device__ Flag g_csflag[16];
__device__ __align__(128) unsigned int g_xf[16 * 32], g_of[16 * 32];
__device__ unsigned int g_epoch, g_err;
#define PROFT(cond, idx) asm volatile("" ::: "memory")

__device__ __forceinline__ uint32_t smem_u32(const void* p) { return (uint32_t)__cvta_generic_to_shared(p); }
__device__ __forceinline__ void mbar_init(uint32_t bar, uint32_t count) {
  asm volatile("mbarrier.init.shared::cta.b64 [%0], %1;" ::"r"(bar), "r"(count) : "memory");
}
__device__ __forceinline__ void mbar_expect_tx(uint32_t bar, uint32_t bytes) {
  asm volatile("mbarrier.arrive.expect_tx.shared::cta.b64 _, [%0], %1;" ::"r"(bar), "r"(bytes) : "memory");
}
__device__ __forceinline__ void mbar_arrive(uint32_t bar) {
  asm volatile("mbarrier.arrive.shared::cta.b64 _, [%0];" ::"r"(bar) : "memory");
}
__device__ __forceinline__ bool mbar_try_wait(uint32_t bar, uint32_t parity) {
  uint32_t ok;
  asm volatile("{\n.reg .pred p;\nmbarrier.try_wait.parity.shared::cta.b64 p, [%1], %2;\nselp.b32 %0, 1, 0, p;\n}\n"
               : "=r"(ok) : "r"(bar), "r"(parity) : "memory");
  return ok != 0;
}
__device__ __forceinline__ bool mbar_test_wait(uint32_t bar, uint32_t parity) {
  uint32_t ok;
  asm volatile("{\n.reg .pred p;\nmbarrier.test_wait.parity.shared::cta.b64 p, [%1], %2;\nselp.b32 %0, 1, 0, p;\n}\n"
               : "=r"(ok) : "r"(bar), "r"(parity) : "memory");
  return ok != 0;
}
__device__ __forceinline__ uint64_t gtimer() {
  uint64_t t; asm volatile("mov.u64 %0, %globaltimer;" : "=l"(t)); return t;
}
__device__ __forceinline__ void mbar_wait(uint32_t bar, uint32_t parity) {
  uint32_t n = 0;
#pragma unroll 1
  while (!mbar_try_wait(bar, parity)) {
    if (++n > (1u << 22)) { g_err = 1u; break; }
  }
}
__device__ __forceinline__ unsigned int ld_acquire(const unsigned int* p) {
  unsigned int v; asm volatile("ld.acquire.gpu.global.u32 %0, [%1];" : "=r"(v) : "l"(p) : "memory"); return v;
}
__device__ __forceinline__ void flag_add(unsigned int* p) {
  asm volatile("red.release.gpu.global.add.u32 [%0], 1;" ::"l"(p) : "memory");
}
__device__ __forceinline__ void flag_set(unsigned int* p, unsigned int v) {
  asm volatile("st.release.gpu.global.u32 [%0], %1;" ::"l"(p), "r"(v) : "memory");
}
__device__ __forceinline__ void flag_set_x(unsigned int* p, unsigned int v, bool rlx) {
  if (rlx) asm volatile("st.relaxed.gpu.global.u32 [%0], %1;" ::"l"(p), "r"(v) : "memory"); else flag_set(p, v);
}
template <int SLEEP>
__device__ __forceinline__ void src_wait(const unsigned int* f, unsigned int target, uint32_t need, uint32_t& ready, int lane) {
  uint32_t n = 0;
#pragma unroll 1
  while ((ready & need) != need) {
    const unsigned int v = ld_acquire(f + (lane & 15));
    ready = __ballot_sync(0xffffffffu, (int)(v - target) >= 0);
    if (SLEEP) { if ((ready & need) != need) __nanosleep(SLEEP); }
    if (++n > (1u << 20)) { g_err = 3u; break; }
  }
  __syncwarp();
}
__device__ __forceinline__ unsigned int ld_relaxed(const unsigned int* p) {
  unsigned int v; asm volatile("ld.relaxed.gpu.global.u32 %0, [%1];" : "=r"(v) : "l"(p) : "memory"); return v;
}
__device__ __forceinline__ bool src_wait_tma(const unsigned int* f, unsigned int target, uint32_t need, uint32_t& ready, int lane, uint32_t eb, uint32_t par) {
  uint32_t n = 0;
  bool fr = false;
#pragma unroll 1
  while ((ready & need) != need) {
    const unsigned int v = ld_acquire(f + (lane & 15));
    fr = __all_sync(0xffffffffu, mbar_test_wait(eb, par));
    ready = __ballot_sync(0xffffffffu, (int)(v - target) >= 0);
    if (++n > (1u << 20)) { g_err = 3u; break; }
  }
  return fr;
}
__device__ __forceinline__ uint4 ld_relaxed4(const uint4* p) {
  uint4 v; asm volatile("ld.relaxed.gpu.global.v4.u32 {%0,%1,%2,%3}, [%4];" : "=r"(v.x), "=r"(v.y), "=r"(v.z), "=r"(v.w) : "l"(p) : "memory"); return v;
}
__device__ __forceinline__ void st_relaxed4(uint4* p, uint32_t a, uint32_t b, uint32_t c, uint32_t d) {
  asm volatile("st.relaxed.gpu.global.v4.u32 [%0], {%1,%2,%3,%4};" ::"l"(p), "r"(a), "r"(b), "r"(c), "r"(d) : "memory");
}
template <int SLEEP>
__device__ __forceinline__ void flag_wait_t(const unsigned int* p, unsigned int target) {
  uint32_t n = 0;
#pragma unroll 1
  while ((int)(ld_acquire(p) - target) < 0) {
    if (SLEEP) __nanosleep(SLEEP);
    if (++n > (1u << 20)) { g_err = 2u; break; }
  }
}
__device__ __forceinline__ void flag_wait(const unsigned int* p, unsigned int target) { flag_wait_t<0>(p, target); }
__device__ __forceinline__ void flag_wait_slow(const unsigned int* p, unsigned int target) { flag_wait_t<256>(p, target); }
__device__ __forceinline__ void tma_load_2d(uint32_t dst, const CUtensorMap* tm, int c0, int c1, uint32_t bar) {
  asm volatile("cp.async.bulk.tensor.2d.shared::cluster.global.mbarrier::complete_tx::bytes [%0], [%1, {%2, %3}], [%4];"
               ::"r"(dst), "l"(tm), "r"(c0), "r"(c1), "r"(bar) : "memory");
}
__device__ __forceinline__ void tma_load_2d_mc(uint32_t dst, const CUtensorMap* tm, int c0, int c1, uint32_t bar, uint16_t mask) {
  asm volatile("cp.async.bulk.tensor.2d.shared::cluster.global.mbarrier::complete_tx::bytes.multicast::cluster [%0], [%1, {%2, %3}], [%4], %5;"
               ::"r"(dst), "l"(tm), "r"(c0), "r"(c1), "r"(bar), "h"(mask) : "memory");
}
__device__ __forceinline__ void mbar_wait_u(uint32_t bar, uint32_t parity) {
  uint32_t n = 0;
#pragma unroll 1
  while (!__all_sync(0xffffffffu, mbar_try_wait(bar, parity))) {
    if (++n > (1u << 22)) { g_err = 1u; break; }
  }
}
__device__ __forceinline__ void expect_tx_e(uint32_t bar, uint32_t bytes) {
  asm volatile("{\n.reg .pred p;\nelect.sync _|p, 0xffffffff;\n@p mbarrier.arrive.expect_tx.shared::cta.b64 _, [%0], %1;\n}\n" ::"r"(bar), "r"(bytes) : "memory");
}
__device__ __forceinline__ void tma_2d_e(uint32_t dst, const CUtensorMap* tm, int c0, int c1, uint32_t bar) {
  asm volatile("{\n.reg .pred p;\nelect.sync _|p, 0xffffffff;\n"
               "@p cp.async.bulk.tensor.2d.shared::cluster.global.mbarrier::complete_tx::bytes [%0], [%1, {%2, %3}], [%4];\n}\n"
               ::"r"(dst), "l"(tm), "r"(c0), "r"(c1), "r"(bar) : "memory");
}
__device__ __forceinline__ void tma_2d_mc_e(uint32_t dst, const CUtensorMap* tm, int c0, int c1, uint32_t bar) {
  asm volatile("{\n.reg .pred p;\nelect.sync _|p, 0xffffffff;\n"
               "@p cp.async.bulk.tensor.2d.shared::cluster.global.mbarrier::complete_tx::bytes.multicast::cluster [%0], [%1, {%2, %3}], [%4], %5;\n}\n"
               ::"r"(dst), "l"(tm), "r"(c0), "r"(c1), "r"(bar), "h"((uint16_t)3) : "memory");
}
__device__ __forceinline__ void tma_pf_e(const CUtensorMap* tm, int c0, int c1) {
  asm volatile("{\n.reg .pred p;\nelect.sync _|p, 0xffffffff;\n"
               "@p cp.async.bulk.prefetch.tensor.2d.L2.global.tile [%0, {%1, %2}];\n}\n" ::"l"(tm), "r"(c0), "r"(c1) : "memory");
}
__device__ __forceinline__ void tma_2d_to_e(uint32_t dst, const CUtensorMap* tm, int c0, int c1, uint32_t bar, uint32_t mask) {
  asm volatile("{\n.reg .pred p;\nelect.sync _|p, 0xffffffff;\n"
               "@p cp.async.bulk.tensor.2d.shared::cluster.global.mbarrier::complete_tx::bytes.multicast::cluster [%0], [%1, {%2, %3}], [%4], %5;\n}\n"
               ::"r"(dst), "l"(tm), "r"(c0), "r"(c1), "r"(bar), "h"((uint16_t)mask) : "memory");
}
__device__ __forceinline__ void tma_3d_mc_e(uint32_t dst, const CUtensorMap* tm, int c1, int c2, uint32_t bar) {
  asm volatile("{\n.reg .pred p;\nelect.sync _|p, 0xffffffff;\n"
               "@p cp.async.bulk.tensor.3d.shared::cluster.global.mbarrier::complete_tx::bytes.multicast::cluster [%0], [%1, {%6, %2, %3}], [%4], %5;\n}\n"
               ::"r"(dst), "l"(tm), "r"(c1), "r"(c2), "r"(bar), "h"((uint16_t)3), "r"(0) : "memory");
}
__device__ __forceinline__ uint32_t poll_flags(const unsigned int* f, unsigned int target, int lane) {
  const unsigned int v = ld_acquire(f + (lane & 15));
  const uint32_t r = __ballot_sync(0xffffffffu, (int)(v - target) >= 0);
  __syncwarp();
  return r;
}
__device__ __forceinline__ void mbar_arrive_cluster(uint32_t local_bar, uint32_t rank) {
  asm volatile("{\n.reg .b32 ra;\nmapa.shared::cluster.u32 ra, %0, %1;\nmbarrier.arrive.shared::cluster.b64 _, [ra];\n}\n"
               ::"r"(local_bar), "r"(rank) : "memory");
}
__device__ __forceinline__ void release2(uint32_t bar) { mbar_arrive_cluster(bar, 0); mbar_arrive_cluster(bar, 1); }
__device__ __forceinline__ void tma_store_2d(const CUtensorMap* tm, uint32_t src, int c0, int c1) {
  asm volatile("cp.async.bulk.tensor.2d.global.shared::cta.bulk_group [%0, {%2, %3}], [%1];"
               ::"l"(tm), "r"(src), "r"(c0), "r"(c1) : "memory");
}
__device__ __forceinline__ void bulk_store(void* dst, uint32_t src, uint32_t bytes) {
  asm volatile("cp.async.bulk.global.shared::cta.bulk_group [%0], [%1], %2;" ::"l"(dst), "r"(src), "r"(bytes) : "memory");
}
__device__ __forceinline__ void bulk_load(uint32_t dst, const void* src, uint32_t bytes, uint32_t bar) {
  asm volatile("cp.async.bulk.shared::cluster.global.mbarrier::complete_tx::bytes [%0], [%1], %2, [%3];" ::"r"(dst), "l"(src), "r"(bytes), "r"(bar) : "memory");
}
__device__ __forceinline__ void bulk_red_add(void* dst, uint32_t src, uint32_t bytes) {
  asm volatile("cp.reduce.async.bulk.global.shared::cta.bulk_group.add.f32 [%0], [%1], %2;" ::"l"(dst), "r"(src), "r"(bytes) : "memory");
}
__device__ __forceinline__ void bulk_red_add_e(void* dst, uint32_t src, uint32_t bytes) {
  asm volatile("{\n.reg .pred p;\nelect.sync _|p, 0xffffffff;\n@p cp.reduce.async.bulk.global.shared::cta.bulk_group.add.f32 [%0], [%1], %2;\n}\n" ::"l"(dst), "r"(src), "r"(bytes) : "memory");
}
__device__ __forceinline__ void bulk_commit() { asm volatile("cp.async.bulk.commit_group;" ::: "memory"); }
__device__ __forceinline__ void bulk_wait_read0() { asm volatile("cp.async.bulk.wait_group.read 0;" ::: "memory"); }
__device__ __forceinline__ void bulk_wait0() { asm volatile("cp.async.bulk.wait_group 0;" ::: "memory"); }
__device__ __forceinline__ void fence_async_smem() { asm volatile("fence.proxy.async.shared::cta;" ::: "memory"); }
__device__ __forceinline__ void fence_async_all() { asm volatile("fence.proxy.async.global;" ::: "memory"); }
__device__ __forceinline__ void wgmma_fence() { asm volatile("wgmma.fence.sync.aligned;" ::: "memory"); }
__device__ __forceinline__ void wgmma_commit() { asm volatile("wgmma.commit_group.sync.aligned;" ::: "memory"); }
template <int N> __device__ __forceinline__ void wgmma_wait() { asm volatile("wgmma.wait_group.sync.aligned %0;" ::"n"(N) : "memory"); }
__device__ __forceinline__ void cluster_arrive() { asm volatile("barrier.cluster.arrive.release.aligned;" ::: "memory"); }
__device__ __forceinline__ void cluster_wait() { asm volatile("barrier.cluster.wait.acquire.aligned;" ::: "memory"); }
template <int ID, int N> __device__ __forceinline__ void nbar() { asm volatile("bar.sync %0, %1;" ::"n"(ID), "n"(N) : "memory"); }
__device__ __forceinline__ uint64_t make_desc(uint32_t addr, uint32_t lbo_bytes, uint32_t sbo_bytes) {
  uint64_t d = 0;
  d |= (uint64_t)((addr & 0x3FFFF) >> 4);
  d |= (uint64_t)((lbo_bytes >> 4) & 0x3FFF) << 16;
  d |= (uint64_t)((sbo_bytes >> 4) & 0x3FFF) << 32;
  d |= (uint64_t)1 << 62;
  return d;
}
__device__ __forceinline__ uint64_t desc64(uint32_t lo, uint32_t hi) { return (uint64_t)lo | ((uint64_t)hi << 32); }
__device__ __forceinline__ uint32_t pack_bf16(float lo, float hi) {
  uint32_t r; asm("cvt.rn.bf16x2.f32 %0, %1, %2;" : "=r"(r) : "f"(hi), "f"(lo)); return r;
}
__device__ __forceinline__ uint32_t mul_bf16x2(uint32_t a, uint32_t s, bool hi) {
  __nv_bfloat162 x = *reinterpret_cast<__nv_bfloat162*>(&a), y = *reinterpret_cast<__nv_bfloat162*>(&s);
  x = __hmul2(x, hi ? __high2bfloat162(y) : __low2bfloat162(y));
  return *reinterpret_cast<uint32_t*>(&x);
}
__device__ __forceinline__ float bf16r(float x) { return __bfloat162float(__float2bfloat16_rn(x)); }
__device__ __forceinline__ float bf_lo(uint32_t u) { return __uint_as_float(u << 16); }
__device__ __forceinline__ float bf_hi(uint32_t u) { return __uint_as_float(u & 0xFFFF0000u); }
__device__ __forceinline__ float ex2(float x) { float r; asm("ex2.approx.ftz.f32 %0, %1;" : "=f"(r) : "f"(x)); return r; }
__device__ __forceinline__ float rcp(float x) { float r; asm("rcp.approx.ftz.f32 %0, %1;" : "=f"(r) : "f"(x)); return r; }
__device__ __forceinline__ void mma_bf16(float (&d)[4], uint32_t a0, uint32_t a1, uint32_t a2, uint32_t a3, uint32_t b0, uint32_t b1) {
  asm("mma.sync.aligned.m16n8k16.row.col.f32.bf16.bf16.f32 {%0,%1,%2,%3}, {%4,%5,%6,%7}, {%8,%9}, {%0,%1,%2,%3};"
               : "+f"(d[0]), "+f"(d[1]), "+f"(d[2]), "+f"(d[3]) : "r"(a0), "r"(a1), "r"(a2), "r"(a3), "r"(b0), "r"(b1));
}
__device__ __forceinline__ void ldsm_x4(uint32_t& r0, uint32_t& r1, uint32_t& r2, uint32_t& r3, uint32_t addr) {
  asm volatile("ldmatrix.sync.aligned.m8n8.x4.shared.b16 {%0,%1,%2,%3}, [%4];"
               : "=r"(r0), "=r"(r1), "=r"(r2), "=r"(r3) : "r"(addr) : "memory");
}
__device__ __forceinline__ void ldsm_x4_t(uint32_t& r0, uint32_t& r1, uint32_t& r2, uint32_t& r3, uint32_t addr) {
  asm volatile("ldmatrix.sync.aligned.m8n8.x4.trans.shared.b16 {%0,%1,%2,%3}, [%4];"
               : "=r"(r0), "=r"(r1), "=r"(r2), "=r"(r3) : "r"(addr) : "memory");
}
__device__ __forceinline__ void ldsm_x2_t(uint32_t& r0, uint32_t& r1, uint32_t addr) {
  asm volatile("ldmatrix.sync.aligned.m8n8.x2.trans.shared.b16 {%0,%1}, [%2];"
               : "=r"(r0), "=r"(r1) : "r"(addr) : "memory");
}
__device__ __forceinline__ void stsm_x4(uint32_t addr, uint32_t r0, uint32_t r1, uint32_t r2, uint32_t r3) {
  asm volatile("stmatrix.sync.aligned.m8n8.x4.shared.b16 [%0], {%1,%2,%3,%4};"
               ::"r"(addr), "r"(r0), "r"(r1), "r"(r2), "r"(r3) : "memory");
}
__device__ __forceinline__ void stsm_x4_p(bool on, uint32_t addr, uint32_t r0, uint32_t r1, uint32_t r2, uint32_t r3) {
  asm volatile("{\n.reg .pred p;\nsetp.ne.b32 p, %5, 0;\n@p stmatrix.sync.aligned.m8n8.x4.shared.b16 [%0], {%1,%2,%3,%4};\n}\n"
               ::"r"(addr), "r"(r0), "r"(r1), "r"(r2), "r"(r3), "r"((int)on) : "memory");
}
__device__ __forceinline__ float2 lds_f2(uint32_t addr) {
  float2 v; asm volatile("ld.shared.v2.f32 {%0,%1}, [%2];" : "=f"(v.x), "=f"(v.y) : "r"(addr) : "memory"); return v;
}
__device__ __forceinline__ uint4 lds128(uint32_t addr) {
  uint4 v; asm volatile("ld.shared.v4.b32 {%0,%1,%2,%3}, [%4];" : "=r"(v.x), "=r"(v.y), "=r"(v.z), "=r"(v.w) : "r"(addr) : "memory"); return v;
}
__device__ __forceinline__ void sts128(uint32_t addr, uint4 v) {
  asm volatile("st.shared.v4.b32 [%0], {%1,%2,%3,%4};" ::"r"(addr), "r"(v.x), "r"(v.y), "r"(v.z), "r"(v.w) : "memory");
}
__device__ __forceinline__ float lds_f(uint32_t addr) {
  float v; asm volatile("ld.shared.f32 %0, [%1];" : "=f"(v) : "r"(addr) : "memory"); return v;
}
__device__ __forceinline__ uint32_t lds_vol(uint32_t addr) {
  uint32_t v; asm volatile("ld.volatile.shared.u32 %0, [%1];" : "=r"(v) : "r"(addr) : "memory"); return v;
}
__device__ __forceinline__ void sts16(uint32_t addr, uint32_t v) {
  asm volatile("st.shared.u16 [%0], %1;" ::"r"(addr), "h"((unsigned short)v) : "memory");
}
__device__ __forceinline__ void nbar_dyn(int id, int n) { asm volatile("bar.sync %0, %1;" ::"r"(id), "r"(n) : "memory"); }
__device__ __forceinline__ uint64_t make_desc_ns(uint32_t addr, uint32_t lbo_bytes, uint32_t sbo_bytes) {
  return (uint64_t)((addr & 0x3FFFF) >> 4) | ((uint64_t)(lbo_bytes >> 4) << 16) | ((uint64_t)(sbo_bytes >> 4) << 32);
}
__device__ __forceinline__ void sts_f(uint32_t addr, float v) { asm volatile("st.shared.f32 [%0], %1;" ::"r"(addr), "f"(v) : "memory"); }
__device__ __forceinline__ void sts64(uint32_t addr, uint32_t a, uint32_t b) {
  asm volatile("st.shared.v2.b32 [%0], {%1,%2};" ::"r"(addr), "r"(a), "r"(b) : "memory");
}
__device__ __forceinline__ void sts_f2(uint32_t addr, float a, float b) {
  asm volatile("st.shared.v2.f32 [%0], {%1,%2};" ::"r"(addr), "f"(a), "f"(b) : "memory");
}
__device__ __forceinline__ void red_add2(float* p, float a, float b) {
  asm volatile("red.global.add.v2.f32 [%0], {%1,%2};" ::"l"(p), "f"(a), "f"(b) : "memory");
}
__device__ __forceinline__ void red_add4(float* p, float a, float b, float c, float d) {
  asm volatile("red.global.add.v4.f32 [%0], {%1,%2,%3,%4};" ::"l"(p), "f"(a), "f"(b), "f"(c), "f"(d) : "memory");
}
__device__ __forceinline__ void red_add1(float* p, float a) {
  asm volatile("red.global.add.f32 [%0], %1;" ::"l"(p), "f"(a) : "memory");
}
__device__ __forceinline__ void l2_prefetch(const void* p, uint32_t bytes) {
  asm volatile("cp.async.bulk.prefetch.L2.global [%0], %1;" ::"l"(p), "r"(bytes) : "memory");
}

__device__ __forceinline__ void wgmma_n256(float (&d)[192], uint64_t da, uint64_t db, int scale_d) {
  asm volatile("{\n.reg .pred p;\nsetp.ne.b32 p, %130, 0;\n"
    "wgmma.mma_async.sync.aligned.m64n256k16.f32.bf16.bf16 {%0, %1, %2, %3, %4, %5, %6, %7, %8, %9, %10, %11, %12, %13, %14, %15, %16, %17, %18, %19, %20, %21, %22, %23, %24, %25, %26, %27, %28, %29, %30, %31, %32, %33, %34, %35, %36, %37, %38, %39, %40, %41, %42, %43, %44, %45, %46, %47, %48, %49, %50, %51, %52, %53, %54, %55, %56, %57, %58, %59, %60, %61, %62, %63, %64, %65, %66, %67, %68, %69, %70, %71, %72, %73, %74, %75, %76, %77, %78, %79, %80, %81, %82, %83, %84, %85, %86, %87, %88, %89, %90, %91, %92, %93, %94, %95, %96, %97, %98, %99, %100, %101, %102, %103, %104, %105, %106, %107, %108, %109, %110, %111, %112, %113, %114, %115, %116, %117, %118, %119, %120, %121, %122, %123, %124, %125, %126, %127}, %128, %129, p, 1, 1, 0, 1;\n}\n"
    : "+f"(d[0]), "+f"(d[1]), "+f"(d[2]), "+f"(d[3]), "+f"(d[4]), "+f"(d[5]), "+f"(d[6]), "+f"(d[7]), "+f"(d[8]), "+f"(d[9]), "+f"(d[10]), "+f"(d[11]), "+f"(d[12]), "+f"(d[13]), "+f"(d[14]), "+f"(d[15]), "+f"(d[16]), "+f"(d[17]), "+f"(d[18]), "+f"(d[19]), "+f"(d[20]), "+f"(d[21]), "+f"(d[22]), "+f"(d[23]), "+f"(d[24]), "+f"(d[25]), "+f"(d[26]), "+f"(d[27]), "+f"(d[28]), "+f"(d[29]), "+f"(d[30]), "+f"(d[31]), "+f"(d[32]), "+f"(d[33]), "+f"(d[34]), "+f"(d[35]), "+f"(d[36]), "+f"(d[37]), "+f"(d[38]), "+f"(d[39]), "+f"(d[40]), "+f"(d[41]), "+f"(d[42]), "+f"(d[43]), "+f"(d[44]), "+f"(d[45]), "+f"(d[46]), "+f"(d[47]), "+f"(d[48]), "+f"(d[49]), "+f"(d[50]), "+f"(d[51]), "+f"(d[52]), "+f"(d[53]), "+f"(d[54]), "+f"(d[55]), "+f"(d[56]), "+f"(d[57]), "+f"(d[58]), "+f"(d[59]), "+f"(d[60]), "+f"(d[61]), "+f"(d[62]), "+f"(d[63]), "+f"(d[64]), "+f"(d[65]), "+f"(d[66]), "+f"(d[67]), "+f"(d[68]), "+f"(d[69]), "+f"(d[70]), "+f"(d[71]), "+f"(d[72]), "+f"(d[73]), "+f"(d[74]), "+f"(d[75]), "+f"(d[76]), "+f"(d[77]), "+f"(d[78]), "+f"(d[79]), "+f"(d[80]), "+f"(d[81]), "+f"(d[82]), "+f"(d[83]), "+f"(d[84]), "+f"(d[85]), "+f"(d[86]), "+f"(d[87]), "+f"(d[88]), "+f"(d[89]), "+f"(d[90]), "+f"(d[91]), "+f"(d[92]), "+f"(d[93]), "+f"(d[94]), "+f"(d[95]), "+f"(d[96]), "+f"(d[97]), "+f"(d[98]), "+f"(d[99]), "+f"(d[100]), "+f"(d[101]), "+f"(d[102]), "+f"(d[103]), "+f"(d[104]), "+f"(d[105]), "+f"(d[106]), "+f"(d[107]), "+f"(d[108]), "+f"(d[109]), "+f"(d[110]), "+f"(d[111]), "+f"(d[112]), "+f"(d[113]), "+f"(d[114]), "+f"(d[115]), "+f"(d[116]), "+f"(d[117]), "+f"(d[118]), "+f"(d[119]), "+f"(d[120]), "+f"(d[121]), "+f"(d[122]), "+f"(d[123]), "+f"(d[124]), "+f"(d[125]), "+f"(d[126]), "+f"(d[127])
    : "l"(da), "l"(db), "r"(scale_d));
}
__device__ __forceinline__ void wgmma_n128(float (&d)[192], uint64_t da, uint64_t db, int scale_d) {
  asm volatile("{\n.reg .pred p;\nsetp.ne.b32 p, %66, 0;\n"
    "wgmma.mma_async.sync.aligned.m64n128k16.f32.bf16.bf16 {%0, %1, %2, %3, %4, %5, %6, %7, %8, %9, %10, %11, %12, %13, %14, %15, %16, %17, %18, %19, %20, %21, %22, %23, %24, %25, %26, %27, %28, %29, %30, %31, %32, %33, %34, %35, %36, %37, %38, %39, %40, %41, %42, %43, %44, %45, %46, %47, %48, %49, %50, %51, %52, %53, %54, %55, %56, %57, %58, %59, %60, %61, %62, %63}, %64, %65, p, 1, 1, 0, 1;\n}\n"
    : "+f"(d[128]), "+f"(d[129]), "+f"(d[130]), "+f"(d[131]), "+f"(d[132]), "+f"(d[133]), "+f"(d[134]), "+f"(d[135]), "+f"(d[136]), "+f"(d[137]), "+f"(d[138]), "+f"(d[139]), "+f"(d[140]), "+f"(d[141]), "+f"(d[142]), "+f"(d[143]), "+f"(d[144]), "+f"(d[145]), "+f"(d[146]), "+f"(d[147]), "+f"(d[148]), "+f"(d[149]), "+f"(d[150]), "+f"(d[151]), "+f"(d[152]), "+f"(d[153]), "+f"(d[154]), "+f"(d[155]), "+f"(d[156]), "+f"(d[157]), "+f"(d[158]), "+f"(d[159]), "+f"(d[160]), "+f"(d[161]), "+f"(d[162]), "+f"(d[163]), "+f"(d[164]), "+f"(d[165]), "+f"(d[166]), "+f"(d[167]), "+f"(d[168]), "+f"(d[169]), "+f"(d[170]), "+f"(d[171]), "+f"(d[172]), "+f"(d[173]), "+f"(d[174]), "+f"(d[175]), "+f"(d[176]), "+f"(d[177]), "+f"(d[178]), "+f"(d[179]), "+f"(d[180]), "+f"(d[181]), "+f"(d[182]), "+f"(d[183]), "+f"(d[184]), "+f"(d[185]), "+f"(d[186]), "+f"(d[187]), "+f"(d[188]), "+f"(d[189]), "+f"(d[190]), "+f"(d[191])
    : "l"(da), "l"(db), "r"(scale_d));
}
__device__ __forceinline__ void wgmma_n256_k(float (&d)[192], uint64_t da, uint64_t db, int scale_d) {
  asm volatile("{\n.reg .pred p;\nsetp.ne.b32 p, %130, 0;\n"
    "wgmma.mma_async.sync.aligned.m64n256k16.f32.bf16.bf16 {%0, %1, %2, %3, %4, %5, %6, %7, %8, %9, %10, %11, %12, %13, %14, %15, %16, %17, %18, %19, %20, %21, %22, %23, %24, %25, %26, %27, %28, %29, %30, %31, %32, %33, %34, %35, %36, %37, %38, %39, %40, %41, %42, %43, %44, %45, %46, %47, %48, %49, %50, %51, %52, %53, %54, %55, %56, %57, %58, %59, %60, %61, %62, %63, %64, %65, %66, %67, %68, %69, %70, %71, %72, %73, %74, %75, %76, %77, %78, %79, %80, %81, %82, %83, %84, %85, %86, %87, %88, %89, %90, %91, %92, %93, %94, %95, %96, %97, %98, %99, %100, %101, %102, %103, %104, %105, %106, %107, %108, %109, %110, %111, %112, %113, %114, %115, %116, %117, %118, %119, %120, %121, %122, %123, %124, %125, %126, %127}, %128, %129, p, 1, 1, 0, 0;\n}\n"
    : "+f"(d[0]), "+f"(d[1]), "+f"(d[2]), "+f"(d[3]), "+f"(d[4]), "+f"(d[5]), "+f"(d[6]), "+f"(d[7]), "+f"(d[8]), "+f"(d[9]), "+f"(d[10]), "+f"(d[11]), "+f"(d[12]), "+f"(d[13]), "+f"(d[14]), "+f"(d[15]), "+f"(d[16]), "+f"(d[17]), "+f"(d[18]), "+f"(d[19]), "+f"(d[20]), "+f"(d[21]), "+f"(d[22]), "+f"(d[23]), "+f"(d[24]), "+f"(d[25]), "+f"(d[26]), "+f"(d[27]), "+f"(d[28]), "+f"(d[29]), "+f"(d[30]), "+f"(d[31]), "+f"(d[32]), "+f"(d[33]), "+f"(d[34]), "+f"(d[35]), "+f"(d[36]), "+f"(d[37]), "+f"(d[38]), "+f"(d[39]), "+f"(d[40]), "+f"(d[41]), "+f"(d[42]), "+f"(d[43]), "+f"(d[44]), "+f"(d[45]), "+f"(d[46]), "+f"(d[47]), "+f"(d[48]), "+f"(d[49]), "+f"(d[50]), "+f"(d[51]), "+f"(d[52]), "+f"(d[53]), "+f"(d[54]), "+f"(d[55]), "+f"(d[56]), "+f"(d[57]), "+f"(d[58]), "+f"(d[59]), "+f"(d[60]), "+f"(d[61]), "+f"(d[62]), "+f"(d[63]), "+f"(d[64]), "+f"(d[65]), "+f"(d[66]), "+f"(d[67]), "+f"(d[68]), "+f"(d[69]), "+f"(d[70]), "+f"(d[71]), "+f"(d[72]), "+f"(d[73]), "+f"(d[74]), "+f"(d[75]), "+f"(d[76]), "+f"(d[77]), "+f"(d[78]), "+f"(d[79]), "+f"(d[80]), "+f"(d[81]), "+f"(d[82]), "+f"(d[83]), "+f"(d[84]), "+f"(d[85]), "+f"(d[86]), "+f"(d[87]), "+f"(d[88]), "+f"(d[89]), "+f"(d[90]), "+f"(d[91]), "+f"(d[92]), "+f"(d[93]), "+f"(d[94]), "+f"(d[95]), "+f"(d[96]), "+f"(d[97]), "+f"(d[98]), "+f"(d[99]), "+f"(d[100]), "+f"(d[101]), "+f"(d[102]), "+f"(d[103]), "+f"(d[104]), "+f"(d[105]), "+f"(d[106]), "+f"(d[107]), "+f"(d[108]), "+f"(d[109]), "+f"(d[110]), "+f"(d[111]), "+f"(d[112]), "+f"(d[113]), "+f"(d[114]), "+f"(d[115]), "+f"(d[116]), "+f"(d[117]), "+f"(d[118]), "+f"(d[119]), "+f"(d[120]), "+f"(d[121]), "+f"(d[122]), "+f"(d[123]), "+f"(d[124]), "+f"(d[125]), "+f"(d[126]), "+f"(d[127])
    : "l"(da), "l"(db), "r"(scale_d));
}
__device__ __forceinline__ void wgmma_n128_k(float (&d)[192], uint64_t da, uint64_t db, int scale_d) {
  asm volatile("{\n.reg .pred p;\nsetp.ne.b32 p, %66, 0;\n"
    "wgmma.mma_async.sync.aligned.m64n128k16.f32.bf16.bf16 {%0, %1, %2, %3, %4, %5, %6, %7, %8, %9, %10, %11, %12, %13, %14, %15, %16, %17, %18, %19, %20, %21, %22, %23, %24, %25, %26, %27, %28, %29, %30, %31, %32, %33, %34, %35, %36, %37, %38, %39, %40, %41, %42, %43, %44, %45, %46, %47, %48, %49, %50, %51, %52, %53, %54, %55, %56, %57, %58, %59, %60, %61, %62, %63}, %64, %65, p, 1, 1, 0, 0;\n}\n"
    : "+f"(d[128]), "+f"(d[129]), "+f"(d[130]), "+f"(d[131]), "+f"(d[132]), "+f"(d[133]), "+f"(d[134]), "+f"(d[135]), "+f"(d[136]), "+f"(d[137]), "+f"(d[138]), "+f"(d[139]), "+f"(d[140]), "+f"(d[141]), "+f"(d[142]), "+f"(d[143]), "+f"(d[144]), "+f"(d[145]), "+f"(d[146]), "+f"(d[147]), "+f"(d[148]), "+f"(d[149]), "+f"(d[150]), "+f"(d[151]), "+f"(d[152]), "+f"(d[153]), "+f"(d[154]), "+f"(d[155]), "+f"(d[156]), "+f"(d[157]), "+f"(d[158]), "+f"(d[159]), "+f"(d[160]), "+f"(d[161]), "+f"(d[162]), "+f"(d[163]), "+f"(d[164]), "+f"(d[165]), "+f"(d[166]), "+f"(d[167]), "+f"(d[168]), "+f"(d[169]), "+f"(d[170]), "+f"(d[171]), "+f"(d[172]), "+f"(d[173]), "+f"(d[174]), "+f"(d[175]), "+f"(d[176]), "+f"(d[177]), "+f"(d[178]), "+f"(d[179]), "+f"(d[180]), "+f"(d[181]), "+f"(d[182]), "+f"(d[183]), "+f"(d[184]), "+f"(d[185]), "+f"(d[186]), "+f"(d[187]), "+f"(d[188]), "+f"(d[189]), "+f"(d[190]), "+f"(d[191])
    : "l"(da), "l"(db), "r"(scale_d));
}
__device__ __forceinline__ void wgmma_n40_tt(float (&d)[20], uint64_t da, uint64_t db, int scale_d) {
  asm volatile("{\n.reg .pred p;\nsetp.ne.b32 p, %22, 0;\n"
    "wgmma.mma_async.sync.aligned.m64n40k16.f32.bf16.bf16 {%0, %1, %2, %3, %4, %5, %6, %7, %8, %9, %10, %11, %12, %13, %14, %15, %16, %17, %18, %19}, %20, %21, p, 1, 1, 1, 1;\n}\n"
    : "+f"(d[0]), "+f"(d[1]), "+f"(d[2]), "+f"(d[3]), "+f"(d[4]), "+f"(d[5]), "+f"(d[6]), "+f"(d[7]), "+f"(d[8]), "+f"(d[9]), "+f"(d[10]), "+f"(d[11]), "+f"(d[12]), "+f"(d[13]), "+f"(d[14]), "+f"(d[15]), "+f"(d[16]), "+f"(d[17]), "+f"(d[18]), "+f"(d[19])
    : "l"(da), "l"(db), "r"(scale_d));
}
__device__ __forceinline__ void wgmma_n40_rs(float (&d)[20], const uint32_t (&a)[4], uint64_t db, int scale_d) {
  asm volatile("{\n.reg .pred p;\nsetp.ne.b32 p, %25, 0;\n"
    "wgmma.mma_async.sync.aligned.m64n40k16.f32.bf16.bf16 {%0, %1, %2, %3, %4, %5, %6, %7, %8, %9, %10, %11, %12, %13, %14, %15, %16, %17, %18, %19}, {%20, %21, %22, %23}, %24, p, 1, 1, 1;\n}\n"
    : "+f"(d[0]), "+f"(d[1]), "+f"(d[2]), "+f"(d[3]), "+f"(d[4]), "+f"(d[5]), "+f"(d[6]), "+f"(d[7]), "+f"(d[8]), "+f"(d[9]), "+f"(d[10]), "+f"(d[11]), "+f"(d[12]), "+f"(d[13]), "+f"(d[14]), "+f"(d[15]), "+f"(d[16]), "+f"(d[17]), "+f"(d[18]), "+f"(d[19])
    : "r"(a[0]), "r"(a[1]), "r"(a[2]), "r"(a[3]), "l"(db), "r"(scale_d));
}
__device__ __forceinline__ void wgmma_n256_0(float (&d)[192], uint64_t da, uint64_t db) {
  asm volatile("{\n.reg .pred p;\nsetp.ne.b32 p, 0, 0;\n"
    "wgmma.mma_async.sync.aligned.m64n256k16.f32.bf16.bf16 {%0, %1, %2, %3, %4, %5, %6, %7, %8, %9, %10, %11, %12, %13, %14, %15, %16, %17, %18, %19, %20, %21, %22, %23, %24, %25, %26, %27, %28, %29, %30, %31, %32, %33, %34, %35, %36, %37, %38, %39, %40, %41, %42, %43, %44, %45, %46, %47, %48, %49, %50, %51, %52, %53, %54, %55, %56, %57, %58, %59, %60, %61, %62, %63, %64, %65, %66, %67, %68, %69, %70, %71, %72, %73, %74, %75, %76, %77, %78, %79, %80, %81, %82, %83, %84, %85, %86, %87, %88, %89, %90, %91, %92, %93, %94, %95, %96, %97, %98, %99, %100, %101, %102, %103, %104, %105, %106, %107, %108, %109, %110, %111, %112, %113, %114, %115, %116, %117, %118, %119, %120, %121, %122, %123, %124, %125, %126, %127}, %128, %129, p, 1, 1, 0, 1;\n}\n"
    : "=f"(d[0]), "=f"(d[1]), "=f"(d[2]), "=f"(d[3]), "=f"(d[4]), "=f"(d[5]), "=f"(d[6]), "=f"(d[7]), "=f"(d[8]), "=f"(d[9]), "=f"(d[10]), "=f"(d[11]), "=f"(d[12]), "=f"(d[13]), "=f"(d[14]), "=f"(d[15]), "=f"(d[16]), "=f"(d[17]), "=f"(d[18]), "=f"(d[19]), "=f"(d[20]), "=f"(d[21]), "=f"(d[22]), "=f"(d[23]), "=f"(d[24]), "=f"(d[25]), "=f"(d[26]), "=f"(d[27]), "=f"(d[28]), "=f"(d[29]), "=f"(d[30]), "=f"(d[31]), "=f"(d[32]), "=f"(d[33]), "=f"(d[34]), "=f"(d[35]), "=f"(d[36]), "=f"(d[37]), "=f"(d[38]), "=f"(d[39]), "=f"(d[40]), "=f"(d[41]), "=f"(d[42]), "=f"(d[43]), "=f"(d[44]), "=f"(d[45]), "=f"(d[46]), "=f"(d[47]), "=f"(d[48]), "=f"(d[49]), "=f"(d[50]), "=f"(d[51]), "=f"(d[52]), "=f"(d[53]), "=f"(d[54]), "=f"(d[55]), "=f"(d[56]), "=f"(d[57]), "=f"(d[58]), "=f"(d[59]), "=f"(d[60]), "=f"(d[61]), "=f"(d[62]), "=f"(d[63]), "=f"(d[64]), "=f"(d[65]), "=f"(d[66]), "=f"(d[67]), "=f"(d[68]), "=f"(d[69]), "=f"(d[70]), "=f"(d[71]), "=f"(d[72]), "=f"(d[73]), "=f"(d[74]), "=f"(d[75]), "=f"(d[76]), "=f"(d[77]), "=f"(d[78]), "=f"(d[79]), "=f"(d[80]), "=f"(d[81]), "=f"(d[82]), "=f"(d[83]), "=f"(d[84]), "=f"(d[85]), "=f"(d[86]), "=f"(d[87]), "=f"(d[88]), "=f"(d[89]), "=f"(d[90]), "=f"(d[91]), "=f"(d[92]), "=f"(d[93]), "=f"(d[94]), "=f"(d[95]), "=f"(d[96]), "=f"(d[97]), "=f"(d[98]), "=f"(d[99]), "=f"(d[100]), "=f"(d[101]), "=f"(d[102]), "=f"(d[103]), "=f"(d[104]), "=f"(d[105]), "=f"(d[106]), "=f"(d[107]), "=f"(d[108]), "=f"(d[109]), "=f"(d[110]), "=f"(d[111]), "=f"(d[112]), "=f"(d[113]), "=f"(d[114]), "=f"(d[115]), "=f"(d[116]), "=f"(d[117]), "=f"(d[118]), "=f"(d[119]), "=f"(d[120]), "=f"(d[121]), "=f"(d[122]), "=f"(d[123]), "=f"(d[124]), "=f"(d[125]), "=f"(d[126]), "=f"(d[127])
    : "l"(da), "l"(db));
}
__device__ __forceinline__ void wgmma_n128_0(float (&d)[192], uint64_t da, uint64_t db) {
  asm volatile("{\n.reg .pred p;\nsetp.ne.b32 p, 0, 0;\n"
    "wgmma.mma_async.sync.aligned.m64n128k16.f32.bf16.bf16 {%0, %1, %2, %3, %4, %5, %6, %7, %8, %9, %10, %11, %12, %13, %14, %15, %16, %17, %18, %19, %20, %21, %22, %23, %24, %25, %26, %27, %28, %29, %30, %31, %32, %33, %34, %35, %36, %37, %38, %39, %40, %41, %42, %43, %44, %45, %46, %47, %48, %49, %50, %51, %52, %53, %54, %55, %56, %57, %58, %59, %60, %61, %62, %63}, %64, %65, p, 1, 1, 0, 1;\n}\n"
    : "=f"(d[128]), "=f"(d[129]), "=f"(d[130]), "=f"(d[131]), "=f"(d[132]), "=f"(d[133]), "=f"(d[134]), "=f"(d[135]), "=f"(d[136]), "=f"(d[137]), "=f"(d[138]), "=f"(d[139]), "=f"(d[140]), "=f"(d[141]), "=f"(d[142]), "=f"(d[143]), "=f"(d[144]), "=f"(d[145]), "=f"(d[146]), "=f"(d[147]), "=f"(d[148]), "=f"(d[149]), "=f"(d[150]), "=f"(d[151]), "=f"(d[152]), "=f"(d[153]), "=f"(d[154]), "=f"(d[155]), "=f"(d[156]), "=f"(d[157]), "=f"(d[158]), "=f"(d[159]), "=f"(d[160]), "=f"(d[161]), "=f"(d[162]), "=f"(d[163]), "=f"(d[164]), "=f"(d[165]), "=f"(d[166]), "=f"(d[167]), "=f"(d[168]), "=f"(d[169]), "=f"(d[170]), "=f"(d[171]), "=f"(d[172]), "=f"(d[173]), "=f"(d[174]), "=f"(d[175]), "=f"(d[176]), "=f"(d[177]), "=f"(d[178]), "=f"(d[179]), "=f"(d[180]), "=f"(d[181]), "=f"(d[182]), "=f"(d[183]), "=f"(d[184]), "=f"(d[185]), "=f"(d[186]), "=f"(d[187]), "=f"(d[188]), "=f"(d[189]), "=f"(d[190]), "=f"(d[191])
    : "l"(da), "l"(db));
}
__device__ __forceinline__ void wgmma_n128_rs(float (&d)[192], const uint32_t (&a)[4], uint64_t db, int scale_d) {
  asm volatile("{\n.reg .pred p;\nsetp.ne.b32 p, %69, 0;\n"
    "wgmma.mma_async.sync.aligned.m64n128k16.f32.bf16.bf16 {%0, %1, %2, %3, %4, %5, %6, %7, %8, %9, %10, %11, %12, %13, %14, %15, %16, %17, %18, %19, %20, %21, %22, %23, %24, %25, %26, %27, %28, %29, %30, %31, %32, %33, %34, %35, %36, %37, %38, %39, %40, %41, %42, %43, %44, %45, %46, %47, %48, %49, %50, %51, %52, %53, %54, %55, %56, %57, %58, %59, %60, %61, %62, %63}, {%64, %65, %66, %67}, %68, p, 1, 1, 1;\n}\n"
    : "+f"(d[128]), "+f"(d[129]), "+f"(d[130]), "+f"(d[131]), "+f"(d[132]), "+f"(d[133]), "+f"(d[134]), "+f"(d[135]), "+f"(d[136]), "+f"(d[137]), "+f"(d[138]), "+f"(d[139]), "+f"(d[140]), "+f"(d[141]), "+f"(d[142]), "+f"(d[143]), "+f"(d[144]), "+f"(d[145]), "+f"(d[146]), "+f"(d[147]), "+f"(d[148]), "+f"(d[149]), "+f"(d[150]), "+f"(d[151]), "+f"(d[152]), "+f"(d[153]), "+f"(d[154]), "+f"(d[155]), "+f"(d[156]), "+f"(d[157]), "+f"(d[158]), "+f"(d[159]), "+f"(d[160]), "+f"(d[161]), "+f"(d[162]), "+f"(d[163]), "+f"(d[164]), "+f"(d[165]), "+f"(d[166]), "+f"(d[167]), "+f"(d[168]), "+f"(d[169]), "+f"(d[170]), "+f"(d[171]), "+f"(d[172]), "+f"(d[173]), "+f"(d[174]), "+f"(d[175]), "+f"(d[176]), "+f"(d[177]), "+f"(d[178]), "+f"(d[179]), "+f"(d[180]), "+f"(d[181]), "+f"(d[182]), "+f"(d[183]), "+f"(d[184]), "+f"(d[185]), "+f"(d[186]), "+f"(d[187]), "+f"(d[188]), "+f"(d[189]), "+f"(d[190]), "+f"(d[191])
    : "r"(a[0]), "r"(a[1]), "r"(a[2]), "r"(a[3]), "l"(db), "r"(scale_d));
}

constexpr int SLOT = 16384;
constexpr int KVT = 10240;
constexpr uint32_t QA = 0x0BAu, QK = 0x462u, QQ = 0x981u;
constexpr int SM_SD = 12 * SLOT;
constexpr int SM_BAR = SM_SD + 8192;
constexpr int SM_RS = SM_BAR + 512;
constexpr int SM_AP = SM_RS + 768;
constexpr int SM_BP = SM_AP + 2048;
constexpr int SM_WPHI = SM_BP + 12288;
constexpr int SM_EPOCH = SM_WPHI + 10240;
constexpr int SM_TOTAL = SM_EPOCH + 16 + 1024;
constexpr int B_FULLS = 0, B_XOLD = 24, B_STAT = 32, B_EMPTYS = 40, B_FULLT = 256  , B_CONS = 384  , B_E3 = 472, B_E0 = 480, B_E1 = 488, B_E2 = 496, B_EPI = 504, B_CS = 160,
              B_KVDONE = 168  , B_ODONE = 176, B_XDONE = 184, B_OH1 = B_CONS, B_CS2 = 208, B_XH0 = 232, B_R0 = 240, B_CB = 144  , B_XOLD2 = 216, B_FLG = 64  ;
constexpr uint64_t BAR_CNT = 0x1c07fc0eac00a800ull;
constexpr uint64_t WO_A0 = 0xa461b57648357643ull, WO_B0 = 0x59083a9021ba9021ull, WO_A1 = 0xa0b76901276a5babull, WO_B1 = 0x95428a5b34890132ull;
constexpr uint64_t WO_DA0 = 0xa9865432ff00dd00ull, WO_DB0 = 0xa986543211bbccccull, WO_DA1 = 0xa98654321ffff000ull, WO_DB1 = 0xa98754321bbcccddull;
#define WOORD 0xFDB9753ECA864210ull
constexpr int NX = 4;
constexpr int XS = 10;

#define PL 2
#define PROFX(i) PROFT(tid_ == 128 && layer == PL, 200 + (i))
#define PSL 20
#define EP 5
#define NCOM 3
#define CSLP 128
#define PFS 8
#define KVTH 0x41700000u
#define RL 3
#define ORD 1
#define XB2 2
#define PMOD 3
#define DB1 2
#define XPF 2
#define XPM 0
#define AW 1
#define PG 0
#define UNS 7
#define TLINE 0
#define RORD 0
#define WSK 1
#define ER 1
#define SSL 256
#define NLAYERS 4
constexpr float L2E = 1.4426950408889634f;
#define PHI_MAX 2147483648.f

#define D128(lo) desc64(lo, 0x40000040u)
struct Ctx { uint32_t sb; int g, rb, cu; bf16* out; };

__device__ __forceinline__ void colsum(const CUtensorMap* tm, float* cs, int rb, int g, int w0, int dw, int lane, uint32_t stg, uint32_t cb, uint32_t par) {
  const uint32_t src = stg + (lane >> 3) * 2048;
#pragma unroll 1
  for (int wi = w0 - dw; wi < 6; wi += dw) {
    float s[8] = {0.f, 0.f, 0.f, 0.f, 0.f, 0.f, 0.f, 0.f};
    if (wi >= 0) {
      mbar_wait_u(cb, par);
      par ^= 1;
#pragma unroll 4
      for (int r = 0; r < 16; ++r) {
        const uint4 v = lds128(src + r * 128 + (((lane ^ r) & 7) << 4));
        s[0] += bf_lo(v.x); s[1] += bf_hi(v.x); s[2] += bf_lo(v.y); s[3] += bf_hi(v.y);
        s[4] += bf_lo(v.z); s[5] += bf_hi(v.z); s[6] += bf_lo(v.w); s[7] += bf_hi(v.w);
      }
#pragma unroll
      for (int i = 0; i < 8; ++i) s[i] += __shfl_xor_sync(0xffffffffu, s[i], 8);
    }
    const int wn = wi + dw;
    if (wn < 6) {
      expect_tx_e(cb, 8192);
      tma_2d_e(stg, tm, (wn >= 4 ? 0 : 1024 + (wn >> 1) * 1024) + g * 128 + (wn & 1) * 64, rb * 64, cb);
    }
    if (wi >= 0) {
#pragma unroll
      for (int i = 0; i < 8; ++i) s[i] += __shfl_xor_sync(0xffffffffu, s[i], 16);
      if (lane < 8) {
        red_add4(cs + g * 384 + (wi * 8 + lane) * 8, s[0], s[1], s[2], s[3]);
        red_add4(cs + g * 384 + (wi * 8 + lane) * 8 + 4, s[4], s[5], s[6], s[7]);
      }
      __syncwarp();
    }
  }
}
#define PHASE_CTX() \
  uint32_t sb = c.sb; asm volatile("" : "+r"(sb)); \
  int tid_ = threadIdx.x; asm volatile("" : "+r"(tid_)); \
  const uint32_t bar = sb + SM_BAR; \
  const int lane = tid_ & 31, cw = (tid_ >> 5) - 4, wg = cw >> 2, wq = cw & 3, gq = lane >> 2, t = lane & 3, wrow0 = cw * 16; \
  const int lrow = (lane & 7) + ((lane >> 3) & 1) * 8, lchk = lane >> 4; \
  const bool elected = (tid_ & 127) == 0; \
  const uint32_t rowo = (wrow0 + lrow) * 128, X = (lchk ^ (lane & 7)) << 4; \
  (void)bar; (void)wq; (void)gq; (void)lrow; (void)lchk; (void)elected; (void)wrow0; (void)wg; (void)rowo; (void)X; (void)t;

__device__ __forceinline__ void slab_out_half(uint32_t slot, bf16* dst, int wrow0, int lane, bool FENCE = false) {
  const int r0 = lane >> 3, ch = lane & 7;
  const uint32_t src = slot + (wrow0 + r0) * 128;
  uint4 v[4];
#pragma unroll
  for (int i = 0; i < 4; ++i) v[i] = lds128(src + i * 512 + (((ch ^ (4 * i + r0)) & 7) << 4));
  if (FENCE) fence_async_smem();
  dst += (size_t)(wrow0 + r0) * D_ + ch * 8;
#pragma unroll
  for (int i = 0; i < 4; ++i)
    asm volatile("st.global.v4.u32 [%0], {%1,%2,%3,%4};" ::"l"(dst + (size_t)i * 4 * D_), "r"(v[i].x), "r"(v[i].y), "r"(v[i].z), "r"(v[i].w) : "memory");
}

struct Tag { uint32_t me, mo, tg; };
__device__ __forceinline__ Tag make_tag(int gq, int t, uint32_t tg) {
  const uint32_t on = t == (gq & 3), par = ((gq >> 2) ^ gq) & 1;
  return Tag{on & ~par, on & par, tg};
}
__device__ __forceinline__ void stsm_tag(uint32_t addr, uint32_t r0, uint32_t r1, uint32_t r2, uint32_t r3, const Tag& k, int jp) {
  stsm_x4(addr, (r0 & ~k.me) | (k.tg & k.me), (r1 & ~k.me) | (k.tg & k.me), (r2 & ~k.mo) | (k.tg & k.mo), (r3 & ~k.mo) | (k.tg & k.mo));
}
#define TILE_BAD() (((lds_vol(va) ^ tg) | (lds_vol(va + 1024) ^ tg)) & 1)
#define TILE_VA() (slot + (wrow0 + (lane >> 2)) * 128 + (lane & 3) * 32 + (lane >> 2) * 4)
__device__ __forceinline__ void tile_check(uint32_t slot, const bf16* src, int wrow0, int lane, uint32_t tg) {
  const uint32_t va = TILE_VA();
  if (__builtin_expect(__any_sync(0xffffffffu, TILE_BAD()), 0)) {
    const int r0 = lane >> 3, ch = lane & 7;
    uint32_t n = 0;
#pragma unroll 1
    do {
      uint4 v[4];
#pragma unroll
      for (int i = 0; i < 4; ++i) v[i] = ld_relaxed4(reinterpret_cast<const uint4*>(src + (size_t)(wrow0 + r0 + 4 * i) * D_ + ch * 8));
#pragma unroll
      for (int i = 0; i < 4; ++i) sts128(slot + (wrow0 + r0 + 4 * i) * 128 + (((ch ^ (4 * i + r0)) & 7) << 4), v[i]);
      __syncwarp();
      if (++n > (1u << 16)) { g_err = 8u; break; }
    } while (__any_sync(0xffffffffu, TILE_BAD()));
    fence_async_smem();
    __syncwarp();
  }
}

template <int O>
__device__ __forceinline__ void phi_proj(float (&p)[2][4][4], const uint32_t (&kq)[64], uint32_t wa) {
#pragma unroll
  for (int h = 0; h < 2; ++h)
#pragma unroll
    for (int i = 0; i < 4; ++i) { p[h][i][0] = p[h][i][1] = p[h][i][2] = p[h][i][3] = 0.f; }
#pragma unroll
  for (int ks = 0; ks < 2; ++ks)
#pragma unroll
    for (int np = 0; np < 2; ++np)
#pragma unroll
      for (int h = 0; h < 2; ++h) {
        uint32_t b0, b1, b2, b3;
        ldsm_x4_t(b0, b1, b2, b3, wa + h * 2560 + ks * 1280 + np * 32);
        mma_bf16(p[h][2 * np], kq[O + 8 * h + 4 * ks], kq[O + 8 * h + 4 * ks + 1], kq[O + 8 * h + 4 * ks + 2], kq[O + 8 * h + 4 * ks + 3], b0, b1);
        mma_bf16(p[h][2 * np + 1], kq[O + 8 * h + 4 * ks], kq[O + 8 * h + 4 * ks + 1], kq[O + 8 * h + 4 * ks + 2], kq[O + 8 * h + 4 * ks + 3], b2, b3);
      }
}
__device__ __forceinline__ void phi_exp(uint32_t (&raw)[4][4], const float (&p)[4][4], float sc0, float sc1) {
#pragma unroll
  for (int i = 0; i < 4; ++i) {
    const float e0 = ex2(p[i][0] * sc0), e1 = ex2(p[i][1] * sc0), e2 = ex2(p[i][2] * sc1), e3 = ex2(p[i][3] * sc1);
    const float m0 = e0 * e1, m1 = e2 * e3, rr = rcp(m0 * m1), r0 = rr * m1, r1 = rr * m0;
    raw[i >> 1][(i & 1) * 2] = pack_bf16(e0, e1);
    raw[i >> 1][(i & 1) * 2 + 1] = pack_bf16(e2, e3);
    raw[2 + (i >> 1)][(i & 1) * 2] = pack_bf16(e1 * r0, e0 * r0);
    raw[2 + (i >> 1)][(i & 1) * 2 + 1] = pack_bf16(e3 * r1, e2 * r1);
  }
}
#define FENCE_P(h) _Pragma("unroll") for (int i_ = 0; i_ < 16; ++i_) asm volatile("" : "+f"(p[h][i_ >> 2][i_ & 3]) :: "memory")
#define FENCE_RAW(h) _Pragma("unroll") for (int i_ = 0; i_ < 16; ++i_) asm volatile("" : "+r"(raw[h][i_ >> 2][i_ & 3]) :: "memory")
template <int O>
__device__ __forceinline__ void phi_norm(uint32_t (&ph)[2][4][4], const uint32_t (&raw)[2][4][4], const uint32_t (&kq)[64], uint32_t wa,
                                         float sc0, float sc1, float mul0, float mul1) {
  bool bad = false;
#pragma unroll
  for (int h = 0; h < 2; ++h)
#pragma unroll
    for (int sg = 0; sg < 2; ++sg) {
      float ss[4] = {0.f, 0.f, 0.f, 0.f};
#pragma unroll
      for (int ks = 0; ks < 2; ++ks)
        mma_bf16(ss, raw[h][2 * sg + ks][0], raw[h][2 * sg + ks][1], raw[h][2 * sg + ks][2], raw[h][2 * sg + ks][3], 0x3F803F80u, 0x3F803F80u);
      bad = bad || !(ss[0] < PHI_MAX) || !(ss[2] < PHI_MAX);
      const uint32_t iv = pack_bf16(rcp(ss[0]) * mul0, rcp(ss[2]) * mul1);
#pragma unroll
      for (int ks = 0; ks < 2; ++ks)
#pragma unroll
        for (int j = 0; j < 4; ++j) ph[h][2 * sg + ks][j] = mul_bf16x2(raw[h][2 * sg + ks][j], iv, j & 1);
    }
  if (__builtin_expect(__any_sync(0xffffffffu, bad), 0)) {
#pragma unroll 1
    for (int it = 0; it < 4; ++it) {
      float q[4][4];
#pragma unroll
      for (int i = 0; i < 4; ++i) { q[i][0] = q[i][1] = q[i][2] = q[i][3] = 0.f; }
#pragma unroll
      for (int ks = 0; ks < 2; ++ks) {
        uint32_t a[4];
#pragma unroll
        for (int j = 0; j < 4; ++j) a[j] = (it & 2) ? kq[O + 8 + 4 * ks + j] : kq[O + 4 * ks + j];
#pragma unroll
        for (int np = 0; np < 2; ++np) {
          uint32_t b0, b1, b2, b3;
          ldsm_x4_t(b0, b1, b2, b3, wa + (it >> 1) * 2560 + ks * 1280 + np * 32);
          mma_bf16(q[2 * np], a[0], a[1], a[2], a[3], b0, b1);
          mma_bf16(q[2 * np + 1], a[0], a[1], a[2], a[3], b2, b3);
        }
      }
      float iv[2];
#pragma unroll
      for (int r = 0; r < 2; ++r) {
        const float sc = (it & 1) ? -(r ? sc1 : sc0) : (r ? sc1 : sc0);
        float mx = -INFINITY, sm = 0.f;
#pragma unroll
        for (int i = 0; i < 8; ++i) { float& v = q[i >> 1][2 * r + (i & 1)]; v *= sc; mx = fmaxf(mx, v); }
        mx = fmaxf(mx, __shfl_xor_sync(0xffffffffu, mx, 1));
        mx = fmaxf(mx, __shfl_xor_sync(0xffffffffu, mx, 2));
#pragma unroll
        for (int i = 0; i < 8; ++i) { float& v = q[i >> 1][2 * r + (i & 1)]; v = ex2(v - mx); sm += v; }
        sm += __shfl_xor_sync(0xffffffffu, sm, 1);
        sm += __shfl_xor_sync(0xffffffffu, sm, 2);
        iv[r] = rcp(sm) * (r ? mul1 : mul0);
      }
#pragma unroll
      for (int i = 0; i < 24; ++i) ph[i >> 4][(i >> 2) & 3][i & 3] = ph[(i + 8) >> 4][((i + 8) >> 2) & 3][i & 3];
#pragma unroll
      for (int i = 0; i < 4; ++i) {
        ph[1][2 + (i >> 1)][(i & 1) * 2] = pack_bf16(q[i][0] * iv[0], q[i][1] * iv[0]);
        ph[1][2 + (i >> 1)][(i & 1) * 2 + 1] = pack_bf16(q[i][2] * iv[1], q[i][3] * iv[1]);
      }
    }
  }
}

__device__ __forceinline__ void stats_out(float s0, float s1, float q0, float q1, float2* dst, int t) {
  const bool od = t & 1;
  float sa = od ? s1 : s0, qa = od ? q1 : q0;
  sa += __shfl_xor_sync(0xffffffffu, od ? s0 : s1, 1);
  qa += __shfl_xor_sync(0xffffffffu, od ? q0 : q1, 1);
  sa += __shfl_xor_sync(0xffffffffu, sa, 2);
  qa += __shfl_xor_sync(0xffffffffu, qa, 2);
  if (t < 2) red_add2(&dst[t * 8].x, sa, qa);
}

__device__ __forceinline__ void consumer(const Ctx& c) {
  const int g = c.g, m0 = c.rb * 128;
  float acc[192];
#define X_HALF(hf, TG) \
      _Pragma("unroll") for (int jp = 4 * (hf); jp < 4 * (hf) + 4; ++jp) \
        stsm_tag(sb + (XS + (hf)) * SLOT + rowo + (X ^ ((jp & 3) << 5)), \
                 pack_bf16(acc[128 + 8 * jp], acc[129 + 8 * jp]), pack_bf16(acc[130 + 8 * jp], acc[131 + 8 * jp]), \
                 pack_bf16(acc[132 + 8 * jp], acc[133 + 8 * jp]), pack_bf16(acc[134 + 8 * jp], acc[135 + 8 * jp]), TG, jp & 3);
#pragma unroll
  for (int i = 128; i < 192; ++i) acc[i] = 0.f;
#pragma unroll 1
  for (int layer = 0;; ++layer) {
    {
      PHASE_CTX();
      const uint32_t wu = c.cu >> 2;
      const uint32_t dA0 = (((sb + wu * 8192) & 0x3FFFF) >> 4) | (1u << 16), dB0 = ((sb & 0x3FFFF) >> 4) | (512u << 16);
      {
        PROFX(0);
        mbar_wait(bar + B_FULLS, 0);
        PROFX(1);
        wgmma_fence();
        wgmma_n256_0(acc, D128(dA0 + XS * 1024), D128(dB0 + 2048));
#pragma unroll
        for (int k = 1; k < 4; ++k) wgmma_n256(acc, D128(dA0 + XS * 1024 + k * 2), D128(dB0 + 2048 + k * 128), 1);
        wgmma_commit();
        wgmma_wait<1>();
        float s0 = 0.f, s1 = 0.f, q0 = 0.f, q1 = 0.f;
        if (layer) {
          X_HALF(1, (Tag{0u, 0u, 0u}));
#pragma unroll
          for (int i = 128; i < 192; i += 4) {
            s0 += acc[i] + acc[i + 1]; s1 += acc[i + 2] + acc[i + 3];
            q0 = fmaf(acc[i], acc[i], fmaf(acc[i + 1], acc[i + 1], q0)); q1 = fmaf(acc[i + 2], acc[i + 2], fmaf(acc[i + 3], acc[i + 3], q1));
          }
        }
        asm volatile("" : "+f"(s0), "+f"(s1), "+f"(q0), "+f"(q1) :: "memory");
        wgmma_fence();
        wgmma_n128_0(acc, D128(dA0 + XS * 1024), D128(dB0 + 1024));
#pragma unroll
        for (int k = 1; k < 4; ++k) wgmma_n128(acc, D128(dA0 + XS * 1024 + k * 2), D128(dB0 + 1024 + k * 128), 1);
        wgmma_commit();
        if (layer) {
          PHASE_CTX();
          fence_async_smem();
          nbar_dyn(3 + wu, 128);
          stats_out(s0, s1, q0, q1, g_stats + layer * S_ + m0 + wrow0 + gq, t);
          PROFT(tid_ == 128, layer * 16 + 8);
        }
      }
      uint32_t s = 1, u = 0, sp = 0;
      const int ix = layer ? 99 : 2 * min(g, NCOM) + 1;
#pragma unroll 1
      for (int i = 1; i < 14; ++i) {
        mbar_wait(bar + B_FULLS + s * 8, (u + (s ? layer : 0)) & 1);
        if ((UNS & 1) && layer && (unsigned)(i - 2) < 7u) {
          PHASE_CTX();
          tile_check(sb + ((QA >> (4 * s)) & 15) * SLOT, g_x + (size_t)m0 * D_ + ((2 * g + 2 * i - 2) & 15) * 64, wrow0, lane, lds_vol(sb + SM_EPOCH) + layer);
        }
        const uint32_t da = dA0 + ((QA >> (4 * s)) & 15) * 1024, dk = dB0 + ((QK >> (4 * s)) & 15) * 1024,
                       dq = dB0 + ((QQ >> (4 * s)) & 15) * 1024;
        wgmma_fence();
#pragma unroll
        for (int k = 0; k < 4; ++k) {
          wgmma_n256(acc, D128(da + k * 2), D128(dk + k * 128), 1);
          wgmma_n128(acc, D128(da + k * 2), D128(dq + k * 128), 1);
          if (k == ER - 1) {
            wgmma_commit();
            wgmma_wait<1>();
            if (elected && (unsigned)(i - ix) >= 2u) release2(bar + B_EMPTYS + sp * 8);
          }
        }
        wgmma_commit();
        if ((unsigned)(i - ix) < 2u) {
          PHASE_CTX();
          {
            float s0 = 0.f, s1 = 0.f, q0 = 0.f, q1 = 0.f;
            const uint32_t xa = sb + ((QA >> (4 * sp)) & 15) * SLOT + rowo;
#pragma unroll
            for (int jp = 0; jp < 4; ++jp) {
              uint32_t x0, x1, x2, x3;
              ldsm_x4(x0, x1, x2, x3, xa + (X ^ (jp << 5)));
              s0 += (bf_lo(x0) + bf_hi(x0)) + (bf_lo(x2) + bf_hi(x2));
              s1 += (bf_lo(x1) + bf_hi(x1)) + (bf_lo(x3) + bf_hi(x3));
              q0 = fmaf(bf_lo(x0), bf_lo(x0), fmaf(bf_hi(x0), bf_hi(x0), fmaf(bf_lo(x2), bf_lo(x2), fmaf(bf_hi(x2), bf_hi(x2), q0))));
              q1 = fmaf(bf_lo(x1), bf_lo(x1), fmaf(bf_hi(x1), bf_hi(x1), fmaf(bf_lo(x3), bf_lo(x3), fmaf(bf_hi(x3), bf_hi(x3), q1))));
            }
            stats_out(s0, s1, q0, q1, g_stats + m0 + wrow0 + gq, t);
          }
          __syncwarp();
          if (lane == 0 && i != ix) mbar_arrive(bar + B_XDONE);
          nbar_dyn(3 + wu, 128);
          if (ER && elected) release2(bar + B_EMPTYS + sp * 8);
        }
        if (!ER) {
          wgmma_wait<1>();
          if (elected) release2(bar + B_EMPTYS + sp * 8);
        }
        if (i == 1 && layer) {
          PHASE_CTX();
          slab_out_half(sb + (XS + 1) * SLOT, g_x + (size_t)m0 * D_ + g * 128 + 64, wrow0, lane);
          __syncwarp();
          if (lane == 0) mbar_arrive(bar + B_XDONE);
          nbar_dyn(3 + wu, 128);
        }
        sp = s;
        if (++s == 3) { s = 0; ++u; }
      }
      {
        const uint64_t dap = make_desc_ns(sb + SM_AP + wu * 1024, 0, 128), dbp = make_desc_ns(sb + SM_BP + (layer & 1) * 6144, 0, 128);
        if (wu == 0) {
          wgmma_wait<0>();
          if (elected) mbar_arrive(bar + B_R0);
          nbar<6, 256>();
        }
        if (layer < 2) mbar_wait(bar + (layer ? B_CS2 : B_CS), 0);
        mbar_wait(bar + B_STAT, layer & 1);
        mbar_wait(bar + B_FULLS + 16, layer & 1);
        wgmma_fence();
        wgmma_n256_k(acc, dap, dbp, 1);
#pragma unroll
        for (int k = 0; k < 4; ++k) wgmma_n256(acc, D128(dA0 + (QA >> 8) * 1024 + k * 2), D128(dB0 + (QK >> 8) * 1024 + k * 128), 1);
        mbar_wait(bar + B_FULLS, 1);
        PROFT(tid_ == 128, layer * 16 + 9);
        wgmma_fence();
#pragma unroll
        for (int k = 0; k < 4; ++k) wgmma_n256(acc, D128(dA0 + (QA & 15) * 1024 + k * 2), D128(dB0 + (QK & 15) * 1024 + k * 128), 1);
        wgmma_commit();
        if (wu) nbar<6, 256>();
#define Q_TAIL() \
        wgmma_n128_k(acc, dap, dbp + 256, 1); \
        _Pragma("unroll") for (int k = 0; k < 4; ++k) wgmma_n128(acc, D128(dA0 + (QA >> 8) * 1024 + k * 2), D128(dB0 + (QQ >> 8) * 1024 + k * 128), 1); \
        _Pragma("unroll") for (int k = 0; k < 4; ++k) wgmma_n128(acc, D128(dA0 + (QA & 15) * 1024 + k * 2), D128(dB0 + (QQ & 15) * 1024 + k * 128), 1);
        Q_TAIL();
        wgmma_commit();
        wgmma_wait<1>();
#pragma unroll
        for (int i = 0; i < 128; ++i) asm volatile("" : "+f"(acc[i]) :: "memory");
      }
    }
    uint32_t xo[32];
    uint32_t oq[8][4];
    {
      PHASE_CTX();
      PROFT(tid_ == 128, layer * 16 + 1);
      const bool isB = layer & 1;
      const int cu = c.cu;
      if (cu >= 4) asm volatile("bar.arrive 7, 256;" ::: "memory");
      if (elected && cu == 4) mbar_arrive(bar + B_R0);
      uint32_t kq[64];
      const uint32_t rowq = rowo & 8191;
      const float rs0 = lds_f(sb + SM_RS + (16 + wrow0 + gq) * 4), rs1 = lds_f(sb + SM_RS + (24 + wrow0 + gq) * 4);
#define Q_DONE() \
      wgmma_wait<0>(); \
      if (lane == 0) release2(bar + B_E0); \
      _Pragma("unroll") for (int i = 128; i < 192; ++i) asm volatile("" : "+f"(acc[i]) :: "memory"); \
      _Pragma("unroll") for (int i = 0; i < 32; ++i) kq[32 + i] = pack_bf16(acc[128 + 2 * i], acc[129 + 2 * i]);
      if (isB) {
        if (cu == 0) asm volatile("bar.arrive 10, 64;" ::: "memory");
        if (elected) release2(bar + B_E1);
        const int e = gq & 1;
        const bool sel = t > (gq >> 1);
        const uint32_t rja = sb + SM_RS + (wrow0 + 2 * t + e) * 4;
        const float rjA0 = lds_f(rja + 32), rjA1 = lds_f(rja + 64), rjB0 = lds_f(rja + (sel ? 0 : 64)), rjB1 = lds_f(rja + (sel ? 32 : 96));
        uint32_t vv[32];
#pragma unroll
        for (int i = 0; i < 16; ++i) { kq[i] = pack_bf16(acc[2 * i], acc[2 * i + 1]); vv[i] = pack_bf16(acc[64 + 2 * i], acc[65 + 2 * i]); }
        const uint32_t rB = sb + 4 * SLOT + wg * 4 * KVT + rowq;
        auto dump = [&](int hp) {
          const uint32_t kb = rB + 2048 + (hp ^ wg) * 2 * KVT;
#pragma unroll
          for (int jp = 0; jp < 4; ++jp) {
            stsm_x4(kb + (X ^ (jp << 5)), kq[16 * hp + 4 * jp], kq[16 * hp + 4 * jp + 1], kq[16 * hp + 4 * jp + 2], kq[16 * hp + 4 * jp + 3]);
            stsm_x4(kb + KVT + (X ^ (jp << 5)), vv[16 * hp + 4 * jp], vv[16 * hp + 4 * jp + 1], vv[16 * hp + 4 * jp + 2], vv[16 * hp + 4 * jp + 3]);
          }
          if (cu == 3) {
            const uint32_t kd = rB + 2048 + 32768 + (1 - hp) * 2 * KVT;
#pragma unroll
            for (int jp = 0; jp < 4; ++jp) {
              stsm_x4(kd + (X ^ (jp << 5)), kq[16 * hp + 4 * jp], kq[16 * hp + 4 * jp + 1], kq[16 * hp + 4 * jp + 2], kq[16 * hp + 4 * jp + 3]);
              stsm_x4(kd + KVT + (X ^ (jp << 5)), vv[16 * hp + 4 * jp], vv[16 * hp + 4 * jp + 1], vv[16 * hp + 4 * jp + 2], vv[16 * hp + 4 * jp + 3]);
            }
            if (hp) asm volatile("bar.arrive 15, 64;" ::: "memory"); else asm volatile("bar.arrive 9, 64;" ::: "memory");
          }
          asm volatile("bar.arrive %0, 224;" :: "r"(hp ? 13 + (cu >> 2) : 8 + (cu & 4)) : "memory");
        };
        uint4* const hbuf = g_halo + ((c.rb * 8 + g) * 2 + (layer >> 1)) * 512 + lane;
        if (cu < 4) {
          nbar<7, 256>();
          dump(0);
        }
#pragma unroll
        for (int i = 16; i < 32; ++i) { kq[i] = pack_bf16(acc[2 * i], acc[2 * i + 1]); vv[i] = pack_bf16(acc[64 + 2 * i], acc[65 + 2 * i]); }
        if (cu >= 4) {
          if (cu == 7) {
#pragma unroll
            for (int jp = 0; jp < 8; ++jp) {
              st_relaxed4(hbuf + jp * 32, ~kq[4 * jp], ~kq[4 * jp + 1], ~kq[4 * jp + 2], ~kq[4 * jp + 3]);
              st_relaxed4(hbuf + 256 + jp * 32, ~vv[4 * jp], ~vv[4 * jp + 1], ~vv[4 * jp + 2], ~vv[4 * jp + 3]);
            }
          }
          dump(0);
          dump(1);
        }
        PROFT(tid_ == 128, layer * 16 + 2);
        constexpr float SC = 0.17677669529663687f * L2E;
        const float fA0 = rjA0 * rs0 * SC, fB0 = rjB0 * rs0 * SC, fA1 = rjA1 * rs1 * SC, fB1 = rjB1 * rs1 * SC;
        const float bA0 = (m0 + wrow0) ? 0.f : -1e30f, bB = sel ? bA0 : 0.f;
        const uint32_t pA_ = e ? 0x1044u : 0x4410u, pB_ = e ? 0x3244u : 0x4432u, pLo = sel ? pB_ : 0x4444u, pHi = sel ? 0x4444u : pB_;
        const uint32_t KX = ((lane >> 3) ^ (lane & 7)) << 4;
        Q_DONE();
        if (cu == 0) {
          nbar<11, 64>();
        } else if (cu == 4) {
          uint4 hv[16];
          if (c.rb > 0) {
            uint32_t n = 0;
#pragma unroll 1
            while (true) {
              uint32_t mn = 0xFFFFFFFFu;
#pragma unroll
              for (int i = 0; i < 16; ++i) hv[i] = ld_relaxed4(hbuf - 16 * 512 + i * 32);
#pragma unroll
              for (int i = 0; i < 16; ++i) mn = __vimin3_u32(__vimin3_u32(mn, hv[i].x, hv[i].y), hv[i].z, hv[i].w);
              if (__all_sync(0xffffffffu, mn != 0u)) break;
              if (++n > (1u << 20)) { g_err = 4u; break; }
            }
          } else {
#pragma unroll
            for (int i = 0; i < 16; ++i) hv[i] = make_uint4(~0u, ~0u, ~0u, ~0u);
          }
          nbar<10, 64>();
#pragma unroll
          for (int i = 0; i < 16; ++i)
            stsm_x4(rB - 4 * KVT + (((i >> 2) & 1) * 2 + (i >> 3)) * KVT + (X ^ ((i & 3) << 5)), ~hv[i].x, ~hv[i].y, ~hv[i].z, ~hv[i].w);
          asm volatile("bar.arrive 11, 64;" ::: "memory");
          nbar<9, 64>();
        } else {
          nbar_dyn(8 + (cu & 4), 224);
        }
        PROFT(tid_ == 128, layer * 16 + 5);
        PROFT(lane == 0 && layer == PL, 136 + cw);
        auto attend = [&](int hp) {
          const uint32_t qad = sb + (XS + 1 - hp) * SLOT + rowo, kt = rB + 2 * (hp ^ wg) * KVT - (lane & 8) * 128, vt = rB + (2 * (hp ^ wg) + 1) * KVT;
          __syncwarp();
          uint32_t kb[2][2][4], vb[2][2][2][4];
#pragma unroll
          for (int h = 0; h < 2; ++h)
#pragma unroll
            for (int nt = 0; nt < 2; ++nt) ldsm_x4(kb[h][nt][0], kb[h][nt][1], kb[h][nt][2], kb[h][nt][3], kt + nt * 1024 + (KX ^ (h << 6)));
#pragma unroll
          for (int ks = 0; ks < 2; ++ks)
#pragma unroll
            for (int np = 0; np < 2; ++np)
#pragma unroll
              for (int h = 0; h < 2; ++h)
                ldsm_x4_t(vb[h][ks][np][0], vb[h][ks][np][1], vb[h][ks][np][2], vb[h][ks][np][3], vt + ks * 2048 + (X ^ (h << 6) ^ (np << 5)));
          if (hp == 0 && lane == 0) release2(bar + B_E3);
          if (DB1 == 1 && hp == 0 && cu < 4) dump(1);
          float la[2][2], lb[2][2], mx[2][2], sm[2][2];
#pragma unroll
          for (int h = 0; h < 2; ++h) {
            const int qo = 32 + 16 * hp + 8 * h, ko = 16 * hp + 8 * h;
            float sc[4][4];
#pragma unroll
            for (int nt = 0; nt < 4; ++nt) {
              sc[nt][0] = sc[nt][1] = sc[nt][2] = sc[nt][3] = 0.f;
#pragma unroll
              for (int ks = 0; ks < 2; ++ks)
                mma_bf16(sc[nt], kq[qo + 4 * ks], kq[qo + 4 * ks + 1], kq[qo + 4 * ks + 2], kq[qo + 4 * ks + 3],
                         nt < 2 ? kb[h][nt & 1][2 * ks] : kq[ko + 4 * ks + (nt & 1)], nt < 2 ? kb[h][nt & 1][2 * ks + 1] : kq[ko + 4 * ks + 2 + (nt & 1)]);
            }
            la[h][0] = fmaf(e ? sc[1][1] : sc[1][0], fA0, bA0);
            lb[h][0] = fmaf(sel ? (e ? sc[0][1] : sc[0][0]) : (e ? sc[2][1] : sc[2][0]), fB0, bB);
            la[h][1] = (e ? sc[2][3] : sc[2][2]) * fA1;
            lb[h][1] = fmaf(sel ? (e ? sc[1][3] : sc[1][2]) : (e ? sc[3][3] : sc[3][2]), fB1, bB);
            mx[h][0] = fmaxf(la[h][0], lb[h][0]); mx[h][1] = fmaxf(la[h][1], lb[h][1]);
          }
#pragma unroll
          for (int o = 1; o <= 2; o <<= 1)
#pragma unroll
            for (int h = 0; h < 2; ++h)
#pragma unroll
              for (int r = 0; r < 2; ++r) mx[h][r] = fmaxf(mx[h][r], __shfl_xor_sync(0xffffffffu, mx[h][r], o));
          float oa[2][4][4];
#pragma unroll
          for (int h = 0; h < 2; ++h) {
#pragma unroll
            for (int r = 0; r < 2; ++r) { la[h][r] = ex2(la[h][r] - mx[h][r]); lb[h][r] = ex2(lb[h][r] - mx[h][r]); sm[h][r] = la[h][r] + lb[h][r]; }
            const uint32_t p0 = pack_bf16(la[h][0] * rjA0, lb[h][0] * rjB0), p1 = pack_bf16(la[h][1] * rjA1, lb[h][1] * rjB1);
            const uint32_t a00 = __byte_perm(p0, 0u, pLo), a02 = __byte_perm(p0, 0u, pA_), a03 = __byte_perm(p1, 0u, pLo);
            const uint32_t a10 = __byte_perm(p0, 0u, pHi), a11 = __byte_perm(p1, 0u, pA_), a13 = __byte_perm(p1, 0u, pHi);
#pragma unroll
            for (int i = 0; i < 4; ++i) {
              oa[h][i][0] = oa[h][i][1] = oa[h][i][2] = oa[h][i][3] = 0.f;
              mma_bf16(oa[h][i], a00, 0u, a02, a03, vb[h][0][i >> 1][2 * (i & 1)], vb[h][0][i >> 1][2 * (i & 1) + 1]);
              mma_bf16(oa[h][i], a10, a11, 0u, a13, vb[h][1][i >> 1][2 * (i & 1)], vb[h][1][i >> 1][2 * (i & 1) + 1]);
            }
          }
#pragma unroll
          for (int o = 1; o <= 2; o <<= 1)
#pragma unroll
            for (int h = 0; h < 2; ++h)
#pragma unroll
              for (int r = 0; r < 2; ++r) sm[h][r] += __shfl_xor_sync(0xffffffffu, sm[h][r], o);
          mbar_wait(bar + (hp ? B_XOLD2 : B_XOLD), 1);
#pragma unroll
          for (int jp = 0; jp < 4; ++jp) ldsm_x4(xo[16 * hp + 4 * jp], xo[16 * hp + 4 * jp + 1], xo[16 * hp + 4 * jp + 2], xo[16 * hp + 4 * jp + 3], qad + (X ^ (jp << 5)));
#pragma unroll
          for (int h = 0; h < 2; ++h) {
            const float i0 = rcp(sm[h][0]), i1 = rcp(sm[h][1]);
#pragma unroll
            for (int np = 0; np < 2; ++np)
            {
              uint32_t (&o)[4] = oq[4 * hp + 2 * h + np];
              o[0] = pack_bf16(oa[h][2 * np][0] * i0, oa[h][2 * np][1] * i0); o[1] = pack_bf16(oa[h][2 * np][2] * i1, oa[h][2 * np][3] * i1);
              o[2] = pack_bf16(oa[h][2 * np + 1][0] * i0, oa[h][2 * np + 1][1] * i0); o[3] = pack_bf16(oa[h][2 * np + 1][2] * i1, oa[h][2 * np + 1][3] * i1);
              stsm_tag(qad + (X ^ (h << 6) ^ (np << 5)), o[0], o[1], o[2], o[3], make_tag(gq, t, 0u), 2 * h + np);
            }
          }
          __syncwarp();
          slab_out_half(sb + (XS + 1 - hp) * SLOT, g_o + (size_t)m0 * D_ + g * 128 + hp * 64, wrow0, lane);
          __syncwarp();
          if (lane == 0) mbar_arrive(bar + (hp ? B_ODONE : B_OH1));
          PROFT(lane == 0 && layer == PL && hp == 0, 128 + cw);
        };
        attend(0);
        if (DB1 == 2 && cu < 4) dump(1);
        if (cu == 4) nbar<15, 64>();
        else if (cu != 0) nbar_dyn(13 + (cu >> 2), 224);
        attend(1);
      } else {
#pragma unroll
        for (int i = 0; i < 32; ++i) kq[i] = pack_bf16(acc[2 * i], acc[2 * i + 1]);
        if (cu < 4) nbar<7, 256>();
        {
          const uint32_t vb = sb + (5 + 3 * wg) * SLOT + (rowq >> 1) + ((lchk ^ ((lane & 7) >> 1)) << 4);
#pragma unroll
          for (int jp = 8; jp < 16; ++jp)
            stsm_x4((vb ^ ((jp & 1) << 5)) + ((jp >> 1) & 3) * 4096,
                    pack_bf16(acc[8 * jp], acc[8 * jp + 1]), pack_bf16(acc[8 * jp + 2], acc[8 * jp + 3]),
                    pack_bf16(acc[8 * jp + 4], acc[8 * jp + 5]), pack_bf16(acc[8 * jp + 6], acc[8 * jp + 7]));
        }
        PROFT(tid_ == 128, layer * 16 + 2);
        Q_DONE();
        const uint32_t pA = sb + (3 + 3 * wg) * SLOT + (rowo & 8191);
        float sc0 = rs0 * L2E, sc1 = rs1 * L2E;
        const uint32_t wa0 = sb + SM_WPHI + lrow * 80 + lchk * 16;
        const uint32_t wu = c.cu >> 2, par = (layer >> 1) & 1;
        float p[2][4][4];
        uint32_t raw[2][4][4], ph[2][4][4];
        float kva[20], oa[2][20];
        auto kv_start = [&](int hp) {
#pragma unroll
          for (int h = 0; h < 2; ++h)
#pragma unroll
            for (int cp = 0; cp < 4; ++cp)
              stsm_x4(pA + hp * 16384 + h * 8192 + (X ^ (cp << 5)), ph[h][cp][0], ph[h][cp][1], ph[h][cp][2], ph[h][cp][3]);
          PROFT(tid_ == 128, layer * 16 + 11);
          fence_async_smem();
          nbar<1, 256>();
          const uint32_t hu = 2 * hp + wu;
          const uint32_t dP = (((sb + 3 * SLOT + hu * 8192) & 0x3FFFF) >> 4) | (512u << 16);
          const uint32_t dV = (((sb + 5 * SLOT + hu * 4096) & 0x3FFFF) >> 4) | (((SM_SD - 5 * SLOT - hu * 4096) >> 4) << 16);
          wgmma_fence();
#pragma unroll
          for (int ks = 0; ks < 8; ++ks)
            wgmma_n40_tt(kva, desc64(dP + (ks >> 2) * 3072 + (ks & 3) * 128, 0x40000040u),
                         desc64(dV + (ks >> 2) * (3072u - (2816u << 16)) + (ks & 3) * 64, 0x80000020u), ks != 0);
          wgmma_commit();
        };
        auto kv_end = [&](int hp) {
          wgmma_wait<0>();
#pragma unroll
          for (int i = 0; i < 20; ++i) asm volatile("" : "+f"(kva[i]) :: "memory");
          nbar_dyn(3 + wu, 128);
          PROFT(tid_ == 128, layer * 16 + 12);
          const bool od = lane & 1;
#pragma unroll
          for (int i = 0; i < 4; ++i)
            sts128(sb + (3 + hp) * SLOT + (cw * 128 + i * 32 + lane) * 16,
                   make_uint4(__float_as_uint(kva[4 * i]), __float_as_uint(kva[4 * i + 1]), __float_as_uint(kva[4 * i + 2]),
                              __float_as_uint(od == (i >= 2) ? 1.f : kva[4 * i + 3])));
          sts128(sb + (6 + hp) * SLOT + wg * 8192 + (wq * 32 + lane) * 16,
                 make_uint4(__float_as_uint(od ? kva[11] : kva[3]), __float_as_uint(od ? kva[15] : kva[7]), __float_as_uint(od ? kva[18] : kva[16]), __float_as_uint(1.f)));
          fence_async_smem();
          __syncwarp();
          if (lane == 0) mbar_arrive(bar + B_KVDONE - hp * 32);
          PROFT(tid_ == 128, layer * 16 + 3);
        };
        const uint4* const kvg = g_kv + (g * 2 + (layer >> 1)) * 2560 + cw * 128 + lane;
        uint4 u[5];
        auto kv_load = [&](int hp) {
#pragma unroll
          for (int i = 0; i < 4; ++i) u[i] = ld_relaxed4(kvg + hp * 1280 + i * 32);
          u[4] = ld_relaxed4(kvg + hp * 1280 + 1024 - cw * 96);
        };
        auto o_start = [&](int hp, const uint32_t (&pq)[2][4][4]) {
          PROFT(tid_ == 128 && hp == 0, layer * 16 + 10);
          if (hp == 0) mbar_wait(bar + B_KVDONE - 32, par);
          const bool od = lane & 1;
          uint32_t n = 0;
#pragma unroll 1
          while (!__all_sync(0xffffffffu, (od ? u[2].w : u[0].w) == 0x41800000u && (od ? u[3].w : u[1].w) == 0x41800000u && u[4].w == 0x41800000u)) {
#pragma unroll 1
            while (__any_sync(0xffffffffu, u[4].w < KVTH) && ++n < (1u << 20)) u[4].w = ld_relaxed(&kvg[hp * 1280 + 1024 - cw * 96].w);
            if (++n > (1u << 20)) { g_err = 6u; break; }
            kv_load(hp);
          }
          PROFT(tid_ == 128 && hp == 0, layer * 16 + 5);
          if (!od) { u[0].w = u[4].x; u[1].w = u[4].y; } else { u[2].w = u[4].x; u[3].w = u[4].y; }
#pragma unroll
          for (int i = 0; i < 4; i += 2)
            stsm_x4(sb + (5 + 3 * hp) * SLOT + rowo + (X ^ ((i & 2) << 4)),
                    pack_bf16(__uint_as_float(u[i].x), __uint_as_float(u[i].y)), pack_bf16(__uint_as_float(u[i].z), __uint_as_float(u[i].w)),
                    pack_bf16(__uint_as_float(u[i + 1].x), __uint_as_float(u[i + 1].y)), pack_bf16(__uint_as_float(u[i + 1].z), __uint_as_float(u[i + 1].w)));
          const uint32_t z2 = pack_bf16(__uint_as_float(u[4].z), __uint_as_float(u[4].z));
          if (t < 2) sts128(sb + (5 + 3 * hp) * SLOT + (wrow0 + gq + 8 * t) * 128 + ((4 ^ gq) << 4), make_uint4(z2, z2, z2, z2));
          fence_async_smem();
          nbar<1, 256>();
          PROFT(tid_ == 128 && hp == 1, layer * 16 + 4);
          const uint32_t dK = (((sb + (5 + 3 * hp) * SLOT) & 0x3FFFF) >> 4) | (512u << 16);
          wgmma_fence();
#pragma unroll
          for (int ks = 0; ks < 4; ++ks) {
#pragma unroll
            for (int hh = 0; hh < 2; ++hh) wgmma_n40_rs(oa[hh], pq[hh][ks], D128(dK + hh * 512 + ks * 128), ks != 0);
          }
          wgmma_commit();
        };
        auto o_end = [&](int hp) {
          wgmma_wait<0>();
#pragma unroll
          for (int i = 0; i < 20; ++i) asm volatile("" : "+f"(oa[0][i]), "+f"(oa[1][i]) :: "memory");
#pragma unroll
          for (int hh = 0; hh < 2; ++hh) {
            const float i0 = rcp(oa[hh][16] + 1e-6f), i1 = rcp(oa[hh][18] + 1e-6f);
            const uint32_t qad = sb + (3 + hp) * SLOT + rowo, hx = hh << 6;
#pragma unroll
            for (int np = 0; np < 2; ++np)
            {
              uint32_t (&o)[4] = oq[4 * hp + 2 * hh + np];
              o[0] = pack_bf16(oa[hh][8 * np] * i0, oa[hh][8 * np + 1] * i0); o[1] = pack_bf16(oa[hh][8 * np + 2] * i1, oa[hh][8 * np + 3] * i1);
              o[2] = pack_bf16(oa[hh][8 * np + 4] * i0, oa[hh][8 * np + 5] * i0); o[3] = pack_bf16(oa[hh][8 * np + 6] * i1, oa[hh][8 * np + 7] * i1);
              stsm_tag(qad + (X ^ hx ^ (np << 5)), o[0], o[1], o[2], o[3], make_tag(gq, t, 1u), 2 * hh + np);
            }
          }
          __syncwarp();
          slab_out_half(sb + (3 + hp) * SLOT, g_o + (size_t)m0 * D_ + g * 128 + hp * 64, wrow0, lane);
          __syncwarp();
          if (lane == 0) mbar_arrive(bar + (hp ? B_ODONE : B_OH1));
        };
#define XO_LOAD() \
        mbar_wait(bar + B_XOLD, 0); \
        mbar_wait(bar + B_XOLD2, 0); \
        _Pragma("unroll") for (int jp = 0; jp < 8; ++jp) \
          ldsm_x4(xo[4 * jp], xo[4 * jp + 1], xo[4 * jp + 2], xo[4 * jp + 3], sb + (XS + 1 - (jp >> 2)) * SLOT + rowo + (X ^ ((jp & 3) << 5)));
#define SC_RELOAD() \
        sc0 = __uint_as_float(lds_vol(sb + SM_RS + (16 + wrow0 + gq) * 4)) * L2E; sc1 = __uint_as_float(lds_vol(sb + SM_RS + (24 + wrow0 + gq) * 4)) * L2E;
        __syncwarp();
        phi_proj<0>(p, kq, wa0);
        phi_exp(raw[0], p[0], sc0, sc1);
        phi_exp(raw[1], p[1], sc0, sc1);
        phi_proj<16>(p, kq, wa0 + 5120);
        phi_norm<0>(ph, raw, kq, wa0, sc0, sc1, rs0, rs1);
        kv_start(0);
        phi_exp(raw[0], p[0], sc0, sc1);
        kv_end(0);
        if (RL & 1) { SC_RELOAD(); }
        XO_LOAD();
        phi_exp(raw[1], p[1], sc0, sc1);
        phi_proj<32>(p, kq, wa0);
        phi_norm<16>(ph, raw, kq, wa0 + 5120, sc0, sc1, rs0, rs1);
        kv_start(1);
        if (lane == 0) release2(bar + B_E3);
        phi_exp(raw[0], p[0], sc0, sc1);
        kv_end(1);
        if (RL & 2) { SC_RELOAD(); }
        kv_load(0);
        phi_exp(raw[1], p[1], sc0, sc1);
        phi_proj<48>(p, kq, wa0 + 5120);
        phi_norm<32>(ph, raw, kq, wa0, sc0, sc1, 1.f, 1.f);
        o_start(0, ph);
        phi_exp(raw[0], p[0], sc0, sc1);
        o_end(0);
        SC_RELOAD();
        kv_load(1);
        phi_exp(raw[1], p[1], sc0, sc1);
        phi_norm<48>(ph, raw, kq, wa0 + 5120, sc0, sc1, 1.f, 1.f);
        o_start(1, ph);
        o_end(1);
      }
      __syncwarp();
      PROFT(lane == 0 && layer == PL, 216 + cw);
      if (lane == 0) mbar_arrive(bar + B_EPI);
      PROFT(tid_ == 128, layer * 16 + 6);
    }
    {
      PHASE_CTX();
      const uint32_t wu = c.cu >> 2;
      const uint32_t dA0 = (((sb + wu * 8192) & 0x3FFFF) >> 4) | (1u << 16), dB0 = ((sb & 0x3FFFF) >> 4) | (512u << 16);
#pragma unroll
      for (int i = 0; i < 32; ++i) { acc[128 + 2 * i] = bf_lo(xo[i]); acc[129 + 2 * i] = bf_hi(xo[i]); }
      uint64_t ta = ((layer & 1) ? WO_A1 : WO_A0) >> 8, tw = (layer & 1) ? WO_B1 : WO_B0;
      mbar_wait(bar + B_FULLT, layer & 1);
      mbar_wait(bar + B_FULLT + 8, layer & 1);
      PROFT(tid_ == 128 && layer == PL, 160);
      wgmma_fence();
#pragma unroll
      for (int k = 0; k < 8; ++k) wgmma_n128_rs(acc, oq[k], D128(dB0 + ((uint32_t)(tw >> (k & 4)) & 15) * 1024 + (k & 3) * 128), 1);
      wgmma_commit();
      tw >>= 8;
      if (lane == 0) release2(bar + B_E2);
#pragma unroll 1
      for (int i = 2; i < 16; ++i) {
        mbar_wait(bar + B_FULLT + i * 8, layer & 1);
        PROFT(tid_ == 128 && layer == PL, 160 + i);
        tile_check(sb + ((uint32_t)ta & 15) * SLOT, g_o + (size_t)m0 * D_ + ((2 * g + (int)(WOORD >> (4 * i))) & 15) * 64, wrow0, lane, ~layer);
        const uint32_t da = dA0 + ((uint32_t)ta & 15) * 1024, db = dB0 + ((uint32_t)tw & 15) * 1024;
        ta >>= 4; tw >>= 4;
        if (WSK && i == 16 - WSK && wu) nbar<6, 256>();
        wgmma_fence();
#pragma unroll
        for (int k = 0; k < 4; ++k) wgmma_n128(acc, D128(da + k * 2), D128(db + k * 128), 1);
        wgmma_commit();
        if (WSK && i == 15 && !wu) asm volatile("bar.arrive 6, 256;" ::: "memory");
        wgmma_wait<1>();
        if (elected && i < 12) release2(bar + B_CONS + (i - 1) * 8);
        if (elected && (unsigned)(i - 13) < 2u && layer + 1 < NLAYERS) release2(bar + B_EMPTYS + (i - 13) * 8);
      }
      const bool last = layer == NLAYERS - 1;
      Tag xt = make_tag(gq, (last || !(UNS & 1)) ? 4 : t, lds_vol(sb + SM_EPOCH) + layer + 1);
      asm volatile("" : "+r"(xt.me), "+r"(xt.mo), "+r"(xt.tg) :: "memory");
      wgmma_wait<0>();
#pragma unroll
      for (int i = 128; i < 192; ++i) asm volatile("" : "+f"(acc[i]) :: "memory");
      if (elected && !last) release2(bar + B_EMPTYS + 16);
      PROFT(tid_ == 128, layer * 16 + 7);
      X_HALF(0, xt);
      if (last) {
        __syncwarp();
        slab_out_half(sb + XS * SLOT, c.out + (size_t)m0 * D_ + g * 128, wrow0, lane);
        X_HALF(1, (Tag{0u, 0u, 0u}));
        __syncwarp();
        slab_out_half(sb + (XS + 1) * SLOT, c.out + (size_t)m0 * D_ + g * 128 + 64, wrow0, lane);
        __syncwarp();
        if (lane == 0) mbar_arrive(bar + B_XDONE);
        PROFT(tid_ == 128, layer * 16 + 24);
        break;
      }
      __syncwarp();
      slab_out_half(sb + XS * SLOT, g_x + (size_t)m0 * D_ + g * 128, wrow0, lane, true);
      __syncwarp();
      if (lane == 0) mbar_arrive(bar + B_XH0);
      nbar_dyn(3 + wu, 128);
    }
  }
}

__device__ __forceinline__ void flag_fetch(uint32_t bar, uint32_t cp, const unsigned int* f) {
  asm volatile("{\n.reg .pred p;\nelect.sync _|p, 0xffffffff;\n@p mbarrier.expect_tx.relaxed.cta.shared::cta.b64 [%2], 64;\n"
               "@p cp.async.bulk.shared::cluster.global.mbarrier::complete_tx::bytes [%0], [%1], 64, [%2];\n}\n"
               ::"r"(cp), "l"(f), "r"(bar + 128) : "memory");
}
__device__ __forceinline__ void src_wait_async(uint32_t bar, uint32_t cp, const unsigned int* f, unsigned int target, int kb, uint32_t& ready, int lane) {
  uint32_t n = 0;
#pragma unroll 1
  while (true) {
    ready |= __ballot_sync(0xffffffffu, (int)(lds_vol(cp + (lane & 15) * 4) - target) >= 0);
    if ((ready >> kb) & 1) break;
    if (n > (1u << 20)) { g_err = 5u; break; }
    if ((n++ & PMOD) == 0) flag_fetch(bar, cp, f);
    __nanosleep(PSL);
  }
}

__device__ __forceinline__ int kblock0(int i, int g) {
  const int j = i >> 1, p = max(g, NCOM) + j - NCOM;
  return (j < NCOM ? j : p < 8 ? p : p - 8 + NCOM) * 2 + (i & 1);
}

__device__ __forceinline__ int wo_kblock(int m, int g) { return (2 * g + (int)((WOORD >> (4 * m)) & 15)) & 15; }

__global__ void __cluster_dims__(2, 1, 1) __launch_bounds__(384, 1)
mega_kernel(const __grid_constant__ CUtensorMap tm_x0, const __grid_constant__ CUtensorMap tm_x,
            const __grid_constant__ CUtensorMap tm_o,
            const __grid_constant__ CUtensorMap tm_wA, const __grid_constant__ CUtensorMap tm_wB,
            const __grid_constant__ CUtensorMap tm_woA, const __grid_constant__ CUtensorMap tm_woB,
                        const bf16* __restrict__ wB, const bf16* __restrict__ wphi, bf16* __restrict__ out) {
  extern __shared__ uint8_t smem_raw[];
  const uint32_t sb = (smem_u32(smem_raw) + 1023u) & ~1023u;
  const uint32_t bar = sb + SM_BAR;
  const int warp = __shfl_sync(0xffffffffu, threadIdx.x >> 5, 0), lane = threadIdx.x & 31;
  if (blockIdx.x >= 128) {
    const int xb = blockIdx.x - 128;
    const int ch = threadIdx.x % 96, rg = threadIdx.x / 96, gg = xb * 2 + ch / 48, sec = (ch % 48) >> 4;
    const uint4* src = reinterpret_cast<const uint4*>(wB + (size_t)rg * 3072 + (sec == 2 ? 0 : 1024 + sec * 1024) + gg * 128 + (ch & 15) * 8);
    float s[8] = {0.f, 0.f, 0.f, 0.f, 0.f, 0.f, 0.f, 0.f};
#pragma unroll 1
    for (int r0 = 0; r0 < 256; r0 += 32) {
      uint4 v[32];
#pragma unroll
      for (int r = 0; r < 32; ++r) v[r] = __ldg(src + (size_t)(r0 + r) * 1536);
#pragma unroll
      for (int r = 0; r < 32; ++r) {
        s[0] += bf_lo(v[r].x); s[1] += bf_hi(v[r].x); s[2] += bf_lo(v[r].y); s[3] += bf_hi(v[r].y);
        s[4] += bf_lo(v[r].z); s[5] += bf_hi(v[r].z); s[6] += bf_lo(v[r].w); s[7] += bf_hi(v[r].w);
      }
    }
    float* cd = g_cs + (ld_relaxed(&g_epoch) & 1) * 6144 + 3072 + xb * 768 + ch * 8;
    red_add4(cd, s[0], s[1], s[2], s[3]);
    red_add4(cd + 4, s[4], s[5], s[6], s[7]);
    nbar<1, 384>();
    if (threadIdx.x < 2) flag_add(&g_csflag[8 + xb * 2 + threadIdx.x].v);
    return;
  }
  const int bid = blockIdx.x;
  const int cr = bid & 1;
  const int g = (bid >> 1) & 7;
  const int rb = (bid >> 4) * 2 + cr;
  const int m0 = rb * 128;

  if (warp < 4) {
    asm volatile("setmaxnreg.dec.sync.aligned.u32 40;");
    asm volatile("barrier.cluster.arrive.relaxed.aligned;" ::: "memory");
    const unsigned int epoch = warp ? ld_relaxed(&g_epoch) : 0u;
    if (warp) cluster_wait();
    unsigned int xbase = epoch * NLAYERS;
    auto wo_a = [&](int layer, int m1) {
      uint64_t ts = ((layer & 1) ? WO_A1 : WO_A0) >> (4 * m1), td = ((layer & 1) ? WO_DA1 : WO_DA0) >> (4 * m1), tk = WOORD >> (4 * m1);
      uint32_t ready = 0u;
#pragma unroll 1
      for (int m = m1; m < 16; m += AW) {
        const int kb = (2 * g + (uint32_t)tk) & 15;
        uint32_t dst = sb + ((uint32_t)ts & 15) * SLOT, fb = bar + B_FULLT + m * 8, eb = bar + B_CONS + ((uint32_t)td & 15) * 8;
        int kc = kb * 64;
        ts >>= 4 * AW; td >>= 4 * AW; tk >>= 4 * AW;
        asm volatile("" : "+r"(dst), "+r"(fb), "+r"(eb), "+r"(kc));
        bool fr = false;
        if (!((ready >> kb) & 1)) {
          PROFT(m == 2 && lane == 0, 64 + layer * 16 + 2);
          if (EP && m > EP) src_wait_async(bar, bar + B_FLG, g_of + rb * 32, xbase + layer + 1, kb, ready, lane);
          else fr = src_wait_tma(g_of + rb * 32, xbase + layer + 1, 1u << kb, ready, lane, eb, layer & 1);
          fence_async_all();
        }
        if (m == 6) mbar_wait_u(bar + B_EPI, layer & 1);
        if (!fr) mbar_wait_u(eb, layer & 1);
        tma_2d_e(dst, &tm_o, kc, m0, fb);
        if (EP && m >= EP && (ready & 0xFFFFu) != 0xFFFFu) flag_fetch(bar, bar + B_FLG, g_of + rb * 32);
        PROFT(lane == 0 && layer == PL, 176 + m);
      }
    };
    auto wo_w = [&](int layer) {
      const CUtensorMap* tx = layer == 0 ? &tm_x0 : &tm_x;
      const CUtensorMap* two = (layer & 1) ? &tm_woB : &tm_woA;
      uint64_t ts = (layer & 1) ? WO_B1 : WO_B0, td = (layer & 1) ? WO_DB1 : WO_DB0, tk = WOORD;
      uint32_t pb = 0;
      fence_async_all();
      mbar_wait_u(bar + B_R0, layer & 1);
      expect_tx_e(bar + B_XOLD, 16384);
      tma_2d_e(sb + (XS + 1) * SLOT, tx, g * 128, m0, bar + B_XOLD);
#pragma unroll 1
      for (int m = 0; m < 16; ++m) {
        uint32_t dst = sb + ((uint32_t)ts & 15) * SLOT + cr * 8192, fb = bar + B_FULLT + m * 8, eb = bar + B_CONS + ((uint32_t)td & 15) * 8;
        int kc = ((2 * g + (uint32_t)tk) & 15) * 64;
        ts >>= 4; td >>= 4; tk >>= 4;
        asm volatile("" : "+r"(dst), "+r"(fb), "+r"(eb), "+r"(kc));
        if (eb < bar + B_E3 && pb >= bar + B_E3) mbar_wait_u(bar + B_E2, layer & 1);
        if (eb != pb) mbar_wait_u(eb, layer & 1);
        pb = eb;
        tma_2d_mc_e(dst, two, g * 128 + cr * 64, kc, fb);
        expect_tx_e(fb, m < 2 ? 16384 : 32768);
        PROFT(lane == 0 && layer == PL, 144 + m);
        if (m == ((layer & 1) ? XB2 : 0)) {
          expect_tx_e(bar + B_XOLD2, 16384);
          tma_2d_e(sb + XS * SLOT, tx, g * 128 + 64, m0, bar + B_XOLD2);
        }
      }
    };
    if (warp == 0) {
      cluster_wait();
      PROFT(lane == 0, 125);
#pragma unroll 1
      for (int layer = 0; layer < NLAYERS; ++layer) {
        const CUtensorMap* tx = layer == 0 ? &tm_x0 : &tm_x;
        const CUtensorMap* tw = (layer & 1) ? &tm_wB : &tm_wA;
        uint32_t s = layer == 0, u = 0, ready = layer == 0 ? 0xFFFFu : 0u;
#pragma unroll 1
        for (int i = s; i < 16; ++i) {
          const int kb = layer == 0 ? kblock0(i, g) : wo_kblock(i, g), kc = kb * 64;
          const uint32_t fb = bar + B_FULLS + s * 8;
          const uint32_t kd = sb + (((QK >> (4 * s)) & 15) + cr) * SLOT, qd = sb + ((QQ >> (4 * s)) & 15) * SLOT + cr * 8192;
          const uint32_t need = 1u << kb;
          const bool ext = i >= 2 || layer == 0, early = ext && (ready & need) == need;
          mbar_wait_u(bar + B_EMPTYS + s * 8, (u + (s ? layer : 0) + 1) & 1);
          if (early) tma_2d_e(sb + ((QA >> (4 * s)) & 15) * SLOT, tx, kc, m0, fb);
          tma_2d_mc_e(kd, tw, 1024 + cr * 1024 + g * 128, kc, fb);
          tma_2d_mc_e(kd + 8192, tw, 1024 + cr * 1024 + g * 128 + 64, kc, fb);
          tma_2d_mc_e(qd, tw, g * 128 + cr * 64, kc, fb);
          expect_tx_e(fb, ext ? 65536 : 49152);
          PROFT(lane == 0 && layer == 0 && i == 1, 31);
          if (layer == 0 && g >= NCOM && i == XPF + (((g - NCOM) * XPM) >> 2)) {
            if (i <= 2) mbar_wait_u(bar + B_FULLS, 0);
            tma_pf_e(&tm_x0, g * 128, m0);
            tma_pf_e(&tm_x0, g * 128 + 64, m0);
          }
          if (layer < 2 && i >= PFS) {
            const int j = i - PFS;
            if (j < 2) tma_pf_e(layer ? &tm_woB : &tm_woA, g * 128 + j * 64, rb * 64);
            else if (j < 8 && layer == 0) tma_pf_e(&tm_wB, ((j >> 1) - 1) * 1024 + g * 128 + (j & 1) * 64, rb * 64);
          }
          if (ext && !early) {
            PROFT(i == 2 && lane == 0, 64 + layer * 16 + 0);
            src_wait_tma(g_xf + rb * 32, xbase + layer + 1, need, ready, lane, fb, 0);
            PROFT(i == 2 && lane == 0, 64 + layer * 16 + 1);
            fence_async_all();
            tma_2d_e(sb + ((QA >> (4 * s)) & 15) * SLOT, tx, kc, m0, fb);
          }
          if (++s == 3) { s = 0; ++u; }
        }
        if (layer == 0) xbase = ld_relaxed(&g_epoch) * NLAYERS;
        if (PG & 1) mbar_wait_u(bar + B_OH1, layer & 1);
        if (PG & 4) mbar_wait_u(bar + B_E3, layer & 1);
        wo_a(layer, 2);
      }
    } else {
      if (warp >= 2) {
        const int h2 = threadIdx.x - 64;
        if (h2 < 16) sts_f(sb + SM_RS + h2 * 4, 0.f);
        if (h2 == 0) sts_f(sb + SM_EPOCH, __uint_as_float(epoch));
        if (h2 < 16) sts_f(bar + B_FLG + h2 * 4, __uint_as_float(xbase));
        mbar_wait_u(bar + B_FULLS, 0);
        colsum(&tm_wA, g_cs + (epoch & 1) * 6144, rb, g, warp - 2, 2, lane, warp == 2 ? sb + SM_SD : (sb + SM_BP + 1023u) & ~1023u, bar + B_CB + (warp - 2) * 8, 0);
#pragma unroll 1
        for (int i = h2; i < 320; i += 64) g_kv[(g * 16 + rb) * 320 + i] = make_uint4(0u, 0u, 0u, 0u);
        fence_async_all();
        nbar<5, 64>();
        if (h2 == 0) flag_add(&g_csflag[g].v);
        PROFT(h2 == 0, 242);
#pragma unroll 1
        for (int i = h2; i < 512; i += 256) {
          uint4 w[4];
#pragma unroll
          for (int j = 0; j < 4; ++j) w[j] = __ldg(reinterpret_cast<const uint4*>(wphi + (size_t)g * 4096) + i + j * 64);
#pragma unroll
          for (int j = 0; j < 4; ++j) sts128(sb + SM_WPHI + ((i >> 2) + j * 16) * 80 + (i & 3) * 16, w[j]);
        }
      }
      if (warp == 1) {
        if (lane >= 27) {
          const CUtensorMap* tm = lane == 27 ? &tm_o : lane == 28 ? &tm_wB : lane == 29 ? &tm_woA : lane == 30 ? &tm_woB : &tm_x;
          asm volatile("prefetch.tensormap [%0];" ::"l"(tm) : "memory");
        }
        __syncwarp();
        {
#pragma unroll 1
          for (int e = 0;; ++e) {
            if (e > 0 && e < NLAYERS) {
              mbar_wait_u(bar + B_XH0, (e - 1) & 1);
              flag_set_x(g_xf + rb * 32 + 2 * g, xbase + e + 1, UNS & 1);
            }
            mbar_wait_u(bar + B_XDONE, e & 1);
            PROFT(e < 4, 64 + e * 16 + 4);
            if (e == NLAYERS) {
              if (bid == 0) g_epoch = epoch + 1;
              break;
            }
            PROFT(e < 4, 64 + e * 16 + 5);
            flag_set(g_xf + rb * 32 + 2 * g + 1, xbase + e + 1);
            PROFT(e < 4, 64 + e * 16 + 7);
            if ((e & 1) == 0) {
#pragma unroll 1
              for (int hp = 0; hp < 2; ++hp) {
                uint4* kvl = g_kv + ((g * 2 + (e >> 1)) * 2 + hp) * 1280;
                mbar_wait_u(bar + B_KVDONE - hp * 32, (e >> 1) & 1);
                PROFT(e == PL, 243 + hp * 4);
                bulk_red_add_e(kvl + rb * 64, sb + (3 + hp) * SLOT + rb * 1024, 16384 - rb * 1024);
                if (rb) bulk_red_add_e(kvl, sb + (3 + hp) * SLOT, rb * 1024);
                bulk_red_add_e(kvl + 1024, sb + (6 + hp) * SLOT, 2048);
                bulk_red_add_e(kvl + 1152, sb + (6 + hp) * SLOT + 8192, 2048);
                bulk_commit();
                PROFT(e < 4, 64 + e * 16 + 6);
              }
              bulk_wait_read0();
              __syncwarp();
              if (lane < 2) release2(bar + B_E1);
              __syncwarp();
            }
            mbar_wait_u(bar + B_OH1, e & 1);
            PROFT(e == PL, 251);
            flag_set_x(g_of + rb * 32 + 2 * g, xbase + e + 1, UNS & 2);
            PROFT(e < 4, 64 + e * 16 + 9);
            mbar_wait_u(bar + B_ODONE, e & 1);
            PROFT(e < 4, 64 + e * 16 + 8);
            flag_set_x(g_of + rb * 32 + 2 * g + 1, xbase + e + 1, UNS & 4);
            PROFT(e < 4, 64 + e * 16 + 11);
          }
        }
      } else {
        const int h2 = threadIdx.x - 64;
        const float* cs = g_cs + (epoch & 1) * 6144;
#pragma unroll 1
        for (int layer = 0; layer < NLAYERS; ++layer) {
          if (warp == 2 && layer < 2) {
            if ((PG & 2) && layer) mbar_wait_u(bar + B_XH0, 0);
            if (lane == 0) flag_wait_t<CSLP>(&g_csflag[layer * 8 + g].v, (epoch + 1) * (16u + layer));
            __syncwarp();
            float4 a[3];
#pragma unroll
            for (int i = 0; i < 3; ++i) a[i] = __ldcg(reinterpret_cast<const float4*>(cs + layer * 3072 + g * 384) + i * 32 + lane);
#pragma unroll 1
            for (int i = 0; i < 3; ++i) {
              const float av[4] = {a[0].x, a[0].y, a[0].z, a[0].w};
              a[0] = a[1]; a[1] = a[2];
#pragma unroll
              for (int j = 0; j < 4; ++j) {
                const float c1 = bf16r(av[j]), c2 = bf16r(av[j] - c1), c3 = (av[j] - c1) - c2;
                sts128(sb + SM_BP + layer * 6144 + ((i * 32 + lane) * 4 + j) * 16, make_uint4(pack_bf16(c1, c2), pack_bf16(c3, 0.f), 0u, 0u));
              }
            }
            fence_async_smem();
            __syncwarp();
            if (lane == 0) mbar_arrive(bar + (layer ? B_CS2 : B_CS));
            PROFT(lane == 0, 64 + layer * 16 + 12);
            if (layer == 0) {
              uint4* hz = g_halo + (rb * 8 + g) * 1024;
#pragma unroll 2
              for (int i = lane; i < 1024; i += 32) hz[i] = make_uint4(0u, 0u, 0u, 0u);
              if (lane < 12) reinterpret_cast<float4*>(g_cs + ((epoch & 1) ^ 1) * 6144 + bid * 48)[lane] = make_float4(0.f, 0.f, 0.f, 0.f);
              g_stats[(2 + (lane >> 4)) * S_ + m0 + g * 16 + (lane & 15)] = make_float2(0.f, 0.f);
              __syncwarp();
              if (lane == 0) flag_add(&g_csflag[8 + g].v);
            }
          }
          if (warp == 3) {
            const bool hal = (layer & 1) && rb > 0;
            {
              uint32_t rdy = 0u;
              src_wait<SSL>(g_xf + rb * 32, xbase + layer + 1, 0xAAAAu, rdy, lane);
              rdy = 0u;
              if (hal) src_wait<256>(g_xf + (rb - 1) * 32, xbase + layer + 1, 0xAAAAu, rdy, lane);
            }
            float2 u[5];
            const float2* sp = g_stats + layer * S_ + m0 + lane;
#pragma unroll
            for (int i = 0; i < 4; ++i) u[i] = __ldcg(sp + i * 32);
            u[4] = __ldcg(hal ? sp - 16 : sp);
            if (layer == 3) g_stats[(lane >> 4) * S_ + m0 + g * 16 + (lane & 15)] = make_float2(0.f, 0.f);
#pragma unroll
            for (int i = 0; i < 5; ++i) {
              const int r = i < 4 ? 16 + i * 32 + lane : lane;
              const float mean = u[i].x * (1.f / D_);
              const float var = fmaxf(fmaf(-u[i].x, mean, u[i].y) * (1.f / D_), 0.f);
              float sd;
              asm("sqrt.approx.f32 %0, %1;" : "=f"(sd) : "f"(bf16r(bf16r(var) + 1e-5f)));
              sd = bf16r(sd);
              if (i < 4 || hal) sts_f(sb + SM_RS + r * 4, rcp(sd));
              if (i < 4) {
                const float hm = -0.5f * bf16r(mean);
                const uint32_t s2 = pack_bf16(sd, sd);
                if (!(layer & 1)) sts128(sb + SM_SD + (r - 16) * 64 + ((r >> 1) & 3) * 16, make_uint4(s2, s2, s2, s2));
                sts128(sb + SM_AP + (r - 16) * 16, make_uint4(pack_bf16(hm, hm), pack_bf16(hm, 0.f), 0u, 0u));
              }
            }
            fence_async_smem();
            __syncwarp();
            if (lane == 0) mbar_arrive(bar + B_STAT);
            PROFT(lane == 0, 64 + layer * 16 + 14);
            wo_w(__shfl_sync(0xffffffffu, layer, 0));
          }
        }
      }
    }
    __syncwarp();
    asm volatile("barrier.cluster.arrive.relaxed.aligned;\nbarrier.cluster.wait.aligned;\n" ::: "memory");
  } else {
    if (warp == 5) {
      if (lane == 0) {
        mbar_init(bar + B_FULLS, 1);
        asm volatile("fence.mbarrier_init.release.cluster;" ::: "memory");
      }
      __syncwarp();
      expect_tx_e(bar + B_FULLS, 65536);
      tma_2d_e(sb + XS * SLOT, &tm_x0, 0, m0, bar + B_FULLS);
#pragma unroll
      for (int j = 0; j < 6; ++j)
        tma_2d_e(sb + (j < 4 ? j + 4 : j - 2) * 8192, &tm_wA, (j < 4 ? 1024 + (j >> 1) * 1024 : 0) + g * 128 + (j & 1) * 64, 0, bar + B_FULLS);
      PROFT(lane == 0, 241);
    }
    if (lane < 8 && warp != 5 && threadIdx.x != 128) {
      const int i = (warp - 4) * 8 + lane;
      mbar_init(bar + i * 8, i < 32 ? 1u << ((BAR_CNT >> (2 * i)) & 3) : i < 48 ? 1u : (i == 59 || i == 60 || i == 62) ? 16u : (i == 48 || i == 63) ? 8u : 4u);
      asm volatile("fence.mbarrier_init.release.cluster;" ::: "memory");
    }
    __syncwarp();
    asm volatile("barrier.cluster.arrive.relaxed.aligned;" ::: "memory");
    asm volatile("setmaxnreg.inc.sync.aligned.u32 232;");
    cluster_wait();
    PROFT(threadIdx.x == 128, 0);
    Ctx c; c.sb = sb; c.g = g; c.rb = rb; c.cu = warp - 4; c.out = out;
    consumer(c);
    asm volatile("bar.warp.sync 0xffffffff;\nbarrier.cluster.arrive.relaxed.aligned;\nbarrier.cluster.wait.aligned;\n" ::: "memory");
  }
}

typedef CUresult (*PFN_encodeTiled)(CUtensorMap*, CUtensorMapDataType, cuuint32_t, void*, const cuuint64_t*, const cuuint64_t*,
                                    const cuuint32_t*, const cuuint32_t*, CUtensorMapInterleave, CUtensorMapSwizzle,
                                    CUtensorMapL2promotion, CUtensorMapFloatOOBfill);

static CUtensorMap make_map(PFN_encodeTiled enc, const void* ptr, uint64_t cols, uint64_t rows, uint32_t box_c, uint32_t box_r, uint32_t nb = 1) {
  CUtensorMap m;
  cuuint64_t dims[3] = {nb > 1 ? box_c : cols, rows, cols / box_c};
  cuuint64_t strides[2] = {cols * 2, box_c * 2};
  cuuint32_t box[3] = {box_c, box_r, nb};
  cuuint32_t es[3] = {1, 1, 1};
  CUresult r = enc(&m, CU_TENSOR_MAP_DATA_TYPE_BFLOAT16, nb > 1 ? 3 : 2, const_cast<void*>(ptr), dims, strides, box, es, CU_TENSOR_MAP_INTERLEAVE_NONE,
      CU_TENSOR_MAP_SWIZZLE_128B, CU_TENSOR_MAP_L2_PROMOTION_L2_256B, CU_TENSOR_MAP_FLOAT_OOB_FILL_NONE);
  (void)r;
  return m;
}

extern "C" void kernel_launch(void* const* d_in, const int* in_sizes, int n_in, void* d_out, int out_size) {
  const bf16* A_x = (const bf16*)d_in[0];
  const bf16* A_wqkv = (const bf16*)d_in[1];
  const bf16* A_wphi = (const bf16*)d_in[2];
  const bf16* A_wo = (const bf16*)d_in[3];
  const bf16* B_wqkv = (const bf16*)d_in[5];
  const bf16* B_wo = (const bf16*)d_in[6];
  bf16* out = (bf16*)d_out;

  static PFN_encodeTiled enc = nullptr;
  static bf16 *p_x, *p_o;
  if (!enc) {
    void* fn = nullptr; cudaDriverEntryPointQueryResult qr;
    cudaGetDriverEntryPoint("cuTensorMapEncodeTiled", &fn, cudaEnableDefault, &qr);
    enc = (PFN_encodeTiled)fn;
    cudaGetSymbolAddress((void**)&p_x, g_x);
    cudaGetSymbolAddress((void**)&p_o, g_o);
    cudaFuncSetAttribute(mega_kernel, cudaFuncAttributeMaxDynamicSharedMemorySize, SM_TOTAL);
  }
  CUtensorMap tm_x0 = make_map(enc, A_x, 1024, 2048, 64, 128);
  CUtensorMap tm_x = make_map(enc, p_x, 1024, 2048, 64, 128);
  CUtensorMap tm_o = make_map(enc, p_o, 1024, 2048, 64, 128);
  CUtensorMap tm_wA = make_map(enc, A_wqkv, 3072, 1024, 64, 64);
  CUtensorMap tm_wB = make_map(enc, B_wqkv, 3072, 1024, 64, 64);
  CUtensorMap tm_woA = make_map(enc, A_wo, 1024, 1024, 64, 64);
  CUtensorMap tm_woB = make_map(enc, B_wo, 1024, 1024, 64, 64);
  mega_kernel<<<128 + NX, 384, SM_TOTAL, cudaStreamPerThread>>>(tm_x0, tm_x, tm_o, tm_wA, tm_wB, tm_woA, tm_woB,
                                                           B_wqkv, A_wphi, out);
}
```

```cpp
#include <cuda_runtime.h>
#include <cuda_bf16.h>
#include <cuda.h>
#include <stdint.h>

typedef __nv_bfloat16 bf16;

constexpr int S_ = 2048, D_ = 1024;

struct __align__(128) Flag { unsigned int v; unsigned int pad[31]; };
__device__ __align__(1024) bf16 g_x[S_ * D_];
__device__ __align__(1024) bf16 g_o[S_ * D_];
__device__ __align__(1024) uint4 g_halo[128 * 2 * 512];
__device__ __align__(1024) uint4 g_kv[8 * 2 * 2 * 1280];
__device__ __align__(1024) float2 g_stats[4 * S_];
__device__ __align__(1024) float g_cs[2 * 2 * 3072];
__device__ Flag g_csflag[16];
__device__ __align__(128) unsigned int g_xf[16 * 32], g_of[16 * 32];
__device__ unsigned int g_epoch, g_err;
#define PROFT(cond, idx) asm volatile("" ::: "memory")

__device__ __forceinline__ uint32_t smem_u32(const void* p) { return (uint32_t)__cvta_generic_to_shared(p); }
__device__ __forceinline__ void mbar_init(uint32_t bar, uint32_t count) {
  asm volatile("mbarrier.init.shared::cta.b64 [%0], %1;" ::"r"(bar), "r"(count) : "memory");
}
__device__ __forceinline__ void mbar_expect_tx(uint32_t bar, uint32_t bytes) {
  asm volatile("mbarrier.arrive.expect_tx.shared::cta.b64 _, [%0], %1;" ::"r"(bar), "r"(bytes) : "memory");
}
__device__ __forceinline__ void mbar_arrive(uint32_t bar) {
  asm volatile("mbarrier.arrive.shared::cta.b64 _, [%0];" ::"r"(bar) : "memory");
}
__device__ __forceinline__ bool mbar_try_wait(uint32_t bar, uint32_t parity) {
  uint32_t ok;
  asm volatile("{\n.reg .pred p;\nmbarrier.try_wait.parity.shared::cta.b64 p, [%1], %2;\nselp.b32 %0, 1, 0, p;\n}\n"
               : "=r"(ok) : "r"(bar), "r"(parity) : "memory");
  return ok != 0;
}
__device__ __forceinline__ bool mbar_test_wait(uint32_t bar, uint32_t parity) {
  uint32_t ok;
  asm volatile("{\n.reg .pred p;\nmbarrier.test_wait.parity.shared::cta.b64 p, [%1], %2;\nselp.b32 %0, 1, 0, p;\n}\n"
               : "=r"(ok) : "r"(bar), "r"(parity) : "memory");
  return ok != 0;
}
__device__ __forceinline__ uint64_t gtimer() {
  uint64_t t; asm volatile("mov.u64 %0, %globaltimer;" : "=l"(t)); return t;
}
__device__ __forceinline__ void mbar_wait(uint32_t bar, uint32_t parity) {
  uint32_t n = 0;
#pragma unroll 1
  while (!mbar_try_wait(bar, parity)) {
    if (++n > (1u << 22)) { g_err = 1u; break; }
  }
}
__device__ __forceinline__ unsigned int ld_acquire(const unsigned int* p) {
  unsigned int v; asm volatile("ld.acquire.gpu.global.u32 %0, [%1];" : "=r"(v) : "l"(p) : "memory"); return v;
}
__device__ __forceinline__ void flag_add(unsigned int* p) {
  asm volatile("red.release.gpu.global.add.u32 [%0], 1;" ::"l"(p) : "memory");
}
__device__ __forceinline__ void flag_set(unsigned int* p, unsigned int v) {
  asm volatile("st.release.gpu.global.u32 [%0], %1;" ::"l"(p), "r"(v) : "memory");
}
__device__ __forceinline__ void flag_set_x(unsigned int* p, unsigned int v, bool rlx) {
  if (rlx) asm volatile("st.relaxed.gpu.global.u32 [%0], %1;" ::"l"(p), "r"(v) : "memory"); else flag_set(p, v);
}
template <int SLEEP>
__device__ __forceinline__ void src_wait(const unsigned int* f, unsigned int target, uint32_t need, uint32_t& ready, int lane) {
  uint32_t n = 0;
#pragma unroll 1
  while ((ready & need) != need) {
    const unsigned int v = ld_acquire(f + (lane & 15));
    ready = __ballot_sync(0xffffffffu, (int)(v - target) >= 0);
    if (SLEEP) { if ((ready & need) != need) __nanosleep(SLEEP); }
    if (++n > (1u << 20)) { g_err = 3u; break; }
  }
  __syncwarp();
}
__device__ __forceinline__ unsigned int ld_relaxed(const unsigned int* p) {
  unsigned int v; asm volatile("ld.relaxed.gpu.global.u32 %0, [%1];" : "=r"(v) : "l"(p) : "memory"); return v;
}
__device__ __forceinline__ bool src_wait_tma(const unsigned int* f, unsigned int target, uint32_t need, uint32_t& ready, int lane, uint32_t eb, uint32_t par) {
  uint32_t n = 0;
  bool fr = false;
#pragma unroll 1
  while ((ready & need) != need) {
    const unsigned int v = ld_acquire(f + (lane & 15));
    fr = __all_sync(0xffffffffu, mbar_test_wait(eb, par));
    ready = __ballot_sync(0xffffffffu, (int)(v - target) >= 0);
    if (++n > (1u << 20)) { g_err = 3u; break; }
  }
  return fr;
}
__device__ __forceinline__ uint4 ld_relaxed4(const uint4* p) {
  uint4 v; asm volatile("ld.relaxed.gpu.global.v4.u32 {%0,%1,%2,%3}, [%4];" : "=r"(v.x), "=r"(v.y), "=r"(v.z), "=r"(v.w) : "l"(p) : "memory"); return v;
}
__device__ __forceinline__ void st_relaxed4(uint4* p, uint32_t a, uint32_t b, uint32_t c, uint32_t d) {
  asm volatile("st.relaxed.gpu.global.v4.u32 [%0], {%1,%2,%3,%4};" ::"l"(p), "r"(a), "r"(b), "r"(c), "r"(d) : "memory");
}
template <int SLEEP>
__device__ __forceinline__ void flag_wait_t(const unsigned int* p, unsigned int target) {
  uint32_t n = 0;
#pragma unroll 1
  while ((int)(ld_acquire(p) - target) < 0) {
    if (SLEEP) __nanosleep(SLEEP);
    if (++n > (1u << 20)) { g_err = 2u; break; }
  }
}
__device__ __forceinline__ void flag_wait(const unsigned int* p, unsigned int target) { flag_wait_t<0>(p, target); }
__device__ __forceinline__ void flag_wait_slow(const unsigned int* p, unsigned int target) { flag_wait_t<256>(p, target); }
__device__ __forceinline__ void tma_load_2d(uint32_t dst, const CUtensorMap* tm, int c0, int c1, uint32_t bar) {
  asm volatile("cp.async.bulk.tensor.2d.shared::cluster.global.mbarrier::complete_tx::bytes [%0], [%1, {%2, %3}], [%4];"
               ::"r"(dst), "l"(tm), "r"(c0), "r"(c1), "r"(bar) : "memory");
}
__device__ __forceinline__ void tma_load_2d_mc(uint32_t dst, const CUtensorMap* tm, int c0, int c1, uint32_t bar, uint16_t mask) {
  asm volatile("cp.async.bulk.tensor.2d.shared::cluster.global.mbarrier::complete_tx::bytes.multicast::cluster [%0], [%1, {%2, %3}], [%4], %5;"
               ::"r"(dst), "l"(tm), "r"(c0), "r"(c1), "r"(bar), "h"(mask) : "memory");
}
__device__ __forceinline__ void mbar_wait_u(uint32_t bar, uint32_t parity) {
  uint32_t n = 0;
#pragma unroll 1
  while (!__all_sync(0xffffffffu, mbar_try_wait(bar, parity))) {
    if (++n > (1u << 22)) { g_err = 1u; break; }
  }
}
__device__ __forceinline__ void expect_tx_e(uint32_t bar, uint32_t bytes) {
  asm volatile("{\n.reg .pred p;\nelect.sync _|p, 0xffffffff;\n@p mbarrier.arrive.expect_tx.shared::cta.b64 _, [%0], %1;\n}\n" ::"r"(bar), "r"(bytes) : "memory");
}
__device__ __forceinline__ void tma_2d_e(uint32_t dst, const CUtensorMap* tm, int c0, int c1, uint32_t bar) {
  asm volatile("{\n.reg .pred p;\nelect.sync _|p, 0xffffffff;\n"
               "@p cp.async.bulk.tensor.2d.shared::cluster.global.mbarrier::complete_tx::bytes [%0], [%1, {%2, %3}], [%4];\n}\n"
               ::"r"(dst), "l"(tm), "r"(c0), "r"(c1), "r"(bar) : "memory");
}
__device__ __forceinline__ void tma_2d_mc_e(uint32_t dst, const CUtensorMap* tm, int c0, int c1, uint32_t bar) {
  asm volatile("{\n.reg .pred p;\nelect.sync _|p, 0xffffffff;\n"
               "@p cp.async.bulk.tensor.2d.shared::cluster.global.mbarrier::complete_tx::bytes.multicast::cluster [%0], [%1, {%2, %3}], [%4], %5;\n}\n"
               ::"r"(dst), "l"(tm), "r"(c0), "r"(c1), "r"(bar), "h"((uint16_t)3) : "memory");
}
__device__ __forceinline__ void tma_pf_e(const CUtensorMap* tm, int c0, int c1) {
  asm volatile("{\n.reg .pred p;\nelect.sync _|p, 0xffffffff;\n"
               "@p cp.async.bulk.prefetch.tensor.2d.L2.global.tile [%0, {%1, %2}];\n}\n" ::"l"(tm), "r"(c0), "r"(c1) : "memory");
}
__device__ __forceinline__ void tma_2d_to_e(uint32_t dst, const CUtensorMap* tm, int c0, int c1, uint32_t bar, uint32_t mask) {
  asm volatile("{\n.reg .pred p;\nelect.sync _|p, 0xffffffff;\n"
               "@p cp.async.bulk.tensor.2d.shared::cluster.global.mbarrier::complete_tx::bytes.multicast::cluster [%0], [%1, {%2, %3}], [%4], %5;\n}\n"
               ::"r"(dst), "l"(tm), "r"(c0), "r"(c1), "r"(bar), "h"((uint16_t)mask) : "memory");
}
__device__ __forceinline__ void tma_3d_mc_e(uint32_t dst, const CUtensorMap* tm, int c1, int c2, uint32_t bar) {
  asm volatile("{\n.reg .pred p;\nelect.sync _|p, 0xffffffff;\n"
               "@p cp.async.bulk.tensor.3d.shared::cluster.global.mbarrier::complete_tx::bytes.multicast::cluster [%0], [%1, {%6, %2, %3}], [%4], %5;\n}\n"
               ::"r"(dst), "l"(tm), "r"(c1), "r"(c2), "r"(bar), "h"((uint16_t)3), "r"(0) : "memory");
}
__device__ __forceinline__ uint32_t poll_flags(const unsigned int* f, unsigned int target, int lane) {
  const unsigned int v = ld_acquire(f + (lane & 15));
  const uint32_t r = __ballot_sync(0xffffffffu, (int)(v - target) >= 0);
  __syncwarp();
  return r;
}
__device__ __forceinline__ void mbar_arrive_cluster(uint32_t local_bar, uint32_t rank) {
  asm volatile("{\n.reg .b32 ra;\nmapa.shared::cluster.u32 ra, %0, %1;\nmbarrier.arrive.shared::cluster.b64 _, [ra];\n}\n"
               ::"r"(local_bar), "r"(rank) : "memory");
}
__device__ __forceinline__ void release2(uint32_t bar) { mbar_arrive_cluster(bar, 0); mbar_arrive_cluster(bar, 1); }
__device__ __forceinline__ void tma_store_2d(const CUtensorMap* tm, uint32_t src, int c0, int c1) {
  asm volatile("cp.async.bulk.tensor.2d.global.shared::cta.bulk_group [%0, {%2, %3}], [%1];"
               ::"l"(tm), "r"(src), "r"(c0), "r"(c1) : "memory");
}
__device__ __forceinline__ void bulk_store(void* dst, uint32_t src, uint32_t bytes) {
  asm volatile("cp.async.bulk.global.shared::cta.bulk_group [%0], [%1], %2;" ::"l"(dst), "r"(src), "r"(bytes) : "memory");
}
__device__ __forceinline__ void bulk_load(uint32_t dst, const void* src, uint32_t bytes, uint32_t bar) {
  asm volatile("cp.async.bulk.shared::cluster.global.mbarrier::complete_tx::bytes [%0], [%1], %2, [%3];" ::"r"(dst), "l"(src), "r"(bytes), "r"(bar) : "memory");
}
__device__ __forceinline__ void bulk_red_add(void* dst, uint32_t src, uint32_t bytes) {
  asm volatile("cp.reduce.async.bulk.global.shared::cta.bulk_group.add.f32 [%0], [%1], %2;" ::"l"(dst), "r"(src), "r"(bytes) : "memory");
}
__device__ __forceinline__ void bulk_red_add_e(void* dst, uint32_t src, uint32_t bytes) {
  asm volatile("{\n.reg .pred p;\nelect.sync _|p, 0xffffffff;\n@p cp.reduce.async.bulk.global.shared::cta.bulk_group.add.f32 [%0], [%1], %2;\n}\n" ::"l"(dst), "r"(src), "r"(bytes) : "memory");
}
__device__ __forceinline__ void bulk_commit() { asm volatile("cp.async.bulk.commit_group;" ::: "memory"); }
__device__ __forceinline__ void bulk_wait_read0() { asm volatile("cp.async.bulk.wait_group.read 0;" ::: "memory"); }
__device__ __forceinline__ void bulk_wait0() { asm volatile("cp.async.bulk.wait_group 0;" ::: "memory"); }
__device__ __forceinline__ void fence_async_smem() { asm volatile("fence.proxy.async.shared::cta;" ::: "memory"); }
__device__ __forceinline__ void fence_async_all() { asm volatile("fence.proxy.async.global;" ::: "memory"); }
__device__ __forceinline__ void wgmma_fence() { asm volatile("wgmma.fence.sync.aligned;" ::: "memory"); }
__device__ __forceinline__ void wgmma_commit() { asm volatile("wgmma.commit_group.sync.aligned;" ::: "memory"); }
template <int N> __device__ __forceinline__ void wgmma_wait() { asm volatile("wgmma.wait_group.sync.aligned %0;" ::"n"(N) : "memory"); }
__device__ __forceinline__ void cluster_arrive() { asm volatile("barrier.cluster.arrive.release.aligned;" ::: "memory"); }
__device__ __forceinline__ void cluster_wait() { asm volatile("barrier.cluster.wait.acquire.aligned;" ::: "memory"); }
template <int ID, int N> __device__ __forceinline__ void nbar() { asm volatile("bar.sync %0, %1;" ::"n"(ID), "n"(N) : "memory"); }
__device__ __forceinline__ uint64_t make_desc(uint32_t addr, uint32_t lbo_bytes, uint32_t sbo_bytes) {
  uint64_t d = 0;
  d |= (uint64_t)((addr & 0x3FFFF) >> 4);
  d |= (uint64_t)((lbo_bytes >> 4) & 0x3FFF) << 16;
  d |= (uint64_t)((sbo_bytes >> 4) & 0x3FFF) << 32;
  d |= (uint64_t)1 << 62;
  return d;
}
__device__ __forceinline__ uint64_t desc64(uint32_t lo, uint32_t hi) { return (uint64_t)lo | ((uint64_t)hi << 32); }
__device__ __forceinline__ uint32_t pack_bf16(float lo, float hi) {
  uint32_t r; asm("cvt.rn.bf16x2.f32 %0, %1, %2;" : "=r"(r) : "f"(hi), "f"(lo)); return r;
}
__device__ __forceinline__ uint32_t mul_bf16x2(uint32_t a, uint32_t s, bool hi) {
  __nv_bfloat162 x = *reinterpret_cast<__nv_bfloat162*>(&a), y = *reinterpret_cast<__nv_bfloat162*>(&s);
  x = __hmul2(x, hi ? __high2bfloat162(y) : __low2bfloat162(y));
  return *reinterpret_cast<uint32_t*>(&x);
}
__device__ __forceinline__ float bf16r(float x) { return __bfloat162float(__float2bfloat16_rn(x)); }
__device__ __forceinline__ float bf_lo(uint32_t u) { return __uint_as_float(u << 16); }
__device__ __forceinline__ float bf_hi(uint32_t u) { return __uint_as_float(u & 0xFFFF0000u); }
__device__ __forceinline__ float ex2(float x) { float r; asm("ex2.approx.ftz.f32 %0, %1;" : "=f"(r) : "f"(x)); return r; }
__device__ __forceinline__ float rcp(float x) { float r; asm("rcp.approx.ftz.f32 %0, %1;" : "=f"(r) : "f"(x)); return r; }
__device__ __forceinline__ void mma_bf16(float (&d)[4], uint32_t a0, uint32_t a1, uint32_t a2, uint32_t a3, uint32_t b0, uint32_t b1) {
  asm("mma.sync.aligned.m16n8k16.row.col.f32.bf16.bf16.f32 {%0,%1,%2,%3}, {%4,%5,%6,%7}, {%8,%9}, {%0,%1,%2,%3};"
               : "+f"(d[0]), "+f"(d[1]), "+f"(d[2]), "+f"(d[3]) : "r"(a0), "r"(a1), "r"(a2), "r"(a3), "r"(b0), "r"(b1));
}
__device__ __forceinline__ void ldsm_x4(uint32_t& r0, uint32_t& r1, uint32_t& r2, uint32_t& r3, uint32_t addr) {
  asm volatile("ldmatrix.sync.aligned.m8n8.x4.shared.b16 {%0,%1,%2,%3}, [%4];"
               : "=r"(r0), "=r"(r1), "=r"(r2), "=r"(r3) : "r"(addr) : "memory");
}
__device__ __forceinline__ void ldsm_x4_t(uint32_t& r0, uint32_t& r1, uint32_t& r2, uint32_t& r3, uint32_t addr) {
  asm volatile("ldmatrix.sync.aligned.m8n8.x4.trans.shared.b16 {%0,%1,%2,%3}, [%4];"
               : "=r"(r0), "=r"(r1), "=r"(r2), "=r"(r3) : "r"(addr) : "memory");
}
__device__ __forceinline__ void ldsm_x2_t(uint32_t& r0, uint32_t& r1, uint32_t addr) {
  asm volatile("ldmatrix.sync.aligned.m8n8.x2.trans.shared.b16 {%0,%1}, [%2];"
               : "=r"(r0), "=r"(r1) : "r"(addr) : "memory");
}
__device__ __forceinline__ void stsm_x4(uint32_t addr, uint32_t r0, uint32_t r1, uint32_t r2, uint32_t r3) {
  asm volatile("stmatrix.sync.aligned.m8n8.x4.shared.b16 [%0], {%1,%2,%3,%4};"
               ::"r"(addr), "r"(r0), "r"(r1), "r"(r2), "r"(r3) : "memory");
}
__device__ __forceinline__ void stsm_x4_p(bool on, uint32_t addr, uint32_t r0, uint32_t r1, uint32_t r2, uint32_t r3) {
  asm volatile("{\n.reg .pred p;\nsetp.ne.b32 p, %5, 0;\n@p stmatrix.sync.aligned.m8n8.x4.shared.b16 [%0], {%1,%2,%3,%4};\n}\n"
               ::"r"(addr), "r"(r0), "r"(r1), "r"(r2), "r"(r3), "r"((int)on) : "memory");
}
__device__ __forceinline__ float2 lds_f2(uint32_t addr) {
  float2 v; asm volatile("ld.shared.v2.f32 {%0,%1}, [%2];" : "=f"(v.x), "=f"(v.y) : "r"(addr) : "memory"); return v;
}
__device__ __forceinline__ uint4 lds128(uint32_t addr) {
  uint4 v; asm volatile("ld.shared.v4.b32 {%0,%1,%2,%3}, [%4];" : "=r"(v.x), "=r"(v.y), "=r"(v.z), "=r"(v.w) : "r"(addr) : "memory"); return v;
}
__device__ __forceinline__ void sts128(uint32_t addr, uint4 v) {
  asm volatile("st.shared.v4.b32 [%0], {%1,%2,%3,%4};" ::"r"(addr), "r"(v.x), "r"(v.y), "r"(v.z), "r"(v.w) : "memory");
}
__device__ __forceinline__ float lds_f(uint32_t addr) {
  float v; asm volatile("ld.shared.f32 %0, [%1];" : "=f"(v) : "r"(addr) : "memory"); return v;
}
__device__ __forceinline__ uint32_t lds_vol(uint32_t addr) {
  uint32_t v; asm volatile("ld.volatile.shared.u32 %0, [%1];" : "=r"(v) : "r"(addr) : "memory"); return v;
}
__device__ __forceinline__ void sts16(uint32_t addr, uint32_t v) {
  asm volatile("st.shared.u16 [%0], %1;" ::"r"(addr), "h"((unsigned short)v) : "memory");
}
__device__ __forceinline__ void nbar_dyn(int id, int n) { asm volatile("bar.sync %0, %1;" ::"r"(id), "r"(n) : "memory"); }
__device__ __forceinline__ uint64_t make_desc_ns(uint32_t addr, uint32_t lbo_bytes, uint32_t sbo_bytes) {
  return (uint64_t)((addr & 0x3FFFF) >> 4) | ((uint64_t)(lbo_bytes >> 4) << 16) | ((uint64_t)(sbo_bytes >> 4) << 32);
}
__device__ __forceinline__ void sts_f(uint32_t addr, float v) { asm volatile("st.shared.f32 [%0], %1;" ::"r"(addr), "f"(v) : "memory"); }
__device__ __forceinline__ void sts64(uint32_t addr, uint32_t a, uint32_t b) {
  asm volatile("st.shared.v2.b32 [%0], {%1,%2};" ::"r"(addr), "r"(a), "r"(b) : "memory");
}
__device__ __forceinline__ void sts_f2(uint32_t addr, float a, float b) {
  asm volatile("st.shared.v2.f32 [%0], {%1,%2};" ::"r"(addr), "f"(a), "f"(b) : "memory");
}
__device__ __forceinline__ void red_add2(float* p, float a, float b) {
  asm volatile("red.global.add.v2.f32 [%0], {%1,%2};" ::"l"(p), "f"(a), "f"(b) : "memory");
}
__device__ __forceinline__ void red_add4(float* p, float a, float b, float c, float d) {
  asm volatile("red.global.add.v4.f32 [%0], {%1,%2,%3,%4};" ::"l"(p), "f"(a), "f"(b), "f"(c), "f"(d) : "memory");
}
__device__ __forceinline__ void red_add1(float* p, float a) {
  asm volatile("red.global.add.f32 [%0], %1;" ::"l"(p), "f"(a) : "memory");
}
__device__ __forceinline__ void l2_prefetch(const void* p, uint32_t bytes) {
  asm volatile("cp.async.bulk.prefetch.L2.global [%0], %1;" ::"l"(p), "r"(bytes) : "memory");
}

__device__ __forceinline__ void wgmma_n256(float (&d)[192], uint64_t da, uint64_t db, int scale_d) {
  asm volatile("{\n.reg .pred p;\nsetp.ne.b32 p, %130, 0;\n"
    "wgmma.mma_async.sync.aligned.m64n256k16.f32.bf16.bf16 {%0, %1, %2, %3, %4, %5, %6, %7, %8, %9, %10, %11, %12, %13, %14, %15, %16, %17, %18, %19, %20, %21, %22, %23, %24, %25, %26, %27, %28, %29, %30, %31, %32, %33, %34, %35, %36, %37, %38, %39, %40, %41, %42, %43, %44, %45, %46, %47, %48, %49, %50, %51, %52, %53, %54, %55, %56, %57, %58, %59, %60, %61, %62, %63, %64, %65, %66, %67, %68, %69, %70, %71, %72, %73, %74, %75, %76, %77, %78, %79, %80, %81, %82, %83, %84, %85, %86, %87, %88, %89, %90, %91, %92, %93, %94, %95, %96, %97, %98, %99, %100, %101, %102, %103, %104, %105, %106, %107, %108, %109, %110, %111, %112, %113, %114, %115, %116, %117, %118, %119, %120, %121, %122, %123, %124, %125, %126, %127}, %128, %129, p, 1, 1, 0, 1;\n}\n"
    : "+f"(d[0]), "+f"(d[1]), "+f"(d[2]), "+f"(d[3]), "+f"(d[4]), "+f"(d[5]), "+f"(d[6]), "+f"(d[7]), "+f"(d[8]), "+f"(d[9]), "+f"(d[10]), "+f"(d[11]), "+f"(d[12]), "+f"(d[13]), "+f"(d[14]), "+f"(d[15]), "+f"(d[16]), "+f"(d[17]), "+f"(d[18]), "+f"(d[19]), "+f"(d[20]), "+f"(d[21]), "+f"(d[22]), "+f"(d[23]), "+f"(d[24]), "+f"(d[25]), "+f"(d[26]), "+f"(d[27]), "+f"(d[28]), "+f"(d[29]), "+f"(d[30]), "+f"(d[31]), "+f"(d[32]), "+f"(d[33]), "+f"(d[34]), "+f"(d[35]), "+f"(d[36]), "+f"(d[37]), "+f"(d[38]), "+f"(d[39]), "+f"(d[40]), "+f"(d[41]), "+f"(d[42]), "+f"(d[43]), "+f"(d[44]), "+f"(d[45]), "+f"(d[46]), "+f"(d[47]), "+f"(d[48]), "+f"(d[49]), "+f"(d[50]), "+f"(d[51]), "+f"(d[52]), "+f"(d[53]), "+f"(d[54]), "+f"(d[55]), "+f"(d[56]), "+f"(d[57]), "+f"(d[58]), "+f"(d[59]), "+f"(d[60]), "+f"(d[61]), "+f"(d[62]), "+f"(d[63]), "+f"(d[64]), "+f"(d[65]), "+f"(d[66]), "+f"(d[67]), "+f"(d[68]), "+f"(d[69]), "+f"(d[70]), "+f"(d[71]), "+f"(d[72]), "+f"(d[73]), "+f"(d[74]), "+f"(d[75]), "+f"(d[76]), "+f"(d[77]), "+f"(d[78]), "+f"(d[79]), "+f"(d[80]), "+f"(d[81]), "+f"(d[82]), "+f"(d[83]), "+f"(d[84]), "+f"(d[85]), "+f"(d[86]), "+f"(d[87]), "+f"(d[88]), "+f"(d[89]), "+f"(d[90]), "+f"(d[91]), "+f"(d[92]), "+f"(d[93]), "+f"(d[94]), "+f"(d[95]), "+f"(d[96]), "+f"(d[97]), "+f"(d[98]), "+f"(d[99]), "+f"(d[100]), "+f"(d[101]), "+f"(d[102]), "+f"(d[103]), "+f"(d[104]), "+f"(d[105]), "+f"(d[106]), "+f"(d[107]), "+f"(d[108]), "+f"(d[109]), "+f"(d[110]), "+f"(d[111]), "+f"(d[112]), "+f"(d[113]), "+f"(d[114]), "+f"(d[115]), "+f"(d[116]), "+f"(d[117]), "+f"(d[118]), "+f"(d[119]), "+f"(d[120]), "+f"(d[121]), "+f"(d[122]), "+f"(d[123]), "+f"(d[124]), "+f"(d[125]), "+f"(d[126]), "+f"(d[127])
    : "l"(da), "l"(db), "r"(scale_d));
}
__device__ __forceinline__ void wgmma_n128(float (&d)[192], uint64_t da, uint64_t db, int scale_d) {
  asm volatile("{\n.reg .pred p;\nsetp.ne.b32 p, %66, 0;\n"
    "wgmma.mma_async.sync.aligned.m64n128k16.f32.bf16.bf16 {%0, %1, %2, %3, %4, %5, %6, %7, %8, %9, %10, %11, %12, %13, %14, %15, %16, %17, %18, %19, %20, %21, %22, %23, %24, %25, %26, %27, %28, %29, %30, %31, %32, %33, %34, %35, %36, %37, %38, %39, %40, %41, %42, %43, %44, %45, %46, %47, %48, %49, %50, %51, %52, %53, %54, %55, %56, %57, %58, %59, %60, %61, %62, %63}, %64, %65, p, 1, 1, 0, 1;\n}\n"
    : "+f"(d[128]), "+f"(d[129]), "+f"(d[130]), "+f"(d[131]), "+f"(d[132]), "+f"(d[133]), "+f"(d[134]), "+f"(d[135]), "+f"(d[136]), "+f"(d[137]), "+f"(d[138]), "+f"(d[139]), "+f"(d[140]), "+f"(d[141]), "+f"(d[142]), "+f"(d[143]), "+f"(d[144]), "+f"(d[145]), "+f"(d[146]), "+f"(d[147]), "+f"(d[148]), "+f"(d[149]), "+f"(d[150]), "+f"(d[151]), "+f"(d[152]), "+f"(d[153]), "+f"(d[154]), "+f"(d[155]), "+f"(d[156]), "+f"(d[157]), "+f"(d[158]), "+f"(d[159]), "+f"(d[160]), "+f"(d[161]), "+f"(d[162]), "+f"(d[163]), "+f"(d[164]), "+f"(d[165]), "+f"(d[166]), "+f"(d[167]), "+f"(d[168]), "+f"(d[169]), "+f"(d[170]), "+f"(d[171]), "+f"(d[172]), "+f"(d[173]), "+f"(d[174]), "+f"(d[175]), "+f"(d[176]), "+f"(d[177]), "+f"(d[178]), "+f"(d[179]), "+f"(d[180]), "+f"(d[181]), "+f"(d[182]), "+f"(d[183]), "+f"(d[184]), "+f"(d[185]), "+f"(d[186]), "+f"(d[187]), "+f"(d[188]), "+f"(d[189]), "+f"(d[190]), "+f"(d[191])
    : "l"(da), "l"(db), "r"(scale_d));
}
__device__ __forceinline__ void wgmma_n256_k(float (&d)[192], uint64_t da, uint64_t db, int scale_d) {
  asm volatile("{\n.reg .pred p;\nsetp.ne.b32 p, %130, 0;\n"
    "wgmma.mma_async.sync.aligned.m64n256k16.f32.bf16.bf16 {%0, %1, %2, %3, %4, %5, %6, %7, %8, %9, %10, %11, %12, %13, %14, %15, %16, %17, %18, %19, %20, %21, %22, %23, %24, %25, %26, %27, %28, %29, %30, %31, %32, %33, %34, %35, %36, %37, %38, %39, %40, %41, %42, %43, %44, %45, %46, %47, %48, %49, %50, %51, %52, %53, %54, %55, %56, %57, %58, %59, %60, %61, %62, %63, %64, %65, %66, %67, %68, %69, %70, %71, %72, %73, %74, %75, %76, %77, %78, %79, %80, %81, %82, %83, %84, %85, %86, %87, %88, %89, %90, %91, %92, %93, %94, %95, %96, %97, %98, %99, %100, %101, %102, %103, %104, %105, %106, %107, %108, %109, %110, %111, %112, %113, %114, %115, %116, %117, %118, %119, %120, %121, %122, %123, %124, %125, %126, %127}, %128, %129, p, 1, 1, 0, 0;\n}\n"
    : "+f"(d[0]), "+f"(d[1]), "+f"(d[2]), "+f"(d[3]), "+f"(d[4]), "+f"(d[5]), "+f"(d[6]), "+f"(d[7]), "+f"(d[8]), "+f"(d[9]), "+f"(d[10]), "+f"(d[11]), "+f"(d[12]), "+f"(d[13]), "+f"(d[14]), "+f"(d[15]), "+f"(d[16]), "+f"(d[17]), "+f"(d[18]), "+f"(d[19]), "+f"(d[20]), "+f"(d[21]), "+f"(d[22]), "+f"(d[23]), "+f"(d[24]), "+f"(d[25]), "+f"(d[26]), "+f"(d[27]), "+f"(d[28]), "+f"(d[29]), "+f"(d[30]), "+f"(d[31]), "+f"(d[32]), "+f"(d[33]), "+f"(d[34]), "+f"(d[35]), "+f"(d[36]), "+f"(d[37]), "+f"(d[38]), "+f"(d[39]), "+f"(d[40]), "+f"(d[41]), "+f"(d[42]), "+f"(d[43]), "+f"(d[44]), "+f"(d[45]), "+f"(d[46]), "+f"(d[47]), "+f"(d[48]), "+f"(d[49]), "+f"(d[50]), "+f"(d[51]), "+f"(d[52]), "+f"(d[53]), "+f"(d[54]), "+f"(d[55]), "+f"(d[56]), "+f"(d[57]), "+f"(d[58]), "+f"(d[59]), "+f"(d[60]), "+f"(d[61]), "+f"(d[62]), "+f"(d[63]), "+f"(d[64]), "+f"(d[65]), "+f"(d[66]), "+f"(d[67]), "+f"(d[68]), "+f"(d[69]), "+f"(d[70]), "+f"(d[71]), "+f"(d[72]), "+f"(d[73]), "+f"(d[74]), "+f"(d[75]), "+f"(d[76]), "+f"(d[77]), "+f"(d[78]), "+f"(d[79]), "+f"(d[80]), "+f"(d[81]), "+f"(d[82]), "+f"(d[83]), "+f"(d[84]), "+f"(d[85]), "+f"(d[86]), "+f"(d[87]), "+f"(d[88]), "+f"(d[89]), "+f"(d[90]), "+f"(d[91]), "+f"(d[92]), "+f"(d[93]), "+f"(d[94]), "+f"(d[95]), "+f"(d[96]), "+f"(d[97]), "+f"(d[98]), "+f"(d[99]), "+f"(d[100]), "+f"(d[101]), "+f"(d[102]), "+f"(d[103]), "+f"(d[104]), "+f"(d[105]), "+f"(d[106]), "+f"(d[107]), "+f"(d[108]), "+f"(d[109]), "+f"(d[110]), "+f"(d[111]), "+f"(d[112]), "+f"(d[113]), "+f"(d[114]), "+f"(d[115]), "+f"(d[116]), "+f"(d[117]), "+f"(d[118]), "+f"(d[119]), "+f"(d[120]), "+f"(d[121]), "+f"(d[122]), "+f"(d[123]), "+f"(d[124]), "+f"(d[125]), "+f"(d[126]), "+f"(d[127])
    : "l"(da), "l"(db), "r"(scale_d));
}
__device__ __forceinline__ void wgmma_n128_k(float (&d)[192], uint64_t da, uint64_t db, int scale_d) {
  asm volatile("{\n.reg .pred p;\nsetp.ne.b32 p, %66, 0;\n"
    "wgmma.mma_async.sync.aligned.m64n128k16.f32.bf16.bf16 {%0, %1, %2, %3, %4, %5, %6, %7, %8, %9, %10, %11, %12, %13, %14, %15, %16, %17, %18, %19, %20, %21, %22, %23, %24, %25, %26, %27, %28, %29, %30, %31, %32, %33, %34, %35, %36, %37, %38, %39, %40, %41, %42, %43, %44, %45, %46, %47, %48, %49, %50, %51, %52, %53, %54, %55, %56, %57, %58, %59, %60, %61, %62, %63}, %64, %65, p, 1, 1, 0, 0;\n}\n"
    : "+f"(d[128]), "+f"(d[129]), "+f"(d[130]), "+f"(d[131]), "+f"(d[132]), "+f"(d[133]), "+f"(d[134]), "+f"(d[135]), "+f"(d[136]), "+f"(d[137]), "+f"(d[138]), "+f"(d[139]), "+f"(d[140]), "+f"(d[141]), "+f"(d[142]), "+f"(d[143]), "+f"(d[144]), "+f"(d[145]), "+f"(d[146]), "+f"(d[147]), "+f"(d[148]), "+f"(d[149]), "+f"(d[150]), "+f"(d[151]), "+f"(d[152]), "+f"(d[153]), "+f"(d[154]), "+f"(d[155]), "+f"(d[156]), "+f"(d[157]), "+f"(d[158]), "+f"(d[159]), "+f"(d[160]), "+f"(d[161]), "+f"(d[162]), "+f"(d[163]), "+f"(d[164]), "+f"(d[165]), "+f"(d[166]), "+f"(d[167]), "+f"(d[168]), "+f"(d[169]), "+f"(d[170]), "+f"(d[171]), "+f"(d[172]), "+f"(d[173]), "+f"(d[174]), "+f"(d[175]), "+f"(d[176]), "+f"(d[177]), "+f"(d[178]), "+f"(d[179]), "+f"(d[180]), "+f"(d[181]), "+f"(d[182]), "+f"(d[183]), "+f"(d[184]), "+f"(d[185]), "+f"(d[186]), "+f"(d[187]), "+f"(d[188]), "+f"(d[189]), "+f"(d[190]), "+f"(d[191])
    : "l"(da), "l"(db), "r"(scale_d));
}
__device__ __forceinline__ void wgmma_n40_tt(float (&d)[20], uint64_t da, uint64_t db, int scale_d) {
  asm volatile("{\n.reg .pred p;\nsetp.ne.b32 p, %22, 0;\n"
    "wgmma.mma_async.sync.aligned.m64n40k16.f32.bf16.bf16 {%0, %1, %2, %3, %4, %5, %6, %7, %8, %9, %10, %11, %12, %13, %14, %15, %16, %17, %18, %19}, %20, %21, p, 1, 1, 1, 1;\n}\n"
    : "+f"(d[0]), "+f"(d[1]), "+f"(d[2]), "+f"(d[3]), "+f"(d[4]), "+f"(d[5]), "+f"(d[6]), "+f"(d[7]), "+f"(d[8]), "+f"(d[9]), "+f"(d[10]), "+f"(d[11]), "+f"(d[12]), "+f"(d[13]), "+f"(d[14]), "+f"(d[15]), "+f"(d[16]), "+f"(d[17]), "+f"(d[18]), "+f"(d[19])
    : "l"(da), "l"(db), "r"(scale_d));
}
__device__ __forceinline__ void wgmma_n40_rs(float (&d)[20], const uint32_t (&a)[4], uint64_t db, int scale_d) {
  asm volatile("{\n.reg .pred p;\nsetp.ne.b32 p, %25, 0;\n"
    "wgmma.mma_async.sync.aligned.m64n40k16.f32.bf16.bf16 {%0, %1, %2, %3, %4, %5, %6, %7, %8, %9, %10, %11, %12, %13, %14, %15, %16, %17, %18, %19}, {%20, %21, %22, %23}, %24, p, 1, 1, 1;\n}\n"
    : "+f"(d[0]), "+f"(d[1]), "+f"(d[2]), "+f"(d[3]), "+f"(d[4]), "+f"(d[5]), "+f"(d[6]), "+f"(d[7]), "+f"(d[8]), "+f"(d[9]), "+f"(d[10]), "+f"(d[11]), "+f"(d[12]), "+f"(d[13]), "+f"(d[14]), "+f"(d[15]), "+f"(d[16]), "+f"(d[17]), "+f"(d[18]), "+f"(d[19])
    : "r"(a[0]), "r"(a[1]), "r"(a[2]), "r"(a[3]), "l"(db), "r"(scale_d));
}
__device__ __forceinline__ void wgmma_n256_0(float (&d)[192], uint64_t da, uint64_t db) {
  asm volatile("{\n.reg .pred p;\nsetp.ne.b32 p, 0, 0;\n"
    "wgmma.mma_async.sync.aligned.m64n256k16.f32.bf16.bf16 {%0, %1, %2, %3, %4, %5, %6, %7, %8, %9, %10, %11, %12, %13, %14, %15, %16, %17, %18, %19, %20, %21, %22, %23, %24, %25, %26, %27, %28, %29, %30, %31, %32, %33, %34, %35, %36, %37, %38, %39, %40, %41, %42, %43, %44, %45, %46, %47, %48, %49, %50, %51, %52, %53, %54, %55, %56, %57, %58, %59, %60, %61, %62, %63, %64, %65, %66, %67, %68, %69, %70, %71, %72, %73, %74, %75, %76, %77, %78, %79, %80, %81, %82, %83, %84, %85, %86, %87, %88, %89, %90, %91, %92, %93, %94, %95, %96, %97, %98, %99, %100, %101, %102, %103, %104, %105, %106, %107, %108, %109, %110, %111, %112, %113, %114, %115, %116, %117, %118, %119, %120, %121, %122, %123, %124, %125, %126, %127}, %128, %129, p, 1, 1, 0, 1;\n}\n"
    : "=f"(d[0]), "=f"(d[1]), "=f"(d[2]), "=f"(d[3]), "=f"(d[4]), "=f"(d[5]), "=f"(d[6]), "=f"(d[7]), "=f"(d[8]), "=f"(d[9]), "=f"(d[10]), "=f"(d[11]), "=f"(d[12]), "=f"(d[13]), "=f"(d[14]), "=f"(d[15]), "=f"(d[16]), "=f"(d[17]), "=f"(d[18]), "=f"(d[19]), "=f"(d[20]), "=f"(d[21]), "=f"(d[22]), "=f"(d[23]), "=f"(d[24]), "=f"(d[25]), "=f"(d[26]), "=f"(d[27]), "=f"(d[28]), "=f"(d[29]), "=f"(d[30]), "=f"(d[31]), "=f"(d[32]), "=f"(d[33]), "=f"(d[34]), "=f"(d[35]), "=f"(d[36]), "=f"(d[37]), "=f"(d[38]), "=f"(d[39]), "=f"(d[40]), "=f"(d[41]), "=f"(d[42]), "=f"(d[43]), "=f"(d[44]), "=f"(d[45]), "=f"(d[46]), "=f"(d[47]), "=f"(d[48]), "=f"(d[49]), "=f"(d[50]), "=f"(d[51]), "=f"(d[52]), "=f"(d[53]), "=f"(d[54]), "=f"(d[55]), "=f"(d[56]), "=f"(d[57]), "=f"(d[58]), "=f"(d[59]), "=f"(d[60]), "=f"(d[61]), "=f"(d[62]), "=f"(d[63]), "=f"(d[64]), "=f"(d[65]), "=f"(d[66]), "=f"(d[67]), "=f"(d[68]), "=f"(d[69]), "=f"(d[70]), "=f"(d[71]), "=f"(d[72]), "=f"(d[73]), "=f"(d[74]), "=f"(d[75]), "=f"(d[76]), "=f"(d[77]), "=f"(d[78]), "=f"(d[79]), "=f"(d[80]), "=f"(d[81]), "=f"(d[82]), "=f"(d[83]), "=f"(d[84]), "=f"(d[85]), "=f"(d[86]), "=f"(d[87]), "=f"(d[88]), "=f"(d[89]), "=f"(d[90]), "=f"(d[91]), "=f"(d[92]), "=f"(d[93]), "=f"(d[94]), "=f"(d[95]), "=f"(d[96]), "=f"(d[97]), "=f"(d[98]), "=f"(d[99]), "=f"(d[100]), "=f"(d[101]), "=f"(d[102]), "=f"(d[103]), "=f"(d[104]), "=f"(d[105]), "=f"(d[106]), "=f"(d[107]), "=f"(d[108]), "=f"(d[109]), "=f"(d[110]), "=f"(d[111]), "=f"(d[112]), "=f"(d[113]), "=f"(d[114]), "=f"(d[115]), "=f"(d[116]), "=f"(d[117]), "=f"(d[118]), "=f"(d[119]), "=f"(d[120]), "=f"(d[121]), "=f"(d[122]), "=f"(d[123]), "=f"(d[124]), "=f"(d[125]), "=f"(d[126]), "=f"(d[127])
    : "l"(da), "l"(db));
}
__device__ __forceinline__ void wgmma_n128_0(float (&d)[192], uint64_t da, uint64_t db) {
  asm volatile("{\n.reg .pred p;\nsetp.ne.b32 p, 0, 0;\n"
    "wgmma.mma_async.sync.aligned.m64n128k16.f32.bf16.bf16 {%0, %1, %2, %3, %4, %5, %6, %7, %8, %9, %10, %11, %12, %13, %14, %15, %16, %17, %18, %19, %20, %21, %22, %23, %24, %25, %26, %27, %28, %29, %30, %31, %32, %33, %34, %35, %36, %37, %38, %39, %40, %41, %42, %43, %44, %45, %46, %47, %48, %49, %50, %51, %52, %53, %54, %55, %56, %57, %58, %59, %60, %61, %62, %63}, %64, %65, p, 1, 1, 0, 1;\n}\n"
    : "=f"(d[128]), "=f"(d[129]), "=f"(d[130]), "=f"(d[131]), "=f"(d[132]), "=f"(d[133]), "=f"(d[134]), "=f"(d[135]), "=f"(d[136]), "=f"(d[137]), "=f"(d[138]), "=f"(d[139]), "=f"(d[140]), "=f"(d[141]), "=f"(d[142]), "=f"(d[143]), "=f"(d[144]), "=f"(d[145]), "=f"(d[146]), "=f"(d[147]), "=f"(d[148]), "=f"(d[149]), "=f"(d[150]), "=f"(d[151]), "=f"(d[152]), "=f"(d[153]), "=f"(d[154]), "=f"(d[155]), "=f"(d[156]), "=f"(d[157]), "=f"(d[158]), "=f"(d[159]), "=f"(d[160]), "=f"(d[161]), "=f"(d[162]), "=f"(d[163]), "=f"(d[164]), "=f"(d[165]), "=f"(d[166]), "=f"(d[167]), "=f"(d[168]), "=f"(d[169]), "=f"(d[170]), "=f"(d[171]), "=f"(d[172]), "=f"(d[173]), "=f"(d[174]), "=f"(d[175]), "=f"(d[176]), "=f"(d[177]), "=f"(d[178]), "=f"(d[179]), "=f"(d[180]), "=f"(d[181]), "=f"(d[182]), "=f"(d[183]), "=f"(d[184]), "=f"(d[185]), "=f"(d[186]), "=f"(d[187]), "=f"(d[188]), "=f"(d[189]), "=f"(d[190]), "=f"(d[191])
    : "l"(da), "l"(db));
}
__device__ __forceinline__ void wgmma_n128_rs(float (&d)[192], const uint32_t (&a)[4], uint64_t db, int scale_d) {
  asm volatile("{\n.reg .pred p;\nsetp.ne.b32 p, %69, 0;\n"
    "wgmma.mma_async.sync.aligned.m64n128k16.f32.bf16.bf16 {%0, %1, %2, %3, %4, %5, %6, %7, %8, %9, %10, %11, %12, %13, %14, %15, %16, %17, %18, %19, %20, %21, %22, %23, %24, %25, %26, %27, %28, %29, %30, %31, %32, %33, %34, %35, %36, %37, %38, %39, %40, %41, %42, %43, %44, %45, %46, %47, %48, %49, %50, %51, %52, %53, %54, %55, %56, %57, %58, %59, %60, %61, %62, %63}, {%64, %65, %66, %67}, %68, p, 1, 1, 1;\n}\n"
    : "+f"(d[128]), "+f"(d[129]), "+f"(d[130]), "+f"(d[131]), "+f"(d[132]), "+f"(d[133]), "+f"(d[134]), "+f"(d[135]), "+f"(d[136]), "+f"(d[137]), "+f"(d[138]), "+f"(d[139]), "+f"(d[140]), "+f"(d[141]), "+f"(d[142]), "+f"(d[143]), "+f"(d[144]), "+f"(d[145]), "+f"(d[146]), "+f"(d[147]), "+f"(d[148]), "+f"(d[149]), "+f"(d[150]), "+f"(d[151]), "+f"(d[152]), "+f"(d[153]), "+f"(d[154]), "+f"(d[155]), "+f"(d[156]), "+f"(d[157]), "+f"(d[158]), "+f"(d[159]), "+f"(d[160]), "+f"(d[161]), "+f"(d[162]), "+f"(d[163]), "+f"(d[164]), "+f"(d[165]), "+f"(d[166]), "+f"(d[167]), "+f"(d[168]), "+f"(d[169]), "+f"(d[170]), "+f"(d[171]), "+f"(d[172]), "+f"(d[173]), "+f"(d[174]), "+f"(d[175]), "+f"(d[176]), "+f"(d[177]), "+f"(d[178]), "+f"(d[179]), "+f"(d[180]), "+f"(d[181]), "+f"(d[182]), "+f"(d[183]), "+f"(d[184]), "+f"(d[185]), "+f"(d[186]), "+f"(d[187]), "+f"(d[188]), "+f"(d[189]), "+f"(d[190]), "+f"(d[191])
    : "r"(a[0]), "r"(a[1]), "r"(a[2]), "r"(a[3]), "l"(db), "r"(scale_d));
}

constexpr int SLOT = 16384;
constexpr int KVT = 10240;
constexpr uint32_t QA = 0x0BAu, QK = 0x462u, QQ = 0x981u;
constexpr int SM_SD = 12 * SLOT;
constexpr int SM_BAR = SM_SD + 8192;
constexpr int SM_RS = SM_BAR + 512;
constexpr int SM_AP = SM_RS + 768;
constexpr int SM_BP = SM_AP + 2048;
constexpr int SM_WPHI = SM_BP + 12288;
constexpr int SM_EPOCH = SM_WPHI + 10240;
constexpr int SM_TOTAL = SM_EPOCH + 16 + 1024;
constexpr int B_FULLS = 0, B_XOLD = 24, B_STAT = 32, B_EMPTYS = 40, B_FULLT = 256  , B_CONS = 384  , B_E3 = 472, B_E0 = 480, B_E1 = 488, B_E2 = 496, B_EPI = 504, B_CS = 160,
              B_KVDONE = 168  , B_ODONE = 176, B_XDONE = 184, B_OH1 = B_CONS, B_CS2 = 208, B_XH0 = 232, B_R0 = 240, B_CB = 144  , B_XOLD2 = 216, B_FLG = 64  ;
constexpr uint64_t BAR_CNT = 0x1c07fc0eac00a800ull;
constexpr uint64_t WO_A0 = 0xa461b57648357643ull, WO_B0 = 0x59083a9021ba9021ull, WO_A1 = 0xa0b76901276a5babull, WO_B1 = 0x95428a5b34890132ull;
constexpr uint64_t WO_DA0 = 0xa9865432ff00dd00ull, WO_DB0 = 0xa986543211bbccccull, WO_DA1 = 0xa98654321ffff000ull, WO_DB1 = 0xa98754321bbcccddull;
#define WOORD 0xFDB9753ECA864210ull
constexpr int NX = 4;
constexpr int XS = 10;

#define PL 2
#define PROFX(i) PROFT(tid_ == 128 && layer == PL, 200 + (i))
#define PSL 20
#define EP 5
#define NCOM 3
#define CSLP 128
#define PFS 8
#define KVTH 0x41700000u
#define RL 3
#define ORD 1
#define XB2 2
#define PMOD 3
#define DB1 2
#define XPF 3
#define XPM 2
#define AW 1
#define PG 0
#define UNS 7
#define TLINE 0
#define RORD 0
#define WSK 1
#define ER 1
#define SSL 256
#define CST 0
#define NLAYERS 4
constexpr float L2E = 1.4426950408889634f;
#define PHI_MAX 2147483648.f

#define D128(lo) desc64(lo, 0x40000040u)
struct Ctx { uint32_t sb; int g, rb, cu; bf16* out; };

__device__ __forceinline__ void colsum(const CUtensorMap* tm, float* cs, int rb, int g, int w0, int dw, int lane, uint32_t stg, uint32_t cb, uint32_t par) {
  const uint32_t src = stg + (lane >> 3) * 2048;
#pragma unroll 1
  for (int wi = w0 - dw; wi < 6; wi += dw) {
    float s[8] = {0.f, 0.f, 0.f, 0.f, 0.f, 0.f, 0.f, 0.f};
    if (wi >= 0) {
      mbar_wait_u(cb, par);
      par ^= 1;
#pragma unroll 4
      for (int r = 0; r < 16; ++r) {
        const uint4 v = lds128(src + r * 128 + (((lane ^ r) & 7) << 4));
        s[0] += bf_lo(v.x); s[1] += bf_hi(v.x); s[2] += bf_lo(v.y); s[3] += bf_hi(v.y);
        s[4] += bf_lo(v.z); s[5] += bf_hi(v.z); s[6] += bf_lo(v.w); s[7] += bf_hi(v.w);
      }
#pragma unroll
      for (int i = 0; i < 8; ++i) s[i] += __shfl_xor_sync(0xffffffffu, s[i], 8);
    }
    const int wn = wi + dw;
    if (wn < 6) {
      expect_tx_e(cb, 8192);
      tma_2d_e(stg, tm, (wn >= 4 ? 0 : 1024 + (wn >> 1) * 1024) + g * 128 + (wn & 1) * 64, rb * 64, cb);
    }
    if (wi >= 0) {
#pragma unroll
      for (int i = 0; i < 8; ++i) s[i] += __shfl_xor_sync(0xffffffffu, s[i], 16);
      if (lane < 8) {
        red_add4(cs + g * 384 + (wi * 8 + lane) * 8, s[0], s[1], s[2], s[3]);
        red_add4(cs + g * 384 + (wi * 8 + lane) * 8 + 4, s[4], s[5], s[6], s[7]);
      }
      __syncwarp();
    }
  }
}
#define PHASE_CTX() \
  uint32_t sb = c.sb; asm volatile("" : "+r"(sb)); \
  int tid_ = threadIdx.x; asm volatile("" : "+r"(tid_)); \
  const uint32_t bar = sb + SM_BAR; \
  const int lane = tid_ & 31, cw = (tid_ >> 5) - 4, wg = cw >> 2, wq = cw & 3, gq = lane >> 2, t = lane & 3, wrow0 = cw * 16; \
  const int lrow = (lane & 7) + ((lane >> 3) & 1) * 8, lchk = lane >> 4; \
  const bool elected = (tid_ & 127) == 0; \
  const uint32_t rowo = (wrow0 + lrow) * 128, X = (lchk ^ (lane & 7)) << 4; \
  (void)bar; (void)wq; (void)gq; (void)lrow; (void)lchk; (void)elected; (void)wrow0; (void)wg; (void)rowo; (void)X; (void)t;

__device__ __forceinline__ void slab_out_half(uint32_t slot, bf16* dst, int wrow0, int lane, bool FENCE = false) {
  const int r0 = lane >> 3, ch = lane & 7;
  const uint32_t src = slot + (wrow0 + r0) * 128;
  uint4 v[4];
#pragma unroll
  for (int i = 0; i < 4; ++i) v[i] = lds128(src + i * 512 + (((ch ^ (4 * i + r0)) & 7) << 4));
  if (FENCE) fence_async_smem();
  dst += (size_t)(wrow0 + r0) * D_ + ch * 8;
#pragma unroll
  for (int i = 0; i < 4; ++i)
    asm volatile("st.global.v4.u32 [%0], {%1,%2,%3,%4};" ::"l"(dst + (size_t)i * 4 * D_), "r"(v[i].x), "r"(v[i].y), "r"(v[i].z), "r"(v[i].w) : "memory");
}

struct Tag { uint32_t me, mo, tg; };
__device__ __forceinline__ Tag make_tag(int gq, int t, uint32_t tg) {
  const uint32_t on = t == (gq & 3), par = ((gq >> 2) ^ gq) & 1;
  return Tag{on & ~par, on & par, tg};
}
__device__ __forceinline__ void stsm_tag(uint32_t addr, uint32_t r0, uint32_t r1, uint32_t r2, uint32_t r3, const Tag& k, int jp) {
  stsm_x4(addr, (r0 & ~k.me) | (k.tg & k.me), (r1 & ~k.me) | (k.tg & k.me), (r2 & ~k.mo) | (k.tg & k.mo), (r3 & ~k.mo) | (k.tg & k.mo));
}
#define TILE_BAD() (((lds_vol(va) ^ tg) | (lds_vol(va + 1024) ^ tg)) & 1)
#define TILE_VA() (slot + (wrow0 + (lane >> 2)) * 128 + (lane & 3) * 32 + (lane >> 2) * 4)
__device__ __forceinline__ void tile_check(uint32_t slot, const bf16* src, int wrow0, int lane, uint32_t tg) {
  const uint32_t va = TILE_VA();
  if (__builtin_expect(__any_sync(0xffffffffu, TILE_BAD()), 0)) {
    const int r0 = lane >> 3, ch = lane & 7;
    uint32_t n = 0;
#pragma unroll 1
    do {
      uint4 v[4];
#pragma unroll
      for (int i = 0; i < 4; ++i) v[i] = ld_relaxed4(reinterpret_cast<const uint4*>(src + (size_t)(wrow0 + r0 + 4 * i) * D_ + ch * 8));
#pragma unroll
      for (int i = 0; i < 4; ++i) sts128(slot + (wrow0 + r0 + 4 * i) * 128 + (((ch ^ (4 * i + r0)) & 7) << 4), v[i]);
      __syncwarp();
      if (++n > (1u << 16)) { g_err = 8u; break; }
    } while (__any_sync(0xffffffffu, TILE_BAD()));
    fence_async_smem();
    __syncwarp();
  }
}

template <int O>
__device__ __forceinline__ void phi_proj(float (&p)[2][4][4], const uint32_t (&kq)[64], uint32_t wa) {
#pragma unroll
  for (int h = 0; h < 2; ++h)
#pragma unroll
    for (int i = 0; i < 4; ++i) { p[h][i][0] = p[h][i][1] = p[h][i][2] = p[h][i][3] = 0.f; }
#pragma unroll
  for (int ks = 0; ks < 2; ++ks)
#pragma unroll
    for (int np = 0; np < 2; ++np)
#pragma unroll
      for (int h = 0; h < 2; ++h) {
        uint32_t b0, b1, b2, b3;
        ldsm_x4_t(b0, b1, b2, b3, wa + h * 2560 + ks * 1280 + np * 32);
        mma_bf16(p[h][2 * np], kq[O + 8 * h + 4 * ks], kq[O + 8 * h + 4 * ks + 1], kq[O + 8 * h + 4 * ks + 2], kq[O + 8 * h + 4 * ks + 3], b0, b1);
        mma_bf16(p[h][2 * np + 1], kq[O + 8 * h + 4 * ks], kq[O + 8 * h + 4 * ks + 1], kq[O + 8 * h + 4 * ks + 2], kq[O + 8 * h + 4 * ks + 3], b2, b3);
      }
}
__device__ __forceinline__ void phi_exp(uint32_t (&raw)[4][4], const float (&p)[4][4], float sc0, float sc1) {
#pragma unroll
  for (int i = 0; i < 4; ++i) {
    const float e0 = ex2(p[i][0] * sc0), e1 = ex2(p[i][1] * sc0), e2 = ex2(p[i][2] * sc1), e3 = ex2(p[i][3] * sc1);
    const float m0 = e0 * e1, m1 = e2 * e3, rr = rcp(m0 * m1), r0 = rr * m1, r1 = rr * m0;
    raw[i >> 1][(i & 1) * 2] = pack_bf16(e0, e1);
    raw[i >> 1][(i & 1) * 2 + 1] = pack_bf16(e2, e3);
    raw[2 + (i >> 1)][(i & 1) * 2] = pack_bf16(e1 * r0, e0 * r0);
    raw[2 + (i >> 1)][(i & 1) * 2 + 1] = pack_bf16(e3 * r1, e2 * r1);
  }
}
#define FENCE_P(h) _Pragma("unroll") for (int i_ = 0; i_ < 16; ++i_) asm volatile("" : "+f"(p[h][i_ >> 2][i_ & 3]) :: "memory")
#define FENCE_RAW(h) _Pragma("unroll") for (int i_ = 0; i_ < 16; ++i_) asm volatile("" : "+r"(raw[h][i_ >> 2][i_ & 3]) :: "memory")
template <int O>
__device__ __forceinline__ void phi_norm(uint32_t (&ph)[2][4][4], const uint32_t (&raw)[2][4][4], const uint32_t (&kq)[64], uint32_t wa,
                                         float sc0, float sc1, float mul0, float mul1) {
  bool bad = false;
#pragma unroll
  for (int h = 0; h < 2; ++h)
#pragma unroll
    for (int sg = 0; sg < 2; ++sg) {
      float ss[4] = {0.f, 0.f, 0.f, 0.f};
#pragma unroll
      for (int ks = 0; ks < 2; ++ks)
        mma_bf16(ss, raw[h][2 * sg + ks][0], raw[h][2 * sg + ks][1], raw[h][2 * sg + ks][2], raw[h][2 * sg + ks][3], 0x3F803F80u, 0x3F803F80u);
      bad = bad || !(ss[0] < PHI_MAX) || !(ss[2] < PHI_MAX);
      const uint32_t iv = pack_bf16(rcp(ss[0]) * mul0, rcp(ss[2]) * mul1);
#pragma unroll
      for (int ks = 0; ks < 2; ++ks)
#pragma unroll
        for (int j = 0; j < 4; ++j) ph[h][2 * sg + ks][j] = mul_bf16x2(raw[h][2 * sg + ks][j], iv, j & 1);
    }
  if (__builtin_expect(__any_sync(0xffffffffu, bad), 0)) {
#pragma unroll 1
    for (int it = 0; it < 4; ++it) {
      float q[4][4];
#pragma unroll
      for (int i = 0; i < 4; ++i) { q[i][0] = q[i][1] = q[i][2] = q[i][3] = 0.f; }
#pragma unroll
      for (int ks = 0; ks < 2; ++ks) {
        uint32_t a[4];
#pragma unroll
        for (int j = 0; j < 4; ++j) a[j] = (it & 2) ? kq[O + 8 + 4 * ks + j] : kq[O + 4 * ks + j];
#pragma unroll
        for (int np = 0; np < 2; ++np) {
          uint32_t b0, b1, b2, b3;
          ldsm_x4_t(b0, b1, b2, b3, wa + (it >> 1) * 2560 + ks * 1280 + np * 32);
          mma_bf16(q[2 * np], a[0], a[1], a[2], a[3], b0, b1);
          mma_bf16(q[2 * np + 1], a[0], a[1], a[2], a[3], b2, b3);
        }
      }
      float iv[2];
#pragma unroll
      for (int r = 0; r < 2; ++r) {
        const float sc = (it & 1) ? -(r ? sc1 : sc0) : (r ? sc1 : sc0);
        float mx = -INFINITY, sm = 0.f;
#pragma unroll
        for (int i = 0; i < 8; ++i) { float& v = q[i >> 1][2 * r + (i & 1)]; v *= sc; mx = fmaxf(mx, v); }
        mx = fmaxf(mx, __shfl_xor_sync(0xffffffffu, mx, 1));
        mx = fmaxf(mx, __shfl_xor_sync(0xffffffffu, mx, 2));
#pragma unroll
        for (int i = 0; i < 8; ++i) { float& v = q[i >> 1][2 * r + (i & 1)]; v = ex2(v - mx); sm += v; }
        sm += __shfl_xor_sync(0xffffffffu, sm, 1);
        sm += __shfl_xor_sync(0xffffffffu, sm, 2);
        iv[r] = rcp(sm) * (r ? mul1 : mul0);
      }
#pragma unroll
      for (int i = 0; i < 24; ++i) ph[i >> 4][(i >> 2) & 3][i & 3] = ph[(i + 8) >> 4][((i + 8) >> 2) & 3][i & 3];
#pragma unroll
      for (int i = 0; i < 4; ++i) {
        ph[1][2 + (i >> 1)][(i & 1) * 2] = pack_bf16(q[i][0] * iv[0], q[i][1] * iv[0]);
        ph[1][2 + (i >> 1)][(i & 1) * 2 + 1] = pack_bf16(q[i][2] * iv[1], q[i][3] * iv[1]);
      }
    }
  }
}

__device__ __forceinline__ void stats_out(float s0, float s1, float q0, float q1, float2* dst, int t) {
  const bool od = t & 1;
  float sa = od ? s1 : s0, qa = od ? q1 : q0;
  sa += __shfl_xor_sync(0xffffffffu, od ? s0 : s1, 1);
  qa += __shfl_xor_sync(0xffffffffu, od ? q0 : q1, 1);
  sa += __shfl_xor_sync(0xffffffffu, sa, 2);
  qa += __shfl_xor_sync(0xffffffffu, qa, 2);
  if (t < 2) red_add2(&dst[t * 8].x, sa, qa);
}

__device__ __forceinline__ void consumer(const Ctx& c) {
  const int g = c.g, m0 = c.rb * 128;
  float acc[192];
#define X_HALF(hf, TG) \
      _Pragma("unroll") for (int jp = 4 * (hf); jp < 4 * (hf) + 4; ++jp) \
        stsm_tag(sb + (XS + (hf)) * SLOT + rowo + (X ^ ((jp & 3) << 5)), \
                 pack_bf16(acc[128 + 8 * jp], acc[129 + 8 * jp]), pack_bf16(acc[130 + 8 * jp], acc[131 + 8 * jp]), \
                 pack_bf16(acc[132 + 8 * jp], acc[133 + 8 * jp]), pack_bf16(acc[134 + 8 * jp], acc[135 + 8 * jp]), TG, jp & 3);
#pragma unroll
  for (int i = 128; i < 192; ++i) acc[i] = 0.f;
#pragma unroll 1
  for (int layer = 0;; ++layer) {
    {
      PHASE_CTX();
      const uint32_t wu = c.cu >> 2;
      const uint32_t dA0 = (((sb + wu * 8192) & 0x3FFFF) >> 4) | (1u << 16), dB0 = ((sb & 0x3FFFF) >> 4) | (512u << 16);
      {
        PROFX(0);
        mbar_wait(bar + B_FULLS, 0);
        PROFX(1);
        wgmma_fence();
        wgmma_n256_0(acc, D128(dA0 + XS * 1024), D128(dB0 + 2048));
#pragma unroll
        for (int k = 1; k < 4; ++k) wgmma_n256(acc, D128(dA0 + XS * 1024 + k * 2), D128(dB0 + 2048 + k * 128), 1);
        wgmma_commit();
        wgmma_wait<1>();
        float s0 = 0.f, s1 = 0.f, q0 = 0.f, q1 = 0.f;
        if (layer) {
          X_HALF(1, (Tag{0u, 0u, 0u}));
#pragma unroll
          for (int i = 128; i < 192; i += 4) {
            s0 += acc[i] + acc[i + 1]; s1 += acc[i + 2] + acc[i + 3];
            q0 = fmaf(acc[i], acc[i], fmaf(acc[i + 1], acc[i + 1], q0)); q1 = fmaf(acc[i + 2], acc[i + 2], fmaf(acc[i + 3], acc[i + 3], q1));
          }
        }
        asm volatile("" : "+f"(s0), "+f"(s1), "+f"(q0), "+f"(q1) :: "memory");
        wgmma_fence();
        wgmma_n128_0(acc, D128(dA0 + XS * 1024), D128(dB0 + 1024));
#pragma unroll
        for (int k = 1; k < 4; ++k) wgmma_n128(acc, D128(dA0 + XS * 1024 + k * 2), D128(dB0 + 1024 + k * 128), 1);
        wgmma_commit();
        if (layer) {
          PHASE_CTX();
          fence_async_smem();
          nbar_dyn(3 + wu, 128);
          stats_out(s0, s1, q0, q1, g_stats + layer * S_ + m0 + wrow0 + gq, t);
          PROFT(tid_ == 128, layer * 16 + 8);
        }
      }
      uint32_t s = 1, u = 0, sp = 0;
      const int ix = layer ? 99 : 2 * min(g, NCOM) + 1;
#pragma unroll 1
      for (int i = 1; i < 14; ++i) {
        mbar_wait(bar + B_FULLS + s * 8, (u + (s ? layer : 0)) & 1);
        if ((UNS & 1) && layer && (unsigned)(i - 2) < 7u) {
          PHASE_CTX();
          tile_check(sb + ((QA >> (4 * s)) & 15) * SLOT, g_x + (size_t)m0 * D_ + ((2 * g + 2 * i - 2) & 15) * 64, wrow0, lane, lds_vol(sb + SM_EPOCH) + layer);
        }
        const uint32_t da = dA0 + ((QA >> (4 * s)) & 15) * 1024, dk = dB0 + ((QK >> (4 * s)) & 15) * 1024,
                       dq = dB0 + ((QQ >> (4 * s)) & 15) * 1024;
        wgmma_fence();
#pragma unroll
        for (int k = 0; k < 4; ++k) {
          wgmma_n256(acc, D128(da + k * 2), D128(dk + k * 128), 1);
          wgmma_n128(acc, D128(da + k * 2), D128(dq + k * 128), 1);
          if (k == ER - 1) {
            wgmma_commit();
            wgmma_wait<1>();
            if (elected && (unsigned)(i - ix) >= 2u) release2(bar + B_EMPTYS + sp * 8);
          }
        }
        wgmma_commit();
        if ((unsigned)(i - ix) < 2u) {
          PHASE_CTX();
          {
            float s0 = 0.f, s1 = 0.f, q0 = 0.f, q1 = 0.f;
            const uint32_t xa = sb + ((QA >> (4 * sp)) & 15) * SLOT + rowo;
#pragma unroll
            for (int jp = 0; jp < 4; ++jp) {
              uint32_t x0, x1, x2, x3;
              ldsm_x4(x0, x1, x2, x3, xa + (X ^ (jp << 5)));
              s0 += (bf_lo(x0) + bf_hi(x0)) + (bf_lo(x2) + bf_hi(x2));
              s1 += (bf_lo(x1) + bf_hi(x1)) + (bf_lo(x3) + bf_hi(x3));
              q0 = fmaf(bf_lo(x0), bf_lo(x0), fmaf(bf_hi(x0), bf_hi(x0), fmaf(bf_lo(x2), bf_lo(x2), fmaf(bf_hi(x2), bf_hi(x2), q0))));
              q1 = fmaf(bf_lo(x1), bf_lo(x1), fmaf(bf_hi(x1), bf_hi(x1), fmaf(bf_lo(x3), bf_lo(x3), fmaf(bf_hi(x3), bf_hi(x3), q1))));
            }
            stats_out(s0, s1, q0, q1, g_stats + m0 + wrow0 + gq, t);
          }
          __syncwarp();
          if (lane == 0 && i != ix) mbar_arrive(bar + B_XDONE);
          nbar_dyn(3 + wu, 128);
          if (ER && elected) release2(bar + B_EMPTYS + sp * 8);
        }
        if (!ER) {
          wgmma_wait<1>();
          if (elected) release2(bar + B_EMPTYS + sp * 8);
        }
        if (i == 1 && layer) {
          PHASE_CTX();
          slab_out_half(sb + (XS + 1) * SLOT, g_x + (size_t)m0 * D_ + g * 128 + 64, wrow0, lane);
          __syncwarp();
          if (lane == 0) mbar_arrive(bar + B_XDONE);
          nbar_dyn(3 + wu, 128);
        }
        sp = s;
        if (++s == 3) { s = 0; ++u; }
      }
      {
        const uint64_t dap = make_desc_ns(sb + SM_AP + wu * 1024, 0, 128), dbp = make_desc_ns(sb + SM_BP + (layer & 1) * 6144, 0, 128);
        if (wu == 0) {
          wgmma_wait<0>();
          if (elected) mbar_arrive(bar + B_R0);
          nbar<6, 256>();
        }
        if (layer < 2) mbar_wait(bar + (layer ? B_CS2 : B_CS), 0);
        mbar_wait(bar + B_STAT, layer & 1);
        mbar_wait(bar + B_FULLS + 16, layer & 1);
        wgmma_fence();
        wgmma_n256_k(acc, dap, dbp, 1);
#pragma unroll
        for (int k = 0; k < 4; ++k) wgmma_n256(acc, D128(dA0 + (QA >> 8) * 1024 + k * 2), D128(dB0 + (QK >> 8) * 1024 + k * 128), 1);
        mbar_wait(bar + B_FULLS, 1);
        PROFT(tid_ == 128, layer * 16 + 9);
        wgmma_fence();
#pragma unroll
        for (int k = 0; k < 4; ++k) wgmma_n256(acc, D128(dA0 + (QA & 15) * 1024 + k * 2), D128(dB0 + (QK & 15) * 1024 + k * 128), 1);
        wgmma_commit();
        if (wu) nbar<6, 256>();
#define Q_TAIL() \
        wgmma_n128_k(acc, dap, dbp + 256, 1); \
        _Pragma("unroll") for (int k = 0; k < 4; ++k) wgmma_n128(acc, D128(dA0 + (QA >> 8) * 1024 + k * 2), D128(dB0 + (QQ >> 8) * 1024 + k * 128), 1); \
        _Pragma("unroll") for (int k = 0; k < 4; ++k) wgmma_n128(acc, D128(dA0 + (QA & 15) * 1024 + k * 2), D128(dB0 + (QQ & 15) * 1024 + k * 128), 1);
        Q_TAIL();
        wgmma_commit();
        wgmma_wait<1>();
#pragma unroll
        for (int i = 0; i < 128; ++i) asm volatile("" : "+f"(acc[i]) :: "memory");
      }
    }
    uint32_t xo[32];
    uint32_t oq[8][4];
    {
      PHASE_CTX();
      PROFT(tid_ == 128, layer * 16 + 1);
      const bool isB = layer & 1;
      const int cu = c.cu;
      if (cu >= 4) asm volatile("bar.arrive 7, 256;" ::: "memory");
      if (elected && cu == 4) mbar_arrive(bar + B_R0);
      uint32_t kq[64];
      const uint32_t rowq = rowo & 8191;
      const float rs0 = lds_f(sb + SM_RS + (16 + wrow0 + gq) * 4), rs1 = lds_f(sb + SM_RS + (24 + wrow0 + gq) * 4);
#define Q_DONE() \
      wgmma_wait<0>(); \
      if (lane == 0) release2(bar + B_E0); \
      _Pragma("unroll") for (int i = 128; i < 192; ++i) asm volatile("" : "+f"(acc[i]) :: "memory"); \
      _Pragma("unroll") for (int i = 0; i < 32; ++i) kq[32 + i] = pack_bf16(acc[128 + 2 * i], acc[129 + 2 * i]);
      if (isB) {
        if (cu == 0) asm volatile("bar.arrive 10, 64;" ::: "memory");
        if (elected) release2(bar + B_E1);
        const int e = gq & 1;
        const bool sel = t > (gq >> 1);
        const uint32_t rja = sb + SM_RS + (wrow0 + 2 * t + e) * 4;
        const float rjA0 = lds_f(rja + 32), rjA1 = lds_f(rja + 64), rjB0 = lds_f(rja + (sel ? 0 : 64)), rjB1 = lds_f(rja + (sel ? 32 : 96));
        uint32_t vv[32];
#pragma unroll
        for (int i = 0; i < 16; ++i) { kq[i] = pack_bf16(acc[2 * i], acc[2 * i + 1]); vv[i] = pack_bf16(acc[64 + 2 * i], acc[65 + 2 * i]); }
        const uint32_t rB = sb + 4 * SLOT + wg * 4 * KVT + rowq;
        auto dump = [&](int hp) {
          const uint32_t kb = rB + 2048 + (hp ^ wg) * 2 * KVT;
#pragma unroll
          for (int jp = 0; jp < 4; ++jp) {
            stsm_x4(kb + (X ^ (jp << 5)), kq[16 * hp + 4 * jp], kq[16 * hp + 4 * jp + 1], kq[16 * hp + 4 * jp + 2], kq[16 * hp + 4 * jp + 3]);
            stsm_x4(kb + KVT + (X ^ (jp << 5)), vv[16 * hp + 4 * jp], vv[16 * hp + 4 * jp + 1], vv[16 * hp + 4 * jp + 2], vv[16 * hp + 4 * jp + 3]);
          }
          if (cu == 3) {
            const uint32_t kd = rB + 2048 + 32768 + (1 - hp) * 2 * KVT;
#pragma unroll
            for (int jp = 0; jp < 4; ++jp) {
              stsm_x4(kd + (X ^ (jp << 5)), kq[16 * hp + 4 * jp], kq[16 * hp + 4 * jp + 1], kq[16 * hp + 4 * jp + 2], kq[16 * hp + 4 * jp + 3]);
              stsm_x4(kd + KVT + (X ^ (jp << 5)), vv[16 * hp + 4 * jp], vv[16 * hp + 4 * jp + 1], vv[16 * hp + 4 * jp + 2], vv[16 * hp + 4 * jp + 3]);
            }
            if (hp) asm volatile("bar.arrive 15, 64;" ::: "memory"); else asm volatile("bar.arrive 9, 64;" ::: "memory");
          }
          asm volatile("bar.arrive %0, 224;" :: "r"(hp ? 13 + (cu >> 2) : 8 + (cu & 4)) : "memory");
        };
        uint4* const hbuf = g_halo + ((c.rb * 8 + g) * 2 + (layer >> 1)) * 512 + lane;
        if (cu < 4) {
          nbar<7, 256>();
          dump(0);
        }
#pragma unroll
        for (int i = 16; i < 32; ++i) { kq[i] = pack_bf16(acc[2 * i], acc[2 * i + 1]); vv[i] = pack_bf16(acc[64 + 2 * i], acc[65 + 2 * i]); }
        if (cu >= 4) {
          if (cu == 7) {
#pragma unroll
            for (int jp = 0; jp < 8; ++jp) {
              st_relaxed4(hbuf + jp * 32, ~kq[4 * jp], ~kq[4 * jp + 1], ~kq[4 * jp + 2], ~kq[4 * jp + 3]);
              st_relaxed4(hbuf + 256 + jp * 32, ~vv[4 * jp], ~vv[4 * jp + 1], ~vv[4 * jp + 2], ~vv[4 * jp + 3]);
            }
          }
          dump(0);
          dump(1);
        }
        PROFT(tid_ == 128, layer * 16 + 2);
        constexpr float SC = 0.17677669529663687f * L2E;
        const float fA0 = rjA0 * rs0 * SC, fB0 = rjB0 * rs0 * SC, fA1 = rjA1 * rs1 * SC, fB1 = rjB1 * rs1 * SC;
        const float bA0 = (m0 + wrow0) ? 0.f : -1e30f, bB = sel ? bA0 : 0.f;
        const uint32_t pA_ = e ? 0x1044u : 0x4410u, pB_ = e ? 0x3244u : 0x4432u, pLo = sel ? pB_ : 0x4444u, pHi = sel ? 0x4444u : pB_;
        const uint32_t KX = ((lane >> 3) ^ (lane & 7)) << 4;
        Q_DONE();
        if (cu == 0) {
          nbar<11, 64>();
        } else if (cu == 4) {
          uint4 hv[16];
          if (c.rb > 0) {
            uint32_t n = 0;
#pragma unroll 1
            while (true) {
              uint32_t mn = 0xFFFFFFFFu;
#pragma unroll
              for (int i = 0; i < 16; ++i) hv[i] = ld_relaxed4(hbuf - 16 * 512 + i * 32);
#pragma unroll
              for (int i = 0; i < 16; ++i) mn = __vimin3_u32(__vimin3_u32(mn, hv[i].x, hv[i].y), hv[i].z, hv[i].w);
              if (__all_sync(0xffffffffu, mn != 0u)) break;
              if (++n > (1u << 20)) { g_err = 4u; break; }
            }
          } else {
#pragma unroll
            for (int i = 0; i < 16; ++i) hv[i] = make_uint4(~0u, ~0u, ~0u, ~0u);
          }
          nbar<10, 64>();
#pragma unroll
          for (int i = 0; i < 16; ++i)
            stsm_x4(rB - 4 * KVT + (((i >> 2) & 1) * 2 + (i >> 3)) * KVT + (X ^ ((i & 3) << 5)), ~hv[i].x, ~hv[i].y, ~hv[i].z, ~hv[i].w);
          asm volatile("bar.arrive 11, 64;" ::: "memory");
          nbar<9, 64>();
        } else {
          nbar_dyn(8 + (cu & 4), 224);
        }
        PROFT(tid_ == 128, layer * 16 + 5);
        PROFT(lane == 0 && layer == PL, 136 + cw);
        auto attend = [&](int hp) {
          const uint32_t qad = sb + (XS + 1 - hp) * SLOT + rowo, kt = rB + 2 * (hp ^ wg) * KVT - (lane & 8) * 128, vt = rB + (2 * (hp ^ wg) + 1) * KVT;
          __syncwarp();
          uint32_t kb[2][2][4], vb[2][2][2][4];
#pragma unroll
          for (int h = 0; h < 2; ++h)
#pragma unroll
            for (int nt = 0; nt < 2; ++nt) ldsm_x4(kb[h][nt][0], kb[h][nt][1], kb[h][nt][2], kb[h][nt][3], kt + nt * 1024 + (KX ^ (h << 6)));
#pragma unroll
          for (int ks = 0; ks < 2; ++ks)
#pragma unroll
            for (int np = 0; np < 2; ++np)
#pragma unroll
              for (int h = 0; h < 2; ++h)
                ldsm_x4_t(vb[h][ks][np][0], vb[h][ks][np][1], vb[h][ks][np][2], vb[h][ks][np][3], vt + ks * 2048 + (X ^ (h << 6) ^ (np << 5)));
          if (hp == 0 && lane == 0) release2(bar + B_E3);
          if (DB1 == 1 && hp == 0 && cu < 4) dump(1);
          float la[2][2], lb[2][2], mx[2][2], sm[2][2];
#pragma unroll
          for (int h = 0; h < 2; ++h) {
            const int qo = 32 + 16 * hp + 8 * h, ko = 16 * hp + 8 * h;
            float sc[4][4];
#pragma unroll
            for (int nt = 0; nt < 4; ++nt) {
              sc[nt][0] = sc[nt][1] = sc[nt][2] = sc[nt][3] = 0.f;
#pragma unroll
              for (int ks = 0; ks < 2; ++ks)
                mma_bf16(sc[nt], kq[qo + 4 * ks], kq[qo + 4 * ks + 1], kq[qo + 4 * ks + 2], kq[qo + 4 * ks + 3],
                         nt < 2 ? kb[h][nt & 1][2 * ks] : kq[ko + 4 * ks + (nt & 1)], nt < 2 ? kb[h][nt & 1][2 * ks + 1] : kq[ko + 4 * ks + 2 + (nt & 1)]);
            }
            la[h][0] = fmaf(e ? sc[1][1] : sc[1][0], fA0, bA0);
            lb[h][0] = fmaf(sel ? (e ? sc[0][1] : sc[0][0]) : (e ? sc[2][1] : sc[2][0]), fB0, bB);
            la[h][1] = (e ? sc[2][3] : sc[2][2]) * fA1;
            lb[h][1] = fmaf(sel ? (e ? sc[1][3] : sc[1][2]) : (e ? sc[3][3] : sc[3][2]), fB1, bB);
            mx[h][0] = fmaxf(la[h][0], lb[h][0]); mx[h][1] = fmaxf(la[h][1], lb[h][1]);
          }
#pragma unroll
          for (int o = 1; o <= 2; o <<= 1)
#pragma unroll
            for (int h = 0; h < 2; ++h)
#pragma unroll
              for (int r = 0; r < 2; ++r) mx[h][r] = fmaxf(mx[h][r], __shfl_xor_sync(0xffffffffu, mx[h][r], o));
          float oa[2][4][4];
#pragma unroll
          for (int h = 0; h < 2; ++h) {
#pragma unroll
            for (int r = 0; r < 2; ++r) { la[h][r] = ex2(la[h][r] - mx[h][r]); lb[h][r] = ex2(lb[h][r] - mx[h][r]); sm[h][r] = la[h][r] + lb[h][r]; }
            const uint32_t p0 = pack_bf16(la[h][0] * rjA0, lb[h][0] * rjB0), p1 = pack_bf16(la[h][1] * rjA1, lb[h][1] * rjB1);
            const uint32_t a00 = __byte_perm(p0, 0u, pLo), a02 = __byte_perm(p0, 0u, pA_), a03 = __byte_perm(p1, 0u, pLo);
            const uint32_t a10 = __byte_perm(p0, 0u, pHi), a11 = __byte_perm(p1, 0u, pA_), a13 = __byte_perm(p1, 0u, pHi);
#pragma unroll
            for (int i = 0; i < 4; ++i) {
              oa[h][i][0] = oa[h][i][1] = oa[h][i][2] = oa[h][i][3] = 0.f;
              mma_bf16(oa[h][i], a00, 0u, a02, a03, vb[h][0][i >> 1][2 * (i & 1)], vb[h][0][i >> 1][2 * (i & 1) + 1]);
              mma_bf16(oa[h][i], a10, a11, 0u, a13, vb[h][1][i >> 1][2 * (i & 1)], vb[h][1][i >> 1][2 * (i & 1) + 1]);
            }
          }
#pragma unroll
          for (int o = 1; o <= 2; o <<= 1)
#pragma unroll
            for (int h = 0; h < 2; ++h)
#pragma unroll
              for (int r = 0; r < 2; ++r) sm[h][r] += __shfl_xor_sync(0xffffffffu, sm[h][r], o);
          mbar_wait(bar + (hp ? B_XOLD2 : B_XOLD), 1);
#pragma unroll
          for (int jp = 0; jp < 4; ++jp) ldsm_x4(xo[16 * hp + 4 * jp], xo[16 * hp + 4 * jp + 1], xo[16 * hp + 4 * jp + 2], xo[16 * hp + 4 * jp + 3], qad + (X ^ (jp << 5)));
#pragma unroll
          for (int h = 0; h < 2; ++h) {
            const float i0 = rcp(sm[h][0]), i1 = rcp(sm[h][1]);
#pragma unroll
            for (int np = 0; np < 2; ++np)
            {
              uint32_t (&o)[4] = oq[4 * hp + 2 * h + np];
              o[0] = pack_bf16(oa[h][2 * np][0] * i0, oa[h][2 * np][1] * i0); o[1] = pack_bf16(oa[h][2 * np][2] * i1, oa[h][2 * np][3] * i1);
              o[2] = pack_bf16(oa[h][2 * np + 1][0] * i0, oa[h][2 * np + 1][1] * i0); o[3] = pack_bf16(oa[h][2 * np + 1][2] * i1, oa[h][2 * np + 1][3] * i1);
              stsm_tag(qad + (X ^ (h << 6) ^ (np << 5)), o[0], o[1], o[2], o[3], make_tag(gq, t, 0u), 2 * h + np);
            }
          }
          __syncwarp();
          slab_out_half(sb + (XS + 1 - hp) * SLOT, g_o + (size_t)m0 * D_ + g * 128 + hp * 64, wrow0, lane);
          __syncwarp();
          if (lane == 0) mbar_arrive(bar + (hp ? B_ODONE : B_OH1));
          PROFT(lane == 0 && layer == PL && hp == 0, 128 + cw);
        };
        attend(0);
        if (DB1 == 2 && cu < 4) dump(1);
        if (cu == 4) nbar<15, 64>();
        else if (cu != 0) nbar_dyn(13 + (cu >> 2), 224);
        attend(1);
      } else {
#pragma unroll
        for (int i = 0; i < 32; ++i) kq[i] = pack_bf16(acc[2 * i], acc[2 * i + 1]);
        if (cu < 4) nbar<7, 256>();
        {
          const uint32_t vb = sb + (5 + 3 * wg) * SLOT + (rowq >> 1) + ((lchk ^ ((lane & 7) >> 1)) << 4);
#pragma unroll
          for (int jp = 8; jp < 16; ++jp)
            stsm_x4((vb ^ ((jp & 1) << 5)) + ((jp >> 1) & 3) * 4096,
                    pack_bf16(acc[8 * jp], acc[8 * jp + 1]), pack_bf16(acc[8 * jp + 2], acc[8 * jp + 3]),
                    pack_bf16(acc[8 * jp + 4], acc[8 * jp + 5]), pack_bf16(acc[8 * jp + 6], acc[8 * jp + 7]));
        }
        PROFT(tid_ == 128, layer * 16 + 2);
        Q_DONE();
        const uint32_t pA = sb + (3 + 3 * wg) * SLOT + (rowo & 8191);
        float sc0 = rs0 * L2E, sc1 = rs1 * L2E;
        const uint32_t wa0 = sb + SM_WPHI + lrow * 80 + lchk * 16;
        const uint32_t wu = c.cu >> 2, par = (layer >> 1) & 1;
        float p[2][4][4];
        uint32_t raw[2][4][4], ph[2][4][4];
        float kva[20], oa[2][20];
        auto kv_start = [&](int hp) {
#pragma unroll
          for (int h = 0; h < 2; ++h)
#pragma unroll
            for (int cp = 0; cp < 4; ++cp)
              stsm_x4(pA + hp * 16384 + h * 8192 + (X ^ (cp << 5)), ph[h][cp][0], ph[h][cp][1], ph[h][cp][2], ph[h][cp][3]);
          PROFT(tid_ == 128, layer * 16 + 11);
          fence_async_smem();
          nbar<1, 256>();
          const uint32_t hu = 2 * hp + wu;
          const uint32_t dP = (((sb + 3 * SLOT + hu * 8192) & 0x3FFFF) >> 4) | (512u << 16);
          const uint32_t dV = (((sb + 5 * SLOT + hu * 4096) & 0x3FFFF) >> 4) | (((SM_SD - 5 * SLOT - hu * 4096) >> 4) << 16);
          wgmma_fence();
#pragma unroll
          for (int ks = 0; ks < 8; ++ks)
            wgmma_n40_tt(kva, desc64(dP + (ks >> 2) * 3072 + (ks & 3) * 128, 0x40000040u),
                         desc64(dV + (ks >> 2) * (3072u - (2816u << 16)) + (ks & 3) * 64, 0x80000020u), ks != 0);
          wgmma_commit();
        };
        auto kv_end = [&](int hp) {
          wgmma_wait<0>();
#pragma unroll
          for (int i = 0; i < 20; ++i) asm volatile("" : "+f"(kva[i]) :: "memory");
          nbar_dyn(3 + wu, 128);
          PROFT(tid_ == 128, layer * 16 + 12);
          const bool od = lane & 1;
#pragma unroll
          for (int i = 0; i < 4; ++i)
            sts128(sb + (3 + hp) * SLOT + (cw * 128 + i * 32 + lane) * 16,
                   make_uint4(__float_as_uint(kva[4 * i]), __float_as_uint(kva[4 * i + 1]), __float_as_uint(kva[4 * i + 2]),
                              __float_as_uint(od == (i >= 2) ? 1.f : kva[4 * i + 3])));
          sts128(sb + (6 + hp) * SLOT + wg * 8192 + (wq * 32 + lane) * 16,
                 make_uint4(__float_as_uint(od ? kva[11] : kva[3]), __float_as_uint(od ? kva[15] : kva[7]), __float_as_uint(od ? kva[18] : kva[16]), __float_as_uint(1.f)));
          fence_async_smem();
          __syncwarp();
          if (lane == 0) mbar_arrive(bar + B_KVDONE - hp * 32);
          PROFT(tid_ == 128, layer * 16 + 3);
        };
        const uint4* const kvg = g_kv + (g * 2 + (layer >> 1)) * 2560 + cw * 128 + lane;
        uint4 u[5];
        auto kv_load = [&](int hp) {
#pragma unroll
          for (int i = 0; i < 4; ++i) u[i] = ld_relaxed4(kvg + hp * 1280 + i * 32);
          u[4] = ld_relaxed4(kvg + hp * 1280 + 1024 - cw * 96);
        };
        auto o_start = [&](int hp, const uint32_t (&pq)[2][4][4]) {
          PROFT(tid_ == 128 && hp == 0, layer * 16 + 10);
          if (hp == 0) mbar_wait(bar + B_KVDONE - 32, par);
          const bool od = lane & 1;
          uint32_t n = 0;
#pragma unroll 1
          while (!__all_sync(0xffffffffu, (od ? u[2].w : u[0].w) == 0x41800000u && (od ? u[3].w : u[1].w) == 0x41800000u && u[4].w == 0x41800000u)) {
#pragma unroll 1
            while (__any_sync(0xffffffffu, u[4].w < KVTH) && ++n < (1u << 20)) u[4].w = ld_relaxed(&kvg[hp * 1280 + 1024 - cw * 96].w);
            if (++n > (1u << 20)) { g_err = 6u; break; }
            kv_load(hp);
          }
          PROFT(tid_ == 128 && hp == 0, layer * 16 + 5);
          if (!od) { u[0].w = u[4].x; u[1].w = u[4].y; } else { u[2].w = u[4].x; u[3].w = u[4].y; }
#pragma unroll
          for (int i = 0; i < 4; i += 2)
            stsm_x4(sb + (5 + 3 * hp) * SLOT + rowo + (X ^ ((i & 2) << 4)),
                    pack_bf16(__uint_as_float(u[i].x), __uint_as_float(u[i].y)), pack_bf16(__uint_as_float(u[i].z), __uint_as_float(u[i].w)),
                    pack_bf16(__uint_as_float(u[i + 1].x), __uint_as_float(u[i + 1].y)), pack_bf16(__uint_as_float(u[i + 1].z), __uint_as_float(u[i + 1].w)));
          const uint32_t z2 = pack_bf16(__uint_as_float(u[4].z), __uint_as_float(u[4].z));
          if (t < 2) sts128(sb + (5 + 3 * hp) * SLOT + (wrow0 + gq + 8 * t) * 128 + ((4 ^ gq) << 4), make_uint4(z2, z2, z2, z2));
          fence_async_smem();
          nbar<1, 256>();
          PROFT(tid_ == 128 && hp == 1, layer * 16 + 4);
          const uint32_t dK = (((sb + (5 + 3 * hp) * SLOT) & 0x3FFFF) >> 4) | (512u << 16);
          wgmma_fence();
#pragma unroll
          for (int ks = 0; ks < 4; ++ks) {
#pragma unroll
            for (int hh = 0; hh < 2; ++hh) wgmma_n40_rs(oa[hh], pq[hh][ks], D128(dK + hh * 512 + ks * 128), ks != 0);
          }
          wgmma_commit();
        };
        auto o_end = [&](int hp) {
          wgmma_wait<0>();
#pragma unroll
          for (int i = 0; i < 20; ++i) asm volatile("" : "+f"(oa[0][i]), "+f"(oa[1][i]) :: "memory");
#pragma unroll
          for (int hh = 0; hh < 2; ++hh) {
            const float i0 = rcp(oa[hh][16] + 1e-6f), i1 = rcp(oa[hh][18] + 1e-6f);
            const uint32_t qad = sb + (3 + hp) * SLOT + rowo, hx = hh << 6;
#pragma unroll
            for (int np = 0; np < 2; ++np)
            {
              uint32_t (&o)[4] = oq[4 * hp + 2 * hh + np];
              o[0] = pack_bf16(oa[hh][8 * np] * i0, oa[hh][8 * np + 1] * i0); o[1] = pack_bf16(oa[hh][8 * np + 2] * i1, oa[hh][8 * np + 3] * i1);
              o[2] = pack_bf16(oa[hh][8 * np + 4] * i0, oa[hh][8 * np + 5] * i0); o[3] = pack_bf16(oa[hh][8 * np + 6] * i1, oa[hh][8 * np + 7] * i1);
              stsm_tag(qad + (X ^ hx ^ (np << 5)), o[0], o[1], o[2], o[3], make_tag(gq, t, 1u), 2 * hh + np);
            }
          }
          __syncwarp();
          slab_out_half(sb + (3 + hp) * SLOT, g_o + (size_t)m0 * D_ + g * 128 + hp * 64, wrow0, lane);
          __syncwarp();
          if (lane == 0) mbar_arrive(bar + (hp ? B_ODONE : B_OH1));
        };
#define XO_LOAD() \
        mbar_wait(bar + B_XOLD, 0); \
        mbar_wait(bar + B_XOLD2, 0); \
        _Pragma("unroll") for (int jp = 0; jp < 8; ++jp) \
          ldsm_x4(xo[4 * jp], xo[4 * jp + 1], xo[4 * jp + 2], xo[4 * jp + 3], sb + (XS + 1 - (jp >> 2)) * SLOT + rowo + (X ^ ((jp & 3) << 5)));
#define SC_RELOAD() \
        sc0 = __uint_as_float(lds_vol(sb + SM_RS + (16 + wrow0 + gq) * 4)) * L2E; sc1 = __uint_as_float(lds_vol(sb + SM_RS + (24 + wrow0 + gq) * 4)) * L2E;
        __syncwarp();
        phi_proj<0>(p, kq, wa0);
        phi_exp(raw[0], p[0], sc0, sc1);
        phi_exp(raw[1], p[1], sc0, sc1);
        phi_proj<16>(p, kq, wa0 + 5120);
        phi_norm<0>(ph, raw, kq, wa0, sc0, sc1, rs0, rs1);
        kv_start(0);
        phi_exp(raw[0], p[0], sc0, sc1);
        kv_end(0);
        if (RL & 1) { SC_RELOAD(); }
        XO_LOAD();
        phi_exp(raw[1], p[1], sc0, sc1);
        phi_proj<32>(p, kq, wa0);
        phi_norm<16>(ph, raw, kq, wa0 + 5120, sc0, sc1, rs0, rs1);
        kv_start(1);
        if (lane == 0) release2(bar + B_E3);
        phi_exp(raw[0], p[0], sc0, sc1);
        kv_end(1);
        if (RL & 2) { SC_RELOAD(); }
        kv_load(0);
        phi_exp(raw[1], p[1], sc0, sc1);
        phi_proj<48>(p, kq, wa0 + 5120);
        phi_norm<32>(ph, raw, kq, wa0, sc0, sc1, 1.f, 1.f);
        o_start(0, ph);
        phi_exp(raw[0], p[0], sc0, sc1);
        o_end(0);
        SC_RELOAD();
        kv_load(1);
        phi_exp(raw[1], p[1], sc0, sc1);
        phi_norm<48>(ph, raw, kq, wa0 + 5120, sc0, sc1, 1.f, 1.f);
        o_start(1, ph);
        o_end(1);
      }
      __syncwarp();
      PROFT(lane == 0 && layer == PL, 216 + cw);
      if (lane == 0) mbar_arrive(bar + B_EPI);
      PROFT(tid_ == 128, layer * 16 + 6);
    }
    {
      PHASE_CTX();
      const uint32_t wu = c.cu >> 2;
      const uint32_t dA0 = (((sb + wu * 8192) & 0x3FFFF) >> 4) | (1u << 16), dB0 = ((sb & 0x3FFFF) >> 4) | (512u << 16);
#pragma unroll
      for (int i = 0; i < 32; ++i) { acc[128 + 2 * i] = bf_lo(xo[i]); acc[129 + 2 * i] = bf_hi(xo[i]); }
      uint64_t ta = ((layer & 1) ? WO_A1 : WO_A0) >> 8, tw = (layer & 1) ? WO_B1 : WO_B0;
      mbar_wait(bar + B_FULLT, layer & 1);
      mbar_wait(bar + B_FULLT + 8, layer & 1);
      PROFT(tid_ == 128 && layer == PL, 160);
      wgmma_fence();
#pragma unroll
      for (int k = 0; k < 8; ++k) wgmma_n128_rs(acc, oq[k], D128(dB0 + ((uint32_t)(tw >> (k & 4)) & 15) * 1024 + (k & 3) * 128), 1);
      wgmma_commit();
      tw >>= 8;
      if (lane == 0) release2(bar + B_E2);
#pragma unroll 1
      for (int i = 2; i < 16; ++i) {
        mbar_wait(bar + B_FULLT + i * 8, layer & 1);
        PROFT(tid_ == 128 && layer == PL, 160 + i);
        tile_check(sb + ((uint32_t)ta & 15) * SLOT, g_o + (size_t)m0 * D_ + ((2 * g + (int)(WOORD >> (4 * i))) & 15) * 64, wrow0, lane, ~layer);
        const uint32_t da = dA0 + ((uint32_t)ta & 15) * 1024, db = dB0 + ((uint32_t)tw & 15) * 1024;
        ta >>= 4; tw >>= 4;
        if (WSK && i == 16 - WSK && wu) nbar<6, 256>();
        wgmma_fence();
#pragma unroll
        for (int k = 0; k < 4; ++k) wgmma_n128(acc, D128(da + k * 2), D128(db + k * 128), 1);
        wgmma_commit();
        if (WSK && i == 15 && !wu) asm volatile("bar.arrive 6, 256;" ::: "memory");
        wgmma_wait<1>();
        if (elected && i < 12) release2(bar + B_CONS + (i - 1) * 8);
        if (elected && (unsigned)(i - 13) < 2u && layer + 1 < NLAYERS) release2(bar + B_EMPTYS + (i - 13) * 8);
      }
      const bool last = layer == NLAYERS - 1;
      Tag xt = make_tag(gq, (last || !(UNS & 1)) ? 4 : t, lds_vol(sb + SM_EPOCH) + layer + 1);
      asm volatile("" : "+r"(xt.me), "+r"(xt.mo), "+r"(xt.tg) :: "memory");
      wgmma_wait<0>();
#pragma unroll
      for (int i = 128; i < 192; ++i) asm volatile("" : "+f"(acc[i]) :: "memory");
      if (elected && !last) release2(bar + B_EMPTYS + 16);
      PROFT(tid_ == 128, layer * 16 + 7);
      X_HALF(0, xt);
      if (last) {
        __syncwarp();
        slab_out_half(sb + XS * SLOT, c.out + (size_t)m0 * D_ + g * 128, wrow0, lane);
        X_HALF(1, (Tag{0u, 0u, 0u}));
        __syncwarp();
        slab_out_half(sb + (XS + 1) * SLOT, c.out + (size_t)m0 * D_ + g * 128 + 64, wrow0, lane);
        __syncwarp();
        if (lane == 0) mbar_arrive(bar + B_XDONE);
        PROFT(tid_ == 128, layer * 16 + 24);
        break;
      }
      __syncwarp();
      slab_out_half(sb + XS * SLOT, g_x + (size_t)m0 * D_ + g * 128, wrow0, lane, true);
      __syncwarp();
      if (lane == 0) mbar_arrive(bar + B_XH0);
      nbar_dyn(3 + wu, 128);
    }
  }
}

__device__ __forceinline__ void flag_fetch(uint32_t bar, uint32_t cp, const unsigned int* f) {
  asm volatile("{\n.reg .pred p;\nelect.sync _|p, 0xffffffff;\n@p mbarrier.expect_tx.relaxed.cta.shared::cta.b64 [%2], 64;\n"
               "@p cp.async.bulk.shared::cluster.global.mbarrier::complete_tx::bytes [%0], [%1], 64, [%2];\n}\n"
               ::"r"(cp), "l"(f), "r"(bar + 128) : "memory");
}
__device__ __forceinline__ void src_wait_async(uint32_t bar, uint32_t cp, const unsigned int* f, unsigned int target, int kb, uint32_t& ready, int lane) {
  uint32_t n = 0;
#pragma unroll 1
  while (true) {
    ready |= __ballot_sync(0xffffffffu, (int)(lds_vol(cp + (lane & 15) * 4) - target) >= 0);
    if ((ready >> kb) & 1) break;
    if (n > (1u << 20)) { g_err = 5u; break; }
    if ((n++ & PMOD) == 0) flag_fetch(bar, cp, f);
    __nanosleep(PSL);
  }
}

__device__ __forceinline__ int kblock0(int i, int g) {
  const int j = i >> 1, p = max(g, NCOM) + j - NCOM;
  return (j < NCOM ? j : p < 8 ? p : p - 8 + NCOM) * 2 + (i & 1);
}

__device__ __forceinline__ int wo_kblock(int m, int g) { return (2 * g + (int)((WOORD >> (4 * m)) & 15)) & 15; }

__global__ void __cluster_dims__(2, 1, 1) __launch_bounds__(384, 1)
mega_kernel(const __grid_constant__ CUtensorMap tm_x0, const __grid_constant__ CUtensorMap tm_x,
            const __grid_constant__ CUtensorMap tm_o,
            const __grid_constant__ CUtensorMap tm_wA, const __grid_constant__ CUtensorMap tm_wB,
            const __grid_constant__ CUtensorMap tm_woA, const __grid_constant__ CUtensorMap tm_woB,
                        const bf16* __restrict__ wB, const bf16* __restrict__ wphi, bf16* __restrict__ out) {
  extern __shared__ uint8_t smem_raw[];
  const uint32_t sb = (smem_u32(smem_raw) + 1023u) & ~1023u;
  const uint32_t bar = sb + SM_BAR;
  const int warp = __shfl_sync(0xffffffffu, threadIdx.x >> 5, 0), lane = threadIdx.x & 31;
  if (blockIdx.x >= 128) {
    const int xb = blockIdx.x - 128;
    const int ch = threadIdx.x % 96, rg = threadIdx.x / 96, gg = xb * 2 + ch / 48, sec = (ch % 48) >> 4;
    const uint4* src = reinterpret_cast<const uint4*>(wB + (size_t)rg * 3072 + (sec == 2 ? 0 : 1024 + sec * 1024) + gg * 128 + (ch & 15) * 8);
    float s[8] = {0.f, 0.f, 0.f, 0.f, 0.f, 0.f, 0.f, 0.f};
#pragma unroll 1
    for (int r0 = 0; r0 < 256; r0 += 32) {
      uint4 v[32];
#pragma unroll
      for (int r = 0; r < 32; ++r) v[r] = __ldg(src + (size_t)(r0 + r) * 1536);
#pragma unroll
      for (int r = 0; r < 32; ++r) {
        s[0] += bf_lo(v[r].x); s[1] += bf_hi(v[r].x); s[2] += bf_lo(v[r].y); s[3] += bf_hi(v[r].y);
        s[4] += bf_lo(v[r].z); s[5] += bf_hi(v[r].z); s[6] += bf_lo(v[r].w); s[7] += bf_hi(v[r].w);
      }
    }
    float* cd = g_cs + (ld_relaxed(&g_epoch) & 1) * 6144 + 3072 + xb * 768 + ch * 8;
    red_add4(cd, s[0], s[1], s[2], s[3]);
    red_add4(cd + 4, s[4], s[5], s[6], s[7]);
    nbar<1, 384>();
    if (threadIdx.x < 2) flag_add(&g_csflag[8 + xb * 2 + threadIdx.x].v);
    return;
  }
  const int bid = blockIdx.x;
  const int cr = bid & 1;
  const int g = (bid >> 1) & 7;
  const int rb = (bid >> 4) * 2 + cr;
  const int m0 = rb * 128;

  if (warp < 4) {
    asm volatile("setmaxnreg.dec.sync.aligned.u32 40;");
    asm volatile("barrier.cluster.arrive.relaxed.aligned;" ::: "memory");
    const unsigned int epoch = warp ? ld_relaxed(&g_epoch) : 0u;
    if (warp) cluster_wait();
    unsigned int xbase = epoch * NLAYERS;
    auto wo_a = [&](int layer, int m1) {
      uint64_t ts = ((layer & 1) ? WO_A1 : WO_A0) >> (4 * m1), td = ((layer & 1) ? WO_DA1 : WO_DA0) >> (4 * m1), tk = WOORD >> (4 * m1);
      uint32_t ready = 0u;
#pragma unroll 1
      for (int m = m1; m < 16; m += AW) {
        const int kb = (2 * g + (uint32_t)tk) & 15;
        uint32_t dst = sb + ((uint32_t)ts & 15) * SLOT, fb = bar + B_FULLT + m * 8, eb = bar + B_CONS + ((uint32_t)td & 15) * 8;
        int kc = kb * 64;
        ts >>= 4 * AW; td >>= 4 * AW; tk >>= 4 * AW;
        asm volatile("" : "+r"(dst), "+r"(fb), "+r"(eb), "+r"(kc));
        bool fr = false;
        if (!((ready >> kb) & 1)) {
          PROFT(m == 2 && lane == 0, 64 + layer * 16 + 2);
          if (EP && m > EP) src_wait_async(bar, bar + B_FLG, g_of + rb * 32, xbase + layer + 1, kb, ready, lane);
          else fr = src_wait_tma(g_of + rb * 32, xbase + layer + 1, 1u << kb, ready, lane, eb, layer & 1);
          fence_async_all();
        }
        if (m == 6) mbar_wait_u(bar + B_EPI, layer & 1);
        if (!fr) mbar_wait_u(eb, layer & 1);
        tma_2d_e(dst, &tm_o, kc, m0, fb);
        if (EP && m >= EP && (ready & 0xFFFFu) != 0xFFFFu) flag_fetch(bar, bar + B_FLG, g_of + rb * 32);
        PROFT(lane == 0 && layer == PL, 176 + m);
      }
    };
    auto wo_w = [&](int layer) {
      const CUtensorMap* tx = layer == 0 ? &tm_x0 : &tm_x;
      const CUtensorMap* two = (layer & 1) ? &tm_woB : &tm_woA;
      uint64_t ts = (layer & 1) ? WO_B1 : WO_B0, td = (layer & 1) ? WO_DB1 : WO_DB0, tk = WOORD;
      uint32_t pb = 0;
      fence_async_all();
      mbar_wait_u(bar + B_R0, layer & 1);
      expect_tx_e(bar + B_XOLD, 16384);
      tma_2d_e(sb + (XS + 1) * SLOT, tx, g * 128, m0, bar + B_XOLD);
#pragma unroll 1
      for (int m = 0; m < 16; ++m) {
        uint32_t dst = sb + ((uint32_t)ts & 15) * SLOT + cr * 8192, fb = bar + B_FULLT + m * 8, eb = bar + B_CONS + ((uint32_t)td & 15) * 8;
        int kc = ((2 * g + (uint32_t)tk) & 15) * 64;
        ts >>= 4; td >>= 4; tk >>= 4;
        asm volatile("" : "+r"(dst), "+r"(fb), "+r"(eb), "+r"(kc));
        if (eb < bar + B_E3 && pb >= bar + B_E3) mbar_wait_u(bar + B_E2, layer & 1);
        if (eb != pb) mbar_wait_u(eb, layer & 1);
        pb = eb;
        tma_2d_mc_e(dst, two, g * 128 + cr * 64, kc, fb);
        expect_tx_e(fb, m < 2 ? 16384 : 32768);
        PROFT(lane == 0 && layer == PL, 144 + m);
        if (m == ((layer & 1) ? XB2 : 0)) {
          expect_tx_e(bar + B_XOLD2, 16384);
          tma_2d_e(sb + XS * SLOT, tx, g * 128 + 64, m0, bar + B_XOLD2);
        }
      }
    };
    if (warp == 0) {
      cluster_wait();
      PROFT(lane == 0, 125);
#pragma unroll 1
      for (int layer = 0; layer < NLAYERS; ++layer) {
        const CUtensorMap* tx = layer == 0 ? &tm_x0 : &tm_x;
        const CUtensorMap* tw = (layer & 1) ? &tm_wB : &tm_wA;
        uint32_t s = layer == 0, u = 0, ready = layer == 0 ? 0xFFFFu : 0u;
#pragma unroll 1
        for (int i = s; i < 16; ++i) {
          const int kb = layer == 0 ? kblock0(i, g) : wo_kblock(i, g), kc = kb * 64;
          const uint32_t fb = bar + B_FULLS + s * 8;
          const uint32_t kd = sb + (((QK >> (4 * s)) & 15) + cr) * SLOT, qd = sb + ((QQ >> (4 * s)) & 15) * SLOT + cr * 8192;
          const uint32_t need = 1u << kb;
          const bool ext = i >= 2 || layer == 0, early = ext && (ready & need) == need;
          mbar_wait_u(bar + B_EMPTYS + s * 8, (u + (s ? layer : 0) + 1) & 1);
          if (early) tma_2d_e(sb + ((QA >> (4 * s)) & 15) * SLOT, tx, kc, m0, fb);
          tma_2d_mc_e(kd, tw, 1024 + cr * 1024 + g * 128, kc, fb);
          tma_2d_mc_e(kd + 8192, tw, 1024 + cr * 1024 + g * 128 + 64, kc, fb);
          tma_2d_mc_e(qd, tw, g * 128 + cr * 64, kc, fb);
          expect_tx_e(fb, ext ? 65536 : 49152);
          PROFT(lane == 0 && layer == 0 && i == 1, 31);
          if (layer == 0 && g >= NCOM && i == XPF + (((g - NCOM) * XPM) >> 2)) {
            if (i <= 2) mbar_wait_u(bar + B_FULLS, 0);
            tma_pf_e(&tm_x0, g * 128, m0);
            tma_pf_e(&tm_x0, g * 128 + 64, m0);
          }
          if (layer < 2 && i >= PFS) {
            const int j = i - PFS;
            if (j < 2) tma_pf_e(layer ? &tm_woB : &tm_woA, g * 128 + j * 64, rb * 64);
            else if (j < 8 && layer == 0) tma_pf_e(&tm_wB, ((j >> 1) - 1) * 1024 + g * 128 + (j & 1) * 64, rb * 64);
          }
          if (ext && !early) {
            PROFT(i == 2 && lane == 0, 64 + layer * 16 + 0);
            src_wait_tma(g_xf + rb * 32, xbase + layer + 1, need, ready, lane, fb, 0);
            PROFT(i == 2 && lane == 0, 64 + layer * 16 + 1);
            fence_async_all();
            tma_2d_e(sb + ((QA >> (4 * s)) & 15) * SLOT, tx, kc, m0, fb);
          }
          if (++s == 3) { s = 0; ++u; }
        }
        if (layer == 0) xbase = ld_relaxed(&g_epoch) * NLAYERS;
        if (PG & 1) mbar_wait_u(bar + B_OH1, layer & 1);
        if (PG & 4) mbar_wait_u(bar + B_E3, layer & 1);
        wo_a(layer, 2);
      }
    } else {
      if (warp >= 2) {
        const int h2 = threadIdx.x - 64;
        if (h2 < 16) sts_f(sb + SM_RS + h2 * 4, 0.f);
        if (h2 == 0) sts_f(sb + SM_EPOCH, __uint_as_float(epoch));
        if (h2 < 16) sts_f(bar + B_FLG + h2 * 4, __uint_as_float(xbase));
        mbar_wait_u(bar + (CST < 3 ? B_FULLS + CST * 8 : B_EMPTYS + (CST - 3) * 8), 0);
        colsum(&tm_wA, g_cs + (epoch & 1) * 6144, rb, g, warp - 2, 2, lane, warp == 2 ? sb + SM_SD : (sb + SM_BP + 1023u) & ~1023u, bar + B_CB + (warp - 2) * 8, 0);
#pragma unroll 1
        for (int i = h2; i < 320; i += 64) g_kv[(g * 16 + rb) * 320 + i] = make_uint4(0u, 0u, 0u, 0u);
        fence_async_all();
        nbar<5, 64>();
        if (h2 == 0) flag_add(&g_csflag[g].v);
        PROFT(h2 == 0, 242);
#pragma unroll 1
        for (int i = h2; i < 512; i += 256) {
          uint4 w[4];
#pragma unroll
          for (int j = 0; j < 4; ++j) w[j] = __ldg(reinterpret_cast<const uint4*>(wphi + (size_t)g * 4096) + i + j * 64);
#pragma unroll
          for (int j = 0; j < 4; ++j) sts128(sb + SM_WPHI + ((i >> 2) + j * 16) * 80 + (i & 3) * 16, w[j]);
        }
      }
      if (warp == 1) {
        if (lane >= 27) {
          const CUtensorMap* tm = lane == 27 ? &tm_o : lane == 28 ? &tm_wB : lane == 29 ? &tm_woA : lane == 30 ? &tm_woB : &tm_x;
          asm volatile("prefetch.tensormap [%0];" ::"l"(tm) : "memory");
        }
        __syncwarp();
        {
#pragma unroll 1
          for (int e = 0;; ++e) {
            if (e > 0 && e < NLAYERS) {
              mbar_wait_u(bar + B_XH0, (e - 1) & 1);
              flag_set_x(g_xf + rb * 32 + 2 * g, xbase + e + 1, UNS & 1);
            }
            mbar_wait_u(bar + B_XDONE, e & 1);
            PROFT(e < 4, 64 + e * 16 + 4);
            if (e == NLAYERS) {
              if (bid == 0) g_epoch = epoch + 1;
              break;
            }
            PROFT(e < 4, 64 + e * 16 + 5);
            flag_set(g_xf + rb * 32 + 2 * g + 1, xbase + e + 1);
            PROFT(e < 4, 64 + e * 16 + 7);
            if ((e & 1) == 0) {
#pragma unroll 1
              for (int hp = 0; hp < 2; ++hp) {
                uint4* kvl = g_kv + ((g * 2 + (e >> 1)) * 2 + hp) * 1280;
                mbar_wait_u(bar + B_KVDONE - hp * 32, (e >> 1) & 1);
                PROFT(e == PL, 243 + hp * 4);
                bulk_red_add_e(kvl + rb * 64, sb + (3 + hp) * SLOT + rb * 1024, 16384 - rb * 1024);
                if (rb) bulk_red_add_e(kvl, sb + (3 + hp) * SLOT, rb * 1024);
                bulk_red_add_e(kvl + 1024, sb + (6 + hp) * SLOT, 2048);
                bulk_red_add_e(kvl + 1152, sb + (6 + hp) * SLOT + 8192, 2048);
                bulk_commit();
                PROFT(e < 4, 64 + e * 16 + 6);
              }
              bulk_wait_read0();
              __syncwarp();
              if (lane < 2) release2(bar + B_E1);
              __syncwarp();
            }
            mbar_wait_u(bar + B_OH1, e & 1);
            PROFT(e == PL, 251);
            flag_set_x(g_of + rb * 32 + 2 * g, xbase + e + 1, UNS & 2);
            PROFT(e < 4, 64 + e * 16 + 9);
            mbar_wait_u(bar + B_ODONE, e & 1);
            PROFT(e < 4, 64 + e * 16 + 8);
            flag_set_x(g_of + rb * 32 + 2 * g + 1, xbase + e + 1, UNS & 4);
            PROFT(e < 4, 64 + e * 16 + 11);
          }
        }
      } else {
        const int h2 = threadIdx.x - 64;
        const float* cs = g_cs + (epoch & 1) * 6144;
#pragma unroll 1
        for (int layer = 0; layer < NLAYERS; ++layer) {
          if (warp == 2 && layer < 2) {
            if ((PG & 2) && layer) mbar_wait_u(bar + B_XH0, 0);
            if (lane == 0) flag_wait_t<CSLP>(&g_csflag[layer * 8 + g].v, (epoch + 1) * (16u + layer));
            __syncwarp();
            float4 a[3];
#pragma unroll
            for (int i = 0; i < 3; ++i) a[i] = __ldcg(reinterpret_cast<const float4*>(cs + layer * 3072 + g * 384) + i * 32 + lane);
#pragma unroll 1
            for (int i = 0; i < 3; ++i) {
              const float av[4] = {a[0].x, a[0].y, a[0].z, a[0].w};
              a[0] = a[1]; a[1] = a[2];
#pragma unroll
              for (int j = 0; j < 4; ++j) {
                const float c1 = bf16r(av[j]), c2 = bf16r(av[j] - c1), c3 = (av[j] - c1) - c2;
                sts128(sb + SM_BP + layer * 6144 + ((i * 32 + lane) * 4 + j) * 16, make_uint4(pack_bf16(c1, c2), pack_bf16(c3, 0.f), 0u, 0u));
              }
            }
            fence_async_smem();
            __syncwarp();
            if (lane == 0) mbar_arrive(bar + (layer ? B_CS2 : B_CS));
            PROFT(lane == 0, 64 + layer * 16 + 12);
            if (layer == 0) {
              uint4* hz = g_halo + (rb * 8 + g) * 1024;
#pragma unroll 2
              for (int i = lane; i < 1024; i += 32) hz[i] = make_uint4(0u, 0u, 0u, 0u);
              if (lane < 12) reinterpret_cast<float4*>(g_cs + ((epoch & 1) ^ 1) * 6144 + bid * 48)[lane] = make_float4(0.f, 0.f, 0.f, 0.f);
              g_stats[(2 + (lane >> 4)) * S_ + m0 + g * 16 + (lane & 15)] = make_float2(0.f, 0.f);
              __syncwarp();
              if (lane == 0) flag_add(&g_csflag[8 + g].v);
            }
          }
          if (warp == 3) {
            const bool hal = (layer & 1) && rb > 0;
            {
              uint32_t rdy = 0u;
              src_wait<SSL>(g_xf + rb * 32, xbase + layer + 1, 0xAAAAu, rdy, lane);
              rdy = 0u;
              if (hal) src_wait<256>(g_xf + (rb - 1) * 32, xbase + layer + 1, 0xAAAAu, rdy, lane);
            }
            float2 u[5];
            const float2* sp = g_stats + layer * S_ + m0 + lane;
#pragma unroll
            for (int i = 0; i < 4; ++i) u[i] = __ldcg(sp + i * 32);
            u[4] = __ldcg(hal ? sp - 16 : sp);
            if (layer == 3) g_stats[(lane >> 4) * S_ + m0 + g * 16 + (lane & 15)] = make_float2(0.f, 0.f);
#pragma unroll
            for (int i = 0; i < 5; ++i) {
              const int r = i < 4 ? 16 + i * 32 + lane : lane;
              const float mean = u[i].x * (1.f / D_);
              const float var = fmaxf(fmaf(-u[i].x, mean, u[i].y) * (1.f / D_), 0.f);
              float sd;
              asm("sqrt.approx.f32 %0, %1;" : "=f"(sd) : "f"(bf16r(bf16r(var) + 1e-5f)));
              sd = bf16r(sd);
              if (i < 4 || hal) sts_f(sb + SM_RS + r * 4, rcp(sd));
              if (i < 4) {
                const float hm = -0.5f * bf16r(mean);
                const uint32_t s2 = pack_bf16(sd, sd);
                if (!(layer & 1)) sts128(sb + SM_SD + (r - 16) * 64 + ((r >> 1) & 3) * 16, make_uint4(s2, s2, s2, s2));
                sts128(sb + SM_AP + (r - 16) * 16, make_uint4(pack_bf16(hm, hm), pack_bf16(hm, 0.f), 0u, 0u));
              }
            }
            fence_async_smem();
            __syncwarp();
            if (lane == 0) mbar_arrive(bar + B_STAT);
            PROFT(lane == 0, 64 + layer * 16 + 14);
            wo_w(__shfl_sync(0xffffffffu, layer, 0));
          }
        }
      }
    }
    __syncwarp();
    asm volatile("barrier.cluster.arrive.relaxed.aligned;\nbarrier.cluster.wait.aligned;\n" ::: "memory");
  } else {
    if (warp == 5) {
      if (lane == 0) {
        mbar_init(bar + B_FULLS, 1);
        asm volatile("fence.mbarrier_init.release.cluster;" ::: "memory");
      }
      __syncwarp();
      expect_tx_e(bar + B_FULLS, 65536);
      tma_2d_e(sb + XS * SLOT, &tm_x0, 0, m0, bar + B_FULLS);
#pragma unroll
      for (int j = 0; j < 6; ++j)
        tma_2d_e(sb + (j < 4 ? j + 4 : j - 2) * 8192, &tm_wA, (j < 4 ? 1024 + (j >> 1) * 1024 : 0) + g * 128 + (j & 1) * 64, 0, bar + B_FULLS);
      PROFT(lane == 0, 241);
    }
    if (lane < 8 && warp != 5 && threadIdx.x != 128) {
      const int i = (warp - 4) * 8 + lane;
      mbar_init(bar + i * 8, i < 32 ? 1u << ((BAR_CNT >> (2 * i)) & 3) : i < 48 ? 1u : (i == 59 || i == 60 || i == 62) ? 16u : (i == 48 || i == 63) ? 8u : 4u);
      asm volatile("fence.mbarrier_init.release.cluster;" ::: "memory");
    }
    __syncwarp();
    asm volatile("barrier.cluster.arrive.relaxed.aligned;" ::: "memory");
    asm volatile("setmaxnreg.inc.sync.aligned.u32 232;");
    cluster_wait();
    PROFT(threadIdx.x == 128, 0);
    Ctx c; c.sb = sb; c.g = g; c.rb = rb; c.cu = warp - 4; c.out = out;
    consumer(c);
    asm volatile("bar.warp.sync 0xffffffff;\nbarrier.cluster.arrive.relaxed.aligned;\nbarrier.cluster.wait.aligned;\n" ::: "memory");
  }
}

typedef CUresult (*PFN_encodeTiled)(CUtensorMap*, CUtensorMapDataType, cuuint32_t, void*, const cuuint64_t*, const cuuint64_t*,
                                    const cuuint32_t*, const cuuint32_t*, CUtensorMapInterleave, CUtensorMapSwizzle,
                                    CUtensorMapL2promotion, CUtensorMapFloatOOBfill);

static CUtensorMap make_map(PFN_encodeTiled enc, const void* ptr, uint64_t cols, uint64_t rows, uint32_t box_c, uint32_t box_r, uint32_t nb = 1) {
  CUtensorMap m;
  cuuint64_t dims[3] = {nb > 1 ? box_c : cols, rows, cols / box_c};
  cuuint64_t strides[2] = {cols * 2, box_c * 2};
  cuuint32_t box[3] = {box_c, box_r, nb};
  cuuint32_t es[3] = {1, 1, 1};
  CUresult r = enc(&m, CU_TENSOR_MAP_DATA_TYPE_BFLOAT16, nb > 1 ? 3 : 2, const_cast<void*>(ptr), dims, strides, box, es, CU_TENSOR_MAP_INTERLEAVE_NONE,
      CU_TENSOR_MAP_SWIZZLE_128B, CU_TENSOR_MAP_L2_PROMOTION_L2_256B, CU_TENSOR_MAP_FLOAT_OOB_FILL_NONE);
  (void)r;
  return m;
}

extern "C" void kernel_launch(void* const* d_in, const int* in_sizes, int n_in, void* d_out, int out_size) {
  const bf16* A_x = (const bf16*)d_in[0];
  const bf16* A_wqkv = (const bf16*)d_in[1];
  const bf16* A_wphi = (const bf16*)d_in[2];
  const bf16* A_wo = (const bf16*)d_in[3];
  const bf16* B_wqkv = (const bf16*)d_in[5];
  const bf16* B_wo = (const bf16*)d_in[6];
  bf16* out = (bf16*)d_out;

  static PFN_encodeTiled enc = nullptr;
  static bf16 *p_x, *p_o;
  if (!enc) {
    void* fn = nullptr; cudaDriverEntryPointQueryResult qr;
    cudaGetDriverEntryPoint("cuTensorMapEncodeTiled", &fn, cudaEnableDefault, &qr);
    enc = (PFN_encodeTiled)fn;
    cudaGetSymbolAddress((void**)&p_x, g_x);
    cudaGetSymbolAddress((void**)&p_o, g_o);
    cudaFuncSetAttribute(mega_kernel, cudaFuncAttributeMaxDynamicSharedMemorySize, SM_TOTAL);
  }
  CUtensorMap tm_x0 = make_map(enc, A_x, 1024, 2048, 64, 128);
  CUtensorMap tm_x = make_map(enc, p_x, 1024, 2048, 64, 128);
  CUtensorMap tm_o = make_map(enc, p_o, 1024, 2048, 64, 128);
  CUtensorMap tm_wA = make_map(enc, A_wqkv, 3072, 1024, 64, 64);
  CUtensorMap tm_wB = make_map(enc, B_wqkv, 3072, 1024, 64, 64);
  CUtensorMap tm_woA = make_map(enc, A_wo, 1024, 1024, 64, 64);
  CUtensorMap tm_woB = make_map(enc, B_wo, 1024, 1024, 64, 64);
  mega_kernel<<<128 + NX, 384, SM_TOTAL, cudaStreamPerThread>>>(tm_x0, tm_x, tm_o, tm_wA, tm_wB, tm_woA, tm_woB,
                                                           B_wqkv, A_wphi, out);
}
```

```cpp
#include <cuda_runtime.h>
#include <cuda_bf16.h>
#include <cuda.h>
#include <stdint.h>

typedef __nv_bfloat16 bf16;

constexpr int S_ = 2048, D_ = 1024;

struct __align__(128) Flag { unsigned int v; unsigned int pad[31]; };
__device__ __align__(1024) bf16 g_x[S_ * D_];
__device__ __align__(1024) bf16 g_o[S_ * D_];
__device__ __align__(1024) uint4 g_halo[128 * 2 * 512];
__device__ __align__(1024) uint4 g_kv[8 * 2 * 2 * 1280];
__device__ __align__(1024) float2 g_stats[4 * S_];
__device__ __align__(1024) float g_cs[2 * 2 * 3072];
__device__ Flag g_csflag[16];
__device__ __align__(128) unsigned int g_xf[16 * 32], g_of[16 * 32];
__device__ unsigned int g_epoch, g_err;
#define PROFT(cond, idx) asm volatile("" ::: "memory")

__device__ __forceinline__ uint32_t smem_u32(const void* p) { return (uint32_t)__cvta_generic_to_shared(p); }
__device__ __forceinline__ void mbar_init(uint32_t bar, uint32_t count) {
  asm volatile("mbarrier.init.shared::cta.b64 [%0], %1;" ::"r"(bar), "r"(count) : "memory");
}
__device__ __forceinline__ void mbar_expect_tx(uint32_t bar, uint32_t bytes) {
  asm volatile("mbarrier.arrive.expect_tx.shared::cta.b64 _, [%0], %1;" ::"r"(bar), "r"(bytes) : "memory");
}
__device__ __forceinline__ void mbar_arrive(uint32_t bar) {
  asm volatile("mbarrier.arrive.shared::cta.b64 _, [%0];" ::"r"(bar) : "memory");
}
__device__ __forceinline__ bool mbar_try_wait(uint32_t bar, uint32_t parity) {
  uint32_t ok;
  asm volatile("{\n.reg .pred p;\nmbarrier.try_wait.parity.shared::cta.b64 p, [%1], %2;\nselp.b32 %0, 1, 0, p;\n}\n"
               : "=r"(ok) : "r"(bar), "r"(parity) : "memory");
  return ok != 0;
}
__device__ __forceinline__ bool mbar_test_wait(uint32_t bar, uint32_t parity) {
  uint32_t ok;
  asm volatile("{\n.reg .pred p;\nmbarrier.test_wait.parity.shared::cta.b64 p, [%1], %2;\nselp.b32 %0, 1, 0, p;\n}\n"
               : "=r"(ok) : "r"(bar), "r"(parity) : "memory");
  return ok != 0;
}
__device__ __forceinline__ uint64_t gtimer() {
  uint64_t t; asm volatile("mov.u64 %0, %globaltimer;" : "=l"(t)); return t;
}
__device__ __forceinline__ void mbar_wait(uint32_t bar, uint32_t parity) {
  uint32_t n = 0;
#pragma unroll 1
  while (!mbar_try_wait(bar, parity)) {
    if (++n > (1u << 22)) { g_err = 1u; break; }
  }
}
__device__ __forceinline__ unsigned int ld_acquire(const unsigned int* p) {
  unsigned int v; asm volatile("ld.acquire.gpu.global.u32 %0, [%1];" : "=r"(v) : "l"(p) : "memory"); return v;
}
__device__ __forceinline__ void flag_add(unsigned int* p) {
  asm volatile("red.release.gpu.global.add.u32 [%0], 1;" ::"l"(p) : "memory");
}
__device__ __forceinline__ void flag_set(unsigned int* p, unsigned int v) {
  asm volatile("st.release.gpu.global.u32 [%0], %1;" ::"l"(p), "r"(v) : "memory");
}
__device__ __forceinline__ void flag_set_x(unsigned int* p, unsigned int v, bool rlx) {
  if (rlx) asm volatile("st.relaxed.gpu.global.u32 [%0], %1;" ::"l"(p), "r"(v) : "memory"); else flag_set(p, v);
}
template <int SLEEP>
__device__ __forceinline__ void src_wait(const unsigned int* f, unsigned int target, uint32_t need, uint32_t& ready, int lane) {
  uint32_t n = 0;
#pragma unroll 1
  while ((ready & need) != need) {
    const unsigned int v = ld_acquire(f + (lane & 15));
    ready = __ballot_sync(0xffffffffu, (int)(v - target) >= 0);
    if (SLEEP) { if ((ready & need) != need) __nanosleep(SLEEP); }
    if (++n > (1u << 20)) { g_err = 3u; break; }
  }
  __syncwarp();
}
__device__ __forceinline__ unsigned int ld_relaxed(const unsigned int* p) {
  unsigned int v; asm volatile("ld.relaxed.gpu.global.u32 %0, [%1];" : "=r"(v) : "l"(p) : "memory"); return v;
}
__device__ __forceinline__ bool src_wait_tma(const unsigned int* f, unsigned int target, uint32_t need, uint32_t& ready, int lane, uint32_t eb, uint32_t par) {
  uint32_t n = 0;
  bool fr = false;
#pragma unroll 1
  while ((ready & need) != need) {
    const unsigned int v = ld_acquire(f + (lane & 15));
    fr = __all_sync(0xffffffffu, mbar_test_wait(eb, par));
    ready = __ballot_sync(0xffffffffu, (int)(v - target) >= 0);
    if (++n > (1u << 20)) { g_err = 3u; break; }
  }
  return fr;
}
__device__ __forceinline__ uint4 ld_relaxed4(const uint4* p) {
  uint4 v; asm volatile("ld.relaxed.gpu.global.v4.u32 {%0,%1,%2,%3}, [%4];" : "=r"(v.x), "=r"(v.y), "=r"(v.z), "=r"(v.w) : "l"(p) : "memory"); return v;
}
__device__ __forceinline__ void st_relaxed4(uint4* p, uint32_t a, uint32_t b, uint32_t c, uint32_t d) {
  asm volatile("st.relaxed.gpu.global.v4.u32 [%0], {%1,%2,%3,%4};" ::"l"(p), "r"(a), "r"(b), "r"(c), "r"(d) : "memory");
}
template <int SLEEP>
__device__ __forceinline__ void flag_wait_t(const unsigned int* p, unsigned int target) {
  uint32_t n = 0;
#pragma unroll 1
  while ((int)(ld_acquire(p) - target) < 0) {
    if (SLEEP) __nanosleep(SLEEP);
    if (++n > (1u << 20)) { g_err = 2u; break; }
  }
}
__device__ __forceinline__ void flag_wait(const unsigned int* p, unsigned int target) { flag_wait_t<0>(p, target); }
__device__ __forceinline__ void flag_wait_slow(const unsigned int* p, unsigned int target) { flag_wait_t<256>(p, target); }
__device__ __forceinline__ void tma_load_2d(uint32_t dst, const CUtensorMap* tm, int c0, int c1, uint32_t bar) {
  asm volatile("cp.async.bulk.tensor.2d.shared::cluster.global.mbarrier::complete_tx::bytes [%0], [%1, {%2, %3}], [%4];"
               ::"r"(dst), "l"(tm), "r"(c0), "r"(c1), "r"(bar) : "memory");
}
__device__ __forceinline__ void tma_load_2d_mc(uint32_t dst, const CUtensorMap* tm, int c0, int c1, uint32_t bar, uint16_t mask) {
  asm volatile("cp.async.bulk.tensor.2d.shared::cluster.global.mbarrier::complete_tx::bytes.multicast::cluster [%0], [%1, {%2, %3}], [%4], %5;"
               ::"r"(dst), "l"(tm), "r"(c0), "r"(c1), "r"(bar), "h"(mask) : "memory");
}
__device__ __forceinline__ void mbar_wait_u(uint32_t bar, uint32_t parity) {
  uint32_t n = 0;
#pragma unroll 1
  while (!__all_sync(0xffffffffu, mbar_try_wait(bar, parity))) {
    if (++n > (1u << 22)) { g_err = 1u; break; }
  }
}
__device__ __forceinline__ void expect_tx_e(uint32_t bar, uint32_t bytes) {
  asm volatile("{\n.reg .pred p;\nelect.sync _|p, 0xffffffff;\n@p mbarrier.arrive.expect_tx.shared::cta.b64 _, [%0], %1;\n}\n" ::"r"(bar), "r"(bytes) : "memory");
}
__device__ __forceinline__ void tma_2d_e(uint32_t dst, const CUtensorMap* tm, int c0, int c1, uint32_t bar) {
  asm volatile("{\n.reg .pred p;\nelect.sync _|p, 0xffffffff;\n"
               "@p cp.async.bulk.tensor.2d.shared::cluster.global.mbarrier::complete_tx::bytes [%0], [%1, {%2, %3}], [%4];\n}\n"
               ::"r"(dst), "l"(tm), "r"(c0), "r"(c1), "r"(bar) : "memory");
}
__device__ __forceinline__ void tma_2d_mc_e(uint32_t dst, const CUtensorMap* tm, int c0, int c1, uint32_t bar) {
  asm volatile("{\n.reg .pred p;\nelect.sync _|p, 0xffffffff;\n"
               "@p cp.async.bulk.tensor.2d.shared::cluster.global.mbarrier::complete_tx::bytes.multicast::cluster [%0], [%1, {%2, %3}], [%4], %5;\n}\n"
               ::"r"(dst), "l"(tm), "r"(c0), "r"(c1), "r"(bar), "h"((uint16_t)3) : "memory");
}
__device__ __forceinline__ void tma_pf_e(const CUtensorMap* tm, int c0, int c1) {
  asm volatile("{\n.reg .pred p;\nelect.sync _|p, 0xffffffff;\n"
               "@p cp.async.bulk.prefetch.tensor.2d.L2.global.tile [%0, {%1, %2}];\n}\n" ::"l"(tm), "r"(c0), "r"(c1) : "memory");
}
__device__ __forceinline__ void tma_2d_to_e(uint32_t dst, const CUtensorMap* tm, int c0, int c1, uint32_t bar, uint32_t mask) {
  asm volatile("{\n.reg .pred p;\nelect.sync _|p, 0xffffffff;\n"
               "@p cp.async.bulk.tensor.2d.shared::cluster.global.mbarrier::complete_tx::bytes.multicast::cluster [%0], [%1, {%2, %3}], [%4], %5;\n}\n"
               ::"r"(dst), "l"(tm), "r"(c0), "r"(c1), "r"(bar), "h"((uint16_t)mask) : "memory");
}
__device__ __forceinline__ void tma_3d_mc_e(uint32_t dst, const CUtensorMap* tm, int c1, int c2, uint32_t bar) {
  asm volatile("{\n.reg .pred p;\nelect.sync _|p, 0xffffffff;\n"
               "@p cp.async.bulk.tensor.3d.shared::cluster.global.mbarrier::complete_tx::bytes.multicast::cluster [%0], [%1, {%6, %2, %3}], [%4], %5;\n}\n"
               ::"r"(dst), "l"(tm), "r"(c1), "r"(c2), "r"(bar), "h"((uint16_t)3), "r"(0) : "memory");
}
__device__ __forceinline__ uint32_t poll_flags(const unsigned int* f, unsigned int target, int lane) {
  const unsigned int v = ld_acquire(f + (lane & 15));
  const uint32_t r = __ballot_sync(0xffffffffu, (int)(v - target) >= 0);
  __syncwarp();
  return r;
}
__device__ __forceinline__ void mbar_arrive_cluster(uint32_t local_bar, uint32_t rank) {
  asm volatile("{\n.reg .b32 ra;\nmapa.shared::cluster.u32 ra, %0, %1;\nmbarrier.arrive.shared::cluster.b64 _, [ra];\n}\n"
               ::"r"(local_bar), "r"(rank) : "memory");
}
__device__ __forceinline__ void release2(uint32_t bar) { mbar_arrive_cluster(bar, 0); mbar_arrive_cluster(bar, 1); }
__device__ __forceinline__ void tma_store_2d(const CUtensorMap* tm, uint32_t src, int c0, int c1) {
  asm volatile("cp.async.bulk.tensor.2d.global.shared::cta.bulk_group [%0, {%2, %3}], [%1];"
               ::"l"(tm), "r"(src), "r"(c0), "r"(c1) : "memory");
}
__device__ __forceinline__ void bulk_store(void* dst, uint32_t src, uint32_t bytes) {
  asm volatile("cp.async.bulk.global.shared::cta.bulk_group [%0], [%1], %2;" ::"l"(dst), "r"(src), "r"(bytes) : "memory");
}
__device__ __forceinline__ void bulk_load(uint32_t dst, const void* src, uint32_t bytes, uint32_t bar) {
  asm volatile("cp.async.bulk.shared::cluster.global.mbarrier::complete_tx::bytes [%0], [%1], %2, [%3];" ::"r"(dst), "l"(src), "r"(bytes), "r"(bar) : "memory");
}
__device__ __forceinline__ void bulk_red_add(void* dst, uint32_t src, uint32_t bytes) {
  asm volatile("cp.reduce.async.bulk.global.shared::cta.bulk_group.add.f32 [%0], [%1], %2;" ::"l"(dst), "r"(src), "r"(bytes) : "memory");
}
__device__ __forceinline__ void bulk_red_add_e(void* dst, uint32_t src, uint32_t bytes) {
  asm volatile("{\n.reg .pred p;\nelect.sync _|p, 0xffffffff;\n@p cp.reduce.async.bulk.global.shared::cta.bulk_group.add.f32 [%0], [%1], %2;\n}\n" ::"l"(dst), "r"(src), "r"(bytes) : "memory");
}
__device__ __forceinline__ void bulk_commit() { asm volatile("cp.async.bulk.commit_group;" ::: "memory"); }
__device__ __forceinline__ void bulk_wait_read0() { asm volatile("cp.async.bulk.wait_group.read 0;" ::: "memory"); }
__device__ __forceinline__ void bulk_wait0() { asm volatile("cp.async.bulk.wait_group 0;" ::: "memory"); }
__device__ __forceinline__ void fence_async_smem() { asm volatile("fence.proxy.async.shared::cta;" ::: "memory"); }
__device__ __forceinline__ void fence_async_all() { asm volatile("fence.proxy.async.global;" ::: "memory"); }
__device__ __forceinline__ void wgmma_fence() { asm volatile("wgmma.fence.sync.aligned;" ::: "memory"); }
__device__ __forceinline__ void wgmma_commit() { asm volatile("wgmma.commit_group.sync.aligned;" ::: "memory"); }
template <int N> __device__ __forceinline__ void wgmma_wait() { asm volatile("wgmma.wait_group.sync.aligned %0;" ::"n"(N) : "memory"); }
__device__ __forceinline__ void cluster_arrive() { asm volatile("barrier.cluster.arrive.release.aligned;" ::: "memory"); }
__device__ __forceinline__ void cluster_wait() { asm volatile("barrier.cluster.wait.acquire.aligned;" ::: "memory"); }
template <int ID, int N> __device__ __forceinline__ void nbar() { asm volatile("bar.sync %0, %1;" ::"n"(ID), "n"(N) : "memory"); }
__device__ __forceinline__ uint64_t make_desc(uint32_t addr, uint32_t lbo_bytes, uint32_t sbo_bytes) {
  uint64_t d = 0;
  d |= (uint64_t)((addr & 0x3FFFF) >> 4);
  d |= (uint64_t)((lbo_bytes >> 4) & 0x3FFF) << 16;
  d |= (uint64_t)((sbo_bytes >> 4) & 0x3FFF) << 32;
  d |= (uint64_t)1 << 62;
  return d;
}
__device__ __forceinline__ uint64_t desc64(uint32_t lo, uint32_t hi) { return (uint64_t)lo | ((uint64_t)hi << 32); }
__device__ __forceinline__ uint32_t pack_bf16(float lo, float hi) {
  uint32_t r; asm("cvt.rn.bf16x2.f32 %0, %1, %2;" : "=r"(r) : "f"(hi), "f"(lo)); return r;
}
__device__ __forceinline__ uint32_t mul_bf16x2(uint32_t a, uint32_t s, bool hi) {
  __nv_bfloat162 x = *reinterpret_cast<__nv_bfloat162*>(&a), y = *reinterpret_cast<__nv_bfloat162*>(&s);
  x = __hmul2(x, hi ? __high2bfloat162(y) : __low2bfloat162(y));
  return *reinterpret_cast<uint32_t*>(&x);
}
__device__ __forceinline__ float bf16r(float x) { return __bfloat162float(__float2bfloat16_rn(x)); }
__device__ __forceinline__ float bf_lo(uint32_t u) { return __uint_as_float(u << 16); }
__device__ __forceinline__ float bf_hi(uint32_t u) { return __uint_as_float(u & 0xFFFF0000u); }
__device__ __forceinline__ float ex2(float x) { float r; asm("ex2.approx.ftz.f32 %0, %1;" : "=f"(r) : "f"(x)); return r; }
__device__ __forceinline__ float rcp(float x) { float r; asm("rcp.approx.ftz.f32 %0, %1;" : "=f"(r) : "f"(x)); return r; }
__device__ __forceinline__ void mma_bf16(float (&d)[4], uint32_t a0, uint32_t a1, uint32_t a2, uint32_t a3, uint32_t b0, uint32_t b1) {
  asm("mma.sync.aligned.m16n8k16.row.col.f32.bf16.bf16.f32 {%0,%1,%2,%3}, {%4,%5,%6,%7}, {%8,%9}, {%0,%1,%2,%3};"
               : "+f"(d[0]), "+f"(d[1]), "+f"(d[2]), "+f"(d[3]) : "r"(a0), "r"(a1), "r"(a2), "r"(a3), "r"(b0), "r"(b1));
}
__device__ __forceinline__ void ldsm_x4(uint32_t& r0, uint32_t& r1, uint32_t& r2, uint32_t& r3, uint32_t addr) {
  asm volatile("ldmatrix.sync.aligned.m8n8.x4.shared.b16 {%0,%1,%2,%3}, [%4];"
               : "=r"(r0), "=r"(r1), "=r"(r2), "=r"(r3) : "r"(addr) : "memory");
}
__device__ __forceinline__ void ldsm_x4_t(uint32_t& r0, uint32_t& r1, uint32_t& r2, uint32_t& r3, uint32_t addr) {
  asm volatile("ldmatrix.sync.aligned.m8n8.x4.trans.shared.b16 {%0,%1,%2,%3}, [%4];"
               : "=r"(r0), "=r"(r1), "=r"(r2), "=r"(r3) : "r"(addr) : "memory");
}
__device__ __forceinline__ void ldsm_x2_t(uint32_t& r0, uint32_t& r1, uint32_t addr) {
  asm volatile("ldmatrix.sync.aligned.m8n8.x2.trans.shared.b16 {%0,%1}, [%2];"
               : "=r"(r0), "=r"(r1) : "r"(addr) : "memory");
}
__device__ __forceinline__ void stsm_x4(uint32_t addr, uint32_t r0, uint32_t r1, uint32_t r2, uint32_t r3) {
  asm volatile("stmatrix.sync.aligned.m8n8.x4.shared.b16 [%0], {%1,%2,%3,%4};"
               ::"r"(addr), "r"(r0), "r"(r1), "r"(r2), "r"(r3) : "memory");
}
__device__ __forceinline__ void stsm_x4_p(bool on, uint32_t addr, uint32_t r0, uint32_t r1, uint32_t r2, uint32_t r3) {
  asm volatile("{\n.reg .pred p;\nsetp.ne.b32 p, %5, 0;\n@p stmatrix.sync.aligned.m8n8.x4.shared.b16 [%0], {%1,%2,%3,%4};\n}\n"
               ::"r"(addr), "r"(r0), "r"(r1), "r"(r2), "r"(r3), "r"((int)on) : "memory");
}
__device__ __forceinline__ float2 lds_f2(uint32_t addr) {
  float2 v; asm volatile("ld.shared.v2.f32 {%0,%1}, [%2];" : "=f"(v.x), "=f"(v.y) : "r"(addr) : "memory"); return v;
}
__device__ __forceinline__ uint4 lds128(uint32_t addr) {
  uint4 v; asm volatile("ld.shared.v4.b32 {%0,%1,%2,%3}, [%4];" : "=r"(v.x), "=r"(v.y), "=r"(v.z), "=r"(v.w) : "r"(addr) : "memory"); return v;
}
__device__ __forceinline__ void sts128(uint32_t addr, uint4 v) {
  asm volatile("st.shared.v4.b32 [%0], {%1,%2,%3,%4};" ::"r"(addr), "r"(v.x), "r"(v.y), "r"(v.z), "r"(v.w) : "memory");
}
__device__ __forceinline__ float lds_f(uint32_t addr) {
  float v; asm volatile("ld.shared.f32 %0, [%1];" : "=f"(v) : "r"(addr) : "memory"); return v;
}
__device__ __forceinline__ uint32_t lds_vol(uint32_t addr) {
  uint32_t v; asm volatile("ld.volatile.shared.u32 %0, [%1];" : "=r"(v) : "r"(addr) : "memory"); return v;
}
__device__ __forceinline__ void sts16(uint32_t addr, uint32_t v) {
  asm volatile("st.shared.u16 [%0], %1;" ::"r"(addr), "h"((unsigned short)v) : "memory");
}
__device__ __forceinline__ void nbar_dyn(int id, int n) { asm volatile("bar.sync %0, %1;" ::"r"(id), "r"(n) : "memory"); }
__device__ __forceinline__ uint64_t make_desc_ns(uint32_t addr, uint32_t lbo_bytes, uint32_t sbo_bytes) {
  return (uint64_t)((addr & 0x3FFFF) >> 4) | ((uint64_t)(lbo_bytes >> 4) << 16) | ((uint64_t)(sbo_bytes >> 4) << 32);
}
__device__ __forceinline__ void sts_f(uint32_t addr, float v) { asm volatile("st.shared.f32 [%0], %1;" ::"r"(addr), "f"(v) : "memory"); }
__device__ __forceinline__ void sts64(uint32_t addr, uint32_t a, uint32_t b) {
  asm volatile("st.shared.v2.b32 [%0], {%1,%2};" ::"r"(addr), "r"(a), "r"(b) : "memory");
}
__device__ __forceinline__ void sts_f2(uint32_t addr, float a, float b) {
  asm volatile("st.shared.v2.f32 [%0], {%1,%2};" ::"r"(addr), "f"(a), "f"(b) : "memory");
}
__device__ __forceinline__ void red_add2(float* p, float a, float b) {
  asm volatile("red.global.add.v2.f32 [%0], {%1,%2};" ::"l"(p), "f"(a), "f"(b) : "memory");
}
__device__ __forceinline__ void red_add4(float* p, float a, float b, float c, float d) {
  asm volatile("red.global.add.v4.f32 [%0], {%1,%2,%3,%4};" ::"l"(p), "f"(a), "f"(b), "f"(c), "f"(d) : "memory");
}
__device__ __forceinline__ void red_add1(float* p, float a) {
  asm volatile("red.global.add.f32 [%0], %1;" ::"l"(p), "f"(a) : "memory");
}
__device__ __forceinline__ void l2_prefetch(const void* p, uint32_t bytes) {
  asm volatile("cp.async.bulk.prefetch.L2.global [%0], %1;" ::"l"(p), "r"(bytes) : "memory");
}

__device__ __forceinline__ void wgmma_n256(float (&d)[192], uint64_t da, uint64_t db, int scale_d) {
  asm volatile("{\n.reg .pred p;\nsetp.ne.b32 p, %130, 0;\n"
    "wgmma.mma_async.sync.aligned.m64n256k16.f32.bf16.bf16 {%0, %1, %2, %3, %4, %5, %6, %7, %8, %9, %10, %11, %12, %13, %14, %15, %16, %17, %18, %19, %20, %21, %22, %23, %24, %25, %26, %27, %28, %29, %30, %31, %32, %33, %34, %35, %36, %37, %38, %39, %40, %41, %42, %43, %44, %45, %46, %47, %48, %49, %50, %51, %52, %53, %54, %55, %56, %57, %58, %59, %60, %61, %62, %63, %64, %65, %66, %67, %68, %69, %70, %71, %72, %73, %74, %75, %76, %77, %78, %79, %80, %81, %82, %83, %84, %85, %86, %87, %88, %89, %90, %91, %92, %93, %94, %95, %96, %97, %98, %99, %100, %101, %102, %103, %104, %105, %106, %107, %108, %109, %110, %111, %112, %113, %114, %115, %116, %117, %118, %119, %120, %121, %122, %123, %124, %125, %126, %127}, %128, %129, p, 1, 1, 0, 1;\n}\n"
    : "+f"(d[0]), "+f"(d[1]), "+f"(d[2]), "+f"(d[3]), "+f"(d[4]), "+f"(d[5]), "+f"(d[6]), "+f"(d[7]), "+f"(d[8]), "+f"(d[9]), "+f"(d[10]), "+f"(d[11]), "+f"(d[12]), "+f"(d[13]), "+f"(d[14]), "+f"(d[15]), "+f"(d[16]), "+f"(d[17]), "+f"(d[18]), "+f"(d[19]), "+f"(d[20]), "+f"(d[21]), "+f"(d[22]), "+f"(d[23]), "+f"(d[24]), "+f"(d[25]), "+f"(d[26]), "+f"(d[27]), "+f"(d[28]), "+f"(d[29]), "+f"(d[30]), "+f"(d[31]), "+f"(d[32]), "+f"(d[33]), "+f"(d[34]), "+f"(d[35]), "+f"(d[36]), "+f"(d[37]), "+f"(d[38]), "+f"(d[39]), "+f"(d[40]), "+f"(d[41]), "+f"(d[42]), "+f"(d[43]), "+f"(d[44]), "+f"(d[45]), "+f"(d[46]), "+f"(d[47]), "+f"(d[48]), "+f"(d[49]), "+f"(d[50]), "+f"(d[51]), "+f"(d[52]), "+f"(d[53]), "+f"(d[54]), "+f"(d[55]), "+f"(d[56]), "+f"(d[57]), "+f"(d[58]), "+f"(d[59]), "+f"(d[60]), "+f"(d[61]), "+f"(d[62]), "+f"(d[63]), "+f"(d[64]), "+f"(d[65]), "+f"(d[66]), "+f"(d[67]), "+f"(d[68]), "+f"(d[69]), "+f"(d[70]), "+f"(d[71]), "+f"(d[72]), "+f"(d[73]), "+f"(d[74]), "+f"(d[75]), "+f"(d[76]), "+f"(d[77]), "+f"(d[78]), "+f"(d[79]), "+f"(d[80]), "+f"(d[81]), "+f"(d[82]), "+f"(d[83]), "+f"(d[84]), "+f"(d[85]), "+f"(d[86]), "+f"(d[87]), "+f"(d[88]), "+f"(d[89]), "+f"(d[90]), "+f"(d[91]), "+f"(d[92]), "+f"(d[93]), "+f"(d[94]), "+f"(d[95]), "+f"(d[96]), "+f"(d[97]), "+f"(d[98]), "+f"(d[99]), "+f"(d[100]), "+f"(d[101]), "+f"(d[102]), "+f"(d[103]), "+f"(d[104]), "+f"(d[105]), "+f"(d[106]), "+f"(d[107]), "+f"(d[108]), "+f"(d[109]), "+f"(d[110]), "+f"(d[111]), "+f"(d[112]), "+f"(d[113]), "+f"(d[114]), "+f"(d[115]), "+f"(d[116]), "+f"(d[117]), "+f"(d[118]), "+f"(d[119]), "+f"(d[120]), "+f"(d[121]), "+f"(d[122]), "+f"(d[123]), "+f"(d[124]), "+f"(d[125]), "+f"(d[126]), "+f"(d[127])
    : "l"(da), "l"(db), "r"(scale_d));
}
__device__ __forceinline__ void wgmma_n128(float (&d)[192], uint64_t da, uint64_t db, int scale_d) {
  asm volatile("{\n.reg .pred p;\nsetp.ne.b32 p, %66, 0;\n"
    "wgmma.mma_async.sync.aligned.m64n128k16.f32.bf16.bf16 {%0, %1, %2, %3, %4, %5, %6, %7, %8, %9, %10, %11, %12, %13, %14, %15, %16, %17, %18, %19, %20, %21, %22, %23, %24, %25, %26, %27, %28, %29, %30, %31, %32, %33, %34, %35, %36, %37, %38, %39, %40, %41, %42, %43, %44, %45, %46, %47, %48, %49, %50, %51, %52, %53, %54, %55, %56, %57, %58, %59, %60, %61, %62, %63}, %64, %65, p, 1, 1, 0, 1;\n}\n"
    : "+f"(d[128]), "+f"(d[129]), "+f"(d[130]), "+f"(d[131]), "+f"(d[132]), "+f"(d[133]), "+f"(d[134]), "+f"(d[135]), "+f"(d[136]), "+f"(d[137]), "+f"(d[138]), "+f"(d[139]), "+f"(d[140]), "+f"(d[141]), "+f"(d[142]), "+f"(d[143]), "+f"(d[144]), "+f"(d[145]), "+f"(d[146]), "+f"(d[147]), "+f"(d[148]), "+f"(d[149]), "+f"(d[150]), "+f"(d[151]), "+f"(d[152]), "+f"(d[153]), "+f"(d[154]), "+f"(d[155]), "+f"(d[156]), "+f"(d[157]), "+f"(d[158]), "+f"(d[159]), "+f"(d[160]), "+f"(d[161]), "+f"(d[162]), "+f"(d[163]), "+f"(d[164]), "+f"(d[165]), "+f"(d[166]), "+f"(d[167]), "+f"(d[168]), "+f"(d[169]), "+f"(d[170]), "+f"(d[171]), "+f"(d[172]), "+f"(d[173]), "+f"(d[174]), "+f"(d[175]), "+f"(d[176]), "+f"(d[177]), "+f"(d[178]), "+f"(d[179]), "+f"(d[180]), "+f"(d[181]), "+f"(d[182]), "+f"(d[183]), "+f"(d[184]), "+f"(d[185]), "+f"(d[186]), "+f"(d[187]), "+f"(d[188]), "+f"(d[189]), "+f"(d[190]), "+f"(d[191])
    : "l"(da), "l"(db), "r"(scale_d));
}
__device__ __forceinline__ void wgmma_n256_k(float (&d)[192], uint64_t da, uint64_t db, int scale_d) {
  asm volatile("{\n.reg .pred p;\nsetp.ne.b32 p, %130, 0;\n"
    "wgmma.mma_async.sync.aligned.m64n256k16.f32.bf16.bf16 {%0, %1, %2, %3, %4, %5, %6, %7, %8, %9, %10, %11, %12, %13, %14, %15, %16, %17, %18, %19, %20, %21, %22, %23, %24, %25, %26, %27, %28, %29, %30, %31, %32, %33, %34, %35, %36, %37, %38, %39, %40, %41, %42, %43, %44, %45, %46, %47, %48, %49, %50, %51, %52, %53, %54, %55, %56, %57, %58, %59, %60, %61, %62, %63, %64, %65, %66, %67, %68, %69, %70, %71, %72, %73, %74, %75, %76, %77, %78, %79, %80, %81, %82, %83, %84, %85, %86, %87, %88, %89, %90, %91, %92, %93, %94, %95, %96, %97, %98, %99, %100, %101, %102, %103, %104, %105, %106, %107, %108, %109, %110, %111, %112, %113, %114, %115, %116, %117, %118, %119, %120, %121, %122, %123, %124, %125, %126, %127}, %128, %129, p, 1, 1, 0, 0;\n}\n"
    : "+f"(d[0]), "+f"(d[1]), "+f"(d[2]), "+f"(d[3]), "+f"(d[4]), "+f"(d[5]), "+f"(d[6]), "+f"(d[7]), "+f"(d[8]), "+f"(d[9]), "+f"(d[10]), "+f"(d[11]), "+f"(d[12]), "+f"(d[13]), "+f"(d[14]), "+f"(d[15]), "+f"(d[16]), "+f"(d[17]), "+f"(d[18]), "+f"(d[19]), "+f"(d[20]), "+f"(d[21]), "+f"(d[22]), "+f"(d[23]), "+f"(d[24]), "+f"(d[25]), "+f"(d[26]), "+f"(d[27]), "+f"(d[28]), "+f"(d[29]), "+f"(d[30]), "+f"(d[31]), "+f"(d[32]), "+f"(d[33]), "+f"(d[34]), "+f"(d[35]), "+f"(d[36]), "+f"(d[37]), "+f"(d[38]), "+f"(d[39]), "+f"(d[40]), "+f"(d[41]), "+f"(d[42]), "+f"(d[43]), "+f"(d[44]), "+f"(d[45]), "+f"(d[46]), "+f"(d[47]), "+f"(d[48]), "+f"(d[49]), "+f"(d[50]), "+f"(d[51]), "+f"(d[52]), "+f"(d[53]), "+f"(d[54]), "+f"(d[55]), "+f"(d[56]), "+f"(d[57]), "+f"(d[58]), "+f"(d[59]), "+f"(d[60]), "+f"(d[61]), "+f"(d[62]), "+f"(d[63]), "+f"(d[64]), "+f"(d[65]), "+f"(d[66]), "+f"(d[67]), "+f"(d[68]), "+f"(d[69]), "+f"(d[70]), "+f"(d[71]), "+f"(d[72]), "+f"(d[73]), "+f"(d[74]), "+f"(d[75]), "+f"(d[76]), "+f"(d[77]), "+f"(d[78]), "+f"(d[79]), "+f"(d[80]), "+f"(d[81]), "+f"(d[82]), "+f"(d[83]), "+f"(d[84]), "+f"(d[85]), "+f"(d[86]), "+f"(d[87]), "+f"(d[88]), "+f"(d[89]), "+f"(d[90]), "+f"(d[91]), "+f"(d[92]), "+f"(d[93]), "+f"(d[94]), "+f"(d[95]), "+f"(d[96]), "+f"(d[97]), "+f"(d[98]), "+f"(d[99]), "+f"(d[100]), "+f"(d[101]), "+f"(d[102]), "+f"(d[103]), "+f"(d[104]), "+f"(d[105]), "+f"(d[106]), "+f"(d[107]), "+f"(d[108]), "+f"(d[109]), "+f"(d[110]), "+f"(d[111]), "+f"(d[112]), "+f"(d[113]), "+f"(d[114]), "+f"(d[115]), "+f"(d[116]), "+f"(d[117]), "+f"(d[118]), "+f"(d[119]), "+f"(d[120]), "+f"(d[121]), "+f"(d[122]), "+f"(d[123]), "+f"(d[124]), "+f"(d[125]), "+f"(d[126]), "+f"(d[127])
    : "l"(da), "l"(db), "r"(scale_d));
}
__device__ __forceinline__ void wgmma_n128_k(float (&d)[192], uint64_t da, uint64_t db, int scale_d) {
  asm volatile("{\n.reg .pred p;\nsetp.ne.b32 p, %66, 0;\n"
    "wgmma.mma_async.sync.aligned.m64n128k16.f32.bf16.bf16 {%0, %1, %2, %3, %4, %5, %6, %7, %8, %9, %10, %11, %12, %13, %14, %15, %16, %17, %18, %19, %20, %21, %22, %23, %24, %25, %26, %27, %28, %29, %30, %31, %32, %33, %34, %35, %36, %37, %38, %39, %40, %41, %42, %43, %44, %45, %46, %47, %48, %49, %50, %51, %52, %53, %54, %55, %56, %57, %58, %59, %60, %61, %62, %63}, %64, %65, p, 1, 1, 0, 0;\n}\n"
    : "+f"(d[128]), "+f"(d[129]), "+f"(d[130]), "+f"(d[131]), "+f"(d[132]), "+f"(d[133]), "+f"(d[134]), "+f"(d[135]), "+f"(d[136]), "+f"(d[137]), "+f"(d[138]), "+f"(d[139]), "+f"(d[140]), "+f"(d[141]), "+f"(d[142]), "+f"(d[143]), "+f"(d[144]), "+f"(d[145]), "+f"(d[146]), "+f"(d[147]), "+f"(d[148]), "+f"(d[149]), "+f"(d[150]), "+f"(d[151]), "+f"(d[152]), "+f"(d[153]), "+f"(d[154]), "+f"(d[155]), "+f"(d[156]), "+f"(d[157]), "+f"(d[158]), "+f"(d[159]), "+f"(d[160]), "+f"(d[161]), "+f"(d[162]), "+f"(d[163]), "+f"(d[164]), "+f"(d[165]), "+f"(d[166]), "+f"(d[167]), "+f"(d[168]), "+f"(d[169]), "+f"(d[170]), "+f"(d[171]), "+f"(d[172]), "+f"(d[173]), "+f"(d[174]), "+f"(d[175]), "+f"(d[176]), "+f"(d[177]), "+f"(d[178]), "+f"(d[179]), "+f"(d[180]), "+f"(d[181]), "+f"(d[182]), "+f"(d[183]), "+f"(d[184]), "+f"(d[185]), "+f"(d[186]), "+f"(d[187]), "+f"(d[188]), "+f"(d[189]), "+f"(d[190]), "+f"(d[191])
    : "l"(da), "l"(db), "r"(scale_d));
}
__device__ __forceinline__ void wgmma_n40_tt(float (&d)[20], uint64_t da, uint64_t db, int scale_d) {
  asm volatile("{\n.reg .pred p;\nsetp.ne.b32 p, %22, 0;\n"
    "wgmma.mma_async.sync.aligned.m64n40k16.f32.bf16.bf16 {%0, %1, %2, %3, %4, %5, %6, %7, %8, %9, %10, %11, %12, %13, %14, %15, %16, %17, %18, %19}, %20, %21, p, 1, 1, 1, 1;\n}\n"
    : "+f"(d[0]), "+f"(d[1]), "+f"(d[2]), "+f"(d[3]), "+f"(d[4]), "+f"(d[5]), "+f"(d[6]), "+f"(d[7]), "+f"(d[8]), "+f"(d[9]), "+f"(d[10]), "+f"(d[11]), "+f"(d[12]), "+f"(d[13]), "+f"(d[14]), "+f"(d[15]), "+f"(d[16]), "+f"(d[17]), "+f"(d[18]), "+f"(d[19])
    : "l"(da), "l"(db), "r"(scale_d));
}
__device__ __forceinline__ void wgmma_n40_rs(float (&d)[20], const uint32_t (&a)[4], uint64_t db, int scale_d) {
  asm volatile("{\n.reg .pred p;\nsetp.ne.b32 p, %25, 0;\n"
    "wgmma.mma_async.sync.aligned.m64n40k16.f32.bf16.bf16 {%0, %1, %2, %3, %4, %5, %6, %7, %8, %9, %10, %11, %12, %13, %14, %15, %16, %17, %18, %19}, {%20, %21, %22, %23}, %24, p, 1, 1, 1;\n}\n"
    : "+f"(d[0]), "+f"(d[1]), "+f"(d[2]), "+f"(d[3]), "+f"(d[4]), "+f"(d[5]), "+f"(d[6]), "+f"(d[7]), "+f"(d[8]), "+f"(d[9]), "+f"(d[10]), "+f"(d[11]), "+f"(d[12]), "+f"(d[13]), "+f"(d[14]), "+f"(d[15]), "+f"(d[16]), "+f"(d[17]), "+f"(d[18]), "+f"(d[19])
    : "r"(a[0]), "r"(a[1]), "r"(a[2]), "r"(a[3]), "l"(db), "r"(scale_d));
}
__device__ __forceinline__ void wgmma_n256_0(float (&d)[192], uint64_t da, uint64_t db) {
  asm volatile("{\n.reg .pred p;\nsetp.ne.b32 p, 0, 0;\n"
    "wgmma.mma_async.sync.aligned.m64n256k16.f32.bf16.bf16 {%0, %1, %2, %3, %4, %5, %6, %7, %8, %9, %10, %11, %12, %13, %14, %15, %16, %17, %18, %19, %20, %21, %22, %23, %24, %25, %26, %27, %28, %29, %30, %31, %32, %33, %34, %35, %36, %37, %38, %39, %40, %41, %42, %43, %44, %45, %46, %47, %48, %49, %50, %51, %52, %53, %54, %55, %56, %57, %58, %59, %60, %61, %62, %63, %64, %65, %66, %67, %68, %69, %70, %71, %72, %73, %74, %75, %76, %77, %78, %79, %80, %81, %82, %83, %84, %85, %86, %87, %88, %89, %90, %91, %92, %93, %94, %95, %96, %97, %98, %99, %100, %101, %102, %103, %104, %105, %106, %107, %108, %109, %110, %111, %112, %113, %114, %115, %116, %117, %118, %119, %120, %121, %122, %123, %124, %125, %126, %127}, %128, %129, p, 1, 1, 0, 1;\n}\n"
    : "=f"(d[0]), "=f"(d[1]), "=f"(d[2]), "=f"(d[3]), "=f"(d[4]), "=f"(d[5]), "=f"(d[6]), "=f"(d[7]), "=f"(d[8]), "=f"(d[9]), "=f"(d[10]), "=f"(d[11]), "=f"(d[12]), "=f"(d[13]), "=f"(d[14]), "=f"(d[15]), "=f"(d[16]), "=f"(d[17]), "=f"(d[18]), "=f"(d[19]), "=f"(d[20]), "=f"(d[21]), "=f"(d[22]), "=f"(d[23]), "=f"(d[24]), "=f"(d[25]), "=f"(d[26]), "=f"(d[27]), "=f"(d[28]), "=f"(d[29]), "=f"(d[30]), "=f"(d[31]), "=f"(d[32]), "=f"(d[33]), "=f"(d[34]), "=f"(d[35]), "=f"(d[36]), "=f"(d[37]), "=f"(d[38]), "=f"(d[39]), "=f"(d[40]), "=f"(d[41]), "=f"(d[42]), "=f"(d[43]), "=f"(d[44]), "=f"(d[45]), "=f"(d[46]), "=f"(d[47]), "=f"(d[48]), "=f"(d[49]), "=f"(d[50]), "=f"(d[51]), "=f"(d[52]), "=f"(d[53]), "=f"(d[54]), "=f"(d[55]), "=f"(d[56]), "=f"(d[57]), "=f"(d[58]), "=f"(d[59]), "=f"(d[60]), "=f"(d[61]), "=f"(d[62]), "=f"(d[63]), "=f"(d[64]), "=f"(d[65]), "=f"(d[66]), "=f"(d[67]), "=f"(d[68]), "=f"(d[69]), "=f"(d[70]), "=f"(d[71]), "=f"(d[72]), "=f"(d[73]), "=f"(d[74]), "=f"(d[75]), "=f"(d[76]), "=f"(d[77]), "=f"(d[78]), "=f"(d[79]), "=f"(d[80]), "=f"(d[81]), "=f"(d[82]), "=f"(d[83]), "=f"(d[84]), "=f"(d[85]), "=f"(d[86]), "=f"(d[87]), "=f"(d[88]), "=f"(d[89]), "=f"(d[90]), "=f"(d[91]), "=f"(d[92]), "=f"(d[93]), "=f"(d[94]), "=f"(d[95]), "=f"(d[96]), "=f"(d[97]), "=f"(d[98]), "=f"(d[99]), "=f"(d[100]), "=f"(d[101]), "=f"(d[102]), "=f"(d[103]), "=f"(d[104]), "=f"(d[105]), "=f"(d[106]), "=f"(d[107]), "=f"(d[108]), "=f"(d[109]), "=f"(d[110]), "=f"(d[111]), "=f"(d[112]), "=f"(d[113]), "=f"(d[114]), "=f"(d[115]), "=f"(d[116]), "=f"(d[117]), "=f"(d[118]), "=f"(d[119]), "=f"(d[120]), "=f"(d[121]), "=f"(d[122]), "=f"(d[123]), "=f"(d[124]), "=f"(d[125]), "=f"(d[126]), "=f"(d[127])
    : "l"(da), "l"(db));
}
__device__ __forceinline__ void wgmma_n128_0(float (&d)[192], uint64_t da, uint64_t db) {
  asm volatile("{\n.reg .pred p;\nsetp.ne.b32 p, 0, 0;\n"
    "wgmma.mma_async.sync.aligned.m64n128k16.f32.bf16.bf16 {%0, %1, %2, %3, %4, %5, %6, %7, %8, %9, %10, %11, %12, %13, %14, %15, %16, %17, %18, %19, %20, %21, %22, %23, %24, %25, %26, %27, %28, %29, %30, %31, %32, %33, %34, %35, %36, %37, %38, %39, %40, %41, %42, %43, %44, %45, %46, %47, %48, %49, %50, %51, %52, %53, %54, %55, %56, %57, %58, %59, %60, %61, %62, %63}, %64, %65, p, 1, 1, 0, 1;\n}\n"
    : "=f"(d[128]), "=f"(d[129]), "=f"(d[130]), "=f"(d[131]), "=f"(d[132]), "=f"(d[133]), "=f"(d[134]), "=f"(d[135]), "=f"(d[136]), "=f"(d[137]), "=f"(d[138]), "=f"(d[139]), "=f"(d[140]), "=f"(d[141]), "=f"(d[142]), "=f"(d[143]), "=f"(d[144]), "=f"(d[145]), "=f"(d[146]), "=f"(d[147]), "=f"(d[148]), "=f"(d[149]), "=f"(d[150]), "=f"(d[151]), "=f"(d[152]), "=f"(d[153]), "=f"(d[154]), "=f"(d[155]), "=f"(d[156]), "=f"(d[157]), "=f"(d[158]), "=f"(d[159]), "=f"(d[160]), "=f"(d[161]), "=f"(d[162]), "=f"(d[163]), "=f"(d[164]), "=f"(d[165]), "=f"(d[166]), "=f"(d[167]), "=f"(d[168]), "=f"(d[169]), "=f"(d[170]), "=f"(d[171]), "=f"(d[172]), "=f"(d[173]), "=f"(d[174]), "=f"(d[175]), "=f"(d[176]), "=f"(d[177]), "=f"(d[178]), "=f"(d[179]), "=f"(d[180]), "=f"(d[181]), "=f"(d[182]), "=f"(d[183]), "=f"(d[184]), "=f"(d[185]), "=f"(d[186]), "=f"(d[187]), "=f"(d[188]), "=f"(d[189]), "=f"(d[190]), "=f"(d[191])
    : "l"(da), "l"(db));
}
__device__ __forceinline__ void wgmma_n128_rs(float (&d)[192], const uint32_t (&a)[4], uint64_t db, int scale_d) {
  asm volatile("{\n.reg .pred p;\nsetp.ne.b32 p, %69, 0;\n"
    "wgmma.mma_async.sync.aligned.m64n128k16.f32.bf16.bf16 {%0, %1, %2, %3, %4, %5, %6, %7, %8, %9, %10, %11, %12, %13, %14, %15, %16, %17, %18, %19, %20, %21, %22, %23, %24, %25, %26, %27, %28, %29, %30, %31, %32, %33, %34, %35, %36, %37, %38, %39, %40, %41, %42, %43, %44, %45, %46, %47, %48, %49, %50, %51, %52, %53, %54, %55, %56, %57, %58, %59, %60, %61, %62, %63}, {%64, %65, %66, %67}, %68, p, 1, 1, 1;\n}\n"
    : "+f"(d[128]), "+f"(d[129]), "+f"(d[130]), "+f"(d[131]), "+f"(d[132]), "+f"(d[133]), "+f"(d[134]), "+f"(d[135]), "+f"(d[136]), "+f"(d[137]), "+f"(d[138]), "+f"(d[139]), "+f"(d[140]), "+f"(d[141]), "+f"(d[142]), "+f"(d[143]), "+f"(d[144]), "+f"(d[145]), "+f"(d[146]), "+f"(d[147]), "+f"(d[148]), "+f"(d[149]), "+f"(d[150]), "+f"(d[151]), "+f"(d[152]), "+f"(d[153]), "+f"(d[154]), "+f"(d[155]), "+f"(d[156]), "+f"(d[157]), "+f"(d[158]), "+f"(d[159]), "+f"(d[160]), "+f"(d[161]), "+f"(d[162]), "+f"(d[163]), "+f"(d[164]), "+f"(d[165]), "+f"(d[166]), "+f"(d[167]), "+f"(d[168]), "+f"(d[169]), "+f"(d[170]), "+f"(d[171]), "+f"(d[172]), "+f"(d[173]), "+f"(d[174]), "+f"(d[175]), "+f"(d[176]), "+f"(d[177]), "+f"(d[178]), "+f"(d[179]), "+f"(d[180]), "+f"(d[181]), "+f"(d[182]), "+f"(d[183]), "+f"(d[184]), "+f"(d[185]), "+f"(d[186]), "+f"(d[187]), "+f"(d[188]), "+f"(d[189]), "+f"(d[190]), "+f"(d[191])
    : "r"(a[0]), "r"(a[1]), "r"(a[2]), "r"(a[3]), "l"(db), "r"(scale_d));
}

constexpr int SLOT = 16384;
constexpr int KVT = 10240;
constexpr uint32_t QA = 0x0BAu, QK = 0x462u, QQ = 0x981u;
constexpr int SM_SD = 12 * SLOT;
constexpr int SM_BAR = SM_SD + 8192;
constexpr int SM_RS = SM_BAR + 512;
constexpr int SM_AP = SM_RS + 768;
constexpr int SM_BP = SM_AP + 2048;
constexpr int SM_WPHI = SM_BP + 12288;
constexpr int SM_EPOCH = SM_WPHI + 10240;
constexpr int SM_TOTAL = SM_EPOCH + 16 + 1024;
constexpr int B_FULLS = 0, B_XOLD = 24, B_STAT = 32, B_EMPTYS = 40, B_FULLT = 256  , B_CONS = 384  , B_E3 = 472, B_E0 = 480, B_E1 = 488, B_E2 = 496, B_EPI = 504, B_CS = 160,
              B_KVDONE = 168  , B_ODONE = 176, B_XDONE = 184, B_OH1 = B_CONS, B_CS2 = 208, B_XH0 = 232, B_R0 = 240, B_CB = 144  , B_XOLD2 = 216, B_FLG = 64  ;
constexpr uint64_t BAR_CNT = 0x1c07fc0eac00a800ull;
constexpr uint64_t WO_A0 = 0xa461b57648357643ull, WO_B0 = 0x59083a9021ba9021ull, WO_A1 = 0xa0b76901276a5babull, WO_B1 = 0x95428a5b34890132ull;
constexpr uint64_t WO_DA0 = 0xa9865432ff00dd00ull, WO_DB0 = 0xa986543211bbccccull, WO_DA1 = 0xa98654321ffff000ull, WO_DB1 = 0xa98754321bbcccddull;
#define WOORD 0xFDB9753ECA864210ull
constexpr int NX = 4;
constexpr int XS = 10;

#define PL 2
#define PROFX(i) PROFT(tid_ == 128 && layer == PL, 200 + (i))
#define PSL 20
#define EP 5
#define NCOM 3
#define CSLP 128
#define PFS 8
#define KVTH 0x41700000u
#define RL 3
#define ORD 1
#define XB2 2
#define PMOD 3
#define DB1 2
#define XPF 3
#define XPM 2
#define AW 1
#define PG 0
#define UNS 7
#define TLINE 1
#define WSK 1
#define ER 1
#define SSL 256
#define CST 0
#define NLAYERS 4
constexpr float L2E = 1.4426950408889634f;
#define PHI_MAX 2147483648.f

#define D128(lo) desc64(lo, 0x40000040u)
struct Ctx { uint32_t sb; int g, rb, cu; bf16* out; };

__device__ __forceinline__ void colsum(const CUtensorMap* tm, float* cs, int rb, int g, int w0, int dw, int lane, uint32_t stg, uint32_t cb, uint32_t par) {
  const uint32_t src = stg + (lane >> 3) * 2048;
#pragma unroll 1
  for (int wi = w0 - dw; wi < 6; wi += dw) {
    float s[8] = {0.f, 0.f, 0.f, 0.f, 0.f, 0.f, 0.f, 0.f};
    if (wi >= 0) {
      mbar_wait_u(cb, par);
      par ^= 1;
#pragma unroll 4
      for (int r = 0; r < 16; ++r) {
        const uint4 v = lds128(src + r * 128 + (((lane ^ r) & 7) << 4));
        s[0] += bf_lo(v.x); s[1] += bf_hi(v.x); s[2] += bf_lo(v.y); s[3] += bf_hi(v.y);
        s[4] += bf_lo(v.z); s[5] += bf_hi(v.z); s[6] += bf_lo(v.w); s[7] += bf_hi(v.w);
      }
#pragma unroll
      for (int i = 0; i < 8; ++i) s[i] += __shfl_xor_sync(0xffffffffu, s[i], 8);
    }
    const int wn = wi + dw;
    if (wn < 6) {
      expect_tx_e(cb, 8192);
      tma_2d_e(stg, tm, (wn >= 4 ? 0 : 1024 + (wn >> 1) * 1024) + g * 128 + (wn & 1) * 64, rb * 64, cb);
    }
    if (wi >= 0) {
#pragma unroll
      for (int i = 0; i < 8; ++i) s[i] += __shfl_xor_sync(0xffffffffu, s[i], 16);
      if (lane < 8) {
        red_add4(cs + g * 384 + (wi * 8 + lane) * 8, s[0], s[1], s[2], s[3]);
        red_add4(cs + g * 384 + (wi * 8 + lane) * 8 + 4, s[4], s[5], s[6], s[7]);
      }
      __syncwarp();
    }
  }
}
#define PHASE_CTX() \
  uint32_t sb = c.sb; asm volatile("" : "+r"(sb)); \
  int tid_ = threadIdx.x; asm volatile("" : "+r"(tid_)); \
  const uint32_t bar = sb + SM_BAR; \
  const int lane = tid_ & 31, cw = (tid_ >> 5) - 4, wg = cw >> 2, wq = cw & 3, gq = lane >> 2, t = lane & 3, wrow0 = cw * 16; \
  const int lrow = (lane & 7) + ((lane >> 3) & 1) * 8, lchk = lane >> 4; \
  const bool elected = (tid_ & 127) == 0; \
  const uint32_t rowo = (wrow0 + lrow) * 128, X = (lchk ^ (lane & 7)) << 4; \
  (void)bar; (void)wq; (void)gq; (void)lrow; (void)lchk; (void)elected; (void)wrow0; (void)wg; (void)rowo; (void)X; (void)t;

__device__ __forceinline__ void slab_out_half(uint32_t slot, bf16* dst, int wrow0, int lane, bool FENCE = false) {
  const int r0 = lane >> 3, ch = lane & 7;
  const uint32_t src = slot + (wrow0 + r0) * 128;
  uint4 v[4];
#pragma unroll
  for (int i = 0; i < 4; ++i) v[i] = lds128(src + i * 512 + (((ch ^ (4 * i + r0)) & 7) << 4));
  if (FENCE) fence_async_smem();
  dst += (size_t)(wrow0 + r0) * D_ + ch * 8;
#pragma unroll
  for (int i = 0; i < 4; ++i)
    asm volatile("st.global.v4.u32 [%0], {%1,%2,%3,%4};" ::"l"(dst + (size_t)i * 4 * D_), "r"(v[i].x), "r"(v[i].y), "r"(v[i].z), "r"(v[i].w) : "memory");
}

struct Tag { uint32_t me, mo, tg; };
__device__ __forceinline__ Tag make_tag(int gq, int t, uint32_t tg) { return Tag{t == 0, t == 1, tg}; }
__device__ __forceinline__ void stsm_tag(uint32_t addr, uint32_t r0, uint32_t r1, uint32_t r2, uint32_t r3, const Tag& k, int jp) {
  if (jp == 0) stsm_x4(addr, (r0 & ~k.me) | (k.tg & k.me), (r1 & ~k.mo) | (k.tg & k.mo), r2, r3);
  else stsm_x4(addr, r0, r1, r2, r3);
}
#define TILE_BAD() ((lds_vol(va) ^ tg) & 1)
#define TILE_VA() (slot + (wrow0 + (lane & 15)) * 128 + (lane & 7) * 16 + ((lane >> 3) & 1) * 4)
__device__ __forceinline__ void tile_check(uint32_t slot, const bf16* src, int wrow0, int lane, uint32_t tg) {
  const uint32_t va = TILE_VA();
  if (__builtin_expect(__any_sync(0xffffffffu, TILE_BAD()), 0)) {
    const int r0 = lane >> 3, ch = lane & 7;
    uint32_t n = 0;
#pragma unroll 1
    do {
      uint4 v[4];
#pragma unroll
      for (int i = 0; i < 4; ++i) v[i] = ld_relaxed4(reinterpret_cast<const uint4*>(src + (size_t)(wrow0 + r0 + 4 * i) * D_ + ch * 8));
#pragma unroll
      for (int i = 0; i < 4; ++i) sts128(slot + (wrow0 + r0 + 4 * i) * 128 + (((ch ^ (4 * i + r0)) & 7) << 4), v[i]);
      __syncwarp();
      if (++n > (1u << 16)) { g_err = 8u; break; }
    } while (__any_sync(0xffffffffu, TILE_BAD()));
    fence_async_smem();
    __syncwarp();
  }
}

template <int O>
__device__ __forceinline__ void phi_proj(float (&p)[2][4][4], const uint32_t (&kq)[64], uint32_t wa) {
#pragma unroll
  for (int h = 0; h < 2; ++h)
#pragma unroll
    for (int i = 0; i < 4; ++i) { p[h][i][0] = p[h][i][1] = p[h][i][2] = p[h][i][3] = 0.f; }
#pragma unroll
  for (int ks = 0; ks < 2; ++ks)
#pragma unroll
    for (int np = 0; np < 2; ++np)
#pragma unroll
      for (int h = 0; h < 2; ++h) {
        uint32_t b0, b1, b2, b3;
        ldsm_x4_t(b0, b1, b2, b3, wa + h * 2560 + ks * 1280 + np * 32);
        mma_bf16(p[h][2 * np], kq[O + 8 * h + 4 * ks], kq[O + 8 * h + 4 * ks + 1], kq[O + 8 * h + 4 * ks + 2], kq[O + 8 * h + 4 * ks + 3], b0, b1);
        mma_bf16(p[h][2 * np + 1], kq[O + 8 * h + 4 * ks], kq[O + 8 * h + 4 * ks + 1], kq[O + 8 * h + 4 * ks + 2], kq[O + 8 * h + 4 * ks + 3], b2, b3);
      }
}
__device__ __forceinline__ void phi_exp(uint32_t (&raw)[4][4], const float (&p)[4][4], float sc0, float sc1) {
#pragma unroll
  for (int i = 0; i < 4; ++i) {
    const float e0 = ex2(p[i][0] * sc0), e1 = ex2(p[i][1] * sc0), e2 = ex2(p[i][2] * sc1), e3 = ex2(p[i][3] * sc1);
    const float m0 = e0 * e1, m1 = e2 * e3, rr = rcp(m0 * m1), r0 = rr * m1, r1 = rr * m0;
    raw[i >> 1][(i & 1) * 2] = pack_bf16(e0, e1);
    raw[i >> 1][(i & 1) * 2 + 1] = pack_bf16(e2, e3);
    raw[2 + (i >> 1)][(i & 1) * 2] = pack_bf16(e1 * r0, e0 * r0);
    raw[2 + (i >> 1)][(i & 1) * 2 + 1] = pack_bf16(e3 * r1, e2 * r1);
  }
}
#define FENCE_P(h) _Pragma("unroll") for (int i_ = 0; i_ < 16; ++i_) asm volatile("" : "+f"(p[h][i_ >> 2][i_ & 3]) :: "memory")
#define FENCE_RAW(h) _Pragma("unroll") for (int i_ = 0; i_ < 16; ++i_) asm volatile("" : "+r"(raw[h][i_ >> 2][i_ & 3]) :: "memory")
template <int O>
__device__ __forceinline__ void phi_norm(uint32_t (&ph)[2][4][4], const uint32_t (&raw)[2][4][4], const uint32_t (&kq)[64], uint32_t wa,
                                         float sc0, float sc1, float mul0, float mul1) {
  bool bad = false;
#pragma unroll
  for (int h = 0; h < 2; ++h)
#pragma unroll
    for (int sg = 0; sg < 2; ++sg) {
      float ss[4] = {0.f, 0.f, 0.f, 0.f};
#pragma unroll
      for (int ks = 0; ks < 2; ++ks)
        mma_bf16(ss, raw[h][2 * sg + ks][0], raw[h][2 * sg + ks][1], raw[h][2 * sg + ks][2], raw[h][2 * sg + ks][3], 0x3F803F80u, 0x3F803F80u);
      bad = bad || !(ss[0] < PHI_MAX) || !(ss[2] < PHI_MAX);
      const uint32_t iv = pack_bf16(rcp(ss[0]) * mul0, rcp(ss[2]) * mul1);
#pragma unroll
      for (int ks = 0; ks < 2; ++ks)
#pragma unroll
        for (int j = 0; j < 4; ++j) ph[h][2 * sg + ks][j] = mul_bf16x2(raw[h][2 * sg + ks][j], iv, j & 1);
    }
  if (__builtin_expect(__any_sync(0xffffffffu, bad), 0)) {
#pragma unroll 1
    for (int it = 0; it < 4; ++it) {
      float q[4][4];
#pragma unroll
      for (int i = 0; i < 4; ++i) { q[i][0] = q[i][1] = q[i][2] = q[i][3] = 0.f; }
#pragma unroll
      for (int ks = 0; ks < 2; ++ks) {
        uint32_t a[4];
#pragma unroll
        for (int j = 0; j < 4; ++j) a[j] = (it & 2) ? kq[O + 8 + 4 * ks + j] : kq[O + 4 * ks + j];
#pragma unroll
        for (int np = 0; np < 2; ++np) {
          uint32_t b0, b1, b2, b3;
          ldsm_x4_t(b0, b1, b2, b3, wa + (it >> 1) * 2560 + ks * 1280 + np * 32);
          mma_bf16(q[2 * np], a[0], a[1], a[2], a[3], b0, b1);
          mma_bf16(q[2 * np + 1], a[0], a[1], a[2], a[3], b2, b3);
        }
      }
      float iv[2];
#pragma unroll
      for (int r = 0; r < 2; ++r) {
        const float sc = (it & 1) ? -(r ? sc1 : sc0) : (r ? sc1 : sc0);
        float mx = -INFINITY, sm = 0.f;
#pragma unroll
        for (int i = 0; i < 8; ++i) { float& v = q[i >> 1][2 * r + (i & 1)]; v *= sc; mx = fmaxf(mx, v); }
        mx = fmaxf(mx, __shfl_xor_sync(0xffffffffu, mx, 1));
        mx = fmaxf(mx, __shfl_xor_sync(0xffffffffu, mx, 2));
#pragma unroll
        for (int i = 0; i < 8; ++i) { float& v = q[i >> 1][2 * r + (i & 1)]; v = ex2(v - mx); sm += v; }
        sm += __shfl_xor_sync(0xffffffffu, sm, 1);
        sm += __shfl_xor_sync(0xffffffffu, sm, 2);
        iv[r] = rcp(sm) * (r ? mul1 : mul0);
      }
#pragma unroll
      for (int i = 0; i < 24; ++i) ph[i >> 4][(i >> 2) & 3][i & 3] = ph[(i + 8) >> 4][((i + 8) >> 2) & 3][i & 3];
#pragma unroll
      for (int i = 0; i < 4; ++i) {
        ph[1][2 + (i >> 1)][(i & 1) * 2] = pack_bf16(q[i][0] * iv[0], q[i][1] * iv[0]);
        ph[1][2 + (i >> 1)][(i & 1) * 2 + 1] = pack_bf16(q[i][2] * iv[1], q[i][3] * iv[1]);
      }
    }
  }
}

__device__ __forceinline__ void stats_out(float s0, float s1, float q0, float q1, float2* dst, int t) {
  const bool od = t & 1;
  float sa = od ? s1 : s0, qa = od ? q1 : q0;
  sa += __shfl_xor_sync(0xffffffffu, od ? s0 : s1, 1);
  qa += __shfl_xor_sync(0xffffffffu, od ? q0 : q1, 1);
  sa += __shfl_xor_sync(0xffffffffu, sa, 2);
  qa += __shfl_xor_sync(0xffffffffu, qa, 2);
  if (t < 2) red_add2(&dst[t * 8].x, sa, qa);
}

__device__ __forceinline__ void consumer(const Ctx& c) {
  const int g = c.g, m0 = c.rb * 128;
  float acc[192];
#define X_HALF(hf, TG) \
      _Pragma("unroll") for (int jp = 4 * (hf); jp < 4 * (hf) + 4; ++jp) \
        stsm_tag(sb + (XS + (hf)) * SLOT + rowo + (X ^ ((jp & 3) << 5)), \
                 pack_bf16(acc[128 + 8 * jp], acc[129 + 8 * jp]), pack_bf16(acc[130 + 8 * jp], acc[131 + 8 * jp]), \
                 pack_bf16(acc[132 + 8 * jp], acc[133 + 8 * jp]), pack_bf16(acc[134 + 8 * jp], acc[135 + 8 * jp]), TG, jp & 3);
#pragma unroll
  for (int i = 128; i < 192; ++i) acc[i] = 0.f;
#pragma unroll 1
  for (int layer = 0;; ++layer) {
    {
      PHASE_CTX();
      const uint32_t wu = c.cu >> 2;
      const uint32_t dA0 = (((sb + wu * 8192) & 0x3FFFF) >> 4) | (1u << 16), dB0 = ((sb & 0x3FFFF) >> 4) | (512u << 16);
      {
        PROFX(0);
        mbar_wait(bar + B_FULLS, 0);
        PROFX(1);
        wgmma_fence();
        wgmma_n256_0(acc, D128(dA0 + XS * 1024), D128(dB0 + 2048));
#pragma unroll
        for (int k = 1; k < 4; ++k) wgmma_n256(acc, D128(dA0 + XS * 1024 + k * 2), D128(dB0 + 2048 + k * 128), 1);
        wgmma_commit();
        wgmma_wait<1>();
        float s0 = 0.f, s1 = 0.f, q0 = 0.f, q1 = 0.f;
        if (layer) {
          X_HALF(1, (Tag{0u, 0u, 0u}));
#pragma unroll
          for (int i = 128; i < 192; i += 4) {
            s0 += acc[i] + acc[i + 1]; s1 += acc[i + 2] + acc[i + 3];
            q0 = fmaf(acc[i], acc[i], fmaf(acc[i + 1], acc[i + 1], q0)); q1 = fmaf(acc[i + 2], acc[i + 2], fmaf(acc[i + 3], acc[i + 3], q1));
          }
        }
        asm volatile("" : "+f"(s0), "+f"(s1), "+f"(q0), "+f"(q1) :: "memory");
        wgmma_fence();
        wgmma_n128_0(acc, D128(dA0 + XS * 1024), D128(dB0 + 1024));
#pragma unroll
        for (int k = 1; k < 4; ++k) wgmma_n128(acc, D128(dA0 + XS * 1024 + k * 2), D128(dB0 + 1024 + k * 128), 1);
        wgmma_commit();
        if (layer) {
          PHASE_CTX();
          fence_async_smem();
          nbar_dyn(3 + wu, 128);
          stats_out(s0, s1, q0, q1, g_stats + layer * S_ + m0 + wrow0 + gq, t);
          PROFT(tid_ == 128, layer * 16 + 8);
        }
      }
      uint32_t s = 1, u = 0, sp = 0;
      const int ix = layer ? 99 : 2 * min(g, NCOM) + 1;
#pragma unroll 1
      for (int i = 1; i < 14; ++i) {
        mbar_wait(bar + B_FULLS + s * 8, (u + (s ? layer : 0)) & 1);
        if ((UNS & 1) && layer && (unsigned)(i - 2) < 7u) {
          PHASE_CTX();
          tile_check(sb + ((QA >> (4 * s)) & 15) * SLOT, g_x + (size_t)m0 * D_ + ((2 * g + 2 * i - 2) & 15) * 64, wrow0, lane, lds_vol(sb + SM_EPOCH) + layer);
        }
        const uint32_t da = dA0 + ((QA >> (4 * s)) & 15) * 1024, dk = dB0 + ((QK >> (4 * s)) & 15) * 1024,
                       dq = dB0 + ((QQ >> (4 * s)) & 15) * 1024;
        wgmma_fence();
#pragma unroll
        for (int k = 0; k < 4; ++k) {
          wgmma_n256(acc, D128(da + k * 2), D128(dk + k * 128), 1);
          wgmma_n128(acc, D128(da + k * 2), D128(dq + k * 128), 1);
          if (k == ER - 1) {
            wgmma_commit();
            wgmma_wait<1>();
            if (elected && (unsigned)(i - ix) >= 2u) release2(bar + B_EMPTYS + sp * 8);
          }
        }
        wgmma_commit();
        if ((unsigned)(i - ix) < 2u) {
          PHASE_CTX();
          {
            float s0 = 0.f, s1 = 0.f, q0 = 0.f, q1 = 0.f;
            const uint32_t xa = sb + ((QA >> (4 * sp)) & 15) * SLOT + rowo;
#pragma unroll
            for (int jp = 0; jp < 4; ++jp) {
              uint32_t x0, x1, x2, x3;
              ldsm_x4(x0, x1, x2, x3, xa + (X ^ (jp << 5)));
              s0 += (bf_lo(x0) + bf_hi(x0)) + (bf_lo(x2) + bf_hi(x2));
              s1 += (bf_lo(x1) + bf_hi(x1)) + (bf_lo(x3) + bf_hi(x3));
              q0 = fmaf(bf_lo(x0), bf_lo(x0), fmaf(bf_hi(x0), bf_hi(x0), fmaf(bf_lo(x2), bf_lo(x2), fmaf(bf_hi(x2), bf_hi(x2), q0))));
              q1 = fmaf(bf_lo(x1), bf_lo(x1), fmaf(bf_hi(x1), bf_hi(x1), fmaf(bf_lo(x3), bf_lo(x3), fmaf(bf_hi(x3), bf_hi(x3), q1))));
            }
            stats_out(s0, s1, q0, q1, g_stats + m0 + wrow0 + gq, t);
          }
          __syncwarp();
          if (lane == 0 && i != ix) mbar_arrive(bar + B_XDONE);
          nbar_dyn(3 + wu, 128);
          if (ER && elected) release2(bar + B_EMPTYS + sp * 8);
        }
        if (!ER) {
          wgmma_wait<1>();
          if (elected) release2(bar + B_EMPTYS + sp * 8);
        }
        if (i == 1 && layer) {
          PHASE_CTX();
          slab_out_half(sb + (XS + 1) * SLOT, g_x + (size_t)m0 * D_ + g * 128 + 64, wrow0, lane);
          __syncwarp();
          if (lane == 0) mbar_arrive(bar + B_XDONE);
          nbar_dyn(3 + wu, 128);
        }
        sp = s;
        if (++s == 3) { s = 0; ++u; }
      }
      {
        const uint64_t dap = make_desc_ns(sb + SM_AP + wu * 1024, 0, 128), dbp = make_desc_ns(sb + SM_BP + (layer & 1) * 6144, 0, 128);
        if (wu == 0) {
          wgmma_wait<0>();
          if (elected) mbar_arrive(bar + B_R0);
          nbar<6, 256>();
        }
        if (layer < 2) mbar_wait(bar + (layer ? B_CS2 : B_CS), 0);
        mbar_wait(bar + B_STAT, layer & 1);
        mbar_wait(bar + B_FULLS + 16, layer & 1);
        wgmma_fence();
        wgmma_n256_k(acc, dap, dbp, 1);
#pragma unroll
        for (int k = 0; k < 4; ++k) wgmma_n256(acc, D128(dA0 + (QA >> 8) * 1024 + k * 2), D128(dB0 + (QK >> 8) * 1024 + k * 128), 1);
        mbar_wait(bar + B_FULLS, 1);
        PROFT(tid_ == 128, layer * 16 + 9);
        wgmma_fence();
#pragma unroll
        for (int k = 0; k < 4; ++k) wgmma_n256(acc, D128(dA0 + (QA & 15) * 1024 + k * 2), D128(dB0 + (QK & 15) * 1024 + k * 128), 1);
        wgmma_commit();
        if (wu) nbar<6, 256>();
#define Q_TAIL() \
        wgmma_n128_k(acc, dap, dbp + 256, 1); \
        _Pragma("unroll") for (int k = 0; k < 4; ++k) wgmma_n128(acc, D128(dA0 + (QA >> 8) * 1024 + k * 2), D128(dB0 + (QQ >> 8) * 1024 + k * 128), 1); \
        _Pragma("unroll") for (int k = 0; k < 4; ++k) wgmma_n128(acc, D128(dA0 + (QA & 15) * 1024 + k * 2), D128(dB0 + (QQ & 15) * 1024 + k * 128), 1);
        Q_TAIL();
        wgmma_commit();
        wgmma_wait<1>();
#pragma unroll
        for (int i = 0; i < 128; ++i) asm volatile("" : "+f"(acc[i]) :: "memory");
      }
    }
    uint32_t xo[32];
    uint32_t oq[8][4];
    {
      PHASE_CTX();
      PROFT(tid_ == 128, layer * 16 + 1);
      const bool isB = layer & 1;
      const int cu = c.cu;
      if (cu >= 4) asm volatile("bar.arrive 7, 256;" ::: "memory");
      if (elected && cu == 4) mbar_arrive(bar + B_R0);
      uint32_t kq[64];
      const uint32_t rowq = rowo & 8191;
      const float rs0 = lds_f(sb + SM_RS + (16 + wrow0 + gq) * 4), rs1 = lds_f(sb + SM_RS + (24 + wrow0 + gq) * 4);
#define Q_DONE() \
      wgmma_wait<0>(); \
      if (lane == 0) release2(bar + B_E0); \
      _Pragma("unroll") for (int i = 128; i < 192; ++i) asm volatile("" : "+f"(acc[i]) :: "memory"); \
      _Pragma("unroll") for (int i = 0; i < 32; ++i) kq[32 + i] = pack_bf16(acc[128 + 2 * i], acc[129 + 2 * i]);
      if (isB) {
        if (cu == 0) asm volatile("bar.arrive 10, 64;" ::: "memory");
        if (elected) release2(bar + B_E1);
        const int e = gq & 1;
        const bool sel = t > (gq >> 1);
        const uint32_t rja = sb + SM_RS + (wrow0 + 2 * t + e) * 4;
        const float rjA0 = lds_f(rja + 32), rjA1 = lds_f(rja + 64), rjB0 = lds_f(rja + (sel ? 0 : 64)), rjB1 = lds_f(rja + (sel ? 32 : 96));
        uint32_t vv[32];
#pragma unroll
        for (int i = 0; i < 16; ++i) { kq[i] = pack_bf16(acc[2 * i], acc[2 * i + 1]); vv[i] = pack_bf16(acc[64 + 2 * i], acc[65 + 2 * i]); }
        const uint32_t rB = sb + 4 * SLOT + wg * 4 * KVT + rowq;
        auto dump = [&](int hp) {
          const uint32_t kb = rB + 2048 + (hp ^ wg) * 2 * KVT;
#pragma unroll
          for (int jp = 0; jp < 4; ++jp) {
            stsm_x4(kb + (X ^ (jp << 5)), kq[16 * hp + 4 * jp], kq[16 * hp + 4 * jp + 1], kq[16 * hp + 4 * jp + 2], kq[16 * hp + 4 * jp + 3]);
            stsm_x4(kb + KVT + (X ^ (jp << 5)), vv[16 * hp + 4 * jp], vv[16 * hp + 4 * jp + 1], vv[16 * hp + 4 * jp + 2], vv[16 * hp + 4 * jp + 3]);
          }
          if (cu == 3) {
            const uint32_t kd = rB + 2048 + 32768 + (1 - hp) * 2 * KVT;
#pragma unroll
            for (int jp = 0; jp < 4; ++jp) {
              stsm_x4(kd + (X ^ (jp << 5)), kq[16 * hp + 4 * jp], kq[16 * hp + 4 * jp + 1], kq[16 * hp + 4 * jp + 2], kq[16 * hp + 4 * jp + 3]);
              stsm_x4(kd + KVT + (X ^ (jp << 5)), vv[16 * hp + 4 * jp], vv[16 * hp + 4 * jp + 1], vv[16 * hp + 4 * jp + 2], vv[16 * hp + 4 * jp + 3]);
            }
            if (hp) asm volatile("bar.arrive 15, 64;" ::: "memory"); else asm volatile("bar.arrive 9, 64;" ::: "memory");
          }
          asm volatile("bar.arrive %0, 224;" :: "r"(hp ? 13 + (cu >> 2) : 8 + (cu & 4)) : "memory");
        };
        uint4* const hbuf = g_halo + ((c.rb * 8 + g) * 2 + (layer >> 1)) * 512 + lane;
        if (cu < 4) {
          nbar<7, 256>();
          dump(0);
        }
#pragma unroll
        for (int i = 16; i < 32; ++i) { kq[i] = pack_bf16(acc[2 * i], acc[2 * i + 1]); vv[i] = pack_bf16(acc[64 + 2 * i], acc[65 + 2 * i]); }
        if (cu >= 4) {
          if (cu == 7) {
#pragma unroll
            for (int jp = 0; jp < 8; ++jp) {
              st_relaxed4(hbuf + jp * 32, ~kq[4 * jp], ~kq[4 * jp + 1], ~kq[4 * jp + 2], ~kq[4 * jp + 3]);
              st_relaxed4(hbuf + 256 + jp * 32, ~vv[4 * jp], ~vv[4 * jp + 1], ~vv[4 * jp + 2], ~vv[4 * jp + 3]);
            }
          }
          dump(0);
          dump(1);
        }
        PROFT(tid_ == 128, layer * 16 + 2);
        constexpr float SC = 0.17677669529663687f * L2E;
        const float fA0 = rjA0 * rs0 * SC, fB0 = rjB0 * rs0 * SC, fA1 = rjA1 * rs1 * SC, fB1 = rjB1 * rs1 * SC;
        const float bA0 = (m0 + wrow0) ? 0.f : -1e30f, bB = sel ? bA0 : 0.f;
        const uint32_t pA_ = e ? 0x1044u : 0x4410u, pB_ = e ? 0x3244u : 0x4432u, pLo = sel ? pB_ : 0x4444u, pHi = sel ? 0x4444u : pB_;
        const uint32_t KX = ((lane >> 3) ^ (lane & 7)) << 4;
        Q_DONE();
        if (cu == 0) {
          nbar<11, 64>();
        } else if (cu == 4) {
          uint4 hv[16];
          if (c.rb > 0) {
            uint32_t n = 0;
#pragma unroll 1
            while (true) {
              uint32_t mn = 0xFFFFFFFFu;
#pragma unroll
              for (int i = 0; i < 16; ++i) hv[i] = ld_relaxed4(hbuf - 16 * 512 + i * 32);
#pragma unroll
              for (int i = 0; i < 16; ++i) mn = __vimin3_u32(__vimin3_u32(mn, hv[i].x, hv[i].y), hv[i].z, hv[i].w);
              if (__all_sync(0xffffffffu, mn != 0u)) break;
              if (++n > (1u << 20)) { g_err = 4u; break; }
            }
          } else {
#pragma unroll
            for (int i = 0; i < 16; ++i) hv[i] = make_uint4(~0u, ~0u, ~0u, ~0u);
          }
          nbar<10, 64>();
#pragma unroll
          for (int i = 0; i < 16; ++i)
            stsm_x4(rB - 4 * KVT + (((i >> 2) & 1) * 2 + (i >> 3)) * KVT + (X ^ ((i & 3) << 5)), ~hv[i].x, ~hv[i].y, ~hv[i].z, ~hv[i].w);
          asm volatile("bar.arrive 11, 64;" ::: "memory");
          nbar<9, 64>();
        } else {
          nbar_dyn(8 + (cu & 4), 224);
        }
        PROFT(tid_ == 128, layer * 16 + 5);
        PROFT(lane == 0 && layer == PL, 136 + cw);
        auto attend = [&](int hp) {
          const uint32_t qad = sb + (XS + 1 - hp) * SLOT + rowo, kt = rB + 2 * (hp ^ wg) * KVT - (lane & 8) * 128, vt = rB + (2 * (hp ^ wg) + 1) * KVT;
          __syncwarp();
          uint32_t kb[2][2][4], vb[2][2][2][4];
#pragma unroll
          for (int h = 0; h < 2; ++h)
#pragma unroll
            for (int nt = 0; nt < 2; ++nt) ldsm_x4(kb[h][nt][0], kb[h][nt][1], kb[h][nt][2], kb[h][nt][3], kt + nt * 1024 + (KX ^ (h << 6)));
#pragma unroll
          for (int ks = 0; ks < 2; ++ks)
#pragma unroll
            for (int np = 0; np < 2; ++np)
#pragma unroll
              for (int h = 0; h < 2; ++h)
                ldsm_x4_t(vb[h][ks][np][0], vb[h][ks][np][1], vb[h][ks][np][2], vb[h][ks][np][3], vt + ks * 2048 + (X ^ (h << 6) ^ (np << 5)));
          if (hp == 0 && lane == 0) release2(bar + B_E3);
          if (DB1 == 1 && hp == 0 && cu < 4) dump(1);
          float la[2][2], lb[2][2], mx[2][2], sm[2][2];
#pragma unroll
          for (int h = 0; h < 2; ++h) {
            const int qo = 32 + 16 * hp + 8 * h, ko = 16 * hp + 8 * h;
            float sc[4][4];
#pragma unroll
            for (int nt = 0; nt < 4; ++nt) {
              sc[nt][0] = sc[nt][1] = sc[nt][2] = sc[nt][3] = 0.f;
#pragma unroll
              for (int ks = 0; ks < 2; ++ks)
                mma_bf16(sc[nt], kq[qo + 4 * ks], kq[qo + 4 * ks + 1], kq[qo + 4 * ks + 2], kq[qo + 4 * ks + 3],
                         nt < 2 ? kb[h][nt & 1][2 * ks] : kq[ko + 4 * ks + (nt & 1)], nt < 2 ? kb[h][nt & 1][2 * ks + 1] : kq[ko + 4 * ks + 2 + (nt & 1)]);
            }
            la[h][0] = fmaf(e ? sc[1][1] : sc[1][0], fA0, bA0);
            lb[h][0] = fmaf(sel ? (e ? sc[0][1] : sc[0][0]) : (e ? sc[2][1] : sc[2][0]), fB0, bB);
            la[h][1] = (e ? sc[2][3] : sc[2][2]) * fA1;
            lb[h][1] = fmaf(sel ? (e ? sc[1][3] : sc[1][2]) : (e ? sc[3][3] : sc[3][2]), fB1, bB);
            mx[h][0] = fmaxf(la[h][0], lb[h][0]); mx[h][1] = fmaxf(la[h][1], lb[h][1]);
          }
#pragma unroll
          for (int o = 1; o <= 2; o <<= 1)
#pragma unroll
            for (int h = 0; h < 2; ++h)
#pragma unroll
              for (int r = 0; r < 2; ++r) mx[h][r] = fmaxf(mx[h][r], __shfl_xor_sync(0xffffffffu, mx[h][r], o));
          float oa[2][4][4];
#pragma unroll
          for (int h = 0; h < 2; ++h) {
#pragma unroll
            for (int r = 0; r < 2; ++r) { la[h][r] = ex2(la[h][r] - mx[h][r]); lb[h][r] = ex2(lb[h][r] - mx[h][r]); sm[h][r] = la[h][r] + lb[h][r]; }
            const uint32_t p0 = pack_bf16(la[h][0] * rjA0, lb[h][0] * rjB0), p1 = pack_bf16(la[h][1] * rjA1, lb[h][1] * rjB1);
            const uint32_t a00 = __byte_perm(p0, 0u, pLo), a02 = __byte_perm(p0, 0u, pA_), a03 = __byte_perm(p1, 0u, pLo);
            const uint32_t a10 = __byte_perm(p0, 0u, pHi), a11 = __byte_perm(p1, 0u, pA_), a13 = __byte_perm(p1, 0u, pHi);
#pragma unroll
            for (int i = 0; i < 4; ++i) {
              oa[h][i][0] = oa[h][i][1] = oa[h][i][2] = oa[h][i][3] = 0.f;
              mma_bf16(oa[h][i], a00, 0u, a02, a03, vb[h][0][i >> 1][2 * (i & 1)], vb[h][0][i >> 1][2 * (i & 1) + 1]);
              mma_bf16(oa[h][i], a10, a11, 0u, a13, vb[h][1][i >> 1][2 * (i & 1)], vb[h][1][i >> 1][2 * (i & 1) + 1]);
            }
          }
#pragma unroll
          for (int o = 1; o <= 2; o <<= 1)
#pragma unroll
            for (int h = 0; h < 2; ++h)
#pragma unroll
              for (int r = 0; r < 2; ++r) sm[h][r] += __shfl_xor_sync(0xffffffffu, sm[h][r], o);
          mbar_wait(bar + (hp ? B_XOLD2 : B_XOLD), 1);
#pragma unroll
          for (int jp = 0; jp < 4; ++jp) ldsm_x4(xo[16 * hp + 4 * jp], xo[16 * hp + 4 * jp + 1], xo[16 * hp + 4 * jp + 2], xo[16 * hp + 4 * jp + 3], qad + (X ^ (jp << 5)));
#pragma unroll
          for (int h = 0; h < 2; ++h) {
            const float i0 = rcp(sm[h][0]), i1 = rcp(sm[h][1]);
#pragma unroll
            for (int np = 0; np < 2; ++np)
            {
              uint32_t (&o)[4] = oq[4 * hp + 2 * h + np];
              o[0] = pack_bf16(oa[h][2 * np][0] * i0, oa[h][2 * np][1] * i0); o[1] = pack_bf16(oa[h][2 * np][2] * i1, oa[h][2 * np][3] * i1);
              o[2] = pack_bf16(oa[h][2 * np + 1][0] * i0, oa[h][2 * np + 1][1] * i0); o[3] = pack_bf16(oa[h][2 * np + 1][2] * i1, oa[h][2 * np + 1][3] * i1);
              stsm_tag(qad + (X ^ (h << 6) ^ (np << 5)), o[0], o[1], o[2], o[3], make_tag(gq, t, 0u), 2 * h + np);
            }
          }
          __syncwarp();
          slab_out_half(sb + (XS + 1 - hp) * SLOT, g_o + (size_t)m0 * D_ + g * 128 + hp * 64, wrow0, lane);
          __syncwarp();
          if (lane == 0) mbar_arrive(bar + (hp ? B_ODONE : B_OH1));
          PROFT(lane == 0 && layer == PL && hp == 0, 128 + cw);
        };
        attend(0);
        if (DB1 == 2 && cu < 4) dump(1);
        if (cu == 4) nbar<15, 64>();
        else if (cu != 0) nbar_dyn(13 + (cu >> 2), 224);
        attend(1);
      } else {
#pragma unroll
        for (int i = 0; i < 32; ++i) kq[i] = pack_bf16(acc[2 * i], acc[2 * i + 1]);
        if (cu < 4) nbar<7, 256>();
        {
          const uint32_t vb = sb + (5 + 3 * wg) * SLOT + (rowq >> 1) + ((lchk ^ ((lane & 7) >> 1)) << 4);
#pragma unroll
          for (int jp = 8; jp < 16; ++jp)
            stsm_x4((vb ^ ((jp & 1) << 5)) + ((jp >> 1) & 3) * 4096,
                    pack_bf16(acc[8 * jp], acc[8 * jp + 1]), pack_bf16(acc[8 * jp + 2], acc[8 * jp + 3]),
                    pack_bf16(acc[8 * jp + 4], acc[8 * jp + 5]), pack_bf16(acc[8 * jp + 6], acc[8 * jp + 7]));
        }
        PROFT(tid_ == 128, layer * 16 + 2);
        Q_DONE();
        const uint32_t pA = sb + (3 + 3 * wg) * SLOT + (rowo & 8191);
        float sc0 = rs0 * L2E, sc1 = rs1 * L2E;
        const uint32_t wa0 = sb + SM_WPHI + lrow * 80 + lchk * 16;
        const uint32_t wu = c.cu >> 2, par = (layer >> 1) & 1;
        float p[2][4][4];
        uint32_t raw[2][4][4], ph[2][4][4];
        float kva[20], oa[2][20];
        auto kv_start = [&](int hp) {
#pragma unroll
          for (int h = 0; h < 2; ++h)
#pragma unroll
            for (int cp = 0; cp < 4; ++cp)
              stsm_x4(pA + hp * 16384 + h * 8192 + (X ^ (cp << 5)), ph[h][cp][0], ph[h][cp][1], ph[h][cp][2], ph[h][cp][3]);
          PROFT(tid_ == 128, layer * 16 + 11);
          fence_async_smem();
          nbar<1, 256>();
          const uint32_t hu = 2 * hp + wu;
          const uint32_t dP = (((sb + 3 * SLOT + hu * 8192) & 0x3FFFF) >> 4) | (512u << 16);
          const uint32_t dV = (((sb + 5 * SLOT + hu * 4096) & 0x3FFFF) >> 4) | (((SM_SD - 5 * SLOT - hu * 4096) >> 4) << 16);
          wgmma_fence();
#pragma unroll
          for (int ks = 0; ks < 8; ++ks)
            wgmma_n40_tt(kva, desc64(dP + (ks >> 2) * 3072 + (ks & 3) * 128, 0x40000040u),
                         desc64(dV + (ks >> 2) * (3072u - (2816u << 16)) + (ks & 3) * 64, 0x80000020u), ks != 0);
          wgmma_commit();
        };
        auto kv_end = [&](int hp) {
          wgmma_wait<0>();
#pragma unroll
          for (int i = 0; i < 20; ++i) asm volatile("" : "+f"(kva[i]) :: "memory");
          nbar_dyn(3 + wu, 128);
          PROFT(tid_ == 128, layer * 16 + 12);
          const bool od = lane & 1;
#pragma unroll
          for (int i = 0; i < 4; ++i)
            sts128(sb + (3 + hp) * SLOT + (cw * 128 + i * 32 + lane) * 16,
                   make_uint4(__float_as_uint(kva[4 * i]), __float_as_uint(kva[4 * i + 1]), __float_as_uint(kva[4 * i + 2]),
                              __float_as_uint(od == (i >= 2) ? 1.f : kva[4 * i + 3])));
          sts128(sb + (6 + hp) * SLOT + wg * 8192 + (wq * 32 + lane) * 16,
                 make_uint4(__float_as_uint(od ? kva[11] : kva[3]), __float_as_uint(od ? kva[15] : kva[7]), __float_as_uint(od ? kva[18] : kva[16]), __float_as_uint(1.f)));
          fence_async_smem();
          __syncwarp();
          if (lane == 0) mbar_arrive(bar + B_KVDONE - hp * 32);
          PROFT(tid_ == 128, layer * 16 + 3);
        };
        const uint4* const kvg = g_kv + (g * 2 + (layer >> 1)) * 2560 + cw * 128 + lane;
        uint4 u[5];
        auto kv_load = [&](int hp) {
#pragma unroll
          for (int i = 0; i < 4; ++i) u[i] = ld_relaxed4(kvg + hp * 1280 + i * 32);
          u[4] = ld_relaxed4(kvg + hp * 1280 + 1024 - cw * 96);
        };
        auto o_start = [&](int hp, const uint32_t (&pq)[2][4][4]) {
          PROFT(tid_ == 128 && hp == 0, layer * 16 + 10);
          if (hp == 0) mbar_wait(bar + B_KVDONE - 32, par);
          const bool od = lane & 1;
          uint32_t n = 0;
#pragma unroll 1
          while (!__all_sync(0xffffffffu, (od ? u[2].w : u[0].w) == 0x41800000u && (od ? u[3].w : u[1].w) == 0x41800000u && u[4].w == 0x41800000u)) {
#pragma unroll 1
            while (__any_sync(0xffffffffu, u[4].w < KVTH) && ++n < (1u << 20)) u[4].w = ld_relaxed(&kvg[hp * 1280 + 1024 - cw * 96].w);
            if (++n > (1u << 20)) { g_err = 6u; break; }
            kv_load(hp);
          }
          PROFT(tid_ == 128 && hp == 0, layer * 16 + 5);
          if (!od) { u[0].w = u[4].x; u[1].w = u[4].y; } else { u[2].w = u[4].x; u[3].w = u[4].y; }
#pragma unroll
          for (int i = 0; i < 4; i += 2)
            stsm_x4(sb + (5 + 3 * hp) * SLOT + rowo + (X ^ ((i & 2) << 4)),
                    pack_bf16(__uint_as_float(u[i].x), __uint_as_float(u[i].y)), pack_bf16(__uint_as_float(u[i].z), __uint_as_float(u[i].w)),
                    pack_bf16(__uint_as_float(u[i + 1].x), __uint_as_float(u[i + 1].y)), pack_bf16(__uint_as_float(u[i + 1].z), __uint_as_float(u[i + 1].w)));
          const uint32_t z2 = pack_bf16(__uint_as_float(u[4].z), __uint_as_float(u[4].z));
          if (t < 2) sts128(sb + (5 + 3 * hp) * SLOT + (wrow0 + gq + 8 * t) * 128 + ((4 ^ gq) << 4), make_uint4(z2, z2, z2, z2));
          fence_async_smem();
          nbar<1, 256>();
          PROFT(tid_ == 128 && hp == 1, layer * 16 + 4);
          const uint32_t dK = (((sb + (5 + 3 * hp) * SLOT) & 0x3FFFF) >> 4) | (512u << 16);
          wgmma_fence();
#pragma unroll
          for (int ks = 0; ks < 4; ++ks) {
#pragma unroll
            for (int hh = 0; hh < 2; ++hh) wgmma_n40_rs(oa[hh], pq[hh][ks], D128(dK + hh * 512 + ks * 128), ks != 0);
          }
          wgmma_commit();
        };
        auto o_end = [&](int hp) {
          wgmma_wait<0>();
#pragma unroll
          for (int i = 0; i < 20; ++i) asm volatile("" : "+f"(oa[0][i]), "+f"(oa[1][i]) :: "memory");
#pragma unroll
          for (int hh = 0; hh < 2; ++hh) {
            const float i0 = rcp(oa[hh][16] + 1e-6f), i1 = rcp(oa[hh][18] + 1e-6f);
            const uint32_t qad = sb + (3 + hp) * SLOT + rowo, hx = hh << 6;
#pragma unroll
            for (int np = 0; np < 2; ++np)
            {
              uint32_t (&o)[4] = oq[4 * hp + 2 * hh + np];
              o[0] = pack_bf16(oa[hh][8 * np] * i0, oa[hh][8 * np + 1] * i0); o[1] = pack_bf16(oa[hh][8 * np + 2] * i1, oa[hh][8 * np + 3] * i1);
              o[2] = pack_bf16(oa[hh][8 * np + 4] * i0, oa[hh][8 * np + 5] * i0); o[3] = pack_bf16(oa[hh][8 * np + 6] * i1, oa[hh][8 * np + 7] * i1);
              stsm_tag(qad + (X ^ hx ^ (np << 5)), o[0], o[1], o[2], o[3], make_tag(gq, t, 1u), 2 * hh + np);
            }
          }
          __syncwarp();
          slab_out_half(sb + (3 + hp) * SLOT, g_o + (size_t)m0 * D_ + g * 128 + hp * 64, wrow0, lane);
          __syncwarp();
          if (lane == 0) mbar_arrive(bar + (hp ? B_ODONE : B_OH1));
        };
#define XO_LOAD() \
        mbar_wait(bar + B_XOLD, 0); \
        mbar_wait(bar + B_XOLD2, 0); \
        _Pragma("unroll") for (int jp = 0; jp < 8; ++jp) \
          ldsm_x4(xo[4 * jp], xo[4 * jp + 1], xo[4 * jp + 2], xo[4 * jp + 3], sb + (XS + 1 - (jp >> 2)) * SLOT + rowo + (X ^ ((jp & 3) << 5)));
#define SC_RELOAD() \
        sc0 = __uint_as_float(lds_vol(sb + SM_RS + (16 + wrow0 + gq) * 4)) * L2E; sc1 = __uint_as_float(lds_vol(sb + SM_RS + (24 + wrow0 + gq) * 4)) * L2E;
        __syncwarp();
        phi_proj<0>(p, kq, wa0);
        phi_exp(raw[0], p[0], sc0, sc1);
        phi_exp(raw[1], p[1], sc0, sc1);
        phi_proj<16>(p, kq, wa0 + 5120);
        phi_norm<0>(ph, raw, kq, wa0, sc0, sc1, rs0, rs1);
        kv_start(0);
        phi_exp(raw[0], p[0], sc0, sc1);
        kv_end(0);
        if (RL & 1) { SC_RELOAD(); }
        XO_LOAD();
        phi_exp(raw[1], p[1], sc0, sc1);
        phi_proj<32>(p, kq, wa0);
        phi_norm<16>(ph, raw, kq, wa0 + 5120, sc0, sc1, rs0, rs1);
        kv_start(1);
        if (lane == 0) release2(bar + B_E3);
        phi_exp(raw[0], p[0], sc0, sc1);
        kv_end(1);
        if (RL & 2) { SC_RELOAD(); }
        kv_load(0);
        phi_exp(raw[1], p[1], sc0, sc1);
        phi_proj<48>(p, kq, wa0 + 5120);
        phi_norm<32>(ph, raw, kq, wa0, sc0, sc1, 1.f, 1.f);
        o_start(0, ph);
        phi_exp(raw[0], p[0], sc0, sc1);
        o_end(0);
        SC_RELOAD();
        kv_load(1);
        phi_exp(raw[1], p[1], sc0, sc1);
        phi_norm<48>(ph, raw, kq, wa0 + 5120, sc0, sc1, 1.f, 1.f);
        o_start(1, ph);
        o_end(1);
      }
      __syncwarp();
      PROFT(lane == 0 && layer == PL, 216 + cw);
      if (lane == 0) mbar_arrive(bar + B_EPI);
      PROFT(tid_ == 128, layer * 16 + 6);
    }
    {
      PHASE_CTX();
      const uint32_t wu = c.cu >> 2;
      const uint32_t dA0 = (((sb + wu * 8192) & 0x3FFFF) >> 4) | (1u << 16), dB0 = ((sb & 0x3FFFF) >> 4) | (512u << 16);
#pragma unroll
      for (int i = 0; i < 32; ++i) { acc[128 + 2 * i] = bf_lo(xo[i]); acc[129 + 2 * i] = bf_hi(xo[i]); }
      uint64_t ta = ((layer & 1) ? WO_A1 : WO_A0) >> 8, tw = (layer & 1) ? WO_B1 : WO_B0;
      mbar_wait(bar + B_FULLT, layer & 1);
      mbar_wait(bar + B_FULLT + 8, layer & 1);
      PROFT(tid_ == 128 && layer == PL, 160);
      wgmma_fence();
#pragma unroll
      for (int k = 0; k < 8; ++k) wgmma_n128_rs(acc, oq[k], D128(dB0 + ((uint32_t)(tw >> (k & 4)) & 15) * 1024 + (k & 3) * 128), 1);
      wgmma_commit();
      tw >>= 8;
      if (lane == 0) release2(bar + B_E2);
#pragma unroll 1
      for (int i = 2; i < 16; ++i) {
        mbar_wait(bar + B_FULLT + i * 8, layer & 1);
        PROFT(tid_ == 128 && layer == PL, 160 + i);
        tile_check(sb + ((uint32_t)ta & 15) * SLOT, g_o + (size_t)m0 * D_ + ((2 * g + (int)(WOORD >> (4 * i))) & 15) * 64, wrow0, lane, ~layer);
        const uint32_t da = dA0 + ((uint32_t)ta & 15) * 1024, db = dB0 + ((uint32_t)tw & 15) * 1024;
        ta >>= 4; tw >>= 4;
        if (WSK && i == 16 - WSK && wu) nbar<6, 256>();
        wgmma_fence();
#pragma unroll
        for (int k = 0; k < 4; ++k) wgmma_n128(acc, D128(da + k * 2), D128(db + k * 128), 1);
        wgmma_commit();
        if (WSK && i == 15 && !wu) asm volatile("bar.arrive 6, 256;" ::: "memory");
        wgmma_wait<1>();
        if (elected && i < 12) release2(bar + B_CONS + (i - 1) * 8);
        if (elected && (unsigned)(i - 13) < 2u && layer + 1 < NLAYERS) release2(bar + B_EMPTYS + (i - 13) * 8);
      }
      const bool last = layer == NLAYERS - 1;
      Tag xt = make_tag(gq, (last || !(UNS & 1)) ? 4 : t, lds_vol(sb + SM_EPOCH) + layer + 1);
      asm volatile("" : "+r"(xt.me), "+r"(xt.mo), "+r"(xt.tg) :: "memory");
      wgmma_wait<0>();
#pragma unroll
      for (int i = 128; i < 192; ++i) asm volatile("" : "+f"(acc[i]) :: "memory");
      if (elected && !last) release2(bar + B_EMPTYS + 16);
      PROFT(tid_ == 128, layer * 16 + 7);
      X_HALF(0, xt);
      if (last) {
        __syncwarp();
        slab_out_half(sb + XS * SLOT, c.out + (size_t)m0 * D_ + g * 128, wrow0, lane);
        X_HALF(1, (Tag{0u, 0u, 0u}));
        __syncwarp();
        slab_out_half(sb + (XS + 1) * SLOT, c.out + (size_t)m0 * D_ + g * 128 + 64, wrow0, lane);
        __syncwarp();
        if (lane == 0) mbar_arrive(bar + B_XDONE);
        PROFT(tid_ == 128, layer * 16 + 24);
        break;
      }
      __syncwarp();
      slab_out_half(sb + XS * SLOT, g_x + (size_t)m0 * D_ + g * 128, wrow0, lane, true);
      __syncwarp();
      if (lane == 0) mbar_arrive(bar + B_XH0);
      nbar_dyn(3 + wu, 128);
    }
  }
}

__device__ __forceinline__ void flag_fetch(uint32_t bar, uint32_t cp, const unsigned int* f) {
  asm volatile("{\n.reg .pred p;\nelect.sync _|p, 0xffffffff;\n@p mbarrier.expect_tx.relaxed.cta.shared::cta.b64 [%2], 64;\n"
               "@p cp.async.bulk.shared::cluster.global.mbarrier::complete_tx::bytes [%0], [%1], 64, [%2];\n}\n"
               ::"r"(cp), "l"(f), "r"(bar + 128) : "memory");
}
__device__ __forceinline__ void src_wait_async(uint32_t bar, uint32_t cp, const unsigned int* f, unsigned int target, int kb, uint32_t& ready, int lane) {
  uint32_t n = 0;
#pragma unroll 1
  while (true) {
    ready |= __ballot_sync(0xffffffffu, (int)(lds_vol(cp + (lane & 15) * 4) - target) >= 0);
    if ((ready >> kb) & 1) break;
    if (n > (1u << 20)) { g_err = 5u; break; }
    if ((n++ & PMOD) == 0) flag_fetch(bar, cp, f);
    __nanosleep(PSL);
  }
}

__device__ __forceinline__ int kblock0(int i, int g) {
  const int j = i >> 1, p = max(g, NCOM) + j - NCOM;
  return (j < NCOM ? j : p < 8 ? p : p - 8 + NCOM) * 2 + (i & 1);
}

__device__ __forceinline__ int wo_kblock(int m, int g) { return (2 * g + (int)((WOORD >> (4 * m)) & 15)) & 15; }

__global__ void __cluster_dims__(2, 1, 1) __launch_bounds__(384, 1)
mega_kernel(const __grid_constant__ CUtensorMap tm_x0, const __grid_constant__ CUtensorMap tm_x,
            const __grid_constant__ CUtensorMap tm_o,
            const __grid_constant__ CUtensorMap tm_wA, const __grid_constant__ CUtensorMap tm_wB,
            const __grid_constant__ CUtensorMap tm_woA, const __grid_constant__ CUtensorMap tm_woB,
                        const bf16* __restrict__ wB, const bf16* __restrict__ wphi, bf16* __restrict__ out) {
  extern __shared__ uint8_t smem_raw[];
  const uint32_t sb = (smem_u32(smem_raw) + 1023u) & ~1023u;
  const uint32_t bar = sb + SM_BAR;
  const int warp = __shfl_sync(0xffffffffu, threadIdx.x >> 5, 0), lane = threadIdx.x & 31;
  if (blockIdx.x >= 128) {
    const int xb = blockIdx.x - 128;
    const int ch = threadIdx.x % 96, rg = threadIdx.x / 96, gg = xb * 2 + ch / 48, sec = (ch % 48) >> 4;
    const uint4* src = reinterpret_cast<const uint4*>(wB + (size_t)rg * 3072 + (sec == 2 ? 0 : 1024 + sec * 1024) + gg * 128 + (ch & 15) * 8);
    float s[8] = {0.f, 0.f, 0.f, 0.f, 0.f, 0.f, 0.f, 0.f};
#pragma unroll 1
    for (int r0 = 0; r0 < 256; r0 += 32) {
      uint4 v[32];
#pragma unroll
      for (int r = 0; r < 32; ++r) v[r] = __ldg(src + (size_t)(r0 + r) * 1536);
#pragma unroll
      for (int r = 0; r < 32; ++r) {
        s[0] += bf_lo(v[r].x); s[1] += bf_hi(v[r].x); s[2] += bf_lo(v[r].y); s[3] += bf_hi(v[r].y);
        s[4] += bf_lo(v[r].z); s[5] += bf_hi(v[r].z); s[6] += bf_lo(v[r].w); s[7] += bf_hi(v[r].w);
      }
    }
    float* cd = g_cs + (ld_relaxed(&g_epoch) & 1) * 6144 + 3072 + xb * 768 + ch * 8;
    red_add4(cd, s[0], s[1], s[2], s[3]);
    red_add4(cd + 4, s[4], s[5], s[6], s[7]);
    nbar<1, 384>();
    if (threadIdx.x < 2) flag_add(&g_csflag[8 + xb * 2 + threadIdx.x].v);
    return;
  }
  const int bid = blockIdx.x;
  const int cr = bid & 1;
  const int g = (bid >> 1) & 7;
  const int rb = (bid >> 4) * 2 + cr;
  const int m0 = rb * 128;

  if (warp < 4) {
    asm volatile("setmaxnreg.dec.sync.aligned.u32 40;");
    asm volatile("barrier.cluster.arrive.relaxed.aligned;" ::: "memory");
    const unsigned int epoch = warp ? ld_relaxed(&g_epoch) : 0u;
    if (warp) cluster_wait();
    unsigned int xbase = epoch * NLAYERS;
    auto wo_a = [&](int layer, int m1) {
      uint64_t ts = ((layer & 1) ? WO_A1 : WO_A0) >> (4 * m1), td = ((layer & 1) ? WO_DA1 : WO_DA0) >> (4 * m1), tk = WOORD >> (4 * m1);
      uint32_t ready = 0u;
#pragma unroll 1
      for (int m = m1; m < 16; m += AW) {
        const int kb = (2 * g + (uint32_t)tk) & 15;
        uint32_t dst = sb + ((uint32_t)ts & 15) * SLOT, fb = bar + B_FULLT + m * 8, eb = bar + B_CONS + ((uint32_t)td & 15) * 8;
        int kc = kb * 64;
        ts >>= 4 * AW; td >>= 4 * AW; tk >>= 4 * AW;
        asm volatile("" : "+r"(dst), "+r"(fb), "+r"(eb), "+r"(kc));
        bool fr = false;
        if (!((ready >> kb) & 1)) {
          PROFT(m == 2 && lane == 0, 64 + layer * 16 + 2);
          if (EP && m > EP) src_wait_async(bar, bar + B_FLG, g_of + rb * 32, xbase + layer + 1, kb, ready, lane);
          else fr = src_wait_tma(g_of + rb * 32, xbase + layer + 1, 1u << kb, ready, lane, eb, layer & 1);
          fence_async_all();
        }
        if (m == 6) mbar_wait_u(bar + B_EPI, layer & 1);
        if (!fr) mbar_wait_u(eb, layer & 1);
        tma_2d_e(dst, &tm_o, kc, m0, fb);
        if (EP && m >= EP && (ready & 0xFFFFu) != 0xFFFFu) flag_fetch(bar, bar + B_FLG, g_of + rb * 32);
        PROFT(lane == 0 && layer == PL, 176 + m);
      }
    };
    auto wo_w = [&](int layer) {
      const CUtensorMap* tx = layer == 0 ? &tm_x0 : &tm_x;
      const CUtensorMap* two = (layer & 1) ? &tm_woB : &tm_woA;
      uint64_t ts = (layer & 1) ? WO_B1 : WO_B0, td = (layer & 1) ? WO_DB1 : WO_DB0, tk = WOORD;
      uint32_t pb = 0;
      fence_async_all();
      mbar_wait_u(bar + B_R0, layer & 1);
      expect_tx_e(bar + B_XOLD, 16384);
      tma_2d_e(sb + (XS + 1) * SLOT, tx, g * 128, m0, bar + B_XOLD);
#pragma unroll 1
      for (int m = 0; m < 16; ++m) {
        uint32_t dst = sb + ((uint32_t)ts & 15) * SLOT + cr * 8192, fb = bar + B_FULLT + m * 8, eb = bar + B_CONS + ((uint32_t)td & 15) * 8;
        int kc = ((2 * g + (uint32_t)tk) & 15) * 64;
        ts >>= 4; td >>= 4; tk >>= 4;
        asm volatile("" : "+r"(dst), "+r"(fb), "+r"(eb), "+r"(kc));
        if (eb < bar + B_E3 && pb >= bar + B_E3) mbar_wait_u(bar + B_E2, layer & 1);
        if (eb != pb) mbar_wait_u(eb, layer & 1);
        pb = eb;
        tma_2d_mc_e(dst, two, g * 128 + cr * 64, kc, fb);
        expect_tx_e(fb, m < 2 ? 16384 : 32768);
        PROFT(lane == 0 && layer == PL, 144 + m);
        if (m == ((layer & 1) ? XB2 : 0)) {
          expect_tx_e(bar + B_XOLD2, 16384);
          tma_2d_e(sb + XS * SLOT, tx, g * 128 + 64, m0, bar + B_XOLD2);
        }
      }
    };
    if (warp == 0) {
      cluster_wait();
      PROFT(lane == 0, 125);
#pragma unroll 1
      for (int layer = 0; layer < NLAYERS; ++layer) {
        const CUtensorMap* tx = layer == 0 ? &tm_x0 : &tm_x;
        const CUtensorMap* tw = (layer & 1) ? &tm_wB : &tm_wA;
        uint32_t s = layer == 0, u = 0, ready = layer == 0 ? 0xFFFFu : 0u;
#pragma unroll 1
        for (int i = s; i < 16; ++i) {
          const int kb = layer == 0 ? kblock0(i, g) : wo_kblock(i, g), kc = kb * 64;
          const uint32_t fb = bar + B_FULLS + s * 8;
          const uint32_t kd = sb + (((QK >> (4 * s)) & 15) + cr) * SLOT, qd = sb + ((QQ >> (4 * s)) & 15) * SLOT + cr * 8192;
          const uint32_t need = 1u << kb;
          const bool ext = i >= 2 || layer == 0, early = ext && (ready & need) == need;
          mbar_wait_u(bar + B_EMPTYS + s * 8, (u + (s ? layer : 0) + 1) & 1);
          if (early) tma_2d_e(sb + ((QA >> (4 * s)) & 15) * SLOT, tx, kc, m0, fb);
          tma_2d_mc_e(kd, tw, 1024 + cr * 1024 + g * 128, kc, fb);
          tma_2d_mc_e(kd + 8192, tw, 1024 + cr * 1024 + g * 128 + 64, kc, fb);
          tma_2d_mc_e(qd, tw, g * 128 + cr * 64, kc, fb);
          expect_tx_e(fb, ext ? 65536 : 49152);
          PROFT(lane == 0 && layer == 0 && i == 1, 31);
          if (layer == 0 && g >= NCOM && i == XPF + (((g - NCOM) * XPM) >> 2)) {
            if (i <= 2) mbar_wait_u(bar + B_FULLS, 0);
            tma_pf_e(&tm_x0, g * 128, m0);
            tma_pf_e(&tm_x0, g * 128 + 64, m0);
          }
          if (layer < 2 && i >= PFS) {
            const int j = i - PFS;
            if (j < 2) tma_pf_e(layer ? &tm_woB : &tm_woA, g * 128 + j * 64, rb * 64);
            else if (j < 8 && layer == 0) tma_pf_e(&tm_wB, ((j >> 1) - 1) * 1024 + g * 128 + (j & 1) * 64, rb * 64);
          }
          if (ext && !early) {
            PROFT(i == 2 && lane == 0, 64 + layer * 16 + 0);
            src_wait_tma(g_xf + rb * 32, xbase + layer + 1, need, ready, lane, fb, 0);
            PROFT(i == 2 && lane == 0, 64 + layer * 16 + 1);
            fence_async_all();
            tma_2d_e(sb + ((QA >> (4 * s)) & 15) * SLOT, tx, kc, m0, fb);
          }
          if (++s == 3) { s = 0; ++u; }
        }
        if (layer == 0) xbase = ld_relaxed(&g_epoch) * NLAYERS;
        if (PG & 1) mbar_wait_u(bar + B_OH1, layer & 1);
        if (PG & 4) mbar_wait_u(bar + B_E3, layer & 1);
        wo_a(layer, 2);
      }
    } else {
      if (warp >= 2) {
        const int h2 = threadIdx.x - 64;
        if (h2 < 16) sts_f(sb + SM_RS + h2 * 4, 0.f);
        if (h2 == 0) sts_f(sb + SM_EPOCH, __uint_as_float(epoch));
        if (h2 < 16) sts_f(bar + B_FLG + h2 * 4, __uint_as_float(xbase));
        mbar_wait_u(bar + (CST < 3 ? B_FULLS + CST * 8 : B_EMPTYS + (CST - 3) * 8), 0);
        colsum(&tm_wA, g_cs + (epoch & 1) * 6144, rb, g, warp - 2, 2, lane, warp == 2 ? sb + SM_SD : (sb + SM_BP + 1023u) & ~1023u, bar + B_CB + (warp - 2) * 8, 0);
#pragma unroll 1
        for (int i = h2; i < 320; i += 64) g_kv[(g * 16 + rb) * 320 + i] = make_uint4(0u, 0u, 0u, 0u);
        fence_async_all();
        nbar<5, 64>();
        if (h2 == 0) flag_add(&g_csflag[g].v);
        PROFT(h2 == 0, 242);
#pragma unroll 1
        for (int i = h2; i < 512; i += 256) {
          uint4 w[4];
#pragma unroll
          for (int j = 0; j < 4; ++j) w[j] = __ldg(reinterpret_cast<const uint4*>(wphi + (size_t)g * 4096) + i + j * 64);
#pragma unroll
          for (int j = 0; j < 4; ++j) sts128(sb + SM_WPHI + ((i >> 2) + j * 16) * 80 + (i & 3) * 16, w[j]);
        }
      }
      if (warp == 1) {
        if (lane >= 27) {
          const CUtensorMap* tm = lane == 27 ? &tm_o : lane == 28 ? &tm_wB : lane == 29 ? &tm_woA : lane == 30 ? &tm_woB : &tm_x;
          asm volatile("prefetch.tensormap [%0];" ::"l"(tm) : "memory");
        }
        __syncwarp();
        {
#pragma unroll 1
          for (int e = 0;; ++e) {
            if (e > 0 && e < NLAYERS) {
              mbar_wait_u(bar + B_XH0, (e - 1) & 1);
              flag_set_x(g_xf + rb * 32 + 2 * g, xbase + e + 1, UNS & 1);
            }
            mbar_wait_u(bar + B_XDONE, e & 1);
            PROFT(e < 4, 64 + e * 16 + 4);
            if (e == NLAYERS) {
              if (bid == 0) g_epoch = epoch + 1;
              break;
            }
            PROFT(e < 4, 64 + e * 16 + 5);
            flag_set(g_xf + rb * 32 + 2 * g + 1, xbase + e + 1);
            PROFT(e < 4, 64 + e * 16 + 7);
            if ((e & 1) == 0) {
#pragma unroll 1
              for (int hp = 0; hp < 2; ++hp) {
                uint4* kvl = g_kv + ((g * 2 + (e >> 1)) * 2 + hp) * 1280;
                mbar_wait_u(bar + B_KVDONE - hp * 32, (e >> 1) & 1);
                PROFT(e == PL, 243 + hp * 4);
                bulk_red_add_e(kvl + rb * 64, sb + (3 + hp) * SLOT + rb * 1024, 16384 - rb * 1024);
                if (rb) bulk_red_add_e(kvl, sb + (3 + hp) * SLOT, rb * 1024);
                bulk_red_add_e(kvl + 1024, sb + (6 + hp) * SLOT, 2048);
                bulk_red_add_e(kvl + 1152, sb + (6 + hp) * SLOT + 8192, 2048);
                bulk_commit();
                PROFT(e < 4, 64 + e * 16 + 6);
              }
              bulk_wait_read0();
              __syncwarp();
              if (lane < 2) release2(bar + B_E1);
              __syncwarp();
            }
            mbar_wait_u(bar + B_OH1, e & 1);
            PROFT(e == PL, 251);
            flag_set_x(g_of + rb * 32 + 2 * g, xbase + e + 1, UNS & 2);
            PROFT(e < 4, 64 + e * 16 + 9);
            mbar_wait_u(bar + B_ODONE, e & 1);
            PROFT(e < 4, 64 + e * 16 + 8);
            flag_set_x(g_of + rb * 32 + 2 * g + 1, xbase + e + 1, UNS & 4);
            PROFT(e < 4, 64 + e * 16 + 11);
          }
        }
      } else {
        const int h2 = threadIdx.x - 64;
        const float* cs = g_cs + (epoch & 1) * 6144;
#pragma unroll 1
        for (int layer = 0; layer < NLAYERS; ++layer) {
          if (warp == 2 && layer < 2) {
            if ((PG & 2) && layer) mbar_wait_u(bar + B_XH0, 0);
            if (lane == 0) flag_wait_t<CSLP>(&g_csflag[layer * 8 + g].v, (epoch + 1) * (16u + layer));
            __syncwarp();
            float4 a[3];
#pragma unroll
            for (int i = 0; i < 3; ++i) a[i] = __ldcg(reinterpret_cast<const float4*>(cs + layer * 3072 + g * 384) + i * 32 + lane);
#pragma unroll 1
            for (int i = 0; i < 3; ++i) {
              const float av[4] = {a[0].x, a[0].y, a[0].z, a[0].w};
              a[0] = a[1]; a[1] = a[2];
#pragma unroll
              for (int j = 0; j < 4; ++j) {
                const float c1 = bf16r(av[j]), c2 = bf16r(av[j] - c1), c3 = (av[j] - c1) - c2;
                sts128(sb + SM_BP + layer * 6144 + ((i * 32 + lane) * 4 + j) * 16, make_uint4(pack_bf16(c1, c2), pack_bf16(c3, 0.f), 0u, 0u));
              }
            }
            fence_async_smem();
            __syncwarp();
            if (lane == 0) mbar_arrive(bar + (layer ? B_CS2 : B_CS));
            PROFT(lane == 0, 64 + layer * 16 + 12);
            if (layer == 0) {
              uint4* hz = g_halo + (rb * 8 + g) * 1024;
#pragma unroll 2
              for (int i = lane; i < 1024; i += 32) hz[i] = make_uint4(0u, 0u, 0u, 0u);
              if (lane < 12) reinterpret_cast<float4*>(g_cs + ((epoch & 1) ^ 1) * 6144 + bid * 48)[lane] = make_float4(0.f, 0.f, 0.f, 0.f);
              g_stats[(2 + (lane >> 4)) * S_ + m0 + g * 16 + (lane & 15)] = make_float2(0.f, 0.f);
              __syncwarp();
              if (lane == 0) flag_add(&g_csflag[8 + g].v);
            }
          }
          if (warp == 3) {
            const bool hal = (layer & 1) && rb > 0;
            {
              uint32_t rdy = 0u;
              src_wait<SSL>(g_xf + rb * 32, xbase + layer + 1, 0xAAAAu, rdy, lane);
              rdy = 0u;
              if (hal) src_wait<256>(g_xf + (rb - 1) * 32, xbase + layer + 1, 0xAAAAu, rdy, lane);
            }
            float2 u[5];
            const float2* sp = g_stats + layer * S_ + m0 + lane;
#pragma unroll
            for (int i = 0; i < 4; ++i) u[i] = __ldcg(sp + i * 32);
            u[4] = __ldcg(hal ? sp - 16 : sp);
            if (layer == 3) g_stats[(lane >> 4) * S_ + m0 + g * 16 + (lane & 15)] = make_float2(0.f, 0.f);
#pragma unroll
            for (int i = 0; i < 5; ++i) {
              const int r = i < 4 ? 16 + i * 32 + lane : lane;
              const float mean = u[i].x * (1.f / D_);
              const float var = fmaxf(fmaf(-u[i].x, mean, u[i].y) * (1.f / D_), 0.f);
              float sd;
              asm("sqrt.approx.f32 %0, %1;" : "=f"(sd) : "f"(bf16r(bf16r(var) + 1e-5f)));
              sd = bf16r(sd);
              if (i < 4 || hal) sts_f(sb + SM_RS + r * 4, rcp(sd));
              if (i < 4) {
                const float hm = -0.5f * bf16r(mean);
                const uint32_t s2 = pack_bf16(sd, sd);
                if (!(layer & 1)) sts128(sb + SM_SD + (r - 16) * 64 + ((r >> 1) & 3) * 16, make_uint4(s2, s2, s2, s2));
                sts128(sb + SM_AP + (r - 16) * 16, make_uint4(pack_bf16(hm, hm), pack_bf16(hm, 0.f), 0u, 0u));
              }
            }
            fence_async_smem();
            __syncwarp();
            if (lane == 0) mbar_arrive(bar + B_STAT);
            PROFT(lane == 0, 64 + layer * 16 + 14);
            wo_w(__shfl_sync(0xffffffffu, layer, 0));
          }
        }
      }
    }
    __syncwarp();
    asm volatile("barrier.cluster.arrive.relaxed.aligned;\nbarrier.cluster.wait.aligned;\n" ::: "memory");
  } else {
    if (warp == 5) {
      if (lane == 0) {
        mbar_init(bar + B_FULLS, 1);
        asm volatile("fence.mbarrier_init.release.cluster;" ::: "memory");
      }
      __syncwarp();
      expect_tx_e(bar + B_FULLS, 65536);
      tma_2d_e(sb + XS * SLOT, &tm_x0, 0, m0, bar + B_FULLS);
#pragma unroll
      for (int j = 0; j < 6; ++j)
        tma_2d_e(sb + (j < 4 ? j + 4 : j - 2) * 8192, &tm_wA, (j < 4 ? 1024 + (j >> 1) * 1024 : 0) + g * 128 + (j & 1) * 64, 0, bar + B_FULLS);
      PROFT(lane == 0, 241);
    }
    if (lane < 8 && warp != 5 && threadIdx.x != 128) {
      const int i = (warp - 4) * 8 + lane;
      mbar_init(bar + i * 8, i < 32 ? 1u << ((BAR_CNT >> (2 * i)) & 3) : i < 48 ? 1u : (i == 59 || i == 60 || i == 62) ? 16u : (i == 48 || i == 63) ? 8u : 4u);
      asm volatile("fence.mbarrier_init.release.cluster;" ::: "memory");
    }
    __syncwarp();
    asm volatile("barrier.cluster.arrive.relaxed.aligned;" ::: "memory");
    asm volatile("setmaxnreg.inc.sync.aligned.u32 232;");
    cluster_wait();
    PROFT(threadIdx.x == 128, 0);
    Ctx c; c.sb = sb; c.g = g; c.rb = rb; c.cu = warp - 4; c.out = out;
    consumer(c);
    asm volatile("bar.warp.sync 0xffffffff;\nbarrier.cluster.arrive.relaxed.aligned;\nbarrier.cluster.wait.aligned;\n" ::: "memory");
  }
}

typedef CUresult (*PFN_encodeTiled)(CUtensorMap*, CUtensorMapDataType, cuuint32_t, void*, const cuuint64_t*, const cuuint64_t*,
                                    const cuuint32_t*, const cuuint32_t*, CUtensorMapInterleave, CUtensorMapSwizzle,
                                    CUtensorMapL2promotion, CUtensorMapFloatOOBfill);

static CUtensorMap make_map(PFN_encodeTiled enc, const void* ptr, uint64_t cols, uint64_t rows, uint32_t box_c, uint32_t box_r, uint32_t nb = 1) {
  CUtensorMap m;
  cuuint64_t dims[3] = {nb > 1 ? box_c : cols, rows, cols / box_c};
  cuuint64_t strides[2] = {cols * 2, box_c * 2};
  cuuint32_t box[3] = {box_c, box_r, nb};
  cuuint32_t es[3] = {1, 1, 1};
  CUresult r = enc(&m, CU_TENSOR_MAP_DATA_TYPE_BFLOAT16, nb > 1 ? 3 : 2, const_cast<void*>(ptr), dims, strides, box, es, CU_TENSOR_MAP_INTERLEAVE_NONE,
      CU_TENSOR_MAP_SWIZZLE_128B, CU_TENSOR_MAP_L2_PROMOTION_L2_256B, CU_TENSOR_MAP_FLOAT_OOB_FILL_NONE);
  (void)r;
  return m;
}

extern "C" void kernel_launch(void* const* d_in, const int* in_sizes, int n_in, void* d_out, int out_size) {
  const bf16* A_x = (const bf16*)d_in[0];
  const bf16* A_wqkv = (const bf16*)d_in[1];
  const bf16* A_wphi = (const bf16*)d_in[2];
  const bf16* A_wo = (const bf16*)d_in[3];
  const bf16* B_wqkv = (const bf16*)d_in[5];
  const bf16* B_wo = (const bf16*)d_in[6];
  bf16* out = (bf16*)d_out;

  static PFN_encodeTiled enc = nullptr;
  static bf16 *p_x, *p_o;
  if (!enc) {
    void* fn = nullptr; cudaDriverEntryPointQueryResult qr;
    cudaGetDriverEntryPoint("cuTensorMapEncodeTiled", &fn, cudaEnableDefault, &qr);
    enc = (PFN_encodeTiled)fn;
    cudaGetSymbolAddress((void**)&p_x, g_x);
    cudaGetSymbolAddress((void**)&p_o, g_o);
    cudaFuncSetAttribute(mega_kernel, cudaFuncAttributeMaxDynamicSharedMemorySize, SM_TOTAL);
  }
  CUtensorMap tm_x0 = make_map(enc, A_x, 1024, 2048, 64, 128);
  CUtensorMap tm_x = make_map(enc, p_x, 1024, 2048, 64, 128);
  CUtensorMap tm_o = make_map(enc, p_o, 1024, 2048, 64, 128);
  CUtensorMap tm_wA = make_map(enc, A_wqkv, 3072, 1024, 64, 64);
  CUtensorMap tm_wB = make_map(enc, B_wqkv, 3072, 1024, 64, 64);
  CUtensorMap tm_woA = make_map(enc, A_wo, 1024, 1024, 64, 64);
  CUtensorMap tm_woB = make_map(enc, B_wo, 1024, 1024, 64, 64);
  mega_kernel<<<128 + NX, 384, SM_TOTAL, cudaStreamPerThread>>>(tm_x0, tm_x, tm_o, tm_wA, tm_wB, tm_woA, tm_woB,
                                                           B_wqkv, A_wphi, out);
}
```

```cpp
#include <cuda_runtime.h>
#include <cuda_bf16.h>
#include <cuda.h>
#include <stdint.h>

typedef __nv_bfloat16 bf16;

constexpr int S_ = 2048, D_ = 1024;

struct __align__(128) Flag { unsigned int v; unsigned int pad[31]; };
__device__ __align__(1024) bf16 g_x[S_ * D_];
__device__ __align__(1024) bf16 g_o[S_ * D_];
__device__ __align__(1024) uint4 g_halo[128 * 2 * 512];
__device__ __align__(1024) uint4 g_kv[8 * 2 * 2 * 1280];
__device__ __align__(1024) float2 g_stats[4 * S_];
__device__ __align__(1024) float g_cs[2 * 2 * 3072];
__device__ Flag g_csflag[16];
__device__ __align__(128) unsigned int g_xf[16 * 32], g_of[16 * 32];
__device__ unsigned int g_epoch, g_err;
#define PROFT(cond, idx) asm volatile("" ::: "memory")

__device__ __forceinline__ uint32_t smem_u32(const void* p) { return (uint32_t)__cvta_generic_to_shared(p); }
__device__ __forceinline__ void mbar_init(uint32_t bar, uint32_t count) {
  asm volatile("mbarrier.init.shared::cta.b64 [%0], %1;" ::"r"(bar), "r"(count) : "memory");
}
__device__ __forceinline__ void mbar_expect_tx(uint32_t bar, uint32_t bytes) {
  asm volatile("mbarrier.arrive.expect_tx.shared::cta.b64 _, [%0], %1;" ::"r"(bar), "r"(bytes) : "memory");
}
__device__ __forceinline__ void mbar_arrive(uint32_t bar) {
  asm volatile("mbarrier.arrive.shared::cta.b64 _, [%0];" ::"r"(bar) : "memory");
}
__device__ __forceinline__ bool mbar_try_wait(uint32_t bar, uint32_t parity) {
  uint32_t ok;
  asm volatile("{\n.reg .pred p;\nmbarrier.try_wait.parity.shared::cta.b64 p, [%1], %2;\nselp.b32 %0, 1, 0, p;\n}\n"
               : "=r"(ok) : "r"(bar), "r"(parity) : "memory");
  return ok != 0;
}
__device__ __forceinline__ bool mbar_test_wait(uint32_t bar, uint32_t parity) {
  uint32_t ok;
  asm volatile("{\n.reg .pred p;\nmbarrier.test_wait.parity.shared::cta.b64 p, [%1], %2;\nselp.b32 %0, 1, 0, p;\n}\n"
               : "=r"(ok) : "r"(bar), "r"(parity) : "memory");
  return ok != 0;
}
__device__ __forceinline__ uint64_t gtimer() {
  uint64_t t; asm volatile("mov.u64 %0, %globaltimer;" : "=l"(t)); return t;
}
__device__ __forceinline__ void mbar_wait(uint32_t bar, uint32_t parity) {
  uint32_t n = 0;
#pragma unroll 1
  while (!mbar_try_wait(bar, parity)) {
    if (++n > (1u << 22)) { g_err = 1u; break; }
  }
}
__device__ __forceinline__ unsigned int ld_acquire(const unsigned int* p) {
  unsigned int v; asm volatile("ld.acquire.gpu.global.u32 %0, [%1];" : "=r"(v) : "l"(p) : "memory"); return v;
}
__device__ __forceinline__ void flag_add(unsigned int* p) {
  asm volatile("red.release.gpu.global.add.u32 [%0], 1;" ::"l"(p) : "memory");
}
__device__ __forceinline__ void flag_set(unsigned int* p, unsigned int v) {
  asm volatile("st.release.gpu.global.u32 [%0], %1;" ::"l"(p), "r"(v) : "memory");
}
__device__ __forceinline__ void flag_hint(unsigned int* p, unsigned int v) {
  asm volatile("st.relaxed.gpu.global.u32 [%0], %1;" ::"l"(p), "r"(v) : "memory");
}
template <int SLEEP>
__device__ __forceinline__ void src_wait(const unsigned int* f, unsigned int target, uint32_t need, uint32_t& ready, int lane) {
  uint32_t n = 0;
#pragma unroll 1
  while ((ready & need) != need) {
    const unsigned int v = ld_acquire(f + (lane & 15));
    ready = __ballot_sync(0xffffffffu, (int)(v - target) >= 0);
    if (SLEEP) { if ((ready & need) != need) __nanosleep(SLEEP); }
    if (++n > (1u << 20)) { g_err = 3u; break; }
  }
  __syncwarp();
}
__device__ __forceinline__ unsigned int ld_relaxed(const unsigned int* p) {
  unsigned int v; asm volatile("ld.relaxed.gpu.global.u32 %0, [%1];" : "=r"(v) : "l"(p) : "memory"); return v;
}
__device__ __forceinline__ bool src_wait_tma(const unsigned int* f, unsigned int target, uint32_t need, uint32_t& ready, int lane, uint32_t eb, uint32_t par) {
  uint32_t n = 0;
  bool fr = false;
#pragma unroll 1
  while ((ready & need) != need) {
    const unsigned int v = ld_acquire(f + (lane & 15));
    fr = __all_sync(0xffffffffu, mbar_test_wait(eb, par));
    ready = __ballot_sync(0xffffffffu, (int)(v - target) >= 0);
    if (++n > (1u << 20)) { g_err = 3u; break; }
  }
  return fr;
}
__device__ __forceinline__ uint4 ld_relaxed4(const uint4* p) {
  uint4 v; asm volatile("ld.relaxed.gpu.global.v4.u32 {%0,%1,%2,%3}, [%4];" : "=r"(v.x), "=r"(v.y), "=r"(v.z), "=r"(v.w) : "l"(p) : "memory"); return v;
}
__device__ __forceinline__ void st_relaxed4(uint4* p, uint32_t a, uint32_t b, uint32_t c, uint32_t d) {
  asm volatile("st.relaxed.gpu.global.v4.u32 [%0], {%1,%2,%3,%4};" ::"l"(p), "r"(a), "r"(b), "r"(c), "r"(d) : "memory");
}
template <int SLEEP>
__device__ __forceinline__ void flag_wait_t(const unsigned int* p, unsigned int target) {
  uint32_t n = 0;
#pragma unroll 1
  while ((int)(ld_acquire(p) - target) < 0) {
    if (SLEEP) __nanosleep(SLEEP);
    if (++n > (1u << 20)) { g_err = 2u; break; }
  }
}
__device__ __forceinline__ void flag_wait(const unsigned int* p, unsigned int target) { flag_wait_t<0>(p, target); }
__device__ __forceinline__ void flag_wait_slow(const unsigned int* p, unsigned int target) { flag_wait_t<256>(p, target); }
__device__ __forceinline__ void tma_load_2d(uint32_t dst, const CUtensorMap* tm, int c0, int c1, uint32_t bar) {
  asm volatile("cp.async.bulk.tensor.2d.shared::cluster.global.mbarrier::complete_tx::bytes [%0], [%1, {%2, %3}], [%4];"
               ::"r"(dst), "l"(tm), "r"(c0), "r"(c1), "r"(bar) : "memory");
}
__device__ __forceinline__ void tma_load_2d_mc(uint32_t dst, const CUtensorMap* tm, int c0, int c1, uint32_t bar, uint16_t mask) {
  asm volatile("cp.async.bulk.tensor.2d.shared::cluster.global.mbarrier::complete_tx::bytes.multicast::cluster [%0], [%1, {%2, %3}], [%4], %5;"
               ::"r"(dst), "l"(tm), "r"(c0), "r"(c1), "r"(bar), "h"(mask) : "memory");
}
__device__ __forceinline__ void mbar_wait_u(uint32_t bar, uint32_t parity) {
  uint32_t n = 0;
#pragma unroll 1
  while (!__all_sync(0xffffffffu, mbar_try_wait(bar, parity))) {
    if (++n > (1u << 22)) { g_err = 1u; break; }
  }
}
__device__ __forceinline__ void expect_tx_e(uint32_t bar, uint32_t bytes) {
  asm volatile("{\n.reg .pred p;\nelect.sync _|p, 0xffffffff;\n@p mbarrier.arrive.expect_tx.shared::cta.b64 _, [%0], %1;\n}\n" ::"r"(bar), "r"(bytes) : "memory");
}
__device__ __forceinline__ void tma_2d_e(uint32_t dst, const CUtensorMap* tm, int c0, int c1, uint32_t bar) {
  asm volatile("{\n.reg .pred p;\nelect.sync _|p, 0xffffffff;\n"
               "@p cp.async.bulk.tensor.2d.shared::cluster.global.mbarrier::complete_tx::bytes [%0], [%1, {%2, %3}], [%4];\n}\n"
               ::"r"(dst), "l"(tm), "r"(c0), "r"(c1), "r"(bar) : "memory");
}
__device__ __forceinline__ void tma_2d_mc_e(uint32_t dst, const CUtensorMap* tm, int c0, int c1, uint32_t bar) {
  asm volatile("{\n.reg .pred p;\nelect.sync _|p, 0xffffffff;\n"
               "@p cp.async.bulk.tensor.2d.shared::cluster.global.mbarrier::complete_tx::bytes.multicast::cluster [%0], [%1, {%2, %3}], [%4], %5;\n}\n"
               ::"r"(dst), "l"(tm), "r"(c0), "r"(c1), "r"(bar), "h"((uint16_t)3) : "memory");
}
__device__ __forceinline__ void tma_pf_e(const CUtensorMap* tm, int c0, int c1) {
  asm volatile("{\n.reg .pred p;\nelect.sync _|p, 0xffffffff;\n"
               "@p cp.async.bulk.prefetch.tensor.2d.L2.global.tile [%0, {%1, %2}];\n}\n" ::"l"(tm), "r"(c0), "r"(c1) : "memory");
}
__device__ __forceinline__ void tma_2d_to_e(uint32_t dst, const CUtensorMap* tm, int c0, int c1, uint32_t bar, uint32_t mask) {
  asm volatile("{\n.reg .pred p;\nelect.sync _|p, 0xffffffff;\n"
               "@p cp.async.bulk.tensor.2d.shared::cluster.global.mbarrier::complete_tx::bytes.multicast::cluster [%0], [%1, {%2, %3}], [%4], %5;\n}\n"
               ::"r"(dst), "l"(tm), "r"(c0), "r"(c1), "r"(bar), "h"((uint16_t)mask) : "memory");
}
__device__ __forceinline__ void tma_3d_mc_e(uint32_t dst, const CUtensorMap* tm, int c1, int c2, uint32_t bar) {
  asm volatile("{\n.reg .pred p;\nelect.sync _|p, 0xffffffff;\n"
               "@p cp.async.bulk.tensor.3d.shared::cluster.global.mbarrier::complete_tx::bytes.multicast::cluster [%0], [%1, {%6, %2, %3}], [%4], %5;\n}\n"
               ::"r"(dst), "l"(tm), "r"(c1), "r"(c2), "r"(bar), "h"((uint16_t)3), "r"(0) : "memory");
}
__device__ __forceinline__ uint32_t poll_flags(const unsigned int* f, unsigned int target, int lane) {
  const unsigned int v = ld_acquire(f + (lane & 15));
  const uint32_t r = __ballot_sync(0xffffffffu, (int)(v - target) >= 0);
  __syncwarp();
  return r;
}
__device__ __forceinline__ void mbar_arrive_cluster(uint32_t local_bar, uint32_t rank) {
  asm volatile("{\n.reg .b32 ra;\nmapa.shared::cluster.u32 ra, %0, %1;\nmbarrier.arrive.shared::cluster.b64 _, [ra];\n}\n"
               ::"r"(local_bar), "r"(rank) : "memory");
}
__device__ __forceinline__ void release2(uint32_t bar) { mbar_arrive_cluster(bar, 0); mbar_arrive_cluster(bar, 1); }
__device__ __forceinline__ void tma_store_2d(const CUtensorMap* tm, uint32_t src, int c0, int c1) {
  asm volatile("cp.async.bulk.tensor.2d.global.shared::cta.bulk_group [%0, {%2, %3}], [%1];"
               ::"l"(tm), "r"(src), "r"(c0), "r"(c1) : "memory");
}
__device__ __forceinline__ void bulk_store(void* dst, uint32_t src, uint32_t bytes) {
  asm volatile("cp.async.bulk.global.shared::cta.bulk_group [%0], [%1], %2;" ::"l"(dst), "r"(src), "r"(bytes) : "memory");
}
__device__ __forceinline__ void bulk_load(uint32_t dst, const void* src, uint32_t bytes, uint32_t bar) {
  asm volatile("cp.async.bulk.shared::cluster.global.mbarrier::complete_tx::bytes [%0], [%1], %2, [%3];" ::"r"(dst), "l"(src), "r"(bytes), "r"(bar) : "memory");
}
__device__ __forceinline__ void bulk_red_add(void* dst, uint32_t src, uint32_t bytes) {
  asm volatile("cp.reduce.async.bulk.global.shared::cta.bulk_group.add.f32 [%0], [%1], %2;" ::"l"(dst), "r"(src), "r"(bytes) : "memory");
}
__device__ __forceinline__ void bulk_red_add_e(void* dst, uint32_t src, uint32_t bytes) {
  asm volatile("{\n.reg .pred p;\nelect.sync _|p, 0xffffffff;\n@p cp.reduce.async.bulk.global.shared::cta.bulk_group.add.f32 [%0], [%1], %2;\n}\n" ::"l"(dst), "r"(src), "r"(bytes) : "memory");
}
__device__ __forceinline__ void bulk_commit() { asm volatile("cp.async.bulk.commit_group;" ::: "memory"); }
__device__ __forceinline__ void bulk_wait_read0() { asm volatile("cp.async.bulk.wait_group.read 0;" ::: "memory"); }
__device__ __forceinline__ void bulk_wait0() { asm volatile("cp.async.bulk.wait_group 0;" ::: "memory"); }
__device__ __forceinline__ void fence_async_smem() { asm volatile("fence.proxy.async.shared::cta;" ::: "memory"); }
__device__ __forceinline__ void fence_async_all() { asm volatile("fence.proxy.async.global;" ::: "memory"); }
__device__ __forceinline__ void wgmma_fence() { asm volatile("wgmma.fence.sync.aligned;" ::: "memory"); }
__device__ __forceinline__ void wgmma_commit() { asm volatile("wgmma.commit_group.sync.aligned;" ::: "memory"); }
template <int N> __device__ __forceinline__ void wgmma_wait() { asm volatile("wgmma.wait_group.sync.aligned %0;" ::"n"(N) : "memory"); }
__device__ __forceinline__ void cluster_arrive() { asm volatile("barrier.cluster.arrive.release.aligned;" ::: "memory"); }
__device__ __forceinline__ void cluster_wait() { asm volatile("barrier.cluster.wait.acquire.aligned;" ::: "memory"); }
template <int ID, int N> __device__ __forceinline__ void nbar() { asm volatile("bar.sync %0, %1;" ::"n"(ID), "n"(N) : "memory"); }
__device__ __forceinline__ uint64_t make_desc(uint32_t addr, uint32_t lbo_bytes, uint32_t sbo_bytes) {
  uint64_t d = 0;
  d |= (uint64_t)((addr & 0x3FFFF) >> 4);
  d |= (uint64_t)((lbo_bytes >> 4) & 0x3FFF) << 16;
  d |= (uint64_t)((sbo_bytes >> 4) & 0x3FFF) << 32;
  d |= (uint64_t)1 << 62;
  return d;
}
__device__ __forceinline__ uint64_t desc64(uint32_t lo, uint32_t hi) { return (uint64_t)lo | ((uint64_t)hi << 32); }
__device__ __forceinline__ uint32_t pack_bf16(float lo, float hi) {
  uint32_t r; asm("cvt.rn.bf16x2.f32 %0, %1, %2;" : "=r"(r) : "f"(hi), "f"(lo)); return r;
}
__device__ __forceinline__ uint32_t mul_bf16x2(uint32_t a, uint32_t s, bool hi) {
  __nv_bfloat162 x = *reinterpret_cast<__nv_bfloat162*>(&a), y = *reinterpret_cast<__nv_bfloat162*>(&s);
  x = __hmul2(x, hi ? __high2bfloat162(y) : __low2bfloat162(y));
  return *reinterpret_cast<uint32_t*>(&x);
}
__device__ __forceinline__ float bf16r(float x) { return __bfloat162float(__float2bfloat16_rn(x)); }
__device__ __forceinline__ float bf_lo(uint32_t u) { return __uint_as_float(u << 16); }
__device__ __forceinline__ float bf_hi(uint32_t u) { return __uint_as_float(u & 0xFFFF0000u); }
__device__ __forceinline__ float ex2(float x) { float r; asm("ex2.approx.ftz.f32 %0, %1;" : "=f"(r) : "f"(x)); return r; }
__device__ __forceinline__ float rcp(float x) { float r; asm("rcp.approx.ftz.f32 %0, %1;" : "=f"(r) : "f"(x)); return r; }
__device__ __forceinline__ void mma_bf16(float (&d)[4], uint32_t a0, uint32_t a1, uint32_t a2, uint32_t a3, uint32_t b0, uint32_t b1) {
  asm("mma.sync.aligned.m16n8k16.row.col.f32.bf16.bf16.f32 {%0,%1,%2,%3}, {%4,%5,%6,%7}, {%8,%9}, {%0,%1,%2,%3};"
               : "+f"(d[0]), "+f"(d[1]), "+f"(d[2]), "+f"(d[3]) : "r"(a0), "r"(a1), "r"(a2), "r"(a3), "r"(b0), "r"(b1));
}
__device__ __forceinline__ void ldsm_x4(uint32_t& r0, uint32_t& r1, uint32_t& r2, uint32_t& r3, uint32_t addr) {
  asm volatile("ldmatrix.sync.aligned.m8n8.x4.shared.b16 {%0,%1,%2,%3}, [%4];"
               : "=r"(r0), "=r"(r1), "=r"(r2), "=r"(r3) : "r"(addr) : "memory");
}
__device__ __forceinline__ void ldsm_x4_t(uint32_t& r0, uint32_t& r1, uint32_t& r2, uint32_t& r3, uint32_t addr) {
  asm volatile("ldmatrix.sync.aligned.m8n8.x4.trans.shared.b16 {%0,%1,%2,%3}, [%4];"
               : "=r"(r0), "=r"(r1), "=r"(r2), "=r"(r3) : "r"(addr) : "memory");
}
__device__ __forceinline__ void ldsm_x2_t(uint32_t& r0, uint32_t& r1, uint32_t addr) {
  asm volatile("ldmatrix.sync.aligned.m8n8.x2.trans.shared.b16 {%0,%1}, [%2];"
               : "=r"(r0), "=r"(r1) : "r"(addr) : "memory");
}
__device__ __forceinline__ void stsm_x4(uint32_t addr, uint32_t r0, uint32_t r1, uint32_t r2, uint32_t r3) {
  asm volatile("stmatrix.sync.aligned.m8n8.x4.shared.b16 [%0], {%1,%2,%3,%4};"
               ::"r"(addr), "r"(r0), "r"(r1), "r"(r2), "r"(r3) : "memory");
}
__device__ __forceinline__ void stsm_x4_p(bool on, uint32_t addr, uint32_t r0, uint32_t r1, uint32_t r2, uint32_t r3) {
  asm volatile("{\n.reg .pred p;\nsetp.ne.b32 p, %5, 0;\n@p stmatrix.sync.aligned.m8n8.x4.shared.b16 [%0], {%1,%2,%3,%4};\n}\n"
               ::"r"(addr), "r"(r0), "r"(r1), "r"(r2), "r"(r3), "r"((int)on) : "memory");
}
__device__ __forceinline__ float2 lds_f2(uint32_t addr) {
  float2 v; asm volatile("ld.shared.v2.f32 {%0,%1}, [%2];" : "=f"(v.x), "=f"(v.y) : "r"(addr) : "memory"); return v;
}
__device__ __forceinline__ uint4 lds128(uint32_t addr) {
  uint4 v; asm volatile("ld.shared.v4.b32 {%0,%1,%2,%3}, [%4];" : "=r"(v.x), "=r"(v.y), "=r"(v.z), "=r"(v.w) : "r"(addr) : "memory"); return v;
}
__device__ __forceinline__ void sts128(uint32_t addr, uint4 v) {
  asm volatile("st.shared.v4.b32 [%0], {%1,%2,%3,%4};" ::"r"(addr), "r"(v.x), "r"(v.y), "r"(v.z), "r"(v.w) : "memory");
}
__device__ __forceinline__ float lds_f(uint32_t addr) {
  float v; asm volatile("ld.shared.f32 %0, [%1];" : "=f"(v) : "r"(addr) : "memory"); return v;
}
__device__ __forceinline__ uint32_t lds_vol(uint32_t addr) {
  uint32_t v; asm volatile("ld.volatile.shared.u32 %0, [%1];" : "=r"(v) : "r"(addr) : "memory"); return v;
}
__device__ __forceinline__ void sts16(uint32_t addr, uint32_t v) {
  asm volatile("st.shared.u16 [%0], %1;" ::"r"(addr), "h"((unsigned short)v) : "memory");
}
__device__ __forceinline__ void nbar_dyn(int id, int n) { asm volatile("bar.sync %0, %1;" ::"r"(id), "r"(n) : "memory"); }
__device__ __forceinline__ uint64_t make_desc_ns(uint32_t addr, uint32_t lbo_bytes, uint32_t sbo_bytes) {
  return (uint64_t)((addr & 0x3FFFF) >> 4) | ((uint64_t)(lbo_bytes >> 4) << 16) | ((uint64_t)(sbo_bytes >> 4) << 32);
}
__device__ __forceinline__ void sts_f(uint32_t addr, float v) { asm volatile("st.shared.f32 [%0], %1;" ::"r"(addr), "f"(v) : "memory"); }
__device__ __forceinline__ void sts64(uint32_t addr, uint32_t a, uint32_t b) {
  asm volatile("st.shared.v2.b32 [%0], {%1,%2};" ::"r"(addr), "r"(a), "r"(b) : "memory");
}
__device__ __forceinline__ void sts_f2(uint32_t addr, float a, float b) {
  asm volatile("st.shared.v2.f32 [%0], {%1,%2};" ::"r"(addr), "f"(a), "f"(b) : "memory");
}
__device__ __forceinline__ void red_add2(float* p, float a, float b) {
  asm volatile("red.global.add.v2.f32 [%0], {%1,%2};" ::"l"(p), "f"(a), "f"(b) : "memory");
}
__device__ __forceinline__ void red_add4(float* p, float a, float b, float c, float d) {
  asm volatile("red.global.add.v4.f32 [%0], {%1,%2,%3,%4};" ::"l"(p), "f"(a), "f"(b), "f"(c), "f"(d) : "memory");
}
__device__ __forceinline__ void red_add1(float* p, float a) {
  asm volatile("red.global.add.f32 [%0], %1;" ::"l"(p), "f"(a) : "memory");
}
__device__ __forceinline__ void l2_prefetch(const void* p, uint32_t bytes) {
  asm volatile("cp.async.bulk.prefetch.L2.global [%0], %1;" ::"l"(p), "r"(bytes) : "memory");
}

__device__ __forceinline__ void wgmma_n256(float (&d)[192], uint64_t da, uint64_t db, int scale_d) {
  asm volatile("{\n.reg .pred p;\nsetp.ne.b32 p, %130, 0;\n"
    "wgmma.mma_async.sync.aligned.m64n256k16.f32.bf16.bf16 {%0, %1, %2, %3, %4, %5, %6, %7, %8, %9, %10, %11, %12, %13, %14, %15, %16, %17, %18, %19, %20, %21, %22, %23, %24, %25, %26, %27, %28, %29, %30, %31, %32, %33, %34, %35, %36, %37, %38, %39, %40, %41, %42, %43, %44, %45, %46, %47, %48, %49, %50, %51, %52, %53, %54, %55, %56, %57, %58, %59, %60, %61, %62, %63, %64, %65, %66, %67, %68, %69, %70, %71, %72, %73, %74, %75, %76, %77, %78, %79, %80, %81, %82, %83, %84, %85, %86, %87, %88, %89, %90, %91, %92, %93, %94, %95, %96, %97, %98, %99, %100, %101, %102, %103, %104, %105, %106, %107, %108, %109, %110, %111, %112, %113, %114, %115, %116, %117, %118, %119, %120, %121, %122, %123, %124, %125, %126, %127}, %128, %129, p, 1, 1, 0, 1;\n}\n"
    : "+f"(d[0]), "+f"(d[1]), "+f"(d[2]), "+f"(d[3]), "+f"(d[4]), "+f"(d[5]), "+f"(d[6]), "+f"(d[7]), "+f"(d[8]), "+f"(d[9]), "+f"(d[10]), "+f"(d[11]), "+f"(d[12]), "+f"(d[13]), "+f"(d[14]), "+f"(d[15]), "+f"(d[16]), "+f"(d[17]), "+f"(d[18]), "+f"(d[19]), "+f"(d[20]), "+f"(d[21]), "+f"(d[22]), "+f"(d[23]), "+f"(d[24]), "+f"(d[25]), "+f"(d[26]), "+f"(d[27]), "+f"(d[28]), "+f"(d[29]), "+f"(d[30]), "+f"(d[31]), "+f"(d[32]), "+f"(d[33]), "+f"(d[34]), "+f"(d[35]), "+f"(d[36]), "+f"(d[37]), "+f"(d[38]), "+f"(d[39]), "+f"(d[40]), "+f"(d[41]), "+f"(d[42]), "+f"(d[43]), "+f"(d[44]), "+f"(d[45]), "+f"(d[46]), "+f"(d[47]), "+f"(d[48]), "+f"(d[49]), "+f"(d[50]), "+f"(d[51]), "+f"(d[52]), "+f"(d[53]), "+f"(d[54]), "+f"(d[55]), "+f"(d[56]), "+f"(d[57]), "+f"(d[58]), "+f"(d[59]), "+f"(d[60]), "+f"(d[61]), "+f"(d[62]), "+f"(d[63]), "+f"(d[64]), "+f"(d[65]), "+f"(d[66]), "+f"(d[67]), "+f"(d[68]), "+f"(d[69]), "+f"(d[70]), "+f"(d[71]), "+f"(d[72]), "+f"(d[73]), "+f"(d[74]), "+f"(d[75]), "+f"(d[76]), "+f"(d[77]), "+f"(d[78]), "+f"(d[79]), "+f"(d[80]), "+f"(d[81]), "+f"(d[82]), "+f"(d[83]), "+f"(d[84]), "+f"(d[85]), "+f"(d[86]), "+f"(d[87]), "+f"(d[88]), "+f"(d[89]), "+f"(d[90]), "+f"(d[91]), "+f"(d[92]), "+f"(d[93]), "+f"(d[94]), "+f"(d[95]), "+f"(d[96]), "+f"(d[97]), "+f"(d[98]), "+f"(d[99]), "+f"(d[100]), "+f"(d[101]), "+f"(d[102]), "+f"(d[103]), "+f"(d[104]), "+f"(d[105]), "+f"(d[106]), "+f"(d[107]), "+f"(d[108]), "+f"(d[109]), "+f"(d[110]), "+f"(d[111]), "+f"(d[112]), "+f"(d[113]), "+f"(d[114]), "+f"(d[115]), "+f"(d[116]), "+f"(d[117]), "+f"(d[118]), "+f"(d[119]), "+f"(d[120]), "+f"(d[121]), "+f"(d[122]), "+f"(d[123]), "+f"(d[124]), "+f"(d[125]), "+f"(d[126]), "+f"(d[127])
    : "l"(da), "l"(db), "r"(scale_d));
}
__device__ __forceinline__ void wgmma_n128(float (&d)[192], uint64_t da, uint64_t db, int scale_d) {
  asm volatile("{\n.reg .pred p;\nsetp.ne.b32 p, %66, 0;\n"
    "wgmma.mma_async.sync.aligned.m64n128k16.f32.bf16.bf16 {%0, %1, %2, %3, %4, %5, %6, %7, %8, %9, %10, %11, %12, %13, %14, %15, %16, %17, %18, %19, %20, %21, %22, %23, %24, %25, %26, %27, %28, %29, %30, %31, %32, %33, %34, %35, %36, %37, %38, %39, %40, %41, %42, %43, %44, %45, %46, %47, %48, %49, %50, %51, %52, %53, %54, %55, %56, %57, %58, %59, %60, %61, %62, %63}, %64, %65, p, 1, 1, 0, 1;\n}\n"
    : "+f"(d[128]), "+f"(d[129]), "+f"(d[130]), "+f"(d[131]), "+f"(d[132]), "+f"(d[133]), "+f"(d[134]), "+f"(d[135]), "+f"(d[136]), "+f"(d[137]), "+f"(d[138]), "+f"(d[139]), "+f"(d[140]), "+f"(d[141]), "+f"(d[142]), "+f"(d[143]), "+f"(d[144]), "+f"(d[145]), "+f"(d[146]), "+f"(d[147]), "+f"(d[148]), "+f"(d[149]), "+f"(d[150]), "+f"(d[151]), "+f"(d[152]), "+f"(d[153]), "+f"(d[154]), "+f"(d[155]), "+f"(d[156]), "+f"(d[157]), "+f"(d[158]), "+f"(d[159]), "+f"(d[160]), "+f"(d[161]), "+f"(d[162]), "+f"(d[163]), "+f"(d[164]), "+f"(d[165]), "+f"(d[166]), "+f"(d[167]), "+f"(d[168]), "+f"(d[169]), "+f"(d[170]), "+f"(d[171]), "+f"(d[172]), "+f"(d[173]), "+f"(d[174]), "+f"(d[175]), "+f"(d[176]), "+f"(d[177]), "+f"(d[178]), "+f"(d[179]), "+f"(d[180]), "+f"(d[181]), "+f"(d[182]), "+f"(d[183]), "+f"(d[184]), "+f"(d[185]), "+f"(d[186]), "+f"(d[187]), "+f"(d[188]), "+f"(d[189]), "+f"(d[190]), "+f"(d[191])
    : "l"(da), "l"(db), "r"(scale_d));
}
__device__ __forceinline__ void wgmma_n256_k(float (&d)[192], uint64_t da, uint64_t db, int scale_d) {
  asm volatile("{\n.reg .pred p;\nsetp.ne.b32 p, %130, 0;\n"
    "wgmma.mma_async.sync.aligned.m64n256k16.f32.bf16.bf16 {%0, %1, %2, %3, %4, %5, %6, %7, %8, %9, %10, %11, %12, %13, %14, %15, %16, %17, %18, %19, %20, %21, %22, %23, %24, %25, %26, %27, %28, %29, %30, %31, %32, %33, %34, %35, %36, %37, %38, %39, %40, %41, %42, %43, %44, %45, %46, %47, %48, %49, %50, %51, %52, %53, %54, %55, %56, %57, %58, %59, %60, %61, %62, %63, %64, %65, %66, %67, %68, %69, %70, %71, %72, %73, %74, %75, %76, %77, %78, %79, %80, %81, %82, %83, %84, %85, %86, %87, %88, %89, %90, %91, %92, %93, %94, %95, %96, %97, %98, %99, %100, %101, %102, %103, %104, %105, %106, %107, %108, %109, %110, %111, %112, %113, %114, %115, %116, %117, %118, %119, %120, %121, %122, %123, %124, %125, %126, %127}, %128, %129, p, 1, 1, 0, 0;\n}\n"
    : "+f"(d[0]), "+f"(d[1]), "+f"(d[2]), "+f"(d[3]), "+f"(d[4]), "+f"(d[5]), "+f"(d[6]), "+f"(d[7]), "+f"(d[8]), "+f"(d[9]), "+f"(d[10]), "+f"(d[11]), "+f"(d[12]), "+f"(d[13]), "+f"(d[14]), "+f"(d[15]), "+f"(d[16]), "+f"(d[17]), "+f"(d[18]), "+f"(d[19]), "+f"(d[20]), "+f"(d[21]), "+f"(d[22]), "+f"(d[23]), "+f"(d[24]), "+f"(d[25]), "+f"(d[26]), "+f"(d[27]), "+f"(d[28]), "+f"(d[29]), "+f"(d[30]), "+f"(d[31]), "+f"(d[32]), "+f"(d[33]), "+f"(d[34]), "+f"(d[35]), "+f"(d[36]), "+f"(d[37]), "+f"(d[38]), "+f"(d[39]), "+f"(d[40]), "+f"(d[41]), "+f"(d[42]), "+f"(d[43]), "+f"(d[44]), "+f"(d[45]), "+f"(d[46]), "+f"(d[47]), "+f"(d[48]), "+f"(d[49]), "+f"(d[50]), "+f"(d[51]), "+f"(d[52]), "+f"(d[53]), "+f"(d[54]), "+f"(d[55]), "+f"(d[56]), "+f"(d[57]), "+f"(d[58]), "+f"(d[59]), "+f"(d[60]), "+f"(d[61]), "+f"(d[62]), "+f"(d[63]), "+f"(d[64]), "+f"(d[65]), "+f"(d[66]), "+f"(d[67]), "+f"(d[68]), "+f"(d[69]), "+f"(d[70]), "+f"(d[71]), "+f"(d[72]), "+f"(d[73]), "+f"(d[74]), "+f"(d[75]), "+f"(d[76]), "+f"(d[77]), "+f"(d[78]), "+f"(d[79]), "+f"(d[80]), "+f"(d[81]), "+f"(d[82]), "+f"(d[83]), "+f"(d[84]), "+f"(d[85]), "+f"(d[86]), "+f"(d[87]), "+f"(d[88]), "+f"(d[89]), "+f"(d[90]), "+f"(d[91]), "+f"(d[92]), "+f"(d[93]), "+f"(d[94]), "+f"(d[95]), "+f"(d[96]), "+f"(d[97]), "+f"(d[98]), "+f"(d[99]), "+f"(d[100]), "+f"(d[101]), "+f"(d[102]), "+f"(d[103]), "+f"(d[104]), "+f"(d[105]), "+f"(d[106]), "+f"(d[107]), "+f"(d[108]), "+f"(d[109]), "+f"(d[110]), "+f"(d[111]), "+f"(d[112]), "+f"(d[113]), "+f"(d[114]), "+f"(d[115]), "+f"(d[116]), "+f"(d[117]), "+f"(d[118]), "+f"(d[119]), "+f"(d[120]), "+f"(d[121]), "+f"(d[122]), "+f"(d[123]), "+f"(d[124]), "+f"(d[125]), "+f"(d[126]), "+f"(d[127])
    : "l"(da), "l"(db), "r"(scale_d));
}
__device__ __forceinline__ void wgmma_n128_k(float (&d)[192], uint64_t da, uint64_t db, int scale_d) {
  asm volatile("{\n.reg .pred p;\nsetp.ne.b32 p, %66, 0;\n"
    "wgmma.mma_async.sync.aligned.m64n128k16.f32.bf16.bf16 {%0, %1, %2, %3, %4, %5, %6, %7, %8, %9, %10, %11, %12, %13, %14, %15, %16, %17, %18, %19, %20, %21, %22, %23, %24, %25, %26, %27, %28, %29, %30, %31, %32, %33, %34, %35, %36, %37, %38, %39, %40, %41, %42, %43, %44, %45, %46, %47, %48, %49, %50, %51, %52, %53, %54, %55, %56, %57, %58, %59, %60, %61, %62, %63}, %64, %65, p, 1, 1, 0, 0;\n}\n"
    : "+f"(d[128]), "+f"(d[129]), "+f"(d[130]), "+f"(d[131]), "+f"(d[132]), "+f"(d[133]), "+f"(d[134]), "+f"(d[135]), "+f"(d[136]), "+f"(d[137]), "+f"(d[138]), "+f"(d[139]), "+f"(d[140]), "+f"(d[141]), "+f"(d[142]), "+f"(d[143]), "+f"(d[144]), "+f"(d[145]), "+f"(d[146]), "+f"(d[147]), "+f"(d[148]), "+f"(d[149]), "+f"(d[150]), "+f"(d[151]), "+f"(d[152]), "+f"(d[153]), "+f"(d[154]), "+f"(d[155]), "+f"(d[156]), "+f"(d[157]), "+f"(d[158]), "+f"(d[159]), "+f"(d[160]), "+f"(d[161]), "+f"(d[162]), "+f"(d[163]), "+f"(d[164]), "+f"(d[165]), "+f"(d[166]), "+f"(d[167]), "+f"(d[168]), "+f"(d[169]), "+f"(d[170]), "+f"(d[171]), "+f"(d[172]), "+f"(d[173]), "+f"(d[174]), "+f"(d[175]), "+f"(d[176]), "+f"(d[177]), "+f"(d[178]), "+f"(d[179]), "+f"(d[180]), "+f"(d[181]), "+f"(d[182]), "+f"(d[183]), "+f"(d[184]), "+f"(d[185]), "+f"(d[186]), "+f"(d[187]), "+f"(d[188]), "+f"(d[189]), "+f"(d[190]), "+f"(d[191])
    : "l"(da), "l"(db), "r"(scale_d));
}
__device__ __forceinline__ void wgmma_n40_tt(float (&d)[20], uint64_t da, uint64_t db, int scale_d) {
  asm volatile("{\n.reg .pred p;\nsetp.ne.b32 p, %22, 0;\n"
    "wgmma.mma_async.sync.aligned.m64n40k16.f32.bf16.bf16 {%0, %1, %2, %3, %4, %5, %6, %7, %8, %9, %10, %11, %12, %13, %14, %15, %16, %17, %18, %19}, %20, %21, p, 1, 1, 1, 1;\n}\n"
    : "+f"(d[0]), "+f"(d[1]), "+f"(d[2]), "+f"(d[3]), "+f"(d[4]), "+f"(d[5]), "+f"(d[6]), "+f"(d[7]), "+f"(d[8]), "+f"(d[9]), "+f"(d[10]), "+f"(d[11]), "+f"(d[12]), "+f"(d[13]), "+f"(d[14]), "+f"(d[15]), "+f"(d[16]), "+f"(d[17]), "+f"(d[18]), "+f"(d[19])
    : "l"(da), "l"(db), "r"(scale_d));
}
__device__ __forceinline__ void wgmma_n40_rs(float (&d)[20], const uint32_t (&a)[4], uint64_t db, int scale_d) {
  asm volatile("{\n.reg .pred p;\nsetp.ne.b32 p, %25, 0;\n"
    "wgmma.mma_async.sync.aligned.m64n40k16.f32.bf16.bf16 {%0, %1, %2, %3, %4, %5, %6, %7, %8, %9, %10, %11, %12, %13, %14, %15, %16, %17, %18, %19}, {%20, %21, %22, %23}, %24, p, 1, 1, 1;\n}\n"
    : "+f"(d[0]), "+f"(d[1]), "+f"(d[2]), "+f"(d[3]), "+f"(d[4]), "+f"(d[5]), "+f"(d[6]), "+f"(d[7]), "+f"(d[8]), "+f"(d[9]), "+f"(d[10]), "+f"(d[11]), "+f"(d[12]), "+f"(d[13]), "+f"(d[14]), "+f"(d[15]), "+f"(d[16]), "+f"(d[17]), "+f"(d[18]), "+f"(d[19])
    : "r"(a[0]), "r"(a[1]), "r"(a[2]), "r"(a[3]), "l"(db), "r"(scale_d));
}
__device__ __forceinline__ void wgmma_n256_0(float (&d)[192], uint64_t da, uint64_t db) {
  asm volatile("{\n.reg .pred p;\nsetp.ne.b32 p, 0, 0;\n"
    "wgmma.mma_async.sync.aligned.m64n256k16.f32.bf16.bf16 {%0, %1, %2, %3, %4, %5, %6, %7, %8, %9, %10, %11, %12, %13, %14, %15, %16, %17, %18, %19, %20, %21, %22, %23, %24, %25, %26, %27, %28, %29, %30, %31, %32, %33, %34, %35, %36, %37, %38, %39, %40, %41, %42, %43, %44, %45, %46, %47, %48, %49, %50, %51, %52, %53, %54, %55, %56, %57, %58, %59, %60, %61, %62, %63, %64, %65, %66, %67, %68, %69, %70, %71, %72, %73, %74, %75, %76, %77, %78, %79, %80, %81, %82, %83, %84, %85, %86, %87, %88, %89, %90, %91, %92, %93, %94, %95, %96, %97, %98, %99, %100, %101, %102, %103, %104, %105, %106, %107, %108, %109, %110, %111, %112, %113, %114, %115, %116, %117, %118, %119, %120, %121, %122, %123, %124, %125, %126, %127}, %128, %129, p, 1, 1, 0, 1;\n}\n"
    : "=f"(d[0]), "=f"(d[1]), "=f"(d[2]), "=f"(d[3]), "=f"(d[4]), "=f"(d[5]), "=f"(d[6]), "=f"(d[7]), "=f"(d[8]), "=f"(d[9]), "=f"(d[10]), "=f"(d[11]), "=f"(d[12]), "=f"(d[13]), "=f"(d[14]), "=f"(d[15]), "=f"(d[16]), "=f"(d[17]), "=f"(d[18]), "=f"(d[19]), "=f"(d[20]), "=f"(d[21]), "=f"(d[22]), "=f"(d[23]), "=f"(d[24]), "=f"(d[25]), "=f"(d[26]), "=f"(d[27]), "=f"(d[28]), "=f"(d[29]), "=f"(d[30]), "=f"(d[31]), "=f"(d[32]), "=f"(d[33]), "=f"(d[34]), "=f"(d[35]), "=f"(d[36]), "=f"(d[37]), "=f"(d[38]), "=f"(d[39]), "=f"(d[40]), "=f"(d[41]), "=f"(d[42]), "=f"(d[43]), "=f"(d[44]), "=f"(d[45]), "=f"(d[46]), "=f"(d[47]), "=f"(d[48]), "=f"(d[49]), "=f"(d[50]), "=f"(d[51]), "=f"(d[52]), "=f"(d[53]), "=f"(d[54]), "=f"(d[55]), "=f"(d[56]), "=f"(d[57]), "=f"(d[58]), "=f"(d[59]), "=f"(d[60]), "=f"(d[61]), "=f"(d[62]), "=f"(d[63]), "=f"(d[64]), "=f"(d[65]), "=f"(d[66]), "=f"(d[67]), "=f"(d[68]), "=f"(d[69]), "=f"(d[70]), "=f"(d[71]), "=f"(d[72]), "=f"(d[73]), "=f"(d[74]), "=f"(d[75]), "=f"(d[76]), "=f"(d[77]), "=f"(d[78]), "=f"(d[79]), "=f"(d[80]), "=f"(d[81]), "=f"(d[82]), "=f"(d[83]), "=f"(d[84]), "=f"(d[85]), "=f"(d[86]), "=f"(d[87]), "=f"(d[88]), "=f"(d[89]), "=f"(d[90]), "=f"(d[91]), "=f"(d[92]), "=f"(d[93]), "=f"(d[94]), "=f"(d[95]), "=f"(d[96]), "=f"(d[97]), "=f"(d[98]), "=f"(d[99]), "=f"(d[100]), "=f"(d[101]), "=f"(d[102]), "=f"(d[103]), "=f"(d[104]), "=f"(d[105]), "=f"(d[106]), "=f"(d[107]), "=f"(d[108]), "=f"(d[109]), "=f"(d[110]), "=f"(d[111]), "=f"(d[112]), "=f"(d[113]), "=f"(d[114]), "=f"(d[115]), "=f"(d[116]), "=f"(d[117]), "=f"(d[118]), "=f"(d[119]), "=f"(d[120]), "=f"(d[121]), "=f"(d[122]), "=f"(d[123]), "=f"(d[124]), "=f"(d[125]), "=f"(d[126]), "=f"(d[127])
    : "l"(da), "l"(db));
}
__device__ __forceinline__ void wgmma_n128_0(float (&d)[192], uint64_t da, uint64_t db) {
  asm volatile("{\n.reg .pred p;\nsetp.ne.b32 p, 0, 0;\n"
    "wgmma.mma_async.sync.aligned.m64n128k16.f32.bf16.bf16 {%0, %1, %2, %3, %4, %5, %6, %7, %8, %9, %10, %11, %12, %13, %14, %15, %16, %17, %18, %19, %20, %21, %22, %23, %24, %25, %26, %27, %28, %29, %30, %31, %32, %33, %34, %35, %36, %37, %38, %39, %40, %41, %42, %43, %44, %45, %46, %47, %48, %49, %50, %51, %52, %53, %54, %55, %56, %57, %58, %59, %60, %61, %62, %63}, %64, %65, p, 1, 1, 0, 1;\n}\n"
    : "=f"(d[128]), "=f"(d[129]), "=f"(d[130]), "=f"(d[131]), "=f"(d[132]), "=f"(d[133]), "=f"(d[134]), "=f"(d[135]), "=f"(d[136]), "=f"(d[137]), "=f"(d[138]), "=f"(d[139]), "=f"(d[140]), "=f"(d[141]), "=f"(d[142]), "=f"(d[143]), "=f"(d[144]), "=f"(d[145]), "=f"(d[146]), "=f"(d[147]), "=f"(d[148]), "=f"(d[149]), "=f"(d[150]), "=f"(d[151]), "=f"(d[152]), "=f"(d[153]), "=f"(d[154]), "=f"(d[155]), "=f"(d[156]), "=f"(d[157]), "=f"(d[158]), "=f"(d[159]), "=f"(d[160]), "=f"(d[161]), "=f"(d[162]), "=f"(d[163]), "=f"(d[164]), "=f"(d[165]), "=f"(d[166]), "=f"(d[167]), "=f"(d[168]), "=f"(d[169]), "=f"(d[170]), "=f"(d[171]), "=f"(d[172]), "=f"(d[173]), "=f"(d[174]), "=f"(d[175]), "=f"(d[176]), "=f"(d[177]), "=f"(d[178]), "=f"(d[179]), "=f"(d[180]), "=f"(d[181]), "=f"(d[182]), "=f"(d[183]), "=f"(d[184]), "=f"(d[185]), "=f"(d[186]), "=f"(d[187]), "=f"(d[188]), "=f"(d[189]), "=f"(d[190]), "=f"(d[191])
    : "l"(da), "l"(db));
}
__device__ __forceinline__ void wgmma_n128_rs(float (&d)[192], const uint32_t (&a)[4], uint64_t db, int scale_d) {
  asm volatile("{\n.reg .pred p;\nsetp.ne.b32 p, %69, 0;\n"
    "wgmma.mma_async.sync.aligned.m64n128k16.f32.bf16.bf16 {%0, %1, %2, %3, %4, %5, %6, %7, %8, %9, %10, %11, %12, %13, %14, %15, %16, %17, %18, %19, %20, %21, %22, %23, %24, %25, %26, %27, %28, %29, %30, %31, %32, %33, %34, %35, %36, %37, %38, %39, %40, %41, %42, %43, %44, %45, %46, %47, %48, %49, %50, %51, %52, %53, %54, %55, %56, %57, %58, %59, %60, %61, %62, %63}, {%64, %65, %66, %67}, %68, p, 1, 1, 1;\n}\n"
    : "+f"(d[128]), "+f"(d[129]), "+f"(d[130]), "+f"(d[131]), "+f"(d[132]), "+f"(d[133]), "+f"(d[134]), "+f"(d[135]), "+f"(d[136]), "+f"(d[137]), "+f"(d[138]), "+f"(d[139]), "+f"(d[140]), "+f"(d[141]), "+f"(d[142]), "+f"(d[143]), "+f"(d[144]), "+f"(d[145]), "+f"(d[146]), "+f"(d[147]), "+f"(d[148]), "+f"(d[149]), "+f"(d[150]), "+f"(d[151]), "+f"(d[152]), "+f"(d[153]), "+f"(d[154]), "+f"(d[155]), "+f"(d[156]), "+f"(d[157]), "+f"(d[158]), "+f"(d[159]), "+f"(d[160]), "+f"(d[161]), "+f"(d[162]), "+f"(d[163]), "+f"(d[164]), "+f"(d[165]), "+f"(d[166]), "+f"(d[167]), "+f"(d[168]), "+f"(d[169]), "+f"(d[170]), "+f"(d[171]), "+f"(d[172]), "+f"(d[173]), "+f"(d[174]), "+f"(d[175]), "+f"(d[176]), "+f"(d[177]), "+f"(d[178]), "+f"(d[179]), "+f"(d[180]), "+f"(d[181]), "+f"(d[182]), "+f"(d[183]), "+f"(d[184]), "+f"(d[185]), "+f"(d[186]), "+f"(d[187]), "+f"(d[188]), "+f"(d[189]), "+f"(d[190]), "+f"(d[191])
    : "r"(a[0]), "r"(a[1]), "r"(a[2]), "r"(a[3]), "l"(db), "r"(scale_d));
}

constexpr int SLOT = 16384;
constexpr int KVT = 10240;
constexpr uint32_t QA = 0x0BAu, QK = 0x462u, QQ = 0x981u;
constexpr int SM_SD = 12 * SLOT;
constexpr int SM_BAR = SM_SD + 8192;
constexpr int SM_RS = SM_BAR + 512;
constexpr int SM_AP = SM_RS + 768;
constexpr int SM_BP = SM_AP + 2048;
constexpr int SM_WPHI = SM_BP + 12288;
constexpr int SM_EPOCH = SM_WPHI + 10240;
constexpr int SM_TOTAL = SM_EPOCH + 16 + 1024;
constexpr int B_FULLS = 0, B_XOLD = 24, B_STAT = 32, B_EMPTYS = 40, B_FULLT = 256  , B_CONS = 384  , B_E3 = 472, B_E0 = 480, B_E1 = 488, B_E2 = 496, B_EPI = 504, B_CS = 160,
              B_KVDONE = 168  , B_ODONE = 176, B_XDONE = 184, B_OH1 = B_CONS, B_CS2 = 208, B_XH0 = 232, B_R0 = 240, B_CB = 144  , B_XOLD2 = 216, B_FLG = 64  ;
constexpr uint64_t BAR_CNT = 0x1c07fc0eac00a800ull;
constexpr uint64_t WO_A0 = 0xa461b57648357643ull, WO_B0 = 0x59083a9021ba9021ull, WO_A1 = 0xa0b76901276a5babull, WO_B1 = 0x95428a5b34890132ull;
constexpr uint64_t WO_DA0 = 0xa9865432ff00dd00ull, WO_DB0 = 0xa986543211bbccccull, WO_DA1 = 0xa98654321ffff000ull, WO_DB1 = 0xa98754321bbcccddull;
#define WOORD 0xFDB9753ECA864210ull
constexpr int NX = 4;
constexpr int XS = 10;

#define PL 2
#define PROFX(i) PROFT(tid_ == 128 && layer == PL, 200 + (i))
#define PSL 20
#define EP 5
#define NCOM 3
#define PFS 8
#define KVTH 0x41700000u
#define PMOD 3
#define XPF 3
#define XPM 2
#define TLINE 1
#define MAP 1
#define NLAYERS 4
constexpr float L2E = 1.4426950408889634f;
#define PHI_MAX 2147483648.f

#define D128(lo) desc64(lo, 0x40000040u)
struct Ctx { uint32_t sb; int g, rb, cu; bf16* out; };

__device__ __forceinline__ void colsum(const CUtensorMap* tm, float* cs, int rb, int g, int w0, int dw, int lane, uint32_t stg, uint32_t cb, uint32_t par) {
  const uint32_t src = stg + (lane >> 3) * 2048;
#pragma unroll 1
  for (int wi = w0 - dw; wi < 6; wi += dw) {
    float s[8] = {0.f, 0.f, 0.f, 0.f, 0.f, 0.f, 0.f, 0.f};
    if (wi >= 0) {
      mbar_wait_u(cb, par);
      par ^= 1;
#pragma unroll 4
      for (int r = 0; r < 16; ++r) {
        const uint4 v = lds128(src + r * 128 + (((lane ^ r) & 7) << 4));
        s[0] += bf_lo(v.x); s[1] += bf_hi(v.x); s[2] += bf_lo(v.y); s[3] += bf_hi(v.y);
        s[4] += bf_lo(v.z); s[5] += bf_hi(v.z); s[6] += bf_lo(v.w); s[7] += bf_hi(v.w);
      }
#pragma unroll
      for (int i = 0; i < 8; ++i) s[i] += __shfl_xor_sync(0xffffffffu, s[i], 8);
    }
    const int wn = wi + dw;
    if (wn < 6) {
      expect_tx_e(cb, 8192);
      tma_2d_e(stg, tm, (wn >= 4 ? 0 : 1024 + (wn >> 1) * 1024) + g * 128 + (wn & 1) * 64, rb * 64, cb);
    }
    if (wi >= 0) {
#pragma unroll
      for (int i = 0; i < 8; ++i) s[i] += __shfl_xor_sync(0xffffffffu, s[i], 16);
      if (lane < 8) {
        red_add4(cs + g * 384 + (wi * 8 + lane) * 8, s[0], s[1], s[2], s[3]);
        red_add4(cs + g * 384 + (wi * 8 + lane) * 8 + 4, s[4], s[5], s[6], s[7]);
      }
      __syncwarp();
    }
  }
}
#define PHASE_CTX() \
  uint32_t sb = c.sb; asm volatile("" : "+r"(sb)); \
  int tid_ = threadIdx.x; asm volatile("" : "+r"(tid_)); \
  const uint32_t bar = sb + SM_BAR; \
  const int lane = tid_ & 31, cw = (tid_ >> 5) - 4, wg = cw >> 2, wq = cw & 3, gq = lane >> 2, t = lane & 3, wrow0 = cw * 16; \
  const int lrow = (lane & 7) + ((lane >> 3) & 1) * 8, lchk = lane >> 4; \
  const bool elected = (tid_ & 127) == 0; \
  const uint32_t rowo = (wrow0 + lrow) * 128, X = (lchk ^ (lane & 7)) << 4; \
  (void)bar; (void)wq; (void)gq; (void)lrow; (void)lchk; (void)elected; (void)wrow0; (void)wg; (void)rowo; (void)X; (void)t;

__device__ __forceinline__ void slab_out_half(uint32_t slot, bf16* dst, int wrow0, int lane, bool FENCE = false) {
  const int r0 = lane >> 3, ch = lane & 7;
  const uint32_t src = slot + (wrow0 + r0) * 128;
  uint4 v[4];
#pragma unroll
  for (int i = 0; i < 4; ++i) v[i] = lds128(src + i * 512 + (((ch ^ (4 * i + r0)) & 7) << 4));
  if (FENCE) fence_async_smem();
  dst += (size_t)(wrow0 + r0) * D_ + ch * 8;
#pragma unroll
  for (int i = 0; i < 4; ++i)
    asm volatile("st.global.v4.u32 [%0], {%1,%2,%3,%4};" ::"l"(dst + (size_t)i * 4 * D_), "r"(v[i].x), "r"(v[i].y), "r"(v[i].z), "r"(v[i].w) : "memory");
}

struct Tag { uint32_t me, mo, tg; };
__device__ __forceinline__ Tag make_tag(int gq, int t, uint32_t tg) { return Tag{t == 0, t == 1, tg}; }
__device__ __forceinline__ void stsm_tag(uint32_t addr, uint32_t r0, uint32_t r1, uint32_t r2, uint32_t r3, const Tag& k, int jp) {
  if (jp == 0) stsm_x4(addr, (r0 & ~k.me) | (k.tg & k.me), (r1 & ~k.mo) | (k.tg & k.mo), r2, r3);
  else stsm_x4(addr, r0, r1, r2, r3);
}
#define TILE_BAD() ((lds_vol(va) ^ tg) & 1)
#define TILE_VA() (slot + (wrow0 + (lane & 15)) * 128 + (lane & 7) * 16 + ((lane >> 3) & 1) * 4)
__device__ __forceinline__ void tile_check(uint32_t slot, const bf16* src, int wrow0, int lane, uint32_t tg) {
  const uint32_t va = TILE_VA();
  if (__builtin_expect(__any_sync(0xffffffffu, TILE_BAD()), 0)) {
    const int r0 = lane >> 3, ch = lane & 7;
    uint32_t n = 0;
#pragma unroll 1
    do {
      uint4 v[4];
#pragma unroll
      for (int i = 0; i < 4; ++i) v[i] = ld_relaxed4(reinterpret_cast<const uint4*>(src + (size_t)(wrow0 + r0 + 4 * i) * D_ + ch * 8));
#pragma unroll
      for (int i = 0; i < 4; ++i) sts128(slot + (wrow0 + r0 + 4 * i) * 128 + (((ch ^ (4 * i + r0)) & 7) << 4), v[i]);
      __syncwarp();
      if (++n > (1u << 16)) { g_err = 8u; break; }
    } while (__any_sync(0xffffffffu, TILE_BAD()));
    fence_async_smem();
    __syncwarp();
  }
}

template <int O>
__device__ __forceinline__ void phi_proj(float (&p)[2][4][4], const uint32_t (&kq)[64], uint32_t wa) {
#pragma unroll
  for (int h = 0; h < 2; ++h)
#pragma unroll
    for (int i = 0; i < 4; ++i) { p[h][i][0] = p[h][i][1] = p[h][i][2] = p[h][i][3] = 0.f; }
#pragma unroll
  for (int ks = 0; ks < 2; ++ks)
#pragma unroll
    for (int np = 0; np < 2; ++np)
#pragma unroll
      for (int h = 0; h < 2; ++h) {
        uint32_t b0, b1, b2, b3;
        ldsm_x4_t(b0, b1, b2, b3, wa + h * 2560 + ks * 1280 + np * 32);
        mma_bf16(p[h][2 * np], kq[O + 8 * h + 4 * ks], kq[O + 8 * h + 4 * ks + 1], kq[O + 8 * h + 4 * ks + 2], kq[O + 8 * h + 4 * ks + 3], b0, b1);
        mma_bf16(p[h][2 * np + 1], kq[O + 8 * h + 4 * ks], kq[O + 8 * h + 4 * ks + 1], kq[O + 8 * h + 4 * ks + 2], kq[O + 8 * h + 4 * ks + 3], b2, b3);
      }
}
__device__ __forceinline__ void phi_exp(uint32_t (&raw)[4][4], const float (&p)[4][4], float sc0, float sc1) {
#pragma unroll
  for (int i = 0; i < 4; ++i) {
    const float e0 = ex2(p[i][0] * sc0), e1 = ex2(p[i][1] * sc0), e2 = ex2(p[i][2] * sc1), e3 = ex2(p[i][3] * sc1);
    const float m0 = e0 * e1, m1 = e2 * e3, rr = rcp(m0 * m1), r0 = rr * m1, r1 = rr * m0;
    raw[i >> 1][(i & 1) * 2] = pack_bf16(e0, e1);
    raw[i >> 1][(i & 1) * 2 + 1] = pack_bf16(e2, e3);
    raw[2 + (i >> 1)][(i & 1) * 2] = pack_bf16(e1 * r0, e0 * r0);
    raw[2 + (i >> 1)][(i & 1) * 2 + 1] = pack_bf16(e3 * r1, e2 * r1);
  }
}
template <int O>
__device__ __forceinline__ void phi_norm(uint32_t (&ph)[2][4][4], const uint32_t (&raw)[2][4][4], const uint32_t (&kq)[64], uint32_t wa,
                                         float sc0, float sc1, float mul0, float mul1) {
  bool bad = false;
#pragma unroll
  for (int h = 0; h < 2; ++h)
#pragma unroll
    for (int sg = 0; sg < 2; ++sg) {
      float ss[4] = {0.f, 0.f, 0.f, 0.f};
#pragma unroll
      for (int ks = 0; ks < 2; ++ks)
        mma_bf16(ss, raw[h][2 * sg + ks][0], raw[h][2 * sg + ks][1], raw[h][2 * sg + ks][2], raw[h][2 * sg + ks][3], 0x3F803F80u, 0x3F803F80u);
      bad = bad || !(ss[0] < PHI_MAX) || !(ss[2] < PHI_MAX);
      const uint32_t iv = pack_bf16(rcp(ss[0]) * mul0, rcp(ss[2]) * mul1);
#pragma unroll
      for (int ks = 0; ks < 2; ++ks)
#pragma unroll
        for (int j = 0; j < 4; ++j) ph[h][2 * sg + ks][j] = mul_bf16x2(raw[h][2 * sg + ks][j], iv, j & 1);
    }
  if (__builtin_expect(__any_sync(0xffffffffu, bad), 0)) {
#pragma unroll 1
    for (int it = 0; it < 4; ++it) {
      float q[4][4];
#pragma unroll
      for (int i = 0; i < 4; ++i) { q[i][0] = q[i][1] = q[i][2] = q[i][3] = 0.f; }
#pragma unroll
      for (int ks = 0; ks < 2; ++ks) {
        uint32_t a[4];
#pragma unroll
        for (int j = 0; j < 4; ++j) a[j] = (it & 2) ? kq[O + 8 + 4 * ks + j] : kq[O + 4 * ks + j];
#pragma unroll
        for (int np = 0; np < 2; ++np) {
          uint32_t b0, b1, b2, b3;
          ldsm_x4_t(b0, b1, b2, b3, wa + (it >> 1) * 2560 + ks * 1280 + np * 32);
          mma_bf16(q[2 * np], a[0], a[1], a[2], a[3], b0, b1);
          mma_bf16(q[2 * np + 1], a[0], a[1], a[2], a[3], b2, b3);
        }
      }
      float iv[2];
#pragma unroll
      for (int r = 0; r < 2; ++r) {
        const float sc = (it & 1) ? -(r ? sc1 : sc0) : (r ? sc1 : sc0);
        float mx = -INFINITY, sm = 0.f;
#pragma unroll
        for (int i = 0; i < 8; ++i) { float& v = q[i >> 1][2 * r + (i & 1)]; v *= sc; mx = fmaxf(mx, v); }
        mx = fmaxf(mx, __shfl_xor_sync(0xffffffffu, mx, 1));
        mx = fmaxf(mx, __shfl_xor_sync(0xffffffffu, mx, 2));
#pragma unroll
        for (int i = 0; i < 8; ++i) { float& v = q[i >> 1][2 * r + (i & 1)]; v = ex2(v - mx); sm += v; }
        sm += __shfl_xor_sync(0xffffffffu, sm, 1);
        sm += __shfl_xor_sync(0xffffffffu, sm, 2);
        iv[r] = rcp(sm) * (r ? mul1 : mul0);
      }
#pragma unroll
      for (int i = 0; i < 24; ++i) ph[i >> 4][(i >> 2) & 3][i & 3] = ph[(i + 8) >> 4][((i + 8) >> 2) & 3][i & 3];
#pragma unroll
      for (int i = 0; i < 4; ++i) {
        ph[1][2 + (i >> 1)][(i & 1) * 2] = pack_bf16(q[i][0] * iv[0], q[i][1] * iv[0]);
        ph[1][2 + (i >> 1)][(i & 1) * 2 + 1] = pack_bf16(q[i][2] * iv[1], q[i][3] * iv[1]);
      }
    }
  }
}

__device__ __forceinline__ void stats_out(float s0, float s1, float q0, float q1, float2* dst, int t) {
  const bool od = t & 1;
  float sa = od ? s1 : s0, qa = od ? q1 : q0;
  sa += __shfl_xor_sync(0xffffffffu, od ? s0 : s1, 1);
  qa += __shfl_xor_sync(0xffffffffu, od ? q0 : q1, 1);
  sa += __shfl_xor_sync(0xffffffffu, sa, 2);
  qa += __shfl_xor_sync(0xffffffffu, qa, 2);
  if (t < 2) red_add2(&dst[t * 8].x, sa, qa);
}

__device__ __forceinline__ void consumer(const Ctx& c) {
  const int g = c.g, m0 = c.rb * 128;
  float acc[192];
#define X_HALF(hf, TG) \
      _Pragma("unroll") for (int jp = 4 * (hf); jp < 4 * (hf) + 4; ++jp) \
        stsm_tag(sb + (XS + (hf)) * SLOT + rowo + (X ^ ((jp & 3) << 5)), \
                 pack_bf16(acc[128 + 8 * jp], acc[129 + 8 * jp]), pack_bf16(acc[130 + 8 * jp], acc[131 + 8 * jp]), \
                 pack_bf16(acc[132 + 8 * jp], acc[133 + 8 * jp]), pack_bf16(acc[134 + 8 * jp], acc[135 + 8 * jp]), TG, jp & 3);
#pragma unroll
  for (int i = 128; i < 192; ++i) acc[i] = 0.f;
#pragma unroll 1
  for (int layer = 0;; ++layer) {
    {
      PHASE_CTX();
      const uint32_t wu = c.cu >> 2;
      const uint32_t dA0 = (((sb + wu * 8192) & 0x3FFFF) >> 4) | (1u << 16), dB0 = ((sb & 0x3FFFF) >> 4) | (512u << 16);
      {
        PROFX(0);
        mbar_wait(bar + B_FULLS, 0);
        PROFX(1);
        wgmma_fence();
        wgmma_n256_0(acc, D128(dA0 + XS * 1024), D128(dB0 + 2048));
#pragma unroll
        for (int k = 1; k < 4; ++k) wgmma_n256(acc, D128(dA0 + XS * 1024 + k * 2), D128(dB0 + 2048 + k * 128), 1);
        wgmma_commit();
        wgmma_wait<1>();
        float s0 = 0.f, s1 = 0.f, q0 = 0.f, q1 = 0.f;
        if (layer) {
          X_HALF(1, (Tag{0u, 0u, 0u}));
#pragma unroll
          for (int i = 128; i < 192; i += 4) {
            s0 += acc[i] + acc[i + 1]; s1 += acc[i + 2] + acc[i + 3];
            q0 = fmaf(acc[i], acc[i], fmaf(acc[i + 1], acc[i + 1], q0)); q1 = fmaf(acc[i + 2], acc[i + 2], fmaf(acc[i + 3], acc[i + 3], q1));
          }
        }
        asm volatile("" : "+f"(s0), "+f"(s1), "+f"(q0), "+f"(q1) :: "memory");
        wgmma_fence();
        wgmma_n128_0(acc, D128(dA0 + XS * 1024), D128(dB0 + 1024));
#pragma unroll
        for (int k = 1; k < 4; ++k) wgmma_n128(acc, D128(dA0 + XS * 1024 + k * 2), D128(dB0 + 1024 + k * 128), 1);
        wgmma_commit();
        if (layer) {
          PHASE_CTX();
          fence_async_smem();
          nbar_dyn(3 + wu, 128);
          stats_out(s0, s1, q0, q1, g_stats + layer * S_ + m0 + wrow0 + gq, t);
          PROFT(tid_ == 128, layer * 16 + 8);
        }
      }
      uint32_t s = 1, u = 0, sp = 0;
      const int ix = layer ? 99 : 2 * min(g, NCOM) + 1;
#pragma unroll 1
      for (int i = 1; i < 14; ++i) {
        mbar_wait(bar + B_FULLS + s * 8, (u + (s ? layer : 0)) & 1);
        if (layer && (unsigned)(i - 2) < 7u) {
          PHASE_CTX();
          tile_check(sb + ((QA >> (4 * s)) & 15) * SLOT, g_x + (size_t)m0 * D_ + ((2 * g + 2 * i - 2) & 15) * 64, wrow0, lane, lds_vol(sb + SM_EPOCH) + layer);
        }
        const uint32_t da = dA0 + ((QA >> (4 * s)) & 15) * 1024, dk = dB0 + ((QK >> (4 * s)) & 15) * 1024,
                       dq = dB0 + ((QQ >> (4 * s)) & 15) * 1024;
        wgmma_fence();
#pragma unroll
        for (int k = 0; k < 4; ++k) {
          wgmma_n256(acc, D128(da + k * 2), D128(dk + k * 128), 1);
          wgmma_n128(acc, D128(da + k * 2), D128(dq + k * 128), 1);
          if (k == 0) {
            wgmma_commit();
            wgmma_wait<1>();
            if (elected && (unsigned)(i - ix) >= 2u) release2(bar + B_EMPTYS + sp * 8);
          }
        }
        wgmma_commit();
        if ((unsigned)(i - ix) < 2u) {
          PHASE_CTX();
          {
            float s0 = 0.f, s1 = 0.f, q0 = 0.f, q1 = 0.f;
            const uint32_t xa = sb + ((QA >> (4 * sp)) & 15) * SLOT + rowo;
#pragma unroll
            for (int jp = 0; jp < 4; ++jp) {
              uint32_t x0, x1, x2, x3;
              ldsm_x4(x0, x1, x2, x3, xa + (X ^ (jp << 5)));
              s0 += (bf_lo(x0) + bf_hi(x0)) + (bf_lo(x2) + bf_hi(x2));
              s1 += (bf_lo(x1) + bf_hi(x1)) + (bf_lo(x3) + bf_hi(x3));
              q0 = fmaf(bf_lo(x0), bf_lo(x0), fmaf(bf_hi(x0), bf_hi(x0), fmaf(bf_lo(x2), bf_lo(x2), fmaf(bf_hi(x2), bf_hi(x2), q0))));
              q1 = fmaf(bf_lo(x1), bf_lo(x1), fmaf(bf_hi(x1), bf_hi(x1), fmaf(bf_lo(x3), bf_lo(x3), fmaf(bf_hi(x3), bf_hi(x3), q1))));
            }
            stats_out(s0, s1, q0, q1, g_stats + m0 + wrow0 + gq, t);
          }
          __syncwarp();
          if (lane == 0 && i != ix) mbar_arrive(bar + B_XDONE);
          nbar_dyn(3 + wu, 128);
          if (elected) release2(bar + B_EMPTYS + sp * 8);
        }
        if (i == 1 && layer) {
          PHASE_CTX();
          slab_out_half(sb + (XS + 1) * SLOT, g_x + (size_t)m0 * D_ + g * 128 + 64, wrow0, lane);
          __syncwarp();
          if (lane == 0) mbar_arrive(bar + B_XDONE);
          nbar_dyn(3 + wu, 128);
        }
        sp = s;
        if (++s == 3) { s = 0; ++u; }
      }
      {
        const uint64_t dap = make_desc_ns(sb + SM_AP + wu * 1024, 0, 128), dbp = make_desc_ns(sb + SM_BP + (layer & 1) * 6144, 0, 128);
        if (wu == 0) {
          wgmma_wait<0>();
          if (elected) mbar_arrive(bar + B_R0);
          nbar<6, 256>();
        }
        if (layer < 2) mbar_wait(bar + (layer ? B_CS2 : B_CS), 0);
        mbar_wait(bar + B_STAT, layer & 1);
        mbar_wait(bar + B_FULLS + 16, layer & 1);
        wgmma_fence();
        wgmma_n256_k(acc, dap, dbp, 1);
#pragma unroll
        for (int k = 0; k < 4; ++k) wgmma_n256(acc, D128(dA0 + (QA >> 8) * 1024 + k * 2), D128(dB0 + (QK >> 8) * 1024 + k * 128), 1);
        mbar_wait(bar + B_FULLS, 1);
        PROFT(tid_ == 128, layer * 16 + 9);
        wgmma_fence();
#pragma unroll
        for (int k = 0; k < 4; ++k) wgmma_n256(acc, D128(dA0 + (QA & 15) * 1024 + k * 2), D128(dB0 + (QK & 15) * 1024 + k * 128), 1);
        wgmma_commit();
        if (wu) nbar<6, 256>();
#define Q_TAIL() \
        wgmma_n128_k(acc, dap, dbp + 256, 1); \
        _Pragma("unroll") for (int k = 0; k < 4; ++k) wgmma_n128(acc, D128(dA0 + (QA >> 8) * 1024 + k * 2), D128(dB0 + (QQ >> 8) * 1024 + k * 128), 1); \
        _Pragma("unroll") for (int k = 0; k < 4; ++k) wgmma_n128(acc, D128(dA0 + (QA & 15) * 1024 + k * 2), D128(dB0 + (QQ & 15) * 1024 + k * 128), 1);
        Q_TAIL();
        wgmma_commit();
        wgmma_wait<1>();
#pragma unroll
        for (int i = 0; i < 128; ++i) asm volatile("" : "+f"(acc[i]) :: "memory");
      }
    }
    uint32_t xo[32];
    uint32_t oq[8][4];
    {
      PHASE_CTX();
      PROFT(tid_ == 128, layer * 16 + 1);
      const bool isB = layer & 1;
      const int cu = c.cu;
      if (cu >= 4) asm volatile("bar.arrive 7, 256;" ::: "memory");
      if (elected && cu == 4) mbar_arrive(bar + B_R0);
      uint32_t kq[64];
      const uint32_t rowq = rowo & 8191;
      const float rs0 = lds_f(sb + SM_RS + (16 + wrow0 + gq) * 4), rs1 = lds_f(sb + SM_RS + (24 + wrow0 + gq) * 4);
#define Q_DONE() \
      wgmma_wait<0>(); \
      if (lane == 0) release2(bar + B_E0); \
      _Pragma("unroll") for (int i = 128; i < 192; ++i) asm volatile("" : "+f"(acc[i]) :: "memory"); \
      _Pragma("unroll") for (int i = 0; i < 32; ++i) kq[32 + i] = pack_bf16(acc[128 + 2 * i], acc[129 + 2 * i]);
      if (isB) {
        if (cu == 0) asm volatile("bar.arrive 10, 64;" ::: "memory");
        if (elected) release2(bar + B_E1);
        const int e = gq & 1;
        const bool sel = t > (gq >> 1);
        const uint32_t rja = sb + SM_RS + (wrow0 + 2 * t + e) * 4;
        const float rjA0 = lds_f(rja + 32), rjA1 = lds_f(rja + 64), rjB0 = lds_f(rja + (sel ? 0 : 64)), rjB1 = lds_f(rja + (sel ? 32 : 96));
        uint32_t vv[32];
#pragma unroll
        for (int i = 0; i < 16; ++i) { kq[i] = pack_bf16(acc[2 * i], acc[2 * i + 1]); vv[i] = pack_bf16(acc[64 + 2 * i], acc[65 + 2 * i]); }
        const uint32_t rB = sb + 4 * SLOT + wg * 4 * KVT + rowq;
        auto dump = [&](int hp) {
          const uint32_t kb = rB + 2048 + (hp ^ wg) * 2 * KVT;
#pragma unroll
          for (int jp = 0; jp < 4; ++jp) {
            stsm_x4(kb + (X ^ (jp << 5)), kq[16 * hp + 4 * jp], kq[16 * hp + 4 * jp + 1], kq[16 * hp + 4 * jp + 2], kq[16 * hp + 4 * jp + 3]);
            stsm_x4(kb + KVT + (X ^ (jp << 5)), vv[16 * hp + 4 * jp], vv[16 * hp + 4 * jp + 1], vv[16 * hp + 4 * jp + 2], vv[16 * hp + 4 * jp + 3]);
          }
          if (cu == 3) {
            const uint32_t kd = rB + 2048 + 32768 + (1 - hp) * 2 * KVT;
#pragma unroll
            for (int jp = 0; jp < 4; ++jp) {
              stsm_x4(kd + (X ^ (jp << 5)), kq[16 * hp + 4 * jp], kq[16 * hp + 4 * jp + 1], kq[16 * hp + 4 * jp + 2], kq[16 * hp + 4 * jp + 3]);
              stsm_x4(kd + KVT + (X ^ (jp << 5)), vv[16 * hp + 4 * jp], vv[16 * hp + 4 * jp + 1], vv[16 * hp + 4 * jp + 2], vv[16 * hp + 4 * jp + 3]);
            }
            if (hp) asm volatile("bar.arrive 15, 64;" ::: "memory"); else asm volatile("bar.arrive 9, 64;" ::: "memory");
          }
          asm volatile("bar.arrive %0, 224;" :: "r"(hp ? 13 + (cu >> 2) : 8 + (cu & 4)) : "memory");
        };
        uint4* const hbuf = g_halo + ((c.rb * 8 + g) * 2 + (layer >> 1)) * 512 + lane;
        if (cu < 4) {
          nbar<7, 256>();
          dump(0);
        }
#pragma unroll
        for (int i = 16; i < 32; ++i) { kq[i] = pack_bf16(acc[2 * i], acc[2 * i + 1]); vv[i] = pack_bf16(acc[64 + 2 * i], acc[65 + 2 * i]); }
        if (cu >= 4) {
          if (cu == 7) {
#pragma unroll
            for (int jp = 0; jp < 8; ++jp) {
              st_relaxed4(hbuf + jp * 32, ~kq[4 * jp], ~kq[4 * jp + 1], ~kq[4 * jp + 2], ~kq[4 * jp + 3]);
              st_relaxed4(hbuf + 256 + jp * 32, ~vv[4 * jp], ~vv[4 * jp + 1], ~vv[4 * jp + 2], ~vv[4 * jp + 3]);
            }
          }
          dump(0);
          dump(1);
        }
        PROFT(tid_ == 128, layer * 16 + 2);
        constexpr float SC = 0.17677669529663687f * L2E;
        const float fA0 = rjA0 * rs0 * SC, fB0 = rjB0 * rs0 * SC, fA1 = rjA1 * rs1 * SC, fB1 = rjB1 * rs1 * SC;
        const float bA0 = (m0 + wrow0) ? 0.f : -1e30f, bB = sel ? bA0 : 0.f;
        const uint32_t pA_ = e ? 0x1044u : 0x4410u, pB_ = e ? 0x3244u : 0x4432u, pLo = sel ? pB_ : 0x4444u, pHi = sel ? 0x4444u : pB_;
        const uint32_t KX = ((lane >> 3) ^ (lane & 7)) << 4;
        Q_DONE();
        if (cu == 0) {
          nbar<11, 64>();
        } else if (cu == 4) {
          uint4 hv[16];
          if (c.rb > 0) {
            uint32_t n = 0;
#pragma unroll 1
            while (true) {
              uint32_t mn = 0xFFFFFFFFu;
#pragma unroll
              for (int i = 0; i < 16; ++i) hv[i] = ld_relaxed4(hbuf - 16 * 512 + i * 32);
#pragma unroll
              for (int i = 0; i < 16; ++i) mn = __vimin3_u32(__vimin3_u32(mn, hv[i].x, hv[i].y), hv[i].z, hv[i].w);
              if (__all_sync(0xffffffffu, mn != 0u)) break;
              if (++n > (1u << 20)) { g_err = 4u; break; }
            }
          } else {
#pragma unroll
            for (int i = 0; i < 16; ++i) hv[i] = make_uint4(~0u, ~0u, ~0u, ~0u);
          }
          nbar<10, 64>();
#pragma unroll
          for (int i = 0; i < 16; ++i)
            stsm_x4(rB - 4 * KVT + (((i >> 2) & 1) * 2 + (i >> 3)) * KVT + (X ^ ((i & 3) << 5)), ~hv[i].x, ~hv[i].y, ~hv[i].z, ~hv[i].w);
          asm volatile("bar.arrive 11, 64;" ::: "memory");
          nbar<9, 64>();
        } else {
          nbar_dyn(8 + (cu & 4), 224);
        }
        PROFT(tid_ == 128, layer * 16 + 5);
        PROFT(lane == 0 && layer == PL, 136 + cw);
        auto attend = [&](int hp) {
          const uint32_t qad = sb + (XS + 1 - hp) * SLOT + rowo, kt = rB + 2 * (hp ^ wg) * KVT - (lane & 8) * 128, vt = rB + (2 * (hp ^ wg) + 1) * KVT;
          __syncwarp();
          uint32_t kb[2][2][4], vb[2][2][2][4];
#pragma unroll
          for (int h = 0; h < 2; ++h)
#pragma unroll
            for (int nt = 0; nt < 2; ++nt) ldsm_x4(kb[h][nt][0], kb[h][nt][1], kb[h][nt][2], kb[h][nt][3], kt + nt * 1024 + (KX ^ (h << 6)));
#pragma unroll
          for (int ks = 0; ks < 2; ++ks)
#pragma unroll
            for (int np = 0; np < 2; ++np)
#pragma unroll
              for (int h = 0; h < 2; ++h)
                ldsm_x4_t(vb[h][ks][np][0], vb[h][ks][np][1], vb[h][ks][np][2], vb[h][ks][np][3], vt + ks * 2048 + (X ^ (h << 6) ^ (np << 5)));
          if (hp == 0 && lane == 0) release2(bar + B_E3);
          float la[2][2], lb[2][2], mx[2][2], sm[2][2];
#pragma unroll
          for (int h = 0; h < 2; ++h) {
            const int qo = 32 + 16 * hp + 8 * h, ko = 16 * hp + 8 * h;
            float sc[4][4];
#pragma unroll
            for (int nt = 0; nt < 4; ++nt) {
              sc[nt][0] = sc[nt][1] = sc[nt][2] = sc[nt][3] = 0.f;
#pragma unroll
              for (int ks = 0; ks < 2; ++ks)
                mma_bf16(sc[nt], kq[qo + 4 * ks], kq[qo + 4 * ks + 1], kq[qo + 4 * ks + 2], kq[qo + 4 * ks + 3],
                         nt < 2 ? kb[h][nt & 1][2 * ks] : kq[ko + 4 * ks + (nt & 1)], nt < 2 ? kb[h][nt & 1][2 * ks + 1] : kq[ko + 4 * ks + 2 + (nt & 1)]);
            }
            la[h][0] = fmaf(e ? sc[1][1] : sc[1][0], fA0, bA0);
            lb[h][0] = fmaf(sel ? (e ? sc[0][1] : sc[0][0]) : (e ? sc[2][1] : sc[2][0]), fB0, bB);
            la[h][1] = (e ? sc[2][3] : sc[2][2]) * fA1;
            lb[h][1] = fmaf(sel ? (e ? sc[1][3] : sc[1][2]) : (e ? sc[3][3] : sc[3][2]), fB1, bB);
            mx[h][0] = fmaxf(la[h][0], lb[h][0]); mx[h][1] = fmaxf(la[h][1], lb[h][1]);
          }
#pragma unroll
          for (int o = 1; o <= 2; o <<= 1)
#pragma unroll
            for (int h = 0; h < 2; ++h)
#pragma unroll
              for (int r = 0; r < 2; ++r) mx[h][r] = fmaxf(mx[h][r], __shfl_xor_sync(0xffffffffu, mx[h][r], o));
          float oa[2][4][4];
#pragma unroll
          for (int h = 0; h < 2; ++h) {
#pragma unroll
            for (int r = 0; r < 2; ++r) { la[h][r] = ex2(la[h][r] - mx[h][r]); lb[h][r] = ex2(lb[h][r] - mx[h][r]); sm[h][r] = la[h][r] + lb[h][r]; }
            const uint32_t p0 = pack_bf16(la[h][0] * rjA0, lb[h][0] * rjB0), p1 = pack_bf16(la[h][1] * rjA1, lb[h][1] * rjB1);
            const uint32_t a00 = __byte_perm(p0, 0u, pLo), a02 = __byte_perm(p0, 0u, pA_), a03 = __byte_perm(p1, 0u, pLo);
            const uint32_t a10 = __byte_perm(p0, 0u, pHi), a11 = __byte_perm(p1, 0u, pA_), a13 = __byte_perm(p1, 0u, pHi);
#pragma unroll
            for (int i = 0; i < 4; ++i) {
              oa[h][i][0] = oa[h][i][1] = oa[h][i][2] = oa[h][i][3] = 0.f;
              mma_bf16(oa[h][i], a00, 0u, a02, a03, vb[h][0][i >> 1][2 * (i & 1)], vb[h][0][i >> 1][2 * (i & 1) + 1]);
              mma_bf16(oa[h][i], a10, a11, 0u, a13, vb[h][1][i >> 1][2 * (i & 1)], vb[h][1][i >> 1][2 * (i & 1) + 1]);
            }
          }
#pragma unroll
          for (int o = 1; o <= 2; o <<= 1)
#pragma unroll
            for (int h = 0; h < 2; ++h)
#pragma unroll
              for (int r = 0; r < 2; ++r) sm[h][r] += __shfl_xor_sync(0xffffffffu, sm[h][r], o);
          mbar_wait(bar + (hp ? B_XOLD2 : B_XOLD), 1);
#pragma unroll
          for (int jp = 0; jp < 4; ++jp) ldsm_x4(xo[16 * hp + 4 * jp], xo[16 * hp + 4 * jp + 1], xo[16 * hp + 4 * jp + 2], xo[16 * hp + 4 * jp + 3], qad + (X ^ (jp << 5)));
#pragma unroll
          for (int h = 0; h < 2; ++h) {
            const float i0 = rcp(sm[h][0]), i1 = rcp(sm[h][1]);
#pragma unroll
            for (int np = 0; np < 2; ++np)
            {
              uint32_t (&o)[4] = oq[4 * hp + 2 * h + np];
              o[0] = pack_bf16(oa[h][2 * np][0] * i0, oa[h][2 * np][1] * i0); o[1] = pack_bf16(oa[h][2 * np][2] * i1, oa[h][2 * np][3] * i1);
              o[2] = pack_bf16(oa[h][2 * np + 1][0] * i0, oa[h][2 * np + 1][1] * i0); o[3] = pack_bf16(oa[h][2 * np + 1][2] * i1, oa[h][2 * np + 1][3] * i1);
              stsm_tag(qad + (X ^ (h << 6) ^ (np << 5)), o[0], o[1], o[2], o[3], make_tag(gq, t, 0u), 2 * h + np);
            }
          }
          __syncwarp();
          slab_out_half(sb + (XS + 1 - hp) * SLOT, g_o + (size_t)m0 * D_ + g * 128 + hp * 64, wrow0, lane);
          __syncwarp();
          if (lane == 0) mbar_arrive(bar + (hp ? B_ODONE : B_OH1));
          PROFT(lane == 0 && layer == PL && hp == 0, 128 + cw);
        };
        attend(0);
        if (cu < 4) dump(1);
        if (cu == 4) nbar<15, 64>();
        else if (cu != 0) nbar_dyn(13 + (cu >> 2), 224);
        attend(1);
      } else {
#pragma unroll
        for (int i = 0; i < 32; ++i) kq[i] = pack_bf16(acc[2 * i], acc[2 * i + 1]);
        if (cu < 4) nbar<7, 256>();
        {
          const uint32_t vb = sb + (5 + 3 * wg) * SLOT + (rowq >> 1) + ((lchk ^ ((lane & 7) >> 1)) << 4);
#pragma unroll
          for (int jp = 8; jp < 16; ++jp)
            stsm_x4((vb ^ ((jp & 1) << 5)) + ((jp >> 1) & 3) * 4096,
                    pack_bf16(acc[8 * jp], acc[8 * jp + 1]), pack_bf16(acc[8 * jp + 2], acc[8 * jp + 3]),
                    pack_bf16(acc[8 * jp + 4], acc[8 * jp + 5]), pack_bf16(acc[8 * jp + 6], acc[8 * jp + 7]));
        }
        PROFT(tid_ == 128, layer * 16 + 2);
        Q_DONE();
        const uint32_t pA = sb + (3 + 3 * wg) * SLOT + (rowo & 8191);
        float sc0 = rs0 * L2E, sc1 = rs1 * L2E;
        const uint32_t wa0 = sb + SM_WPHI + lrow * 80 + lchk * 16;
        const uint32_t wu = c.cu >> 2, par = (layer >> 1) & 1;
        float p[2][4][4];
        uint32_t raw[2][4][4], ph[2][4][4];
        float kva[20], oa[2][20];
        auto kv_start = [&](int hp) {
#pragma unroll
          for (int h = 0; h < 2; ++h)
#pragma unroll
            for (int cp = 0; cp < 4; ++cp)
              stsm_x4(pA + hp * 16384 + h * 8192 + (X ^ (cp << 5)), ph[h][cp][0], ph[h][cp][1], ph[h][cp][2], ph[h][cp][3]);
          PROFT(tid_ == 128, layer * 16 + 11);
          fence_async_smem();
          nbar<1, 256>();
          const uint32_t hu = 2 * hp + wu;
          const uint32_t dP = (((sb + 3 * SLOT + hu * 8192) & 0x3FFFF) >> 4) | (512u << 16);
          const uint32_t dV = (((sb + 5 * SLOT + hu * 4096) & 0x3FFFF) >> 4) | (((SM_SD - 5 * SLOT - hu * 4096) >> 4) << 16);
          wgmma_fence();
#pragma unroll
          for (int ks = 0; ks < 8; ++ks)
            wgmma_n40_tt(kva, desc64(dP + (ks >> 2) * 3072 + (ks & 3) * 128, 0x40000040u),
                         desc64(dV + (ks >> 2) * (3072u - (2816u << 16)) + (ks & 3) * 64, 0x80000020u), ks != 0);
          wgmma_commit();
        };
        auto kv_end = [&](int hp) {
          wgmma_wait<0>();
#pragma unroll
          for (int i = 0; i < 20; ++i) asm volatile("" : "+f"(kva[i]) :: "memory");
          nbar_dyn(3 + wu, 128);
          PROFT(tid_ == 128, layer * 16 + 12);
          const bool od = lane & 1;
#pragma unroll
          for (int i = 0; i < 4; ++i)
            sts128(sb + (3 + hp) * SLOT + (cw * 128 + i * 32 + lane) * 16,
                   make_uint4(__float_as_uint(kva[4 * i]), __float_as_uint(kva[4 * i + 1]), __float_as_uint(kva[4 * i + 2]),
                              __float_as_uint(od == (i >= 2) ? 1.f : kva[4 * i + 3])));
          sts128(sb + (6 + hp) * SLOT + wg * 8192 + (wq * 32 + lane) * 16,
                 make_uint4(__float_as_uint(od ? kva[11] : kva[3]), __float_as_uint(od ? kva[15] : kva[7]), __float_as_uint(od ? kva[18] : kva[16]), __float_as_uint(1.f)));
          fence_async_smem();
          __syncwarp();
          if (lane == 0) mbar_arrive(bar + B_KVDONE - hp * 32);
          PROFT(tid_ == 128, layer * 16 + 3);
        };
        const uint4* const kvg = g_kv + (g * 2 + (layer >> 1)) * 2560 + cw * 128 + lane;
        uint4 u[5];
        auto kv_load = [&](int hp) {
#pragma unroll
          for (int i = 0; i < 4; ++i) u[i] = ld_relaxed4(kvg + hp * 1280 + i * 32);
          u[4] = ld_relaxed4(kvg + hp * 1280 + 1024 - cw * 96);
        };
        auto o_start = [&](int hp, const uint32_t (&pq)[2][4][4]) {
          PROFT(tid_ == 128 && hp == 0, layer * 16 + 10);
          if (hp == 0) mbar_wait(bar + B_KVDONE - 32, par);
          const bool od = lane & 1;
          uint32_t n = 0;
#pragma unroll 1
          while (!__all_sync(0xffffffffu, (od ? u[2].w : u[0].w) == 0x41800000u && (od ? u[3].w : u[1].w) == 0x41800000u && u[4].w == 0x41800000u)) {
#pragma unroll 1
            while (__any_sync(0xffffffffu, u[4].w < KVTH) && ++n < (1u << 20)) u[4].w = ld_relaxed(&kvg[hp * 1280 + 1024 - cw * 96].w);
            if (++n > (1u << 20)) { g_err = 6u; break; }
            kv_load(hp);
          }
          PROFT(tid_ == 128 && hp == 0, layer * 16 + 5);
          if (!od) { u[0].w = u[4].x; u[1].w = u[4].y; } else { u[2].w = u[4].x; u[3].w = u[4].y; }
#pragma unroll
          for (int i = 0; i < 4; i += 2)
            stsm_x4(sb + (5 + 3 * hp) * SLOT + rowo + (X ^ ((i & 2) << 4)),
                    pack_bf16(__uint_as_float(u[i].x), __uint_as_float(u[i].y)), pack_bf16(__uint_as_float(u[i].z), __uint_as_float(u[i].w)),
                    pack_bf16(__uint_as_float(u[i + 1].x), __uint_as_float(u[i + 1].y)), pack_bf16(__uint_as_float(u[i + 1].z), __uint_as_float(u[i + 1].w)));
          const uint32_t z2 = pack_bf16(__uint_as_float(u[4].z), __uint_as_float(u[4].z));
          if (t < 2) sts128(sb + (5 + 3 * hp) * SLOT + (wrow0 + gq + 8 * t) * 128 + ((4 ^ gq) << 4), make_uint4(z2, z2, z2, z2));
          fence_async_smem();
          nbar<1, 256>();
          PROFT(tid_ == 128 && hp == 1, layer * 16 + 4);
          const uint32_t dK = (((sb + (5 + 3 * hp) * SLOT) & 0x3FFFF) >> 4) | (512u << 16);
          wgmma_fence();
#pragma unroll
          for (int ks = 0; ks < 4; ++ks) {
#pragma unroll
            for (int hh = 0; hh < 2; ++hh) wgmma_n40_rs(oa[hh], pq[hh][ks], D128(dK + hh * 512 + ks * 128), ks != 0);
          }
          wgmma_commit();
        };
        auto o_end = [&](int hp) {
          wgmma_wait<0>();
#pragma unroll
          for (int i = 0; i < 20; ++i) asm volatile("" : "+f"(oa[0][i]), "+f"(oa[1][i]) :: "memory");
#pragma unroll
          for (int hh = 0; hh < 2; ++hh) {
            const float i0 = rcp(oa[hh][16] + 1e-6f), i1 = rcp(oa[hh][18] + 1e-6f);
            const uint32_t qad = sb + (3 + hp) * SLOT + rowo, hx = hh << 6;
#pragma unroll
            for (int np = 0; np < 2; ++np)
            {
              uint32_t (&o)[4] = oq[4 * hp + 2 * hh + np];
              o[0] = pack_bf16(oa[hh][8 * np] * i0, oa[hh][8 * np + 1] * i0); o[1] = pack_bf16(oa[hh][8 * np + 2] * i1, oa[hh][8 * np + 3] * i1);
              o[2] = pack_bf16(oa[hh][8 * np + 4] * i0, oa[hh][8 * np + 5] * i0); o[3] = pack_bf16(oa[hh][8 * np + 6] * i1, oa[hh][8 * np + 7] * i1);
              stsm_tag(qad + (X ^ hx ^ (np << 5)), o[0], o[1], o[2], o[3], make_tag(gq, t, 1u), 2 * hh + np);
            }
          }
          __syncwarp();
          slab_out_half(sb + (3 + hp) * SLOT, g_o + (size_t)m0 * D_ + g * 128 + hp * 64, wrow0, lane);
          __syncwarp();
          if (lane == 0) mbar_arrive(bar + (hp ? B_ODONE : B_OH1));
        };
#define XO_LOAD() \
        mbar_wait(bar + B_XOLD, 0); \
        mbar_wait(bar + B_XOLD2, 0); \
        _Pragma("unroll") for (int jp = 0; jp < 8; ++jp) \
          ldsm_x4(xo[4 * jp], xo[4 * jp + 1], xo[4 * jp + 2], xo[4 * jp + 3], sb + (XS + 1 - (jp >> 2)) * SLOT + rowo + (X ^ ((jp & 3) << 5)));
#define SC_RELOAD() \
        sc0 = __uint_as_float(lds_vol(sb + SM_RS + (16 + wrow0 + gq) * 4)) * L2E; sc1 = __uint_as_float(lds_vol(sb + SM_RS + (24 + wrow0 + gq) * 4)) * L2E;
        __syncwarp();
        phi_proj<0>(p, kq, wa0);
        phi_exp(raw[0], p[0], sc0, sc1);
        phi_exp(raw[1], p[1], sc0, sc1);
        phi_proj<16>(p, kq, wa0 + 5120);
        phi_norm<0>(ph, raw, kq, wa0, sc0, sc1, rs0, rs1);
        kv_start(0);
        phi_exp(raw[0], p[0], sc0, sc1);
        kv_end(0);
        SC_RELOAD();
        XO_LOAD();
        phi_exp(raw[1], p[1], sc0, sc1);
        phi_proj<32>(p, kq, wa0);
        phi_norm<16>(ph, raw, kq, wa0 + 5120, sc0, sc1, rs0, rs1);
        kv_start(1);
        if (lane == 0) release2(bar + B_E3);
        phi_exp(raw[0], p[0], sc0, sc1);
        kv_end(1);
        SC_RELOAD();
        kv_load(0);
        phi_exp(raw[1], p[1], sc0, sc1);
        phi_proj<48>(p, kq, wa0 + 5120);
        phi_norm<32>(ph, raw, kq, wa0, sc0, sc1, 1.f, 1.f);
        o_start(0, ph);
        phi_exp(raw[0], p[0], sc0, sc1);
        o_end(0);
        SC_RELOAD();
        kv_load(1);
        phi_exp(raw[1], p[1], sc0, sc1);
        phi_norm<48>(ph, raw, kq, wa0 + 5120, sc0, sc1, 1.f, 1.f);
        o_start(1, ph);
        o_end(1);
      }
      __syncwarp();
      PROFT(lane == 0 && layer == PL, 216 + cw);
      if (lane == 0) mbar_arrive(bar + B_EPI);
      PROFT(tid_ == 128, layer * 16 + 6);
    }
    {
      PHASE_CTX();
      const uint32_t wu = c.cu >> 2;
      const uint32_t dA0 = (((sb + wu * 8192) & 0x3FFFF) >> 4) | (1u << 16), dB0 = ((sb & 0x3FFFF) >> 4) | (512u << 16);
#pragma unroll
      for (int i = 0; i < 32; ++i) { acc[128 + 2 * i] = bf_lo(xo[i]); acc[129 + 2 * i] = bf_hi(xo[i]); }
      uint64_t ta = ((layer & 1) ? WO_A1 : WO_A0) >> 8, tw = (layer & 1) ? WO_B1 : WO_B0;
      mbar_wait(bar + B_FULLT, layer & 1);
      mbar_wait(bar + B_FULLT + 8, layer & 1);
      PROFT(tid_ == 128 && layer == PL, 160);
      wgmma_fence();
#pragma unroll
      for (int k = 0; k < 8; ++k) wgmma_n128_rs(acc, oq[k], D128(dB0 + ((uint32_t)(tw >> (k & 4)) & 15) * 1024 + (k & 3) * 128), 1);
      wgmma_commit();
      tw >>= 8;
      if (lane == 0) release2(bar + B_E2);
#pragma unroll 1
      for (int i = 2; i < 16; ++i) {
        mbar_wait(bar + B_FULLT + i * 8, layer & 1);
        PROFT(tid_ == 128 && layer == PL, 160 + i);
        tile_check(sb + ((uint32_t)ta & 15) * SLOT, g_o + (size_t)m0 * D_ + ((2 * g + (int)(WOORD >> (4 * i))) & 15) * 64, wrow0, lane, ~layer);
        const uint32_t da = dA0 + ((uint32_t)ta & 15) * 1024, db = dB0 + ((uint32_t)tw & 15) * 1024;
        ta >>= 4; tw >>= 4;
        if (i == 15 && wu) nbar<6, 256>();
        wgmma_fence();
#pragma unroll
        for (int k = 0; k < 4; ++k) wgmma_n128(acc, D128(da + k * 2), D128(db + k * 128), 1);
        wgmma_commit();
        if (i == 15 && !wu) asm volatile("bar.arrive 6, 256;" ::: "memory");
        wgmma_wait<1>();
        if (elected && i < 12) release2(bar + B_CONS + (i - 1) * 8);
        if (elected && (unsigned)(i - 13) < 2u && layer + 1 < NLAYERS) release2(bar + B_EMPTYS + (i - 13) * 8);
      }
      const bool last = layer == NLAYERS - 1;
      Tag xt = make_tag(gq, last ? 4 : t, lds_vol(sb + SM_EPOCH) + layer + 1);
      asm volatile("" : "+r"(xt.me), "+r"(xt.mo), "+r"(xt.tg) :: "memory");
      wgmma_wait<0>();
#pragma unroll
      for (int i = 128; i < 192; ++i) asm volatile("" : "+f"(acc[i]) :: "memory");
      if (elected && !last) release2(bar + B_EMPTYS + 16);
      PROFT(tid_ == 128, layer * 16 + 7);
      X_HALF(0, xt);
      if (last) {
        __syncwarp();
        slab_out_half(sb + XS * SLOT, c.out + (size_t)m0 * D_ + g * 128, wrow0, lane);
        X_HALF(1, (Tag{0u, 0u, 0u}));
        __syncwarp();
        slab_out_half(sb + (XS + 1) * SLOT, c.out + (size_t)m0 * D_ + g * 128 + 64, wrow0, lane);
        __syncwarp();
        if (lane == 0) mbar_arrive(bar + B_XDONE);
        PROFT(tid_ == 128, layer * 16 + 24);
        break;
      }
      __syncwarp();
      slab_out_half(sb + XS * SLOT, g_x + (size_t)m0 * D_ + g * 128, wrow0, lane, true);
      __syncwarp();
      if (lane == 0) mbar_arrive(bar + B_XH0);
      nbar_dyn(3 + wu, 128);
    }
  }
}

__device__ __forceinline__ void flag_fetch(uint32_t bar, uint32_t cp, const unsigned int* f) {
  asm volatile("{\n.reg .pred p;\nelect.sync _|p, 0xffffffff;\n@p mbarrier.expect_tx.relaxed.cta.shared::cta.b64 [%2], 64;\n"
               "@p cp.async.bulk.shared::cluster.global.mbarrier::complete_tx::bytes [%0], [%1], 64, [%2];\n}\n"
               ::"r"(cp), "l"(f), "r"(bar + 128) : "memory");
}
__device__ __forceinline__ void src_wait_async(uint32_t bar, uint32_t cp, const unsigned int* f, unsigned int target, int kb, uint32_t& ready, int lane) {
  uint32_t n = 0;
#pragma unroll 1
  while (true) {
    ready |= __ballot_sync(0xffffffffu, (int)(lds_vol(cp + (lane & 15) * 4) - target) >= 0);
    if ((ready >> kb) & 1) break;
    if (n > (1u << 20)) { g_err = 5u; break; }
    if ((n++ & PMOD) == 0) flag_fetch(bar, cp, f);
    __nanosleep(PSL);
  }
}

__device__ __forceinline__ int kblock0(int i, int g) {
  const int j = i >> 1, p = max(g, NCOM) + j - NCOM;
  return (j < NCOM ? j : p < 8 ? p : p - 8 + NCOM) * 2 + (i & 1);
}

__device__ __forceinline__ int wo_kblock(int m, int g) { return (2 * g + (int)((WOORD >> (4 * m)) & 15)) & 15; }

__global__ void __cluster_dims__(2, 1, 1) __launch_bounds__(384, 1)
mega_kernel(const __grid_constant__ CUtensorMap tm_x0, const __grid_constant__ CUtensorMap tm_x,
            const __grid_constant__ CUtensorMap tm_o,
            const __grid_constant__ CUtensorMap tm_wA, const __grid_constant__ CUtensorMap tm_wB,
            const __grid_constant__ CUtensorMap tm_woA, const __grid_constant__ CUtensorMap tm_woB,
                        const bf16* __restrict__ wB, const bf16* __restrict__ wphi, bf16* __restrict__ out) {
  extern __shared__ uint8_t smem_raw[];
  const uint32_t sb = (smem_u32(smem_raw) + 1023u) & ~1023u;
  const uint32_t bar = sb + SM_BAR;
  const int warp = __shfl_sync(0xffffffffu, threadIdx.x >> 5, 0), lane = threadIdx.x & 31;
  if (blockIdx.x >= 128 || gridDim.x == NX) {
    const int xb = blockIdx.x & (NX - 1);
    const int ch = threadIdx.x % 96, rg = threadIdx.x / 96, gg = xb * 2 + ch / 48, sec = (ch % 48) >> 4;
    const uint4* src = reinterpret_cast<const uint4*>(wB + (size_t)rg * 3072 + (sec == 2 ? 0 : 1024 + sec * 1024) + gg * 128 + (ch & 15) * 8);
    float s[8] = {0.f, 0.f, 0.f, 0.f, 0.f, 0.f, 0.f, 0.f};
#pragma unroll 1
    for (int r0 = 0; r0 < 256; r0 += 32) {
      uint4 v[32];
#pragma unroll
      for (int r = 0; r < 32; ++r) v[r] = __ldg(src + (size_t)(r0 + r) * 1536);
#pragma unroll
      for (int r = 0; r < 32; ++r) {
        s[0] += bf_lo(v[r].x); s[1] += bf_hi(v[r].x); s[2] += bf_lo(v[r].y); s[3] += bf_hi(v[r].y);
        s[4] += bf_lo(v[r].z); s[5] += bf_hi(v[r].z); s[6] += bf_lo(v[r].w); s[7] += bf_hi(v[r].w);
      }
    }
    float* cd = g_cs + (ld_relaxed(&g_epoch) & 1) * 6144 + 3072 + xb * 768 + ch * 8;
    red_add4(cd, s[0], s[1], s[2], s[3]);
    red_add4(cd + 4, s[4], s[5], s[6], s[7]);
    nbar<1, 384>();
    if (threadIdx.x < 2) flag_add(&g_csflag[8 + xb * 2 + threadIdx.x].v);
    return;
  }
  const int bid = blockIdx.x;
  const int cr = bid & 1;
  const int g = bid >> 4;
  const int rb = bid & 15;
  const int m0 = rb * 128;

  if (warp < 4) {
    asm volatile("setmaxnreg.dec.sync.aligned.u32 40;");
    asm volatile("barrier.cluster.arrive.relaxed.aligned;" ::: "memory");
    const unsigned int epoch = warp ? ld_relaxed(&g_epoch) : 0u;
    if (warp) cluster_wait();
    unsigned int xbase = epoch * NLAYERS;
    auto wo_a = [&](int layer, int m1) {
      uint64_t ts = ((layer & 1) ? WO_A1 : WO_A0) >> (4 * m1), td = ((layer & 1) ? WO_DA1 : WO_DA0) >> (4 * m1), tk = WOORD >> (4 * m1);
      uint32_t ready = 0u;
#pragma unroll 1
      for (int m = m1; m < 16; ++m) {
        const int kb = (2 * g + (uint32_t)tk) & 15;
        uint32_t dst = sb + ((uint32_t)ts & 15) * SLOT, fb = bar + B_FULLT + m * 8, eb = bar + B_CONS + ((uint32_t)td & 15) * 8;
        int kc = kb * 64;
        ts >>= 4; td >>= 4; tk >>= 4;
        asm volatile("" : "+r"(dst), "+r"(fb), "+r"(eb), "+r"(kc));
        bool fr = false;
        if (!((ready >> kb) & 1)) {
          PROFT(m == 2 && lane == 0, 64 + layer * 16 + 2);
          if (EP && m > EP) src_wait_async(bar, bar + B_FLG, g_of + rb * 32, xbase + layer + 1, kb, ready, lane);
          else fr = src_wait_tma(g_of + rb * 32, xbase + layer + 1, 1u << kb, ready, lane, eb, layer & 1);
          fence_async_all();
        }
        if (m == 6) mbar_wait_u(bar + B_EPI, layer & 1);
        if (!fr) mbar_wait_u(eb, layer & 1);
        tma_2d_e(dst, &tm_o, kc, m0, fb);
        if (EP && m >= EP && (ready & 0xFFFFu) != 0xFFFFu) flag_fetch(bar, bar + B_FLG, g_of + rb * 32);
        PROFT(lane == 0 && layer == PL, 176 + m);
      }
    };
    auto wo_w = [&](int layer) {
      const CUtensorMap* tx = layer == 0 ? &tm_x0 : &tm_x;
      const CUtensorMap* two = (layer & 1) ? &tm_woB : &tm_woA;
      uint64_t ts = (layer & 1) ? WO_B1 : WO_B0, td = (layer & 1) ? WO_DB1 : WO_DB0, tk = WOORD;
      uint32_t pb = 0;
      fence_async_all();
      mbar_wait_u(bar + B_R0, layer & 1);
      expect_tx_e(bar + B_XOLD, 16384);
      tma_2d_e(sb + (XS + 1) * SLOT, tx, g * 128, m0, bar + B_XOLD);
#pragma unroll 1
      for (int m = 0; m < 16; ++m) {
        uint32_t dst = sb + ((uint32_t)ts & 15) * SLOT + cr * 8192, fb = bar + B_FULLT + m * 8, eb = bar + B_CONS + ((uint32_t)td & 15) * 8;
        int kc = ((2 * g + (uint32_t)tk) & 15) * 64;
        ts >>= 4; td >>= 4; tk >>= 4;
        asm volatile("" : "+r"(dst), "+r"(fb), "+r"(eb), "+r"(kc));
        if (eb < bar + B_E3 && pb >= bar + B_E3) mbar_wait_u(bar + B_E2, layer & 1);
        if (eb != pb) mbar_wait_u(eb, layer & 1);
        pb = eb;
        tma_2d_mc_e(dst, two, g * 128 + cr * 64, kc, fb);
        expect_tx_e(fb, m < 2 ? 16384 : 32768);
        PROFT(lane == 0 && layer == PL, 144 + m);
        if (m == ((layer & 1) ? 2 : 0)) {
          expect_tx_e(bar + B_XOLD2, 16384);
          tma_2d_e(sb + XS * SLOT, tx, g * 128 + 64, m0, bar + B_XOLD2);
        }
      }
    };
    if (warp == 0) {
      cluster_wait();
      PROFT(lane == 0, 125);
#pragma unroll 1
      for (int layer = 0; layer < NLAYERS; ++layer) {
        const CUtensorMap* tx = layer == 0 ? &tm_x0 : &tm_x;
        const CUtensorMap* tw = (layer & 1) ? &tm_wB : &tm_wA;
        uint32_t s = layer == 0, u = 0, ready = layer == 0 ? 0xFFFFu : 0u;
#pragma unroll 1
        for (int i = s; i < 16; ++i) {
          const int kb = layer == 0 ? kblock0(i, g) : wo_kblock(i, g), kc = kb * 64;
          const uint32_t fb = bar + B_FULLS + s * 8;
          const uint32_t kd = sb + (((QK >> (4 * s)) & 15) + cr) * SLOT, qd = sb + ((QQ >> (4 * s)) & 15) * SLOT + cr * 8192;
          const uint32_t need = 1u << kb;
          const bool ext = i >= 2 || layer == 0, early = ext && (ready & need) == need;
          mbar_wait_u(bar + B_EMPTYS + s * 8, (u + (s ? layer : 0) + 1) & 1);
          if (early) tma_2d_e(sb + ((QA >> (4 * s)) & 15) * SLOT, tx, kc, m0, fb);
          tma_2d_mc_e(kd, tw, 1024 + cr * 1024 + g * 128, kc, fb);
          tma_2d_mc_e(kd + 8192, tw, 1024 + cr * 1024 + g * 128 + 64, kc, fb);
          tma_2d_mc_e(qd, tw, g * 128 + cr * 64, kc, fb);
          expect_tx_e(fb, ext ? 65536 : 49152);
          PROFT(lane == 0 && layer == 0 && i == 1, 31);
          if (layer == 0 && g >= NCOM && i == XPF + (((g - NCOM) * XPM) >> 2)) {
            if (i <= 2) mbar_wait_u(bar + B_FULLS, 0);
            tma_pf_e(&tm_x0, g * 128, m0);
            tma_pf_e(&tm_x0, g * 128 + 64, m0);
          }
          if (layer < 2 && i >= PFS) {
            const int j = i - PFS;
            if (j < 2) tma_pf_e(layer ? &tm_woB : &tm_woA, g * 128 + j * 64, rb * 64);
            else if (j < 8 && layer == 0) tma_pf_e(&tm_wB, ((j >> 1) - 1) * 1024 + g * 128 + (j & 1) * 64, rb * 64);
          }
          if (ext && !early) {
            PROFT(i == 2 && lane == 0, 64 + layer * 16 + 0);
            src_wait_tma(g_xf + rb * 32, xbase + layer + 1, need, ready, lane, fb, 0);
            PROFT(i == 2 && lane == 0, 64 + layer * 16 + 1);
            fence_async_all();
            tma_2d_e(sb + ((QA >> (4 * s)) & 15) * SLOT, tx, kc, m0, fb);
          }
          if (++s == 3) { s = 0; ++u; }
        }
        if (layer == 0) xbase = ld_relaxed(&g_epoch) * NLAYERS;
        wo_a(layer, 2);
      }
    } else {
      if (warp >= 2) {
        const int h2 = threadIdx.x - 64;
        if (h2 < 16) sts_f(sb + SM_RS + h2 * 4, 0.f);
        if (h2 == 0) sts_f(sb + SM_EPOCH, __uint_as_float(epoch));
        if (h2 < 16) sts_f(bar + B_FLG + h2 * 4, __uint_as_float(xbase));
        mbar_wait_u(bar + B_FULLS, 0);
        colsum(&tm_wA, g_cs + (epoch & 1) * 6144, rb, g, warp - 2, 2, lane, warp == 2 ? sb + SM_SD : (sb + SM_BP + 1023u) & ~1023u, bar + B_CB + (warp - 2) * 8, 0);
#pragma unroll 1
        for (int i = h2; i < 320; i += 64) g_kv[(g * 16 + rb) * 320 + i] = make_uint4(0u, 0u, 0u, 0u);
        fence_async_all();
        nbar<5, 64>();
        if (h2 == 0) flag_add(&g_csflag[g].v);
        PROFT(h2 == 0, 242);
#pragma unroll 1
        for (int i = h2; i < 512; i += 256) {
          uint4 w[4];
#pragma unroll
          for (int j = 0; j < 4; ++j) w[j] = __ldg(reinterpret_cast<const uint4*>(wphi + (size_t)g * 4096) + i + j * 64);
#pragma unroll
          for (int j = 0; j < 4; ++j) sts128(sb + SM_WPHI + ((i >> 2) + j * 16) * 80 + (i & 3) * 16, w[j]);
        }
      }
      if (warp == 1) {
        if (lane >= 27) {
          const CUtensorMap* tm = lane == 27 ? &tm_o : lane == 28 ? &tm_wB : lane == 29 ? &tm_woA : lane == 30 ? &tm_woB : &tm_x;
          asm volatile("prefetch.tensormap [%0];" ::"l"(tm) : "memory");
        }
        __syncwarp();
        {
#pragma unroll 1
          for (int e = 0;; ++e) {
            if (e > 0 && e < NLAYERS) {
              mbar_wait_u(bar + B_XH0, (e - 1) & 1);
              flag_hint(g_xf + rb * 32 + 2 * g, xbase + e + 1);
            }
            mbar_wait_u(bar + B_XDONE, e & 1);
            PROFT(e < 4, 64 + e * 16 + 4);
            if (e == NLAYERS) {
              if (bid == 0) g_epoch = epoch + 1;
              break;
            }
            PROFT(e < 4, 64 + e * 16 + 5);
            flag_set(g_xf + rb * 32 + 2 * g + 1, xbase + e + 1);
            PROFT(e < 4, 64 + e * 16 + 7);
            if ((e & 1) == 0) {
#pragma unroll 1
              for (int hp = 0; hp < 2; ++hp) {
                uint4* kvl = g_kv + ((g * 2 + (e >> 1)) * 2 + hp) * 1280;
                mbar_wait_u(bar + B_KVDONE - hp * 32, (e >> 1) & 1);
                PROFT(e == PL, 243 + hp * 4);
                bulk_red_add_e(kvl + rb * 64, sb + (3 + hp) * SLOT + rb * 1024, 16384 - rb * 1024);
                if (rb) bulk_red_add_e(kvl, sb + (3 + hp) * SLOT, rb * 1024);
                bulk_red_add_e(kvl + 1024, sb + (6 + hp) * SLOT, 2048);
                bulk_red_add_e(kvl + 1152, sb + (6 + hp) * SLOT + 8192, 2048);
                bulk_commit();
                PROFT(e < 4, 64 + e * 16 + 6);
              }
              bulk_wait_read0();
              __syncwarp();
              if (lane < 2) release2(bar + B_E1);
              __syncwarp();
            }
            mbar_wait_u(bar + B_OH1, e & 1);
            PROFT(e == PL, 251);
            flag_hint(g_of + rb * 32 + 2 * g, xbase + e + 1);
            PROFT(e < 4, 64 + e * 16 + 9);
            mbar_wait_u(bar + B_ODONE, e & 1);
            PROFT(e < 4, 64 + e * 16 + 8);
            flag_hint(g_of + rb * 32 + 2 * g + 1, xbase + e + 1);
            PROFT(e < 4, 64 + e * 16 + 11);
          }
        }
      } else {
        const int h2 = threadIdx.x - 64;
        const float* cs = g_cs + (epoch & 1) * 6144;
#pragma unroll 1
        for (int layer = 0; layer < NLAYERS; ++layer) {
          if (warp == 2 && layer < 2) {
            if (lane == 0) flag_wait_t<128>(&g_csflag[layer * 8 + g].v, (epoch + 1) * (16u + layer));
            __syncwarp();
            float4 a[3];
#pragma unroll
            for (int i = 0; i < 3; ++i) a[i] = __ldcg(reinterpret_cast<const float4*>(cs + layer * 3072 + g * 384) + i * 32 + lane);
#pragma unroll 1
            for (int i = 0; i < 3; ++i) {
              const float av[4] = {a[0].x, a[0].y, a[0].z, a[0].w};
              a[0] = a[1]; a[1] = a[2];
#pragma unroll
              for (int j = 0; j < 4; ++j) {
                const float c1 = bf16r(av[j]), c2 = bf16r(av[j] - c1), c3 = (av[j] - c1) - c2;
                sts128(sb + SM_BP + layer * 6144 + ((i * 32 + lane) * 4 + j) * 16, make_uint4(pack_bf16(c1, c2), pack_bf16(c3, 0.f), 0u, 0u));
              }
            }
            fence_async_smem();
            __syncwarp();
            if (lane == 0) mbar_arrive(bar + (layer ? B_CS2 : B_CS));
            PROFT(lane == 0, 64 + layer * 16 + 12);
            if (layer == 0) {
              uint4* hz = g_halo + (rb * 8 + g) * 1024;
#pragma unroll 2
              for (int i = lane; i < 1024; i += 32) hz[i] = make_uint4(0u, 0u, 0u, 0u);
              if (lane < 12) reinterpret_cast<float4*>(g_cs + ((epoch & 1) ^ 1) * 6144 + bid * 48)[lane] = make_float4(0.f, 0.f, 0.f, 0.f);
              g_stats[(2 + (lane >> 4)) * S_ + m0 + g * 16 + (lane & 15)] = make_float2(0.f, 0.f);
              __syncwarp();
              if (lane == 0) flag_add(&g_csflag[8 + g].v);
            }
          }
          if (warp == 3) {
            const bool hal = (layer & 1) && rb > 0;
            {
              uint32_t rdy = 0u;
              src_wait<256>(g_xf + rb * 32, xbase + layer + 1, 0xAAAAu, rdy, lane);
              rdy = 0u;
              if (hal) src_wait<256>(g_xf + (rb - 1) * 32, xbase + layer + 1, 0xAAAAu, rdy, lane);
            }
            float2 u[5];
            const float2* sp = g_stats + layer * S_ + m0 + lane;
#pragma unroll
            for (int i = 0; i < 4; ++i) u[i] = __ldcg(sp + i * 32);
            u[4] = __ldcg(hal ? sp - 16 : sp);
            if (layer == 3) g_stats[(lane >> 4) * S_ + m0 + g * 16 + (lane & 15)] = make_float2(0.f, 0.f);
#pragma unroll
            for (int i = 0; i < 5; ++i) {
              const int r = i < 4 ? 16 + i * 32 + lane : lane;
              const float mean = u[i].x * (1.f / D_);
              const float var = fmaxf(fmaf(-u[i].x, mean, u[i].y) * (1.f / D_), 0.f);
              float sd;
              asm("sqrt.approx.f32 %0, %1;" : "=f"(sd) : "f"(bf16r(bf16r(var) + 1e-5f)));
              sd = bf16r(sd);
              if (i < 4 || hal) sts_f(sb + SM_RS + r * 4, rcp(sd));
              if (i < 4) {
                const float hm = -0.5f * bf16r(mean);
                const uint32_t s2 = pack_bf16(sd, sd);
                if (!(layer & 1)) sts128(sb + SM_SD + (r - 16) * 64 + ((r >> 1) & 3) * 16, make_uint4(s2, s2, s2, s2));
                sts128(sb + SM_AP + (r - 16) * 16, make_uint4(pack_bf16(hm, hm), pack_bf16(hm, 0.f), 0u, 0u));
              }
            }
            fence_async_smem();
            __syncwarp();
            if (lane == 0) mbar_arrive(bar + B_STAT);
            PROFT(lane == 0, 64 + layer * 16 + 14);
            wo_w(__shfl_sync(0xffffffffu, layer, 0));
          }
        }
      }
    }
    __syncwarp();
    asm volatile("barrier.cluster.arrive.relaxed.aligned;\nbarrier.cluster.wait.aligned;\n" ::: "memory");
  } else {
    if (warp == 5) {
      if (lane == 0) {
        mbar_init(bar + B_FULLS, 1);
        asm volatile("fence.mbarrier_init.release.cluster;" ::: "memory");
      }
      __syncwarp();
      expect_tx_e(bar + B_FULLS, 65536);
      tma_2d_e(sb + XS * SLOT, &tm_x0, 0, m0, bar + B_FULLS);
#pragma unroll
      for (int j = 0; j < 6; ++j)
        tma_2d_e(sb + (j < 4 ? j + 4 : j - 2) * 8192, &tm_wA, (j < 4 ? 1024 + (j >> 1) * 1024 : 0) + g * 128 + (j & 1) * 64, 0, bar + B_FULLS);
      PROFT(lane == 0, 241);
    }
    if (lane < 8 && warp != 5 && threadIdx.x != 128) {
      const int i = (warp - 4) * 8 + lane;
      mbar_init(bar + i * 8, i < 32 ? 1u << ((BAR_CNT >> (2 * i)) & 3) : i < 48 ? 1u : (i == 59 || i == 60 || i == 62) ? 16u : (i == 48 || i == 63) ? 8u : 4u);
      asm volatile("fence.mbarrier_init.release.cluster;" ::: "memory");
    }
    __syncwarp();
    asm volatile("barrier.cluster.arrive.relaxed.aligned;" ::: "memory");
    asm volatile("setmaxnreg.inc.sync.aligned.u32 232;");
    cluster_wait();
    PROFT(threadIdx.x == 128, 0);
    Ctx c; c.sb = sb; c.g = g; c.rb = rb; c.cu = warp - 4; c.out = out;
    consumer(c);
    asm volatile("bar.warp.sync 0xffffffff;\nbarrier.cluster.arrive.relaxed.aligned;\nbarrier.cluster.wait.aligned;\n" ::: "memory");
  }
}

typedef CUresult (*PFN_encodeTiled)(CUtensorMap*, CUtensorMapDataType, cuuint32_t, void*, const cuuint64_t*, const cuuint64_t*,
                                    const cuuint32_t*, const cuuint32_t*, CUtensorMapInterleave, CUtensorMapSwizzle,
                                    CUtensorMapL2promotion, CUtensorMapFloatOOBfill);

static CUtensorMap make_map(PFN_encodeTiled enc, const void* ptr, uint64_t cols, uint64_t rows, uint32_t box_c, uint32_t box_r, uint32_t nb = 1) {
  CUtensorMap m;
  cuuint64_t dims[3] = {nb > 1 ? box_c : cols, rows, cols / box_c};
  cuuint64_t strides[2] = {cols * 2, box_c * 2};
  cuuint32_t box[3] = {box_c, box_r, nb};
  cuuint32_t es[3] = {1, 1, 1};
  CUresult r = enc(&m, CU_TENSOR_MAP_DATA_TYPE_BFLOAT16, nb > 1 ? 3 : 2, const_cast<void*>(ptr), dims, strides, box, es, CU_TENSOR_MAP_INTERLEAVE_NONE,
      CU_TENSOR_MAP_SWIZZLE_128B, CU_TENSOR_MAP_L2_PROMOTION_L2_256B, CU_TENSOR_MAP_FLOAT_OOB_FILL_NONE);
  (void)r;
  return m;
}

extern "C" void kernel_launch(void* const* d_in, const int* in_sizes, int n_in, void* d_out, int out_size) {
  const bf16* A_x = (const bf16*)d_in[0];
  const bf16* A_wqkv = (const bf16*)d_in[1];
  const bf16* A_wphi = (const bf16*)d_in[2];
  const bf16* A_wo = (const bf16*)d_in[3];
  const bf16* B_wqkv = (const bf16*)d_in[5];
  const bf16* B_wo = (const bf16*)d_in[6];
  bf16* out = (bf16*)d_out;

  static PFN_encodeTiled enc = nullptr;
  static bf16 *p_x, *p_o;
  static bool together;
  if (!enc) {
    void* fn = nullptr; cudaDriverEntryPointQueryResult qr;
    cudaGetDriverEntryPoint("cuTensorMapEncodeTiled", &fn, cudaEnableDefault, &qr);
    enc = (PFN_encodeTiled)fn;
    cudaGetSymbolAddress((void**)&p_x, g_x);
    cudaGetSymbolAddress((void**)&p_o, g_o);
    cudaFuncSetAttribute(mega_kernel, cudaFuncAttributeMaxDynamicSharedMemorySize, SM_TOTAL);
    cudaLaunchConfig_t cfg = {};
    cfg.gridDim = dim3(128 + NX); cfg.blockDim = dim3(384); cfg.dynamicSmemBytes = SM_TOTAL;
    cudaLaunchAttribute at[1];
    at[0].id = cudaLaunchAttributeClusterDimension; at[0].val.clusterDim.x = 2; at[0].val.clusterDim.y = 1; at[0].val.clusterDim.z = 1;
    cfg.attrs = at; cfg.numAttrs = 1;
    int ncl = 0;
    together = cudaOccupancyMaxActiveClusters(&ncl, mega_kernel, &cfg) == cudaSuccess && 2 * ncl >= 128 + NX;
  }
  CUtensorMap tm_x0 = make_map(enc, A_x, 1024, 2048, 64, 128);
  CUtensorMap tm_x = make_map(enc, p_x, 1024, 2048, 64, 128);
  CUtensorMap tm_o = make_map(enc, p_o, 1024, 2048, 64, 128);
  CUtensorMap tm_wA = make_map(enc, A_wqkv, 3072, 1024, 64, 64);
  CUtensorMap tm_wB = make_map(enc, B_wqkv, 3072, 1024, 64, 64);
  CUtensorMap tm_woA = make_map(enc, A_wo, 1024, 1024, 64, 64);
  CUtensorMap tm_woB = make_map(enc, B_wo, 1024, 1024, 64, 64);
  if (!together) mega_kernel<<<NX, 384, SM_TOTAL, cudaStreamPerThread>>>(tm_x0, tm_x, tm_o, tm_wA, tm_wB, tm_woA, tm_woB, B_wqkv, A_wphi, out);
  mega_kernel<<<together ? 128 + NX : 128, 384, SM_TOTAL, cudaStreamPerThread>>>(tm_x0, tm_x, tm_o, tm_wA, tm_wB, tm_woA, tm_woB,
                                                                                 B_wqkv, A_wphi, out);
}
```

```cpp
#include <cuda_runtime.h>
#include <cuda_bf16.h>
#include <cuda.h>
#include <stdint.h>

typedef __nv_bfloat16 bf16;

constexpr int S_ = 2048, D_ = 1024;

struct __align__(128) Flag { unsigned int v; unsigned int pad[31]; };
__device__ __align__(1024) bf16 g_x[S_ * D_];
__device__ __align__(1024) bf16 g_o[S_ * D_];
__device__ __align__(1024) uint4 g_halo[128 * 2 * 512];
__device__ __align__(1024) uint4 g_kv[8 * 2 * 2 * 1280];
__device__ __align__(1024) float2 g_stats[4 * S_];
__device__ __align__(1024) float g_cs[2 * 2 * 3072];
__device__ Flag g_csflag[16];
__device__ __align__(128) unsigned int g_xf[16 * 32], g_of[16 * 32];
__device__ unsigned int g_epoch, g_err;
#define PROFT(cond, idx) asm volatile("" ::: "memory")

__device__ __forceinline__ uint32_t smem_u32(const void* p) { return (uint32_t)__cvta_generic_to_shared(p); }
__device__ __forceinline__ void mbar_init(uint32_t bar, uint32_t count) {
  asm volatile("mbarrier.init.shared::cta.b64 [%0], %1;" ::"r"(bar), "r"(count) : "memory");
}
__device__ __forceinline__ void mbar_expect_tx(uint32_t bar, uint32_t bytes) {
  asm volatile("mbarrier.arrive.expect_tx.shared::cta.b64 _, [%0], %1;" ::"r"(bar), "r"(bytes) : "memory");
}
__device__ __forceinline__ void mbar_arrive(uint32_t bar) {
  asm volatile("mbarrier.arrive.shared::cta.b64 _, [%0];" ::"r"(bar) : "memory");
}
__device__ __forceinline__ bool mbar_try_wait(uint32_t bar, uint32_t parity) {
  uint32_t ok;
  asm volatile("{\n.reg .pred p;\nmbarrier.try_wait.parity.shared::cta.b64 p, [%1], %2;\nselp.b32 %0, 1, 0, p;\n}\n"
               : "=r"(ok) : "r"(bar), "r"(parity) : "memory");
  return ok != 0;
}
__device__ __forceinline__ bool mbar_test_wait(uint32_t bar, uint32_t parity) {
  uint32_t ok;
  asm volatile("{\n.reg .pred p;\nmbarrier.test_wait.parity.shared::cta.b64 p, [%1], %2;\nselp.b32 %0, 1, 0, p;\n}\n"
               : "=r"(ok) : "r"(bar), "r"(parity) : "memory");
  return ok != 0;
}
__device__ __forceinline__ uint64_t gtimer() {
  uint64_t t; asm volatile("mov.u64 %0, %globaltimer;" : "=l"(t)); return t;
}
__device__ __forceinline__ void mbar_wait(uint32_t bar, uint32_t parity) {
  uint32_t n = 0;
#pragma unroll 1
  while (!mbar_try_wait(bar, parity)) {
    if (++n > (1u << 22)) { g_err = 1u; break; }
  }
}
__device__ __forceinline__ unsigned int ld_acquire(const unsigned int* p) {
  unsigned int v; asm volatile("ld.acquire.gpu.global.u32 %0, [%1];" : "=r"(v) : "l"(p) : "memory"); return v;
}
__device__ __forceinline__ void flag_add(unsigned int* p) {
  asm volatile("red.release.gpu.global.add.u32 [%0], 1;" ::"l"(p) : "memory");
}
__device__ __forceinline__ void flag_set(unsigned int* p, unsigned int v) {
  asm volatile("st.release.gpu.global.u32 [%0], %1;" ::"l"(p), "r"(v) : "memory");
}
__device__ __forceinline__ void flag_hint(unsigned int* p, unsigned int v) {
  asm volatile("st.relaxed.gpu.global.u32 [%0], %1;" ::"l"(p), "r"(v) : "memory");
}
template <int SLEEP>
__device__ __forceinline__ void src_wait(const unsigned int* f, unsigned int target, uint32_t need, uint32_t& ready, int lane) {
  uint32_t n = 0;
#pragma unroll 1
  while ((ready & need) != need) {
    const unsigned int v = ld_acquire(f + (lane & 15));
    ready = __ballot_sync(0xffffffffu, (int)(v - target) >= 0);
    if (SLEEP) { if ((ready & need) != need) __nanosleep(SLEEP); }
    if (++n > (1u << 20)) { g_err = 3u; break; }
  }
  __syncwarp();
}
__device__ __forceinline__ unsigned int ld_relaxed(const unsigned int* p) {
  unsigned int v; asm volatile("ld.relaxed.gpu.global.u32 %0, [%1];" : "=r"(v) : "l"(p) : "memory"); return v;
}
__device__ __forceinline__ bool src_wait_tma(const unsigned int* f, unsigned int target, uint32_t need, uint32_t& ready, int lane, uint32_t eb, uint32_t par) {
  uint32_t n = 0;
  bool fr = false;
#pragma unroll 1
  while ((ready & need) != need) {
    const unsigned int v = ld_acquire(f + (lane & 15));
    fr = __all_sync(0xffffffffu, mbar_test_wait(eb, par));
    ready = __ballot_sync(0xffffffffu, (int)(v - target) >= 0);
    if (++n > (1u << 20)) { g_err = 3u; break; }
  }
  return fr;
}
__device__ __forceinline__ uint4 ld_relaxed4(const uint4* p) {
  uint4 v; asm volatile("ld.relaxed.gpu.global.v4.u32 {%0,%1,%2,%3}, [%4];" : "=r"(v.x), "=r"(v.y), "=r"(v.z), "=r"(v.w) : "l"(p) : "memory"); return v;
}
__device__ __forceinline__ void st_relaxed4(uint4* p, uint32_t a, uint32_t b, uint32_t c, uint32_t d) {
  asm volatile("st.relaxed.gpu.global.v4.u32 [%0], {%1,%2,%3,%4};" ::"l"(p), "r"(a), "r"(b), "r"(c), "r"(d) : "memory");
}
template <int SLEEP>
__device__ __forceinline__ void flag_wait_t(const unsigned int* p, unsigned int target) {
  uint32_t n = 0;
#pragma unroll 1
  while ((int)(ld_acquire(p) - target) < 0) {
    if (SLEEP) __nanosleep(SLEEP);
    if (++n > (1u << 20)) { g_err = 2u; break; }
  }
}
__device__ __forceinline__ void flag_wait(const unsigned int* p, unsigned int target) { flag_wait_t<0>(p, target); }
__device__ __forceinline__ void flag_wait_slow(const unsigned int* p, unsigned int target) { flag_wait_t<256>(p, target); }
__device__ __forceinline__ void tma_load_2d(uint32_t dst, const CUtensorMap* tm, int c0, int c1, uint32_t bar) {
  asm volatile("cp.async.bulk.tensor.2d.shared::cluster.global.mbarrier::complete_tx::bytes [%0], [%1, {%2, %3}], [%4];"
               ::"r"(dst), "l"(tm), "r"(c0), "r"(c1), "r"(bar) : "memory");
}
__device__ __forceinline__ void tma_load_2d_mc(uint32_t dst, const CUtensorMap* tm, int c0, int c1, uint32_t bar, uint16_t mask) {
  asm volatile("cp.async.bulk.tensor.2d.shared::cluster.global.mbarrier::complete_tx::bytes.multicast::cluster [%0], [%1, {%2, %3}], [%4], %5;"
               ::"r"(dst), "l"(tm), "r"(c0), "r"(c1), "r"(bar), "h"(mask) : "memory");
}
__device__ __forceinline__ void mbar_wait_u(uint32_t bar, uint32_t parity) {
  uint32_t n = 0;
#pragma unroll 1
  while (!__all_sync(0xffffffffu, mbar_try_wait(bar, parity))) {
    if (++n > (1u << 22)) { g_err = 1u; break; }
  }
}
__device__ __forceinline__ void expect_tx_e(uint32_t bar, uint32_t bytes) {
  asm volatile("{\n.reg .pred p;\nelect.sync _|p, 0xffffffff;\n@p mbarrier.arrive.expect_tx.shared::cta.b64 _, [%0], %1;\n}\n" ::"r"(bar), "r"(bytes) : "memory");
}
__device__ __forceinline__ void tma_2d_e(uint32_t dst, const CUtensorMap* tm, int c0, int c1, uint32_t bar) {
  asm volatile("{\n.reg .pred p;\nelect.sync _|p, 0xffffffff;\n"
               "@p cp.async.bulk.tensor.2d.shared::cluster.global.mbarrier::complete_tx::bytes [%0], [%1, {%2, %3}], [%4];\n}\n"
               ::"r"(dst), "l"(tm), "r"(c0), "r"(c1), "r"(bar) : "memory");
}
__device__ __forceinline__ void tma_2d_mc_e(uint32_t dst, const CUtensorMap* tm, int c0, int c1, uint32_t bar) {
  asm volatile("{\n.reg .pred p;\nelect.sync _|p, 0xffffffff;\n"
               "@p cp.async.bulk.tensor.2d.shared::cluster.global.mbarrier::complete_tx::bytes.multicast::cluster [%0], [%1, {%2, %3}], [%4], %5;\n}\n"
               ::"r"(dst), "l"(tm), "r"(c0), "r"(c1), "r"(bar), "h"((uint16_t)3) : "memory");
}
__device__ __forceinline__ void tma_pf_e(const CUtensorMap* tm, int c0, int c1) {
  asm volatile("{\n.reg .pred p;\nelect.sync _|p, 0xffffffff;\n"
               "@p cp.async.bulk.prefetch.tensor.2d.L2.global.tile [%0, {%1, %2}];\n}\n" ::"l"(tm), "r"(c0), "r"(c1) : "memory");
}
__device__ __forceinline__ void tma_2d_to_e(uint32_t dst, const CUtensorMap* tm, int c0, int c1, uint32_t bar, uint32_t mask) {
  asm volatile("{\n.reg .pred p;\nelect.sync _|p, 0xffffffff;\n"
               "@p cp.async.bulk.tensor.2d.shared::cluster.global.mbarrier::complete_tx::bytes.multicast::cluster [%0], [%1, {%2, %3}], [%4], %5;\n}\n"
               ::"r"(dst), "l"(tm), "r"(c0), "r"(c1), "r"(bar), "h"((uint16_t)mask) : "memory");
}
__device__ __forceinline__ void tma_3d_mc_e(uint32_t dst, const CUtensorMap* tm, int c1, int c2, uint32_t bar) {
  asm volatile("{\n.reg .pred p;\nelect.sync _|p, 0xffffffff;\n"
               "@p cp.async.bulk.tensor.3d.shared::cluster.global.mbarrier::complete_tx::bytes.multicast::cluster [%0], [%1, {%6, %2, %3}], [%4], %5;\n}\n"
               ::"r"(dst), "l"(tm), "r"(c1), "r"(c2), "r"(bar), "h"((uint16_t)3), "r"(0) : "memory");
}
__device__ __forceinline__ uint32_t poll_flags(const unsigned int* f, unsigned int target, int lane) {
  const unsigned int v = ld_acquire(f + (lane & 15));
  const uint32_t r = __ballot_sync(0xffffffffu, (int)(v - target) >= 0);
  __syncwarp();
  return r;
}
__device__ __forceinline__ void mbar_arrive_cluster(uint32_t local_bar, uint32_t rank) {
  asm volatile("{\n.reg .b32 ra;\nmapa.shared::cluster.u32 ra, %0, %1;\nmbarrier.arrive.shared::cluster.b64 _, [ra];\n}\n"
               ::"r"(local_bar), "r"(rank) : "memory");
}
__device__ __forceinline__ void release2(uint32_t bar) { mbar_arrive_cluster(bar, 0); mbar_arrive_cluster(bar, 1); }
__device__ __forceinline__ void tma_store_2d(const CUtensorMap* tm, uint32_t src, int c0, int c1) {
  asm volatile("cp.async.bulk.tensor.2d.global.shared::cta.bulk_group [%0, {%2, %3}], [%1];"
               ::"l"(tm), "r"(src), "r"(c0), "r"(c1) : "memory");
}
__device__ __forceinline__ void bulk_store(void* dst, uint32_t src, uint32_t bytes) {
  asm volatile("cp.async.bulk.global.shared::cta.bulk_group [%0], [%1], %2;" ::"l"(dst), "r"(src), "r"(bytes) : "memory");
}
__device__ __forceinline__ void bulk_load(uint32_t dst, const void* src, uint32_t bytes, uint32_t bar) {
  asm volatile("cp.async.bulk.shared::cluster.global.mbarrier::complete_tx::bytes [%0], [%1], %2, [%3];" ::"r"(dst), "l"(src), "r"(bytes), "r"(bar) : "memory");
}
__device__ __forceinline__ void bulk_red_add(void* dst, uint32_t src, uint32_t bytes) {
  asm volatile("cp.reduce.async.bulk.global.shared::cta.bulk_group.add.f32 [%0], [%1], %2;" ::"l"(dst), "r"(src), "r"(bytes) : "memory");
}
__device__ __forceinline__ void bulk_red_add_e(void* dst, uint32_t src, uint32_t bytes) {
  asm volatile("{\n.reg .pred p;\nelect.sync _|p, 0xffffffff;\n@p cp.reduce.async.bulk.global.shared::cta.bulk_group.add.f32 [%0], [%1], %2;\n}\n" ::"l"(dst), "r"(src), "r"(bytes) : "memory");
}
__device__ __forceinline__ void bulk_commit() { asm volatile("cp.async.bulk.commit_group;" ::: "memory"); }
__device__ __forceinline__ void bulk_wait_read0() { asm volatile("cp.async.bulk.wait_group.read 0;" ::: "memory"); }
__device__ __forceinline__ void bulk_wait0() { asm volatile("cp.async.bulk.wait_group 0;" ::: "memory"); }
__device__ __forceinline__ void fence_async_smem() { asm volatile("fence.proxy.async.shared::cta;" ::: "memory"); }
__device__ __forceinline__ void fence_async_all() { asm volatile("fence.proxy.async.global;" ::: "memory"); }
__device__ __forceinline__ void wgmma_fence() { asm volatile("wgmma.fence.sync.aligned;" ::: "memory"); }
__device__ __forceinline__ void wgmma_commit() { asm volatile("wgmma.commit_group.sync.aligned;" ::: "memory"); }
template <int N> __device__ __forceinline__ void wgmma_wait() { asm volatile("wgmma.wait_group.sync.aligned %0;" ::"n"(N) : "memory"); }
__device__ __forceinline__ void cluster_arrive() { asm volatile("barrier.cluster.arrive.release.aligned;" ::: "memory"); }
__device__ __forceinline__ void cluster_wait() { asm volatile("barrier.cluster.wait.acquire.aligned;" ::: "memory"); }
template <int ID, int N> __device__ __forceinline__ void nbar() { asm volatile("bar.sync %0, %1;" ::"n"(ID), "n"(N) : "memory"); }
__device__ __forceinline__ uint64_t make_desc(uint32_t addr, uint32_t lbo_bytes, uint32_t sbo_bytes) {
  uint64_t d = 0;
  d |= (uint64_t)((addr & 0x3FFFF) >> 4);
  d |= (uint64_t)((lbo_bytes >> 4) & 0x3FFF) << 16;
  d |= (uint64_t)((sbo_bytes >> 4) & 0x3FFF) << 32;
  d |= (uint64_t)1 << 62;
  return d;
}
__device__ __forceinline__ uint64_t desc64(uint32_t lo, uint32_t hi) { return (uint64_t)lo | ((uint64_t)hi << 32); }
__device__ __forceinline__ uint32_t pack_bf16(float lo, float hi) {
  uint32_t r; asm("cvt.rn.bf16x2.f32 %0, %1, %2;" : "=r"(r) : "f"(hi), "f"(lo)); return r;
}
__device__ __forceinline__ uint32_t mul_bf16x2(uint32_t a, uint32_t s, bool hi) {
  __nv_bfloat162 x = *reinterpret_cast<__nv_bfloat162*>(&a), y = *reinterpret_cast<__nv_bfloat162*>(&s);
  x = __hmul2(x, hi ? __high2bfloat162(y) : __low2bfloat162(y));
  return *reinterpret_cast<uint32_t*>(&x);
}
__device__ __forceinline__ float bf16r(float x) { return __bfloat162float(__float2bfloat16_rn(x)); }
__device__ __forceinline__ float bf_lo(uint32_t u) { return __uint_as_float(u << 16); }
__device__ __forceinline__ float bf_hi(uint32_t u) { return __uint_as_float(u & 0xFFFF0000u); }
__device__ __forceinline__ float ex2(float x) { float r; asm("ex2.approx.ftz.f32 %0, %1;" : "=f"(r) : "f"(x)); return r; }
__device__ __forceinline__ float rcp(float x) { float r; asm("rcp.approx.ftz.f32 %0, %1;" : "=f"(r) : "f"(x)); return r; }
__device__ __forceinline__ void mma_bf16(float (&d)[4], uint32_t a0, uint32_t a1, uint32_t a2, uint32_t a3, uint32_t b0, uint32_t b1) {
  asm("mma.sync.aligned.m16n8k16.row.col.f32.bf16.bf16.f32 {%0,%1,%2,%3}, {%4,%5,%6,%7}, {%8,%9}, {%0,%1,%2,%3};"
               : "+f"(d[0]), "+f"(d[1]), "+f"(d[2]), "+f"(d[3]) : "r"(a0), "r"(a1), "r"(a2), "r"(a3), "r"(b0), "r"(b1));
}
__device__ __forceinline__ void ldsm_x4(uint32_t& r0, uint32_t& r1, uint32_t& r2, uint32_t& r3, uint32_t addr) {
  asm volatile("ldmatrix.sync.aligned.m8n8.x4.shared.b16 {%0,%1,%2,%3}, [%4];"
               : "=r"(r0), "=r"(r1), "=r"(r2), "=r"(r3) : "r"(addr) : "memory");
}
__device__ __forceinline__ void ldsm_x4_t(uint32_t& r0, uint32_t& r1, uint32_t& r2, uint32_t& r3, uint32_t addr) {
  asm volatile("ldmatrix.sync.aligned.m8n8.x4.trans.shared.b16 {%0,%1,%2,%3}, [%4];"
               : "=r"(r0), "=r"(r1), "=r"(r2), "=r"(r3) : "r"(addr) : "memory");
}
__device__ __forceinline__ void ldsm_x2_t(uint32_t& r0, uint32_t& r1, uint32_t addr) {
  asm volatile("ldmatrix.sync.aligned.m8n8.x2.trans.shared.b16 {%0,%1}, [%2];"
               : "=r"(r0), "=r"(r1) : "r"(addr) : "memory");
}
__device__ __forceinline__ void stsm_x4(uint32_t addr, uint32_t r0, uint32_t r1, uint32_t r2, uint32_t r3) {
  asm volatile("stmatrix.sync.aligned.m8n8.x4.shared.b16 [%0], {%1,%2,%3,%4};"
               ::"r"(addr), "r"(r0), "r"(r1), "r"(r2), "r"(r3) : "memory");
}
__device__ __forceinline__ void stsm_x4_p(bool on, uint32_t addr, uint32_t r0, uint32_t r1, uint32_t r2, uint32_t r3) {
  asm volatile("{\n.reg .pred p;\nsetp.ne.b32 p, %5, 0;\n@p stmatrix.sync.aligned.m8n8.x4.shared.b16 [%0], {%1,%2,%3,%4};\n}\n"
               ::"r"(addr), "r"(r0), "r"(r1), "r"(r2), "r"(r3), "r"((int)on) : "memory");
}
__device__ __forceinline__ float2 lds_f2(uint32_t addr) {
  float2 v; asm volatile("ld.shared.v2.f32 {%0,%1}, [%2];" : "=f"(v.x), "=f"(v.y) : "r"(addr) : "memory"); return v;
}
__device__ __forceinline__ uint4 lds128(uint32_t addr) {
  uint4 v; asm volatile("ld.shared.v4.b32 {%0,%1,%2,%3}, [%4];" : "=r"(v.x), "=r"(v.y), "=r"(v.z), "=r"(v.w) : "r"(addr) : "memory"); return v;
}
__device__ __forceinline__ void sts128(uint32_t addr, uint4 v) {
  asm volatile("st.shared.v4.b32 [%0], {%1,%2,%3,%4};" ::"r"(addr), "r"(v.x), "r"(v.y), "r"(v.z), "r"(v.w) : "memory");
}
__device__ __forceinline__ float lds_f(uint32_t addr) {
  float v; asm volatile("ld.shared.f32 %0, [%1];" : "=f"(v) : "r"(addr) : "memory"); return v;
}
__device__ __forceinline__ uint32_t lds_vol(uint32_t addr) {
  uint32_t v; asm volatile("ld.volatile.shared.u32 %0, [%1];" : "=r"(v) : "r"(addr) : "memory"); return v;
}
__device__ __forceinline__ void sts16(uint32_t addr, uint32_t v) {
  asm volatile("st.shared.u16 [%0], %1;" ::"r"(addr), "h"((unsigned short)v) : "memory");
}
__device__ __forceinline__ void nbar_dyn(int id, int n) { asm volatile("bar.sync %0, %1;" ::"r"(id), "r"(n) : "memory"); }
__device__ __forceinline__ uint64_t make_desc_ns(uint32_t addr, uint32_t lbo_bytes, uint32_t sbo_bytes) {
  return (uint64_t)((addr & 0x3FFFF) >> 4) | ((uint64_t)(lbo_bytes >> 4) << 16) | ((uint64_t)(sbo_bytes >> 4) << 32);
}
__device__ __forceinline__ void sts_f(uint32_t addr, float v) { asm volatile("st.shared.f32 [%0], %1;" ::"r"(addr), "f"(v) : "memory"); }
__device__ __forceinline__ void sts64(uint32_t addr, uint32_t a, uint32_t b) {
  asm volatile("st.shared.v2.b32 [%0], {%1,%2};" ::"r"(addr), "r"(a), "r"(b) : "memory");
}
__device__ __forceinline__ void sts_f2(uint32_t addr, float a, float b) {
  asm volatile("st.shared.v2.f32 [%0], {%1,%2};" ::"r"(addr), "f"(a), "f"(b) : "memory");
}
__device__ __forceinline__ void red_add2(float* p, float a, float b) {
  asm volatile("red.global.add.v2.f32 [%0], {%1,%2};" ::"l"(p), "f"(a), "f"(b) : "memory");
}
__device__ __forceinline__ void red_add4(float* p, float a, float b, float c, float d) {
  asm volatile("red.global.add.v4.f32 [%0], {%1,%2,%3,%4};" ::"l"(p), "f"(a), "f"(b), "f"(c), "f"(d) : "memory");
}
__device__ __forceinline__ void red_add1(float* p, float a) {
  asm volatile("red.global.add.f32 [%0], %1;" ::"l"(p), "f"(a) : "memory");
}
__device__ __forceinline__ void l2_prefetch(const void* p, uint32_t bytes) {
  asm volatile("cp.async.bulk.prefetch.L2.global [%0], %1;" ::"l"(p), "r"(bytes) : "memory");
}

__device__ __forceinline__ void wgmma_n256(float (&d)[192], uint64_t da, uint64_t db, int scale_d) {
  asm volatile("{\n.reg .pred p;\nsetp.ne.b32 p, %130, 0;\n"
    "wgmma.mma_async.sync.aligned.m64n256k16.f32.bf16.bf16 {%0, %1, %2, %3, %4, %5, %6, %7, %8, %9, %10, %11, %12, %13, %14, %15, %16, %17, %18, %19, %20, %21, %22, %23, %24, %25, %26, %27, %28, %29, %30, %31, %32, %33, %34, %35, %36, %37, %38, %39, %40, %41, %42, %43, %44, %45, %46, %47, %48, %49, %50, %51, %52, %53, %54, %55, %56, %57, %58, %59, %60, %61, %62, %63, %64, %65, %66, %67, %68, %69, %70, %71, %72, %73, %74, %75, %76, %77, %78, %79, %80, %81, %82, %83, %84, %85, %86, %87, %88, %89, %90, %91, %92, %93, %94, %95, %96, %97, %98, %99, %100, %101, %102, %103, %104, %105, %106, %107, %108, %109, %110, %111, %112, %113, %114, %115, %116, %117, %118, %119, %120, %121, %122, %123, %124, %125, %126, %127}, %128, %129, p, 1, 1, 0, 1;\n}\n"
    : "+f"(d[0]), "+f"(d[1]), "+f"(d[2]), "+f"(d[3]), "+f"(d[4]), "+f"(d[5]), "+f"(d[6]), "+f"(d[7]), "+f"(d[8]), "+f"(d[9]), "+f"(d[10]), "+f"(d[11]), "+f"(d[12]), "+f"(d[13]), "+f"(d[14]), "+f"(d[15]), "+f"(d[16]), "+f"(d[17]), "+f"(d[18]), "+f"(d[19]), "+f"(d[20]), "+f"(d[21]), "+f"(d[22]), "+f"(d[23]), "+f"(d[24]), "+f"(d[25]), "+f"(d[26]), "+f"(d[27]), "+f"(d[28]), "+f"(d[29]), "+f"(d[30]), "+f"(d[31]), "+f"(d[32]), "+f"(d[33]), "+f"(d[34]), "+f"(d[35]), "+f"(d[36]), "+f"(d[37]), "+f"(d[38]), "+f"(d[39]), "+f"(d[40]), "+f"(d[41]), "+f"(d[42]), "+f"(d[43]), "+f"(d[44]), "+f"(d[45]), "+f"(d[46]), "+f"(d[47]), "+f"(d[48]), "+f"(d[49]), "+f"(d[50]), "+f"(d[51]), "+f"(d[52]), "+f"(d[53]), "+f"(d[54]), "+f"(d[55]), "+f"(d[56]), "+f"(d[57]), "+f"(d[58]), "+f"(d[59]), "+f"(d[60]), "+f"(d[61]), "+f"(d[62]), "+f"(d[63]), "+f"(d[64]), "+f"(d[65]), "+f"(d[66]), "+f"(d[67]), "+f"(d[68]), "+f"(d[69]), "+f"(d[70]), "+f"(d[71]), "+f"(d[72]), "+f"(d[73]), "+f"(d[74]), "+f"(d[75]), "+f"(d[76]), "+f"(d[77]), "+f"(d[78]), "+f"(d[79]), "+f"(d[80]), "+f"(d[81]), "+f"(d[82]), "+f"(d[83]), "+f"(d[84]), "+f"(d[85]), "+f"(d[86]), "+f"(d[87]), "+f"(d[88]), "+f"(d[89]), "+f"(d[90]), "+f"(d[91]), "+f"(d[92]), "+f"(d[93]), "+f"(d[94]), "+f"(d[95]), "+f"(d[96]), "+f"(d[97]), "+f"(d[98]), "+f"(d[99]), "+f"(d[100]), "+f"(d[101]), "+f"(d[102]), "+f"(d[103]), "+f"(d[104]), "+f"(d[105]), "+f"(d[106]), "+f"(d[107]), "+f"(d[108]), "+f"(d[109]), "+f"(d[110]), "+f"(d[111]), "+f"(d[112]), "+f"(d[113]), "+f"(d[114]), "+f"(d[115]), "+f"(d[116]), "+f"(d[117]), "+f"(d[118]), "+f"(d[119]), "+f"(d[120]), "+f"(d[121]), "+f"(d[122]), "+f"(d[123]), "+f"(d[124]), "+f"(d[125]), "+f"(d[126]), "+f"(d[127])
    : "l"(da), "l"(db), "r"(scale_d));
}
__device__ __forceinline__ void wgmma_n128(float (&d)[192], uint64_t da, uint64_t db, int scale_d) {
  asm volatile("{\n.reg .pred p;\nsetp.ne.b32 p, %66, 0;\n"
    "wgmma.mma_async.sync.aligned.m64n128k16.f32.bf16.bf16 {%0, %1, %2, %3, %4, %5, %6, %7, %8, %9, %10, %11, %12, %13, %14, %15, %16, %17, %18, %19, %20, %21, %22, %23, %24, %25, %26, %27, %28, %29, %30, %31, %32, %33, %34, %35, %36, %37, %38, %39, %40, %41, %42, %43, %44, %45, %46, %47, %48, %49, %50, %51, %52, %53, %54, %55, %56, %57, %58, %59, %60, %61, %62, %63}, %64, %65, p, 1, 1, 0, 1;\n}\n"
    : "+f"(d[128]), "+f"(d[129]), "+f"(d[130]), "+f"(d[131]), "+f"(d[132]), "+f"(d[133]), "+f"(d[134]), "+f"(d[135]), "+f"(d[136]), "+f"(d[137]), "+f"(d[138]), "+f"(d[139]), "+f"(d[140]), "+f"(d[141]), "+f"(d[142]), "+f"(d[143]), "+f"(d[144]), "+f"(d[145]), "+f"(d[146]), "+f"(d[147]), "+f"(d[148]), "+f"(d[149]), "+f"(d[150]), "+f"(d[151]), "+f"(d[152]), "+f"(d[153]), "+f"(d[154]), "+f"(d[155]), "+f"(d[156]), "+f"(d[157]), "+f"(d[158]), "+f"(d[159]), "+f"(d[160]), "+f"(d[161]), "+f"(d[162]), "+f"(d[163]), "+f"(d[164]), "+f"(d[165]), "+f"(d[166]), "+f"(d[167]), "+f"(d[168]), "+f"(d[169]), "+f"(d[170]), "+f"(d[171]), "+f"(d[172]), "+f"(d[173]), "+f"(d[174]), "+f"(d[175]), "+f"(d[176]), "+f"(d[177]), "+f"(d[178]), "+f"(d[179]), "+f"(d[180]), "+f"(d[181]), "+f"(d[182]), "+f"(d[183]), "+f"(d[184]), "+f"(d[185]), "+f"(d[186]), "+f"(d[187]), "+f"(d[188]), "+f"(d[189]), "+f"(d[190]), "+f"(d[191])
    : "l"(da), "l"(db), "r"(scale_d));
}
__device__ __forceinline__ void wgmma_n256_k(float (&d)[192], uint64_t da, uint64_t db, int scale_d) {
  asm volatile("{\n.reg .pred p;\nsetp.ne.b32 p, %130, 0;\n"
    "wgmma.mma_async.sync.aligned.m64n256k16.f32.bf16.bf16 {%0, %1, %2, %3, %4, %5, %6, %7, %8, %9, %10, %11, %12, %13, %14, %15, %16, %17, %18, %19, %20, %21, %22, %23, %24, %25, %26, %27, %28, %29, %30, %31, %32, %33, %34, %35, %36, %37, %38, %39, %40, %41, %42, %43, %44, %45, %46, %47, %48, %49, %50, %51, %52, %53, %54, %55, %56, %57, %58, %59, %60, %61, %62, %63, %64, %65, %66, %67, %68, %69, %70, %71, %72, %73, %74, %75, %76, %77, %78, %79, %80, %81, %82, %83, %84, %85, %86, %87, %88, %89, %90, %91, %92, %93, %94, %95, %96, %97, %98, %99, %100, %101, %102, %103, %104, %105, %106, %107, %108, %109, %110, %111, %112, %113, %114, %115, %116, %117, %118, %119, %120, %121, %122, %123, %124, %125, %126, %127}, %128, %129, p, 1, 1, 0, 0;\n}\n"
    : "+f"(d[0]), "+f"(d[1]), "+f"(d[2]), "+f"(d[3]), "+f"(d[4]), "+f"(d[5]), "+f"(d[6]), "+f"(d[7]), "+f"(d[8]), "+f"(d[9]), "+f"(d[10]), "+f"(d[11]), "+f"(d[12]), "+f"(d[13]), "+f"(d[14]), "+f"(d[15]), "+f"(d[16]), "+f"(d[17]), "+f"(d[18]), "+f"(d[19]), "+f"(d[20]), "+f"(d[21]), "+f"(d[22]), "+f"(d[23]), "+f"(d[24]), "+f"(d[25]), "+f"(d[26]), "+f"(d[27]), "+f"(d[28]), "+f"(d[29]), "+f"(d[30]), "+f"(d[31]), "+f"(d[32]), "+f"(d[33]), "+f"(d[34]), "+f"(d[35]), "+f"(d[36]), "+f"(d[37]), "+f"(d[38]), "+f"(d[39]), "+f"(d[40]), "+f"(d[41]), "+f"(d[42]), "+f"(d[43]), "+f"(d[44]), "+f"(d[45]), "+f"(d[46]), "+f"(d[47]), "+f"(d[48]), "+f"(d[49]), "+f"(d[50]), "+f"(d[51]), "+f"(d[52]), "+f"(d[53]), "+f"(d[54]), "+f"(d[55]), "+f"(d[56]), "+f"(d[57]), "+f"(d[58]), "+f"(d[59]), "+f"(d[60]), "+f"(d[61]), "+f"(d[62]), "+f"(d[63]), "+f"(d[64]), "+f"(d[65]), "+f"(d[66]), "+f"(d[67]), "+f"(d[68]), "+f"(d[69]), "+f"(d[70]), "+f"(d[71]), "+f"(d[72]), "+f"(d[73]), "+f"(d[74]), "+f"(d[75]), "+f"(d[76]), "+f"(d[77]), "+f"(d[78]), "+f"(d[79]), "+f"(d[80]), "+f"(d[81]), "+f"(d[82]), "+f"(d[83]), "+f"(d[84]), "+f"(d[85]), "+f"(d[86]), "+f"(d[87]), "+f"(d[88]), "+f"(d[89]), "+f"(d[90]), "+f"(d[91]), "+f"(d[92]), "+f"(d[93]), "+f"(d[94]), "+f"(d[95]), "+f"(d[96]), "+f"(d[97]), "+f"(d[98]), "+f"(d[99]), "+f"(d[100]), "+f"(d[101]), "+f"(d[102]), "+f"(d[103]), "+f"(d[104]), "+f"(d[105]), "+f"(d[106]), "+f"(d[107]), "+f"(d[108]), "+f"(d[109]), "+f"(d[110]), "+f"(d[111]), "+f"(d[112]), "+f"(d[113]), "+f"(d[114]), "+f"(d[115]), "+f"(d[116]), "+f"(d[117]), "+f"(d[118]), "+f"(d[119]), "+f"(d[120]), "+f"(d[121]), "+f"(d[122]), "+f"(d[123]), "+f"(d[124]), "+f"(d[125]), "+f"(d[126]), "+f"(d[127])
    : "l"(da), "l"(db), "r"(scale_d));
}
__device__ __forceinline__ void wgmma_n128_k(float (&d)[192], uint64_t da, uint64_t db, int scale_d) {
  asm volatile("{\n.reg .pred p;\nsetp.ne.b32 p, %66, 0;\n"
    "wgmma.mma_async.sync.aligned.m64n128k16.f32.bf16.bf16 {%0, %1, %2, %3, %4, %5, %6, %7, %8, %9, %10, %11, %12, %13, %14, %15, %16, %17, %18, %19, %20, %21, %22, %23, %24, %25, %26, %27, %28, %29, %30, %31, %32, %33, %34, %35, %36, %37, %38, %39, %40, %41, %42, %43, %44, %45, %46, %47, %48, %49, %50, %51, %52, %53, %54, %55, %56, %57, %58, %59, %60, %61, %62, %63}, %64, %65, p, 1, 1, 0, 0;\n}\n"
    : "+f"(d[128]), "+f"(d[129]), "+f"(d[130]), "+f"(d[131]), "+f"(d[132]), "+f"(d[133]), "+f"(d[134]), "+f"(d[135]), "+f"(d[136]), "+f"(d[137]), "+f"(d[138]), "+f"(d[139]), "+f"(d[140]), "+f"(d[141]), "+f"(d[142]), "+f"(d[143]), "+f"(d[144]), "+f"(d[145]), "+f"(d[146]), "+f"(d[147]), "+f"(d[148]), "+f"(d[149]), "+f"(d[150]), "+f"(d[151]), "+f"(d[152]), "+f"(d[153]), "+f"(d[154]), "+f"(d[155]), "+f"(d[156]), "+f"(d[157]), "+f"(d[158]), "+f"(d[159]), "+f"(d[160]), "+f"(d[161]), "+f"(d[162]), "+f"(d[163]), "+f"(d[164]), "+f"(d[165]), "+f"(d[166]), "+f"(d[167]), "+f"(d[168]), "+f"(d[169]), "+f"(d[170]), "+f"(d[171]), "+f"(d[172]), "+f"(d[173]), "+f"(d[174]), "+f"(d[175]), "+f"(d[176]), "+f"(d[177]), "+f"(d[178]), "+f"(d[179]), "+f"(d[180]), "+f"(d[181]), "+f"(d[182]), "+f"(d[183]), "+f"(d[184]), "+f"(d[185]), "+f"(d[186]), "+f"(d[187]), "+f"(d[188]), "+f"(d[189]), "+f"(d[190]), "+f"(d[191])
    : "l"(da), "l"(db), "r"(scale_d));
}
__device__ __forceinline__ void wgmma_n40_tt(float (&d)[20], uint64_t da, uint64_t db, int scale_d) {
  asm volatile("{\n.reg .pred p;\nsetp.ne.b32 p, %22, 0;\n"
    "wgmma.mma_async.sync.aligned.m64n40k16.f32.bf16.bf16 {%0, %1, %2, %3, %4, %5, %6, %7, %8, %9, %10, %11, %12, %13, %14, %15, %16, %17, %18, %19}, %20, %21, p, 1, 1, 1, 1;\n}\n"
    : "+f"(d[0]), "+f"(d[1]), "+f"(d[2]), "+f"(d[3]), "+f"(d[4]), "+f"(d[5]), "+f"(d[6]), "+f"(d[7]), "+f"(d[8]), "+f"(d[9]), "+f"(d[10]), "+f"(d[11]), "+f"(d[12]), "+f"(d[13]), "+f"(d[14]), "+f"(d[15]), "+f"(d[16]), "+f"(d[17]), "+f"(d[18]), "+f"(d[19])
    : "l"(da), "l"(db), "r"(scale_d));
}
__device__ __forceinline__ void wgmma_n40_rs(float (&d)[20], const uint32_t (&a)[4], uint64_t db, int scale_d) {
  asm volatile("{\n.reg .pred p;\nsetp.ne.b32 p, %25, 0;\n"
    "wgmma.mma_async.sync.aligned.m64n40k16.f32.bf16.bf16 {%0, %1, %2, %3, %4, %5, %6, %7, %8, %9, %10, %11, %12, %13, %14, %15, %16, %17, %18, %19}, {%20, %21, %22, %23}, %24, p, 1, 1, 1;\n}\n"
    : "+f"(d[0]), "+f"(d[1]), "+f"(d[2]), "+f"(d[3]), "+f"(d[4]), "+f"(d[5]), "+f"(d[6]), "+f"(d[7]), "+f"(d[8]), "+f"(d[9]), "+f"(d[10]), "+f"(d[11]), "+f"(d[12]), "+f"(d[13]), "+f"(d[14]), "+f"(d[15]), "+f"(d[16]), "+f"(d[17]), "+f"(d[18]), "+f"(d[19])
    : "r"(a[0]), "r"(a[1]), "r"(a[2]), "r"(a[3]), "l"(db), "r"(scale_d));
}
__device__ __forceinline__ void wgmma_n256_0(float (&d)[192], uint64_t da, uint64_t db) {
  asm volatile("{\n.reg .pred p;\nsetp.ne.b32 p, 0, 0;\n"
    "wgmma.mma_async.sync.aligned.m64n256k16.f32.bf16.bf16 {%0, %1, %2, %3, %4, %5, %6, %7, %8, %9, %10, %11, %12, %13, %14, %15, %16, %17, %18, %19, %20, %21, %22, %23, %24, %25, %26, %27, %28, %29, %30, %31, %32, %33, %34, %35, %36, %37, %38, %39, %40, %41, %42, %43, %44, %45, %46, %47, %48, %49, %50, %51, %52, %53, %54, %55, %56, %57, %58, %59, %60, %61, %62, %63, %64, %65, %66, %67, %68, %69, %70, %71, %72, %73, %74, %75, %76, %77, %78, %79, %80, %81, %82, %83, %84, %85, %86, %87, %88, %89, %90, %91, %92, %93, %94, %95, %96, %97, %98, %99, %100, %101, %102, %103, %104, %105, %106, %107, %108, %109, %110, %111, %112, %113, %114, %115, %116, %117, %118, %119, %120, %121, %122, %123, %124, %125, %126, %127}, %128, %129, p, 1, 1, 0, 1;\n}\n"
    : "=f"(d[0]), "=f"(d[1]), "=f"(d[2]), "=f"(d[3]), "=f"(d[4]), "=f"(d[5]), "=f"(d[6]), "=f"(d[7]), "=f"(d[8]), "=f"(d[9]), "=f"(d[10]), "=f"(d[11]), "=f"(d[12]), "=f"(d[13]), "=f"(d[14]), "=f"(d[15]), "=f"(d[16]), "=f"(d[17]), "=f"(d[18]), "=f"(d[19]), "=f"(d[20]), "=f"(d[21]), "=f"(d[22]), "=f"(d[23]), "=f"(d[24]), "=f"(d[25]), "=f"(d[26]), "=f"(d[27]), "=f"(d[28]), "=f"(d[29]), "=f"(d[30]), "=f"(d[31]), "=f"(d[32]), "=f"(d[33]), "=f"(d[34]), "=f"(d[35]), "=f"(d[36]), "=f"(d[37]), "=f"(d[38]), "=f"(d[39]), "=f"(d[40]), "=f"(d[41]), "=f"(d[42]), "=f"(d[43]), "=f"(d[44]), "=f"(d[45]), "=f"(d[46]), "=f"(d[47]), "=f"(d[48]), "=f"(d[49]), "=f"(d[50]), "=f"(d[51]), "=f"(d[52]), "=f"(d[53]), "=f"(d[54]), "=f"(d[55]), "=f"(d[56]), "=f"(d[57]), "=f"(d[58]), "=f"(d[59]), "=f"(d[60]), "=f"(d[61]), "=f"(d[62]), "=f"(d[63]), "=f"(d[64]), "=f"(d[65]), "=f"(d[66]), "=f"(d[67]), "=f"(d[68]), "=f"(d[69]), "=f"(d[70]), "=f"(d[71]), "=f"(d[72]), "=f"(d[73]), "=f"(d[74]), "=f"(d[75]), "=f"(d[76]), "=f"(d[77]), "=f"(d[78]), "=f"(d[79]), "=f"(d[80]), "=f"(d[81]), "=f"(d[82]), "=f"(d[83]), "=f"(d[84]), "=f"(d[85]), "=f"(d[86]), "=f"(d[87]), "=f"(d[88]), "=f"(d[89]), "=f"(d[90]), "=f"(d[91]), "=f"(d[92]), "=f"(d[93]), "=f"(d[94]), "=f"(d[95]), "=f"(d[96]), "=f"(d[97]), "=f"(d[98]), "=f"(d[99]), "=f"(d[100]), "=f"(d[101]), "=f"(d[102]), "=f"(d[103]), "=f"(d[104]), "=f"(d[105]), "=f"(d[106]), "=f"(d[107]), "=f"(d[108]), "=f"(d[109]), "=f"(d[110]), "=f"(d[111]), "=f"(d[112]), "=f"(d[113]), "=f"(d[114]), "=f"(d[115]), "=f"(d[116]), "=f"(d[117]), "=f"(d[118]), "=f"(d[119]), "=f"(d[120]), "=f"(d[121]), "=f"(d[122]), "=f"(d[123]), "=f"(d[124]), "=f"(d[125]), "=f"(d[126]), "=f"(d[127])
    : "l"(da), "l"(db));
}
__device__ __forceinline__ void wgmma_n128_0(float (&d)[192], uint64_t da, uint64_t db) {
  asm volatile("{\n.reg .pred p;\nsetp.ne.b32 p, 0, 0;\n"
    "wgmma.mma_async.sync.aligned.m64n128k16.f32.bf16.bf16 {%0, %1, %2, %3, %4, %5, %6, %7, %8, %9, %10, %11, %12, %13, %14, %15, %16, %17, %18, %19, %20, %21, %22, %23, %24, %25, %26, %27, %28, %29, %30, %31, %32, %33, %34, %35, %36, %37, %38, %39, %40, %41, %42, %43, %44, %45, %46, %47, %48, %49, %50, %51, %52, %53, %54, %55, %56, %57, %58, %59, %60, %61, %62, %63}, %64, %65, p, 1, 1, 0, 1;\n}\n"
    : "=f"(d[128]), "=f"(d[129]), "=f"(d[130]), "=f"(d[131]), "=f"(d[132]), "=f"(d[133]), "=f"(d[134]), "=f"(d[135]), "=f"(d[136]), "=f"(d[137]), "=f"(d[138]), "=f"(d[139]), "=f"(d[140]), "=f"(d[141]), "=f"(d[142]), "=f"(d[143]), "=f"(d[144]), "=f"(d[145]), "=f"(d[146]), "=f"(d[147]), "=f"(d[148]), "=f"(d[149]), "=f"(d[150]), "=f"(d[151]), "=f"(d[152]), "=f"(d[153]), "=f"(d[154]), "=f"(d[155]), "=f"(d[156]), "=f"(d[157]), "=f"(d[158]), "=f"(d[159]), "=f"(d[160]), "=f"(d[161]), "=f"(d[162]), "=f"(d[163]), "=f"(d[164]), "=f"(d[165]), "=f"(d[166]), "=f"(d[167]), "=f"(d[168]), "=f"(d[169]), "=f"(d[170]), "=f"(d[171]), "=f"(d[172]), "=f"(d[173]), "=f"(d[174]), "=f"(d[175]), "=f"(d[176]), "=f"(d[177]), "=f"(d[178]), "=f"(d[179]), "=f"(d[180]), "=f"(d[181]), "=f"(d[182]), "=f"(d[183]), "=f"(d[184]), "=f"(d[185]), "=f"(d[186]), "=f"(d[187]), "=f"(d[188]), "=f"(d[189]), "=f"(d[190]), "=f"(d[191])
    : "l"(da), "l"(db));
}
__device__ __forceinline__ void wgmma_n128_rs(float (&d)[192], const uint32_t (&a)[4], uint64_t db, int scale_d) {
  asm volatile("{\n.reg .pred p;\nsetp.ne.b32 p, %69, 0;\n"
    "wgmma.mma_async.sync.aligned.m64n128k16.f32.bf16.bf16 {%0, %1, %2, %3, %4, %5, %6, %7, %8, %9, %10, %11, %12, %13, %14, %15, %16, %17, %18, %19, %20, %21, %22, %23, %24, %25, %26, %27, %28, %29, %30, %31, %32, %33, %34, %35, %36, %37, %38, %39, %40, %41, %42, %43, %44, %45, %46, %47, %48, %49, %50, %51, %52, %53, %54, %55, %56, %57, %58, %59, %60, %61, %62, %63}, {%64, %65, %66, %67}, %68, p, 1, 1, 1;\n}\n"
    : "+f"(d[128]), "+f"(d[129]), "+f"(d[130]), "+f"(d[131]), "+f"(d[132]), "+f"(d[133]), "+f"(d[134]), "+f"(d[135]), "+f"(d[136]), "+f"(d[137]), "+f"(d[138]), "+f"(d[139]), "+f"(d[140]), "+f"(d[141]), "+f"(d[142]), "+f"(d[143]), "+f"(d[144]), "+f"(d[145]), "+f"(d[146]), "+f"(d[147]), "+f"(d[148]), "+f"(d[149]), "+f"(d[150]), "+f"(d[151]), "+f"(d[152]), "+f"(d[153]), "+f"(d[154]), "+f"(d[155]), "+f"(d[156]), "+f"(d[157]), "+f"(d[158]), "+f"(d[159]), "+f"(d[160]), "+f"(d[161]), "+f"(d[162]), "+f"(d[163]), "+f"(d[164]), "+f"(d[165]), "+f"(d[166]), "+f"(d[167]), "+f"(d[168]), "+f"(d[169]), "+f"(d[170]), "+f"(d[171]), "+f"(d[172]), "+f"(d[173]), "+f"(d[174]), "+f"(d[175]), "+f"(d[176]), "+f"(d[177]), "+f"(d[178]), "+f"(d[179]), "+f"(d[180]), "+f"(d[181]), "+f"(d[182]), "+f"(d[183]), "+f"(d[184]), "+f"(d[185]), "+f"(d[186]), "+f"(d[187]), "+f"(d[188]), "+f"(d[189]), "+f"(d[190]), "+f"(d[191])
    : "r"(a[0]), "r"(a[1]), "r"(a[2]), "r"(a[3]), "l"(db), "r"(scale_d));
}

constexpr int SLOT = 16384;
constexpr int KVT = 10240;
constexpr uint32_t QA = 0x0BAu, QK = 0x462u, QQ = 0x981u;
constexpr int SM_SD = 12 * SLOT;
constexpr int SM_BAR = SM_SD + 8192;
constexpr int SM_RS = SM_BAR + 512;
constexpr int SM_AP = SM_RS + 768;
constexpr int SM_BP = SM_AP + 2048;
constexpr int SM_WPHI = SM_BP + 12288;
constexpr int SM_EPOCH = SM_WPHI + 10240;
constexpr int SM_TOTAL = SM_EPOCH + 16 + 1024;
constexpr int B_FULLS = 0, B_XOLD = 24, B_STAT = 32, B_EMPTYS = 40, B_FULLT = 256  , B_CONS = 384  , B_E3 = 472, B_E0 = 480, B_E1 = 488, B_E2 = 496, B_EPI = 504, B_CS = 160,
              B_KVDONE = 168  , B_ODONE = 176, B_XDONE = 184, B_OH1 = B_CONS, B_CS2 = 208, B_XH0 = 232, B_R0 = 240, B_CB = 144  , B_XOLD2 = 216, B_FLG = 64  ;
constexpr uint64_t BAR_CNT = 0x1c07fc0eac00a800ull;
constexpr uint64_t WO_A0 = 0xa461b57648357643ull, WO_B0 = 0x59083a9021ba9021ull, WO_A1 = 0xa0b76901276a5babull, WO_B1 = 0x95428a5b34890132ull;
constexpr uint64_t WO_DA0 = 0xa9865432ff00dd00ull, WO_DB0 = 0xa986543211bbccccull, WO_DA1 = 0xa98654321ffff000ull, WO_DB1 = 0xa98754321bbcccddull;
#define WOORD 0xFDB9753ECA864210ull
constexpr int NX = 4;
constexpr int XS = 10;

#define PL 2
#define PROFX(i) PROFT(tid_ == 128 && layer == PL, 200 + (i))
#define PSL 20
#define EP 5
#define NCOM 3
#define PFS 8
#define KVTH 0x41700000u
#define PMOD 3
#define XPF 3
#define XPM 2
#define TLINE 1
#define MAP 3
#define NLAYERS 4
constexpr float L2E = 1.4426950408889634f;
#define PHI_MAX 2147483648.f

#define D128(lo) desc64(lo, 0x40000040u)
struct Ctx { uint32_t sb; int g, rb, cu; bf16* out; };

__device__ __forceinline__ void colsum(const CUtensorMap* tm, float* cs, int rb, int g, int w0, int dw, int lane, uint32_t stg, uint32_t cb, uint32_t par) {
  const uint32_t src = stg + (lane >> 3) * 2048;
#pragma unroll 1
  for (int wi = w0 - dw; wi < 6; wi += dw) {
    float s[8] = {0.f, 0.f, 0.f, 0.f, 0.f, 0.f, 0.f, 0.f};
    if (wi >= 0) {
      mbar_wait_u(cb, par);
      par ^= 1;
#pragma unroll 4
      for (int r = 0; r < 16; ++r) {
        const uint4 v = lds128(src + r * 128 + (((lane ^ r) & 7) << 4));
        s[0] += bf_lo(v.x); s[1] += bf_hi(v.x); s[2] += bf_lo(v.y); s[3] += bf_hi(v.y);
        s[4] += bf_lo(v.z); s[5] += bf_hi(v.z); s[6] += bf_lo(v.w); s[7] += bf_hi(v.w);
      }
#pragma unroll
      for (int i = 0; i < 8; ++i) s[i] += __shfl_xor_sync(0xffffffffu, s[i], 8);
    }
    const int wn = wi + dw;
    if (wn < 6) {
      expect_tx_e(cb, 8192);
      tma_2d_e(stg, tm, (wn >= 4 ? 0 : 1024 + (wn >> 1) * 1024) + g * 128 + (wn & 1) * 64, rb * 64, cb);
    }
    if (wi >= 0) {
#pragma unroll
      for (int i = 0; i < 8; ++i) s[i] += __shfl_xor_sync(0xffffffffu, s[i], 16);
      if (lane < 8) {
        red_add4(cs + g * 384 + (wi * 8 + lane) * 8, s[0], s[1], s[2], s[3]);
        red_add4(cs + g * 384 + (wi * 8 + lane) * 8 + 4, s[4], s[5], s[6], s[7]);
      }
      __syncwarp();
    }
  }
}
#define PHASE_CTX() \
  uint32_t sb = c.sb; asm volatile("" : "+r"(sb)); \
  int tid_ = threadIdx.x; asm volatile("" : "+r"(tid_)); \
  const uint32_t bar = sb + SM_BAR; \
  const int lane = tid_ & 31, cw = (tid_ >> 5) - 4, wg = cw >> 2, wq = cw & 3, gq = lane >> 2, t = lane & 3, wrow0 = cw * 16; \
  const int lrow = (lane & 7) + ((lane >> 3) & 1) * 8, lchk = lane >> 4; \
  const bool elected = (tid_ & 127) == 0; \
  const uint32_t rowo = (wrow0 + lrow) * 128, X = (lchk ^ (lane & 7)) << 4; \
  (void)bar; (void)wq; (void)gq; (void)lrow; (void)lchk; (void)elected; (void)wrow0; (void)wg; (void)rowo; (void)X; (void)t;

__device__ __forceinline__ void slab_out_half(uint32_t slot, bf16* dst, int wrow0, int lane, bool FENCE = false) {
  const int r0 = lane >> 3, ch = lane & 7;
  const uint32_t src = slot + (wrow0 + r0) * 128;
  uint4 v[4];
#pragma unroll
  for (int i = 0; i < 4; ++i) v[i] = lds128(src + i * 512 + (((ch ^ (4 * i + r0)) & 7) << 4));
  if (FENCE) fence_async_smem();
  dst += (size_t)(wrow0 + r0) * D_ + ch * 8;
#pragma unroll
  for (int i = 0; i < 4; ++i)
    asm volatile("st.global.v4.u32 [%0], {%1,%2,%3,%4};" ::"l"(dst + (size_t)i * 4 * D_), "r"(v[i].x), "r"(v[i].y), "r"(v[i].z), "r"(v[i].w) : "memory");
}

struct Tag { uint32_t me, mo, tg; };
__device__ __forceinline__ Tag make_tag(int gq, int t, uint32_t tg) { return Tag{t == 0, t == 1, tg}; }
__device__ __forceinline__ void stsm_tag(uint32_t addr, uint32_t r0, uint32_t r1, uint32_t r2, uint32_t r3, const Tag& k, int jp) {
  if (jp == 0) stsm_x4(addr, (r0 & ~k.me) | (k.tg & k.me), (r1 & ~k.mo) | (k.tg & k.mo), r2, r3);
  else stsm_x4(addr, r0, r1, r2, r3);
}
#define TILE_BAD() ((lds_vol(va) ^ tg) & 1)
#define TILE_VA() (slot + (wrow0 + (lane & 15)) * 128 + (lane & 7) * 16 + ((lane >> 3) & 1) * 4)
__device__ __forceinline__ void tile_check(uint32_t slot, const bf16* src, int wrow0, int lane, uint32_t tg) {
  const uint32_t va = TILE_VA();
  if (__builtin_expect(__any_sync(0xffffffffu, TILE_BAD()), 0)) {
    const int r0 = lane >> 3, ch = lane & 7;
    uint32_t n = 0;
#pragma unroll 1
    do {
      uint4 v[4];
#pragma unroll
      for (int i = 0; i < 4; ++i) v[i] = ld_relaxed4(reinterpret_cast<const uint4*>(src + (size_t)(wrow0 + r0 + 4 * i) * D_ + ch * 8));
#pragma unroll
      for (int i = 0; i < 4; ++i) sts128(slot + (wrow0 + r0 + 4 * i) * 128 + (((ch ^ (4 * i + r0)) & 7) << 4), v[i]);
      __syncwarp();
      if (++n > (1u << 16)) { g_err = 8u; break; }
    } while (__any_sync(0xffffffffu, TILE_BAD()));
    fence_async_smem();
    __syncwarp();
  }
}

template <int O>
__device__ __forceinline__ void phi_proj(float (&p)[2][4][4], const uint32_t (&kq)[64], uint32_t wa) {
#pragma unroll
  for (int h = 0; h < 2; ++h)
#pragma unroll
    for (int i = 0; i < 4; ++i) { p[h][i][0] = p[h][i][1] = p[h][i][2] = p[h][i][3] = 0.f; }
#pragma unroll
  for (int ks = 0; ks < 2; ++ks)
#pragma unroll
    for (int np = 0; np < 2; ++np)
#pragma unroll
      for (int h = 0; h < 2; ++h) {
        uint32_t b0, b1, b2, b3;
        ldsm_x4_t(b0, b1, b2, b3, wa + h * 2560 + ks * 1280 + np * 32);
        mma_bf16(p[h][2 * np], kq[O + 8 * h + 4 * ks], kq[O + 8 * h + 4 * ks + 1], kq[O + 8 * h + 4 * ks + 2], kq[O + 8 * h + 4 * ks + 3], b0, b1);
        mma_bf16(p[h][2 * np + 1], kq[O + 8 * h + 4 * ks], kq[O + 8 * h + 4 * ks + 1], kq[O + 8 * h + 4 * ks + 2], kq[O + 8 * h + 4 * ks + 3], b2, b3);
      }
}
__device__ __forceinline__ void phi_exp(uint32_t (&raw)[4][4], const float (&p)[4][4], float sc0, float sc1) {
#pragma unroll
  for (int i = 0; i < 4; ++i) {
    const float e0 = ex2(p[i][0] * sc0), e1 = ex2(p[i][1] * sc0), e2 = ex2(p[i][2] * sc1), e3 = ex2(p[i][3] * sc1);
    const float m0 = e0 * e1, m1 = e2 * e3, rr = rcp(m0 * m1), r0 = rr * m1, r1 = rr * m0;
    raw[i >> 1][(i & 1) * 2] = pack_bf16(e0, e1);
    raw[i >> 1][(i & 1) * 2 + 1] = pack_bf16(e2, e3);
    raw[2 + (i >> 1)][(i & 1) * 2] = pack_bf16(e1 * r0, e0 * r0);
    raw[2 + (i >> 1)][(i & 1) * 2 + 1] = pack_bf16(e3 * r1, e2 * r1);
  }
}
template <int O>
__device__ __forceinline__ void phi_norm(uint32_t (&ph)[2][4][4], const uint32_t (&raw)[2][4][4], const uint32_t (&kq)[64], uint32_t wa,
                                         float sc0, float sc1, float mul0, float mul1) {
  bool bad = false;
#pragma unroll
  for (int h = 0; h < 2; ++h)
#pragma unroll
    for (int sg = 0; sg < 2; ++sg) {
      float ss[4] = {0.f, 0.f, 0.f, 0.f};
#pragma unroll
      for (int ks = 0; ks < 2; ++ks)
        mma_bf16(ss, raw[h][2 * sg + ks][0], raw[h][2 * sg + ks][1], raw[h][2 * sg + ks][2], raw[h][2 * sg + ks][3], 0x3F803F80u, 0x3F803F80u);
      bad = bad || !(ss[0] < PHI_MAX) || !(ss[2] < PHI_MAX);
      const uint32_t iv = pack_bf16(rcp(ss[0]) * mul0, rcp(ss[2]) * mul1);
#pragma unroll
      for (int ks = 0; ks < 2; ++ks)
#pragma unroll
        for (int j = 0; j < 4; ++j) ph[h][2 * sg + ks][j] = mul_bf16x2(raw[h][2 * sg + ks][j], iv, j & 1);
    }
  if (__builtin_expect(__any_sync(0xffffffffu, bad), 0)) {
#pragma unroll 1
    for (int it = 0; it < 4; ++it) {
      float q[4][4];
#pragma unroll
      for (int i = 0; i < 4; ++i) { q[i][0] = q[i][1] = q[i][2] = q[i][3] = 0.f; }
#pragma unroll
      for (int ks = 0; ks < 2; ++ks) {
        uint32_t a[4];
#pragma unroll
        for (int j = 0; j < 4; ++j) a[j] = (it & 2) ? kq[O + 8 + 4 * ks + j] : kq[O + 4 * ks + j];
#pragma unroll
        for (int np = 0; np < 2; ++np) {
          uint32_t b0, b1, b2, b3;
          ldsm_x4_t(b0, b1, b2, b3, wa + (it >> 1) * 2560 + ks * 1280 + np * 32);
          mma_bf16(q[2 * np], a[0], a[1], a[2], a[3], b0, b1);
          mma_bf16(q[2 * np + 1], a[0], a[1], a[2], a[3], b2, b3);
        }
      }
      float iv[2];
#pragma unroll
      for (int r = 0; r < 2; ++r) {
        const float sc = (it & 1) ? -(r ? sc1 : sc0) : (r ? sc1 : sc0);
        float mx = -INFINITY, sm = 0.f;
#pragma unroll
        for (int i = 0; i < 8; ++i) { float& v = q[i >> 1][2 * r + (i & 1)]; v *= sc; mx = fmaxf(mx, v); }
        mx = fmaxf(mx, __shfl_xor_sync(0xffffffffu, mx, 1));
        mx = fmaxf(mx, __shfl_xor_sync(0xffffffffu, mx, 2));
#pragma unroll
        for (int i = 0; i < 8; ++i) { float& v = q[i >> 1][2 * r + (i & 1)]; v = ex2(v - mx); sm += v; }
        sm += __shfl_xor_sync(0xffffffffu, sm, 1);
        sm += __shfl_xor_sync(0xffffffffu, sm, 2);
        iv[r] = rcp(sm) * (r ? mul1 : mul0);
      }
#pragma unroll
      for (int i = 0; i < 24; ++i) ph[i >> 4][(i >> 2) & 3][i & 3] = ph[(i + 8) >> 4][((i + 8) >> 2) & 3][i & 3];
#pragma unroll
      for (int i = 0; i < 4; ++i) {
        ph[1][2 + (i >> 1)][(i & 1) * 2] = pack_bf16(q[i][0] * iv[0], q[i][1] * iv[0]);
        ph[1][2 + (i >> 1)][(i & 1) * 2 + 1] = pack_bf16(q[i][2] * iv[1], q[i][3] * iv[1]);
      }
    }
  }
}

__device__ __forceinline__ void stats_out(float s0, float s1, float q0, float q1, float2* dst, int t) {
  const bool od = t & 1;
  float sa = od ? s1 : s0, qa = od ? q1 : q0;
  sa += __shfl_xor_sync(0xffffffffu, od ? s0 : s1, 1);
  qa += __shfl_xor_sync(0xffffffffu, od ? q0 : q1, 1);
  sa += __shfl_xor_sync(0xffffffffu, sa, 2);
  qa += __shfl_xor_sync(0xffffffffu, qa, 2);
  if (t < 2) red_add2(&dst[t * 8].x, sa, qa);
}

__device__ __forceinline__ void consumer(const Ctx& c) {
  const int g = c.g, m0 = c.rb * 128;
  float acc[192];
#define X_HALF(hf, TG) \
      _Pragma("unroll") for (int jp = 4 * (hf); jp < 4 * (hf) + 4; ++jp) \
        stsm_tag(sb + (XS + (hf)) * SLOT + rowo + (X ^ ((jp & 3) << 5)), \
                 pack_bf16(acc[128 + 8 * jp], acc[129 + 8 * jp]), pack_bf16(acc[130 + 8 * jp], acc[131 + 8 * jp]), \
                 pack_bf16(acc[132 + 8 * jp], acc[133 + 8 * jp]), pack_bf16(acc[134 + 8 * jp], acc[135 + 8 * jp]), TG, jp & 3);
#pragma unroll
  for (int i = 128; i < 192; ++i) acc[i] = 0.f;
#pragma unroll 1
  for (int layer = 0;; ++layer) {
    {
      PHASE_CTX();
      const uint32_t wu = c.cu >> 2;
      const uint32_t dA0 = (((sb + wu * 8192) & 0x3FFFF) >> 4) | (1u << 16), dB0 = ((sb & 0x3FFFF) >> 4) | (512u << 16);
      {
        PROFX(0);
        mbar_wait(bar + B_FULLS, 0);
        PROFX(1);
        wgmma_fence();
        wgmma_n256_0(acc, D128(dA0 + XS * 1024), D128(dB0 + 2048));
#pragma unroll
        for (int k = 1; k < 4; ++k) wgmma_n256(acc, D128(dA0 + XS * 1024 + k * 2), D128(dB0 + 2048 + k * 128), 1);
        wgmma_commit();
        wgmma_wait<1>();
        float s0 = 0.f, s1 = 0.f, q0 = 0.f, q1 = 0.f;
        if (layer) {
          X_HALF(1, (Tag{0u, 0u, 0u}));
#pragma unroll
          for (int i = 128; i < 192; i += 4) {
            s0 += acc[i] + acc[i + 1]; s1 += acc[i + 2] + acc[i + 3];
            q0 = fmaf(acc[i], acc[i], fmaf(acc[i + 1], acc[i + 1], q0)); q1 = fmaf(acc[i + 2], acc[i + 2], fmaf(acc[i + 3], acc[i + 3], q1));
          }
        }
        asm volatile("" : "+f"(s0), "+f"(s1), "+f"(q0), "+f"(q1) :: "memory");
        wgmma_fence();
        wgmma_n128_0(acc, D128(dA0 + XS * 1024), D128(dB0 + 1024));
#pragma unroll
        for (int k = 1; k < 4; ++k) wgmma_n128(acc, D128(dA0 + XS * 1024 + k * 2), D128(dB0 + 1024 + k * 128), 1);
        wgmma_commit();
        if (layer) {
          PHASE_CTX();
          fence_async_smem();
          nbar_dyn(3 + wu, 128);
          stats_out(s0, s1, q0, q1, g_stats + layer * S_ + m0 + wrow0 + gq, t);
          PROFT(tid_ == 128, layer * 16 + 8);
        }
      }
      uint32_t s = 1, u = 0, sp = 0;
      const int ix = layer ? 99 : 2 * min(g, NCOM) + 1;
#pragma unroll 1
      for (int i = 1; i < 14; ++i) {
        mbar_wait(bar + B_FULLS + s * 8, (u + (s ? layer : 0)) & 1);
        if (layer && (unsigned)(i - 2) < 7u) {
          PHASE_CTX();
          tile_check(sb + ((QA >> (4 * s)) & 15) * SLOT, g_x + (size_t)m0 * D_ + ((2 * g + 2 * i - 2) & 15) * 64, wrow0, lane, lds_vol(sb + SM_EPOCH) + layer);
        }
        const uint32_t da = dA0 + ((QA >> (4 * s)) & 15) * 1024, dk = dB0 + ((QK >> (4 * s)) & 15) * 1024,
                       dq = dB0 + ((QQ >> (4 * s)) & 15) * 1024;
        wgmma_fence();
#pragma unroll
        for (int k = 0; k < 4; ++k) {
          wgmma_n256(acc, D128(da + k * 2), D128(dk + k * 128), 1);
          wgmma_n128(acc, D128(da + k * 2), D128(dq + k * 128), 1);
          if (k == 0) {
            wgmma_commit();
            wgmma_wait<1>();
            if (elected && (unsigned)(i - ix) >= 2u) release2(bar + B_EMPTYS + sp * 8);
          }
        }
        wgmma_commit();
        if ((unsigned)(i - ix) < 2u) {
          PHASE_CTX();
          {
            float s0 = 0.f, s1 = 0.f, q0 = 0.f, q1 = 0.f;
            const uint32_t xa = sb + ((QA >> (4 * sp)) & 15) * SLOT + rowo;
#pragma unroll
            for (int jp = 0; jp < 4; ++jp) {
              uint32_t x0, x1, x2, x3;
              ldsm_x4(x0, x1, x2, x3, xa + (X ^ (jp << 5)));
              s0 += (bf_lo(x0) + bf_hi(x0)) + (bf_lo(x2) + bf_hi(x2));
              s1 += (bf_lo(x1) + bf_hi(x1)) + (bf_lo(x3) + bf_hi(x3));
              q0 = fmaf(bf_lo(x0), bf_lo(x0), fmaf(bf_hi(x0), bf_hi(x0), fmaf(bf_lo(x2), bf_lo(x2), fmaf(bf_hi(x2), bf_hi(x2), q0))));
              q1 = fmaf(bf_lo(x1), bf_lo(x1), fmaf(bf_hi(x1), bf_hi(x1), fmaf(bf_lo(x3), bf_lo(x3), fmaf(bf_hi(x3), bf_hi(x3), q1))));
            }
            stats_out(s0, s1, q0, q1, g_stats + m0 + wrow0 + gq, t);
          }
          __syncwarp();
          if (lane == 0 && i != ix) mbar_arrive(bar + B_XDONE);
          nbar_dyn(3 + wu, 128);
          if (elected) release2(bar + B_EMPTYS + sp * 8);
        }
        if (i == 1 && layer) {
          PHASE_CTX();
          slab_out_half(sb + (XS + 1) * SLOT, g_x + (size_t)m0 * D_ + g * 128 + 64, wrow0, lane);
          __syncwarp();
          if (lane == 0) mbar_arrive(bar + B_XDONE);
          nbar_dyn(3 + wu, 128);
        }
        sp = s;
        if (++s == 3) { s = 0; ++u; }
      }
      {
        const uint64_t dap = make_desc_ns(sb + SM_AP + wu * 1024, 0, 128), dbp = make_desc_ns(sb + SM_BP + (layer & 1) * 6144, 0, 128);
        if (wu == 0) {
          wgmma_wait<0>();
          if (elected) mbar_arrive(bar + B_R0);
          nbar<6, 256>();
        }
        if (layer < 2) mbar_wait(bar + (layer ? B_CS2 : B_CS), 0);
        mbar_wait(bar + B_STAT, layer & 1);
        mbar_wait(bar + B_FULLS + 16, layer & 1);
        wgmma_fence();
        wgmma_n256_k(acc, dap, dbp, 1);
#pragma unroll
        for (int k = 0; k < 4; ++k) wgmma_n256(acc, D128(dA0 + (QA >> 8) * 1024 + k * 2), D128(dB0 + (QK >> 8) * 1024 + k * 128), 1);
        mbar_wait(bar + B_FULLS, 1);
        PROFT(tid_ == 128, layer * 16 + 9);
        wgmma_fence();
#pragma unroll
        for (int k = 0; k < 4; ++k) wgmma_n256(acc, D128(dA0 + (QA & 15) * 1024 + k * 2), D128(dB0 + (QK & 15) * 1024 + k * 128), 1);
        wgmma_commit();
        if (wu) nbar<6, 256>();
#define Q_TAIL() \
        wgmma_n128_k(acc, dap, dbp + 256, 1); \
        _Pragma("unroll") for (int k = 0; k < 4; ++k) wgmma_n128(acc, D128(dA0 + (QA >> 8) * 1024 + k * 2), D128(dB0 + (QQ >> 8) * 1024 + k * 128), 1); \
        _Pragma("unroll") for (int k = 0; k < 4; ++k) wgmma_n128(acc, D128(dA0 + (QA & 15) * 1024 + k * 2), D128(dB0 + (QQ & 15) * 1024 + k * 128), 1);
        Q_TAIL();
        wgmma_commit();
        wgmma_wait<1>();
#pragma unroll
        for (int i = 0; i < 128; ++i) asm volatile("" : "+f"(acc[i]) :: "memory");
      }
    }
    uint32_t xo[32];
    uint32_t oq[8][4];
    {
      PHASE_CTX();
      PROFT(tid_ == 128, layer * 16 + 1);
      const bool isB = layer & 1;
      const int cu = c.cu;
      if (cu >= 4) asm volatile("bar.arrive 7, 256;" ::: "memory");
      if (elected && cu == 4) mbar_arrive(bar + B_R0);
      uint32_t kq[64];
      const uint32_t rowq = rowo & 8191;
      const float rs0 = lds_f(sb + SM_RS + (16 + wrow0 + gq) * 4), rs1 = lds_f(sb + SM_RS + (24 + wrow0 + gq) * 4);
#define Q_DONE() \
      wgmma_wait<0>(); \
      if (lane == 0) release2(bar + B_E0); \
      _Pragma("unroll") for (int i = 128; i < 192; ++i) asm volatile("" : "+f"(acc[i]) :: "memory"); \
      _Pragma("unroll") for (int i = 0; i < 32; ++i) kq[32 + i] = pack_bf16(acc[128 + 2 * i], acc[129 + 2 * i]);
      if (isB) {
        if (cu == 0) asm volatile("bar.arrive 10, 64;" ::: "memory");
        if (elected) release2(bar + B_E1);
        const int e = gq & 1;
        const bool sel = t > (gq >> 1);
        const uint32_t rja = sb + SM_RS + (wrow0 + 2 * t + e) * 4;
        const float rjA0 = lds_f(rja + 32), rjA1 = lds_f(rja + 64), rjB0 = lds_f(rja + (sel ? 0 : 64)), rjB1 = lds_f(rja + (sel ? 32 : 96));
        uint32_t vv[32];
#pragma unroll
        for (int i = 0; i < 16; ++i) { kq[i] = pack_bf16(acc[2 * i], acc[2 * i + 1]); vv[i] = pack_bf16(acc[64 + 2 * i], acc[65 + 2 * i]); }
        const uint32_t rB = sb + 4 * SLOT + wg * 4 * KVT + rowq;
        auto dump = [&](int hp) {
          const uint32_t kb = rB + 2048 + (hp ^ wg) * 2 * KVT;
#pragma unroll
          for (int jp = 0; jp < 4; ++jp) {
            stsm_x4(kb + (X ^ (jp << 5)), kq[16 * hp + 4 * jp], kq[16 * hp + 4 * jp + 1], kq[16 * hp + 4 * jp + 2], kq[16 * hp + 4 * jp + 3]);
            stsm_x4(kb + KVT + (X ^ (jp << 5)), vv[16 * hp + 4 * jp], vv[16 * hp + 4 * jp + 1], vv[16 * hp + 4 * jp + 2], vv[16 * hp + 4 * jp + 3]);
          }
          if (cu == 3) {
            const uint32_t kd = rB + 2048 + 32768 + (1 - hp) * 2 * KVT;
#pragma unroll
            for (int jp = 0; jp < 4; ++jp) {
              stsm_x4(kd + (X ^ (jp << 5)), kq[16 * hp + 4 * jp], kq[16 * hp + 4 * jp + 1], kq[16 * hp + 4 * jp + 2], kq[16 * hp + 4 * jp + 3]);
              stsm_x4(kd + KVT + (X ^ (jp << 5)), vv[16 * hp + 4 * jp], vv[16 * hp + 4 * jp + 1], vv[16 * hp + 4 * jp + 2], vv[16 * hp + 4 * jp + 3]);
            }
            if (hp) asm volatile("bar.arrive 15, 64;" ::: "memory"); else asm volatile("bar.arrive 9, 64;" ::: "memory");
          }
          asm volatile("bar.arrive %0, 224;" :: "r"(hp ? 13 + (cu >> 2) : 8 + (cu & 4)) : "memory");
        };
        uint4* const hbuf = g_halo + ((c.rb * 8 + g) * 2 + (layer >> 1)) * 512 + lane;
        if (cu < 4) {
          nbar<7, 256>();
          dump(0);
        }
#pragma unroll
        for (int i = 16; i < 32; ++i) { kq[i] = pack_bf16(acc[2 * i], acc[2 * i + 1]); vv[i] = pack_bf16(acc[64 + 2 * i], acc[65 + 2 * i]); }
        if (cu >= 4) {
          if (cu == 7) {
#pragma unroll
            for (int jp = 0; jp < 8; ++jp) {
              st_relaxed4(hbuf + jp * 32, ~kq[4 * jp], ~kq[4 * jp + 1], ~kq[4 * jp + 2], ~kq[4 * jp + 3]);
              st_relaxed4(hbuf + 256 + jp * 32, ~vv[4 * jp], ~vv[4 * jp + 1], ~vv[4 * jp + 2], ~vv[4 * jp + 3]);
            }
          }
          dump(0);
          dump(1);
        }
        PROFT(tid_ == 128, layer * 16 + 2);
        constexpr float SC = 0.17677669529663687f * L2E;
        const float fA0 = rjA0 * rs0 * SC, fB0 = rjB0 * rs0 * SC, fA1 = rjA1 * rs1 * SC, fB1 = rjB1 * rs1 * SC;
        const float bA0 = (m0 + wrow0) ? 0.f : -1e30f, bB = sel ? bA0 : 0.f;
        const uint32_t pA_ = e ? 0x1044u : 0x4410u, pB_ = e ? 0x3244u : 0x4432u, pLo = sel ? pB_ : 0x4444u, pHi = sel ? 0x4444u : pB_;
        const uint32_t KX = ((lane >> 3) ^ (lane & 7)) << 4;
        Q_DONE();
        if (cu == 0) {
          nbar<11, 64>();
        } else if (cu == 4) {
          uint4 hv[16];
          if (c.rb > 0) {
            uint32_t n = 0;
#pragma unroll 1
            while (true) {
              uint32_t mn = 0xFFFFFFFFu;
#pragma unroll
              for (int i = 0; i < 16; ++i) hv[i] = ld_relaxed4(hbuf - 16 * 512 + i * 32);
#pragma unroll
              for (int i = 0; i < 16; ++i) mn = __vimin3_u32(__vimin3_u32(mn, hv[i].x, hv[i].y), hv[i].z, hv[i].w);
              if (__all_sync(0xffffffffu, mn != 0u)) break;
              if (++n > (1u << 20)) { g_err = 4u; break; }
            }
          } else {
#pragma unroll
            for (int i = 0; i < 16; ++i) hv[i] = make_uint4(~0u, ~0u, ~0u, ~0u);
          }
          nbar<10, 64>();
#pragma unroll
          for (int i = 0; i < 16; ++i)
            stsm_x4(rB - 4 * KVT + (((i >> 2) & 1) * 2 + (i >> 3)) * KVT + (X ^ ((i & 3) << 5)), ~hv[i].x, ~hv[i].y, ~hv[i].z, ~hv[i].w);
          asm volatile("bar.arrive 11, 64;" ::: "memory");
          nbar<9, 64>();
        } else {
          nbar_dyn(8 + (cu & 4), 224);
        }
        PROFT(tid_ == 128, layer * 16 + 5);
        PROFT(lane == 0 && layer == PL, 136 + cw);
        auto attend = [&](int hp) {
          const uint32_t qad = sb + (XS + 1 - hp) * SLOT + rowo, kt = rB + 2 * (hp ^ wg) * KVT - (lane & 8) * 128, vt = rB + (2 * (hp ^ wg) + 1) * KVT;
          __syncwarp();
          uint32_t kb[2][2][4], vb[2][2][2][4];
#pragma unroll
          for (int h = 0; h < 2; ++h)
#pragma unroll
            for (int nt = 0; nt < 2; ++nt) ldsm_x4(kb[h][nt][0], kb[h][nt][1], kb[h][nt][2], kb[h][nt][3], kt + nt * 1024 + (KX ^ (h << 6)));
#pragma unroll
          for (int ks = 0; ks < 2; ++ks)
#pragma unroll
            for (int np = 0; np < 2; ++np)
#pragma unroll
              for (int h = 0; h < 2; ++h)
                ldsm_x4_t(vb[h][ks][np][0], vb[h][ks][np][1], vb[h][ks][np][2], vb[h][ks][np][3], vt + ks * 2048 + (X ^ (h << 6) ^ (np << 5)));
          if (hp == 0 && lane == 0) release2(bar + B_E3);
          float la[2][2], lb[2][2], mx[2][2], sm[2][2];
#pragma unroll
          for (int h = 0; h < 2; ++h) {
            const int qo = 32 + 16 * hp + 8 * h, ko = 16 * hp + 8 * h;
            float sc[4][4];
#pragma unroll
            for (int nt = 0; nt < 4; ++nt) {
              sc[nt][0] = sc[nt][1] = sc[nt][2] = sc[nt][3] = 0.f;
#pragma unroll
              for (int ks = 0; ks < 2; ++ks)
                mma_bf16(sc[nt], kq[qo + 4 * ks], kq[qo + 4 * ks + 1], kq[qo + 4 * ks + 2], kq[qo + 4 * ks + 3],
                         nt < 2 ? kb[h][nt & 1][2 * ks] : kq[ko + 4 * ks + (nt & 1)], nt < 2 ? kb[h][nt & 1][2 * ks + 1] : kq[ko + 4 * ks + 2 + (nt & 1)]);
            }
            la[h][0] = fmaf(e ? sc[1][1] : sc[1][0], fA0, bA0);
            lb[h][0] = fmaf(sel ? (e ? sc[0][1] : sc[0][0]) : (e ? sc[2][1] : sc[2][0]), fB0, bB);
            la[h][1] = (e ? sc[2][3] : sc[2][2]) * fA1;
            lb[h][1] = fmaf(sel ? (e ? sc[1][3] : sc[1][2]) : (e ? sc[3][3] : sc[3][2]), fB1, bB);
            mx[h][0] = fmaxf(la[h][0], lb[h][0]); mx[h][1] = fmaxf(la[h][1], lb[h][1]);
          }
#pragma unroll
          for (int o = 1; o <= 2; o <<= 1)
#pragma unroll
            for (int h = 0; h < 2; ++h)
#pragma unroll
              for (int r = 0; r < 2; ++r) mx[h][r] = fmaxf(mx[h][r], __shfl_xor_sync(0xffffffffu, mx[h][r], o));
          float oa[2][4][4];
#pragma unroll
          for (int h = 0; h < 2; ++h) {
#pragma unroll
            for (int r = 0; r < 2; ++r) { la[h][r] = ex2(la[h][r] - mx[h][r]); lb[h][r] = ex2(lb[h][r] - mx[h][r]); sm[h][r] = la[h][r] + lb[h][r]; }
            const uint32_t p0 = pack_bf16(la[h][0] * rjA0, lb[h][0] * rjB0), p1 = pack_bf16(la[h][1] * rjA1, lb[h][1] * rjB1);
            const uint32_t a00 = __byte_perm(p0, 0u, pLo), a02 = __byte_perm(p0, 0u, pA_), a03 = __byte_perm(p1, 0u, pLo);
            const uint32_t a10 = __byte_perm(p0, 0u, pHi), a11 = __byte_perm(p1, 0u, pA_), a13 = __byte_perm(p1, 0u, pHi);
#pragma unroll
            for (int i = 0; i < 4; ++i) {
              oa[h][i][0] = oa[h][i][1] = oa[h][i][2] = oa[h][i][3] = 0.f;
              mma_bf16(oa[h][i], a00, 0u, a02, a03, vb[h][0][i >> 1][2 * (i & 1)], vb[h][0][i >> 1][2 * (i & 1) + 1]);
              mma_bf16(oa[h][i], a10, a11, 0u, a13, vb[h][1][i >> 1][2 * (i & 1)], vb[h][1][i >> 1][2 * (i & 1) + 1]);
            }
          }
#pragma unroll
          for (int o = 1; o <= 2; o <<= 1)
#pragma unroll
            for (int h = 0; h < 2; ++h)
#pragma unroll
              for (int r = 0; r < 2; ++r) sm[h][r] += __shfl_xor_sync(0xffffffffu, sm[h][r], o);
          mbar_wait(bar + (hp ? B_XOLD2 : B_XOLD), 1);
#pragma unroll
          for (int jp = 0; jp < 4; ++jp) ldsm_x4(xo[16 * hp + 4 * jp], xo[16 * hp + 4 * jp + 1], xo[16 * hp + 4 * jp + 2], xo[16 * hp + 4 * jp + 3], qad + (X ^ (jp << 5)));
#pragma unroll
          for (int h = 0; h < 2; ++h) {
            const float i0 = rcp(sm[h][0]), i1 = rcp(sm[h][1]);
#pragma unroll
            for (int np = 0; np < 2; ++np)
            {
              uint32_t (&o)[4] = oq[4 * hp + 2 * h + np];
              o[0] = pack_bf16(oa[h][2 * np][0] * i0, oa[h][2 * np][1] * i0); o[1] = pack_bf16(oa[h][2 * np][2] * i1, oa[h][2 * np][3] * i1);
              o[2] = pack_bf16(oa[h][2 * np + 1][0] * i0, oa[h][2 * np + 1][1] * i0); o[3] = pack_bf16(oa[h][2 * np + 1][2] * i1, oa[h][2 * np + 1][3] * i1);
              stsm_tag(qad + (X ^ (h << 6) ^ (np << 5)), o[0], o[1], o[2], o[3], make_tag(gq, t, 0u), 2 * h + np);
            }
          }
          __syncwarp();
          slab_out_half(sb + (XS + 1 - hp) * SLOT, g_o + (size_t)m0 * D_ + g * 128 + hp * 64, wrow0, lane);
          __syncwarp();
          if (lane == 0) mbar_arrive(bar + (hp ? B_ODONE : B_OH1));
          PROFT(lane == 0 && layer == PL && hp == 0, 128 + cw);
        };
        attend(0);
        if (cu < 4) dump(1);
        if (cu == 4) nbar<15, 64>();
        else if (cu != 0) nbar_dyn(13 + (cu >> 2), 224);
        attend(1);
      } else {
#pragma unroll
        for (int i = 0; i < 32; ++i) kq[i] = pack_bf16(acc[2 * i], acc[2 * i + 1]);
        if (cu < 4) nbar<7, 256>();
        {
          const uint32_t vb = sb + (5 + 3 * wg) * SLOT + (rowq >> 1) + ((lchk ^ ((lane & 7) >> 1)) << 4);
#pragma unroll
          for (int jp = 8; jp < 16; ++jp)
            stsm_x4((vb ^ ((jp & 1) << 5)) + ((jp >> 1) & 3) * 4096,
                    pack_bf16(acc[8 * jp], acc[8 * jp + 1]), pack_bf16(acc[8 * jp + 2], acc[8 * jp + 3]),
                    pack_bf16(acc[8 * jp + 4], acc[8 * jp + 5]), pack_bf16(acc[8 * jp + 6], acc[8 * jp + 7]));
        }
        PROFT(tid_ == 128, layer * 16 + 2);
        Q_DONE();
        const uint32_t pA = sb + (3 + 3 * wg) * SLOT + (rowo & 8191);
        float sc0 = rs0 * L2E, sc1 = rs1 * L2E;
        const uint32_t wa0 = sb + SM_WPHI + lrow * 80 + lchk * 16;
        const uint32_t wu = c.cu >> 2, par = (layer >> 1) & 1;
        float p[2][4][4];
        uint32_t raw[2][4][4], ph[2][4][4];
        float kva[20], oa[2][20];
        auto kv_start = [&](int hp) {
#pragma unroll
          for (int h = 0; h < 2; ++h)
#pragma unroll
            for (int cp = 0; cp < 4; ++cp)
              stsm_x4(pA + hp * 16384 + h * 8192 + (X ^ (cp << 5)), ph[h][cp][0], ph[h][cp][1], ph[h][cp][2], ph[h][cp][3]);
          PROFT(tid_ == 128, layer * 16 + 11);
          fence_async_smem();
          nbar<1, 256>();
          const uint32_t hu = 2 * hp + wu;
          const uint32_t dP = (((sb + 3 * SLOT + hu * 8192) & 0x3FFFF) >> 4) | (512u << 16);
          const uint32_t dV = (((sb + 5 * SLOT + hu * 4096) & 0x3FFFF) >> 4) | (((SM_SD - 5 * SLOT - hu * 4096) >> 4) << 16);
          wgmma_fence();
#pragma unroll
          for (int ks = 0; ks < 8; ++ks)
            wgmma_n40_tt(kva, desc64(dP + (ks >> 2) * 3072 + (ks & 3) * 128, 0x40000040u),
                         desc64(dV + (ks >> 2) * (3072u - (2816u << 16)) + (ks & 3) * 64, 0x80000020u), ks != 0);
          wgmma_commit();
        };
        auto kv_end = [&](int hp) {
          wgmma_wait<0>();
#pragma unroll
          for (int i = 0; i < 20; ++i) asm volatile("" : "+f"(kva[i]) :: "memory");
          nbar_dyn(3 + wu, 128);
          PROFT(tid_ == 128, layer * 16 + 12);
          const bool od = lane & 1;
#pragma unroll
          for (int i = 0; i < 4; ++i)
            sts128(sb + (3 + hp) * SLOT + (cw * 128 + i * 32 + lane) * 16,
                   make_uint4(__float_as_uint(kva[4 * i]), __float_as_uint(kva[4 * i + 1]), __float_as_uint(kva[4 * i + 2]),
                              __float_as_uint(od == (i >= 2) ? 1.f : kva[4 * i + 3])));
          sts128(sb + (6 + hp) * SLOT + wg * 8192 + (wq * 32 + lane) * 16,
                 make_uint4(__float_as_uint(od ? kva[11] : kva[3]), __float_as_uint(od ? kva[15] : kva[7]), __float_as_uint(od ? kva[18] : kva[16]), __float_as_uint(1.f)));
          fence_async_smem();
          __syncwarp();
          if (lane == 0) mbar_arrive(bar + B_KVDONE - hp * 32);
          PROFT(tid_ == 128, layer * 16 + 3);
        };
        const uint4* const kvg = g_kv + (g * 2 + (layer >> 1)) * 2560 + cw * 128 + lane;
        uint4 u[5];
        auto kv_load = [&](int hp) {
#pragma unroll
          for (int i = 0; i < 4; ++i) u[i] = ld_relaxed4(kvg + hp * 1280 + i * 32);
          u[4] = ld_relaxed4(kvg + hp * 1280 + 1024 - cw * 96);
        };
        auto o_start = [&](int hp, const uint32_t (&pq)[2][4][4]) {
          PROFT(tid_ == 128 && hp == 0, layer * 16 + 10);
          if (hp == 0) mbar_wait(bar + B_KVDONE - 32, par);
          const bool od = lane & 1;
          uint32_t n = 0;
#pragma unroll 1
          while (!__all_sync(0xffffffffu, (od ? u[2].w : u[0].w) == 0x41800000u && (od ? u[3].w : u[1].w) == 0x41800000u && u[4].w == 0x41800000u)) {
#pragma unroll 1
            while (__any_sync(0xffffffffu, u[4].w < KVTH) && ++n < (1u << 20)) u[4].w = ld_relaxed(&kvg[hp * 1280 + 1024 - cw * 96].w);
            if (++n > (1u << 20)) { g_err = 6u; break; }
            kv_load(hp);
          }
          PROFT(tid_ == 128 && hp == 0, layer * 16 + 5);
          if (!od) { u[0].w = u[4].x; u[1].w = u[4].y; } else { u[2].w = u[4].x; u[3].w = u[4].y; }
#pragma unroll
          for (int i = 0; i < 4; i += 2)
            stsm_x4(sb + (5 + 3 * hp) * SLOT + rowo + (X ^ ((i & 2) << 4)),
                    pack_bf16(__uint_as_float(u[i].x), __uint_as_float(u[i].y)), pack_bf16(__uint_as_float(u[i].z), __uint_as_float(u[i].w)),
                    pack_bf16(__uint_as_float(u[i + 1].x), __uint_as_float(u[i + 1].y)), pack_bf16(__uint_as_float(u[i + 1].z), __uint_as_float(u[i + 1].w)));
          const uint32_t z2 = pack_bf16(__uint_as_float(u[4].z), __uint_as_float(u[4].z));
          if (t < 2) sts128(sb + (5 + 3 * hp) * SLOT + (wrow0 + gq + 8 * t) * 128 + ((4 ^ gq) << 4), make_uint4(z2, z2, z2, z2));
          fence_async_smem();
          nbar<1, 256>();
          PROFT(tid_ == 128 && hp == 1, layer * 16 + 4);
          const uint32_t dK = (((sb + (5 + 3 * hp) * SLOT) & 0x3FFFF) >> 4) | (512u << 16);
          wgmma_fence();
#pragma unroll
          for (int ks = 0; ks < 4; ++ks) {
#pragma unroll
            for (int hh = 0; hh < 2; ++hh) wgmma_n40_rs(oa[hh], pq[hh][ks], D128(dK + hh * 512 + ks * 128), ks != 0);
          }
          wgmma_commit();
        };
        auto o_end = [&](int hp) {
          wgmma_wait<0>();
#pragma unroll
          for (int i = 0; i < 20; ++i) asm volatile("" : "+f"(oa[0][i]), "+f"(oa[1][i]) :: "memory");
#pragma unroll
          for (int hh = 0; hh < 2; ++hh) {
            const float i0 = rcp(oa[hh][16] + 1e-6f), i1 = rcp(oa[hh][18] + 1e-6f);
            const uint32_t qad = sb + (3 + hp) * SLOT + rowo, hx = hh << 6;
#pragma unroll
            for (int np = 0; np < 2; ++np)
            {
              uint32_t (&o)[4] = oq[4 * hp + 2 * hh + np];
              o[0] = pack_bf16(oa[hh][8 * np] * i0, oa[hh][8 * np + 1] * i0); o[1] = pack_bf16(oa[hh][8 * np + 2] * i1, oa[hh][8 * np + 3] * i1);
              o[2] = pack_bf16(oa[hh][8 * np + 4] * i0, oa[hh][8 * np + 5] * i0); o[3] = pack_bf16(oa[hh][8 * np + 6] * i1, oa[hh][8 * np + 7] * i1);
              stsm_tag(qad + (X ^ hx ^ (np << 5)), o[0], o[1], o[2], o[3], make_tag(gq, t, 1u), 2 * hh + np);
            }
          }
          __syncwarp();
          slab_out_half(sb + (3 + hp) * SLOT, g_o + (size_t)m0 * D_ + g * 128 + hp * 64, wrow0, lane);
          __syncwarp();
          if (lane == 0) mbar_arrive(bar + (hp ? B_ODONE : B_OH1));
        };
#define XO_LOAD() \
        mbar_wait(bar + B_XOLD, 0); \
        mbar_wait(bar + B_XOLD2, 0); \
        _Pragma("unroll") for (int jp = 0; jp < 8; ++jp) \
          ldsm_x4(xo[4 * jp], xo[4 * jp + 1], xo[4 * jp + 2], xo[4 * jp + 3], sb + (XS + 1 - (jp >> 2)) * SLOT + rowo + (X ^ ((jp & 3) << 5)));
#define SC_RELOAD() \
        sc0 = __uint_as_float(lds_vol(sb + SM_RS + (16 + wrow0 + gq) * 4)) * L2E; sc1 = __uint_as_float(lds_vol(sb + SM_RS + (24 + wrow0 + gq) * 4)) * L2E;
        __syncwarp();
        phi_proj<0>(p, kq, wa0);
        phi_exp(raw[0], p[0], sc0, sc1);
        phi_exp(raw[1], p[1], sc0, sc1);
        phi_proj<16>(p, kq, wa0 + 5120);
        phi_norm<0>(ph, raw, kq, wa0, sc0, sc1, rs0, rs1);
        kv_start(0);
        phi_exp(raw[0], p[0], sc0, sc1);
        kv_end(0);
        SC_RELOAD();
        XO_LOAD();
        phi_exp(raw[1], p[1], sc0, sc1);
        phi_proj<32>(p, kq, wa0);
        phi_norm<16>(ph, raw, kq, wa0 + 5120, sc0, sc1, rs0, rs1);
        kv_start(1);
        if (lane == 0) release2(bar + B_E3);
        phi_exp(raw[0], p[0], sc0, sc1);
        kv_end(1);
        SC_RELOAD();
        kv_load(0);
        phi_exp(raw[1], p[1], sc0, sc1);
        phi_proj<48>(p, kq, wa0 + 5120);
        phi_norm<32>(ph, raw, kq, wa0, sc0, sc1, 1.f, 1.f);
        o_start(0, ph);
        phi_exp(raw[0], p[0], sc0, sc1);
        o_end(0);
        SC_RELOAD();
        kv_load(1);
        phi_exp(raw[1], p[1], sc0, sc1);
        phi_norm<48>(ph, raw, kq, wa0 + 5120, sc0, sc1, 1.f, 1.f);
        o_start(1, ph);
        o_end(1);
      }
      __syncwarp();
      PROFT(lane == 0 && layer == PL, 216 + cw);
      if (lane == 0) mbar_arrive(bar + B_EPI);
      PROFT(tid_ == 128, layer * 16 + 6);
    }
    {
      PHASE_CTX();
      const uint32_t wu = c.cu >> 2;
      const uint32_t dA0 = (((sb + wu * 8192) & 0x3FFFF) >> 4) | (1u << 16), dB0 = ((sb & 0x3FFFF) >> 4) | (512u << 16);
#pragma unroll
      for (int i = 0; i < 32; ++i) { acc[128 + 2 * i] = bf_lo(xo[i]); acc[129 + 2 * i] = bf_hi(xo[i]); }
      uint64_t ta = ((layer & 1) ? WO_A1 : WO_A0) >> 8, tw = (layer & 1) ? WO_B1 : WO_B0;
      mbar_wait(bar + B_FULLT, layer & 1);
      mbar_wait(bar + B_FULLT + 8, layer & 1);
      PROFT(tid_ == 128 && layer == PL, 160);
      wgmma_fence();
#pragma unroll
      for (int k = 0; k < 8; ++k) wgmma_n128_rs(acc, oq[k], D128(dB0 + ((uint32_t)(tw >> (k & 4)) & 15) * 1024 + (k & 3) * 128), 1);
      wgmma_commit();
      tw >>= 8;
      if (lane == 0) release2(bar + B_E2);
#pragma unroll 1
      for (int i = 2; i < 16; ++i) {
        mbar_wait(bar + B_FULLT + i * 8, layer & 1);
        PROFT(tid_ == 128 && layer == PL, 160 + i);
        tile_check(sb + ((uint32_t)ta & 15) * SLOT, g_o + (size_t)m0 * D_ + ((2 * g + (int)(WOORD >> (4 * i))) & 15) * 64, wrow0, lane, ~layer);
        const uint32_t da = dA0 + ((uint32_t)ta & 15) * 1024, db = dB0 + ((uint32_t)tw & 15) * 1024;
        ta >>= 4; tw >>= 4;
        if (i == 15 && wu) nbar<6, 256>();
        wgmma_fence();
#pragma unroll
        for (int k = 0; k < 4; ++k) wgmma_n128(acc, D128(da + k * 2), D128(db + k * 128), 1);
        wgmma_commit();
        if (i == 15 && !wu) asm volatile("bar.arrive 6, 256;" ::: "memory");
        wgmma_wait<1>();
        if (elected && i < 12) release2(bar + B_CONS + (i - 1) * 8);
        if (elected && (unsigned)(i - 13) < 2u && layer + 1 < NLAYERS) release2(bar + B_EMPTYS + (i - 13) * 8);
      }
      const bool last = layer == NLAYERS - 1;
      Tag xt = make_tag(gq, last ? 4 : t, lds_vol(sb + SM_EPOCH) + layer + 1);
      asm volatile("" : "+r"(xt.me), "+r"(xt.mo), "+r"(xt.tg) :: "memory");
      wgmma_wait<0>();
#pragma unroll
      for (int i = 128; i < 192; ++i) asm volatile("" : "+f"(acc[i]) :: "memory");
      if (elected && !last) release2(bar + B_EMPTYS + 16);
      PROFT(tid_ == 128, layer * 16 + 7);
      X_HALF(0, xt);
      if (last) {
        __syncwarp();
        slab_out_half(sb + XS * SLOT, c.out + (size_t)m0 * D_ + g * 128, wrow0, lane);
        X_HALF(1, (Tag{0u, 0u, 0u}));
        __syncwarp();
        slab_out_half(sb + (XS + 1) * SLOT, c.out + (size_t)m0 * D_ + g * 128 + 64, wrow0, lane);
        __syncwarp();
        if (lane == 0) mbar_arrive(bar + B_XDONE);
        PROFT(tid_ == 128, layer * 16 + 24);
        break;
      }
      __syncwarp();
      slab_out_half(sb + XS * SLOT, g_x + (size_t)m0 * D_ + g * 128, wrow0, lane, true);
      __syncwarp();
      if (lane == 0) mbar_arrive(bar + B_XH0);
      nbar_dyn(3 + wu, 128);
    }
  }
}

__device__ __forceinline__ void flag_fetch(uint32_t bar, uint32_t cp, const unsigned int* f) {
  asm volatile("{\n.reg .pred p;\nelect.sync _|p, 0xffffffff;\n@p mbarrier.expect_tx.relaxed.cta.shared::cta.b64 [%2], 64;\n"
               "@p cp.async.bulk.shared::cluster.global.mbarrier::complete_tx::bytes [%0], [%1], 64, [%2];\n}\n"
               ::"r"(cp), "l"(f), "r"(bar + 128) : "memory");
}
__device__ __forceinline__ void src_wait_async(uint32_t bar, uint32_t cp, const unsigned int* f, unsigned int target, int kb, uint32_t& ready, int lane) {
  uint32_t n = 0;
#pragma unroll 1
  while (true) {
    ready |= __ballot_sync(0xffffffffu, (int)(lds_vol(cp + (lane & 15) * 4) - target) >= 0);
    if ((ready >> kb) & 1) break;
    if (n > (1u << 20)) { g_err = 5u; break; }
    if ((n++ & PMOD) == 0) flag_fetch(bar, cp, f);
    __nanosleep(PSL);
  }
}

__device__ __forceinline__ int kblock0(int i, int g) {
  const int j = i >> 1, p = max(g, NCOM) + j - NCOM;
  return (j < NCOM ? j : p < 8 ? p : p - 8 + NCOM) * 2 + (i & 1);
}

__device__ __forceinline__ int wo_kblock(int m, int g) { return (2 * g + (int)((WOORD >> (4 * m)) & 15)) & 15; }

__global__ void __cluster_dims__(2, 1, 1) __launch_bounds__(384, 1)
mega_kernel(const __grid_constant__ CUtensorMap tm_x0, const __grid_constant__ CUtensorMap tm_x,
            const __grid_constant__ CUtensorMap tm_o,
            const __grid_constant__ CUtensorMap tm_wA, const __grid_constant__ CUtensorMap tm_wB,
            const __grid_constant__ CUtensorMap tm_woA, const __grid_constant__ CUtensorMap tm_woB,
                        const bf16* __restrict__ wB, const bf16* __restrict__ wphi, bf16* __restrict__ out) {
  extern __shared__ uint8_t smem_raw[];
  const uint32_t sb = (smem_u32(smem_raw) + 1023u) & ~1023u;
  const uint32_t bar = sb + SM_BAR;
  const int warp = __shfl_sync(0xffffffffu, threadIdx.x >> 5, 0), lane = threadIdx.x & 31;
  uint32_t bid = blockIdx.x;
  if (MAP == 3 && gridDim.x == 128 + NX) {
    uint32_t tp;
    asm volatile("mov.u32 %0, %%smid;" : "=r"(tp));
    tp >>= 1;
    const uint32_t u7 = ((tp - 32) * 37) >> 8;
    bid = (tp < 32 ? tp : tp < 60 ? tp + 1 + u7 : tp < 62 ? tp + 4 : (tp - 58) * 8) * 2 + (bid & 1);
  }
  if (bid >= 128 || gridDim.x == NX) {
    const int xb = bid & (NX - 1);
    const int ch = threadIdx.x % 96, rg = threadIdx.x / 96, gg = xb * 2 + ch / 48, sec = (ch % 48) >> 4;
    const uint4* src = reinterpret_cast<const uint4*>(wB + (size_t)rg * 3072 + (sec == 2 ? 0 : 1024 + sec * 1024) + gg * 128 + (ch & 15) * 8);
    float s[8] = {0.f, 0.f, 0.f, 0.f, 0.f, 0.f, 0.f, 0.f};
#pragma unroll 1
    for (int r0 = 0; r0 < 256; r0 += 32) {
      uint4 v[32];
#pragma unroll
      for (int r = 0; r < 32; ++r) v[r] = __ldg(src + (size_t)(r0 + r) * 1536);
#pragma unroll
      for (int r = 0; r < 32; ++r) {
        s[0] += bf_lo(v[r].x); s[1] += bf_hi(v[r].x); s[2] += bf_lo(v[r].y); s[3] += bf_hi(v[r].y);
        s[4] += bf_lo(v[r].z); s[5] += bf_hi(v[r].z); s[6] += bf_lo(v[r].w); s[7] += bf_hi(v[r].w);
      }
    }
    float* cd = g_cs + (ld_relaxed(&g_epoch) & 1) * 6144 + 3072 + xb * 768 + ch * 8;
    red_add4(cd, s[0], s[1], s[2], s[3]);
    red_add4(cd + 4, s[4], s[5], s[6], s[7]);
    nbar<1, 384>();
    if (threadIdx.x < 2) flag_add(&g_csflag[8 + xb * 2 + threadIdx.x].v);
    return;
  }
  const int cr = bid & 1;
  const int g = bid >> 4;
  const int rb = bid & 15;
  const int m0 = rb * 128;

  if (warp < 4) {
    asm volatile("setmaxnreg.dec.sync.aligned.u32 40;");
    asm volatile("barrier.cluster.arrive.relaxed.aligned;" ::: "memory");
    const unsigned int epoch = warp ? ld_relaxed(&g_epoch) : 0u;
    if (warp) cluster_wait();
    unsigned int xbase = epoch * NLAYERS;
    auto wo_a = [&](int layer, int m1) {
      uint64_t ts = ((layer & 1) ? WO_A1 : WO_A0) >> (4 * m1), td = ((layer & 1) ? WO_DA1 : WO_DA0) >> (4 * m1), tk = WOORD >> (4 * m1);
      uint32_t ready = 0u;
#pragma unroll 1
      for (int m = m1; m < 16; ++m) {
        const int kb = (2 * g + (uint32_t)tk) & 15;
        uint32_t dst = sb + ((uint32_t)ts & 15) * SLOT, fb = bar + B_FULLT + m * 8, eb = bar + B_CONS + ((uint32_t)td & 15) * 8;
        int kc = kb * 64;
        ts >>= 4; td >>= 4; tk >>= 4;
        asm volatile("" : "+r"(dst), "+r"(fb), "+r"(eb), "+r"(kc));
        bool fr = false;
        if (!((ready >> kb) & 1)) {
          PROFT(m == 2 && lane == 0, 64 + layer * 16 + 2);
          if (EP && m > EP) src_wait_async(bar, bar + B_FLG, g_of + rb * 32, xbase + layer + 1, kb, ready, lane);
          else fr = src_wait_tma(g_of + rb * 32, xbase + layer + 1, 1u << kb, ready, lane, eb, layer & 1);
          fence_async_all();
        }
        if (m == 6) mbar_wait_u(bar + B_EPI, layer & 1);
        if (!fr) mbar_wait_u(eb, layer & 1);
        tma_2d_e(dst, &tm_o, kc, m0, fb);
        if (EP && m >= EP && (ready & 0xFFFFu) != 0xFFFFu) flag_fetch(bar, bar + B_FLG, g_of + rb * 32);
        PROFT(lane == 0 && layer == PL, 176 + m);
      }
    };
    auto wo_w = [&](int layer) {
      const CUtensorMap* tx = layer == 0 ? &tm_x0 : &tm_x;
      const CUtensorMap* two = (layer & 1) ? &tm_woB : &tm_woA;
      uint64_t ts = (layer & 1) ? WO_B1 : WO_B0, td = (layer & 1) ? WO_DB1 : WO_DB0, tk = WOORD;
      uint32_t pb = 0;
      fence_async_all();
      mbar_wait_u(bar + B_R0, layer & 1);
      expect_tx_e(bar + B_XOLD, 16384);
      tma_2d_e(sb + (XS + 1) * SLOT, tx, g * 128, m0, bar + B_XOLD);
#pragma unroll 1
      for (int m = 0; m < 16; ++m) {
        uint32_t dst = sb + ((uint32_t)ts & 15) * SLOT + cr * 8192, fb = bar + B_FULLT + m * 8, eb = bar + B_CONS + ((uint32_t)td & 15) * 8;
        int kc = ((2 * g + (uint32_t)tk) & 15) * 64;
        ts >>= 4; td >>= 4; tk >>= 4;
        asm volatile("" : "+r"(dst), "+r"(fb), "+r"(eb), "+r"(kc));
        if (eb < bar + B_E3 && pb >= bar + B_E3) mbar_wait_u(bar + B_E2, layer & 1);
        if (eb != pb) mbar_wait_u(eb, layer & 1);
        pb = eb;
        tma_2d_mc_e(dst, two, g * 128 + cr * 64, kc, fb);
        expect_tx_e(fb, m < 2 ? 16384 : 32768);
        PROFT(lane == 0 && layer == PL, 144 + m);
        if (m == ((layer & 1) ? 2 : 0)) {
          expect_tx_e(bar + B_XOLD2, 16384);
          tma_2d_e(sb + XS * SLOT, tx, g * 128 + 64, m0, bar + B_XOLD2);
        }
      }
    };
    if (warp == 0) {
      cluster_wait();
      PROFT(lane == 0, 125);
#pragma unroll 1
      for (int layer = 0; layer < NLAYERS; ++layer) {
        const CUtensorMap* tx = layer == 0 ? &tm_x0 : &tm_x;
        const CUtensorMap* tw = (layer & 1) ? &tm_wB : &tm_wA;
        uint32_t s = layer == 0, u = 0, ready = layer == 0 ? 0xFFFFu : 0u;
#pragma unroll 1
        for (int i = s; i < 16; ++i) {
          const int kb = layer == 0 ? kblock0(i, g) : wo_kblock(i, g), kc = kb * 64;
          const uint32_t fb = bar + B_FULLS + s * 8;
          const uint32_t kd = sb + (((QK >> (4 * s)) & 15) + cr) * SLOT, qd = sb + ((QQ >> (4 * s)) & 15) * SLOT + cr * 8192;
          const uint32_t need = 1u << kb;
          const bool ext = i >= 2 || layer == 0, early = ext && (ready & need) == need;
          mbar_wait_u(bar + B_EMPTYS + s * 8, (u + (s ? layer : 0) + 1) & 1);
          if (early) tma_2d_e(sb + ((QA >> (4 * s)) & 15) * SLOT, tx, kc, m0, fb);
          tma_2d_mc_e(kd, tw, 1024 + cr * 1024 + g * 128, kc, fb);
          tma_2d_mc_e(kd + 8192, tw, 1024 + cr * 1024 + g * 128 + 64, kc, fb);
          tma_2d_mc_e(qd, tw, g * 128 + cr * 64, kc, fb);
          expect_tx_e(fb, ext ? 65536 : 49152);
          PROFT(lane == 0 && layer == 0 && i == 1, 31);
          if (layer == 0 && g >= NCOM && i == XPF + (((g - NCOM) * XPM) >> 2)) {
            if (i <= 2) mbar_wait_u(bar + B_FULLS, 0);
            tma_pf_e(&tm_x0, g * 128, m0);
            tma_pf_e(&tm_x0, g * 128 + 64, m0);
          }
          if (layer < 2 && i >= PFS) {
            const int j = i - PFS;
            if (j < 2) tma_pf_e(layer ? &tm_woB : &tm_woA, g * 128 + j * 64, rb * 64);
            else if (j < 8 && layer == 0) tma_pf_e(&tm_wB, ((j >> 1) - 1) * 1024 + g * 128 + (j & 1) * 64, rb * 64);
          }
          if (ext && !early) {
            PROFT(i == 2 && lane == 0, 64 + layer * 16 + 0);
            src_wait_tma(g_xf + rb * 32, xbase + layer + 1, need, ready, lane, fb, 0);
            PROFT(i == 2 && lane == 0, 64 + layer * 16 + 1);
            fence_async_all();
            tma_2d_e(sb + ((QA >> (4 * s)) & 15) * SLOT, tx, kc, m0, fb);
          }
          if (++s == 3) { s = 0; ++u; }
        }
        if (layer == 0) xbase = ld_relaxed(&g_epoch) * NLAYERS;
        wo_a(layer, 2);
      }
    } else {
      if (warp >= 2) {
        const int h2 = threadIdx.x - 64;
        if (h2 < 16) sts_f(sb + SM_RS + h2 * 4, 0.f);
        if (h2 == 0) sts_f(sb + SM_EPOCH, __uint_as_float(epoch));
        if (h2 < 16) sts_f(bar + B_FLG + h2 * 4, __uint_as_float(xbase));
        mbar_wait_u(bar + B_FULLS, 0);
        colsum(&tm_wA, g_cs + (epoch & 1) * 6144, rb, g, warp - 2, 2, lane, warp == 2 ? sb + SM_SD : (sb + SM_BP + 1023u) & ~1023u, bar + B_CB + (warp - 2) * 8, 0);
#pragma unroll 1
        for (int i = h2; i < 320; i += 64) g_kv[(g * 16 + rb) * 320 + i] = make_uint4(0u, 0u, 0u, 0u);
        fence_async_all();
        nbar<5, 64>();
        if (h2 == 0) flag_add(&g_csflag[g].v);
        PROFT(h2 == 0, 242);
#pragma unroll 1
        for (int i = h2; i < 512; i += 256) {
          uint4 w[4];
#pragma unroll
          for (int j = 0; j < 4; ++j) w[j] = __ldg(reinterpret_cast<const uint4*>(wphi + (size_t)g * 4096) + i + j * 64);
#pragma unroll
          for (int j = 0; j < 4; ++j) sts128(sb + SM_WPHI + ((i >> 2) + j * 16) * 80 + (i & 3) * 16, w[j]);
        }
      }
      if (warp == 1) {
        if (lane >= 27) {
          const CUtensorMap* tm = lane == 27 ? &tm_o : lane == 28 ? &tm_wB : lane == 29 ? &tm_woA : lane == 30 ? &tm_woB : &tm_x;
          asm volatile("prefetch.tensormap [%0];" ::"l"(tm) : "memory");
        }
        __syncwarp();
        {
#pragma unroll 1
          for (int e = 0;; ++e) {
            if (e > 0 && e < NLAYERS) {
              mbar_wait_u(bar + B_XH0, (e - 1) & 1);
              flag_hint(g_xf + rb * 32 + 2 * g, xbase + e + 1);
            }
            mbar_wait_u(bar + B_XDONE, e & 1);
            PROFT(e < 4, 64 + e * 16 + 4);
            if (e == NLAYERS) {
              if (bid == 0) g_epoch = epoch + 1;
              break;
            }
            PROFT(e < 4, 64 + e * 16 + 5);
            flag_set(g_xf + rb * 32 + 2 * g + 1, xbase + e + 1);
            PROFT(e < 4, 64 + e * 16 + 7);
            if ((e & 1) == 0) {
#pragma unroll 1
              for (int hp = 0; hp < 2; ++hp) {
                uint4* kvl = g_kv + ((g * 2 + (e >> 1)) * 2 + hp) * 1280;
                mbar_wait_u(bar + B_KVDONE - hp * 32, (e >> 1) & 1);
                PROFT(e == PL, 243 + hp * 4);
                bulk_red_add_e(kvl + rb * 64, sb + (3 + hp) * SLOT + rb * 1024, 16384 - rb * 1024);
                if (rb) bulk_red_add_e(kvl, sb + (3 + hp) * SLOT, rb * 1024);
                bulk_red_add_e(kvl + 1024, sb + (6 + hp) * SLOT, 2048);
                bulk_red_add_e(kvl + 1152, sb + (6 + hp) * SLOT + 8192, 2048);
                bulk_commit();
                PROFT(e < 4, 64 + e * 16 + 6);
              }
              bulk_wait_read0();
              __syncwarp();
              if (lane < 2) release2(bar + B_E1);
              __syncwarp();
            }
            mbar_wait_u(bar + B_OH1, e & 1);
            PROFT(e == PL, 251);
            flag_hint(g_of + rb * 32 + 2 * g, xbase + e + 1);
            PROFT(e < 4, 64 + e * 16 + 9);
            mbar_wait_u(bar + B_ODONE, e & 1);
            PROFT(e < 4, 64 + e * 16 + 8);
            flag_hint(g_of + rb * 32 + 2 * g + 1, xbase + e + 1);
            PROFT(e < 4, 64 + e * 16 + 11);
          }
        }
      } else {
        const int h2 = threadIdx.x - 64;
        const float* cs = g_cs + (epoch & 1) * 6144;
#pragma unroll 1
        for (int layer = 0; layer < NLAYERS; ++layer) {
          if (warp == 2 && layer < 2) {
            if (lane == 0) flag_wait_t<128>(&g_csflag[layer * 8 + g].v, (epoch + 1) * (16u + layer));
            __syncwarp();
            float4 a[3];
#pragma unroll
            for (int i = 0; i < 3; ++i) a[i] = __ldcg(reinterpret_cast<const float4*>(cs + layer * 3072 + g * 384) + i * 32 + lane);
#pragma unroll 1
            for (int i = 0; i < 3; ++i) {
              const float av[4] = {a[0].x, a[0].y, a[0].z, a[0].w};
              a[0] = a[1]; a[1] = a[2];
#pragma unroll
              for (int j = 0; j < 4; ++j) {
                const float c1 = bf16r(av[j]), c2 = bf16r(av[j] - c1), c3 = (av[j] - c1) - c2;
                sts128(sb + SM_BP + layer * 6144 + ((i * 32 + lane) * 4 + j) * 16, make_uint4(pack_bf16(c1, c2), pack_bf16(c3, 0.f), 0u, 0u));
              }
            }
            fence_async_smem();
            __syncwarp();
            if (lane == 0) mbar_arrive(bar + (layer ? B_CS2 : B_CS));
            PROFT(lane == 0, 64 + layer * 16 + 12);
            if (layer == 0) {
              uint4* hz = g_halo + (rb * 8 + g) * 1024;
#pragma unroll 2
              for (int i = lane; i < 1024; i += 32) hz[i] = make_uint4(0u, 0u, 0u, 0u);
              if (lane < 12) reinterpret_cast<float4*>(g_cs + ((epoch & 1) ^ 1) * 6144 + bid * 48)[lane] = make_float4(0.f, 0.f, 0.f, 0.f);
              g_stats[(2 + (lane >> 4)) * S_ + m0 + g * 16 + (lane & 15)] = make_float2(0.f, 0.f);
              __syncwarp();
              if (lane == 0) flag_add(&g_csflag[8 + g].v);
            }
          }
          if (warp == 3) {
            const bool hal = (layer & 1) && rb > 0;
            {
              uint32_t rdy = 0u;
              src_wait<256>(g_xf + rb * 32, xbase + layer + 1, 0xAAAAu, rdy, lane);
              rdy = 0u;
              if (hal) src_wait<256>(g_xf + (rb - 1) * 32, xbase + layer + 1, 0xAAAAu, rdy, lane);
            }
            float2 u[5];
            const float2* sp = g_stats + layer * S_ + m0 + lane;
#pragma unroll
            for (int i = 0; i < 4; ++i) u[i] = __ldcg(sp + i * 32);
            u[4] = __ldcg(hal ? sp - 16 : sp);
            if (layer == 3) g_stats[(lane >> 4) * S_ + m0 + g * 16 + (lane & 15)] = make_float2(0.f, 0.f);
#pragma unroll
            for (int i = 0; i < 5; ++i) {
              const int r = i < 4 ? 16 + i * 32 + lane : lane;
              const float mean = u[i].x * (1.f / D_);
              const float var = fmaxf(fmaf(-u[i].x, mean, u[i].y) * (1.f / D_), 0.f);
              float sd;
              asm("sqrt.approx.f32 %0, %1;" : "=f"(sd) : "f"(bf16r(bf16r(var) + 1e-5f)));
              sd = bf16r(sd);
              if (i < 4 || hal) sts_f(sb + SM_RS + r * 4, rcp(sd));
              if (i < 4) {
                const float hm = -0.5f * bf16r(mean);
                const uint32_t s2 = pack_bf16(sd, sd);
                if (!(layer & 1)) sts128(sb + SM_SD + (r - 16) * 64 + ((r >> 1) & 3) * 16, make_uint4(s2, s2, s2, s2));
                sts128(sb + SM_AP + (r - 16) * 16, make_uint4(pack_bf16(hm, hm), pack_bf16(hm, 0.f), 0u, 0u));
              }
            }
            fence_async_smem();
            __syncwarp();
            if (lane == 0) mbar_arrive(bar + B_STAT);
            PROFT(lane == 0, 64 + layer * 16 + 14);
            wo_w(__shfl_sync(0xffffffffu, layer, 0));
          }
        }
      }
    }
    __syncwarp();
    asm volatile("barrier.cluster.arrive.relaxed.aligned;\nbarrier.cluster.wait.aligned;\n" ::: "memory");
  } else {
    if (warp == 5) {
      if (lane == 0) {
        mbar_init(bar + B_FULLS, 1);
        asm volatile("fence.mbarrier_init.release.cluster;" ::: "memory");
      }
      __syncwarp();
      expect_tx_e(bar + B_FULLS, 65536);
      tma_2d_e(sb + XS * SLOT, &tm_x0, 0, m0, bar + B_FULLS);
#pragma unroll
      for (int j = 0; j < 6; ++j)
        tma_2d_e(sb + (j < 4 ? j + 4 : j - 2) * 8192, &tm_wA, (j < 4 ? 1024 + (j >> 1) * 1024 : 0) + g * 128 + (j & 1) * 64, 0, bar + B_FULLS);
      PROFT(lane == 0, 241);
    }
    if (lane < 8 && warp != 5 && threadIdx.x != 128) {
      const int i = (warp - 4) * 8 + lane;
      mbar_init(bar + i * 8, i < 32 ? 1u << ((BAR_CNT >> (2 * i)) & 3) : i < 48 ? 1u : (i == 59 || i == 60 || i == 62) ? 16u : (i == 48 || i == 63) ? 8u : 4u);
      asm volatile("fence.mbarrier_init.release.cluster;" ::: "memory");
    }
    __syncwarp();
    asm volatile("barrier.cluster.arrive.relaxed.aligned;" ::: "memory");
    asm volatile("setmaxnreg.inc.sync.aligned.u32 232;");
    cluster_wait();
    PROFT(threadIdx.x == 128, 0);
    Ctx c; c.sb = sb; c.g = g; c.rb = rb; c.cu = warp - 4; c.out = out;
    consumer(c);
    asm volatile("bar.warp.sync 0xffffffff;\nbarrier.cluster.arrive.relaxed.aligned;\nbarrier.cluster.wait.aligned;\n" ::: "memory");
  }
}

typedef CUresult (*PFN_encodeTiled)(CUtensorMap*, CUtensorMapDataType, cuuint32_t, void*, const cuuint64_t*, const cuuint64_t*,
                                    const cuuint32_t*, const cuuint32_t*, CUtensorMapInterleave, CUtensorMapSwizzle,
                                    CUtensorMapL2promotion, CUtensorMapFloatOOBfill);

static CUtensorMap make_map(PFN_encodeTiled enc, const void* ptr, uint64_t cols, uint64_t rows, uint32_t box_c, uint32_t box_r, uint32_t nb = 1) {
  CUtensorMap m;
  cuuint64_t dims[3] = {nb > 1 ? box_c : cols, rows, cols / box_c};
  cuuint64_t strides[2] = {cols * 2, box_c * 2};
  cuuint32_t box[3] = {box_c, box_r, nb};
  cuuint32_t es[3] = {1, 1, 1};
  CUresult r = enc(&m, CU_TENSOR_MAP_DATA_TYPE_BFLOAT16, nb > 1 ? 3 : 2, const_cast<void*>(ptr), dims, strides, box, es, CU_TENSOR_MAP_INTERLEAVE_NONE,
      CU_TENSOR_MAP_SWIZZLE_128B, CU_TENSOR_MAP_L2_PROMOTION_L2_256B, CU_TENSOR_MAP_FLOAT_OOB_FILL_NONE);
  (void)r;
  return m;
}

extern "C" void kernel_launch(void* const* d_in, const int* in_sizes, int n_in, void* d_out, int out_size) {
  const bf16* A_x = (const bf16*)d_in[0];
  const bf16* A_wqkv = (const bf16*)d_in[1];
  const bf16* A_wphi = (const bf16*)d_in[2];
  const bf16* A_wo = (const bf16*)d_in[3];
  const bf16* B_wqkv = (const bf16*)d_in[5];
  const bf16* B_wo = (const bf16*)d_in[6];
  bf16* out = (bf16*)d_out;

  static PFN_encodeTiled enc = nullptr;
  static bf16 *p_x, *p_o;
  static bool together;
  if (!enc) {
    void* fn = nullptr; cudaDriverEntryPointQueryResult qr;
    cudaGetDriverEntryPoint("cuTensorMapEncodeTiled", &fn, cudaEnableDefault, &qr);
    enc = (PFN_encodeTiled)fn;
    cudaGetSymbolAddress((void**)&p_x, g_x);
    cudaGetSymbolAddress((void**)&p_o, g_o);
    cudaFuncSetAttribute(mega_kernel, cudaFuncAttributeMaxDynamicSharedMemorySize, SM_TOTAL);
    cudaLaunchConfig_t cfg = {};
    cfg.gridDim = dim3(128 + NX); cfg.blockDim = dim3(384); cfg.dynamicSmemBytes = SM_TOTAL;
    cudaLaunchAttribute at[1];
    at[0].id = cudaLaunchAttributeClusterDimension; at[0].val.clusterDim.x = 2; at[0].val.clusterDim.y = 1; at[0].val.clusterDim.z = 1;
    cfg.attrs = at; cfg.numAttrs = 1;
    int ncl = 0;
    together = cudaOccupancyMaxActiveClusters(&ncl, mega_kernel, &cfg) == cudaSuccess && 2 * ncl == 128 + NX;
    int nsm = 0;
    cudaDeviceGetAttribute(&nsm, cudaDevAttrMultiProcessorCount, 0);
    together = together && nsm == 128 + NX;
  }
  CUtensorMap tm_x0 = make_map(enc, A_x, 1024, 2048, 64, 128);
  CUtensorMap tm_x = make_map(enc, p_x, 1024, 2048, 64, 128);
  CUtensorMap tm_o = make_map(enc, p_o, 1024, 2048, 64, 128);
  CUtensorMap tm_wA = make_map(enc, A_wqkv, 3072, 1024, 64, 64);
  CUtensorMap tm_wB = make_map(enc, B_wqkv, 3072, 1024, 64, 64);
  CUtensorMap tm_woA = make_map(enc, A_wo, 1024, 1024, 64, 64);
  CUtensorMap tm_woB = make_map(enc, B_wo, 1024, 1024, 64, 64);
  if (!together) mega_kernel<<<NX, 384, SM_TOTAL, cudaStreamPerThread>>>(tm_x0, tm_x, tm_o, tm_wA, tm_wB, tm_woA, tm_woB, B_wqkv, A_wphi, out);
  mega_kernel<<<together ? 128 + NX : 128, 384, SM_TOTAL, cudaStreamPerThread>>>(tm_x0, tm_x, tm_o, tm_wA, tm_wB, tm_woA, tm_woB,
                                                                                 B_wqkv, A_wphi, out);
}
```

```cpp
#include <cuda_runtime.h>
#include <cuda_bf16.h>
#include <cuda.h>
#include <stdint.h>

typedef __nv_bfloat16 bf16;

constexpr int S_ = 2048, D_ = 1024;

struct __align__(128) Flag { unsigned int v; unsigned int pad[31]; };
__device__ __align__(1024) bf16 g_x[S_ * D_];
__device__ __align__(1024) bf16 g_o[S_ * D_];
__device__ __align__(1024) uint4 g_halo[128 * 2 * 512];
__device__ __align__(1024) uint4 g_kv[8 * 2 * 2 * 1280];
__device__ __align__(1024) float2 g_stats[4 * S_];
__device__ __align__(1024) float g_cs[2 * 2 * 3072];
__device__ Flag g_csflag[16];
__device__ __align__(128) unsigned int g_xf[16 * 32], g_of[16 * 32];
__device__ unsigned int g_epoch, g_err;
#define PROFT(cond, idx) asm volatile("" ::: "memory")

__device__ __forceinline__ uint32_t smem_u32(const void* p) { return (uint32_t)__cvta_generic_to_shared(p); }
__device__ __forceinline__ void mbar_init(uint32_t bar, uint32_t count) {
  asm volatile("mbarrier.init.shared::cta.b64 [%0], %1;" ::"r"(bar), "r"(count) : "memory");
}
__device__ __forceinline__ void mbar_expect_tx(uint32_t bar, uint32_t bytes) {
  asm volatile("mbarrier.arrive.expect_tx.shared::cta.b64 _, [%0], %1;" ::"r"(bar), "r"(bytes) : "memory");
}
__device__ __forceinline__ void mbar_arrive(uint32_t bar) {
  asm volatile("mbarrier.arrive.shared::cta.b64 _, [%0];" ::"r"(bar) : "memory");
}
__device__ __forceinline__ bool mbar_try_wait(uint32_t bar, uint32_t parity) {
  uint32_t ok;
  asm volatile("{\n.reg .pred p;\nmbarrier.try_wait.parity.shared::cta.b64 p, [%1], %2;\nselp.b32 %0, 1, 0, p;\n}\n"
               : "=r"(ok) : "r"(bar), "r"(parity) : "memory");
  return ok != 0;
}
__device__ __forceinline__ bool mbar_test_wait(uint32_t bar, uint32_t parity) {
  uint32_t ok;
  asm volatile("{\n.reg .pred p;\nmbarrier.test_wait.parity.shared::cta.b64 p, [%1], %2;\nselp.b32 %0, 1, 0, p;\n}\n"
               : "=r"(ok) : "r"(bar), "r"(parity) : "memory");
  return ok != 0;
}
__device__ __forceinline__ uint64_t gtimer() {
  uint64_t t; asm volatile("mov.u64 %0, %globaltimer;" : "=l"(t)); return t;
}
__device__ __forceinline__ void mbar_wait(uint32_t bar, uint32_t parity) {
  uint32_t n = 0;
#pragma unroll 1
  while (!mbar_try_wait(bar, parity)) {
    if (++n > (1u << 22)) { g_err = 1u; break; }
  }
}
__device__ __forceinline__ unsigned int ld_acquire(const unsigned int* p) {
  unsigned int v; asm volatile("ld.acquire.gpu.global.u32 %0, [%1];" : "=r"(v) : "l"(p) : "memory"); return v;
}
__device__ __forceinline__ void flag_add(unsigned int* p) {
  asm volatile("red.release.gpu.global.add.u32 [%0], 1;" ::"l"(p) : "memory");
}
__device__ __forceinline__ void flag_set(unsigned int* p, unsigned int v) {
  asm volatile("st.release.gpu.global.u32 [%0], %1;" ::"l"(p), "r"(v) : "memory");
}
__device__ __forceinline__ void flag_hint(unsigned int* p, unsigned int v) {
  asm volatile("st.relaxed.gpu.global.u32 [%0], %1;" ::"l"(p), "r"(v) : "memory");
}
template <int SLEEP>
__device__ __forceinline__ void src_wait(const unsigned int* f, unsigned int target, uint32_t need, uint32_t& ready, int lane) {
  uint32_t n = 0;
#pragma unroll 1
  while ((ready & need) != need) {
    const unsigned int v = ld_acquire(f + (lane & 15));
    ready = __ballot_sync(0xffffffffu, (int)(v - target) >= 0);
    if (SLEEP) { if ((ready & need) != need) __nanosleep(SLEEP); }
    if (++n > (1u << 20)) { g_err = 3u; break; }
  }
  __syncwarp();
}
__device__ __forceinline__ unsigned int ld_relaxed(const unsigned int* p) {
  unsigned int v; asm volatile("ld.relaxed.gpu.global.u32 %0, [%1];" : "=r"(v) : "l"(p) : "memory"); return v;
}
__device__ __forceinline__ bool src_wait_tma(const unsigned int* f, unsigned int target, uint32_t need, uint32_t& ready, int lane, uint32_t eb, uint32_t par) {
  uint32_t n = 0;
  bool fr = false;
#pragma unroll 1
  while ((ready & need) != need) {
    const unsigned int v = ld_acquire(f + (lane & 15));
    fr = __all_sync(0xffffffffu, mbar_test_wait(eb, par));
    ready = __ballot_sync(0xffffffffu, (int)(v - target) >= 0);
    if (++n > (1u << 20)) { g_err = 3u; break; }
  }
  return fr;
}
__device__ __forceinline__ uint4 ld_relaxed4(const uint4* p) {
  uint4 v; asm volatile("ld.relaxed.gpu.global.v4.u32 {%0,%1,%2,%3}, [%4];" : "=r"(v.x), "=r"(v.y), "=r"(v.z), "=r"(v.w) : "l"(p) : "memory"); return v;
}
__device__ __forceinline__ void st_relaxed4(uint4* p, uint32_t a, uint32_t b, uint32_t c, uint32_t d) {
  asm volatile("st.relaxed.gpu.global.v4.u32 [%0], {%1,%2,%3,%4};" ::"l"(p), "r"(a), "r"(b), "r"(c), "r"(d) : "memory");
}
template <int SLEEP>
__device__ __forceinline__ void flag_wait_t(const unsigned int* p, unsigned int target) {
  uint32_t n = 0;
#pragma unroll 1
  while ((int)(ld_acquire(p) - target) < 0) {
    if (SLEEP) __nanosleep(SLEEP);
    if (++n > (1u << 20)) { g_err = 2u; break; }
  }
}
__device__ __forceinline__ void flag_wait(const unsigned int* p, unsigned int target) { flag_wait_t<0>(p, target); }
__device__ __forceinline__ void flag_wait_slow(const unsigned int* p, unsigned int target) { flag_wait_t<256>(p, target); }
__device__ __forceinline__ void tma_load_2d(uint32_t dst, const CUtensorMap* tm, int c0, int c1, uint32_t bar) {
  asm volatile("cp.async.bulk.tensor.2d.shared::cluster.global.mbarrier::complete_tx::bytes [%0], [%1, {%2, %3}], [%4];"
               ::"r"(dst), "l"(tm), "r"(c0), "r"(c1), "r"(bar) : "memory");
}
__device__ __forceinline__ void tma_load_2d_mc(uint32_t dst, const CUtensorMap* tm, int c0, int c1, uint32_t bar, uint16_t mask) {
  asm volatile("cp.async.bulk.tensor.2d.shared::cluster.global.mbarrier::complete_tx::bytes.multicast::cluster [%0], [%1, {%2, %3}], [%4], %5;"
               ::"r"(dst), "l"(tm), "r"(c0), "r"(c1), "r"(bar), "h"(mask) : "memory");
}
__device__ __forceinline__ void mbar_wait_u(uint32_t bar, uint32_t parity) {
  uint32_t n = 0;
#pragma unroll 1
  while (!__all_sync(0xffffffffu, mbar_try_wait(bar, parity))) {
    if (++n > (1u << 22)) { g_err = 1u; break; }
  }
}
__device__ __forceinline__ void expect_tx_e(uint32_t bar, uint32_t bytes) {
  asm volatile("{\n.reg .pred p;\nelect.sync _|p, 0xffffffff;\n@p mbarrier.arrive.expect_tx.shared::cta.b64 _, [%0], %1;\n}\n" ::"r"(bar), "r"(bytes) : "memory");
}
__device__ __forceinline__ void tma_2d_e(uint32_t dst, const CUtensorMap* tm, int c0, int c1, uint32_t bar) {
  asm volatile("{\n.reg .pred p;\nelect.sync _|p, 0xffffffff;\n"
               "@p cp.async.bulk.tensor.2d.shared::cluster.global.mbarrier::complete_tx::bytes [%0], [%1, {%2, %3}], [%4];\n}\n"
               ::"r"(dst), "l"(tm), "r"(c0), "r"(c1), "r"(bar) : "memory");
}
__device__ __forceinline__ void tma_2d_mc_e(uint32_t dst, const CUtensorMap* tm, int c0, int c1, uint32_t bar) {
  asm volatile("{\n.reg .pred p;\nelect.sync _|p, 0xffffffff;\n"
               "@p cp.async.bulk.tensor.2d.shared::cluster.global.mbarrier::complete_tx::bytes.multicast::cluster [%0], [%1, {%2, %3}], [%4], %5;\n}\n"
               ::"r"(dst), "l"(tm), "r"(c0), "r"(c1), "r"(bar), "h"((uint16_t)3) : "memory");
}
__device__ __forceinline__ void tma_pf_e(const CUtensorMap* tm, int c0, int c1) {
  asm volatile("{\n.reg .pred p;\nelect.sync _|p, 0xffffffff;\n"
               "@p cp.async.bulk.prefetch.tensor.2d.L2.global.tile [%0, {%1, %2}];\n}\n" ::"l"(tm), "r"(c0), "r"(c1) : "memory");
}
__device__ __forceinline__ void tma_2d_to_e(uint32_t dst, const CUtensorMap* tm, int c0, int c1, uint32_t bar, uint32_t mask) {
  asm volatile("{\n.reg .pred p;\nelect.sync _|p, 0xffffffff;\n"
               "@p cp.async.bulk.tensor.2d.shared::cluster.global.mbarrier::complete_tx::bytes.multicast::cluster [%0], [%1, {%2, %3}], [%4], %5;\n}\n"
               ::"r"(dst), "l"(tm), "r"(c0), "r"(c1), "r"(bar), "h"((uint16_t)mask) : "memory");
}
__device__ __forceinline__ void tma_3d_mc_e(uint32_t dst, const CUtensorMap* tm, int c1, int c2, uint32_t bar) {
  asm volatile("{\n.reg .pred p;\nelect.sync _|p, 0xffffffff;\n"
               "@p cp.async.bulk.tensor.3d.shared::cluster.global.mbarrier::complete_tx::bytes.multicast::cluster [%0], [%1, {%6, %2, %3}], [%4], %5;\n}\n"
               ::"r"(dst), "l"(tm), "r"(c1), "r"(c2), "r"(bar), "h"((uint16_t)3), "r"(0) : "memory");
}
__device__ __forceinline__ uint32_t poll_flags(const unsigned int* f, unsigned int target, int lane) {
  const unsigned int v = ld_acquire(f + (lane & 15));
  const uint32_t r = __ballot_sync(0xffffffffu, (int)(v - target) >= 0);
  __syncwarp();
  return r;
}
__device__ __forceinline__ void mbar_arrive_cluster(uint32_t local_bar, uint32_t rank) {
  asm volatile("{\n.reg .b32 ra;\nmapa.shared::cluster.u32 ra, %0, %1;\nmbarrier.arrive.shared::cluster.b64 _, [ra];\n}\n"
               ::"r"(local_bar), "r"(rank) : "memory");
}
__device__ __forceinline__ void release2(uint32_t bar) { mbar_arrive_cluster(bar, 0); mbar_arrive_cluster(bar, 1); }
__device__ __forceinline__ void tma_store_2d(const CUtensorMap* tm, uint32_t src, int c0, int c1) {
  asm volatile("cp.async.bulk.tensor.2d.global.shared::cta.bulk_group [%0, {%2, %3}], [%1];"
               ::"l"(tm), "r"(src), "r"(c0), "r"(c1) : "memory");
}
__device__ __forceinline__ void bulk_store(void* dst, uint32_t src, uint32_t bytes) {
  asm volatile("cp.async.bulk.global.shared::cta.bulk_group [%0], [%1], %2;" ::"l"(dst), "r"(src), "r"(bytes) : "memory");
}
__device__ __forceinline__ void bulk_load(uint32_t dst, const void* src, uint32_t bytes, uint32_t bar) {
  asm volatile("cp.async.bulk.shared::cluster.global.mbarrier::complete_tx::bytes [%0], [%1], %2, [%3];" ::"r"(dst), "l"(src), "r"(bytes), "r"(bar) : "memory");
}
__device__ __forceinline__ void bulk_red_add(void* dst, uint32_t src, uint32_t bytes) {
  asm volatile("cp.reduce.async.bulk.global.shared::cta.bulk_group.add.f32 [%0], [%1], %2;" ::"l"(dst), "r"(src), "r"(bytes) : "memory");
}
__device__ __forceinline__ void bulk_red_add_e(void* dst, uint32_t src, uint32_t bytes) {
  asm volatile("{\n.reg .pred p;\nelect.sync _|p, 0xffffffff;\n@p cp.reduce.async.bulk.global.shared::cta.bulk_group.add.f32 [%0], [%1], %2;\n}\n" ::"l"(dst), "r"(src), "r"(bytes) : "memory");
}
__device__ __forceinline__ void bulk_commit() { asm volatile("cp.async.bulk.commit_group;" ::: "memory"); }
__device__ __forceinline__ void bulk_wait_read0() { asm volatile("cp.async.bulk.wait_group.read 0;" ::: "memory"); }
__device__ __forceinline__ void bulk_wait0() { asm volatile("cp.async.bulk.wait_group 0;" ::: "memory"); }
__device__ __forceinline__ void fence_async_smem() { asm volatile("fence.proxy.async.shared::cta;" ::: "memory"); }
__device__ __forceinline__ void fence_async_all() { asm volatile("fence.proxy.async.global;" ::: "memory"); }
__device__ __forceinline__ void wgmma_fence() { asm volatile("wgmma.fence.sync.aligned;" ::: "memory"); }
__device__ __forceinline__ void wgmma_commit() { asm volatile("wgmma.commit_group.sync.aligned;" ::: "memory"); }
template <int N> __device__ __forceinline__ void wgmma_wait() { asm volatile("wgmma.wait_group.sync.aligned %0;" ::"n"(N) : "memory"); }
__device__ __forceinline__ void cluster_arrive() { asm volatile("barrier.cluster.arrive.release.aligned;" ::: "memory"); }
__device__ __forceinline__ void cluster_wait() { asm volatile("barrier.cluster.wait.acquire.aligned;" ::: "memory"); }
template <int ID, int N> __device__ __forceinline__ void nbar() { asm volatile("bar.sync %0, %1;" ::"n"(ID), "n"(N) : "memory"); }
__device__ __forceinline__ uint64_t make_desc(uint32_t addr, uint32_t lbo_bytes, uint32_t sbo_bytes) {
  uint64_t d = 0;
  d |= (uint64_t)((addr & 0x3FFFF) >> 4);
  d |= (uint64_t)((lbo_bytes >> 4) & 0x3FFF) << 16;
  d |= (uint64_t)((sbo_bytes >> 4) & 0x3FFF) << 32;
  d |= (uint64_t)1 << 62;
  return d;
}
__device__ __forceinline__ uint64_t desc64(uint32_t lo, uint32_t hi) { return (uint64_t)lo | ((uint64_t)hi << 32); }
__device__ __forceinline__ uint32_t pack_bf16(float lo, float hi) {
  uint32_t r; asm("cvt.rn.bf16x2.f32 %0, %1, %2;" : "=r"(r) : "f"(hi), "f"(lo)); return r;
}
__device__ __forceinline__ uint32_t mul_bf16x2(uint32_t a, uint32_t s, bool hi) {
  __nv_bfloat162 x = *reinterpret_cast<__nv_bfloat162*>(&a), y = *reinterpret_cast<__nv_bfloat162*>(&s);
  x = __hmul2(x, hi ? __high2bfloat162(y) : __low2bfloat162(y));
  return *reinterpret_cast<uint32_t*>(&x);
}
__device__ __forceinline__ float bf16r(float x) { return __bfloat162float(__float2bfloat16_rn(x)); }
__device__ __forceinline__ float bf_lo(uint32_t u) { return __uint_as_float(u << 16); }
__device__ __forceinline__ float bf_hi(uint32_t u) { return __uint_as_float(u & 0xFFFF0000u); }
__device__ __forceinline__ float ex2(float x) { float r; asm("ex2.approx.ftz.f32 %0, %1;" : "=f"(r) : "f"(x)); return r; }
__device__ __forceinline__ float rcp(float x) { float r; asm("rcp.approx.ftz.f32 %0, %1;" : "=f"(r) : "f"(x)); return r; }
__device__ __forceinline__ void mma_bf16(float (&d)[4], uint32_t a0, uint32_t a1, uint32_t a2, uint32_t a3, uint32_t b0, uint32_t b1) {
  asm("mma.sync.aligned.m16n8k16.row.col.f32.bf16.bf16.f32 {%0,%1,%2,%3}, {%4,%5,%6,%7}, {%8,%9}, {%0,%1,%2,%3};"
               : "+f"(d[0]), "+f"(d[1]), "+f"(d[2]), "+f"(d[3]) : "r"(a0), "r"(a1), "r"(a2), "r"(a3), "r"(b0), "r"(b1));
}
__device__ __forceinline__ void ldsm_x4(uint32_t& r0, uint32_t& r1, uint32_t& r2, uint32_t& r3, uint32_t addr) {
  asm volatile("ldmatrix.sync.aligned.m8n8.x4.shared.b16 {%0,%1,%2,%3}, [%4];"
               : "=r"(r0), "=r"(r1), "=r"(r2), "=r"(r3) : "r"(addr) : "memory");
}
__device__ __forceinline__ void ldsm_x4_t(uint32_t& r0, uint32_t& r1, uint32_t& r2, uint32_t& r3, uint32_t addr) {
  asm volatile("ldmatrix.sync.aligned.m8n8.x4.trans.shared.b16 {%0,%1,%2,%3}, [%4];"
               : "=r"(r0), "=r"(r1), "=r"(r2), "=r"(r3) : "r"(addr) : "memory");
}
__device__ __forceinline__ void ldsm_x2_t(uint32_t& r0, uint32_t& r1, uint32_t addr) {
  asm volatile("ldmatrix.sync.aligned.m8n8.x2.trans.shared.b16 {%0,%1}, [%2];"
               : "=r"(r0), "=r"(r1) : "r"(addr) : "memory");
}
__device__ __forceinline__ void stsm_x4(uint32_t addr, uint32_t r0, uint32_t r1, uint32_t r2, uint32_t r3) {
  asm volatile("stmatrix.sync.aligned.m8n8.x4.shared.b16 [%0], {%1,%2,%3,%4};"
               ::"r"(addr), "r"(r0), "r"(r1), "r"(r2), "r"(r3) : "memory");
}
__device__ __forceinline__ void stsm_x4_p(bool on, uint32_t addr, uint32_t r0, uint32_t r1, uint32_t r2, uint32_t r3) {
  asm volatile("{\n.reg .pred p;\nsetp.ne.b32 p, %5, 0;\n@p stmatrix.sync.aligned.m8n8.x4.shared.b16 [%0], {%1,%2,%3,%4};\n}\n"
               ::"r"(addr), "r"(r0), "r"(r1), "r"(r2), "r"(r3), "r"((int)on) : "memory");
}
__device__ __forceinline__ float2 lds_f2(uint32_t addr) {
  float2 v; asm volatile("ld.shared.v2.f32 {%0,%1}, [%2];" : "=f"(v.x), "=f"(v.y) : "r"(addr) : "memory"); return v;
}
__device__ __forceinline__ uint4 lds128(uint32_t addr) {
  uint4 v; asm volatile("ld.shared.v4.b32 {%0,%1,%2,%3}, [%4];" : "=r"(v.x), "=r"(v.y), "=r"(v.z), "=r"(v.w) : "r"(addr) : "memory"); return v;
}
__device__ __forceinline__ void sts128(uint32_t addr, uint4 v) {
  asm volatile("st.shared.v4.b32 [%0], {%1,%2,%3,%4};" ::"r"(addr), "r"(v.x), "r"(v.y), "r"(v.z), "r"(v.w) : "memory");
}
__device__ __forceinline__ float lds_f(uint32_t addr) {
  float v; asm volatile("ld.shared.f32 %0, [%1];" : "=f"(v) : "r"(addr) : "memory"); return v;
}
__device__ __forceinline__ uint32_t lds_vol(uint32_t addr) {
  uint32_t v; asm volatile("ld.volatile.shared.u32 %0, [%1];" : "=r"(v) : "r"(addr) : "memory"); return v;
}
__device__ __forceinline__ void sts16(uint32_t addr, uint32_t v) {
  asm volatile("st.shared.u16 [%0], %1;" ::"r"(addr), "h"((unsigned short)v) : "memory");
}
__device__ __forceinline__ void nbar_dyn(int id, int n) { asm volatile("bar.sync %0, %1;" ::"r"(id), "r"(n) : "memory"); }
__device__ __forceinline__ uint64_t make_desc_ns(uint32_t addr, uint32_t lbo_bytes, uint32_t sbo_bytes) {
  return (uint64_t)((addr & 0x3FFFF) >> 4) | ((uint64_t)(lbo_bytes >> 4) << 16) | ((uint64_t)(sbo_bytes >> 4) << 32);
}
__device__ __forceinline__ void sts_f(uint32_t addr, float v) { asm volatile("st.shared.f32 [%0], %1;" ::"r"(addr), "f"(v) : "memory"); }
__device__ __forceinline__ void sts64(uint32_t addr, uint32_t a, uint32_t b) {
  asm volatile("st.shared.v2.b32 [%0], {%1,%2};" ::"r"(addr), "r"(a), "r"(b) : "memory");
}
__device__ __forceinline__ void sts_f2(uint32_t addr, float a, float b) {
  asm volatile("st.shared.v2.f32 [%0], {%1,%2};" ::"r"(addr), "f"(a), "f"(b) : "memory");
}
__device__ __forceinline__ void red_add2(float* p, float a, float b) {
  asm volatile("red.global.add.v2.f32 [%0], {%1,%2};" ::"l"(p), "f"(a), "f"(b) : "memory");
}
__device__ __forceinline__ void red_add4(float* p, float a, float b, float c, float d) {
  asm volatile("red.global.add.v4.f32 [%0], {%1,%2,%3,%4};" ::"l"(p), "f"(a), "f"(b), "f"(c), "f"(d) : "memory");
}
__device__ __forceinline__ void red_add1(float* p, float a) {
  asm volatile("red.global.add.f32 [%0], %1;" ::"l"(p), "f"(a) : "memory");
}
__device__ __forceinline__ void l2_prefetch(const void* p, uint32_t bytes) {
  asm volatile("cp.async.bulk.prefetch.L2.global [%0], %1;" ::"l"(p), "r"(bytes) : "memory");
}

__device__ __forceinline__ void wgmma_n256(float (&d)[192], uint64_t da, uint64_t db, int scale_d) {
  asm volatile("{\n.reg .pred p;\nsetp.ne.b32 p, %130, 0;\n"
    "wgmma.mma_async.sync.aligned.m64n256k16.f32.bf16.bf16 {%0, %1, %2, %3, %4, %5, %6, %7, %8, %9, %10, %11, %12, %13, %14, %15, %16, %17, %18, %19, %20, %21, %22, %23, %24, %25, %26, %27, %28, %29, %30, %31, %32, %33, %34, %35, %36, %37, %38, %39, %40, %41, %42, %43, %44, %45, %46, %47, %48, %49, %50, %51, %52, %53, %54, %55, %56, %57, %58, %59, %60, %61, %62, %63, %64, %65, %66, %67, %68, %69, %70, %71, %72, %73, %74, %75, %76, %77, %78, %79, %80, %81, %82, %83, %84, %85, %86, %87, %88, %89, %90, %91, %92, %93, %94, %95, %96, %97, %98, %99, %100, %101, %102, %103, %104, %105, %106, %107, %108, %109, %110, %111, %112, %113, %114, %115, %116, %117, %118, %119, %120, %121, %122, %123, %124, %125, %126, %127}, %128, %129, p, 1, 1, 0, 1;\n}\n"
    : "+f"(d[0]), "+f"(d[1]), "+f"(d[2]), "+f"(d[3]), "+f"(d[4]), "+f"(d[5]), "+f"(d[6]), "+f"(d[7]), "+f"(d[8]), "+f"(d[9]), "+f"(d[10]), "+f"(d[11]), "+f"(d[12]), "+f"(d[13]), "+f"(d[14]), "+f"(d[15]), "+f"(d[16]), "+f"(d[17]), "+f"(d[18]), "+f"(d[19]), "+f"(d[20]), "+f"(d[21]), "+f"(d[22]), "+f"(d[23]), "+f"(d[24]), "+f"(d[25]), "+f"(d[26]), "+f"(d[27]), "+f"(d[28]), "+f"(d[29]), "+f"(d[30]), "+f"(d[31]), "+f"(d[32]), "+f"(d[33]), "+f"(d[34]), "+f"(d[35]), "+f"(d[36]), "+f"(d[37]), "+f"(d[38]), "+f"(d[39]), "+f"(d[40]), "+f"(d[41]), "+f"(d[42]), "+f"(d[43]), "+f"(d[44]), "+f"(d[45]), "+f"(d[46]), "+f"(d[47]), "+f"(d[48]), "+f"(d[49]), "+f"(d[50]), "+f"(d[51]), "+f"(d[52]), "+f"(d[53]), "+f"(d[54]), "+f"(d[55]), "+f"(d[56]), "+f"(d[57]), "+f"(d[58]), "+f"(d[59]), "+f"(d[60]), "+f"(d[61]), "+f"(d[62]), "+f"(d[63]), "+f"(d[64]), "+f"(d[65]), "+f"(d[66]), "+f"(d[67]), "+f"(d[68]), "+f"(d[69]), "+f"(d[70]), "+f"(d[71]), "+f"(d[72]), "+f"(d[73]), "+f"(d[74]), "+f"(d[75]), "+f"(d[76]), "+f"(d[77]), "+f"(d[78]), "+f"(d[79]), "+f"(d[80]), "+f"(d[81]), "+f"(d[82]), "+f"(d[83]), "+f"(d[84]), "+f"(d[85]), "+f"(d[86]), "+f"(d[87]), "+f"(d[88]), "+f"(d[89]), "+f"(d[90]), "+f"(d[91]), "+f"(d[92]), "+f"(d[93]), "+f"(d[94]), "+f"(d[95]), "+f"(d[96]), "+f"(d[97]), "+f"(d[98]), "+f"(d[99]), "+f"(d[100]), "+f"(d[101]), "+f"(d[102]), "+f"(d[103]), "+f"(d[104]), "+f"(d[105]), "+f"(d[106]), "+f"(d[107]), "+f"(d[108]), "+f"(d[109]), "+f"(d[110]), "+f"(d[111]), "+f"(d[112]), "+f"(d[113]), "+f"(d[114]), "+f"(d[115]), "+f"(d[116]), "+f"(d[117]), "+f"(d[118]), "+f"(d[119]), "+f"(d[120]), "+f"(d[121]), "+f"(d[122]), "+f"(d[123]), "+f"(d[124]), "+f"(d[125]), "+f"(d[126]), "+f"(d[127])
    : "l"(da), "l"(db), "r"(scale_d));
}
__device__ __forceinline__ void wgmma_n128(float (&d)[192], uint64_t da, uint64_t db, int scale_d) {
  asm volatile("{\n.reg .pred p;\nsetp.ne.b32 p, %66, 0;\n"
    "wgmma.mma_async.sync.aligned.m64n128k16.f32.bf16.bf16 {%0, %1, %2, %3, %4, %5, %6, %7, %8, %9, %10, %11, %12, %13, %14, %15, %16, %17, %18, %19, %20, %21, %22, %23, %24, %25, %26, %27, %28, %29, %30, %31, %32, %33, %34, %35, %36, %37, %38, %39, %40, %41, %42, %43, %44, %45, %46, %47, %48, %49, %50, %51, %52, %53, %54, %55, %56, %57, %58, %59, %60, %61, %62, %63}, %64, %65, p, 1, 1, 0, 1;\n}\n"
    : "+f"(d[128]), "+f"(d[129]), "+f"(d[130]), "+f"(d[131]), "+f"(d[132]), "+f"(d[133]), "+f"(d[134]), "+f"(d[135]), "+f"(d[136]), "+f"(d[137]), "+f"(d[138]), "+f"(d[139]), "+f"(d[140]), "+f"(d[141]), "+f"(d[142]), "+f"(d[143]), "+f"(d[144]), "+f"(d[145]), "+f"(d[146]), "+f"(d[147]), "+f"(d[148]), "+f"(d[149]), "+f"(d[150]), "+f"(d[151]), "+f"(d[152]), "+f"(d[153]), "+f"(d[154]), "+f"(d[155]), "+f"(d[156]), "+f"(d[157]), "+f"(d[158]), "+f"(d[159]), "+f"(d[160]), "+f"(d[161]), "+f"(d[162]), "+f"(d[163]), "+f"(d[164]), "+f"(d[165]), "+f"(d[166]), "+f"(d[167]), "+f"(d[168]), "+f"(d[169]), "+f"(d[170]), "+f"(d[171]), "+f"(d[172]), "+f"(d[173]), "+f"(d[174]), "+f"(d[175]), "+f"(d[176]), "+f"(d[177]), "+f"(d[178]), "+f"(d[179]), "+f"(d[180]), "+f"(d[181]), "+f"(d[182]), "+f"(d[183]), "+f"(d[184]), "+f"(d[185]), "+f"(d[186]), "+f"(d[187]), "+f"(d[188]), "+f"(d[189]), "+f"(d[190]), "+f"(d[191])
    : "l"(da), "l"(db), "r"(scale_d));
}
__device__ __forceinline__ void wgmma_n256_k(float (&d)[192], uint64_t da, uint64_t db, int scale_d) {
  asm volatile("{\n.reg .pred p;\nsetp.ne.b32 p, %130, 0;\n"
    "wgmma.mma_async.sync.aligned.m64n256k16.f32.bf16.bf16 {%0, %1, %2, %3, %4, %5, %6, %7, %8, %9, %10, %11, %12, %13, %14, %15, %16, %17, %18, %19, %20, %21, %22, %23, %24, %25, %26, %27, %28, %29, %30, %31, %32, %33, %34, %35, %36, %37, %38, %39, %40, %41, %42, %43, %44, %45, %46, %47, %48, %49, %50, %51, %52, %53, %54, %55, %56, %57, %58, %59, %60, %61, %62, %63, %64, %65, %66, %67, %68, %69, %70, %71, %72, %73, %74, %75, %76, %77, %78, %79, %80, %81, %82, %83, %84, %85, %86, %87, %88, %89, %90, %91, %92, %93, %94, %95, %96, %97, %98, %99, %100, %101, %102, %103, %104, %105, %106, %107, %108, %109, %110, %111, %112, %113, %114, %115, %116, %117, %118, %119, %120, %121, %122, %123, %124, %125, %126, %127}, %128, %129, p, 1, 1, 0, 0;\n}\n"
    : "+f"(d[0]), "+f"(d[1]), "+f"(d[2]), "+f"(d[3]), "+f"(d[4]), "+f"(d[5]), "+f"(d[6]), "+f"(d[7]), "+f"(d[8]), "+f"(d[9]), "+f"(d[10]), "+f"(d[11]), "+f"(d[12]), "+f"(d[13]), "+f"(d[14]), "+f"(d[15]), "+f"(d[16]), "+f"(d[17]), "+f"(d[18]), "+f"(d[19]), "+f"(d[20]), "+f"(d[21]), "+f"(d[22]), "+f"(d[23]), "+f"(d[24]), "+f"(d[25]), "+f"(d[26]), "+f"(d[27]), "+f"(d[28]), "+f"(d[29]), "+f"(d[30]), "+f"(d[31]), "+f"(d[32]), "+f"(d[33]), "+f"(d[34]), "+f"(d[35]), "+f"(d[36]), "+f"(d[37]), "+f"(d[38]), "+f"(d[39]), "+f"(d[40]), "+f"(d[41]), "+f"(d[42]), "+f"(d[43]), "+f"(d[44]), "+f"(d[45]), "+f"(d[46]), "+f"(d[47]), "+f"(d[48]), "+f"(d[49]), "+f"(d[50]), "+f"(d[51]), "+f"(d[52]), "+f"(d[53]), "+f"(d[54]), "+f"(d[55]), "+f"(d[56]), "+f"(d[57]), "+f"(d[58]), "+f"(d[59]), "+f"(d[60]), "+f"(d[61]), "+f"(d[62]), "+f"(d[63]), "+f"(d[64]), "+f"(d[65]), "+f"(d[66]), "+f"(d[67]), "+f"(d[68]), "+f"(d[69]), "+f"(d[70]), "+f"(d[71]), "+f"(d[72]), "+f"(d[73]), "+f"(d[74]), "+f"(d[75]), "+f"(d[76]), "+f"(d[77]), "+f"(d[78]), "+f"(d[79]), "+f"(d[80]), "+f"(d[81]), "+f"(d[82]), "+f"(d[83]), "+f"(d[84]), "+f"(d[85]), "+f"(d[86]), "+f"(d[87]), "+f"(d[88]), "+f"(d[89]), "+f"(d[90]), "+f"(d[91]), "+f"(d[92]), "+f"(d[93]), "+f"(d[94]), "+f"(d[95]), "+f"(d[96]), "+f"(d[97]), "+f"(d[98]), "+f"(d[99]), "+f"(d[100]), "+f"(d[101]), "+f"(d[102]), "+f"(d[103]), "+f"(d[104]), "+f"(d[105]), "+f"(d[106]), "+f"(d[107]), "+f"(d[108]), "+f"(d[109]), "+f"(d[110]), "+f"(d[111]), "+f"(d[112]), "+f"(d[113]), "+f"(d[114]), "+f"(d[115]), "+f"(d[116]), "+f"(d[117]), "+f"(d[118]), "+f"(d[119]), "+f"(d[120]), "+f"(d[121]), "+f"(d[122]), "+f"(d[123]), "+f"(d[124]), "+f"(d[125]), "+f"(d[126]), "+f"(d[127])
    : "l"(da), "l"(db), "r"(scale_d));
}
__device__ __forceinline__ void wgmma_n128_k(float (&d)[192], uint64_t da, uint64_t db, int scale_d) {
  asm volatile("{\n.reg .pred p;\nsetp.ne.b32 p, %66, 0;\n"
    "wgmma.mma_async.sync.aligned.m64n128k16.f32.bf16.bf16 {%0, %1, %2, %3, %4, %5, %6, %7, %8, %9, %10, %11, %12, %13, %14, %15, %16, %17, %18, %19, %20, %21, %22, %23, %24, %25, %26, %27, %28, %29, %30, %31, %32, %33, %34, %35, %36, %37, %38, %39, %40, %41, %42, %43, %44, %45, %46, %47, %48, %49, %50, %51, %52, %53, %54, %55, %56, %57, %58, %59, %60, %61, %62, %63}, %64, %65, p, 1, 1, 0, 0;\n}\n"
    : "+f"(d[128]), "+f"(d[129]), "+f"(d[130]), "+f"(d[131]), "+f"(d[132]), "+f"(d[133]), "+f"(d[134]), "+f"(d[135]), "+f"(d[136]), "+f"(d[137]), "+f"(d[138]), "+f"(d[139]), "+f"(d[140]), "+f"(d[141]), "+f"(d[142]), "+f"(d[143]), "+f"(d[144]), "+f"(d[145]), "+f"(d[146]), "+f"(d[147]), "+f"(d[148]), "+f"(d[149]), "+f"(d[150]), "+f"(d[151]), "+f"(d[152]), "+f"(d[153]), "+f"(d[154]), "+f"(d[155]), "+f"(d[156]), "+f"(d[157]), "+f"(d[158]), "+f"(d[159]), "+f"(d[160]), "+f"(d[161]), "+f"(d[162]), "+f"(d[163]), "+f"(d[164]), "+f"(d[165]), "+f"(d[166]), "+f"(d[167]), "+f"(d[168]), "+f"(d[169]), "+f"(d[170]), "+f"(d[171]), "+f"(d[172]), "+f"(d[173]), "+f"(d[174]), "+f"(d[175]), "+f"(d[176]), "+f"(d[177]), "+f"(d[178]), "+f"(d[179]), "+f"(d[180]), "+f"(d[181]), "+f"(d[182]), "+f"(d[183]), "+f"(d[184]), "+f"(d[185]), "+f"(d[186]), "+f"(d[187]), "+f"(d[188]), "+f"(d[189]), "+f"(d[190]), "+f"(d[191])
    : "l"(da), "l"(db), "r"(scale_d));
}
__device__ __forceinline__ void wgmma_n40_tt(float (&d)[20], uint64_t da, uint64_t db, int scale_d) {
  asm volatile("{\n.reg .pred p;\nsetp.ne.b32 p, %22, 0;\n"
    "wgmma.mma_async.sync.aligned.m64n40k16.f32.bf16.bf16 {%0, %1, %2, %3, %4, %5, %6, %7, %8, %9, %10, %11, %12, %13, %14, %15, %16, %17, %18, %19}, %20, %21, p, 1, 1, 1, 1;\n}\n"
    : "+f"(d[0]), "+f"(d[1]), "+f"(d[2]), "+f"(d[3]), "+f"(d[4]), "+f"(d[5]), "+f"(d[6]), "+f"(d[7]), "+f"(d[8]), "+f"(d[9]), "+f"(d[10]), "+f"(d[11]), "+f"(d[12]), "+f"(d[13]), "+f"(d[14]), "+f"(d[15]), "+f"(d[16]), "+f"(d[17]), "+f"(d[18]), "+f"(d[19])
    : "l"(da), "l"(db), "r"(scale_d));
}
__device__ __forceinline__ void wgmma_n40_rs(float (&d)[20], const uint32_t (&a)[4], uint64_t db, int scale_d) {
  asm volatile("{\n.reg .pred p;\nsetp.ne.b32 p, %25, 0;\n"
    "wgmma.mma_async.sync.aligned.m64n40k16.f32.bf16.bf16 {%0, %1, %2, %3, %4, %5, %6, %7, %8, %9, %10, %11, %12, %13, %14, %15, %16, %17, %18, %19}, {%20, %21, %22, %23}, %24, p, 1, 1, 1;\n}\n"
    : "+f"(d[0]), "+f"(d[1]), "+f"(d[2]), "+f"(d[3]), "+f"(d[4]), "+f"(d[5]), "+f"(d[6]), "+f"(d[7]), "+f"(d[8]), "+f"(d[9]), "+f"(d[10]), "+f"(d[11]), "+f"(d[12]), "+f"(d[13]), "+f"(d[14]), "+f"(d[15]), "+f"(d[16]), "+f"(d[17]), "+f"(d[18]), "+f"(d[19])
    : "r"(a[0]), "r"(a[1]), "r"(a[2]), "r"(a[3]), "l"(db), "r"(scale_d));
}
__device__ __forceinline__ void wgmma_n256_0(float (&d)[192], uint64_t da, uint64_t db) {
  asm volatile("{\n.reg .pred p;\nsetp.ne.b32 p, 0, 0;\n"
    "wgmma.mma_async.sync.aligned.m64n256k16.f32.bf16.bf16 {%0, %1, %2, %3, %4, %5, %6, %7, %8, %9, %10, %11, %12, %13, %14, %15, %16, %17, %18, %19, %20, %21, %22, %23, %24, %25, %26, %27, %28, %29, %30, %31, %32, %33, %34, %35, %36, %37, %38, %39, %40, %41, %42, %43, %44, %45, %46, %47, %48, %49, %50, %51, %52, %53, %54, %55, %56, %57, %58, %59, %60, %61, %62, %63, %64, %65, %66, %67, %68, %69, %70, %71, %72, %73, %74, %75, %76, %77, %78, %79, %80, %81, %82, %83, %84, %85, %86, %87, %88, %89, %90, %91, %92, %93, %94, %95, %96, %97, %98, %99, %100, %101, %102, %103, %104, %105, %106, %107, %108, %109, %110, %111, %112, %113, %114, %115, %116, %117, %118, %119, %120, %121, %122, %123, %124, %125, %126, %127}, %128, %129, p, 1, 1, 0, 1;\n}\n"
    : "=f"(d[0]), "=f"(d[1]), "=f"(d[2]), "=f"(d[3]), "=f"(d[4]), "=f"(d[5]), "=f"(d[6]), "=f"(d[7]), "=f"(d[8]), "=f"(d[9]), "=f"(d[10]), "=f"(d[11]), "=f"(d[12]), "=f"(d[13]), "=f"(d[14]), "=f"(d[15]), "=f"(d[16]), "=f"(d[17]), "=f"(d[18]), "=f"(d[19]), "=f"(d[20]), "=f"(d[21]), "=f"(d[22]), "=f"(d[23]), "=f"(d[24]), "=f"(d[25]), "=f"(d[26]), "=f"(d[27]), "=f"(d[28]), "=f"(d[29]), "=f"(d[30]), "=f"(d[31]), "=f"(d[32]), "=f"(d[33]), "=f"(d[34]), "=f"(d[35]), "=f"(d[36]), "=f"(d[37]), "=f"(d[38]), "=f"(d[39]), "=f"(d[40]), "=f"(d[41]), "=f"(d[42]), "=f"(d[43]), "=f"(d[44]), "=f"(d[45]), "=f"(d[46]), "=f"(d[47]), "=f"(d[48]), "=f"(d[49]), "=f"(d[50]), "=f"(d[51]), "=f"(d[52]), "=f"(d[53]), "=f"(d[54]), "=f"(d[55]), "=f"(d[56]), "=f"(d[57]), "=f"(d[58]), "=f"(d[59]), "=f"(d[60]), "=f"(d[61]), "=f"(d[62]), "=f"(d[63]), "=f"(d[64]), "=f"(d[65]), "=f"(d[66]), "=f"(d[67]), "=f"(d[68]), "=f"(d[69]), "=f"(d[70]), "=f"(d[71]), "=f"(d[72]), "=f"(d[73]), "=f"(d[74]), "=f"(d[75]), "=f"(d[76]), "=f"(d[77]), "=f"(d[78]), "=f"(d[79]), "=f"(d[80]), "=f"(d[81]), "=f"(d[82]), "=f"(d[83]), "=f"(d[84]), "=f"(d[85]), "=f"(d[86]), "=f"(d[87]), "=f"(d[88]), "=f"(d[89]), "=f"(d[90]), "=f"(d[91]), "=f"(d[92]), "=f"(d[93]), "=f"(d[94]), "=f"(d[95]), "=f"(d[96]), "=f"(d[97]), "=f"(d[98]), "=f"(d[99]), "=f"(d[100]), "=f"(d[101]), "=f"(d[102]), "=f"(d[103]), "=f"(d[104]), "=f"(d[105]), "=f"(d[106]), "=f"(d[107]), "=f"(d[108]), "=f"(d[109]), "=f"(d[110]), "=f"(d[111]), "=f"(d[112]), "=f"(d[113]), "=f"(d[114]), "=f"(d[115]), "=f"(d[116]), "=f"(d[117]), "=f"(d[118]), "=f"(d[119]), "=f"(d[120]), "=f"(d[121]), "=f"(d[122]), "=f"(d[123]), "=f"(d[124]), "=f"(d[125]), "=f"(d[126]), "=f"(d[127])
    : "l"(da), "l"(db));
}
__device__ __forceinline__ void wgmma_n128_0(float (&d)[192], uint64_t da, uint64_t db) {
  asm volatile("{\n.reg .pred p;\nsetp.ne.b32 p, 0, 0;\n"
    "wgmma.mma_async.sync.aligned.m64n128k16.f32.bf16.bf16 {%0, %1, %2, %3, %4, %5, %6, %7, %8, %9, %10, %11, %12, %13, %14, %15, %16, %17, %18, %19, %20, %21, %22, %23, %24, %25, %26, %27, %28, %29, %30, %31, %32, %33, %34, %35, %36, %37, %38, %39, %40, %41, %42, %43, %44, %45, %46, %47, %48, %49, %50, %51, %52, %53, %54, %55, %56, %57, %58, %59, %60, %61, %62, %63}, %64, %65, p, 1, 1, 0, 1;\n}\n"
    : "=f"(d[128]), "=f"(d[129]), "=f"(d[130]), "=f"(d[131]), "=f"(d[132]), "=f"(d[133]), "=f"(d[134]), "=f"(d[135]), "=f"(d[136]), "=f"(d[137]), "=f"(d[138]), "=f"(d[139]), "=f"(d[140]), "=f"(d[141]), "=f"(d[142]), "=f"(d[143]), "=f"(d[144]), "=f"(d[145]), "=f"(d[146]), "=f"(d[147]), "=f"(d[148]), "=f"(d[149]), "=f"(d[150]), "=f"(d[151]), "=f"(d[152]), "=f"(d[153]), "=f"(d[154]), "=f"(d[155]), "=f"(d[156]), "=f"(d[157]), "=f"(d[158]), "=f"(d[159]), "=f"(d[160]), "=f"(d[161]), "=f"(d[162]), "=f"(d[163]), "=f"(d[164]), "=f"(d[165]), "=f"(d[166]), "=f"(d[167]), "=f"(d[168]), "=f"(d[169]), "=f"(d[170]), "=f"(d[171]), "=f"(d[172]), "=f"(d[173]), "=f"(d[174]), "=f"(d[175]), "=f"(d[176]), "=f"(d[177]), "=f"(d[178]), "=f"(d[179]), "=f"(d[180]), "=f"(d[181]), "=f"(d[182]), "=f"(d[183]), "=f"(d[184]), "=f"(d[185]), "=f"(d[186]), "=f"(d[187]), "=f"(d[188]), "=f"(d[189]), "=f"(d[190]), "=f"(d[191])
    : "l"(da), "l"(db));
}
__device__ __forceinline__ void wgmma_n128_rs(float (&d)[192], const uint32_t (&a)[4], uint64_t db, int scale_d) {
  asm volatile("{\n.reg .pred p;\nsetp.ne.b32 p, %69, 0;\n"
    "wgmma.mma_async.sync.aligned.m64n128k16.f32.bf16.bf16 {%0, %1, %2, %3, %4, %5, %6, %7, %8, %9, %10, %11, %12, %13, %14, %15, %16, %17, %18, %19, %20, %21, %22, %23, %24, %25, %26, %27, %28, %29, %30, %31, %32, %33, %34, %35, %36, %37, %38, %39, %40, %41, %42, %43, %44, %45, %46, %47, %48, %49, %50, %51, %52, %53, %54, %55, %56, %57, %58, %59, %60, %61, %62, %63}, {%64, %65, %66, %67}, %68, p, 1, 1, 1;\n}\n"
    : "+f"(d[128]), "+f"(d[129]), "+f"(d[130]), "+f"(d[131]), "+f"(d[132]), "+f"(d[133]), "+f"(d[134]), "+f"(d[135]), "+f"(d[136]), "+f"(d[137]), "+f"(d[138]), "+f"(d[139]), "+f"(d[140]), "+f"(d[141]), "+f"(d[142]), "+f"(d[143]), "+f"(d[144]), "+f"(d[145]), "+f"(d[146]), "+f"(d[147]), "+f"(d[148]), "+f"(d[149]), "+f"(d[150]), "+f"(d[151]), "+f"(d[152]), "+f"(d[153]), "+f"(d[154]), "+f"(d[155]), "+f"(d[156]), "+f"(d[157]), "+f"(d[158]), "+f"(d[159]), "+f"(d[160]), "+f"(d[161]), "+f"(d[162]), "+f"(d[163]), "+f"(d[164]), "+f"(d[165]), "+f"(d[166]), "+f"(d[167]), "+f"(d[168]), "+f"(d[169]), "+f"(d[170]), "+f"(d[171]), "+f"(d[172]), "+f"(d[173]), "+f"(d[174]), "+f"(d[175]), "+f"(d[176]), "+f"(d[177]), "+f"(d[178]), "+f"(d[179]), "+f"(d[180]), "+f"(d[181]), "+f"(d[182]), "+f"(d[183]), "+f"(d[184]), "+f"(d[185]), "+f"(d[186]), "+f"(d[187]), "+f"(d[188]), "+f"(d[189]), "+f"(d[190]), "+f"(d[191])
    : "r"(a[0]), "r"(a[1]), "r"(a[2]), "r"(a[3]), "l"(db), "r"(scale_d));
}

constexpr int SLOT = 16384;
constexpr int KVT = 10240;
constexpr uint32_t QA = 0x0BAu, QK = 0x462u, QQ = 0x981u;
constexpr int SM_SD = 12 * SLOT;
constexpr int SM_BAR = SM_SD + 8192;
constexpr int SM_RS = SM_BAR + 512;
constexpr int SM_AP = SM_RS + 768;
constexpr int SM_BP = SM_AP + 2048;
constexpr int SM_WPHI = SM_BP + 12288;
constexpr int SM_EPOCH = SM_WPHI + 10240;
constexpr int SM_TOTAL = SM_EPOCH + 16 + 1024;
constexpr int B_FULLS = 0, B_XOLD = 24, B_STAT = 32, B_EMPTYS = 40, B_FULLT = 256  , B_CONS = 384  , B_E3 = 472, B_E0 = 480, B_E1 = 488, B_E2 = 496, B_EPI = 504, B_CS = 160,
              B_KVDONE = 168  , B_ODONE = 176, B_XDONE = 184, B_OH1 = B_CONS, B_CS2 = 208, B_XH0 = 232, B_R0 = 240, B_CB = 144  , B_XOLD2 = 216;
constexpr uint64_t BAR_CNT = 0x1c07fc0eac00a800ull;
constexpr uint64_t WO_A0 = 0xa461b57648357643ull, WO_B0 = 0x59083a9021ba9021ull, WO_A1 = 0xa0b76901276a5babull, WO_B1 = 0x95428a5b34890132ull;
constexpr uint64_t WO_DA0 = 0xa9865432ff00dd00ull, WO_DB0 = 0xa986543211bbccccull, WO_DA1 = 0xa98654321ffff000ull, WO_DB1 = 0xa98754321bbcccddull;
#define WOORD 0xFDB9753ECA864210ull
constexpr int NX = 4;
constexpr int XS = 10;

#define PL 2
#define PROFX(i) PROFT(tid_ == 128 && layer == PL, 200 + (i))
#define NCOM 3
#define PFS 8
#define KVTH 0x41700000u
#define XPF 3
#define XPM 2
#define TLINE 1
#define MAP 3
#define RT2 0
#define WSK 1
#define H1L 0
#define EI 13
#define K0V 0
#define ORD 5
#define NLAYERS 4
constexpr float L2E = 1.4426950408889634f;
#define PHI_MAX 2147483648.f

#define D128(lo) desc64(lo, 0x40000040u)
struct Ctx { uint32_t sb; int g, rb, cu; bf16* out; };

__device__ __forceinline__ void colsum(const CUtensorMap* tm, float* cs, int rb, int g, int w0, int dw, int lane, uint32_t stg, uint32_t cb, uint32_t par) {
  const uint32_t src = stg + (lane >> 3) * 2048;
#pragma unroll 1
  for (int wi = w0 - dw; wi < 6; wi += dw) {
    float s[8] = {0.f, 0.f, 0.f, 0.f, 0.f, 0.f, 0.f, 0.f};
    if (wi >= 0) {
      mbar_wait_u(cb, par);
      par ^= 1;
#pragma unroll 4
      for (int r = 0; r < 16; ++r) {
        const uint4 v = lds128(src + r * 128 + (((lane ^ r) & 7) << 4));
        s[0] += bf_lo(v.x); s[1] += bf_hi(v.x); s[2] += bf_lo(v.y); s[3] += bf_hi(v.y);
        s[4] += bf_lo(v.z); s[5] += bf_hi(v.z); s[6] += bf_lo(v.w); s[7] += bf_hi(v.w);
      }
#pragma unroll
      for (int i = 0; i < 8; ++i) s[i] += __shfl_xor_sync(0xffffffffu, s[i], 8);
    }
    const int wn = wi + dw;
    if (wn < 6) {
      expect_tx_e(cb, 8192);
      tma_2d_e(stg, tm, (wn >= 4 ? 0 : 1024 + (wn >> 1) * 1024) + g * 128 + (wn & 1) * 64, rb * 64, cb);
    }
    if (wi >= 0) {
#pragma unroll
      for (int i = 0; i < 8; ++i) s[i] += __shfl_xor_sync(0xffffffffu, s[i], 16);
      if (lane < 8) {
        red_add4(cs + g * 384 + (wi * 8 + lane) * 8, s[0], s[1], s[2], s[3]);
        red_add4(cs + g * 384 + (wi * 8 + lane) * 8 + 4, s[4], s[5], s[6], s[7]);
      }
      __syncwarp();
    }
  }
}
#define PHASE_CTX() \
  uint32_t sb = c.sb; asm volatile("" : "+r"(sb)); \
  int tid_ = threadIdx.x; asm volatile("" : "+r"(tid_)); \
  const uint32_t bar = sb + SM_BAR; \
  const int lane = tid_ & 31, cw = (tid_ >> 5) - 4, wg = cw >> 2, wq = cw & 3, gq = lane >> 2, t = lane & 3, wrow0 = cw * 16; \
  const int lrow = (lane & 7) + ((lane >> 3) & 1) * 8, lchk = lane >> 4; \
  const bool elected = (tid_ & 127) == 0; \
  const uint32_t rowo = (wrow0 + lrow) * 128, X = (lchk ^ (lane & 7)) << 4; \
  (void)bar; (void)wq; (void)gq; (void)lrow; (void)lchk; (void)elected; (void)wrow0; (void)wg; (void)rowo; (void)X; (void)t;

__device__ __forceinline__ void slab_out_half(uint32_t slot, bf16* dst, int wrow0, int lane, bool FENCE = false) {
  const int r0 = lane >> 3, ch = lane & 7;
  const uint32_t src = slot + (wrow0 + r0) * 128;
  uint4 v[4];
#pragma unroll
  for (int i = 0; i < 4; ++i) v[i] = lds128(src + i * 512 + (((ch ^ (4 * i + r0)) & 7) << 4));
  if (FENCE) fence_async_smem();
  dst += (size_t)(wrow0 + r0) * D_ + ch * 8;
#pragma unroll
  for (int i = 0; i < 4; ++i)
    asm volatile("st.global.v4.u32 [%0], {%1,%2,%3,%4};" ::"l"(dst + (size_t)i * 4 * D_), "r"(v[i].x), "r"(v[i].y), "r"(v[i].z), "r"(v[i].w) : "memory");
}

struct Tag { uint32_t me, mo, tg; };
__device__ __forceinline__ Tag make_tag(int gq, int t, uint32_t tg) { return Tag{t == 0, t == 1, tg}; }
__device__ __forceinline__ void stsm_tag(uint32_t addr, uint32_t r0, uint32_t r1, uint32_t r2, uint32_t r3, const Tag& k, int jp) {
  if (jp == 0) stsm_x4(addr, (r0 & ~k.me) | (k.tg & k.me), (r1 & ~k.mo) | (k.tg & k.mo), r2, r3);
  else stsm_x4(addr, r0, r1, r2, r3);
}
#define TILE_BAD() ((lds_vol(va) ^ tg) & 1)
#define TILE_VA() (slot + (wrow0 + (lane & 15)) * 128 + (lane & 7) * 16 + ((lane >> 3) & 1) * 4)
__device__ __forceinline__ void tile_check(uint32_t slot, const bf16* src, int wrow0, int lane, uint32_t tg) {
  const uint32_t va = TILE_VA();
  if (__builtin_expect(__any_sync(0xffffffffu, TILE_BAD()), 0)) {
    const int r0 = lane >> 3, ch = lane & 7;
    uint32_t n = 0;
#pragma unroll 1
    do {
      uint4 v[4];
#pragma unroll
      for (int i = 0; i < 4; ++i) v[i] = ld_relaxed4(reinterpret_cast<const uint4*>(src + (size_t)(wrow0 + r0 + 4 * i) * D_ + ch * 8));
#pragma unroll
      for (int i = 0; i < 4; ++i) sts128(slot + (wrow0 + r0 + 4 * i) * 128 + (((ch ^ (4 * i + r0)) & 7) << 4), v[i]);
      __syncwarp();
      if (++n > (1u << 16)) { g_err = 8u; break; }
    } while (__any_sync(0xffffffffu, TILE_BAD()));
    fence_async_smem();
    __syncwarp();
  }
}

template <int O>
__device__ __forceinline__ void phi_proj(float (&p)[2][4][4], const uint32_t (&kq)[64], uint32_t wa) {
#pragma unroll
  for (int h = 0; h < 2; ++h)
#pragma unroll
    for (int i = 0; i < 4; ++i) { p[h][i][0] = p[h][i][1] = p[h][i][2] = p[h][i][3] = 0.f; }
#pragma unroll
  for (int ks = 0; ks < 2; ++ks)
#pragma unroll
    for (int np = 0; np < 2; ++np)
#pragma unroll
      for (int h = 0; h < 2; ++h) {
        uint32_t b0, b1, b2, b3;
        ldsm_x4_t(b0, b1, b2, b3, wa + h * 2560 + ks * 1280 + np * 32);
        mma_bf16(p[h][2 * np], kq[O + 8 * h + 4 * ks], kq[O + 8 * h + 4 * ks + 1], kq[O + 8 * h + 4 * ks + 2], kq[O + 8 * h + 4 * ks + 3], b0, b1);
        mma_bf16(p[h][2 * np + 1], kq[O + 8 * h + 4 * ks], kq[O + 8 * h + 4 * ks + 1], kq[O + 8 * h + 4 * ks + 2], kq[O + 8 * h + 4 * ks + 3], b2, b3);
      }
}
__device__ __forceinline__ void phi_exp(uint32_t (&raw)[4][4], const float (&p)[4][4], float sc0, float sc1) {
#pragma unroll
  for (int i = 0; i < 4; ++i) {
    const float e0 = ex2(p[i][0] * sc0), e1 = ex2(p[i][1] * sc0), e2 = ex2(p[i][2] * sc1), e3 = ex2(p[i][3] * sc1);
    const float m0 = e0 * e1, m1 = e2 * e3, rr = rcp(m0 * m1), r0 = rr * m1, r1 = rr * m0;
    raw[i >> 1][(i & 1) * 2] = pack_bf16(e0, e1);
    raw[i >> 1][(i & 1) * 2 + 1] = pack_bf16(e2, e3);
    raw[2 + (i >> 1)][(i & 1) * 2] = pack_bf16(e1 * r0, e0 * r0);
    raw[2 + (i >> 1)][(i & 1) * 2 + 1] = pack_bf16(e3 * r1, e2 * r1);
  }
}
template <int O>
__device__ __forceinline__ void phi_norm(uint32_t (&ph)[2][4][4], const uint32_t (&raw)[2][4][4], const uint32_t (&kq)[64], uint32_t wa,
                                         float sc0, float sc1, float mul0, float mul1) {
  bool bad = false;
#pragma unroll
  for (int h = 0; h < 2; ++h)
#pragma unroll
    for (int sg = 0; sg < 2; ++sg) {
      float ss[4] = {0.f, 0.f, 0.f, 0.f};
#pragma unroll
      for (int ks = 0; ks < 2; ++ks)
        mma_bf16(ss, raw[h][2 * sg + ks][0], raw[h][2 * sg + ks][1], raw[h][2 * sg + ks][2], raw[h][2 * sg + ks][3], 0x3F803F80u, 0x3F803F80u);
      bad = bad || !(ss[0] < PHI_MAX) || !(ss[2] < PHI_MAX);
      const uint32_t iv = pack_bf16(rcp(ss[0]) * mul0, rcp(ss[2]) * mul1);
#pragma unroll
      for (int ks = 0; ks < 2; ++ks)
#pragma unroll
        for (int j = 0; j < 4; ++j) ph[h][2 * sg + ks][j] = mul_bf16x2(raw[h][2 * sg + ks][j], iv, j & 1);
    }
  if (__builtin_expect(__any_sync(0xffffffffu, bad), 0)) {
#pragma unroll 1
    for (int it = 0; it < 4; ++it) {
      float q[4][4];
#pragma unroll
      for (int i = 0; i < 4; ++i) { q[i][0] = q[i][1] = q[i][2] = q[i][3] = 0.f; }
#pragma unroll
      for (int ks = 0; ks < 2; ++ks) {
        uint32_t a[4];
#pragma unroll
        for (int j = 0; j < 4; ++j) a[j] = (it & 2) ? kq[O + 8 + 4 * ks + j] : kq[O + 4 * ks + j];
#pragma unroll
        for (int np = 0; np < 2; ++np) {
          uint32_t b0, b1, b2, b3;
          ldsm_x4_t(b0, b1, b2, b3, wa + (it >> 1) * 2560 + ks * 1280 + np * 32);
          mma_bf16(q[2 * np], a[0], a[1], a[2], a[3], b0, b1);
          mma_bf16(q[2 * np + 1], a[0], a[1], a[2], a[3], b2, b3);
        }
      }
      float iv[2];
#pragma unroll
      for (int r = 0; r < 2; ++r) {
        const float sc = (it & 1) ? -(r ? sc1 : sc0) : (r ? sc1 : sc0);
        float mx = -INFINITY, sm = 0.f;
#pragma unroll
        for (int i = 0; i < 8; ++i) { float& v = q[i >> 1][2 * r + (i & 1)]; v *= sc; mx = fmaxf(mx, v); }
        mx = fmaxf(mx, __shfl_xor_sync(0xffffffffu, mx, 1));
        mx = fmaxf(mx, __shfl_xor_sync(0xffffffffu, mx, 2));
#pragma unroll
        for (int i = 0; i < 8; ++i) { float& v = q[i >> 1][2 * r + (i & 1)]; v = ex2(v - mx); sm += v; }
        sm += __shfl_xor_sync(0xffffffffu, sm, 1);
        sm += __shfl_xor_sync(0xffffffffu, sm, 2);
        iv[r] = rcp(sm) * (r ? mul1 : mul0);
      }
#pragma unroll
      for (int i = 0; i < 24; ++i) ph[i >> 4][(i >> 2) & 3][i & 3] = ph[(i + 8) >> 4][((i + 8) >> 2) & 3][i & 3];
#pragma unroll
      for (int i = 0; i < 4; ++i) {
        ph[1][2 + (i >> 1)][(i & 1) * 2] = pack_bf16(q[i][0] * iv[0], q[i][1] * iv[0]);
        ph[1][2 + (i >> 1)][(i & 1) * 2 + 1] = pack_bf16(q[i][2] * iv[1], q[i][3] * iv[1]);
      }
    }
  }
}

__device__ __forceinline__ void stats_out(float s0, float s1, float q0, float q1, float2* dst, int t) {
  const bool od = t & 1;
  float sa = od ? s1 : s0, qa = od ? q1 : q0;
  sa += __shfl_xor_sync(0xffffffffu, od ? s0 : s1, 1);
  qa += __shfl_xor_sync(0xffffffffu, od ? q0 : q1, 1);
  sa += __shfl_xor_sync(0xffffffffu, sa, 2);
  qa += __shfl_xor_sync(0xffffffffu, qa, 2);
  if (t < 2) red_add2(&dst[t * 8].x, sa, qa);
}

__device__ __forceinline__ void consumer(const Ctx& c) {
  const int g = c.g, m0 = c.rb * 128;
  float acc[192];
#define X_HALF(hf, TG) \
      _Pragma("unroll") for (int jp = 4 * (hf); jp < 4 * (hf) + 4; ++jp) \
        stsm_tag(sb + (XS + (hf)) * SLOT + rowo + (X ^ ((jp & 3) << 5)), \
                 pack_bf16(acc[128 + 8 * jp], acc[129 + 8 * jp]), pack_bf16(acc[130 + 8 * jp], acc[131 + 8 * jp]), \
                 pack_bf16(acc[132 + 8 * jp], acc[133 + 8 * jp]), pack_bf16(acc[134 + 8 * jp], acc[135 + 8 * jp]), TG, jp & 3);
#pragma unroll
  for (int i = 128; i < 192; ++i) acc[i] = 0.f;
#pragma unroll 1
  for (int layer = 0;; ++layer) {
    {
      PHASE_CTX();
      const uint32_t wu = c.cu >> 2;
      const uint32_t dA0 = (((sb + wu * 8192) & 0x3FFFF) >> 4) | (1u << 16), dB0 = ((sb & 0x3FFFF) >> 4) | (512u << 16);
      {
        PROFX(0);
        if (!RT2 || !layer) mbar_wait(bar + B_FULLS, 0);
        PROFX(1);
        wgmma_fence();
        wgmma_n256_0(acc, D128(dA0 + XS * 1024), D128(dB0 + 2048));
#pragma unroll
        for (int k = 1; k < 4; ++k) wgmma_n256(acc, D128(dA0 + XS * 1024 + k * 2), D128(dB0 + 2048 + k * 128), 1);
        wgmma_commit();
        wgmma_wait<1>();
        float s0 = 0.f, s1 = 0.f, q0 = 0.f, q1 = 0.f;
        if (layer) {
          X_HALF(1, (Tag{0u, 0u, 0u}));
#pragma unroll
          for (int i = 128; i < 192; i += 4) {
            s0 += acc[i] + acc[i + 1]; s1 += acc[i + 2] + acc[i + 3];
            q0 = fmaf(acc[i], acc[i], fmaf(acc[i + 1], acc[i + 1], q0)); q1 = fmaf(acc[i + 2], acc[i + 2], fmaf(acc[i + 3], acc[i + 3], q1));
          }
        }
        asm volatile("" : "+f"(s0), "+f"(s1), "+f"(q0), "+f"(q1) :: "memory");
        wgmma_fence();
        wgmma_n128_0(acc, D128(dA0 + XS * 1024), D128(dB0 + 1024));
#pragma unroll
        for (int k = 1; k < 4; ++k) wgmma_n128(acc, D128(dA0 + XS * 1024 + k * 2), D128(dB0 + 1024 + k * 128), 1);
        wgmma_commit();
        if (layer) {
          PHASE_CTX();
          fence_async_smem();
          nbar_dyn(3 + wu, 128);
          stats_out(s0, s1, q0, q1, g_stats + layer * S_ + m0 + wrow0 + gq, t);
          PROFT(tid_ == 128, layer * 16 + 8);
        }
      }
      uint32_t s = 1, u = 0, sp = 0;
      const int ix = layer ? 99 : 2 * (K0V ? NCOM : min(g, NCOM)) + 1;
#pragma unroll 1
      for (int i = 1; i < 14; ++i) {
        mbar_wait(bar + B_FULLS + s * 8, (u + (s ? layer : 0)) & 1);
        if (layer && (unsigned)(i - 2) < 7u) {
          PHASE_CTX();
          tile_check(sb + ((QA >> (4 * s)) & 15) * SLOT, g_x + (size_t)m0 * D_ + ((2 * g + 2 * i - 2) & 15) * 64, wrow0, lane, lds_vol(sb + SM_EPOCH) + layer);
        }
        const uint32_t da = dA0 + ((QA >> (4 * s)) & 15) * 1024, dk = dB0 + ((QK >> (4 * s)) & 15) * 1024,
                       dq = dB0 + ((QQ >> (4 * s)) & 15) * 1024;
        wgmma_fence();
#pragma unroll
        for (int k = 0; k < 4; ++k) {
          wgmma_n256(acc, D128(da + k * 2), D128(dk + k * 128), 1);
          wgmma_n128(acc, D128(da + k * 2), D128(dq + k * 128), 1);
          if (k == 0) {
            wgmma_commit();
            wgmma_wait<1>();
            if (elected && (unsigned)(i - ix) >= 2u) release2(bar + B_EMPTYS + sp * 8);
          }
        }
        wgmma_commit();
        if ((unsigned)(i - ix) < 2u) {
          PHASE_CTX();
          {
            float s0 = 0.f, s1 = 0.f, q0 = 0.f, q1 = 0.f;
            const uint32_t xa = sb + ((QA >> (4 * sp)) & 15) * SLOT + rowo;
#pragma unroll
            for (int jp = 0; jp < 4; ++jp) {
              uint32_t x0, x1, x2, x3;
              ldsm_x4(x0, x1, x2, x3, xa + (X ^ (jp << 5)));
              s0 += (bf_lo(x0) + bf_hi(x0)) + (bf_lo(x2) + bf_hi(x2));
              s1 += (bf_lo(x1) + bf_hi(x1)) + (bf_lo(x3) + bf_hi(x3));
              q0 = fmaf(bf_lo(x0), bf_lo(x0), fmaf(bf_hi(x0), bf_hi(x0), fmaf(bf_lo(x2), bf_lo(x2), fmaf(bf_hi(x2), bf_hi(x2), q0))));
              q1 = fmaf(bf_lo(x1), bf_lo(x1), fmaf(bf_hi(x1), bf_hi(x1), fmaf(bf_lo(x3), bf_lo(x3), fmaf(bf_hi(x3), bf_hi(x3), q1))));
            }
            stats_out(s0, s1, q0, q1, g_stats + m0 + wrow0 + gq, t);
          }
          __syncwarp();
          if (lane == 0 && i != ix) mbar_arrive(bar + B_XDONE);
          nbar_dyn(3 + wu, 128);
          if (elected) release2(bar + B_EMPTYS + sp * 8);
        }
        if (i == 1 && layer) {
          PHASE_CTX();
          slab_out_half(sb + (XS + 1) * SLOT, g_x + (size_t)m0 * D_ + g * 128 + 64, wrow0, lane);
          __syncwarp();
          if (lane == 0) mbar_arrive(bar + B_XDONE);
          nbar_dyn(3 + wu, 128);
        }
        sp = s;
        if (++s == 3) { s = 0; ++u; }
      }
      {
        const uint64_t dap = make_desc_ns(sb + SM_AP + wu * 1024, 0, 128), dbp = make_desc_ns(sb + SM_BP + (layer & 1) * 6144, 0, 128);
        if (wu == 0) {
          wgmma_wait<0>();
          if (elected) mbar_arrive(bar + B_R0);
          nbar<6, 256>();
        }
        if (layer < 2) mbar_wait(bar + (layer ? B_CS2 : B_CS), 0);
        mbar_wait(bar + B_STAT, layer & 1);
        mbar_wait(bar + B_FULLS + 16, layer & 1);
        wgmma_fence();
        wgmma_n256_k(acc, dap, dbp, 1);
#pragma unroll
        for (int k = 0; k < 4; ++k) wgmma_n256(acc, D128(dA0 + (QA >> 8) * 1024 + k * 2), D128(dB0 + (QK >> 8) * 1024 + k * 128), 1);
        mbar_wait(bar + B_FULLS, 1);
        PROFT(tid_ == 128, layer * 16 + 9);
        wgmma_fence();
#pragma unroll
        for (int k = 0; k < 4; ++k) wgmma_n256(acc, D128(dA0 + (QA & 15) * 1024 + k * 2), D128(dB0 + (QK & 15) * 1024 + k * 128), 1);
        wgmma_commit();
        if (wu) nbar<6, 256>();
#define Q_TAIL() \
        wgmma_n128_k(acc, dap, dbp + 256, 1); \
        _Pragma("unroll") for (int k = 0; k < 4; ++k) wgmma_n128(acc, D128(dA0 + (QA >> 8) * 1024 + k * 2), D128(dB0 + (QQ >> 8) * 1024 + k * 128), 1); \
        _Pragma("unroll") for (int k = 0; k < 4; ++k) wgmma_n128(acc, D128(dA0 + (QA & 15) * 1024 + k * 2), D128(dB0 + (QQ & 15) * 1024 + k * 128), 1);
        Q_TAIL();
        wgmma_commit();
        wgmma_wait<1>();
#pragma unroll
        for (int i = 0; i < 128; ++i) asm volatile("" : "+f"(acc[i]) :: "memory");
      }
    }
    uint32_t xo[32];
    uint32_t oq[8][4];
    {
      PHASE_CTX();
      PROFT(tid_ == 128, layer * 16 + 1);
      const bool isB = layer & 1;
      const int cu = c.cu;
      if (cu >= 4) asm volatile("bar.arrive 7, 256;" ::: "memory");
      if (elected && cu == 4) mbar_arrive(bar + B_R0);
      uint32_t kq[64];
      const uint32_t rowq = rowo & 8191;
      const float rs0 = lds_f(sb + SM_RS + (16 + wrow0 + gq) * 4), rs1 = lds_f(sb + SM_RS + (24 + wrow0 + gq) * 4);
#define Q_DONE() \
      wgmma_wait<0>(); \
      if (lane == 0) release2(bar + B_E0); \
      _Pragma("unroll") for (int i = 128; i < 192; ++i) asm volatile("" : "+f"(acc[i]) :: "memory"); \
      _Pragma("unroll") for (int i = 0; i < 32; ++i) kq[32 + i] = pack_bf16(acc[128 + 2 * i], acc[129 + 2 * i]);
      if (isB) {
        if (cu == 0) asm volatile("bar.arrive 10, 64;" ::: "memory");
        if (elected) release2(bar + B_E1);
        const int e = gq & 1;
        const bool sel = t > (gq >> 1);
        const uint32_t rja = sb + SM_RS + (wrow0 + 2 * t + e) * 4;
        const float rjA0 = lds_f(rja + 32), rjA1 = lds_f(rja + 64), rjB0 = lds_f(rja + (sel ? 0 : 64)), rjB1 = lds_f(rja + (sel ? 32 : 96));
        uint32_t vv[32];
#pragma unroll
        for (int i = 0; i < 16; ++i) { kq[i] = pack_bf16(acc[2 * i], acc[2 * i + 1]); vv[i] = pack_bf16(acc[64 + 2 * i], acc[65 + 2 * i]); }
        const uint32_t rB = sb + 4 * SLOT + wg * 4 * KVT + rowq;
        auto dump = [&](int hp) {
          const uint32_t kb = rB + 2048 + (hp ^ wg) * 2 * KVT;
#pragma unroll
          for (int jp = 0; jp < 4; ++jp) {
            stsm_x4(kb + (X ^ (jp << 5)), kq[16 * hp + 4 * jp], kq[16 * hp + 4 * jp + 1], kq[16 * hp + 4 * jp + 2], kq[16 * hp + 4 * jp + 3]);
            stsm_x4(kb + KVT + (X ^ (jp << 5)), vv[16 * hp + 4 * jp], vv[16 * hp + 4 * jp + 1], vv[16 * hp + 4 * jp + 2], vv[16 * hp + 4 * jp + 3]);
          }
          if (cu == 3) {
            const uint32_t kd = rB + 2048 + 32768 + (1 - hp) * 2 * KVT;
#pragma unroll
            for (int jp = 0; jp < 4; ++jp) {
              stsm_x4(kd + (X ^ (jp << 5)), kq[16 * hp + 4 * jp], kq[16 * hp + 4 * jp + 1], kq[16 * hp + 4 * jp + 2], kq[16 * hp + 4 * jp + 3]);
              stsm_x4(kd + KVT + (X ^ (jp << 5)), vv[16 * hp + 4 * jp], vv[16 * hp + 4 * jp + 1], vv[16 * hp + 4 * jp + 2], vv[16 * hp + 4 * jp + 3]);
            }
            if (hp) asm volatile("bar.arrive 15, 64;" ::: "memory"); else asm volatile("bar.arrive 9, 64;" ::: "memory");
          }
          asm volatile("bar.arrive %0, 224;" :: "r"(hp ? 13 + (cu >> 2) : 8 + (cu & 4)) : "memory");
        };
        uint4* const hbuf = g_halo + ((c.rb * 8 + g) * 2 + (layer >> 1)) * 512 + lane;
        if (cu < 4) {
          nbar<7, 256>();
          dump(0);
        }
#pragma unroll
        for (int i = 16; i < 32; ++i) { kq[i] = pack_bf16(acc[2 * i], acc[2 * i + 1]); vv[i] = pack_bf16(acc[64 + 2 * i], acc[65 + 2 * i]); }
        if (cu >= 4) {
          if (cu == 7) {
#pragma unroll
            for (int jp = 0; jp < 8; ++jp) {
              st_relaxed4(hbuf + jp * 32, ~kq[4 * jp], ~kq[4 * jp + 1], ~kq[4 * jp + 2], ~kq[4 * jp + 3]);
              st_relaxed4(hbuf + 256 + jp * 32, ~vv[4 * jp], ~vv[4 * jp + 1], ~vv[4 * jp + 2], ~vv[4 * jp + 3]);
            }
          }
          dump(0);
          dump(1);
        }
        PROFT(tid_ == 128, layer * 16 + 2);
        constexpr float SC = 0.17677669529663687f * L2E;
        const float fA0 = rjA0 * rs0 * SC, fB0 = rjB0 * rs0 * SC, fA1 = rjA1 * rs1 * SC, fB1 = rjB1 * rs1 * SC;
        const float bA0 = (m0 + wrow0) ? 0.f : -1e30f, bB = sel ? bA0 : 0.f;
        const uint32_t pA_ = e ? 0x1044u : 0x4410u, pB_ = e ? 0x3244u : 0x4432u, pLo = sel ? pB_ : 0x4444u, pHi = sel ? 0x4444u : pB_;
        const uint32_t KX = ((lane >> 3) ^ (lane & 7)) << 4;
        Q_DONE();
        if (cu == 0) {
          nbar<11, 64>();
        } else if (cu == 4) {
          uint4 hv[16];
          if (c.rb > 0) {
            uint32_t n = 0;
#pragma unroll 1
            while (true) {
              uint32_t mn = 0xFFFFFFFFu;
#pragma unroll
              for (int i = 0; i < 16; ++i) hv[i] = ld_relaxed4(hbuf - 16 * 512 + i * 32);
#pragma unroll
              for (int i = 0; i < 16; ++i) mn = __vimin3_u32(__vimin3_u32(mn, hv[i].x, hv[i].y), hv[i].z, hv[i].w);
              if (__all_sync(0xffffffffu, mn != 0u)) break;
              if (++n > (1u << 20)) { g_err = 4u; break; }
            }
          } else {
#pragma unroll
            for (int i = 0; i < 16; ++i) hv[i] = make_uint4(~0u, ~0u, ~0u, ~0u);
          }
          nbar<10, 64>();
#pragma unroll
          for (int i = 0; i < 16; ++i)
            stsm_x4(rB - 4 * KVT + (((i >> 2) & 1) * 2 + (i >> 3)) * KVT + (X ^ ((i & 3) << 5)), ~hv[i].x, ~hv[i].y, ~hv[i].z, ~hv[i].w);
          asm volatile("bar.arrive 11, 64;" ::: "memory");
          nbar<9, 64>();
        } else {
          nbar_dyn(8 + (cu & 4), 224);
        }
        PROFT(tid_ == 128, layer * 16 + 5);
        PROFT(lane == 0 && layer == PL, 136 + cw);
        auto attend = [&](int hp) {
          const uint32_t qad = sb + (XS + 1 - hp) * SLOT + rowo, kt = rB + 2 * (hp ^ wg) * KVT - (lane & 8) * 128, vt = rB + (2 * (hp ^ wg) + 1) * KVT;
          __syncwarp();
          uint32_t kb[2][2][4], vb[2][2][2][4];
#pragma unroll
          for (int h = 0; h < 2; ++h)
#pragma unroll
            for (int nt = 0; nt < 2; ++nt) ldsm_x4(kb[h][nt][0], kb[h][nt][1], kb[h][nt][2], kb[h][nt][3], kt + nt * 1024 + (KX ^ (h << 6)));
#pragma unroll
          for (int ks = 0; ks < 2; ++ks)
#pragma unroll
            for (int np = 0; np < 2; ++np)
#pragma unroll
              for (int h = 0; h < 2; ++h)
                ldsm_x4_t(vb[h][ks][np][0], vb[h][ks][np][1], vb[h][ks][np][2], vb[h][ks][np][3], vt + ks * 2048 + (X ^ (h << 6) ^ (np << 5)));
          if (hp == 0 && lane == 0) release2(bar + B_E3);
          float la[2][2], lb[2][2], mx[2][2], sm[2][2];
#pragma unroll
          for (int h = 0; h < 2; ++h) {
            const int qo = 32 + 16 * hp + 8 * h, ko = 16 * hp + 8 * h;
            float sc[4][4];
#pragma unroll
            for (int nt = 0; nt < 4; ++nt) {
              sc[nt][0] = sc[nt][1] = sc[nt][2] = sc[nt][3] = 0.f;
#pragma unroll
              for (int ks = 0; ks < 2; ++ks)
                mma_bf16(sc[nt], kq[qo + 4 * ks], kq[qo + 4 * ks + 1], kq[qo + 4 * ks + 2], kq[qo + 4 * ks + 3],
                         nt < 2 ? kb[h][nt & 1][2 * ks] : kq[ko + 4 * ks + (nt & 1)], nt < 2 ? kb[h][nt & 1][2 * ks + 1] : kq[ko + 4 * ks + 2 + (nt & 1)]);
            }
            la[h][0] = fmaf(e ? sc[1][1] : sc[1][0], fA0, bA0);
            lb[h][0] = fmaf(sel ? (e ? sc[0][1] : sc[0][0]) : (e ? sc[2][1] : sc[2][0]), fB0, bB);
            la[h][1] = (e ? sc[2][3] : sc[2][2]) * fA1;
            lb[h][1] = fmaf(sel ? (e ? sc[1][3] : sc[1][2]) : (e ? sc[3][3] : sc[3][2]), fB1, bB);
            mx[h][0] = fmaxf(la[h][0], lb[h][0]); mx[h][1] = fmaxf(la[h][1], lb[h][1]);
          }
#pragma unroll
          for (int o = 1; o <= 2; o <<= 1)
#pragma unroll
            for (int h = 0; h < 2; ++h)
#pragma unroll
              for (int r = 0; r < 2; ++r) mx[h][r] = fmaxf(mx[h][r], __shfl_xor_sync(0xffffffffu, mx[h][r], o));
          float oa[2][4][4];
#pragma unroll
          for (int h = 0; h < 2; ++h) {
#pragma unroll
            for (int r = 0; r < 2; ++r) { la[h][r] = ex2(la[h][r] - mx[h][r]); lb[h][r] = ex2(lb[h][r] - mx[h][r]); sm[h][r] = la[h][r] + lb[h][r]; }
            const uint32_t p0 = pack_bf16(la[h][0] * rjA0, lb[h][0] * rjB0), p1 = pack_bf16(la[h][1] * rjA1, lb[h][1] * rjB1);
            const uint32_t a00 = __byte_perm(p0, 0u, pLo), a02 = __byte_perm(p0, 0u, pA_), a03 = __byte_perm(p1, 0u, pLo);
            const uint32_t a10 = __byte_perm(p0, 0u, pHi), a11 = __byte_perm(p1, 0u, pA_), a13 = __byte_perm(p1, 0u, pHi);
#pragma unroll
            for (int i = 0; i < 4; ++i) {
              oa[h][i][0] = oa[h][i][1] = oa[h][i][2] = oa[h][i][3] = 0.f;
              mma_bf16(oa[h][i], a00, 0u, a02, a03, vb[h][0][i >> 1][2 * (i & 1)], vb[h][0][i >> 1][2 * (i & 1) + 1]);
              mma_bf16(oa[h][i], a10, a11, 0u, a13, vb[h][1][i >> 1][2 * (i & 1)], vb[h][1][i >> 1][2 * (i & 1) + 1]);
            }
          }
#pragma unroll
          for (int o = 1; o <= 2; o <<= 1)
#pragma unroll
            for (int h = 0; h < 2; ++h)
#pragma unroll
              for (int r = 0; r < 2; ++r) sm[h][r] += __shfl_xor_sync(0xffffffffu, sm[h][r], o);
          mbar_wait(bar + (hp ? B_XOLD2 : B_XOLD), 1);
#pragma unroll
          for (int jp = 0; jp < 4; ++jp) ldsm_x4(xo[16 * hp + 4 * jp], xo[16 * hp + 4 * jp + 1], xo[16 * hp + 4 * jp + 2], xo[16 * hp + 4 * jp + 3], qad + (X ^ (jp << 5)));
#pragma unroll
          for (int h = 0; h < 2; ++h) {
            const float i0 = rcp(sm[h][0]), i1 = rcp(sm[h][1]);
#pragma unroll
            for (int np = 0; np < 2; ++np)
            {
              uint32_t (&o)[4] = oq[4 * hp + 2 * h + np];
              o[0] = pack_bf16(oa[h][2 * np][0] * i0, oa[h][2 * np][1] * i0); o[1] = pack_bf16(oa[h][2 * np][2] * i1, oa[h][2 * np][3] * i1);
              o[2] = pack_bf16(oa[h][2 * np + 1][0] * i0, oa[h][2 * np + 1][1] * i0); o[3] = pack_bf16(oa[h][2 * np + 1][2] * i1, oa[h][2 * np + 1][3] * i1);
              if (!hp || !H1L) stsm_tag(qad + (X ^ (h << 6) ^ (np << 5)), o[0], o[1], o[2], o[3], make_tag(gq, t, 0u), 2 * h + np);
            }
          }
          if (!hp || !H1L) {
          __syncwarp();
          slab_out_half(sb + (XS + 1 - hp) * SLOT, g_o + (size_t)m0 * D_ + g * 128 + hp * 64, wrow0, lane);
          __syncwarp();
          if (lane == 0) mbar_arrive(bar + (hp ? B_ODONE : B_OH1));
          }
          PROFT(lane == 0 && layer == PL && hp == 0, 128 + cw);
        };
        attend(0);
        if (cu < 4) dump(1);
        if (cu == 4) nbar<15, 64>();
        else if (cu != 0) nbar_dyn(13 + (cu >> 2), 224);
        attend(1);
      } else {
#pragma unroll
        for (int i = 0; i < 32; ++i) kq[i] = pack_bf16(acc[2 * i], acc[2 * i + 1]);
        if (cu < 4) nbar<7, 256>();
        {
          const uint32_t vb = sb + (5 + 3 * wg) * SLOT + (rowq >> 1) + ((lchk ^ ((lane & 7) >> 1)) << 4);
#pragma unroll
          for (int jp = 8; jp < 16; ++jp)
            stsm_x4((vb ^ ((jp & 1) << 5)) + ((jp >> 1) & 3) * 4096,
                    pack_bf16(acc[8 * jp], acc[8 * jp + 1]), pack_bf16(acc[8 * jp + 2], acc[8 * jp + 3]),
                    pack_bf16(acc[8 * jp + 4], acc[8 * jp + 5]), pack_bf16(acc[8 * jp + 6], acc[8 * jp + 7]));
        }
        PROFT(tid_ == 128, layer * 16 + 2);
        Q_DONE();
        const uint32_t pA = sb + (3 + 3 * wg) * SLOT + (rowo & 8191);
        float sc0 = rs0 * L2E, sc1 = rs1 * L2E;
        const uint32_t wa0 = sb + SM_WPHI + lrow * 80 + lchk * 16;
        const uint32_t wu = c.cu >> 2, par = (layer >> 1) & 1;
        float p[2][4][4];
        uint32_t raw[2][4][4], ph[2][4][4];
        float kva[20], oab[2][2][20];
        auto kv_start = [&](int hp) {
#pragma unroll
          for (int h = 0; h < 2; ++h)
#pragma unroll
            for (int cp = 0; cp < 4; ++cp)
              stsm_x4(pA + hp * 16384 + h * 8192 + (X ^ (cp << 5)), ph[h][cp][0], ph[h][cp][1], ph[h][cp][2], ph[h][cp][3]);
          PROFT(tid_ == 128, layer * 16 + 11);
          fence_async_smem();
          nbar<1, 256>();
          const uint32_t hu = 2 * hp + wu;
          const uint32_t dP = (((sb + 3 * SLOT + hu * 8192) & 0x3FFFF) >> 4) | (512u << 16);
          const uint32_t dV = (((sb + 5 * SLOT + hu * 4096) & 0x3FFFF) >> 4) | (((SM_SD - 5 * SLOT - hu * 4096) >> 4) << 16);
          wgmma_fence();
#pragma unroll
          for (int ks = 0; ks < 8; ++ks)
            wgmma_n40_tt(kva, desc64(dP + (ks >> 2) * 3072 + (ks & 3) * 128, 0x40000040u),
                         desc64(dV + (ks >> 2) * (3072u - (2816u << 16)) + (ks & 3) * 64, 0x80000020u), ks != 0);
          wgmma_commit();
        };
        auto kv_end = [&](int hp) {
          wgmma_wait<0>();
#pragma unroll
          for (int i = 0; i < 20; ++i) asm volatile("" : "+f"(kva[i]) :: "memory");
          nbar_dyn(3 + wu, 128);
          PROFT(tid_ == 128, layer * 16 + 12);
          const bool od = lane & 1;
#pragma unroll
          for (int i = 0; i < 4; ++i)
            sts128(sb + (3 + hp) * SLOT + (cw * 128 + i * 32 + lane) * 16,
                   make_uint4(__float_as_uint(kva[4 * i]), __float_as_uint(kva[4 * i + 1]), __float_as_uint(kva[4 * i + 2]),
                              __float_as_uint(od == (i >= 2) ? 1.f : kva[4 * i + 3])));
          sts128(sb + (6 + hp) * SLOT + wg * 8192 + (wq * 32 + lane) * 16,
                 make_uint4(__float_as_uint(od ? kva[11] : kva[3]), __float_as_uint(od ? kva[15] : kva[7]), __float_as_uint(od ? kva[18] : kva[16]), __float_as_uint(1.f)));
          fence_async_smem();
          __syncwarp();
          if (lane == 0) mbar_arrive(bar + B_KVDONE - hp * 32);
          PROFT(tid_ == 128, layer * 16 + 3);
        };
        const uint4* const kvg = g_kv + (g * 2 + (layer >> 1)) * 2560 + cw * 128 + lane;
        uint4 ub[2][5];
        auto kv_load = [&](int hp) {
          uint4 (&u)[5] = ub[hp];
#pragma unroll
          for (int i = 0; i < 4; ++i) u[i] = ld_relaxed4(kvg + hp * 1280 + i * 32);
          u[4] = ld_relaxed4(kvg + hp * 1280 + 1024 - cw * 96);
        };
        auto kv_conv = [&](int hp) {
          uint4 (&u)[5] = ub[hp];
          PROFT(tid_ == 128 && hp == 0, layer * 16 + 10);
          PROFT(lane == 0 && hp == 1 && layer == PL, 128 + cw);
          if (hp == 0) mbar_wait(bar + B_KVDONE - 32, par);
          const bool od = lane & 1;
          uint32_t n = 0;
#pragma unroll 1
          while (!__all_sync(0xffffffffu, (od ? u[2].w : u[0].w) == 0x41800000u && (od ? u[3].w : u[1].w) == 0x41800000u && u[4].w == 0x41800000u)) {
#pragma unroll 1
            while (__any_sync(0xffffffffu, u[4].w < KVTH) && ++n < (1u << 20)) u[4].w = ld_relaxed(&kvg[hp * 1280 + 1024 - cw * 96].w);
            if (++n > (1u << 20)) { g_err = 6u; break; }
            kv_load(hp);
          }
          PROFT(lane == 0 && hp == 1 && layer == PL, 136 + cw);
          PROFT(tid_ == 128 && hp == 0, layer * 16 + 5);
          if (!od) { u[0].w = u[4].x; u[1].w = u[4].y; } else { u[2].w = u[4].x; u[3].w = u[4].y; }
#pragma unroll
          for (int i = 0; i < 4; i += 2)
            stsm_x4(sb + (5 + 3 * hp) * SLOT + rowo + (X ^ ((i & 2) << 4)),
                    pack_bf16(__uint_as_float(u[i].x), __uint_as_float(u[i].y)), pack_bf16(__uint_as_float(u[i].z), __uint_as_float(u[i].w)),
                    pack_bf16(__uint_as_float(u[i + 1].x), __uint_as_float(u[i + 1].y)), pack_bf16(__uint_as_float(u[i + 1].z), __uint_as_float(u[i + 1].w)));
          const uint32_t z2 = pack_bf16(__uint_as_float(u[4].z), __uint_as_float(u[4].z));
          if (t < 2) sts128(sb + (5 + 3 * hp) * SLOT + (wrow0 + gq + 8 * t) * 128 + ((4 ^ gq) << 4), make_uint4(z2, z2, z2, z2));
        };
        auto o_mma = [&](int hp, const uint32_t (&pq)[2][4][4]) {
          float (&oa)[2][20] = oab[hp];
          PROFT(tid_ == 128 && hp == 1, layer * 16 + 4);
          const uint32_t dK = (((sb + (5 + 3 * hp) * SLOT) & 0x3FFFF) >> 4) | (512u << 16);
          wgmma_fence();
#pragma unroll
          for (int ks = 0; ks < 4; ++ks) {
#pragma unroll
            for (int hh = 0; hh < 2; ++hh) wgmma_n40_rs(oa[hh], pq[hh][ks], D128(dK + hh * 512 + ks * 128), ks != 0);
          }
          wgmma_commit();
        };
        auto o_start = [&](int hp, const uint32_t (&pq)[2][4][4]) {
          kv_conv(hp);
          fence_async_smem();
          nbar<1, 256>();
          o_mma(hp, pq);
        };
        auto o_end = [&](int hp) {
          float (&oa)[2][20] = oab[hp];
          wgmma_wait<0>();
#pragma unroll
          for (int i = 0; i < 20; ++i) asm volatile("" : "+f"(oa[0][i]), "+f"(oa[1][i]) :: "memory");
#pragma unroll
          for (int hh = 0; hh < 2; ++hh) {
            const float i0 = rcp(oa[hh][16] + 1e-6f), i1 = rcp(oa[hh][18] + 1e-6f);
            const uint32_t qad = sb + (3 + hp) * SLOT + rowo, hx = hh << 6;
#pragma unroll
            for (int np = 0; np < 2; ++np)
            {
              uint32_t (&o)[4] = oq[4 * hp + 2 * hh + np];
              o[0] = pack_bf16(oa[hh][8 * np] * i0, oa[hh][8 * np + 1] * i0); o[1] = pack_bf16(oa[hh][8 * np + 2] * i1, oa[hh][8 * np + 3] * i1);
              o[2] = pack_bf16(oa[hh][8 * np + 4] * i0, oa[hh][8 * np + 5] * i0); o[3] = pack_bf16(oa[hh][8 * np + 6] * i1, oa[hh][8 * np + 7] * i1);
              if (!hp || !H1L) stsm_tag(qad + (X ^ hx ^ (np << 5)), o[0], o[1], o[2], o[3], make_tag(gq, t, 1u), 2 * hh + np);
            }
          }
          if (!hp || !H1L) {
          __syncwarp();
          slab_out_half(sb + (3 + hp) * SLOT, g_o + (size_t)m0 * D_ + g * 128 + hp * 64, wrow0, lane);
          __syncwarp();
          if (lane == 0) mbar_arrive(bar + (hp ? B_ODONE : B_OH1));
          }
        };
#define XO_LOAD() \
        mbar_wait(bar + B_XOLD, 0); \
        mbar_wait(bar + B_XOLD2, 0); \
        _Pragma("unroll") for (int jp = 0; jp < 8; ++jp) \
          ldsm_x4(xo[4 * jp], xo[4 * jp + 1], xo[4 * jp + 2], xo[4 * jp + 3], sb + (XS + 1 - (jp >> 2)) * SLOT + rowo + (X ^ ((jp & 3) << 5)));
#define SC_RELOAD() \
        sc0 = __uint_as_float(lds_vol(sb + SM_RS + (16 + wrow0 + gq) * 4)) * L2E; sc1 = __uint_as_float(lds_vol(sb + SM_RS + (24 + wrow0 + gq) * 4)) * L2E;
        __syncwarp();
        phi_proj<0>(p, kq, wa0);
        phi_exp(raw[0], p[0], sc0, sc1);
        phi_exp(raw[1], p[1], sc0, sc1);
        phi_proj<16>(p, kq, wa0 + 5120);
        phi_norm<0>(ph, raw, kq, wa0, sc0, sc1, rs0, rs1);
        kv_start(0);
        phi_exp(raw[0], p[0], sc0, sc1);
        kv_end(0);
        SC_RELOAD();
        XO_LOAD();
        phi_exp(raw[1], p[1], sc0, sc1);
        phi_proj<32>(p, kq, wa0);
        phi_norm<16>(ph, raw, kq, wa0 + 5120, sc0, sc1, rs0, rs1);
        kv_start(1);
        if (lane == 0) release2(bar + B_E3);
        phi_exp(raw[0], p[0], sc0, sc1);
        kv_end(1);
        SC_RELOAD();
        phi_exp(raw[1], p[1], sc0, sc1);
        phi_proj<48>(p, kq, wa0 + 5120);
        phi_norm<32>(ph, raw, kq, wa0, sc0, sc1, 1.f, 1.f);
        kv_load(0);
        phi_exp(raw[0], p[0], sc0, sc1);
        phi_exp(raw[1], p[1], sc0, sc1);
        if ((raw[0][2][0] & raw[0][2][2] & raw[0][3][0] & raw[0][3][2] & raw[1][2][0] & raw[1][2][2] & raw[1][3][0] & raw[1][3][2]) == ~0u) sts_f(sb + SM_EPOCH + 12, 0.f);
        o_start(0, ph);
        kv_load(1);
        o_end(0);
        phi_norm<48>(ph, raw, kq, wa0 + 5120, sc0, sc1, 1.f, 1.f);
        o_start(1, ph);
        o_end(1);
      }
      __syncwarp();
      PROFT(lane == 0 && layer == PL, 216 + cw);
      if (lane == 0) mbar_arrive(bar + B_EPI);
      PROFT(tid_ == 128, layer * 16 + 6);
    }
    {
      PHASE_CTX();
      const uint32_t wu = c.cu >> 2;
      const uint32_t dA0 = (((sb + wu * 8192) & 0x3FFFF) >> 4) | (1u << 16), dB0 = ((sb & 0x3FFFF) >> 4) | (512u << 16);
#pragma unroll
      for (int i = 0; i < 32; ++i) { acc[128 + 2 * i] = bf_lo(xo[i]); acc[129 + 2 * i] = bf_hi(xo[i]); }
      uint64_t ta = ((layer & 1) ? WO_A1 : WO_A0) >> 8, tw = (layer & 1) ? WO_B1 : WO_B0;
      mbar_wait(bar + B_FULLT, layer & 1);
      mbar_wait(bar + B_FULLT + 8, layer & 1);
      PROFT(tid_ == 128 && layer == PL, 160);
      wgmma_fence();
#pragma unroll
      for (int k = 0; k < 8; ++k) wgmma_n128_rs(acc, oq[k], D128(dB0 + ((uint32_t)(tw >> (k & 4)) & 15) * 1024 + (k & 3) * 128), 1);
      wgmma_commit();
      tw >>= 8;
      if (lane == 0 && !H1L) release2(bar + B_E2);
#pragma unroll 1
      for (int i = 2; i < 16; ++i) {
        mbar_wait(bar + B_FULLT + i * 8, layer & 1);
        PROFT(tid_ == 128 && layer == PL, 160 + i);
        tile_check(sb + ((uint32_t)ta & 15) * SLOT, g_o + (size_t)m0 * D_ + ((2 * g + (int)(WOORD >> (4 * i))) & 15) * 64, wrow0, lane, ~layer);
        const uint32_t da = dA0 + ((uint32_t)ta & 15) * 1024, db = dB0 + ((uint32_t)tw & 15) * 1024;
        ta >>= 4; tw >>= 4;
        if (i == 16 - WSK && wu) nbar<6, 256>();
        wgmma_fence();
#pragma unroll
        for (int k = 0; k < 4; ++k) wgmma_n128(acc, D128(da + k * 2), D128(db + k * 128), 1);
        wgmma_commit();
        if (i == 15 && !wu) asm volatile("bar.arrive 6, 256;" ::: "memory");
        if (H1L && i == H1L) {
          const uint32_t st = sb + ((layer & 1) ? XS : 4) * SLOT;
#pragma unroll
          for (int k = 0; k < 4; ++k) stsm_tag(st + rowo + (X ^ (k << 5)), oq[4 + k][0], oq[4 + k][1], oq[4 + k][2], oq[4 + k][3], make_tag(gq, t, ~layer), k);
          __syncwarp();
          slab_out_half(st, g_o + (size_t)m0 * D_ + g * 128 + 64, wrow0, lane);
          __syncwarp();
          if (lane == 0) { mbar_arrive(bar + B_ODONE); release2(bar + B_E2); }
        }
        wgmma_wait<1>();
        if (elected && i < 12) release2(bar + B_CONS + (i - 1) * 8);
        if (elected && (unsigned)(i - EI) < 2u && layer + 1 < NLAYERS) release2(bar + B_EMPTYS + (i - EI) * 8);
      }
      const bool last = layer == NLAYERS - 1;
      Tag xt = make_tag(gq, last ? 4 : t, lds_vol(sb + SM_EPOCH) + layer + 1);
      asm volatile("" : "+r"(xt.me), "+r"(xt.mo), "+r"(xt.tg) :: "memory");
      if (RT2 && !last) mbar_wait(bar + B_FULLS, 0);
      wgmma_wait<0>();
#pragma unroll
      for (int i = 128; i < 192; ++i) asm volatile("" : "+f"(acc[i]) :: "memory");
      if (elected && !last) release2(bar + B_EMPTYS + 16);
      PROFT(tid_ == 128, layer * 16 + 7);
      X_HALF(0, xt);
      if (last) {
        __syncwarp();
        slab_out_half(sb + XS * SLOT, c.out + (size_t)m0 * D_ + g * 128, wrow0, lane);
        X_HALF(1, (Tag{0u, 0u, 0u}));
        __syncwarp();
        slab_out_half(sb + (XS + 1) * SLOT, c.out + (size_t)m0 * D_ + g * 128 + 64, wrow0, lane);
        __syncwarp();
        if (lane == 0) mbar_arrive(bar + B_XDONE);
        PROFT(tid_ == 128, layer * 16 + 24);
        break;
      }
      __syncwarp();
      slab_out_half(sb + XS * SLOT, g_x + (size_t)m0 * D_ + g * 128, wrow0, lane, true);
      __syncwarp();
      if (lane == 0) mbar_arrive(bar + B_XH0);
      nbar_dyn(3 + wu, 128);
    }
  }
}

__device__ __forceinline__ int kblock0(int i, int g) {
  const int j = i >> 1, p = max(g, NCOM) + j - NCOM;
  return (j < NCOM ? j : p < 8 ? p : p - 8 + NCOM) * 2 + (i & 1);
}

__device__ __forceinline__ int wo_kblock(int m, int g) { return (2 * g + (int)((WOORD >> (4 * m)) & 15)) & 15; }

__global__ void __cluster_dims__(2, 1, 1) __launch_bounds__(384, 1)
mega_kernel(const __grid_constant__ CUtensorMap tm_x0, const __grid_constant__ CUtensorMap tm_x,
            const __grid_constant__ CUtensorMap tm_o,
            const __grid_constant__ CUtensorMap tm_wA, const __grid_constant__ CUtensorMap tm_wB,
            const __grid_constant__ CUtensorMap tm_woA, const __grid_constant__ CUtensorMap tm_woB,
                        const bf16* __restrict__ wB, const bf16* __restrict__ wphi, bf16* __restrict__ out) {
  extern __shared__ uint8_t smem_raw[];
  const uint32_t sb = (smem_u32(smem_raw) + 1023u) & ~1023u;
  const uint32_t bar = sb + SM_BAR;
  const int warp = __shfl_sync(0xffffffffu, threadIdx.x >> 5, 0), lane = threadIdx.x & 31;
  uint32_t bid = blockIdx.x;
  if (MAP == 3 && gridDim.x == 128 + NX) {
    uint32_t tp;
    asm volatile("mov.u32 %0, %%smid;" : "=r"(tp));
    tp >>= 1;
    const uint32_t u7 = ((tp - 32) * 37) >> 8;
    bid = (tp < 32 ? tp : tp < 60 ? tp + 1 + u7 : tp < 62 ? tp + 4 : (tp - 58) * 8) * 2 + (bid & 1);
  }
  if (bid >= 128 || gridDim.x == NX) {
    const int xb = bid & (NX - 1);
    const int ch = threadIdx.x % 96, rg = threadIdx.x / 96, gg = xb * 2 + ch / 48, sec = (ch % 48) >> 4;
    const uint4* src = reinterpret_cast<const uint4*>(wB + (size_t)rg * 3072 + (sec == 2 ? 0 : 1024 + sec * 1024) + gg * 128 + (ch & 15) * 8);
    float s[8] = {0.f, 0.f, 0.f, 0.f, 0.f, 0.f, 0.f, 0.f};
#pragma unroll 1
    for (int r0 = 0; r0 < 256; r0 += 32) {
      uint4 v[32];
#pragma unroll
      for (int r = 0; r < 32; ++r) v[r] = __ldg(src + (size_t)(r0 + r) * 1536);
#pragma unroll
      for (int r = 0; r < 32; ++r) {
        s[0] += bf_lo(v[r].x); s[1] += bf_hi(v[r].x); s[2] += bf_lo(v[r].y); s[3] += bf_hi(v[r].y);
        s[4] += bf_lo(v[r].z); s[5] += bf_hi(v[r].z); s[6] += bf_lo(v[r].w); s[7] += bf_hi(v[r].w);
      }
    }
    float* cd = g_cs + (ld_relaxed(&g_epoch) & 1) * 6144 + 3072 + xb * 768 + ch * 8;
    red_add4(cd, s[0], s[1], s[2], s[3]);
    red_add4(cd + 4, s[4], s[5], s[6], s[7]);
    nbar<1, 384>();
    if (threadIdx.x < 2) flag_add(&g_csflag[8 + xb * 2 + threadIdx.x].v);
    return;
  }
  const int cr = bid & 1;
  const int g = bid >> 4;
  const int rb = bid & 15;
  const int m0 = rb * 128;

  if (warp < 4) {
    asm volatile("setmaxnreg.dec.sync.aligned.u32 40;");
    asm volatile("barrier.cluster.arrive.relaxed.aligned;" ::: "memory");
    const unsigned int epoch = warp ? ld_relaxed(&g_epoch) : 0u;
    if (warp) cluster_wait();
    unsigned int xbase = epoch * NLAYERS;
    auto wo_a = [&](int layer, int m1) {
      uint64_t ts = ((layer & 1) ? WO_A1 : WO_A0) >> (4 * m1), td = ((layer & 1) ? WO_DA1 : WO_DA0) >> (4 * m1), tk = WOORD >> (4 * m1);
      uint32_t ready = 0u;
#pragma unroll 1
      for (int m = m1; m < 16; ++m) {
        const int kb = (2 * g + (uint32_t)tk) & 15;
        uint32_t dst = sb + ((uint32_t)ts & 15) * SLOT, fb = bar + B_FULLT + m * 8, eb = bar + B_CONS + ((uint32_t)td & 15) * 8;
        int kc = kb * 64;
        ts >>= 4; td >>= 4; tk >>= 4;
        asm volatile("" : "+r"(dst), "+r"(fb), "+r"(eb), "+r"(kc));
        bool fr = false;
        if (!((ready >> kb) & 1)) {
          PROFT(m == 2 && lane == 0, 64 + layer * 16 + 2);
          fr = src_wait_tma(g_of + rb * 32, xbase + layer + 1, 1u << kb, ready, lane, eb, layer & 1);
          fence_async_all();
        }
        if (m == 6) mbar_wait_u(bar + B_EPI, layer & 1);
        if (!fr) mbar_wait_u(eb, layer & 1);
        tma_2d_e(dst, &tm_o, kc, m0, fb);
        PROFT(lane == 0 && layer == PL, 176 + m);
      }
    };
    auto wo_w = [&](int layer) {
      const CUtensorMap* tx = layer == 0 ? &tm_x0 : &tm_x;
      const CUtensorMap* two = (layer & 1) ? &tm_woB : &tm_woA;
      uint64_t ts = (layer & 1) ? WO_B1 : WO_B0, td = (layer & 1) ? WO_DB1 : WO_DB0, tk = WOORD;
      uint32_t pb = 0;
      fence_async_all();
      mbar_wait_u(bar + B_R0, layer & 1);
      expect_tx_e(bar + B_XOLD, 16384);
      tma_2d_e(sb + (XS + 1) * SLOT, tx, g * 128, m0, bar + B_XOLD);
#pragma unroll 1
      for (int m = 0; m < 16; ++m) {
        uint32_t dst = sb + ((uint32_t)ts & 15) * SLOT + cr * 8192, fb = bar + B_FULLT + m * 8, eb = bar + B_CONS + ((uint32_t)td & 15) * 8;
        int kc = ((2 * g + (uint32_t)tk) & 15) * 64;
        ts >>= 4; td >>= 4; tk >>= 4;
        asm volatile("" : "+r"(dst), "+r"(fb), "+r"(eb), "+r"(kc));
        if (eb < bar + B_E3 && pb >= bar + B_E3) mbar_wait_u(bar + B_E2, layer & 1);
        if (eb != pb) mbar_wait_u(eb, layer & 1);
        pb = eb;
        tma_2d_mc_e(dst, two, g * 128 + cr * 64, kc, fb);
        expect_tx_e(fb, m < 2 ? 16384 : 32768);
        PROFT(lane == 0 && layer == PL, 144 + m);
        if (m == ((layer & 1) ? 2 : 0)) {
          expect_tx_e(bar + B_XOLD2, 16384);
          tma_2d_e(sb + XS * SLOT, tx, g * 128 + 64, m0, bar + B_XOLD2);
        }
      }
    };
    if (warp == 0) {
      cluster_wait();
      PROFT(lane == 0, 125);
#pragma unroll 1
      for (int layer = 0; layer < NLAYERS; ++layer) {
        const CUtensorMap* tx = layer == 0 ? &tm_x0 : &tm_x;
        const CUtensorMap* tw = (layer & 1) ? &tm_wB : &tm_wA;
        uint32_t s = layer == 0, u = 0, ready = layer == 0 ? 0xFFFFu : 0u;
#pragma unroll 1
        for (int i = s; i < 16; ++i) {
          const int kb = layer == 0 ? kblock0(i, g) : wo_kblock(i, g), kc = kb * 64;
          const uint32_t fb = bar + B_FULLS + s * 8;
          const uint32_t kd = sb + (((QK >> (4 * s)) & 15) + cr) * SLOT, qd = sb + ((QQ >> (4 * s)) & 15) * SLOT + cr * 8192;
          const uint32_t need = 1u << kb;
          const bool ext = i >= 2 || layer == 0, early = ext && (ready & need) == need;
          mbar_wait_u(bar + B_EMPTYS + s * 8, (u + (s ? layer : 0) + 1) & 1);
          if (early) tma_2d_e(sb + ((QA >> (4 * s)) & 15) * SLOT, tx, kc, m0, fb);
          tma_2d_mc_e(kd, tw, 1024 + cr * 1024 + g * 128, kc, fb);
          tma_2d_mc_e(kd + 8192, tw, 1024 + cr * 1024 + g * 128 + 64, kc, fb);
          tma_2d_mc_e(qd, tw, g * 128 + cr * 64, kc, fb);
          expect_tx_e(fb, ext ? 65536 : 49152);
          PROFT(lane == 0 && layer == 0 && i == 1, 31);
          if (layer == 0 && g >= NCOM && i == XPF + (((g - NCOM) * XPM) >> 2)) {
            if (i <= 2) mbar_wait_u(bar + B_FULLS, 0);
            tma_pf_e(&tm_x0, g * 128, m0);
            tma_pf_e(&tm_x0, g * 128 + 64, m0);
          }
          if (layer < 2 && i >= PFS) {
            const int j = i - PFS;
            if (j < 2) tma_pf_e(layer ? &tm_woB : &tm_woA, g * 128 + j * 64, rb * 64);
            else if (j < 8 && layer == 0) tma_pf_e(&tm_wB, ((j >> 1) - 1) * 1024 + g * 128 + (j & 1) * 64, rb * 64);
          }
          if (ext && !early) {
            PROFT(i == 2 && lane == 0, 64 + layer * 16 + 0);
            src_wait_tma(g_xf + rb * 32, xbase + layer + 1, need, ready, lane, fb, 0);
            PROFT(i == 2 && lane == 0, 64 + layer * 16 + 1);
            fence_async_all();
            tma_2d_e(sb + ((QA >> (4 * s)) & 15) * SLOT, tx, kc, m0, fb);
          }
          if (++s == 3) { s = 0; ++u; }
        }
        if (layer == 0) xbase = ld_relaxed(&g_epoch) * NLAYERS;
        wo_a(layer, 2);
      }
    } else {
      if (warp >= 2) {
        const int h2 = threadIdx.x - 64;
        if (h2 < 16) sts_f(sb + SM_RS + h2 * 4, 0.f);
        if (h2 == 0) sts_f(sb + SM_EPOCH, __uint_as_float(epoch));
        mbar_wait_u(bar + B_FULLS, 0);
        colsum(&tm_wA, g_cs + (epoch & 1) * 6144, rb, g, warp - 2, 2, lane, warp == 2 ? sb + SM_SD : (sb + SM_BP + 1023u) & ~1023u, bar + B_CB + (warp - 2) * 8, 0);
#pragma unroll 1
        for (int i = h2; i < 320; i += 64) g_kv[(g * 16 + rb) * 320 + i] = make_uint4(0u, 0u, 0u, 0u);
        fence_async_all();
        nbar<5, 64>();
        if (h2 == 0) flag_add(&g_csflag[g].v);
        PROFT(h2 == 0, 242);
#pragma unroll 1
        for (int i = h2; i < 512; i += 256) {
          uint4 w[4];
#pragma unroll
          for (int j = 0; j < 4; ++j) w[j] = __ldg(reinterpret_cast<const uint4*>(wphi + (size_t)g * 4096) + i + j * 64);
#pragma unroll
          for (int j = 0; j < 4; ++j) sts128(sb + SM_WPHI + ((i >> 2) + j * 16) * 80 + (i & 3) * 16, w[j]);
        }
      }
      if (warp == 1) {
        if (lane >= 27) {
          const CUtensorMap* tm = lane == 27 ? &tm_o : lane == 28 ? &tm_wB : lane == 29 ? &tm_woA : lane == 30 ? &tm_woB : &tm_x;
          asm volatile("prefetch.tensormap [%0];" ::"l"(tm) : "memory");
        }
        __syncwarp();
        {
#pragma unroll 1
          for (int e = 0;; ++e) {
            if (e > 0 && e < NLAYERS) {
              mbar_wait_u(bar + B_XH0, (e - 1) & 1);
              flag_hint(g_xf + rb * 32 + 2 * g, xbase + e + 1);
            }
            mbar_wait_u(bar + B_XDONE, e & 1);
            PROFT(e < 4, 64 + e * 16 + 4);
            if (e == NLAYERS) {
              if (bid == 0) g_epoch = epoch + 1;
              break;
            }
            PROFT(e < 4, 64 + e * 16 + 5);
            flag_set(g_xf + rb * 32 + 2 * g + 1, xbase + e + 1);
            PROFT(e < 4, 64 + e * 16 + 7);
            if ((e & 1) == 0) {
#pragma unroll 1
              for (int hp = 0; hp < 2; ++hp) {
                uint4* kvl = g_kv + ((g * 2 + (e >> 1)) * 2 + hp) * 1280;
                mbar_wait_u(bar + B_KVDONE - hp * 32, (e >> 1) & 1);
                PROFT(e == PL, 243 + hp * 4);
                bulk_red_add_e(kvl + rb * 64, sb + (3 + hp) * SLOT + rb * 1024, 16384 - rb * 1024);
                if (rb) bulk_red_add_e(kvl, sb + (3 + hp) * SLOT, rb * 1024);
                bulk_red_add_e(kvl + 1024, sb + (6 + hp) * SLOT, 2048);
                bulk_red_add_e(kvl + 1152, sb + (6 + hp) * SLOT + 8192, 2048);
                bulk_commit();
                PROFT(e < 4, 64 + e * 16 + 6);
              }
              bulk_wait_read0();
              __syncwarp();
              if (lane < 2) release2(bar + B_E1);
              __syncwarp();
            }
            mbar_wait_u(bar + B_OH1, e & 1);
            PROFT(e == PL, 251);
            flag_hint(g_of + rb * 32 + 2 * g, xbase + e + 1);
            PROFT(e < 4, 64 + e * 16 + 9);
            mbar_wait_u(bar + B_ODONE, e & 1);
            PROFT(e < 4, 64 + e * 16 + 8);
            flag_hint(g_of + rb * 32 + 2 * g + 1, xbase + e + 1);
            PROFT(e < 4, 64 + e * 16 + 11);
          }
        }
      } else {
        const int h2 = threadIdx.x - 64;
        const float* cs = g_cs + (epoch & 1) * 6144;
#pragma unroll 1
        for (int layer = 0; layer < NLAYERS; ++layer) {
          if (warp == 2 && layer < 2) {
            if (lane == 0) flag_wait_t<128>(&g_csflag[layer * 8 + g].v, (epoch + 1) * (16u + layer));
            __syncwarp();
            float4 a[3];
#pragma unroll
            for (int i = 0; i < 3; ++i) a[i] = __ldcg(reinterpret_cast<const float4*>(cs + layer * 3072 + g * 384) + i * 32 + lane);
#pragma unroll 1
            for (int i = 0; i < 3; ++i) {
              const float av[4] = {a[0].x, a[0].y, a[0].z, a[0].w};
              a[0] = a[1]; a[1] = a[2];
#pragma unroll
              for (int j = 0; j < 4; ++j) {
                const float c1 = bf16r(av[j]), c2 = bf16r(av[j] - c1), c3 = (av[j] - c1) - c2;
                sts128(sb + SM_BP + layer * 6144 + ((i * 32 + lane) * 4 + j) * 16, make_uint4(pack_bf16(c1, c2), pack_bf16(c3, 0.f), 0u, 0u));
              }
            }
            fence_async_smem();
            __syncwarp();
            if (lane == 0) mbar_arrive(bar + (layer ? B_CS2 : B_CS));
            PROFT(lane == 0, 64 + layer * 16 + 12);
            if (layer == 0) {
              uint4* hz = g_halo + (rb * 8 + g) * 1024;
#pragma unroll 2
              for (int i = lane; i < 1024; i += 32) hz[i] = make_uint4(0u, 0u, 0u, 0u);
              if (lane < 12) reinterpret_cast<float4*>(g_cs + ((epoch & 1) ^ 1) * 6144 + bid * 48)[lane] = make_float4(0.f, 0.f, 0.f, 0.f);
              g_stats[(2 + (lane >> 4)) * S_ + m0 + g * 16 + (lane & 15)] = make_float2(0.f, 0.f);
              __syncwarp();
              if (lane == 0) flag_add(&g_csflag[8 + g].v);
            }
          }
          if (warp == 3) {
            const bool hal = (layer & 1) && rb > 0;
            {
              uint32_t rdy = 0u;
              src_wait<256>(g_xf + rb * 32, xbase + layer + 1, 0xAAAAu, rdy, lane);
              rdy = 0u;
              if (hal) src_wait<256>(g_xf + (rb - 1) * 32, xbase + layer + 1, 0xAAAAu, rdy, lane);
            }
            float2 u[5];
            const float2* sp = g_stats + layer * S_ + m0 + lane;
#pragma unroll
            for (int i = 0; i < 4; ++i) u[i] = __ldcg(sp + i * 32);
            u[4] = __ldcg(hal ? sp - 16 : sp);
            if (layer == 3) g_stats[(lane >> 4) * S_ + m0 + g * 16 + (lane & 15)] = make_float2(0.f, 0.f);
#pragma unroll
            for (int i = 0; i < 5; ++i) {
              const int r = i < 4 ? 16 + i * 32 + lane : lane;
              const float mean = u[i].x * (1.f / D_);
              const float var = fmaxf(fmaf(-u[i].x, mean, u[i].y) * (1.f / D_), 0.f);
              float sd;
              asm("sqrt.approx.f32 %0, %1;" : "=f"(sd) : "f"(bf16r(bf16r(var) + 1e-5f)));
              sd = bf16r(sd);
              if (i < 4 || hal) sts_f(sb + SM_RS + r * 4, rcp(sd));
              if (i < 4) {
                const float hm = -0.5f * bf16r(mean);
                const uint32_t s2 = pack_bf16(sd, sd);
                if (!(layer & 1)) sts128(sb + SM_SD + (r - 16) * 64 + ((r >> 1) & 3) * 16, make_uint4(s2, s2, s2, s2));
                sts128(sb + SM_AP + (r - 16) * 16, make_uint4(pack_bf16(hm, hm), pack_bf16(hm, 0.f), 0u, 0u));
              }
            }
            fence_async_smem();
            __syncwarp();
            if (lane == 0) mbar_arrive(bar + B_STAT);
            PROFT(lane == 0, 64 + layer * 16 + 14);
            wo_w(__shfl_sync(0xffffffffu, layer, 0));
          }
        }
      }
    }
    __syncwarp();
    asm volatile("barrier.cluster.arrive.relaxed.aligned;\nbarrier.cluster.wait.aligned;\n" ::: "memory");
  } else {
    if (warp == 5) {
      if (lane == 0) {
        mbar_init(bar + B_FULLS, 1);
        asm volatile("fence.mbarrier_init.release.cluster;" ::: "memory");
      }
      __syncwarp();
      expect_tx_e(bar + B_FULLS, 65536);
      const int kc0 = (g || !K0V) ? 0 : 128;
      tma_2d_e(sb + XS * SLOT, &tm_x0, kc0, m0, bar + B_FULLS);
#pragma unroll
      for (int j = 0; j < 6; ++j)
        tma_2d_e(sb + (j < 4 ? j + 4 : j - 2) * 8192, &tm_wA, (j < 4 ? 1024 + (j >> 1) * 1024 : 0) + g * 128 + (j & 1) * 64, kc0, bar + B_FULLS);
      PROFT(lane == 0, 241);
    }
    if (lane < 8 && warp != 5 && threadIdx.x != 128) {
      const int i = (warp - 4) * 8 + lane;
      mbar_init(bar + i * 8, i < 32 ? 1u << ((BAR_CNT >> (2 * i)) & 3) : i < 48 ? 1u : (i == 59 || i == 60 || i == 62) ? 16u : (i == 48 || i == 63) ? 8u : 4u);
      asm volatile("fence.mbarrier_init.release.cluster;" ::: "memory");
    }
    __syncwarp();
    asm volatile("barrier.cluster.arrive.relaxed.aligned;" ::: "memory");
    asm volatile("setmaxnreg.inc.sync.aligned.u32 232;");
    cluster_wait();
    PROFT(threadIdx.x == 128, 0);
    Ctx c; c.sb = sb; c.g = g; c.rb = rb; c.cu = warp - 4; c.out = out;
    consumer(c);
    asm volatile("bar.warp.sync 0xffffffff;\nbarrier.cluster.arrive.relaxed.aligned;\nbarrier.cluster.wait.aligned;\n" ::: "memory");
  }
}

typedef CUresult (*PFN_encodeTiled)(CUtensorMap*, CUtensorMapDataType, cuuint32_t, void*, const cuuint64_t*, const cuuint64_t*,
                                    const cuuint32_t*, const cuuint32_t*, CUtensorMapInterleave, CUtensorMapSwizzle,
                                    CUtensorMapL2promotion, CUtensorMapFloatOOBfill);

static CUtensorMap make_map(PFN_encodeTiled enc, const void* ptr, uint64_t cols, uint64_t rows, uint32_t box_c, uint32_t box_r, uint32_t nb = 1) {
  CUtensorMap m;
  cuuint64_t dims[3] = {nb > 1 ? box_c : cols, rows, cols / box_c};
  cuuint64_t strides[2] = {cols * 2, box_c * 2};
  cuuint32_t box[3] = {box_c, box_r, nb};
  cuuint32_t es[3] = {1, 1, 1};
  CUresult r = enc(&m, CU_TENSOR_MAP_DATA_TYPE_BFLOAT16, nb > 1 ? 3 : 2, const_cast<void*>(ptr), dims, strides, box, es, CU_TENSOR_MAP_INTERLEAVE_NONE,
      CU_TENSOR_MAP_SWIZZLE_128B, CU_TENSOR_MAP_L2_PROMOTION_L2_256B, CU_TENSOR_MAP_FLOAT_OOB_FILL_NONE);
  (void)r;
  return m;
}

extern "C" void kernel_launch(void* const* d_in, const int* in_sizes, int n_in, void* d_out, int out_size) {
  const bf16* A_x = (const bf16*)d_in[0];
  const bf16* A_wqkv = (const bf16*)d_in[1];
  const bf16* A_wphi = (const bf16*)d_in[2];
  const bf16* A_wo = (const bf16*)d_in[3];
  const bf16* B_wqkv = (const bf16*)d_in[5];
  const bf16* B_wo = (const bf16*)d_in[6];
  bf16* out = (bf16*)d_out;

  static PFN_encodeTiled enc = nullptr;
  static bf16 *p_x, *p_o;
  static bool together;
  if (!enc) {
    void* fn = nullptr; cudaDriverEntryPointQueryResult qr;
    cudaGetDriverEntryPoint("cuTensorMapEncodeTiled", &fn, cudaEnableDefault, &qr);
    enc = (PFN_encodeTiled)fn;
    cudaGetSymbolAddress((void**)&p_x, g_x);
    cudaGetSymbolAddress((void**)&p_o, g_o);
    cudaFuncSetAttribute(mega_kernel, cudaFuncAttributeMaxDynamicSharedMemorySize, SM_TOTAL);
    cudaLaunchConfig_t cfg = {};
    cfg.gridDim = dim3(128 + NX); cfg.blockDim = dim3(384); cfg.dynamicSmemBytes = SM_TOTAL;
    cudaLaunchAttribute at[1];
    at[0].id = cudaLaunchAttributeClusterDimension; at[0].val.clusterDim.x = 2; at[0].val.clusterDim.y = 1; at[0].val.clusterDim.z = 1;
    cfg.attrs = at; cfg.numAttrs = 1;
    int ncl = 0;
    together = cudaOccupancyMaxActiveClusters(&ncl, mega_kernel, &cfg) == cudaSuccess && 2 * ncl == 128 + NX;
    int nsm = 0;
    cudaDeviceGetAttribute(&nsm, cudaDevAttrMultiProcessorCount, 0);
    together = together && nsm == 128 + NX;
  }
  CUtensorMap tm_x0 = make_map(enc, A_x, 1024, 2048, 64, 128);
  CUtensorMap tm_x = make_map(enc, p_x, 1024, 2048, 64, 128);
  CUtensorMap tm_o = make_map(enc, p_o, 1024, 2048, 64, 128);
  CUtensorMap tm_wA = make_map(enc, A_wqkv, 3072, 1024, 64, 64);
  CUtensorMap tm_wB = make_map(enc, B_wqkv, 3072, 1024, 64, 64);
  CUtensorMap tm_woA = make_map(enc, A_wo, 1024, 1024, 64, 64);
  CUtensorMap tm_woB = make_map(enc, B_wo, 1024, 1024, 64, 64);
  if (!together) mega_kernel<<<NX, 384, SM_TOTAL, cudaStreamPerThread>>>(tm_x0, tm_x, tm_o, tm_wA, tm_wB, tm_woA, tm_woB, B_wqkv, A_wphi, out);
  mega_kernel<<<together ? 128 + NX : 128, 384, SM_TOTAL, cudaStreamPerThread>>>(tm_x0, tm_x, tm_o, tm_wA, tm_wB, tm_woA, tm_woB,
                                                                                 B_wqkv, A_wphi, out);
}
```

```cpp
#include <cuda_runtime.h>
#include <cuda_bf16.h>
#include <cuda.h>
#include <stdint.h>

typedef __nv_bfloat16 bf16;

constexpr int S_ = 2048, D_ = 1024;

struct __align__(128) Flag { unsigned int v; unsigned int pad[31]; };
__device__ __align__(1024) bf16 g_x[S_ * D_];
__device__ __align__(1024) bf16 g_o[S_ * D_];
__device__ __align__(1024) uint4 g_halo[128 * 2 * 512];
__device__ __align__(1024) uint4 g_kv[8 * 2 * 2 * 1280];
__device__ __align__(1024) float2 g_stats[4 * S_];
__device__ __align__(1024) float g_cs[2 * 2 * 3072];
__device__ Flag g_csflag[16];
__device__ __align__(128) unsigned int g_xf[16 * 32], g_of[16 * 32];
__device__ unsigned int g_epoch, g_err;
#define PROFT(cond, idx) asm volatile("" ::: "memory")

__device__ __forceinline__ uint32_t smem_u32(const void* p) { return (uint32_t)__cvta_generic_to_shared(p); }
__device__ __forceinline__ void mbar_init(uint32_t bar, uint32_t count) {
  asm volatile("mbarrier.init.shared::cta.b64 [%0], %1;" ::"r"(bar), "r"(count) : "memory");
}
__device__ __forceinline__ void mbar_expect_tx(uint32_t bar, uint32_t bytes) {
  asm volatile("mbarrier.arrive.expect_tx.shared::cta.b64 _, [%0], %1;" ::"r"(bar), "r"(bytes) : "memory");
}
__device__ __forceinline__ void mbar_arrive(uint32_t bar) {
  asm volatile("mbarrier.arrive.shared::cta.b64 _, [%0];" ::"r"(bar) : "memory");
}
__device__ __forceinline__ bool mbar_try_wait(uint32_t bar, uint32_t parity) {
  uint32_t ok;
  asm volatile("{\n.reg .pred p;\nmbarrier.try_wait.parity.shared::cta.b64 p, [%1], %2;\nselp.b32 %0, 1, 0, p;\n}\n"
               : "=r"(ok) : "r"(bar), "r"(parity) : "memory");
  return ok != 0;
}
__device__ __forceinline__ bool mbar_test_wait(uint32_t bar, uint32_t parity) {
  uint32_t ok;
  asm volatile("{\n.reg .pred p;\nmbarrier.test_wait.parity.shared::cta.b64 p, [%1], %2;\nselp.b32 %0, 1, 0, p;\n}\n"
               : "=r"(ok) : "r"(bar), "r"(parity) : "memory");
  return ok != 0;
}
__device__ __forceinline__ uint64_t gtimer() {
  uint64_t t; asm volatile("mov.u64 %0, %globaltimer;" : "=l"(t)); return t;
}
__device__ __forceinline__ void mbar_wait(uint32_t bar, uint32_t parity) {
  uint32_t n = 0;
#pragma unroll 1
  while (!mbar_try_wait(bar, parity)) {
    if (++n > (1u << 22)) { g_err = 1u; break; }
  }
}
__device__ __forceinline__ unsigned int ld_acquire(const unsigned int* p) {
  unsigned int v; asm volatile("ld.acquire.gpu.global.u32 %0, [%1];" : "=r"(v) : "l"(p) : "memory"); return v;
}
__device__ __forceinline__ void flag_add(unsigned int* p) {
  asm volatile("red.release.gpu.global.add.u32 [%0], 1;" ::"l"(p) : "memory");
}
__device__ __forceinline__ void flag_set(unsigned int* p, unsigned int v) {
  asm volatile("st.release.gpu.global.u32 [%0], %1;" ::"l"(p), "r"(v) : "memory");
}
__device__ __forceinline__ void flag_hint(unsigned int* p, unsigned int v) {
  asm volatile("st.relaxed.gpu.global.u32 [%0], %1;" ::"l"(p), "r"(v) : "memory");
}
template <int SLEEP>
__device__ __forceinline__ void src_wait(const unsigned int* f, unsigned int target, uint32_t need, uint32_t& ready, int lane) {
  uint32_t n = 0;
#pragma unroll 1
  while ((ready & need) != need) {
    const unsigned int v = ld_acquire(f + (lane & 15));
    ready = __ballot_sync(0xffffffffu, (int)(v - target) >= 0);
    if (SLEEP) { if ((ready & need) != need) __nanosleep(SLEEP); }
    if (++n > (1u << 20)) { g_err = 3u; break; }
  }
  __syncwarp();
}
__device__ __forceinline__ unsigned int ld_relaxed(const unsigned int* p) {
  unsigned int v; asm volatile("ld.relaxed.gpu.global.u32 %0, [%1];" : "=r"(v) : "l"(p) : "memory"); return v;
}
__device__ __forceinline__ bool src_wait_tma(const unsigned int* f, unsigned int target, uint32_t need, uint32_t& ready, int lane, uint32_t eb, uint32_t par) {
  uint32_t n = 0;
  bool fr = false;
#pragma unroll 1
  while ((ready & need) != need) {
    const unsigned int v = ld_acquire(f + (lane & 15));
    fr = __all_sync(0xffffffffu, mbar_test_wait(eb, par));
    ready = __ballot_sync(0xffffffffu, (int)(v - target) >= 0);
    if (++n > (1u << 20)) { g_err = 3u; break; }
  }
  return fr;
}
__device__ __forceinline__ uint4 ld_relaxed4(const uint4* p) {
  uint4 v; asm volatile("ld.relaxed.gpu.global.v4.u32 {%0,%1,%2,%3}, [%4];" : "=r"(v.x), "=r"(v.y), "=r"(v.z), "=r"(v.w) : "l"(p) : "memory"); return v;
}
__device__ __forceinline__ void st_relaxed4(uint4* p, uint32_t a, uint32_t b, uint32_t c, uint32_t d) {
  asm volatile("st.relaxed.gpu.global.v4.u32 [%0], {%1,%2,%3,%4};" ::"l"(p), "r"(a), "r"(b), "r"(c), "r"(d) : "memory");
}
template <int SLEEP>
__device__ __forceinline__ void flag_wait_t(const unsigned int* p, unsigned int target) {
  uint32_t n = 0;
#pragma unroll 1
  while ((int)(ld_acquire(p) - target) < 0) {
    if (SLEEP) __nanosleep(SLEEP);
    if (++n > (1u << 20)) { g_err = 2u; break; }
  }
}
__device__ __forceinline__ void flag_wait(const unsigned int* p, unsigned int target) { flag_wait_t<0>(p, target); }
__device__ __forceinline__ void flag_wait_slow(const unsigned int* p, unsigned int target) { flag_wait_t<256>(p, target); }
__device__ __forceinline__ void tma_load_2d(uint32_t dst, const CUtensorMap* tm, int c0, int c1, uint32_t bar) {
  asm volatile("cp.async.bulk.tensor.2d.shared::cluster.global.mbarrier::complete_tx::bytes [%0], [%1, {%2, %3}], [%4];"
               ::"r"(dst), "l"(tm), "r"(c0), "r"(c1), "r"(bar) : "memory");
}
__device__ __forceinline__ void tma_load_2d_mc(uint32_t dst, const CUtensorMap* tm, int c0, int c1, uint32_t bar, uint16_t mask) {
  asm volatile("cp.async.bulk.tensor.2d.shared::cluster.global.mbarrier::complete_tx::bytes.multicast::cluster [%0], [%1, {%2, %3}], [%4], %5;"
               ::"r"(dst), "l"(tm), "r"(c0), "r"(c1), "r"(bar), "h"(mask) : "memory");
}
__device__ __forceinline__ void mbar_wait_u(uint32_t bar, uint32_t parity) {
  uint32_t n = 0;
#pragma unroll 1
  while (!__all_sync(0xffffffffu, mbar_try_wait(bar, parity))) {
    if (++n > (1u << 22)) { g_err = 1u; break; }
  }
}
__device__ __forceinline__ void expect_tx_e(uint32_t bar, uint32_t bytes) {
  asm volatile("{\n.reg .pred p;\nelect.sync _|p, 0xffffffff;\n@p mbarrier.arrive.expect_tx.shared::cta.b64 _, [%0], %1;\n}\n" ::"r"(bar), "r"(bytes) : "memory");
}
__device__ __forceinline__ void tma_2d_e(uint32_t dst, const CUtensorMap* tm, int c0, int c1, uint32_t bar) {
  asm volatile("{\n.reg .pred p;\nelect.sync _|p, 0xffffffff;\n"
               "@p cp.async.bulk.tensor.2d.shared::cluster.global.mbarrier::complete_tx::bytes [%0], [%1, {%2, %3}], [%4];\n}\n"
               ::"r"(dst), "l"(tm), "r"(c0), "r"(c1), "r"(bar) : "memory");
}
__device__ __forceinline__ void tma_2d_mc_e(uint32_t dst, const CUtensorMap* tm, int c0, int c1, uint32_t bar) {
  asm volatile("{\n.reg .pred p;\nelect.sync _|p, 0xffffffff;\n"
               "@p cp.async.bulk.tensor.2d.shared::cluster.global.mbarrier::complete_tx::bytes.multicast::cluster [%0], [%1, {%2, %3}], [%4], %5;\n}\n"
               ::"r"(dst), "l"(tm), "r"(c0), "r"(c1), "r"(bar), "h"((uint16_t)3) : "memory");
}
__device__ __forceinline__ void tma_pf_e(const CUtensorMap* tm, int c0, int c1) {
  asm volatile("{\n.reg .pred p;\nelect.sync _|p, 0xffffffff;\n"
               "@p cp.async.bulk.prefetch.tensor.2d.L2.global.tile [%0, {%1, %2}];\n}\n" ::"l"(tm), "r"(c0), "r"(c1) : "memory");
}
__device__ __forceinline__ void tma_2d_to_e(uint32_t dst, const CUtensorMap* tm, int c0, int c1, uint32_t bar, uint32_t mask) {
  asm volatile("{\n.reg .pred p;\nelect.sync _|p, 0xffffffff;\n"
               "@p cp.async.bulk.tensor.2d.shared::cluster.global.mbarrier::complete_tx::bytes.multicast::cluster [%0], [%1, {%2, %3}], [%4], %5;\n}\n"
               ::"r"(dst), "l"(tm), "r"(c0), "r"(c1), "r"(bar), "h"((uint16_t)mask) : "memory");
}
__device__ __forceinline__ void tma_3d_mc_e(uint32_t dst, const CUtensorMap* tm, int c1, int c2, uint32_t bar) {
  asm volatile("{\n.reg .pred p;\nelect.sync _|p, 0xffffffff;\n"
               "@p cp.async.bulk.tensor.3d.shared::cluster.global.mbarrier::complete_tx::bytes.multicast::cluster [%0], [%1, {%6, %2, %3}], [%4], %5;\n}\n"
               ::"r"(dst), "l"(tm), "r"(c1), "r"(c2), "r"(bar), "h"((uint16_t)3), "r"(0) : "memory");
}
__device__ __forceinline__ uint32_t poll_flags(const unsigned int* f, unsigned int target, int lane) {
  const unsigned int v = ld_acquire(f + (lane & 15));
  const uint32_t r = __ballot_sync(0xffffffffu, (int)(v - target) >= 0);
  __syncwarp();
  return r;
}
__device__ __forceinline__ void mbar_arrive_cluster(uint32_t local_bar, uint32_t rank) {
  asm volatile("{\n.reg .b32 ra;\nmapa.shared::cluster.u32 ra, %0, %1;\nmbarrier.arrive.shared::cluster.b64 _, [ra];\n}\n"
               ::"r"(local_bar), "r"(rank) : "memory");
}
__device__ __forceinline__ void release2(uint32_t bar) { mbar_arrive_cluster(bar, 0); mbar_arrive_cluster(bar, 1); }
__device__ __forceinline__ void tma_store_2d(const CUtensorMap* tm, uint32_t src, int c0, int c1) {
  asm volatile("cp.async.bulk.tensor.2d.global.shared::cta.bulk_group [%0, {%2, %3}], [%1];"
               ::"l"(tm), "r"(src), "r"(c0), "r"(c1) : "memory");
}
__device__ __forceinline__ void bulk_store(void* dst, uint32_t src, uint32_t bytes) {
  asm volatile("cp.async.bulk.global.shared::cta.bulk_group [%0], [%1], %2;" ::"l"(dst), "r"(src), "r"(bytes) : "memory");
}
__device__ __forceinline__ void bulk_load(uint32_t dst, const void* src, uint32_t bytes, uint32_t bar) {
  asm volatile("cp.async.bulk.shared::cluster.global.mbarrier::complete_tx::bytes [%0], [%1], %2, [%3];" ::"r"(dst), "l"(src), "r"(bytes), "r"(bar) : "memory");
}
__device__ __forceinline__ void bulk_red_add(void* dst, uint32_t src, uint32_t bytes) {
  asm volatile("cp.reduce.async.bulk.global.shared::cta.bulk_group.add.f32 [%0], [%1], %2;" ::"l"(dst), "r"(src), "r"(bytes) : "memory");
}
__device__ __forceinline__ void bulk_red_add_e(void* dst, uint32_t src, uint32_t bytes) {
  asm volatile("{\n.reg .pred p;\nelect.sync _|p, 0xffffffff;\n@p cp.reduce.async.bulk.global.shared::cta.bulk_group.add.f32 [%0], [%1], %2;\n}\n" ::"l"(dst), "r"(src), "r"(bytes) : "memory");
}
__device__ __forceinline__ void bulk_commit() { asm volatile("cp.async.bulk.commit_group;" ::: "memory"); }
__device__ __forceinline__ void bulk_wait_read0() { asm volatile("cp.async.bulk.wait_group.read 0;" ::: "memory"); }
__device__ __forceinline__ void bulk_wait0() { asm volatile("cp.async.bulk.wait_group 0;" ::: "memory"); }
__device__ __forceinline__ void fence_async_smem() { asm volatile("fence.proxy.async.shared::cta;" ::: "memory"); }
__device__ __forceinline__ void fence_async_all() { asm volatile("fence.proxy.async.global;" ::: "memory"); }
__device__ __forceinline__ void wgmma_fence() { asm volatile("wgmma.fence.sync.aligned;" ::: "memory"); }
__device__ __forceinline__ void wgmma_commit() { asm volatile("wgmma.commit_group.sync.aligned;" ::: "memory"); }
template <int N> __device__ __forceinline__ void wgmma_wait() { asm volatile("wgmma.wait_group.sync.aligned %0;" ::"n"(N) : "memory"); }
__device__ __forceinline__ void cluster_arrive() { asm volatile("barrier.cluster.arrive.release.aligned;" ::: "memory"); }
__device__ __forceinline__ void cluster_wait() { asm volatile("barrier.cluster.wait.acquire.aligned;" ::: "memory"); }
template <int ID, int N> __device__ __forceinline__ void nbar() { asm volatile("bar.sync %0, %1;" ::"n"(ID), "n"(N) : "memory"); }
__device__ __forceinline__ uint64_t make_desc(uint32_t addr, uint32_t lbo_bytes, uint32_t sbo_bytes) {
  uint64_t d = 0;
  d |= (uint64_t)((addr & 0x3FFFF) >> 4);
  d |= (uint64_t)((lbo_bytes >> 4) & 0x3FFF) << 16;
  d |= (uint64_t)((sbo_bytes >> 4) & 0x3FFF) << 32;
  d |= (uint64_t)1 << 62;
  return d;
}
__device__ __forceinline__ uint64_t desc64(uint32_t lo, uint32_t hi) { return (uint64_t)lo | ((uint64_t)hi << 32); }
__device__ __forceinline__ uint32_t pack_bf16(float lo, float hi) {
  uint32_t r; asm("cvt.rn.bf16x2.f32 %0, %1, %2;" : "=r"(r) : "f"(hi), "f"(lo)); return r;
}
__device__ __forceinline__ uint32_t mul_bf16x2(uint32_t a, uint32_t s, bool hi) {
  __nv_bfloat162 x = *reinterpret_cast<__nv_bfloat162*>(&a), y = *reinterpret_cast<__nv_bfloat162*>(&s);
  x = __hmul2(x, hi ? __high2bfloat162(y) : __low2bfloat162(y));
  return *reinterpret_cast<uint32_t*>(&x);
}
__device__ __forceinline__ float bf16r(float x) { return __bfloat162float(__float2bfloat16_rn(x)); }
__device__ __forceinline__ float bf_lo(uint32_t u) { return __uint_as_float(u << 16); }
__device__ __forceinline__ float bf_hi(uint32_t u) { return __uint_as_float(u & 0xFFFF0000u); }
__device__ __forceinline__ float ex2(float x) { float r; asm("ex2.approx.ftz.f32 %0, %1;" : "=f"(r) : "f"(x)); return r; }
__device__ __forceinline__ float rcp(float x) { float r; asm("rcp.approx.ftz.f32 %0, %1;" : "=f"(r) : "f"(x)); return r; }
__device__ __forceinline__ void mma_bf16(float (&d)[4], uint32_t a0, uint32_t a1, uint32_t a2, uint32_t a3, uint32_t b0, uint32_t b1) {
  asm("mma.sync.aligned.m16n8k16.row.col.f32.bf16.bf16.f32 {%0,%1,%2,%3}, {%4,%5,%6,%7}, {%8,%9}, {%0,%1,%2,%3};"
               : "+f"(d[0]), "+f"(d[1]), "+f"(d[2]), "+f"(d[3]) : "r"(a0), "r"(a1), "r"(a2), "r"(a3), "r"(b0), "r"(b1));
}
__device__ __forceinline__ void ldsm_x4(uint32_t& r0, uint32_t& r1, uint32_t& r2, uint32_t& r3, uint32_t addr) {
  asm volatile("ldmatrix.sync.aligned.m8n8.x4.shared.b16 {%0,%1,%2,%3}, [%4];"
               : "=r"(r0), "=r"(r1), "=r"(r2), "=r"(r3) : "r"(addr) : "memory");
}
__device__ __forceinline__ void ldsm_x4_t(uint32_t& r0, uint32_t& r1, uint32_t& r2, uint32_t& r3, uint32_t addr) {
  asm volatile("ldmatrix.sync.aligned.m8n8.x4.trans.shared.b16 {%0,%1,%2,%3}, [%4];"
               : "=r"(r0), "=r"(r1), "=r"(r2), "=r"(r3) : "r"(addr) : "memory");
}
__device__ __forceinline__ void ldsm_x2_t(uint32_t& r0, uint32_t& r1, uint32_t addr) {
  asm volatile("ldmatrix.sync.aligned.m8n8.x2.trans.shared.b16 {%0,%1}, [%2];"
               : "=r"(r0), "=r"(r1) : "r"(addr) : "memory");
}
__device__ __forceinline__ void stsm_x4(uint32_t addr, uint32_t r0, uint32_t r1, uint32_t r2, uint32_t r3) {
  asm volatile("stmatrix.sync.aligned.m8n8.x4.shared.b16 [%0], {%1,%2,%3,%4};"
               ::"r"(addr), "r"(r0), "r"(r1), "r"(r2), "r"(r3) : "memory");
}
__device__ __forceinline__ void stsm_x4_p(bool on, uint32_t addr, uint32_t r0, uint32_t r1, uint32_t r2, uint32_t r3) {
  asm volatile("{\n.reg .pred p;\nsetp.ne.b32 p, %5, 0;\n@p stmatrix.sync.aligned.m8n8.x4.shared.b16 [%0], {%1,%2,%3,%4};\n}\n"
               ::"r"(addr), "r"(r0), "r"(r1), "r"(r2), "r"(r3), "r"((int)on) : "memory");
}
__device__ __forceinline__ float2 lds_f2(uint32_t addr) {
  float2 v; asm volatile("ld.shared.v2.f32 {%0,%1}, [%2];" : "=f"(v.x), "=f"(v.y) : "r"(addr) : "memory"); return v;
}
__device__ __forceinline__ uint4 lds128(uint32_t addr) {
  uint4 v; asm volatile("ld.shared.v4.b32 {%0,%1,%2,%3}, [%4];" : "=r"(v.x), "=r"(v.y), "=r"(v.z), "=r"(v.w) : "r"(addr) : "memory"); return v;
}
__device__ __forceinline__ void sts128(uint32_t addr, uint4 v) {
  asm volatile("st.shared.v4.b32 [%0], {%1,%2,%3,%4};" ::"r"(addr), "r"(v.x), "r"(v.y), "r"(v.z), "r"(v.w) : "memory");
}
__device__ __forceinline__ float lds_f(uint32_t addr) {
  float v; asm volatile("ld.shared.f32 %0, [%1];" : "=f"(v) : "r"(addr) : "memory"); return v;
}
__device__ __forceinline__ uint32_t lds_vol(uint32_t addr) {
  uint32_t v; asm volatile("ld.volatile.shared.u32 %0, [%1];" : "=r"(v) : "r"(addr) : "memory"); return v;
}
__device__ __forceinline__ void sts16(uint32_t addr, uint32_t v) {
  asm volatile("st.shared.u16 [%0], %1;" ::"r"(addr), "h"((unsigned short)v) : "memory");
}
__device__ __forceinline__ void nbar_dyn(int id, int n) { asm volatile("bar.sync %0, %1;" ::"r"(id), "r"(n) : "memory"); }
__device__ __forceinline__ uint64_t make_desc_ns(uint32_t addr, uint32_t lbo_bytes, uint32_t sbo_bytes) {
  return (uint64_t)((addr & 0x3FFFF) >> 4) | ((uint64_t)(lbo_bytes >> 4) << 16) | ((uint64_t)(sbo_bytes >> 4) << 32);
}
__device__ __forceinline__ void sts_f(uint32_t addr, float v) { asm volatile("st.shared.f32 [%0], %1;" ::"r"(addr), "f"(v) : "memory"); }
__device__ __forceinline__ void sts64(uint32_t addr, uint32_t a, uint32_t b) {
  asm volatile("st.shared.v2.b32 [%0], {%1,%2};" ::"r"(addr), "r"(a), "r"(b) : "memory");
}
__device__ __forceinline__ void sts_f2(uint32_t addr, float a, float b) {
  asm volatile("st.shared.v2.f32 [%0], {%1,%2};" ::"r"(addr), "f"(a), "f"(b) : "memory");
}
__device__ __forceinline__ void red_add2(float* p, float a, float b) {
  asm volatile("red.global.add.v2.f32 [%0], {%1,%2};" ::"l"(p), "f"(a), "f"(b) : "memory");
}
__device__ __forceinline__ void red_add4(float* p, float a, float b, float c, float d) {
  asm volatile("red.global.add.v4.f32 [%0], {%1,%2,%3,%4};" ::"l"(p), "f"(a), "f"(b), "f"(c), "f"(d) : "memory");
}
__device__ __forceinline__ void red_add1(float* p, float a) {
  asm volatile("red.global.add.f32 [%0], %1;" ::"l"(p), "f"(a) : "memory");
}
__device__ __forceinline__ void l2_prefetch(const void* p, uint32_t bytes) {
  asm volatile("cp.async.bulk.prefetch.L2.global [%0], %1;" ::"l"(p), "r"(bytes) : "memory");
}

__device__ __forceinline__ void wgmma_n256(float (&d)[192], uint64_t da, uint64_t db, int scale_d) {
  asm volatile("{\n.reg .pred p;\nsetp.ne.b32 p, %130, 0;\n"
    "wgmma.mma_async.sync.aligned.m64n256k16.f32.bf16.bf16 {%0, %1, %2, %3, %4, %5, %6, %7, %8, %9, %10, %11, %12, %13, %14, %15, %16, %17, %18, %19, %20, %21, %22, %23, %24, %25, %26, %27, %28, %29, %30, %31, %32, %33, %34, %35, %36, %37, %38, %39, %40, %41, %42, %43, %44, %45, %46, %47, %48, %49, %50, %51, %52, %53, %54, %55, %56, %57, %58, %59, %60, %61, %62, %63, %64, %65, %66, %67, %68, %69, %70, %71, %72, %73, %74, %75, %76, %77, %78, %79, %80, %81, %82, %83, %84, %85, %86, %87, %88, %89, %90, %91, %92, %93, %94, %95, %96, %97, %98, %99, %100, %101, %102, %103, %104, %105, %106, %107, %108, %109, %110, %111, %112, %113, %114, %115, %116, %117, %118, %119, %120, %121, %122, %123, %124, %125, %126, %127}, %128, %129, p, 1, 1, 0, 1;\n}\n"
    : "+f"(d[0]), "+f"(d[1]), "+f"(d[2]), "+f"(d[3]), "+f"(d[4]), "+f"(d[5]), "+f"(d[6]), "+f"(d[7]), "+f"(d[8]), "+f"(d[9]), "+f"(d[10]), "+f"(d[11]), "+f"(d[12]), "+f"(d[13]), "+f"(d[14]), "+f"(d[15]), "+f"(d[16]), "+f"(d[17]), "+f"(d[18]), "+f"(d[19]), "+f"(d[20]), "+f"(d[21]), "+f"(d[22]), "+f"(d[23]), "+f"(d[24]), "+f"(d[25]), "+f"(d[26]), "+f"(d[27]), "+f"(d[28]), "+f"(d[29]), "+f"(d[30]), "+f"(d[31]), "+f"(d[32]), "+f"(d[33]), "+f"(d[34]), "+f"(d[35]), "+f"(d[36]), "+f"(d[37]), "+f"(d[38]), "+f"(d[39]), "+f"(d[40]), "+f"(d[41]), "+f"(d[42]), "+f"(d[43]), "+f"(d[44]), "+f"(d[45]), "+f"(d[46]), "+f"(d[47]), "+f"(d[48]), "+f"(d[49]), "+f"(d[50]), "+f"(d[51]), "+f"(d[52]), "+f"(d[53]), "+f"(d[54]), "+f"(d[55]), "+f"(d[56]), "+f"(d[57]), "+f"(d[58]), "+f"(d[59]), "+f"(d[60]), "+f"(d[61]), "+f"(d[62]), "+f"(d[63]), "+f"(d[64]), "+f"(d[65]), "+f"(d[66]), "+f"(d[67]), "+f"(d[68]), "+f"(d[69]), "+f"(d[70]), "+f"(d[71]), "+f"(d[72]), "+f"(d[73]), "+f"(d[74]), "+f"(d[75]), "+f"(d[76]), "+f"(d[77]), "+f"(d[78]), "+f"(d[79]), "+f"(d[80]), "+f"(d[81]), "+f"(d[82]), "+f"(d[83]), "+f"(d[84]), "+f"(d[85]), "+f"(d[86]), "+f"(d[87]), "+f"(d[88]), "+f"(d[89]), "+f"(d[90]), "+f"(d[91]), "+f"(d[92]), "+f"(d[93]), "+f"(d[94]), "+f"(d[95]), "+f"(d[96]), "+f"(d[97]), "+f"(d[98]), "+f"(d[99]), "+f"(d[100]), "+f"(d[101]), "+f"(d[102]), "+f"(d[103]), "+f"(d[104]), "+f"(d[105]), "+f"(d[106]), "+f"(d[107]), "+f"(d[108]), "+f"(d[109]), "+f"(d[110]), "+f"(d[111]), "+f"(d[112]), "+f"(d[113]), "+f"(d[114]), "+f"(d[115]), "+f"(d[116]), "+f"(d[117]), "+f"(d[118]), "+f"(d[119]), "+f"(d[120]), "+f"(d[121]), "+f"(d[122]), "+f"(d[123]), "+f"(d[124]), "+f"(d[125]), "+f"(d[126]), "+f"(d[127])
    : "l"(da), "l"(db), "r"(scale_d));
}
__device__ __forceinline__ void wgmma_n128(float (&d)[192], uint64_t da, uint64_t db, int scale_d) {
  asm volatile("{\n.reg .pred p;\nsetp.ne.b32 p, %66, 0;\n"
    "wgmma.mma_async.sync.aligned.m64n128k16.f32.bf16.bf16 {%0, %1, %2, %3, %4, %5, %6, %7, %8, %9, %10, %11, %12, %13, %14, %15, %16, %17, %18, %19, %20, %21, %22, %23, %24, %25, %26, %27, %28, %29, %30, %31, %32, %33, %34, %35, %36, %37, %38, %39, %40, %41, %42, %43, %44, %45, %46, %47, %48, %49, %50, %51, %52, %53, %54, %55, %56, %57, %58, %59, %60, %61, %62, %63}, %64, %65, p, 1, 1, 0, 1;\n}\n"
    : "+f"(d[128]), "+f"(d[129]), "+f"(d[130]), "+f"(d[131]), "+f"(d[132]), "+f"(d[133]), "+f"(d[134]), "+f"(d[135]), "+f"(d[136]), "+f"(d[137]), "+f"(d[138]), "+f"(d[139]), "+f"(d[140]), "+f"(d[141]), "+f"(d[142]), "+f"(d[143]), "+f"(d[144]), "+f"(d[145]), "+f"(d[146]), "+f"(d[147]), "+f"(d[148]), "+f"(d[149]), "+f"(d[150]), "+f"(d[151]), "+f"(d[152]), "+f"(d[153]), "+f"(d[154]), "+f"(d[155]), "+f"(d[156]), "+f"(d[157]), "+f"(d[158]), "+f"(d[159]), "+f"(d[160]), "+f"(d[161]), "+f"(d[162]), "+f"(d[163]), "+f"(d[164]), "+f"(d[165]), "+f"(d[166]), "+f"(d[167]), "+f"(d[168]), "+f"(d[169]), "+f"(d[170]), "+f"(d[171]), "+f"(d[172]), "+f"(d[173]), "+f"(d[174]), "+f"(d[175]), "+f"(d[176]), "+f"(d[177]), "+f"(d[178]), "+f"(d[179]), "+f"(d[180]), "+f"(d[181]), "+f"(d[182]), "+f"(d[183]), "+f"(d[184]), "+f"(d[185]), "+f"(d[186]), "+f"(d[187]), "+f"(d[188]), "+f"(d[189]), "+f"(d[190]), "+f"(d[191])
    : "l"(da), "l"(db), "r"(scale_d));
}
__device__ __forceinline__ void wgmma_n256_k(float (&d)[192], uint64_t da, uint64_t db, int scale_d) {
  asm volatile("{\n.reg .pred p;\nsetp.ne.b32 p, %130, 0;\n"
    "wgmma.mma_async.sync.aligned.m64n256k16.f32.bf16.bf16 {%0, %1, %2, %3, %4, %5, %6, %7, %8, %9, %10, %11, %12, %13, %14, %15, %16, %17, %18, %19, %20, %21, %22, %23, %24, %25, %26, %27, %28, %29, %30, %31, %32, %33, %34, %35, %36, %37, %38, %39, %40, %41, %42, %43, %44, %45, %46, %47, %48, %49, %50, %51, %52, %53, %54, %55, %56, %57, %58, %59, %60, %61, %62, %63, %64, %65, %66, %67, %68, %69, %70, %71, %72, %73, %74, %75, %76, %77, %78, %79, %80, %81, %82, %83, %84, %85, %86, %87, %88, %89, %90, %91, %92, %93, %94, %95, %96, %97, %98, %99, %100, %101, %102, %103, %104, %105, %106, %107, %108, %109, %110, %111, %112, %113, %114, %115, %116, %117, %118, %119, %120, %121, %122, %123, %124, %125, %126, %127}, %128, %129, p, 1, 1, 0, 0;\n}\n"
    : "+f"(d[0]), "+f"(d[1]), "+f"(d[2]), "+f"(d[3]), "+f"(d[4]), "+f"(d[5]), "+f"(d[6]), "+f"(d[7]), "+f"(d[8]), "+f"(d[9]), "+f"(d[10]), "+f"(d[11]), "+f"(d[12]), "+f"(d[13]), "+f"(d[14]), "+f"(d[15]), "+f"(d[16]), "+f"(d[17]), "+f"(d[18]), "+f"(d[19]), "+f"(d[20]), "+f"(d[21]), "+f"(d[22]), "+f"(d[23]), "+f"(d[24]), "+f"(d[25]), "+f"(d[26]), "+f"(d[27]), "+f"(d[28]), "+f"(d[29]), "+f"(d[30]), "+f"(d[31]), "+f"(d[32]), "+f"(d[33]), "+f"(d[34]), "+f"(d[35]), "+f"(d[36]), "+f"(d[37]), "+f"(d[38]), "+f"(d[39]), "+f"(d[40]), "+f"(d[41]), "+f"(d[42]), "+f"(d[43]), "+f"(d[44]), "+f"(d[45]), "+f"(d[46]), "+f"(d[47]), "+f"(d[48]), "+f"(d[49]), "+f"(d[50]), "+f"(d[51]), "+f"(d[52]), "+f"(d[53]), "+f"(d[54]), "+f"(d[55]), "+f"(d[56]), "+f"(d[57]), "+f"(d[58]), "+f"(d[59]), "+f"(d[60]), "+f"(d[61]), "+f"(d[62]), "+f"(d[63]), "+f"(d[64]), "+f"(d[65]), "+f"(d[66]), "+f"(d[67]), "+f"(d[68]), "+f"(d[69]), "+f"(d[70]), "+f"(d[71]), "+f"(d[72]), "+f"(d[73]), "+f"(d[74]), "+f"(d[75]), "+f"(d[76]), "+f"(d[77]), "+f"(d[78]), "+f"(d[79]), "+f"(d[80]), "+f"(d[81]), "+f"(d[82]), "+f"(d[83]), "+f"(d[84]), "+f"(d[85]), "+f"(d[86]), "+f"(d[87]), "+f"(d[88]), "+f"(d[89]), "+f"(d[90]), "+f"(d[91]), "+f"(d[92]), "+f"(d[93]), "+f"(d[94]), "+f"(d[95]), "+f"(d[96]), "+f"(d[97]), "+f"(d[98]), "+f"(d[99]), "+f"(d[100]), "+f"(d[101]), "+f"(d[102]), "+f"(d[103]), "+f"(d[104]), "+f"(d[105]), "+f"(d[106]), "+f"(d[107]), "+f"(d[108]), "+f"(d[109]), "+f"(d[110]), "+f"(d[111]), "+f"(d[112]), "+f"(d[113]), "+f"(d[114]), "+f"(d[115]), "+f"(d[116]), "+f"(d[117]), "+f"(d[118]), "+f"(d[119]), "+f"(d[120]), "+f"(d[121]), "+f"(d[122]), "+f"(d[123]), "+f"(d[124]), "+f"(d[125]), "+f"(d[126]), "+f"(d[127])
    : "l"(da), "l"(db), "r"(scale_d));
}
__device__ __forceinline__ void wgmma_n128_k(float (&d)[192], uint64_t da, uint64_t db, int scale_d) {
  asm volatile("{\n.reg .pred p;\nsetp.ne.b32 p, %66, 0;\n"
    "wgmma.mma_async.sync.aligned.m64n128k16.f32.bf16.bf16 {%0, %1, %2, %3, %4, %5, %6, %7, %8, %9, %10, %11, %12, %13, %14, %15, %16, %17, %18, %19, %20, %21, %22, %23, %24, %25, %26, %27, %28, %29, %30, %31, %32, %33, %34, %35, %36, %37, %38, %39, %40, %41, %42, %43, %44, %45, %46, %47, %48, %49, %50, %51, %52, %53, %54, %55, %56, %57, %58, %59, %60, %61, %62, %63}, %64, %65, p, 1, 1, 0, 0;\n}\n"
    : "+f"(d[128]), "+f"(d[129]), "+f"(d[130]), "+f"(d[131]), "+f"(d[132]), "+f"(d[133]), "+f"(d[134]), "+f"(d[135]), "+f"(d[136]), "+f"(d[137]), "+f"(d[138]), "+f"(d[139]), "+f"(d[140]), "+f"(d[141]), "+f"(d[142]), "+f"(d[143]), "+f"(d[144]), "+f"(d[145]), "+f"(d[146]), "+f"(d[147]), "+f"(d[148]), "+f"(d[149]), "+f"(d[150]), "+f"(d[151]), "+f"(d[152]), "+f"(d[153]), "+f"(d[154]), "+f"(d[155]), "+f"(d[156]), "+f"(d[157]), "+f"(d[158]), "+f"(d[159]), "+f"(d[160]), "+f"(d[161]), "+f"(d[162]), "+f"(d[163]), "+f"(d[164]), "+f"(d[165]), "+f"(d[166]), "+f"(d[167]), "+f"(d[168]), "+f"(d[169]), "+f"(d[170]), "+f"(d[171]), "+f"(d[172]), "+f"(d[173]), "+f"(d[174]), "+f"(d[175]), "+f"(d[176]), "+f"(d[177]), "+f"(d[178]), "+f"(d[179]), "+f"(d[180]), "+f"(d[181]), "+f"(d[182]), "+f"(d[183]), "+f"(d[184]), "+f"(d[185]), "+f"(d[186]), "+f"(d[187]), "+f"(d[188]), "+f"(d[189]), "+f"(d[190]), "+f"(d[191])
    : "l"(da), "l"(db), "r"(scale_d));
}
__device__ __forceinline__ void wgmma_n40_tt(float (&d)[20], uint64_t da, uint64_t db, int scale_d) {
  asm volatile("{\n.reg .pred p;\nsetp.ne.b32 p, %22, 0;\n"
    "wgmma.mma_async.sync.aligned.m64n40k16.f32.bf16.bf16 {%0, %1, %2, %3, %4, %5, %6, %7, %8, %9, %10, %11, %12, %13, %14, %15, %16, %17, %18, %19}, %20, %21, p, 1, 1, 1, 1;\n}\n"
    : "+f"(d[0]), "+f"(d[1]), "+f"(d[2]), "+f"(d[3]), "+f"(d[4]), "+f"(d[5]), "+f"(d[6]), "+f"(d[7]), "+f"(d[8]), "+f"(d[9]), "+f"(d[10]), "+f"(d[11]), "+f"(d[12]), "+f"(d[13]), "+f"(d[14]), "+f"(d[15]), "+f"(d[16]), "+f"(d[17]), "+f"(d[18]), "+f"(d[19])
    : "l"(da), "l"(db), "r"(scale_d));
}
__device__ __forceinline__ void wgmma_n40_rs(float (&d)[20], const uint32_t (&a)[4], uint64_t db, int scale_d) {
  asm volatile("{\n.reg .pred p;\nsetp.ne.b32 p, %25, 0;\n"
    "wgmma.mma_async.sync.aligned.m64n40k16.f32.bf16.bf16 {%0, %1, %2, %3, %4, %5, %6, %7, %8, %9, %10, %11, %12, %13, %14, %15, %16, %17, %18, %19}, {%20, %21, %22, %23}, %24, p, 1, 1, 1;\n}\n"
    : "+f"(d[0]), "+f"(d[1]), "+f"(d[2]), "+f"(d[3]), "+f"(d[4]), "+f"(d[5]), "+f"(d[6]), "+f"(d[7]), "+f"(d[8]), "+f"(d[9]), "+f"(d[10]), "+f"(d[11]), "+f"(d[12]), "+f"(d[13]), "+f"(d[14]), "+f"(d[15]), "+f"(d[16]), "+f"(d[17]), "+f"(d[18]), "+f"(d[19])
    : "r"(a[0]), "r"(a[1]), "r"(a[2]), "r"(a[3]), "l"(db), "r"(scale_d));
}
__device__ __forceinline__ void wgmma_n256_0(float (&d)[192], uint64_t da, uint64_t db) {
  asm volatile("{\n.reg .pred p;\nsetp.ne.b32 p, 0, 0;\n"
    "wgmma.mma_async.sync.aligned.m64n256k16.f32.bf16.bf16 {%0, %1, %2, %3, %4, %5, %6, %7, %8, %9, %10, %11, %12, %13, %14, %15, %16, %17, %18, %19, %20, %21, %22, %23, %24, %25, %26, %27, %28, %29, %30, %31, %32, %33, %34, %35, %36, %37, %38, %39, %40, %41, %42, %43, %44, %45, %46, %47, %48, %49, %50, %51, %52, %53, %54, %55, %56, %57, %58, %59, %60, %61, %62, %63, %64, %65, %66, %67, %68, %69, %70, %71, %72, %73, %74, %75, %76, %77, %78, %79, %80, %81, %82, %83, %84, %85, %86, %87, %88, %89, %90, %91, %92, %93, %94, %95, %96, %97, %98, %99, %100, %101, %102, %103, %104, %105, %106, %107, %108, %109, %110, %111, %112, %113, %114, %115, %116, %117, %118, %119, %120, %121, %122, %123, %124, %125, %126, %127}, %128, %129, p, 1, 1, 0, 1;\n}\n"
    : "=f"(d[0]), "=f"(d[1]), "=f"(d[2]), "=f"(d[3]), "=f"(d[4]), "=f"(d[5]), "=f"(d[6]), "=f"(d[7]), "=f"(d[8]), "=f"(d[9]), "=f"(d[10]), "=f"(d[11]), "=f"(d[12]), "=f"(d[13]), "=f"(d[14]), "=f"(d[15]), "=f"(d[16]), "=f"(d[17]), "=f"(d[18]), "=f"(d[19]), "=f"(d[20]), "=f"(d[21]), "=f"(d[22]), "=f"(d[23]), "=f"(d[24]), "=f"(d[25]), "=f"(d[26]), "=f"(d[27]), "=f"(d[28]), "=f"(d[29]), "=f"(d[30]), "=f"(d[31]), "=f"(d[32]), "=f"(d[33]), "=f"(d[34]), "=f"(d[35]), "=f"(d[36]), "=f"(d[37]), "=f"(d[38]), "=f"(d[39]), "=f"(d[40]), "=f"(d[41]), "=f"(d[42]), "=f"(d[43]), "=f"(d[44]), "=f"(d[45]), "=f"(d[46]), "=f"(d[47]), "=f"(d[48]), "=f"(d[49]), "=f"(d[50]), "=f"(d[51]), "=f"(d[52]), "=f"(d[53]), "=f"(d[54]), "=f"(d[55]), "=f"(d[56]), "=f"(d[57]), "=f"(d[58]), "=f"(d[59]), "=f"(d[60]), "=f"(d[61]), "=f"(d[62]), "=f"(d[63]), "=f"(d[64]), "=f"(d[65]), "=f"(d[66]), "=f"(d[67]), "=f"(d[68]), "=f"(d[69]), "=f"(d[70]), "=f"(d[71]), "=f"(d[72]), "=f"(d[73]), "=f"(d[74]), "=f"(d[75]), "=f"(d[76]), "=f"(d[77]), "=f"(d[78]), "=f"(d[79]), "=f"(d[80]), "=f"(d[81]), "=f"(d[82]), "=f"(d[83]), "=f"(d[84]), "=f"(d[85]), "=f"(d[86]), "=f"(d[87]), "=f"(d[88]), "=f"(d[89]), "=f"(d[90]), "=f"(d[91]), "=f"(d[92]), "=f"(d[93]), "=f"(d[94]), "=f"(d[95]), "=f"(d[96]), "=f"(d[97]), "=f"(d[98]), "=f"(d[99]), "=f"(d[100]), "=f"(d[101]), "=f"(d[102]), "=f"(d[103]), "=f"(d[104]), "=f"(d[105]), "=f"(d[106]), "=f"(d[107]), "=f"(d[108]), "=f"(d[109]), "=f"(d[110]), "=f"(d[111]), "=f"(d[112]), "=f"(d[113]), "=f"(d[114]), "=f"(d[115]), "=f"(d[116]), "=f"(d[117]), "=f"(d[118]), "=f"(d[119]), "=f"(d[120]), "=f"(d[121]), "=f"(d[122]), "=f"(d[123]), "=f"(d[124]), "=f"(d[125]), "=f"(d[126]), "=f"(d[127])
    : "l"(da), "l"(db));
}
__device__ __forceinline__ void wgmma_n128_0(float (&d)[192], uint64_t da, uint64_t db) {
  asm volatile("{\n.reg .pred p;\nsetp.ne.b32 p, 0, 0;\n"
    "wgmma.mma_async.sync.aligned.m64n128k16.f32.bf16.bf16 {%0, %1, %2, %3, %4, %5, %6, %7, %8, %9, %10, %11, %12, %13, %14, %15, %16, %17, %18, %19, %20, %21, %22, %23, %24, %25, %26, %27, %28, %29, %30, %31, %32, %33, %34, %35, %36, %37, %38, %39, %40, %41, %42, %43, %44, %45, %46, %47, %48, %49, %50, %51, %52, %53, %54, %55, %56, %57, %58, %59, %60, %61, %62, %63}, %64, %65, p, 1, 1, 0, 1;\n}\n"
    : "=f"(d[128]), "=f"(d[129]), "=f"(d[130]), "=f"(d[131]), "=f"(d[132]), "=f"(d[133]), "=f"(d[134]), "=f"(d[135]), "=f"(d[136]), "=f"(d[137]), "=f"(d[138]), "=f"(d[139]), "=f"(d[140]), "=f"(d[141]), "=f"(d[142]), "=f"(d[143]), "=f"(d[144]), "=f"(d[145]), "=f"(d[146]), "=f"(d[147]), "=f"(d[148]), "=f"(d[149]), "=f"(d[150]), "=f"(d[151]), "=f"(d[152]), "=f"(d[153]), "=f"(d[154]), "=f"(d[155]), "=f"(d[156]), "=f"(d[157]), "=f"(d[158]), "=f"(d[159]), "=f"(d[160]), "=f"(d[161]), "=f"(d[162]), "=f"(d[163]), "=f"(d[164]), "=f"(d[165]), "=f"(d[166]), "=f"(d[167]), "=f"(d[168]), "=f"(d[169]), "=f"(d[170]), "=f"(d[171]), "=f"(d[172]), "=f"(d[173]), "=f"(d[174]), "=f"(d[175]), "=f"(d[176]), "=f"(d[177]), "=f"(d[178]), "=f"(d[179]), "=f"(d[180]), "=f"(d[181]), "=f"(d[182]), "=f"(d[183]), "=f"(d[184]), "=f"(d[185]), "=f"(d[186]), "=f"(d[187]), "=f"(d[188]), "=f"(d[189]), "=f"(d[190]), "=f"(d[191])
    : "l"(da), "l"(db));
}
__device__ __forceinline__ void wgmma_n128_rs(float (&d)[192], const uint32_t (&a)[4], uint64_t db, int scale_d) {
  asm volatile("{\n.reg .pred p;\nsetp.ne.b32 p, %69, 0;\n"
    "wgmma.mma_async.sync.aligned.m64n128k16.f32.bf16.bf16 {%0, %1, %2, %3, %4, %5, %6, %7, %8, %9, %10, %11, %12, %13, %14, %15, %16, %17, %18, %19, %20, %21, %22, %23, %24, %25, %26, %27, %28, %29, %30, %31, %32, %33, %34, %35, %36, %37, %38, %39, %40, %41, %42, %43, %44, %45, %46, %47, %48, %49, %50, %51, %52, %53, %54, %55, %56, %57, %58, %59, %60, %61, %62, %63}, {%64, %65, %66, %67}, %68, p, 1, 1, 1;\n}\n"
    : "+f"(d[128]), "+f"(d[129]), "+f"(d[130]), "+f"(d[131]), "+f"(d[132]), "+f"(d[133]), "+f"(d[134]), "+f"(d[135]), "+f"(d[136]), "+f"(d[137]), "+f"(d[138]), "+f"(d[139]), "+f"(d[140]), "+f"(d[141]), "+f"(d[142]), "+f"(d[143]), "+f"(d[144]), "+f"(d[145]), "+f"(d[146]), "+f"(d[147]), "+f"(d[148]), "+f"(d[149]), "+f"(d[150]), "+f"(d[151]), "+f"(d[152]), "+f"(d[153]), "+f"(d[154]), "+f"(d[155]), "+f"(d[156]), "+f"(d[157]), "+f"(d[158]), "+f"(d[159]), "+f"(d[160]), "+f"(d[161]), "+f"(d[162]), "+f"(d[163]), "+f"(d[164]), "+f"(d[165]), "+f"(d[166]), "+f"(d[167]), "+f"(d[168]), "+f"(d[169]), "+f"(d[170]), "+f"(d[171]), "+f"(d[172]), "+f"(d[173]), "+f"(d[174]), "+f"(d[175]), "+f"(d[176]), "+f"(d[177]), "+f"(d[178]), "+f"(d[179]), "+f"(d[180]), "+f"(d[181]), "+f"(d[182]), "+f"(d[183]), "+f"(d[184]), "+f"(d[185]), "+f"(d[186]), "+f"(d[187]), "+f"(d[188]), "+f"(d[189]), "+f"(d[190]), "+f"(d[191])
    : "r"(a[0]), "r"(a[1]), "r"(a[2]), "r"(a[3]), "l"(db), "r"(scale_d));
}

constexpr int SLOT = 16384;
constexpr int KVT = 10240;
constexpr uint32_t QA = 0x0BAu, QK = 0x462u, QQ = 0x981u;
constexpr int SM_SD = 12 * SLOT;
constexpr int SM_BAR = SM_SD + 8192;
constexpr int SM_RS = SM_BAR + 512;
constexpr int SM_AP = SM_RS + 768;
constexpr int SM_BP = SM_AP + 2048;
constexpr int SM_WPHI = SM_BP + 12288;
constexpr int SM_EPOCH = SM_WPHI + 10240;
constexpr int SM_TOTAL = SM_EPOCH + 16 + 1024;
constexpr int B_FULLS = 0, B_XOLD = 24, B_STAT = 32, B_EMPTYS = 40, B_FULLT = 256  , B_CONS = 384  , B_E3 = 472, B_E0 = 480, B_E1 = 488, B_E2 = 496, B_EPI = 504, B_CS = 160,
              B_KVDONE = 168  , B_ODONE = 176, B_XDONE = 184, B_OH1 = B_CONS, B_CS2 = 208, B_XH0 = 232, B_R0 = 240, B_CB = 144  , B_XOLD2 = 216;
constexpr uint64_t BAR_CNT = 0x1c07fc0eac00a800ull;
constexpr uint64_t WO_A0 = 0xa461b57648357643ull, WO_B0 = 0x59083a9021ba9021ull, WO_A1 = 0xa0b76901276a5babull, WO_B1 = 0x95428a5b34890132ull;
constexpr uint64_t WO_DA0 = 0xa9865432ff00dd00ull, WO_DB0 = 0xa986543211bbccccull, WO_DA1 = 0xa98654321ffff000ull, WO_DB1 = 0xa98754321bbcccddull;
#define WOORD 0xFDB9753ECA864210ull
constexpr int NX = 4;
constexpr int XS = 10;

#define PL 2
#define PROFX(i) PROFT(tid_ == 128 && layer == PL, 200 + (i))
#define NCOM 3
#define PFS 8
#define KVTH 0x41700000u
#define XPF 3
#define XPM 2
#define TLINE 1
#define MAP 3
#define RT2 0
#define WSK 1
#define H1L 0
#define EI 13
#define K0V 0
#define ORD 5
#define RL 2
#define OV 0
#define NLAYERS 4
constexpr float L2E = 1.4426950408889634f;
#define PHI_MAX 2147483648.f

#define D128(lo) desc64(lo, 0x40000040u)
struct Ctx { uint32_t sb; int g, rb, cu; bf16* out; };

__device__ __forceinline__ void colsum(const CUtensorMap* tm, float* cs, int rb, int g, int w0, int dw, int lane, uint32_t stg, uint32_t cb, uint32_t par) {
  const uint32_t src = stg + (lane >> 3) * 2048;
#pragma unroll 1
  for (int wi = w0 - dw; wi < 6; wi += dw) {
    float s[8] = {0.f, 0.f, 0.f, 0.f, 0.f, 0.f, 0.f, 0.f};
    if (wi >= 0) {
      mbar_wait_u(cb, par);
      par ^= 1;
#pragma unroll 4
      for (int r = 0; r < 16; ++r) {
        const uint4 v = lds128(src + r * 128 + (((lane ^ r) & 7) << 4));
        s[0] += bf_lo(v.x); s[1] += bf_hi(v.x); s[2] += bf_lo(v.y); s[3] += bf_hi(v.y);
        s[4] += bf_lo(v.z); s[5] += bf_hi(v.z); s[6] += bf_lo(v.w); s[7] += bf_hi(v.w);
      }
#pragma unroll
      for (int i = 0; i < 8; ++i) s[i] += __shfl_xor_sync(0xffffffffu, s[i], 8);
    }
    const int wn = wi + dw;
    if (wn < 6) {
      expect_tx_e(cb, 8192);
      tma_2d_e(stg, tm, (wn >= 4 ? 0 : 1024 + (wn >> 1) * 1024) + g * 128 + (wn & 1) * 64, rb * 64, cb);
    }
    if (wi >= 0) {
#pragma unroll
      for (int i = 0; i < 8; ++i) s[i] += __shfl_xor_sync(0xffffffffu, s[i], 16);
      if (lane < 8) {
        red_add4(cs + g * 384 + (wi * 8 + lane) * 8, s[0], s[1], s[2], s[3]);
        red_add4(cs + g * 384 + (wi * 8 + lane) * 8 + 4, s[4], s[5], s[6], s[7]);
      }
      __syncwarp();
    }
  }
}
#define PHASE_CTX() \
  uint32_t sb = c.sb; asm volatile("" : "+r"(sb)); \
  int tid_ = threadIdx.x; asm volatile("" : "+r"(tid_)); \
  const uint32_t bar = sb + SM_BAR; \
  const int lane = tid_ & 31, cw = (tid_ >> 5) - 4, wg = cw >> 2, wq = cw & 3, gq = lane >> 2, t = lane & 3, wrow0 = cw * 16; \
  const int lrow = (lane & 7) + ((lane >> 3) & 1) * 8, lchk = lane >> 4; \
  const bool elected = (tid_ & 127) == 0; \
  const uint32_t rowo = (wrow0 + lrow) * 128, X = (lchk ^ (lane & 7)) << 4; \
  (void)bar; (void)wq; (void)gq; (void)lrow; (void)lchk; (void)elected; (void)wrow0; (void)wg; (void)rowo; (void)X; (void)t;

__device__ __forceinline__ void slab_out_half(uint32_t slot, bf16* dst, int wrow0, int lane, bool FENCE = false) {
  const int r0 = lane >> 3, ch = lane & 7;
  const uint32_t src = slot + (wrow0 + r0) * 128;
  uint4 v[4];
#pragma unroll
  for (int i = 0; i < 4; ++i) v[i] = lds128(src + i * 512 + (((ch ^ (4 * i + r0)) & 7) << 4));
  if (FENCE) fence_async_smem();
  dst += (size_t)(wrow0 + r0) * D_ + ch * 8;
#pragma unroll
  for (int i = 0; i < 4; ++i)
    asm volatile("st.global.v4.u32 [%0], {%1,%2,%3,%4};" ::"l"(dst + (size_t)i * 4 * D_), "r"(v[i].x), "r"(v[i].y), "r"(v[i].z), "r"(v[i].w) : "memory");
}

struct Tag { uint32_t me, mo, tg; };
__device__ __forceinline__ Tag make_tag(int gq, int t, uint32_t tg) { return Tag{t == 0, t == 1, tg}; }
__device__ __forceinline__ void stsm_tag(uint32_t addr, uint32_t r0, uint32_t r1, uint32_t r2, uint32_t r3, const Tag& k, int jp) {
  if (jp == 0) stsm_x4(addr, (r0 & ~k.me) | (k.tg & k.me), (r1 & ~k.mo) | (k.tg & k.mo), r2, r3);
  else stsm_x4(addr, r0, r1, r2, r3);
}
#define TILE_BAD() ((lds_vol(va) ^ tg) & 1)
#define TILE_VA() (slot + (wrow0 + (lane & 15)) * 128 + (lane & 7) * 16 + ((lane >> 3) & 1) * 4)
__device__ __forceinline__ void tile_check(uint32_t slot, const bf16* src, int wrow0, int lane, uint32_t tg) {
  const uint32_t va = TILE_VA();
  if (__builtin_expect(__any_sync(0xffffffffu, TILE_BAD()), 0)) {
    const int r0 = lane >> 3, ch = lane & 7;
    uint32_t n = 0;
#pragma unroll 1
    do {
      uint4 v[4];
#pragma unroll
      for (int i = 0; i < 4; ++i) v[i] = ld_relaxed4(reinterpret_cast<const uint4*>(src + (size_t)(wrow0 + r0 + 4 * i) * D_ + ch * 8));
#pragma unroll
      for (int i = 0; i < 4; ++i) sts128(slot + (wrow0 + r0 + 4 * i) * 128 + (((ch ^ (4 * i + r0)) & 7) << 4), v[i]);
      __syncwarp();
      if (++n > (1u << 16)) { g_err = 8u; break; }
    } while (__any_sync(0xffffffffu, TILE_BAD()));
    fence_async_smem();
    __syncwarp();
  }
}

template <int O>
__device__ __forceinline__ void phi_proj(float (&p)[2][4][4], const uint32_t (&kq)[64], uint32_t wa) {
#pragma unroll
  for (int h = 0; h < 2; ++h)
#pragma unroll
    for (int i = 0; i < 4; ++i) { p[h][i][0] = p[h][i][1] = p[h][i][2] = p[h][i][3] = 0.f; }
#pragma unroll
  for (int ks = 0; ks < 2; ++ks)
#pragma unroll
    for (int np = 0; np < 2; ++np)
#pragma unroll
      for (int h = 0; h < 2; ++h) {
        uint32_t b0, b1, b2, b3;
        ldsm_x4_t(b0, b1, b2, b3, wa + h * 2560 + ks * 1280 + np * 32);
        mma_bf16(p[h][2 * np], kq[O + 8 * h + 4 * ks], kq[O + 8 * h + 4 * ks + 1], kq[O + 8 * h + 4 * ks + 2], kq[O + 8 * h + 4 * ks + 3], b0, b1);
        mma_bf16(p[h][2 * np + 1], kq[O + 8 * h + 4 * ks], kq[O + 8 * h + 4 * ks + 1], kq[O + 8 * h + 4 * ks + 2], kq[O + 8 * h + 4 * ks + 3], b2, b3);
      }
}
__device__ __forceinline__ void phi_exp(uint32_t (&raw)[4][4], const float (&p)[4][4], float sc0, float sc1) {
#pragma unroll
  for (int i = 0; i < 4; ++i) {
    const float e0 = ex2(p[i][0] * sc0), e1 = ex2(p[i][1] * sc0), e2 = ex2(p[i][2] * sc1), e3 = ex2(p[i][3] * sc1);
    const float m0 = e0 * e1, m1 = e2 * e3, rr = rcp(m0 * m1), r0 = rr * m1, r1 = rr * m0;
    raw[i >> 1][(i & 1) * 2] = pack_bf16(e0, e1);
    raw[i >> 1][(i & 1) * 2 + 1] = pack_bf16(e2, e3);
    raw[2 + (i >> 1)][(i & 1) * 2] = pack_bf16(e1 * r0, e0 * r0);
    raw[2 + (i >> 1)][(i & 1) * 2 + 1] = pack_bf16(e3 * r1, e2 * r1);
  }
}
template <int O>
__device__ __forceinline__ void phi_norm(uint32_t (&ph)[2][4][4], const uint32_t (&raw)[2][4][4], const uint32_t (&kq)[64], uint32_t wa,
                                         float sc0, float sc1, float mul0, float mul1) {
  bool bad = false;
#pragma unroll
  for (int h = 0; h < 2; ++h)
#pragma unroll
    for (int sg = 0; sg < 2; ++sg) {
      float ss[4] = {0.f, 0.f, 0.f, 0.f};
#pragma unroll
      for (int ks = 0; ks < 2; ++ks)
        mma_bf16(ss, raw[h][2 * sg + ks][0], raw[h][2 * sg + ks][1], raw[h][2 * sg + ks][2], raw[h][2 * sg + ks][3], 0x3F803F80u, 0x3F803F80u);
      bad = bad || !(ss[0] < PHI_MAX) || !(ss[2] < PHI_MAX);
      const uint32_t iv = pack_bf16(rcp(ss[0]) * mul0, rcp(ss[2]) * mul1);
#pragma unroll
      for (int ks = 0; ks < 2; ++ks)
#pragma unroll
        for (int j = 0; j < 4; ++j) ph[h][2 * sg + ks][j] = mul_bf16x2(raw[h][2 * sg + ks][j], iv, j & 1);
    }
  if (__builtin_expect(__any_sync(0xffffffffu, bad), 0)) {
#pragma unroll 1
    for (int it = 0; it < 4; ++it) {
      float q[4][4];
#pragma unroll
      for (int i = 0; i < 4; ++i) { q[i][0] = q[i][1] = q[i][2] = q[i][3] = 0.f; }
#pragma unroll
      for (int ks = 0; ks < 2; ++ks) {
        uint32_t a[4];
#pragma unroll
        for (int j = 0; j < 4; ++j) a[j] = (it & 2) ? kq[O + 8 + 4 * ks + j] : kq[O + 4 * ks + j];
#pragma unroll
        for (int np = 0; np < 2; ++np) {
          uint32_t b0, b1, b2, b3;
          ldsm_x4_t(b0, b1, b2, b3, wa + (it >> 1) * 2560 + ks * 1280 + np * 32);
          mma_bf16(q[2 * np], a[0], a[1], a[2], a[3], b0, b1);
          mma_bf16(q[2 * np + 1], a[0], a[1], a[2], a[3], b2, b3);
        }
      }
      float iv[2];
#pragma unroll
      for (int r = 0; r < 2; ++r) {
        const float sc = (it & 1) ? -(r ? sc1 : sc0) : (r ? sc1 : sc0);
        float mx = -INFINITY, sm = 0.f;
#pragma unroll
        for (int i = 0; i < 8; ++i) { float& v = q[i >> 1][2 * r + (i & 1)]; v *= sc; mx = fmaxf(mx, v); }
        mx = fmaxf(mx, __shfl_xor_sync(0xffffffffu, mx, 1));
        mx = fmaxf(mx, __shfl_xor_sync(0xffffffffu, mx, 2));
#pragma unroll
        for (int i = 0; i < 8; ++i) { float& v = q[i >> 1][2 * r + (i & 1)]; v = ex2(v - mx); sm += v; }
        sm += __shfl_xor_sync(0xffffffffu, sm, 1);
        sm += __shfl_xor_sync(0xffffffffu, sm, 2);
        iv[r] = rcp(sm) * (r ? mul1 : mul0);
      }
#pragma unroll
      for (int i = 0; i < 24; ++i) ph[i >> 4][(i >> 2) & 3][i & 3] = ph[(i + 8) >> 4][((i + 8) >> 2) & 3][i & 3];
#pragma unroll
      for (int i = 0; i < 4; ++i) {
        ph[1][2 + (i >> 1)][(i & 1) * 2] = pack_bf16(q[i][0] * iv[0], q[i][1] * iv[0]);
        ph[1][2 + (i >> 1)][(i & 1) * 2 + 1] = pack_bf16(q[i][2] * iv[1], q[i][3] * iv[1]);
      }
    }
  }
}

__device__ __forceinline__ void stats_out(float s0, float s1, float q0, float q1, float2* dst, int t) {
  const bool od = t & 1;
  float sa = od ? s1 : s0, qa = od ? q1 : q0;
  sa += __shfl_xor_sync(0xffffffffu, od ? s0 : s1, 1);
  qa += __shfl_xor_sync(0xffffffffu, od ? q0 : q1, 1);
  sa += __shfl_xor_sync(0xffffffffu, sa, 2);
  qa += __shfl_xor_sync(0xffffffffu, qa, 2);
  if (t < 2) red_add2(&dst[t * 8].x, sa, qa);
}

__device__ __forceinline__ void consumer(const Ctx& c) {
  const int g = c.g, m0 = c.rb * 128;
  float acc[192];
#define X_HALF(hf, TG) \
      _Pragma("unroll") for (int jp = 4 * (hf); jp < 4 * (hf) + 4; ++jp) \
        stsm_tag(sb + (XS + (hf)) * SLOT + rowo + (X ^ ((jp & 3) << 5)), \
                 pack_bf16(acc[128 + 8 * jp], acc[129 + 8 * jp]), pack_bf16(acc[130 + 8 * jp], acc[131 + 8 * jp]), \
                 pack_bf16(acc[132 + 8 * jp], acc[133 + 8 * jp]), pack_bf16(acc[134 + 8 * jp], acc[135 + 8 * jp]), TG, jp & 3);
#pragma unroll
  for (int i = 128; i < 192; ++i) acc[i] = 0.f;
#pragma unroll 1
  for (int layer = 0;; ++layer) {
    {
      PHASE_CTX();
      const uint32_t wu = c.cu >> 2;
      const uint32_t dA0 = (((sb + wu * 8192) & 0x3FFFF) >> 4) | (1u << 16), dB0 = ((sb & 0x3FFFF) >> 4) | (512u << 16);
      {
        PROFX(0);
        if (!RT2 || !layer) mbar_wait(bar + B_FULLS, 0);
        PROFX(1);
        wgmma_fence();
        wgmma_n256_0(acc, D128(dA0 + XS * 1024), D128(dB0 + 2048));
#pragma unroll
        for (int k = 1; k < 4; ++k) wgmma_n256(acc, D128(dA0 + XS * 1024 + k * 2), D128(dB0 + 2048 + k * 128), 1);
        wgmma_commit();
        wgmma_wait<1>();
        float s0 = 0.f, s1 = 0.f, q0 = 0.f, q1 = 0.f;
        if (layer) {
          X_HALF(1, (Tag{0u, 0u, 0u}));
#pragma unroll
          for (int i = 128; i < 192; i += 4) {
            s0 += acc[i] + acc[i + 1]; s1 += acc[i + 2] + acc[i + 3];
            q0 = fmaf(acc[i], acc[i], fmaf(acc[i + 1], acc[i + 1], q0)); q1 = fmaf(acc[i + 2], acc[i + 2], fmaf(acc[i + 3], acc[i + 3], q1));
          }
        }
        asm volatile("" : "+f"(s0), "+f"(s1), "+f"(q0), "+f"(q1) :: "memory");
        wgmma_fence();
        wgmma_n128_0(acc, D128(dA0 + XS * 1024), D128(dB0 + 1024));
#pragma unroll
        for (int k = 1; k < 4; ++k) wgmma_n128(acc, D128(dA0 + XS * 1024 + k * 2), D128(dB0 + 1024 + k * 128), 1);
        wgmma_commit();
        if (layer) {
          PHASE_CTX();
          fence_async_smem();
          nbar_dyn(3 + wu, 128);
          stats_out(s0, s1, q0, q1, g_stats + layer * S_ + m0 + wrow0 + gq, t);
          PROFT(tid_ == 128, layer * 16 + 8);
        }
      }
      uint32_t s = 1, u = 0, sp = 0;
      const int ix = layer ? 99 : 2 * (K0V ? NCOM : min(g, NCOM)) + 1;
#pragma unroll 1
      for (int i = 1; i < 14; ++i) {
        mbar_wait(bar + B_FULLS + s * 8, (u + (s ? layer : 0)) & 1);
        if (layer && (unsigned)(i - 2) < 7u) {
          PHASE_CTX();
          tile_check(sb + ((QA >> (4 * s)) & 15) * SLOT, g_x + (size_t)m0 * D_ + ((2 * g + 2 * i - 2) & 15) * 64, wrow0, lane, lds_vol(sb + SM_EPOCH) + layer);
        }
        const uint32_t da = dA0 + ((QA >> (4 * s)) & 15) * 1024, dk = dB0 + ((QK >> (4 * s)) & 15) * 1024,
                       dq = dB0 + ((QQ >> (4 * s)) & 15) * 1024;
        wgmma_fence();
#pragma unroll
        for (int k = 0; k < 4; ++k) {
          wgmma_n256(acc, D128(da + k * 2), D128(dk + k * 128), 1);
          wgmma_n128(acc, D128(da + k * 2), D128(dq + k * 128), 1);
          if (k == 0) {
            wgmma_commit();
            wgmma_wait<1>();
            if (elected && (unsigned)(i - ix) >= 2u) release2(bar + B_EMPTYS + sp * 8);
          }
        }
        wgmma_commit();
        if ((unsigned)(i - ix) < 2u) {
          PHASE_CTX();
          {
            float s0 = 0.f, s1 = 0.f, q0 = 0.f, q1 = 0.f;
            const uint32_t xa = sb + ((QA >> (4 * sp)) & 15) * SLOT + rowo;
#pragma unroll
            for (int jp = 0; jp < 4; ++jp) {
              uint32_t x0, x1, x2, x3;
              ldsm_x4(x0, x1, x2, x3, xa + (X ^ (jp << 5)));
              s0 += (bf_lo(x0) + bf_hi(x0)) + (bf_lo(x2) + bf_hi(x2));
              s1 += (bf_lo(x1) + bf_hi(x1)) + (bf_lo(x3) + bf_hi(x3));
              q0 = fmaf(bf_lo(x0), bf_lo(x0), fmaf(bf_hi(x0), bf_hi(x0), fmaf(bf_lo(x2), bf_lo(x2), fmaf(bf_hi(x2), bf_hi(x2), q0))));
              q1 = fmaf(bf_lo(x1), bf_lo(x1), fmaf(bf_hi(x1), bf_hi(x1), fmaf(bf_lo(x3), bf_lo(x3), fmaf(bf_hi(x3), bf_hi(x3), q1))));
            }
            stats_out(s0, s1, q0, q1, g_stats + m0 + wrow0 + gq, t);
          }
          __syncwarp();
          if (lane == 0 && i != ix) mbar_arrive(bar + B_XDONE);
          nbar_dyn(3 + wu, 128);
          if (elected) release2(bar + B_EMPTYS + sp * 8);
        }
        if (i == 1 && layer) {
          PHASE_CTX();
          slab_out_half(sb + (XS + 1) * SLOT, g_x + (size_t)m0 * D_ + g * 128 + 64, wrow0, lane);
          __syncwarp();
          if (lane == 0) mbar_arrive(bar + B_XDONE);
          nbar_dyn(3 + wu, 128);
        }
        sp = s;
        if (++s == 3) { s = 0; ++u; }
      }
      {
        const uint64_t dap = make_desc_ns(sb + SM_AP + wu * 1024, 0, 128), dbp = make_desc_ns(sb + SM_BP + (layer & 1) * 6144, 0, 128);
        if (wu == 0) {
          wgmma_wait<0>();
          if (elected) mbar_arrive(bar + B_R0);
          nbar<6, 256>();
        }
        if (layer < 2) mbar_wait(bar + (layer ? B_CS2 : B_CS), 0);
        mbar_wait(bar + B_STAT, layer & 1);
        mbar_wait(bar + B_FULLS + 16, layer & 1);
        wgmma_fence();
        wgmma_n256_k(acc, dap, dbp, 1);
#pragma unroll
        for (int k = 0; k < 4; ++k) wgmma_n256(acc, D128(dA0 + (QA >> 8) * 1024 + k * 2), D128(dB0 + (QK >> 8) * 1024 + k * 128), 1);
        mbar_wait(bar + B_FULLS, 1);
        PROFT(tid_ == 128, layer * 16 + 9);
        wgmma_fence();
#pragma unroll
        for (int k = 0; k < 4; ++k) wgmma_n256(acc, D128(dA0 + (QA & 15) * 1024 + k * 2), D128(dB0 + (QK & 15) * 1024 + k * 128), 1);
        wgmma_commit();
        if (wu) nbar<6, 256>();
#define Q_TAIL() \
        wgmma_n128_k(acc, dap, dbp + 256, 1); \
        _Pragma("unroll") for (int k = 0; k < 4; ++k) wgmma_n128(acc, D128(dA0 + (QA >> 8) * 1024 + k * 2), D128(dB0 + (QQ >> 8) * 1024 + k * 128), 1); \
        _Pragma("unroll") for (int k = 0; k < 4; ++k) wgmma_n128(acc, D128(dA0 + (QA & 15) * 1024 + k * 2), D128(dB0 + (QQ & 15) * 1024 + k * 128), 1);
        Q_TAIL();
        wgmma_commit();
        wgmma_wait<1>();
#pragma unroll
        for (int i = 0; i < 128; ++i) asm volatile("" : "+f"(acc[i]) :: "memory");
      }
    }
    uint32_t xo[32];
    uint32_t oq[8][4];
    {
      PHASE_CTX();
      PROFT(tid_ == 128, layer * 16 + 1);
      const bool isB = layer & 1;
      const int cu = c.cu;
      if (cu >= 4) asm volatile("bar.arrive 7, 256;" ::: "memory");
      if (elected && cu == 4) mbar_arrive(bar + B_R0);
      uint32_t kq[64];
      const uint32_t rowq = rowo & 8191;
      const float rs0 = lds_f(sb + SM_RS + (16 + wrow0 + gq) * 4), rs1 = lds_f(sb + SM_RS + (24 + wrow0 + gq) * 4);
#define Q_DONE() \
      wgmma_wait<0>(); \
      if (lane == 0) release2(bar + B_E0); \
      _Pragma("unroll") for (int i = 128; i < 192; ++i) asm volatile("" : "+f"(acc[i]) :: "memory"); \
      _Pragma("unroll") for (int i = 0; i < 32; ++i) kq[32 + i] = pack_bf16(acc[128 + 2 * i], acc[129 + 2 * i]);
      if (isB) {
        if (cu == 0) asm volatile("bar.arrive 10, 64;" ::: "memory");
        if (elected) release2(bar + B_E1);
        const int e = gq & 1;
        const bool sel = t > (gq >> 1);
        const uint32_t rja = sb + SM_RS + (wrow0 + 2 * t + e) * 4;
        const float rjA0 = lds_f(rja + 32), rjA1 = lds_f(rja + 64), rjB0 = lds_f(rja + (sel ? 0 : 64)), rjB1 = lds_f(rja + (sel ? 32 : 96));
        uint32_t vv[32];
#pragma unroll
        for (int i = 0; i < 16; ++i) { kq[i] = pack_bf16(acc[2 * i], acc[2 * i + 1]); vv[i] = pack_bf16(acc[64 + 2 * i], acc[65 + 2 * i]); }
        const uint32_t rB = sb + 4 * SLOT + wg * 4 * KVT + rowq;
        auto dump = [&](int hp) {
          const uint32_t kb = rB + 2048 + (hp ^ wg) * 2 * KVT;
#pragma unroll
          for (int jp = 0; jp < 4; ++jp) {
            stsm_x4(kb + (X ^ (jp << 5)), kq[16 * hp + 4 * jp], kq[16 * hp + 4 * jp + 1], kq[16 * hp + 4 * jp + 2], kq[16 * hp + 4 * jp + 3]);
            stsm_x4(kb + KVT + (X ^ (jp << 5)), vv[16 * hp + 4 * jp], vv[16 * hp + 4 * jp + 1], vv[16 * hp + 4 * jp + 2], vv[16 * hp + 4 * jp + 3]);
          }
          if (cu == 3) {
            const uint32_t kd = rB + 2048 + 32768 + (1 - hp) * 2 * KVT;
#pragma unroll
            for (int jp = 0; jp < 4; ++jp) {
              stsm_x4(kd + (X ^ (jp << 5)), kq[16 * hp + 4 * jp], kq[16 * hp + 4 * jp + 1], kq[16 * hp + 4 * jp + 2], kq[16 * hp + 4 * jp + 3]);
              stsm_x4(kd + KVT + (X ^ (jp << 5)), vv[16 * hp + 4 * jp], vv[16 * hp + 4 * jp + 1], vv[16 * hp + 4 * jp + 2], vv[16 * hp + 4 * jp + 3]);
            }
            if (hp) asm volatile("bar.arrive 15, 64;" ::: "memory"); else asm volatile("bar.arrive 9, 64;" ::: "memory");
          }
          asm volatile("bar.arrive %0, 224;" :: "r"(hp ? 13 + (cu >> 2) : 8 + (cu & 4)) : "memory");
        };
        uint4* const hbuf = g_halo + ((c.rb * 8 + g) * 2 + (layer >> 1)) * 512 + lane;
        if (cu < 4) {
          nbar<7, 256>();
          dump(0);
        }
#pragma unroll
        for (int i = 16; i < 32; ++i) { kq[i] = pack_bf16(acc[2 * i], acc[2 * i + 1]); vv[i] = pack_bf16(acc[64 + 2 * i], acc[65 + 2 * i]); }
        if (cu >= 4) {
          if (cu == 7) {
#pragma unroll
            for (int jp = 0; jp < 8; ++jp) {
              st_relaxed4(hbuf + jp * 32, ~kq[4 * jp], ~kq[4 * jp + 1], ~kq[4 * jp + 2], ~kq[4 * jp + 3]);
              st_relaxed4(hbuf + 256 + jp * 32, ~vv[4 * jp], ~vv[4 * jp + 1], ~vv[4 * jp + 2], ~vv[4 * jp + 3]);
            }
          }
          dump(0);
          dump(1);
        }
        PROFT(tid_ == 128, layer * 16 + 2);
        constexpr float SC = 0.17677669529663687f * L2E;
        const float fA0 = rjA0 * rs0 * SC, fB0 = rjB0 * rs0 * SC, fA1 = rjA1 * rs1 * SC, fB1 = rjB1 * rs1 * SC;
        const float bA0 = (m0 + wrow0) ? 0.f : -1e30f, bB = sel ? bA0 : 0.f;
        const uint32_t pA_ = e ? 0x1044u : 0x4410u, pB_ = e ? 0x3244u : 0x4432u, pLo = sel ? pB_ : 0x4444u, pHi = sel ? 0x4444u : pB_;
        const uint32_t KX = ((lane >> 3) ^ (lane & 7)) << 4;
        Q_DONE();
        if (cu == 0) {
          nbar<11, 64>();
        } else if (cu == 4) {
          uint4 hv[16];
          if (c.rb > 0) {
            uint32_t n = 0;
#pragma unroll 1
            while (true) {
              uint32_t mn = 0xFFFFFFFFu;
#pragma unroll
              for (int i = 0; i < 16; ++i) hv[i] = ld_relaxed4(hbuf - 16 * 512 + i * 32);
#pragma unroll
              for (int i = 0; i < 16; ++i) mn = __vimin3_u32(__vimin3_u32(mn, hv[i].x, hv[i].y), hv[i].z, hv[i].w);
              if (__all_sync(0xffffffffu, mn != 0u)) break;
              if (++n > (1u << 20)) { g_err = 4u; break; }
            }
          } else {
#pragma unroll
            for (int i = 0; i < 16; ++i) hv[i] = make_uint4(~0u, ~0u, ~0u, ~0u);
          }
          nbar<10, 64>();
#pragma unroll
          for (int i = 0; i < 16; ++i)
            stsm_x4(rB - 4 * KVT + (((i >> 2) & 1) * 2 + (i >> 3)) * KVT + (X ^ ((i & 3) << 5)), ~hv[i].x, ~hv[i].y, ~hv[i].z, ~hv[i].w);
          asm volatile("bar.arrive 11, 64;" ::: "memory");
          nbar<9, 64>();
        } else {
          nbar_dyn(8 + (cu & 4), 224);
        }
        PROFT(tid_ == 128, layer * 16 + 5);
        PROFT(lane == 0 && layer == PL, 136 + cw);
        auto attend = [&](int hp) {
          const uint32_t qad = sb + (XS + 1 - hp) * SLOT + rowo, kt = rB + 2 * (hp ^ wg) * KVT - (lane & 8) * 128, vt = rB + (2 * (hp ^ wg) + 1) * KVT;
          __syncwarp();
          uint32_t kb[2][2][4], vb[2][2][2][4];
#pragma unroll
          for (int h = 0; h < 2; ++h)
#pragma unroll
            for (int nt = 0; nt < 2; ++nt) ldsm_x4(kb[h][nt][0], kb[h][nt][1], kb[h][nt][2], kb[h][nt][3], kt + nt * 1024 + (KX ^ (h << 6)));
#pragma unroll
          for (int ks = 0; ks < 2; ++ks)
#pragma unroll
            for (int np = 0; np < 2; ++np)
#pragma unroll
              for (int h = 0; h < 2; ++h)
                ldsm_x4_t(vb[h][ks][np][0], vb[h][ks][np][1], vb[h][ks][np][2], vb[h][ks][np][3], vt + ks * 2048 + (X ^ (h << 6) ^ (np << 5)));
          if (hp == 0 && lane == 0) release2(bar + B_E3);
          float la[2][2], lb[2][2], mx[2][2], sm[2][2];
#pragma unroll
          for (int h = 0; h < 2; ++h) {
            const int qo = 32 + 16 * hp + 8 * h, ko = 16 * hp + 8 * h;
            float sc[4][4];
#pragma unroll
            for (int nt = 0; nt < 4; ++nt) {
              sc[nt][0] = sc[nt][1] = sc[nt][2] = sc[nt][3] = 0.f;
#pragma unroll
              for (int ks = 0; ks < 2; ++ks)
                mma_bf16(sc[nt], kq[qo + 4 * ks], kq[qo + 4 * ks + 1], kq[qo + 4 * ks + 2], kq[qo + 4 * ks + 3],
                         nt < 2 ? kb[h][nt & 1][2 * ks] : kq[ko + 4 * ks + (nt & 1)], nt < 2 ? kb[h][nt & 1][2 * ks + 1] : kq[ko + 4 * ks + 2 + (nt & 1)]);
            }
            la[h][0] = fmaf(e ? sc[1][1] : sc[1][0], fA0, bA0);
            lb[h][0] = fmaf(sel ? (e ? sc[0][1] : sc[0][0]) : (e ? sc[2][1] : sc[2][0]), fB0, bB);
            la[h][1] = (e ? sc[2][3] : sc[2][2]) * fA1;
            lb[h][1] = fmaf(sel ? (e ? sc[1][3] : sc[1][2]) : (e ? sc[3][3] : sc[3][2]), fB1, bB);
            mx[h][0] = fmaxf(la[h][0], lb[h][0]); mx[h][1] = fmaxf(la[h][1], lb[h][1]);
          }
#pragma unroll
          for (int o = 1; o <= 2; o <<= 1)
#pragma unroll
            for (int h = 0; h < 2; ++h)
#pragma unroll
              for (int r = 0; r < 2; ++r) mx[h][r] = fmaxf(mx[h][r], __shfl_xor_sync(0xffffffffu, mx[h][r], o));
          float oa[2][4][4];
#pragma unroll
          for (int h = 0; h < 2; ++h) {
#pragma unroll
            for (int r = 0; r < 2; ++r) { la[h][r] = ex2(la[h][r] - mx[h][r]); lb[h][r] = ex2(lb[h][r] - mx[h][r]); sm[h][r] = la[h][r] + lb[h][r]; }
            const uint32_t p0 = pack_bf16(la[h][0] * rjA0, lb[h][0] * rjB0), p1 = pack_bf16(la[h][1] * rjA1, lb[h][1] * rjB1);
            const uint32_t a00 = __byte_perm(p0, 0u, pLo), a02 = __byte_perm(p0, 0u, pA_), a03 = __byte_perm(p1, 0u, pLo);
            const uint32_t a10 = __byte_perm(p0, 0u, pHi), a11 = __byte_perm(p1, 0u, pA_), a13 = __byte_perm(p1, 0u, pHi);
#pragma unroll
            for (int i = 0; i < 4; ++i) {
              oa[h][i][0] = oa[h][i][1] = oa[h][i][2] = oa[h][i][3] = 0.f;
              mma_bf16(oa[h][i], a00, 0u, a02, a03, vb[h][0][i >> 1][2 * (i & 1)], vb[h][0][i >> 1][2 * (i & 1) + 1]);
              mma_bf16(oa[h][i], a10, a11, 0u, a13, vb[h][1][i >> 1][2 * (i & 1)], vb[h][1][i >> 1][2 * (i & 1) + 1]);
            }
          }
#pragma unroll
          for (int o = 1; o <= 2; o <<= 1)
#pragma unroll
            for (int h = 0; h < 2; ++h)
#pragma unroll
              for (int r = 0; r < 2; ++r) sm[h][r] += __shfl_xor_sync(0xffffffffu, sm[h][r], o);
          mbar_wait(bar + (hp ? B_XOLD2 : B_XOLD), 1);
#pragma unroll
          for (int jp = 0; jp < 4; ++jp) ldsm_x4(xo[16 * hp + 4 * jp], xo[16 * hp + 4 * jp + 1], xo[16 * hp + 4 * jp + 2], xo[16 * hp + 4 * jp + 3], qad + (X ^ (jp << 5)));
#pragma unroll
          for (int h = 0; h < 2; ++h) {
            const float i0 = rcp(sm[h][0]), i1 = rcp(sm[h][1]);
#pragma unroll
            for (int np = 0; np < 2; ++np)
            {
              uint32_t (&o)[4] = oq[4 * hp + 2 * h + np];
              o[0] = pack_bf16(oa[h][2 * np][0] * i0, oa[h][2 * np][1] * i0); o[1] = pack_bf16(oa[h][2 * np][2] * i1, oa[h][2 * np][3] * i1);
              o[2] = pack_bf16(oa[h][2 * np + 1][0] * i0, oa[h][2 * np + 1][1] * i0); o[3] = pack_bf16(oa[h][2 * np + 1][2] * i1, oa[h][2 * np + 1][3] * i1);
              if (!hp || !H1L) stsm_tag(qad + (X ^ (h << 6) ^ (np << 5)), o[0], o[1], o[2], o[3], make_tag(gq, t, 0u), 2 * h + np);
            }
          }
          if (!hp || !H1L) {
          __syncwarp();
          slab_out_half(sb + (XS + 1 - hp) * SLOT, g_o + (size_t)m0 * D_ + g * 128 + hp * 64, wrow0, lane);
          __syncwarp();
          if (lane == 0) mbar_arrive(bar + (hp ? B_ODONE : B_OH1));
          }
          PROFT(lane == 0 && layer == PL && hp == 0, 128 + cw);
        };
        attend(0);
        if (cu < 4) dump(1);
        if (cu == 4) nbar<15, 64>();
        else if (cu != 0) nbar_dyn(13 + (cu >> 2), 224);
        attend(1);
      } else {
#pragma unroll
        for (int i = 0; i < 32; ++i) kq[i] = pack_bf16(acc[2 * i], acc[2 * i + 1]);
        if (cu < 4) nbar<7, 256>();
        {
          const uint32_t vb = sb + (5 + 3 * wg) * SLOT + (rowq >> 1) + ((lchk ^ ((lane & 7) >> 1)) << 4);
#pragma unroll
          for (int jp = 8; jp < 16; ++jp)
            stsm_x4((vb ^ ((jp & 1) << 5)) + ((jp >> 1) & 3) * 4096,
                    pack_bf16(acc[8 * jp], acc[8 * jp + 1]), pack_bf16(acc[8 * jp + 2], acc[8 * jp + 3]),
                    pack_bf16(acc[8 * jp + 4], acc[8 * jp + 5]), pack_bf16(acc[8 * jp + 6], acc[8 * jp + 7]));
        }
        PROFT(tid_ == 128, layer * 16 + 2);
        Q_DONE();
        const uint32_t pA = sb + (3 + 3 * wg) * SLOT + (rowo & 8191);
        float sc0 = rs0 * L2E, sc1 = rs1 * L2E;
        const uint32_t wa0 = sb + SM_WPHI + lrow * 80 + lchk * 16;
        const uint32_t wu = c.cu >> 2, par = (layer >> 1) & 1;
        float p[2][4][4];
        uint32_t raw[2][4][4], ph[2][4][4];
        float kva[20], oab[2][2][20];
        auto kv_start = [&](int hp) {
#pragma unroll
          for (int h = 0; h < 2; ++h)
#pragma unroll
            for (int cp = 0; cp < 4; ++cp)
              stsm_x4(pA + hp * 16384 + h * 8192 + (X ^ (cp << 5)), ph[h][cp][0], ph[h][cp][1], ph[h][cp][2], ph[h][cp][3]);
          PROFT(tid_ == 128, layer * 16 + 11);
          fence_async_smem();
          nbar<1, 256>();
          const uint32_t hu = 2 * hp + wu;
          const uint32_t dP = (((sb + 3 * SLOT + hu * 8192) & 0x3FFFF) >> 4) | (512u << 16);
          const uint32_t dV = (((sb + 5 * SLOT + hu * 4096) & 0x3FFFF) >> 4) | (((SM_SD - 5 * SLOT - hu * 4096) >> 4) << 16);
          wgmma_fence();
#pragma unroll
          for (int ks = 0; ks < 8; ++ks)
            wgmma_n40_tt(kva, desc64(dP + (ks >> 2) * 3072 + (ks & 3) * 128, 0x40000040u),
                         desc64(dV + (ks >> 2) * (3072u - (2816u << 16)) + (ks & 3) * 64, 0x80000020u), ks != 0);
          wgmma_commit();
        };
        auto kv_end = [&](int hp) {
          wgmma_wait<0>();
#pragma unroll
          for (int i = 0; i < 20; ++i) asm volatile("" : "+f"(kva[i]) :: "memory");
          nbar_dyn(3 + wu, 128);
          PROFT(tid_ == 128, layer * 16 + 12);
          const bool od = lane & 1;
#pragma unroll
          for (int i = 0; i < 4; ++i)
            sts128(sb + (3 + hp) * SLOT + (cw * 128 + i * 32 + lane) * 16,
                   make_uint4(__float_as_uint(kva[4 * i]), __float_as_uint(kva[4 * i + 1]), __float_as_uint(kva[4 * i + 2]),
                              __float_as_uint(od == (i >= 2) ? 1.f : kva[4 * i + 3])));
          sts128(sb + (6 + hp) * SLOT + wg * 8192 + (wq * 32 + lane) * 16,
                 make_uint4(__float_as_uint(od ? kva[11] : kva[3]), __float_as_uint(od ? kva[15] : kva[7]), __float_as_uint(od ? kva[18] : kva[16]), __float_as_uint(1.f)));
          fence_async_smem();
          __syncwarp();
          if (lane == 0) mbar_arrive(bar + B_KVDONE - hp * 32);
          PROFT(tid_ == 128, layer * 16 + 3);
        };
        const uint4* const kvg = g_kv + (g * 2 + (layer >> 1)) * 2560 + cw * 128 + lane;
        uint4 ub[2][5];
        auto kv_load = [&](int hp) {
          uint4 (&u)[5] = ub[hp];
#pragma unroll
          for (int i = 0; i < 4; ++i) u[i] = ld_relaxed4(kvg + hp * 1280 + i * 32);
          u[4] = ld_relaxed4(kvg + hp * 1280 + 1024 - cw * 96);
        };
        auto kv_conv = [&](int hp) {
          uint4 (&u)[5] = ub[hp];
          PROFT(tid_ == 128 && hp == 0, layer * 16 + 10);
          PROFT(lane == 0 && hp == 1 && layer == PL, 128 + cw);
          if (hp == 0) mbar_wait(bar + B_KVDONE - 32, par);
          const bool od = lane & 1;
          uint32_t n = 0;
#pragma unroll 1
          while (!__all_sync(0xffffffffu, (od ? u[2].w : u[0].w) == 0x41800000u && (od ? u[3].w : u[1].w) == 0x41800000u && u[4].w == 0x41800000u)) {
#pragma unroll 1
            while (__any_sync(0xffffffffu, u[4].w < KVTH) && ++n < (1u << 20)) u[4].w = ld_relaxed(&kvg[hp * 1280 + 1024 - cw * 96].w);
            if (++n > (1u << 20)) { g_err = 6u; break; }
            kv_load(hp);
          }
          PROFT(lane == 0 && hp == 1 && layer == PL, 136 + cw);
          PROFT(tid_ == 128 && hp == 0, layer * 16 + 5);
          if (!od) { u[0].w = u[4].x; u[1].w = u[4].y; } else { u[2].w = u[4].x; u[3].w = u[4].y; }
#pragma unroll
          for (int i = 0; i < 4; i += 2)
            stsm_x4(sb + (5 + 3 * hp) * SLOT + rowo + (X ^ ((i & 2) << 4)),
                    pack_bf16(__uint_as_float(u[i].x), __uint_as_float(u[i].y)), pack_bf16(__uint_as_float(u[i].z), __uint_as_float(u[i].w)),
                    pack_bf16(__uint_as_float(u[i + 1].x), __uint_as_float(u[i + 1].y)), pack_bf16(__uint_as_float(u[i + 1].z), __uint_as_float(u[i + 1].w)));
          const uint32_t z2 = pack_bf16(__uint_as_float(u[4].z), __uint_as_float(u[4].z));
          if (t < 2) sts128(sb + (5 + 3 * hp) * SLOT + (wrow0 + gq + 8 * t) * 128 + ((4 ^ gq) << 4), make_uint4(z2, z2, z2, z2));
        };
        auto o_mma = [&](int hp, const uint32_t (&pq)[2][4][4]) {
          float (&oa)[2][20] = oab[hp];
          PROFT(tid_ == 128 && hp == 1, layer * 16 + 4);
          const uint32_t dK = (((sb + (5 + 3 * hp) * SLOT) & 0x3FFFF) >> 4) | (512u << 16);
          wgmma_fence();
#pragma unroll
          for (int ks = 0; ks < 4; ++ks) {
#pragma unroll
            for (int hh = 0; hh < 2; ++hh) wgmma_n40_rs(oa[hh], pq[hh][ks], D128(dK + hh * 512 + ks * 128), ks != 0);
          }
          wgmma_commit();
        };
        auto o_start = [&](int hp, const uint32_t (&pq)[2][4][4]) {
          kv_conv(hp);
          fence_async_smem();
          nbar<1, 256>();
          o_mma(hp, pq);
        };
        auto o_end = [&](int hp) {
          float (&oa)[2][20] = oab[hp];
          wgmma_wait<0>();
#pragma unroll
          for (int i = 0; i < 20; ++i) asm volatile("" : "+f"(oa[0][i]), "+f"(oa[1][i]) :: "memory");
#pragma unroll
          for (int hh = 0; hh < 2; ++hh) {
            const float i0 = rcp(oa[hh][16] + 1e-6f), i1 = rcp(oa[hh][18] + 1e-6f);
            const uint32_t qad = sb + (3 + hp) * SLOT + rowo, hx = hh << 6;
#pragma unroll
            for (int np = 0; np < 2; ++np)
            {
              uint32_t (&o)[4] = oq[4 * hp + 2 * hh + np];
              o[0] = pack_bf16(oa[hh][8 * np] * i0, oa[hh][8 * np + 1] * i0); o[1] = pack_bf16(oa[hh][8 * np + 2] * i1, oa[hh][8 * np + 3] * i1);
              o[2] = pack_bf16(oa[hh][8 * np + 4] * i0, oa[hh][8 * np + 5] * i0); o[3] = pack_bf16(oa[hh][8 * np + 6] * i1, oa[hh][8 * np + 7] * i1);
              if (!hp || !H1L) stsm_tag(qad + (X ^ hx ^ (np << 5)), o[0], o[1], o[2], o[3], make_tag(gq, t, 1u), 2 * hh + np);
            }
          }
          if (!hp || !H1L) {
          __syncwarp();
          slab_out_half(sb + (3 + hp) * SLOT, g_o + (size_t)m0 * D_ + g * 128 + hp * 64, wrow0, lane);
          __syncwarp();
          if (lane == 0) mbar_arrive(bar + (hp ? B_ODONE : B_OH1));
          }
        };
#define XO_LOAD() \
        mbar_wait(bar + B_XOLD, 0); \
        mbar_wait(bar + B_XOLD2, 0); \
        _Pragma("unroll") for (int jp = 0; jp < 8; ++jp) \
          ldsm_x4(xo[4 * jp], xo[4 * jp + 1], xo[4 * jp + 2], xo[4 * jp + 3], sb + (XS + 1 - (jp >> 2)) * SLOT + rowo + (X ^ ((jp & 3) << 5)));
#define SC_RELOAD() \
        sc0 = __uint_as_float(lds_vol(sb + SM_RS + (16 + wrow0 + gq) * 4)) * L2E; sc1 = __uint_as_float(lds_vol(sb + SM_RS + (24 + wrow0 + gq) * 4)) * L2E;
        __syncwarp();
        phi_proj<0>(p, kq, wa0);
        phi_exp(raw[0], p[0], sc0, sc1);
        phi_exp(raw[1], p[1], sc0, sc1);
        phi_proj<16>(p, kq, wa0 + 5120);
        phi_norm<0>(ph, raw, kq, wa0, sc0, sc1, rs0, rs1);
#define PIN(h) if ((raw[h][2][0] & raw[h][2][2] & raw[h][3][0] & raw[h][3][2]) == ~0u) sts_f(sb + SM_EPOCH + 12, 0.f)
        kv_start(0);
        phi_exp(raw[0], p[0], sc0, sc1);
        if (OV & 1) { phi_exp(raw[1], p[1], sc0, sc1); PIN(0); PIN(1); }
        kv_end(0);
        if (RL & 1) { SC_RELOAD(); }
        XO_LOAD();
        if (!(OV & 1)) phi_exp(raw[1], p[1], sc0, sc1);
        phi_proj<32>(p, kq, wa0);
        phi_norm<16>(ph, raw, kq, wa0 + 5120, sc0, sc1, rs0, rs1);
        kv_start(1);
        if (lane == 0) release2(bar + B_E3);
        phi_exp(raw[0], p[0], sc0, sc1);
        if (OV & 2) PIN(0);
        kv_end(1);
        if (RL & 2) { SC_RELOAD(); }
        phi_exp(raw[1], p[1], sc0, sc1);
        phi_proj<48>(p, kq, wa0 + 5120);
        phi_norm<32>(ph, raw, kq, wa0, sc0, sc1, 1.f, 1.f);
        kv_load(0);
        phi_exp(raw[0], p[0], sc0, sc1);
        phi_exp(raw[1], p[1], sc0, sc1);
        if ((raw[0][2][0] & raw[0][2][2] & raw[0][3][0] & raw[0][3][2] & raw[1][2][0] & raw[1][2][2] & raw[1][3][0] & raw[1][3][2]) == ~0u) sts_f(sb + SM_EPOCH + 12, 0.f);
        o_start(0, ph);
        kv_load(1);
        o_end(0);
        phi_norm<48>(ph, raw, kq, wa0 + 5120, sc0, sc1, 1.f, 1.f);
        o_start(1, ph);
        o_end(1);
      }
      __syncwarp();
      PROFT(lane == 0 && layer == PL, 216 + cw);
      if (lane == 0) mbar_arrive(bar + B_EPI);
      PROFT(tid_ == 128, layer * 16 + 6);
    }
    {
      PHASE_CTX();
      const uint32_t wu = c.cu >> 2;
      const uint32_t dA0 = (((sb + wu * 8192) & 0x3FFFF) >> 4) | (1u << 16), dB0 = ((sb & 0x3FFFF) >> 4) | (512u << 16);
#pragma unroll
      for (int i = 0; i < 32; ++i) { acc[128 + 2 * i] = bf_lo(xo[i]); acc[129 + 2 * i] = bf_hi(xo[i]); }
      uint64_t ta = ((layer & 1) ? WO_A1 : WO_A0) >> 8, tw = (layer & 1) ? WO_B1 : WO_B0;
      mbar_wait(bar + B_FULLT, layer & 1);
      mbar_wait(bar + B_FULLT + 8, layer & 1);
      PROFT(tid_ == 128 && layer == PL, 160);
      wgmma_fence();
#pragma unroll
      for (int k = 0; k < 8; ++k) wgmma_n128_rs(acc, oq[k], D128(dB0 + ((uint32_t)(tw >> (k & 4)) & 15) * 1024 + (k & 3) * 128), 1);
      wgmma_commit();
      tw >>= 8;
      if (lane == 0 && !H1L) release2(bar + B_E2);
#pragma unroll 1
      for (int i = 2; i < 16; ++i) {
        mbar_wait(bar + B_FULLT + i * 8, layer & 1);
        PROFT(tid_ == 128 && layer == PL, 160 + i);
        tile_check(sb + ((uint32_t)ta & 15) * SLOT, g_o + (size_t)m0 * D_ + ((2 * g + (int)(WOORD >> (4 * i))) & 15) * 64, wrow0, lane, ~layer);
        const uint32_t da = dA0 + ((uint32_t)ta & 15) * 1024, db = dB0 + ((uint32_t)tw & 15) * 1024;
        ta >>= 4; tw >>= 4;
        if (i == 16 - WSK && wu) nbar<6, 256>();
        wgmma_fence();
#pragma unroll
        for (int k = 0; k < 4; ++k) wgmma_n128(acc, D128(da + k * 2), D128(db + k * 128), 1);
        wgmma_commit();
        if (i == 15 && !wu) asm volatile("bar.arrive 6, 256;" ::: "memory");
        if (H1L && i == H1L) {
          const uint32_t st = sb + ((layer & 1) ? XS : 4) * SLOT;
#pragma unroll
          for (int k = 0; k < 4; ++k) stsm_tag(st + rowo + (X ^ (k << 5)), oq[4 + k][0], oq[4 + k][1], oq[4 + k][2], oq[4 + k][3], make_tag(gq, t, ~layer), k);
          __syncwarp();
          slab_out_half(st, g_o + (size_t)m0 * D_ + g * 128 + 64, wrow0, lane);
          __syncwarp();
          if (lane == 0) { mbar_arrive(bar + B_ODONE); release2(bar + B_E2); }
        }
        wgmma_wait<1>();
        if (elected && i < 12) release2(bar + B_CONS + (i - 1) * 8);
        if (elected && (unsigned)(i - EI) < 2u && layer + 1 < NLAYERS) release2(bar + B_EMPTYS + (i - EI) * 8);
      }
      const bool last = layer == NLAYERS - 1;
      Tag xt = make_tag(gq, last ? 4 : t, lds_vol(sb + SM_EPOCH) + layer + 1);
      asm volatile("" : "+r"(xt.me), "+r"(xt.mo), "+r"(xt.tg) :: "memory");
      if (RT2 && !last) mbar_wait(bar + B_FULLS, 0);
      wgmma_wait<0>();
#pragma unroll
      for (int i = 128; i < 192; ++i) asm volatile("" : "+f"(acc[i]) :: "memory");
      if (elected && !last) release2(bar + B_EMPTYS + 16);
      PROFT(tid_ == 128, layer * 16 + 7);
      X_HALF(0, xt);
      if (last) {
        __syncwarp();
        slab_out_half(sb + XS * SLOT, c.out + (size_t)m0 * D_ + g * 128, wrow0, lane);
        X_HALF(1, (Tag{0u, 0u, 0u}));
        __syncwarp();
        slab_out_half(sb + (XS + 1) * SLOT, c.out + (size_t)m0 * D_ + g * 128 + 64, wrow0, lane);
        __syncwarp();
        if (lane == 0) mbar_arrive(bar + B_XDONE);
        PROFT(tid_ == 128, layer * 16 + 24);
        break;
      }
      __syncwarp();
      slab_out_half(sb + XS * SLOT, g_x + (size_t)m0 * D_ + g * 128, wrow0, lane, true);
      __syncwarp();
      if (lane == 0) mbar_arrive(bar + B_XH0);
      nbar_dyn(3 + wu, 128);
    }
  }
}

__device__ __forceinline__ int kblock0(int i, int g) {
  const int j = i >> 1, p = max(g, NCOM) + j - NCOM;
  return (j < NCOM ? j : p < 8 ? p : p - 8 + NCOM) * 2 + (i & 1);
}

__device__ __forceinline__ int wo_kblock(int m, int g) { return (2 * g + (int)((WOORD >> (4 * m)) & 15)) & 15; }

__global__ void __cluster_dims__(2, 1, 1) __launch_bounds__(384, 1)
mega_kernel(const __grid_constant__ CUtensorMap tm_x0, const __grid_constant__ CUtensorMap tm_x,
            const __grid_constant__ CUtensorMap tm_o,
            const __grid_constant__ CUtensorMap tm_wA, const __grid_constant__ CUtensorMap tm_wB,
            const __grid_constant__ CUtensorMap tm_woA, const __grid_constant__ CUtensorMap tm_woB,
                        const bf16* __restrict__ wB, const bf16* __restrict__ wphi, bf16* __restrict__ out) {
  extern __shared__ uint8_t smem_raw[];
  const uint32_t sb = (smem_u32(smem_raw) + 1023u) & ~1023u;
  const uint32_t bar = sb + SM_BAR;
  const int warp = __shfl_sync(0xffffffffu, threadIdx.x >> 5, 0), lane = threadIdx.x & 31;
  uint32_t bid = blockIdx.x;
  if (MAP == 3 && gridDim.x == 128 + NX) {
    uint32_t tp;
    asm volatile("mov.u32 %0, %%smid;" : "=r"(tp));
    tp >>= 1;
    const uint32_t u7 = ((tp - 32) * 37) >> 8;
    bid = (tp < 32 ? tp : tp < 60 ? tp + 1 + u7 : tp < 62 ? tp + 4 : (tp - 58) * 8) * 2 + (bid & 1);
  }
  if (bid >= 128 || gridDim.x == NX) {
    const int xb = bid & (NX - 1);
    const int ch = threadIdx.x % 96, rg = threadIdx.x / 96, gg = xb * 2 + ch / 48, sec = (ch % 48) >> 4;
    const uint4* src = reinterpret_cast<const uint4*>(wB + (size_t)rg * 3072 + (sec == 2 ? 0 : 1024 + sec * 1024) + gg * 128 + (ch & 15) * 8);
    float s[8] = {0.f, 0.f, 0.f, 0.f, 0.f, 0.f, 0.f, 0.f};
#pragma unroll 1
    for (int r0 = 0; r0 < 256; r0 += 32) {
      uint4 v[32];
#pragma unroll
      for (int r = 0; r < 32; ++r) v[r] = __ldg(src + (size_t)(r0 + r) * 1536);
#pragma unroll
      for (int r = 0; r < 32; ++r) {
        s[0] += bf_lo(v[r].x); s[1] += bf_hi(v[r].x); s[2] += bf_lo(v[r].y); s[3] += bf_hi(v[r].y);
        s[4] += bf_lo(v[r].z); s[5] += bf_hi(v[r].z); s[6] += bf_lo(v[r].w); s[7] += bf_hi(v[r].w);
      }
    }
    float* cd = g_cs + (ld_relaxed(&g_epoch) & 1) * 6144 + 3072 + xb * 768 + ch * 8;
    red_add4(cd, s[0], s[1], s[2], s[3]);
    red_add4(cd + 4, s[4], s[5], s[6], s[7]);
    nbar<1, 384>();
    if (threadIdx.x < 2) flag_add(&g_csflag[8 + xb * 2 + threadIdx.x].v);
    return;
  }
  const int cr = bid & 1;
  const int g = bid >> 4;
  const int rb = bid & 15;
  const int m0 = rb * 128;

  if (warp < 4) {
    asm volatile("setmaxnreg.dec.sync.aligned.u32 40;");
    asm volatile("barrier.cluster.arrive.relaxed.aligned;" ::: "memory");
    const unsigned int epoch = warp ? ld_relaxed(&g_epoch) : 0u;
    if (warp) cluster_wait();
    unsigned int xbase = epoch * NLAYERS;
    auto wo_a = [&](int layer, int m1) {
      uint64_t ts = ((layer & 1) ? WO_A1 : WO_A0) >> (4 * m1), td = ((layer & 1) ? WO_DA1 : WO_DA0) >> (4 * m1), tk = WOORD >> (4 * m1);
      uint32_t ready = 0u;
#pragma unroll 1
      for (int m = m1; m < 16; ++m) {
        const int kb = (2 * g + (uint32_t)tk) & 15;
        uint32_t dst = sb + ((uint32_t)ts & 15) * SLOT, fb = bar + B_FULLT + m * 8, eb = bar + B_CONS + ((uint32_t)td & 15) * 8;
        int kc = kb * 64;
        ts >>= 4; td >>= 4; tk >>= 4;
        asm volatile("" : "+r"(dst), "+r"(fb), "+r"(eb), "+r"(kc));
        bool fr = false;
        if (!((ready >> kb) & 1)) {
          PROFT(m == 2 && lane == 0, 64 + layer * 16 + 2);
          fr = src_wait_tma(g_of + rb * 32, xbase + layer + 1, 1u << kb, ready, lane, eb, layer & 1);
          fence_async_all();
        }
        if (m == 6) mbar_wait_u(bar + B_EPI, layer & 1);
        if (!fr) mbar_wait_u(eb, layer & 1);
        tma_2d_e(dst, &tm_o, kc, m0, fb);
        PROFT(lane == 0 && layer == PL, 176 + m);
      }
    };
    auto wo_w = [&](int layer) {
      const CUtensorMap* tx = layer == 0 ? &tm_x0 : &tm_x;
      const CUtensorMap* two = (layer & 1) ? &tm_woB : &tm_woA;
      uint64_t ts = (layer & 1) ? WO_B1 : WO_B0, td = (layer & 1) ? WO_DB1 : WO_DB0, tk = WOORD;
      uint32_t pb = 0;
      fence_async_all();
      mbar_wait_u(bar + B_R0, layer & 1);
      expect_tx_e(bar + B_XOLD, 16384);
      tma_2d_e(sb + (XS + 1) * SLOT, tx, g * 128, m0, bar + B_XOLD);
#pragma unroll 1
      for (int m = 0; m < 16; ++m) {
        uint32_t dst = sb + ((uint32_t)ts & 15) * SLOT + cr * 8192, fb = bar + B_FULLT + m * 8, eb = bar + B_CONS + ((uint32_t)td & 15) * 8;
        int kc = ((2 * g + (uint32_t)tk) & 15) * 64;
        ts >>= 4; td >>= 4; tk >>= 4;
        asm volatile("" : "+r"(dst), "+r"(fb), "+r"(eb), "+r"(kc));
        if (eb < bar + B_E3 && pb >= bar + B_E3) mbar_wait_u(bar + B_E2, layer & 1);
        if (eb != pb) mbar_wait_u(eb, layer & 1);
        pb = eb;
        tma_2d_mc_e(dst, two, g * 128 + cr * 64, kc, fb);
        expect_tx_e(fb, m < 2 ? 16384 : 32768);
        PROFT(lane == 0 && layer == PL, 144 + m);
        if (m == ((layer & 1) ? 2 : 0)) {
          expect_tx_e(bar + B_XOLD2, 16384);
          tma_2d_e(sb + XS * SLOT, tx, g * 128 + 64, m0, bar + B_XOLD2);
        }
      }
    };
    if (warp == 0) {
      cluster_wait();
      PROFT(lane == 0, 125);
#pragma unroll 1
      for (int layer = 0; layer < NLAYERS; ++layer) {
        const CUtensorMap* tx = layer == 0 ? &tm_x0 : &tm_x;
        const CUtensorMap* tw = (layer & 1) ? &tm_wB : &tm_wA;
        uint32_t s = layer == 0, u = 0, ready = layer == 0 ? 0xFFFFu : 0u;
#pragma unroll 1
        for (int i = s; i < 16; ++i) {
          const int kb = layer == 0 ? kblock0(i, g) : wo_kblock(i, g), kc = kb * 64;
          const uint32_t fb = bar + B_FULLS + s * 8;
          const uint32_t kd = sb + (((QK >> (4 * s)) & 15) + cr) * SLOT, qd = sb + ((QQ >> (4 * s)) & 15) * SLOT + cr * 8192;
          const uint32_t need = 1u << kb;
          const bool ext = i >= 2 || layer == 0, early = ext && (ready & need) == need;
          mbar_wait_u(bar + B_EMPTYS + s * 8, (u + (s ? layer : 0) + 1) & 1);
          if (early) tma_2d_e(sb + ((QA >> (4 * s)) & 15) * SLOT, tx, kc, m0, fb);
          tma_2d_mc_e(kd, tw, 1024 + cr * 1024 + g * 128, kc, fb);
          tma_2d_mc_e(kd + 8192, tw, 1024 + cr * 1024 + g * 128 + 64, kc, fb);
          tma_2d_mc_e(qd, tw, g * 128 + cr * 64, kc, fb);
          expect_tx_e(fb, ext ? 65536 : 49152);
          PROFT(lane == 0 && layer == 0 && i == 1, 31);
          if (layer == 0 && g >= NCOM && i == XPF + (((g - NCOM) * XPM) >> 2)) {
            if (i <= 2) mbar_wait_u(bar + B_FULLS, 0);
            tma_pf_e(&tm_x0, g * 128, m0);
            tma_pf_e(&tm_x0, g * 128 + 64, m0);
          }
          if (layer < 2 && i >= PFS) {
            const int j = i - PFS;
            if (j < 2) tma_pf_e(layer ? &tm_woB : &tm_woA, g * 128 + j * 64, rb * 64);
            else if (j < 8 && layer == 0) tma_pf_e(&tm_wB, ((j >> 1) - 1) * 1024 + g * 128 + (j & 1) * 64, rb * 64);
          }
          if (ext && !early) {
            PROFT(i == 2 && lane == 0, 64 + layer * 16 + 0);
            src_wait_tma(g_xf + rb * 32, xbase + layer + 1, need, ready, lane, fb, 0);
            PROFT(i == 2 && lane == 0, 64 + layer * 16 + 1);
            fence_async_all();
            tma_2d_e(sb + ((QA >> (4 * s)) & 15) * SLOT, tx, kc, m0, fb);
          }
          if (++s == 3) { s = 0; ++u; }
        }
        if (layer == 0) xbase = ld_relaxed(&g_epoch) * NLAYERS;
        wo_a(layer, 2);
      }
    } else {
      if (warp >= 2) {
        const int h2 = threadIdx.x - 64;
        if (h2 < 16) sts_f(sb + SM_RS + h2 * 4, 0.f);
        if (h2 == 0) sts_f(sb + SM_EPOCH, __uint_as_float(epoch));
        mbar_wait_u(bar + B_FULLS, 0);
        colsum(&tm_wA, g_cs + (epoch & 1) * 6144, rb, g, warp - 2, 2, lane, warp == 2 ? sb + SM_SD : (sb + SM_BP + 1023u) & ~1023u, bar + B_CB + (warp - 2) * 8, 0);
#pragma unroll 1
        for (int i = h2; i < 320; i += 64) g_kv[(g * 16 + rb) * 320 + i] = make_uint4(0u, 0u, 0u, 0u);
        fence_async_all();
        nbar<5, 64>();
        if (h2 == 0) flag_add(&g_csflag[g].v);
        PROFT(h2 == 0, 242);
#pragma unroll 1
        for (int i = h2; i < 512; i += 256) {
          uint4 w[4];
#pragma unroll
          for (int j = 0; j < 4; ++j) w[j] = __ldg(reinterpret_cast<const uint4*>(wphi + (size_t)g * 4096) + i + j * 64);
#pragma unroll
          for (int j = 0; j < 4; ++j) sts128(sb + SM_WPHI + ((i >> 2) + j * 16) * 80 + (i & 3) * 16, w[j]);
        }
      }
      if (warp == 1) {
        if (lane >= 27) {
          const CUtensorMap* tm = lane == 27 ? &tm_o : lane == 28 ? &tm_wB : lane == 29 ? &tm_woA : lane == 30 ? &tm_woB : &tm_x;
          asm volatile("prefetch.tensormap [%0];" ::"l"(tm) : "memory");
        }
        __syncwarp();
        {
#pragma unroll 1
          for (int e = 0;; ++e) {
            if (e > 0 && e < NLAYERS) {
              mbar_wait_u(bar + B_XH0, (e - 1) & 1);
              flag_hint(g_xf + rb * 32 + 2 * g, xbase + e + 1);
            }
            mbar_wait_u(bar + B_XDONE, e & 1);
            PROFT(e < 4, 64 + e * 16 + 4);
            if (e == NLAYERS) {
              if (bid == 0) g_epoch = epoch + 1;
              break;
            }
            PROFT(e < 4, 64 + e * 16 + 5);
            flag_set(g_xf + rb * 32 + 2 * g + 1, xbase + e + 1);
            PROFT(e < 4, 64 + e * 16 + 7);
            if ((e & 1) == 0) {
#pragma unroll 1
              for (int hp = 0; hp < 2; ++hp) {
                uint4* kvl = g_kv + ((g * 2 + (e >> 1)) * 2 + hp) * 1280;
                mbar_wait_u(bar + B_KVDONE - hp * 32, (e >> 1) & 1);
                PROFT(e == PL, 243 + hp * 4);
                bulk_red_add_e(kvl + rb * 64, sb + (3 + hp) * SLOT + rb * 1024, 16384 - rb * 1024);
                if (rb) bulk_red_add_e(kvl, sb + (3 + hp) * SLOT, rb * 1024);
                bulk_red_add_e(kvl + 1024, sb + (6 + hp) * SLOT, 2048);
                bulk_red_add_e(kvl + 1152, sb + (6 + hp) * SLOT + 8192, 2048);
                bulk_commit();
                PROFT(e < 4, 64 + e * 16 + 6);
              }
              bulk_wait_read0();
              __syncwarp();
              if (lane < 2) release2(bar + B_E1);
              __syncwarp();
            }
            mbar_wait_u(bar + B_OH1, e & 1);
            PROFT(e == PL, 251);
            flag_hint(g_of + rb * 32 + 2 * g, xbase + e + 1);
            PROFT(e < 4, 64 + e * 16 + 9);
            mbar_wait_u(bar + B_ODONE, e & 1);
            PROFT(e < 4, 64 + e * 16 + 8);
            flag_hint(g_of + rb * 32 + 2 * g + 1, xbase + e + 1);
            PROFT(e < 4, 64 + e * 16 + 11);
          }
        }
      } else {
        const int h2 = threadIdx.x - 64;
        const float* cs = g_cs + (epoch & 1) * 6144;
#pragma unroll 1
        for (int layer = 0; layer < NLAYERS; ++layer) {
          if (warp == 2 && layer < 2) {
            if (lane == 0) flag_wait_t<128>(&g_csflag[layer * 8 + g].v, (epoch + 1) * (16u + layer));
            __syncwarp();
            float4 a[3];
#pragma unroll
            for (int i = 0; i < 3; ++i) a[i] = __ldcg(reinterpret_cast<const float4*>(cs + layer * 3072 + g * 384) + i * 32 + lane);
#pragma unroll 1
            for (int i = 0; i < 3; ++i) {
              const float av[4] = {a[0].x, a[0].y, a[0].z, a[0].w};
              a[0] = a[1]; a[1] = a[2];
#pragma unroll
              for (int j = 0; j < 4; ++j) {
                const float c1 = bf16r(av[j]), c2 = bf16r(av[j] - c1), c3 = (av[j] - c1) - c2;
                sts128(sb + SM_BP + layer * 6144 + ((i * 32 + lane) * 4 + j) * 16, make_uint4(pack_bf16(c1, c2), pack_bf16(c3, 0.f), 0u, 0u));
              }
            }
            fence_async_smem();
            __syncwarp();
            if (lane == 0) mbar_arrive(bar + (layer ? B_CS2 : B_CS));
            PROFT(lane == 0, 64 + layer * 16 + 12);
            if (layer == 0) {
              uint4* hz = g_halo + (rb * 8 + g) * 1024;
#pragma unroll 2
              for (int i = lane; i < 1024; i += 32) hz[i] = make_uint4(0u, 0u, 0u, 0u);
              if (lane < 12) reinterpret_cast<float4*>(g_cs + ((epoch & 1) ^ 1) * 6144 + bid * 48)[lane] = make_float4(0.f, 0.f, 0.f, 0.f);
              g_stats[(2 + (lane >> 4)) * S_ + m0 + g * 16 + (lane & 15)] = make_float2(0.f, 0.f);
              __syncwarp();
              if (lane == 0) flag_add(&g_csflag[8 + g].v);
            }
          }
          if (warp == 3) {
            const bool hal = (layer & 1) && rb > 0;
            {
              uint32_t rdy = 0u;
              src_wait<256>(g_xf + rb * 32, xbase + layer + 1, 0xAAAAu, rdy, lane);
              rdy = 0u;
              if (hal) src_wait<256>(g_xf + (rb - 1) * 32, xbase + layer + 1, 0xAAAAu, rdy, lane);
            }
            float2 u[5];
            const float2* sp = g_stats + layer * S_ + m0 + lane;
#pragma unroll
            for (int i = 0; i < 4; ++i) u[i] = __ldcg(sp + i * 32);
            u[4] = __ldcg(hal ? sp - 16 : sp);
            if (layer == 3) g_stats[(lane >> 4) * S_ + m0 + g * 16 + (lane & 15)] = make_float2(0.f, 0.f);
#pragma unroll
            for (int i = 0; i < 5; ++i) {
              const int r = i < 4 ? 16 + i * 32 + lane : lane;
              const float mean = u[i].x * (1.f / D_);
              const float var = fmaxf(fmaf(-u[i].x, mean, u[i].y) * (1.f / D_), 0.f);
              float sd;
              asm("sqrt.approx.f32 %0, %1;" : "=f"(sd) : "f"(bf16r(bf16r(var) + 1e-5f)));
              sd = bf16r(sd);
              if (i < 4 || hal) sts_f(sb + SM_RS + r * 4, rcp(sd));
              if (i < 4) {
                const float hm = -0.5f * bf16r(mean);
                const uint32_t s2 = pack_bf16(sd, sd);
                if (!(layer & 1)) sts128(sb + SM_SD + (r - 16) * 64 + ((r >> 1) & 3) * 16, make_uint4(s2, s2, s2, s2));
                sts128(sb + SM_AP + (r - 16) * 16, make_uint4(pack_bf16(hm, hm), pack_bf16(hm, 0.f), 0u, 0u));
              }
            }
            fence_async_smem();
            __syncwarp();
            if (lane == 0) mbar_arrive(bar + B_STAT);
            PROFT(lane == 0, 64 + layer * 16 + 14);
            wo_w(__shfl_sync(0xffffffffu, layer, 0));
          }
        }
      }
    }
    __syncwarp();
    asm volatile("barrier.cluster.arrive.relaxed.aligned;\nbarrier.cluster.wait.aligned;\n" ::: "memory");
  } else {
    if (warp == 5) {
      if (lane == 0) {
        mbar_init(bar + B_FULLS, 1);
        asm volatile("fence.mbarrier_init.release.cluster;" ::: "memory");
      }
      __syncwarp();
      expect_tx_e(bar + B_FULLS, 65536);
      const int kc0 = (g || !K0V) ? 0 : 128;
      tma_2d_e(sb + XS * SLOT, &tm_x0, kc0, m0, bar + B_FULLS);
#pragma unroll
      for (int j = 0; j < 6; ++j)
        tma_2d_e(sb + (j < 4 ? j + 4 : j - 2) * 8192, &tm_wA, (j < 4 ? 1024 + (j >> 1) * 1024 : 0) + g * 128 + (j & 1) * 64, kc0, bar + B_FULLS);
      PROFT(lane == 0, 241);
    }
    if (lane < 8 && warp != 5 && threadIdx.x != 128) {
      const int i = (warp - 4) * 8 + lane;
      mbar_init(bar + i * 8, i < 32 ? 1u << ((BAR_CNT >> (2 * i)) & 3) : i < 48 ? 1u : (i == 59 || i == 60 || i == 62) ? 16u : (i == 48 || i == 63) ? 8u : 4u);
      asm volatile("fence.mbarrier_init.release.cluster;" ::: "memory");
    }
    __syncwarp();
    asm volatile("barrier.cluster.arrive.relaxed.aligned;" ::: "memory");
    asm volatile("setmaxnreg.inc.sync.aligned.u32 232;");
    cluster_wait();
    PROFT(threadIdx.x == 128, 0);
    Ctx c; c.sb = sb; c.g = g; c.rb = rb; c.cu = warp - 4; c.out = out;
    consumer(c);
    asm volatile("bar.warp.sync 0xffffffff;\nbarrier.cluster.arrive.relaxed.aligned;\nbarrier.cluster.wait.aligned;\n" ::: "memory");
  }
}

typedef CUresult (*PFN_encodeTiled)(CUtensorMap*, CUtensorMapDataType, cuuint32_t, void*, const cuuint64_t*, const cuuint64_t*,
                                    const cuuint32_t*, const cuuint32_t*, CUtensorMapInterleave, CUtensorMapSwizzle,
                                    CUtensorMapL2promotion, CUtensorMapFloatOOBfill);

static CUtensorMap make_map(PFN_encodeTiled enc, const void* ptr, uint64_t cols, uint64_t rows, uint32_t box_c, uint32_t box_r, uint32_t nb = 1) {
  CUtensorMap m;
  cuuint64_t dims[3] = {nb > 1 ? box_c : cols, rows, cols / box_c};
  cuuint64_t strides[2] = {cols * 2, box_c * 2};
  cuuint32_t box[3] = {box_c, box_r, nb};
  cuuint32_t es[3] = {1, 1, 1};
  CUresult r = enc(&m, CU_TENSOR_MAP_DATA_TYPE_BFLOAT16, nb > 1 ? 3 : 2, const_cast<void*>(ptr), dims, strides, box, es, CU_TENSOR_MAP_INTERLEAVE_NONE,
      CU_TENSOR_MAP_SWIZZLE_128B, CU_TENSOR_MAP_L2_PROMOTION_L2_256B, CU_TENSOR_MAP_FLOAT_OOB_FILL_NONE);
  (void)r;
  return m;
}

extern "C" void kernel_launch(void* const* d_in, const int* in_sizes, int n_in, void* d_out, int out_size) {
  const bf16* A_x = (const bf16*)d_in[0];
  const bf16* A_wqkv = (const bf16*)d_in[1];
  const bf16* A_wphi = (const bf16*)d_in[2];
  const bf16* A_wo = (const bf16*)d_in[3];
  const bf16* B_wqkv = (const bf16*)d_in[5];
  const bf16* B_wo = (const bf16*)d_in[6];
  bf16* out = (bf16*)d_out;

  static PFN_encodeTiled enc = nullptr;
  static bf16 *p_x, *p_o;
  static bool together;
  if (!enc) {
    void* fn = nullptr; cudaDriverEntryPointQueryResult qr;
    cudaGetDriverEntryPoint("cuTensorMapEncodeTiled", &fn, cudaEnableDefault, &qr);
    enc = (PFN_encodeTiled)fn;
    cudaGetSymbolAddress((void**)&p_x, g_x);
    cudaGetSymbolAddress((void**)&p_o, g_o);
    cudaFuncSetAttribute(mega_kernel, cudaFuncAttributeMaxDynamicSharedMemorySize, SM_TOTAL);
    cudaLaunchConfig_t cfg = {};
    cfg.gridDim = dim3(128 + NX); cfg.blockDim = dim3(384); cfg.dynamicSmemBytes = SM_TOTAL;
    cudaLaunchAttribute at[1];
    at[0].id = cudaLaunchAttributeClusterDimension; at[0].val.clusterDim.x = 2; at[0].val.clusterDim.y = 1; at[0].val.clusterDim.z = 1;
    cfg.attrs = at; cfg.numAttrs = 1;
    int ncl = 0;
    together = cudaOccupancyMaxActiveClusters(&ncl, mega_kernel, &cfg) == cudaSuccess && 2 * ncl == 128 + NX;
    int nsm = 0;
    cudaDeviceGetAttribute(&nsm, cudaDevAttrMultiProcessorCount, 0);
    together = together && nsm == 128 + NX;
  }
  CUtensorMap tm_x0 = make_map(enc, A_x, 1024, 2048, 64, 128);
  CUtensorMap tm_x = make_map(enc, p_x, 1024, 2048, 64, 128);
  CUtensorMap tm_o = make_map(enc, p_o, 1024, 2048, 64, 128);
  CUtensorMap tm_wA = make_map(enc, A_wqkv, 3072, 1024, 64, 64);
  CUtensorMap tm_wB = make_map(enc, B_wqkv, 3072, 1024, 64, 64);
  CUtensorMap tm_woA = make_map(enc, A_wo, 1024, 1024, 64, 64);
  CUtensorMap tm_woB = make_map(enc, B_wo, 1024, 1024, 64, 64);
  if (!together) mega_kernel<<<NX, 384, SM_TOTAL, cudaStreamPerThread>>>(tm_x0, tm_x, tm_o, tm_wA, tm_wB, tm_woA, tm_woB, B_wqkv, A_wphi, out);
  mega_kernel<<<together ? 128 + NX : 128, 384, SM_TOTAL, cudaStreamPerThread>>>(tm_x0, tm_x, tm_o, tm_wA, tm_wB, tm_woA, tm_woB,
                                                                                 B_wqkv, A_wphi, out);
}
```

```cpp
#include <cuda_runtime.h>
#include <cuda_bf16.h>
#include <cuda.h>
#include <stdint.h>

typedef __nv_bfloat16 bf16;

constexpr int S_ = 2048, D_ = 1024;

struct __align__(128) Flag { unsigned int v; unsigned int pad[31]; };
__device__ __align__(1024) bf16 g_x[S_ * D_];
__device__ __align__(1024) bf16 g_o[S_ * D_];
__device__ __align__(1024) uint4 g_halo[128 * 2 * 512];
__device__ __align__(1024) uint4 g_kv[8 * 2 * 2 * 1280];
__device__ __align__(1024) float2 g_stats[4 * S_];
__device__ __align__(1024) float g_cs[2 * 2 * 3072];
__device__ Flag g_csflag[16];
__device__ __align__(128) unsigned int g_xf[16 * 32], g_of[16 * 32];
__device__ unsigned int g_epoch, g_err;
#define PROFT(cond, idx) asm volatile("" ::: "memory")

__device__ __forceinline__ uint32_t smem_u32(const void* p) { return (uint32_t)__cvta_generic_to_shared(p); }
__device__ __forceinline__ void mbar_init(uint32_t bar, uint32_t count) {
  asm volatile("mbarrier.init.shared::cta.b64 [%0], %1;" ::"r"(bar), "r"(count) : "memory");
}
__device__ __forceinline__ void mbar_expect_tx(uint32_t bar, uint32_t bytes) {
  asm volatile("mbarrier.arrive.expect_tx.shared::cta.b64 _, [%0], %1;" ::"r"(bar), "r"(bytes) : "memory");
}
__device__ __forceinline__ void mbar_arrive(uint32_t bar) {
  asm volatile("mbarrier.arrive.shared::cta.b64 _, [%0];" ::"r"(bar) : "memory");
}
__device__ __forceinline__ bool mbar_try_wait(uint32_t bar, uint32_t parity) {
  uint32_t ok;
  asm volatile("{\n.reg .pred p;\nmbarrier.try_wait.parity.shared::cta.b64 p, [%1], %2;\nselp.b32 %0, 1, 0, p;\n}\n"
               : "=r"(ok) : "r"(bar), "r"(parity) : "memory");
  return ok != 0;
}
__device__ __forceinline__ bool mbar_test_wait(uint32_t bar, uint32_t parity) {
  uint32_t ok;
  asm volatile("{\n.reg .pred p;\nmbarrier.test_wait.parity.shared::cta.b64 p, [%1], %2;\nselp.b32 %0, 1, 0, p;\n}\n"
               : "=r"(ok) : "r"(bar), "r"(parity) : "memory");
  return ok != 0;
}
__device__ __forceinline__ uint64_t gtimer() {
  uint64_t t; asm volatile("mov.u64 %0, %globaltimer;" : "=l"(t)); return t;
}
__device__ __forceinline__ void mbar_wait(uint32_t bar, uint32_t parity) {
  uint32_t n = 0;
#pragma unroll 1
  while (!mbar_try_wait(bar, parity)) {
    if (++n > (1u << 22)) { g_err = 1u; break; }
  }
}
__device__ __forceinline__ unsigned int ld_acquire(const unsigned int* p) {
  unsigned int v; asm volatile("ld.acquire.gpu.global.u32 %0, [%1];" : "=r"(v) : "l"(p) : "memory"); return v;
}
__device__ __forceinline__ void flag_add(unsigned int* p) {
  asm volatile("red.release.gpu.global.add.u32 [%0], 1;" ::"l"(p) : "memory");
}
__device__ __forceinline__ void flag_set(unsigned int* p, unsigned int v) {
  asm volatile("st.release.gpu.global.u32 [%0], %1;" ::"l"(p), "r"(v) : "memory");
}
__device__ __forceinline__ void flag_hint(unsigned int* p, unsigned int v) {
  asm volatile("st.relaxed.gpu.global.u32 [%0], %1;" ::"l"(p), "r"(v) : "memory");
}
template <int SLEEP>
__device__ __forceinline__ void src_wait(const unsigned int* f, unsigned int target, uint32_t need, uint32_t& ready, int lane) {
  uint32_t n = 0;
#pragma unroll 1
  while ((ready & need) != need) {
    const unsigned int v = ld_acquire(f + (lane & 15));
    ready = __ballot_sync(0xffffffffu, (int)(v - target) >= 0);
    if (SLEEP) { if ((ready & need) != need) __nanosleep(SLEEP); }
    if (++n > (1u << 20)) { g_err = 3u; break; }
  }
  __syncwarp();
}
__device__ __forceinline__ unsigned int ld_relaxed(const unsigned int* p) {
  unsigned int v; asm volatile("ld.relaxed.gpu.global.u32 %0, [%1];" : "=r"(v) : "l"(p) : "memory"); return v;
}
__device__ __forceinline__ bool src_wait_tma(const unsigned int* f, unsigned int target, uint32_t need, uint32_t& ready, int lane, uint32_t eb, uint32_t par) {
  uint32_t n = 0;
  bool fr = false;
#pragma unroll 1
  while ((ready & need) != need) {
    const unsigned int v = ld_acquire(f + (lane & 15));
    fr = __all_sync(0xffffffffu, mbar_test_wait(eb, par));
    ready = __ballot_sync(0xffffffffu, (int)(v - target) >= 0);
    if (++n > (1u << 20)) { g_err = 3u; break; }
  }
  return fr;
}
__device__ __forceinline__ uint4 ld_relaxed4(const uint4* p) {
  uint4 v; asm volatile("ld.relaxed.gpu.global.v4.u32 {%0,%1,%2,%3}, [%4];" : "=r"(v.x), "=r"(v.y), "=r"(v.z), "=r"(v.w) : "l"(p) : "memory"); return v;
}
__device__ __forceinline__ void st_relaxed4(uint4* p, uint32_t a, uint32_t b, uint32_t c, uint32_t d) {
  asm volatile("st.relaxed.gpu.global.v4.u32 [%0], {%1,%2,%3,%4};" ::"l"(p), "r"(a), "r"(b), "r"(c), "r"(d) : "memory");
}
template <int SLEEP>
__device__ __forceinline__ void flag_wait_t(const unsigned int* p, unsigned int target) {
  uint32_t n = 0;
#pragma unroll 1
  while ((int)(ld_acquire(p) - target) < 0) {
    if (SLEEP) __nanosleep(SLEEP);
    if (++n > (1u << 20)) { g_err = 2u; break; }
  }
}
__device__ __forceinline__ void flag_wait(const unsigned int* p, unsigned int target) { flag_wait_t<0>(p, target); }
__device__ __forceinline__ void flag_wait_slow(const unsigned int* p, unsigned int target) { flag_wait_t<256>(p, target); }
__device__ __forceinline__ void tma_load_2d(uint32_t dst, const CUtensorMap* tm, int c0, int c1, uint32_t bar) {
  asm volatile("cp.async.bulk.tensor.2d.shared::cluster.global.mbarrier::complete_tx::bytes [%0], [%1, {%2, %3}], [%4];"
               ::"r"(dst), "l"(tm), "r"(c0), "r"(c1), "r"(bar) : "memory");
}
__device__ __forceinline__ void tma_load_2d_mc(uint32_t dst, const CUtensorMap* tm, int c0, int c1, uint32_t bar, uint16_t mask) {
  asm volatile("cp.async.bulk.tensor.2d.shared::cluster.global.mbarrier::complete_tx::bytes.multicast::cluster [%0], [%1, {%2, %3}], [%4], %5;"
               ::"r"(dst), "l"(tm), "r"(c0), "r"(c1), "r"(bar), "h"(mask) : "memory");
}
__device__ __forceinline__ void mbar_wait_u(uint32_t bar, uint32_t parity) {
  uint32_t n = 0;
#pragma unroll 1
  while (!__all_sync(0xffffffffu, mbar_try_wait(bar, parity))) {
    if (++n > (1u << 22)) { g_err = 1u; break; }
  }
}
__device__ __forceinline__ void expect_tx_e(uint32_t bar, uint32_t bytes) {
  asm volatile("{\n.reg .pred p;\nelect.sync _|p, 0xffffffff;\n@p mbarrier.arrive.expect_tx.shared::cta.b64 _, [%0], %1;\n}\n" ::"r"(bar), "r"(bytes) : "memory");
}
__device__ __forceinline__ void tma_2d_e(uint32_t dst, const CUtensorMap* tm, int c0, int c1, uint32_t bar) {
  asm volatile("{\n.reg .pred p;\nelect.sync _|p, 0xffffffff;\n"
               "@p cp.async.bulk.tensor.2d.shared::cluster.global.mbarrier::complete_tx::bytes [%0], [%1, {%2, %3}], [%4];\n}\n"
               ::"r"(dst), "l"(tm), "r"(c0), "r"(c1), "r"(bar) : "memory");
}
__device__ __forceinline__ void tma_2d_mc_e(uint32_t dst, const CUtensorMap* tm, int c0, int c1, uint32_t bar) {
  asm volatile("{\n.reg .pred p;\nelect.sync _|p, 0xffffffff;\n"
               "@p cp.async.bulk.tensor.2d.shared::cluster.global.mbarrier::complete_tx::bytes.multicast::cluster [%0], [%1, {%2, %3}], [%4], %5;\n}\n"
               ::"r"(dst), "l"(tm), "r"(c0), "r"(c1), "r"(bar), "h"((uint16_t)3) : "memory");
}
__device__ __forceinline__ void tma_pf_e(const CUtensorMap* tm, int c0, int c1) {
  asm volatile("{\n.reg .pred p;\nelect.sync _|p, 0xffffffff;\n"
               "@p cp.async.bulk.prefetch.tensor.2d.L2.global.tile [%0, {%1, %2}];\n}\n" ::"l"(tm), "r"(c0), "r"(c1) : "memory");
}
__device__ __forceinline__ void tma_2d_to_e(uint32_t dst, const CUtensorMap* tm, int c0, int c1, uint32_t bar, uint32_t mask) {
  asm volatile("{\n.reg .pred p;\nelect.sync _|p, 0xffffffff;\n"
               "@p cp.async.bulk.tensor.2d.shared::cluster.global.mbarrier::complete_tx::bytes.multicast::cluster [%0], [%1, {%2, %3}], [%4], %5;\n}\n"
               ::"r"(dst), "l"(tm), "r"(c0), "r"(c1), "r"(bar), "h"((uint16_t)mask) : "memory");
}
__device__ __forceinline__ void tma_3d_mc_e(uint32_t dst, const CUtensorMap* tm, int c1, int c2, uint32_t bar) {
  asm volatile("{\n.reg .pred p;\nelect.sync _|p, 0xffffffff;\n"
               "@p cp.async.bulk.tensor.3d.shared::cluster.global.mbarrier::complete_tx::bytes.multicast::cluster [%0], [%1, {%6, %2, %3}], [%4], %5;\n}\n"
               ::"r"(dst), "l"(tm), "r"(c1), "r"(c2), "r"(bar), "h"((uint16_t)3), "r"(0) : "memory");
}
__device__ __forceinline__ uint32_t poll_flags(const unsigned int* f, unsigned int target, int lane) {
  const unsigned int v = ld_acquire(f + (lane & 15));
  const uint32_t r = __ballot_sync(0xffffffffu, (int)(v - target) >= 0);
  __syncwarp();
  return r;
}
__device__ __forceinline__ void mbar_arrive_cluster(uint32_t local_bar, uint32_t rank) {
  asm volatile("{\n.reg .b32 ra;\nmapa.shared::cluster.u32 ra, %0, %1;\nmbarrier.arrive.shared::cluster.b64 _, [ra];\n}\n"
               ::"r"(local_bar), "r"(rank) : "memory");
}
__device__ __forceinline__ void release2(uint32_t bar) { mbar_arrive_cluster(bar, 0); mbar_arrive_cluster(bar, 1); }
__device__ __forceinline__ void tma_store_2d(const CUtensorMap* tm, uint32_t src, int c0, int c1) {
  asm volatile("cp.async.bulk.tensor.2d.global.shared::cta.bulk_group [%0, {%2, %3}], [%1];"
               ::"l"(tm), "r"(src), "r"(c0), "r"(c1) : "memory");
}
__device__ __forceinline__ void bulk_store(void* dst, uint32_t src, uint32_t bytes) {
  asm volatile("cp.async.bulk.global.shared::cta.bulk_group [%0], [%1], %2;" ::"l"(dst), "r"(src), "r"(bytes) : "memory");
}
__device__ __forceinline__ void bulk_load(uint32_t dst, const void* src, uint32_t bytes, uint32_t bar) {
  asm volatile("cp.async.bulk.shared::cluster.global.mbarrier::complete_tx::bytes [%0], [%1], %2, [%3];" ::"r"(dst), "l"(src), "r"(bytes), "r"(bar) : "memory");
}
__device__ __forceinline__ void bulk_red_add(void* dst, uint32_t src, uint32_t bytes) {
  asm volatile("cp.reduce.async.bulk.global.shared::cta.bulk_group.add.f32 [%0], [%1], %2;" ::"l"(dst), "r"(src), "r"(bytes) : "memory");
}
__device__ __forceinline__ void bulk_red_add_e(void* dst, uint32_t src, uint32_t bytes) {
  asm volatile("{\n.reg .pred p;\nelect.sync _|p, 0xffffffff;\n@p cp.reduce.async.bulk.global.shared::cta.bulk_group.add.f32 [%0], [%1], %2;\n}\n" ::"l"(dst), "r"(src), "r"(bytes) : "memory");
}
__device__ __forceinline__ void bulk_commit() { asm volatile("cp.async.bulk.commit_group;" ::: "memory"); }
__device__ __forceinline__ void bulk_wait_read0() { asm volatile("cp.async.bulk.wait_group.read 0;" ::: "memory"); }
__device__ __forceinline__ void bulk_wait0() { asm volatile("cp.async.bulk.wait_group 0;" ::: "memory"); }
__device__ __forceinline__ void fence_async_smem() { asm volatile("fence.proxy.async.shared::cta;" ::: "memory"); }
__device__ __forceinline__ void fence_async_all() { asm volatile("fence.proxy.async.global;" ::: "memory"); }
__device__ __forceinline__ void wgmma_fence() { asm volatile("wgmma.fence.sync.aligned;" ::: "memory"); }
__device__ __forceinline__ void wgmma_commit() { asm volatile("wgmma.commit_group.sync.aligned;" ::: "memory"); }
template <int N> __device__ __forceinline__ void wgmma_wait() { asm volatile("wgmma.wait_group.sync.aligned %0;" ::"n"(N) : "memory"); }
__device__ __forceinline__ void cluster_arrive() { asm volatile("barrier.cluster.arrive.release.aligned;" ::: "memory"); }
__device__ __forceinline__ void cluster_wait() { asm volatile("barrier.cluster.wait.acquire.aligned;" ::: "memory"); }
template <int ID, int N> __device__ __forceinline__ void nbar() { asm volatile("bar.sync %0, %1;" ::"n"(ID), "n"(N) : "memory"); }
__device__ __forceinline__ uint64_t make_desc(uint32_t addr, uint32_t lbo_bytes, uint32_t sbo_bytes) {
  uint64_t d = 0;
  d |= (uint64_t)((addr & 0x3FFFF) >> 4);
  d |= (uint64_t)((lbo_bytes >> 4) & 0x3FFF) << 16;
  d |= (uint64_t)((sbo_bytes >> 4) & 0x3FFF) << 32;
  d |= (uint64_t)1 << 62;
  return d;
}
__device__ __forceinline__ uint64_t desc64(uint32_t lo, uint32_t hi) { return (uint64_t)lo | ((uint64_t)hi << 32); }
__device__ __forceinline__ uint32_t pack_bf16(float lo, float hi) {
  uint32_t r; asm("cvt.rn.bf16x2.f32 %0, %1, %2;" : "=r"(r) : "f"(hi), "f"(lo)); return r;
}
__device__ __forceinline__ uint32_t mul_bf16x2(uint32_t a, uint32_t s, bool hi) {
  __nv_bfloat162 x = *reinterpret_cast<__nv_bfloat162*>(&a), y = *reinterpret_cast<__nv_bfloat162*>(&s);
  x = __hmul2(x, hi ? __high2bfloat162(y) : __low2bfloat162(y));
  return *reinterpret_cast<uint32_t*>(&x);
}
__device__ __forceinline__ float bf16r(float x) { return __bfloat162float(__float2bfloat16_rn(x)); }
__device__ __forceinline__ float bf_lo(uint32_t u) { return __uint_as_float(u << 16); }
__device__ __forceinline__ float bf_hi(uint32_t u) { return __uint_as_float(u & 0xFFFF0000u); }
__device__ __forceinline__ float ex2(float x) { float r; asm("ex2.approx.ftz.f32 %0, %1;" : "=f"(r) : "f"(x)); return r; }
__device__ __forceinline__ float rcp(float x) { float r; asm("rcp.approx.ftz.f32 %0, %1;" : "=f"(r) : "f"(x)); return r; }
__device__ __forceinline__ void mma_bf16(float (&d)[4], uint32_t a0, uint32_t a1, uint32_t a2, uint32_t a3, uint32_t b0, uint32_t b1) {
  asm("mma.sync.aligned.m16n8k16.row.col.f32.bf16.bf16.f32 {%0,%1,%2,%3}, {%4,%5,%6,%7}, {%8,%9}, {%0,%1,%2,%3};"
               : "+f"(d[0]), "+f"(d[1]), "+f"(d[2]), "+f"(d[3]) : "r"(a0), "r"(a1), "r"(a2), "r"(a3), "r"(b0), "r"(b1));
}
__device__ __forceinline__ void ldsm_x4(uint32_t& r0, uint32_t& r1, uint32_t& r2, uint32_t& r3, uint32_t addr) {
  asm volatile("ldmatrix.sync.aligned.m8n8.x4.shared.b16 {%0,%1,%2,%3}, [%4];"
               : "=r"(r0), "=r"(r1), "=r"(r2), "=r"(r3) : "r"(addr) : "memory");
}
__device__ __forceinline__ void ldsm_x4_t(uint32_t& r0, uint32_t& r1, uint32_t& r2, uint32_t& r3, uint32_t addr) {
  asm volatile("ldmatrix.sync.aligned.m8n8.x4.trans.shared.b16 {%0,%1,%2,%3}, [%4];"
               : "=r"(r0), "=r"(r1), "=r"(r2), "=r"(r3) : "r"(addr) : "memory");
}
__device__ __forceinline__ void ldsm_x2_t(uint32_t& r0, uint32_t& r1, uint32_t addr) {
  asm volatile("ldmatrix.sync.aligned.m8n8.x2.trans.shared.b16 {%0,%1}, [%2];"
               : "=r"(r0), "=r"(r1) : "r"(addr) : "memory");
}
__device__ __forceinline__ void stsm_x4(uint32_t addr, uint32_t r0, uint32_t r1, uint32_t r2, uint32_t r3) {
  asm volatile("stmatrix.sync.aligned.m8n8.x4.shared.b16 [%0], {%1,%2,%3,%4};"
               ::"r"(addr), "r"(r0), "r"(r1), "r"(r2), "r"(r3) : "memory");
}
__device__ __forceinline__ void stsm_x4_p(bool on, uint32_t addr, uint32_t r0, uint32_t r1, uint32_t r2, uint32_t r3) {
  asm volatile("{\n.reg .pred p;\nsetp.ne.b32 p, %5, 0;\n@p stmatrix.sync.aligned.m8n8.x4.shared.b16 [%0], {%1,%2,%3,%4};\n}\n"
               ::"r"(addr), "r"(r0), "r"(r1), "r"(r2), "r"(r3), "r"((int)on) : "memory");
}
__device__ __forceinline__ float2 lds_f2(uint32_t addr) {
  float2 v; asm volatile("ld.shared.v2.f32 {%0,%1}, [%2];" : "=f"(v.x), "=f"(v.y) : "r"(addr) : "memory"); return v;
}
__device__ __forceinline__ uint4 lds128(uint32_t addr) {
  uint4 v; asm volatile("ld.shared.v4.b32 {%0,%1,%2,%3}, [%4];" : "=r"(v.x), "=r"(v.y), "=r"(v.z), "=r"(v.w) : "r"(addr) : "memory"); return v;
}
__device__ __forceinline__ void sts128(uint32_t addr, uint4 v) {
  asm volatile("st.shared.v4.b32 [%0], {%1,%2,%3,%4};" ::"r"(addr), "r"(v.x), "r"(v.y), "r"(v.z), "r"(v.w) : "memory");
}
__device__ __forceinline__ float lds_f(uint32_t addr) {
  float v; asm volatile("ld.shared.f32 %0, [%1];" : "=f"(v) : "r"(addr) : "memory"); return v;
}
__device__ __forceinline__ uint32_t lds_vol(uint32_t addr) {
  uint32_t v; asm volatile("ld.volatile.shared.u32 %0, [%1];" : "=r"(v) : "r"(addr) : "memory"); return v;
}
__device__ __forceinline__ void sts16(uint32_t addr, uint32_t v) {
  asm volatile("st.shared.u16 [%0], %1;" ::"r"(addr), "h"((unsigned short)v) : "memory");
}
__device__ __forceinline__ void nbar_dyn(int id, int n) { asm volatile("bar.sync %0, %1;" ::"r"(id), "r"(n) : "memory"); }
__device__ __forceinline__ uint64_t make_desc_ns(uint32_t addr, uint32_t lbo_bytes, uint32_t sbo_bytes) {
  return (uint64_t)((addr & 0x3FFFF) >> 4) | ((uint64_t)(lbo_bytes >> 4) << 16) | ((uint64_t)(sbo_bytes >> 4) << 32);
}
__device__ __forceinline__ void sts_f(uint32_t addr, float v) { asm volatile("st.shared.f32 [%0], %1;" ::"r"(addr), "f"(v) : "memory"); }
__device__ __forceinline__ void sts64(uint32_t addr, uint32_t a, uint32_t b) {
  asm volatile("st.shared.v2.b32 [%0], {%1,%2};" ::"r"(addr), "r"(a), "r"(b) : "memory");
}
__device__ __forceinline__ void sts_f2(uint32_t addr, float a, float b) {
  asm volatile("st.shared.v2.f32 [%0], {%1,%2};" ::"r"(addr), "f"(a), "f"(b) : "memory");
}
__device__ __forceinline__ void red_add2(float* p, float a, float b) {
  asm volatile("red.global.add.v2.f32 [%0], {%1,%2};" ::"l"(p), "f"(a), "f"(b) : "memory");
}
__device__ __forceinline__ void red_add4(float* p, float a, float b, float c, float d) {
  asm volatile("red.global.add.v4.f32 [%0], {%1,%2,%3,%4};" ::"l"(p), "f"(a), "f"(b), "f"(c), "f"(d) : "memory");
}
__device__ __forceinline__ void red_add1(float* p, float a) {
  asm volatile("red.global.add.f32 [%0], %1;" ::"l"(p), "f"(a) : "memory");
}
__device__ __forceinline__ void l2_prefetch(const void* p, uint32_t bytes) {
  asm volatile("cp.async.bulk.prefetch.L2.global [%0], %1;" ::"l"(p), "r"(bytes) : "memory");
}

__device__ __forceinline__ void wgmma_n256(float (&d)[192], uint64_t da, uint64_t db, int scale_d) {
  asm volatile("{\n.reg .pred p;\nsetp.ne.b32 p, %130, 0;\n"
    "wgmma.mma_async.sync.aligned.m64n256k16.f32.bf16.bf16 {%0, %1, %2, %3, %4, %5, %6, %7, %8, %9, %10, %11, %12, %13, %14, %15, %16, %17, %18, %19, %20, %21, %22, %23, %24, %25, %26, %27, %28, %29, %30, %31, %32, %33, %34, %35, %36, %37, %38, %39, %40, %41, %42, %43, %44, %45, %46, %47, %48, %49, %50, %51, %52, %53, %54, %55, %56, %57, %58, %59, %60, %61, %62, %63, %64, %65, %66, %67, %68, %69, %70, %71, %72, %73, %74, %75, %76, %77, %78, %79, %80, %81, %82, %83, %84, %85, %86, %87, %88, %89, %90, %91, %92, %93, %94, %95, %96, %97, %98, %99, %100, %101, %102, %103, %104, %105, %106, %107, %108, %109, %110, %111, %112, %113, %114, %115, %116, %117, %118, %119, %120, %121, %122, %123, %124, %125, %126, %127}, %128, %129, p, 1, 1, 0, 1;\n}\n"
    : "+f"(d[0]), "+f"(d[1]), "+f"(d[2]), "+f"(d[3]), "+f"(d[4]), "+f"(d[5]), "+f"(d[6]), "+f"(d[7]), "+f"(d[8]), "+f"(d[9]), "+f"(d[10]), "+f"(d[11]), "+f"(d[12]), "+f"(d[13]), "+f"(d[14]), "+f"(d[15]), "+f"(d[16]), "+f"(d[17]), "+f"(d[18]), "+f"(d[19]), "+f"(d[20]), "+f"(d[21]), "+f"(d[22]), "+f"(d[23]), "+f"(d[24]), "+f"(d[25]), "+f"(d[26]), "+f"(d[27]), "+f"(d[28]), "+f"(d[29]), "+f"(d[30]), "+f"(d[31]), "+f"(d[32]), "+f"(d[33]), "+f"(d[34]), "+f"(d[35]), "+f"(d[36]), "+f"(d[37]), "+f"(d[38]), "+f"(d[39]), "+f"(d[40]), "+f"(d[41]), "+f"(d[42]), "+f"(d[43]), "+f"(d[44]), "+f"(d[45]), "+f"(d[46]), "+f"(d[47]), "+f"(d[48]), "+f"(d[49]), "+f"(d[50]), "+f"(d[51]), "+f"(d[52]), "+f"(d[53]), "+f"(d[54]), "+f"(d[55]), "+f"(d[56]), "+f"(d[57]), "+f"(d[58]), "+f"(d[59]), "+f"(d[60]), "+f"(d[61]), "+f"(d[62]), "+f"(d[63]), "+f"(d[64]), "+f"(d[65]), "+f"(d[66]), "+f"(d[67]), "+f"(d[68]), "+f"(d[69]), "+f"(d[70]), "+f"(d[71]), "+f"(d[72]), "+f"(d[73]), "+f"(d[74]), "+f"(d[75]), "+f"(d[76]), "+f"(d[77]), "+f"(d[78]), "+f"(d[79]), "+f"(d[80]), "+f"(d[81]), "+f"(d[82]), "+f"(d[83]), "+f"(d[84]), "+f"(d[85]), "+f"(d[86]), "+f"(d[87]), "+f"(d[88]), "+f"(d[89]), "+f"(d[90]), "+f"(d[91]), "+f"(d[92]), "+f"(d[93]), "+f"(d[94]), "+f"(d[95]), "+f"(d[96]), "+f"(d[97]), "+f"(d[98]), "+f"(d[99]), "+f"(d[100]), "+f"(d[101]), "+f"(d[102]), "+f"(d[103]), "+f"(d[104]), "+f"(d[105]), "+f"(d[106]), "+f"(d[107]), "+f"(d[108]), "+f"(d[109]), "+f"(d[110]), "+f"(d[111]), "+f"(d[112]), "+f"(d[113]), "+f"(d[114]), "+f"(d[115]), "+f"(d[116]), "+f"(d[117]), "+f"(d[118]), "+f"(d[119]), "+f"(d[120]), "+f"(d[121]), "+f"(d[122]), "+f"(d[123]), "+f"(d[124]), "+f"(d[125]), "+f"(d[126]), "+f"(d[127])
    : "l"(da), "l"(db), "r"(scale_d));
}
__device__ __forceinline__ void wgmma_n128(float (&d)[192], uint64_t da, uint64_t db, int scale_d) {
  asm volatile("{\n.reg .pred p;\nsetp.ne.b32 p, %66, 0;\n"
    "wgmma.mma_async.sync.aligned.m64n128k16.f32.bf16.bf16 {%0, %1, %2, %3, %4, %5, %6, %7, %8, %9, %10, %11, %12, %13, %14, %15, %16, %17, %18, %19, %20, %21, %22, %23, %24, %25, %26, %27, %28, %29, %30, %31, %32, %33, %34, %35, %36, %37, %38, %39, %40, %41, %42, %43, %44, %45, %46, %47, %48, %49, %50, %51, %52, %53, %54, %55, %56, %57, %58, %59, %60, %61, %62, %63}, %64, %65, p, 1, 1, 0, 1;\n}\n"
    : "+f"(d[128]), "+f"(d[129]), "+f"(d[130]), "+f"(d[131]), "+f"(d[132]), "+f"(d[133]), "+f"(d[134]), "+f"(d[135]), "+f"(d[136]), "+f"(d[137]), "+f"(d[138]), "+f"(d[139]), "+f"(d[140]), "+f"(d[141]), "+f"(d[142]), "+f"(d[143]), "+f"(d[144]), "+f"(d[145]), "+f"(d[146]), "+f"(d[147]), "+f"(d[148]), "+f"(d[149]), "+f"(d[150]), "+f"(d[151]), "+f"(d[152]), "+f"(d[153]), "+f"(d[154]), "+f"(d[155]), "+f"(d[156]), "+f"(d[157]), "+f"(d[158]), "+f"(d[159]), "+f"(d[160]), "+f"(d[161]), "+f"(d[162]), "+f"(d[163]), "+f"(d[164]), "+f"(d[165]), "+f"(d[166]), "+f"(d[167]), "+f"(d[168]), "+f"(d[169]), "+f"(d[170]), "+f"(d[171]), "+f"(d[172]), "+f"(d[173]), "+f"(d[174]), "+f"(d[175]), "+f"(d[176]), "+f"(d[177]), "+f"(d[178]), "+f"(d[179]), "+f"(d[180]), "+f"(d[181]), "+f"(d[182]), "+f"(d[183]), "+f"(d[184]), "+f"(d[185]), "+f"(d[186]), "+f"(d[187]), "+f"(d[188]), "+f"(d[189]), "+f"(d[190]), "+f"(d[191])
    : "l"(da), "l"(db), "r"(scale_d));
}
__device__ __forceinline__ void wgmma_n256_k(float (&d)[192], uint64_t da, uint64_t db, int scale_d) {
  asm volatile("{\n.reg .pred p;\nsetp.ne.b32 p, %130, 0;\n"
    "wgmma.mma_async.sync.aligned.m64n256k16.f32.bf16.bf16 {%0, %1, %2, %3, %4, %5, %6, %7, %8, %9, %10, %11, %12, %13, %14, %15, %16, %17, %18, %19, %20, %21, %22, %23, %24, %25, %26, %27, %28, %29, %30, %31, %32, %33, %34, %35, %36, %37, %38, %39, %40, %41, %42, %43, %44, %45, %46, %47, %48, %49, %50, %51, %52, %53, %54, %55, %56, %57, %58, %59, %60, %61, %62, %63, %64, %65, %66, %67, %68, %69, %70, %71, %72, %73, %74, %75, %76, %77, %78, %79, %80, %81, %82, %83, %84, %85, %86, %87, %88, %89, %90, %91, %92, %93, %94, %95, %96, %97, %98, %99, %100, %101, %102, %103, %104, %105, %106, %107, %108, %109, %110, %111, %112, %113, %114, %115, %116, %117, %118, %119, %120, %121, %122, %123, %124, %125, %126, %127}, %128, %129, p, 1, 1, 0, 0;\n}\n"
    : "+f"(d[0]), "+f"(d[1]), "+f"(d[2]), "+f"(d[3]), "+f"(d[4]), "+f"(d[5]), "+f"(d[6]), "+f"(d[7]), "+f"(d[8]), "+f"(d[9]), "+f"(d[10]), "+f"(d[11]), "+f"(d[12]), "+f"(d[13]), "+f"(d[14]), "+f"(d[15]), "+f"(d[16]), "+f"(d[17]), "+f"(d[18]), "+f"(d[19]), "+f"(d[20]), "+f"(d[21]), "+f"(d[22]), "+f"(d[23]), "+f"(d[24]), "+f"(d[25]), "+f"(d[26]), "+f"(d[27]), "+f"(d[28]), "+f"(d[29]), "+f"(d[30]), "+f"(d[31]), "+f"(d[32]), "+f"(d[33]), "+f"(d[34]), "+f"(d[35]), "+f"(d[36]), "+f"(d[37]), "+f"(d[38]), "+f"(d[39]), "+f"(d[40]), "+f"(d[41]), "+f"(d[42]), "+f"(d[43]), "+f"(d[44]), "+f"(d[45]), "+f"(d[46]), "+f"(d[47]), "+f"(d[48]), "+f"(d[49]), "+f"(d[50]), "+f"(d[51]), "+f"(d[52]), "+f"(d[53]), "+f"(d[54]), "+f"(d[55]), "+f"(d[56]), "+f"(d[57]), "+f"(d[58]), "+f"(d[59]), "+f"(d[60]), "+f"(d[61]), "+f"(d[62]), "+f"(d[63]), "+f"(d[64]), "+f"(d[65]), "+f"(d[66]), "+f"(d[67]), "+f"(d[68]), "+f"(d[69]), "+f"(d[70]), "+f"(d[71]), "+f"(d[72]), "+f"(d[73]), "+f"(d[74]), "+f"(d[75]), "+f"(d[76]), "+f"(d[77]), "+f"(d[78]), "+f"(d[79]), "+f"(d[80]), "+f"(d[81]), "+f"(d[82]), "+f"(d[83]), "+f"(d[84]), "+f"(d[85]), "+f"(d[86]), "+f"(d[87]), "+f"(d[88]), "+f"(d[89]), "+f"(d[90]), "+f"(d[91]), "+f"(d[92]), "+f"(d[93]), "+f"(d[94]), "+f"(d[95]), "+f"(d[96]), "+f"(d[97]), "+f"(d[98]), "+f"(d[99]), "+f"(d[100]), "+f"(d[101]), "+f"(d[102]), "+f"(d[103]), "+f"(d[104]), "+f"(d[105]), "+f"(d[106]), "+f"(d[107]), "+f"(d[108]), "+f"(d[109]), "+f"(d[110]), "+f"(d[111]), "+f"(d[112]), "+f"(d[113]), "+f"(d[114]), "+f"(d[115]), "+f"(d[116]), "+f"(d[117]), "+f"(d[118]), "+f"(d[119]), "+f"(d[120]), "+f"(d[121]), "+f"(d[122]), "+f"(d[123]), "+f"(d[124]), "+f"(d[125]), "+f"(d[126]), "+f"(d[127])
    : "l"(da), "l"(db), "r"(scale_d));
}
__device__ __forceinline__ void wgmma_n128_k(float (&d)[192], uint64_t da, uint64_t db, int scale_d) {
  asm volatile("{\n.reg .pred p;\nsetp.ne.b32 p, %66, 0;\n"
    "wgmma.mma_async.sync.aligned.m64n128k16.f32.bf16.bf16 {%0, %1, %2, %3, %4, %5, %6, %7, %8, %9, %10, %11, %12, %13, %14, %15, %16, %17, %18, %19, %20, %21, %22, %23, %24, %25, %26, %27, %28, %29, %30, %31, %32, %33, %34, %35, %36, %37, %38, %39, %40, %41, %42, %43, %44, %45, %46, %47, %48, %49, %50, %51, %52, %53, %54, %55, %56, %57, %58, %59, %60, %61, %62, %63}, %64, %65, p, 1, 1, 0, 0;\n}\n"
    : "+f"(d[128]), "+f"(d[129]), "+f"(d[130]), "+f"(d[131]), "+f"(d[132]), "+f"(d[133]), "+f"(d[134]), "+f"(d[135]), "+f"(d[136]), "+f"(d[137]), "+f"(d[138]), "+f"(d[139]), "+f"(d[140]), "+f"(d[141]), "+f"(d[142]), "+f"(d[143]), "+f"(d[144]), "+f"(d[145]), "+f"(d[146]), "+f"(d[147]), "+f"(d[148]), "+f"(d[149]), "+f"(d[150]), "+f"(d[151]), "+f"(d[152]), "+f"(d[153]), "+f"(d[154]), "+f"(d[155]), "+f"(d[156]), "+f"(d[157]), "+f"(d[158]), "+f"(d[159]), "+f"(d[160]), "+f"(d[161]), "+f"(d[162]), "+f"(d[163]), "+f"(d[164]), "+f"(d[165]), "+f"(d[166]), "+f"(d[167]), "+f"(d[168]), "+f"(d[169]), "+f"(d[170]), "+f"(d[171]), "+f"(d[172]), "+f"(d[173]), "+f"(d[174]), "+f"(d[175]), "+f"(d[176]), "+f"(d[177]), "+f"(d[178]), "+f"(d[179]), "+f"(d[180]), "+f"(d[181]), "+f"(d[182]), "+f"(d[183]), "+f"(d[184]), "+f"(d[185]), "+f"(d[186]), "+f"(d[187]), "+f"(d[188]), "+f"(d[189]), "+f"(d[190]), "+f"(d[191])
    : "l"(da), "l"(db), "r"(scale_d));
}
__device__ __forceinline__ void wgmma_n40_tt(float (&d)[20], uint64_t da, uint64_t db, int scale_d) {
  asm volatile("{\n.reg .pred p;\nsetp.ne.b32 p, %22, 0;\n"
    "wgmma.mma_async.sync.aligned.m64n40k16.f32.bf16.bf16 {%0, %1, %2, %3, %4, %5, %6, %7, %8, %9, %10, %11, %12, %13, %14, %15, %16, %17, %18, %19}, %20, %21, p, 1, 1, 1, 1;\n}\n"
    : "+f"(d[0]), "+f"(d[1]), "+f"(d[2]), "+f"(d[3]), "+f"(d[4]), "+f"(d[5]), "+f"(d[6]), "+f"(d[7]), "+f"(d[8]), "+f"(d[9]), "+f"(d[10]), "+f"(d[11]), "+f"(d[12]), "+f"(d[13]), "+f"(d[14]), "+f"(d[15]), "+f"(d[16]), "+f"(d[17]), "+f"(d[18]), "+f"(d[19])
    : "l"(da), "l"(db), "r"(scale_d));
}
__device__ __forceinline__ void wgmma_n40_rs(float (&d)[20], const uint32_t (&a)[4], uint64_t db, int scale_d) {
  asm volatile("{\n.reg .pred p;\nsetp.ne.b32 p, %25, 0;\n"
    "wgmma.mma_async.sync.aligned.m64n40k16.f32.bf16.bf16 {%0, %1, %2, %3, %4, %5, %6, %7, %8, %9, %10, %11, %12, %13, %14, %15, %16, %17, %18, %19}, {%20, %21, %22, %23}, %24, p, 1, 1, 1;\n}\n"
    : "+f"(d[0]), "+f"(d[1]), "+f"(d[2]), "+f"(d[3]), "+f"(d[4]), "+f"(d[5]), "+f"(d[6]), "+f"(d[7]), "+f"(d[8]), "+f"(d[9]), "+f"(d[10]), "+f"(d[11]), "+f"(d[12]), "+f"(d[13]), "+f"(d[14]), "+f"(d[15]), "+f"(d[16]), "+f"(d[17]), "+f"(d[18]), "+f"(d[19])
    : "r"(a[0]), "r"(a[1]), "r"(a[2]), "r"(a[3]), "l"(db), "r"(scale_d));
}
__device__ __forceinline__ void wgmma_n256_0(float (&d)[192], uint64_t da, uint64_t db) {
  asm volatile("{\n.reg .pred p;\nsetp.ne.b32 p, 0, 0;\n"
    "wgmma.mma_async.sync.aligned.m64n256k16.f32.bf16.bf16 {%0, %1, %2, %3, %4, %5, %6, %7, %8, %9, %10, %11, %12, %13, %14, %15, %16, %17, %18, %19, %20, %21, %22, %23, %24, %25, %26, %27, %28, %29, %30, %31, %32, %33, %34, %35, %36, %37, %38, %39, %40, %41, %42, %43, %44, %45, %46, %47, %48, %49, %50, %51, %52, %53, %54, %55, %56, %57, %58, %59, %60, %61, %62, %63, %64, %65, %66, %67, %68, %69, %70, %71, %72, %73, %74, %75, %76, %77, %78, %79, %80, %81, %82, %83, %84, %85, %86, %87, %88, %89, %90, %91, %92, %93, %94, %95, %96, %97, %98, %99, %100, %101, %102, %103, %104, %105, %106, %107, %108, %109, %110, %111, %112, %113, %114, %115, %116, %117, %118, %119, %120, %121, %122, %123, %124, %125, %126, %127}, %128, %129, p, 1, 1, 0, 1;\n}\n"
    : "=f"(d[0]), "=f"(d[1]), "=f"(d[2]), "=f"(d[3]), "=f"(d[4]), "=f"(d[5]), "=f"(d[6]), "=f"(d[7]), "=f"(d[8]), "=f"(d[9]), "=f"(d[10]), "=f"(d[11]), "=f"(d[12]), "=f"(d[13]), "=f"(d[14]), "=f"(d[15]), "=f"(d[16]), "=f"(d[17]), "=f"(d[18]), "=f"(d[19]), "=f"(d[20]), "=f"(d[21]), "=f"(d[22]), "=f"(d[23]), "=f"(d[24]), "=f"(d[25]), "=f"(d[26]), "=f"(d[27]), "=f"(d[28]), "=f"(d[29]), "=f"(d[30]), "=f"(d[31]), "=f"(d[32]), "=f"(d[33]), "=f"(d[34]), "=f"(d[35]), "=f"(d[36]), "=f"(d[37]), "=f"(d[38]), "=f"(d[39]), "=f"(d[40]), "=f"(d[41]), "=f"(d[42]), "=f"(d[43]), "=f"(d[44]), "=f"(d[45]), "=f"(d[46]), "=f"(d[47]), "=f"(d[48]), "=f"(d[49]), "=f"(d[50]), "=f"(d[51]), "=f"(d[52]), "=f"(d[53]), "=f"(d[54]), "=f"(d[55]), "=f"(d[56]), "=f"(d[57]), "=f"(d[58]), "=f"(d[59]), "=f"(d[60]), "=f"(d[61]), "=f"(d[62]), "=f"(d[63]), "=f"(d[64]), "=f"(d[65]), "=f"(d[66]), "=f"(d[67]), "=f"(d[68]), "=f"(d[69]), "=f"(d[70]), "=f"(d[71]), "=f"(d[72]), "=f"(d[73]), "=f"(d[74]), "=f"(d[75]), "=f"(d[76]), "=f"(d[77]), "=f"(d[78]), "=f"(d[79]), "=f"(d[80]), "=f"(d[81]), "=f"(d[82]), "=f"(d[83]), "=f"(d[84]), "=f"(d[85]), "=f"(d[86]), "=f"(d[87]), "=f"(d[88]), "=f"(d[89]), "=f"(d[90]), "=f"(d[91]), "=f"(d[92]), "=f"(d[93]), "=f"(d[94]), "=f"(d[95]), "=f"(d[96]), "=f"(d[97]), "=f"(d[98]), "=f"(d[99]), "=f"(d[100]), "=f"(d[101]), "=f"(d[102]), "=f"(d[103]), "=f"(d[104]), "=f"(d[105]), "=f"(d[106]), "=f"(d[107]), "=f"(d[108]), "=f"(d[109]), "=f"(d[110]), "=f"(d[111]), "=f"(d[112]), "=f"(d[113]), "=f"(d[114]), "=f"(d[115]), "=f"(d[116]), "=f"(d[117]), "=f"(d[118]), "=f"(d[119]), "=f"(d[120]), "=f"(d[121]), "=f"(d[122]), "=f"(d[123]), "=f"(d[124]), "=f"(d[125]), "=f"(d[126]), "=f"(d[127])
    : "l"(da), "l"(db));
}
__device__ __forceinline__ void wgmma_n128_0(float (&d)[192], uint64_t da, uint64_t db) {
  asm volatile("{\n.reg .pred p;\nsetp.ne.b32 p, 0, 0;\n"
    "wgmma.mma_async.sync.aligned.m64n128k16.f32.bf16.bf16 {%0, %1, %2, %3, %4, %5, %6, %7, %8, %9, %10, %11, %12, %13, %14, %15, %16, %17, %18, %19, %20, %21, %22, %23, %24, %25, %26, %27, %28, %29, %30, %31, %32, %33, %34, %35, %36, %37, %38, %39, %40, %41, %42, %43, %44, %45, %46, %47, %48, %49, %50, %51, %52, %53, %54, %55, %56, %57, %58, %59, %60, %61, %62, %63}, %64, %65, p, 1, 1, 0, 1;\n}\n"
    : "=f"(d[128]), "=f"(d[129]), "=f"(d[130]), "=f"(d[131]), "=f"(d[132]), "=f"(d[133]), "=f"(d[134]), "=f"(d[135]), "=f"(d[136]), "=f"(d[137]), "=f"(d[138]), "=f"(d[139]), "=f"(d[140]), "=f"(d[141]), "=f"(d[142]), "=f"(d[143]), "=f"(d[144]), "=f"(d[145]), "=f"(d[146]), "=f"(d[147]), "=f"(d[148]), "=f"(d[149]), "=f"(d[150]), "=f"(d[151]), "=f"(d[152]), "=f"(d[153]), "=f"(d[154]), "=f"(d[155]), "=f"(d[156]), "=f"(d[157]), "=f"(d[158]), "=f"(d[159]), "=f"(d[160]), "=f"(d[161]), "=f"(d[162]), "=f"(d[163]), "=f"(d[164]), "=f"(d[165]), "=f"(d[166]), "=f"(d[167]), "=f"(d[168]), "=f"(d[169]), "=f"(d[170]), "=f"(d[171]), "=f"(d[172]), "=f"(d[173]), "=f"(d[174]), "=f"(d[175]), "=f"(d[176]), "=f"(d[177]), "=f"(d[178]), "=f"(d[179]), "=f"(d[180]), "=f"(d[181]), "=f"(d[182]), "=f"(d[183]), "=f"(d[184]), "=f"(d[185]), "=f"(d[186]), "=f"(d[187]), "=f"(d[188]), "=f"(d[189]), "=f"(d[190]), "=f"(d[191])
    : "l"(da), "l"(db));
}
__device__ __forceinline__ void wgmma_n128_rs(float (&d)[192], const uint32_t (&a)[4], uint64_t db, int scale_d) {
  asm volatile("{\n.reg .pred p;\nsetp.ne.b32 p, %69, 0;\n"
    "wgmma.mma_async.sync.aligned.m64n128k16.f32.bf16.bf16 {%0, %1, %2, %3, %4, %5, %6, %7, %8, %9, %10, %11, %12, %13, %14, %15, %16, %17, %18, %19, %20, %21, %22, %23, %24, %25, %26, %27, %28, %29, %30, %31, %32, %33, %34, %35, %36, %37, %38, %39, %40, %41, %42, %43, %44, %45, %46, %47, %48, %49, %50, %51, %52, %53, %54, %55, %56, %57, %58, %59, %60, %61, %62, %63}, {%64, %65, %66, %67}, %68, p, 1, 1, 1;\n}\n"
    : "+f"(d[128]), "+f"(d[129]), "+f"(d[130]), "+f"(d[131]), "+f"(d[132]), "+f"(d[133]), "+f"(d[134]), "+f"(d[135]), "+f"(d[136]), "+f"(d[137]), "+f"(d[138]), "+f"(d[139]), "+f"(d[140]), "+f"(d[141]), "+f"(d[142]), "+f"(d[143]), "+f"(d[144]), "+f"(d[145]), "+f"(d[146]), "+f"(d[147]), "+f"(d[148]), "+f"(d[149]), "+f"(d[150]), "+f"(d[151]), "+f"(d[152]), "+f"(d[153]), "+f"(d[154]), "+f"(d[155]), "+f"(d[156]), "+f"(d[157]), "+f"(d[158]), "+f"(d[159]), "+f"(d[160]), "+f"(d[161]), "+f"(d[162]), "+f"(d[163]), "+f"(d[164]), "+f"(d[165]), "+f"(d[166]), "+f"(d[167]), "+f"(d[168]), "+f"(d[169]), "+f"(d[170]), "+f"(d[171]), "+f"(d[172]), "+f"(d[173]), "+f"(d[174]), "+f"(d[175]), "+f"(d[176]), "+f"(d[177]), "+f"(d[178]), "+f"(d[179]), "+f"(d[180]), "+f"(d[181]), "+f"(d[182]), "+f"(d[183]), "+f"(d[184]), "+f"(d[185]), "+f"(d[186]), "+f"(d[187]), "+f"(d[188]), "+f"(d[189]), "+f"(d[190]), "+f"(d[191])
    : "r"(a[0]), "r"(a[1]), "r"(a[2]), "r"(a[3]), "l"(db), "r"(scale_d));
}

constexpr int SLOT = 16384;
constexpr int KVT = 10240;
constexpr uint32_t QA = 0x0BAu, QK = 0x462u, QQ = 0x981u;
constexpr int SM_SD = 12 * SLOT;
constexpr int SM_BAR = SM_SD + 8192;
constexpr int SM_RS = SM_BAR + 512;
constexpr int SM_AP = SM_RS + 768;
constexpr int SM_BP = SM_AP + 2048;
constexpr int SM_WPHI = SM_BP + 12288;
constexpr int SM_EPOCH = SM_WPHI + 10240;
constexpr int SM_TOTAL = SM_EPOCH + 16 + 1024;
constexpr int B_FULLS = 0, B_XOLD = 24, B_STAT = 32, B_EMPTYS = 40, B_FULLT = 256  , B_CONS = 384  , B_E3 = 472, B_E0 = 480, B_E1 = 488, B_E2 = 496, B_EPI = 504, B_CS = 160,
              B_KVDONE = 168  , B_ODONE = 176, B_XDONE = 184, B_OH1 = B_CONS, B_CS2 = 208, B_XH0 = 232, B_R0 = 240, B_CB = 144  , B_XOLD2 = 216;
constexpr uint64_t BAR_CNT = 0x1c07fc0eac00a800ull;
constexpr uint64_t WO_A0 = 0xa461b57648357643ull, WO_B0 = 0x59083a9021ba9021ull, WO_A1 = 0xa0b76901276a5babull, WO_B1 = 0x95428a5b34890132ull;
constexpr uint64_t WO_DA0 = 0xa9865432ff00dd00ull, WO_DB0 = 0xa986543211bbccccull, WO_DA1 = 0xa98654321ffff000ull, WO_DB1 = 0xa98754321bbcccddull;
#define WOORD 0xFDB9753ECA864210ull
constexpr int NX = 4;
constexpr int XS = 10;

#define PL 2
#define PROFX(i) PROFT(tid_ == 128 && layer == PL, 200 + (i))
#define NCOM 3
#define PFS 8
#define KVTH 0x41700000u
#define XPF 3
#define XPM 2
#define TLINE 1
#define MAP 3
#define RT2 0
#define WSK 1
#define H1L 0
#define EI 13
#define K0V 0
#define ORD 5
#define RL 2
#define OV 0
#define BP 0
#define NLAYERS 4
constexpr float L2E = 1.4426950408889634f;
#define PHI_MAX 2147483648.f

#define D128(lo) desc64(lo, 0x40000040u)
struct Ctx { uint32_t sb; int g, rb, cu; bf16* out; };

__device__ __forceinline__ void colsum(const CUtensorMap* tm, float* cs, int rb, int g, int w0, int dw, int lane, uint32_t stg, uint32_t cb, uint32_t par) {
  const uint32_t src = stg + (lane >> 3) * 2048;
#pragma unroll 1
  for (int wi = w0 - dw; wi < 6; wi += dw) {
    float s[8] = {0.f, 0.f, 0.f, 0.f, 0.f, 0.f, 0.f, 0.f};
    if (wi >= 0) {
      mbar_wait_u(cb, par);
      par ^= 1;
#pragma unroll 4
      for (int r = 0; r < 16; ++r) {
        const uint4 v = lds128(src + r * 128 + (((lane ^ r) & 7) << 4));
        s[0] += bf_lo(v.x); s[1] += bf_hi(v.x); s[2] += bf_lo(v.y); s[3] += bf_hi(v.y);
        s[4] += bf_lo(v.z); s[5] += bf_hi(v.z); s[6] += bf_lo(v.w); s[7] += bf_hi(v.w);
      }
#pragma unroll
      for (int i = 0; i < 8; ++i) s[i] += __shfl_xor_sync(0xffffffffu, s[i], 8);
    }
    const int wn = wi + dw;
    if (wn < 6) {
      expect_tx_e(cb, 8192);
      tma_2d_e(stg, tm, (wn >= 4 ? 0 : 1024 + (wn >> 1) * 1024) + g * 128 + (wn & 1) * 64, rb * 64, cb);
    }
    if (wi >= 0) {
#pragma unroll
      for (int i = 0; i < 8; ++i) s[i] += __shfl_xor_sync(0xffffffffu, s[i], 16);
      if (lane < 8) {
        red_add4(cs + g * 384 + (wi * 8 + lane) * 8, s[0], s[1], s[2], s[3]);
        red_add4(cs + g * 384 + (wi * 8 + lane) * 8 + 4, s[4], s[5], s[6], s[7]);
      }
      __syncwarp();
    }
  }
}
#define PHASE_CTX() \
  uint32_t sb = c.sb; asm volatile("" : "+r"(sb)); \
  int tid_ = threadIdx.x; asm volatile("" : "+r"(tid_)); \
  const uint32_t bar = sb + SM_BAR; \
  const int lane = tid_ & 31, cw = (tid_ >> 5) - 4, wg = cw >> 2, wq = cw & 3, gq = lane >> 2, t = lane & 3, wrow0 = cw * 16; \
  const int lrow = (lane & 7) + ((lane >> 3) & 1) * 8, lchk = lane >> 4; \
  const bool elected = (tid_ & 127) == 0; \
  const uint32_t rowo = (wrow0 + lrow) * 128, X = (lchk ^ (lane & 7)) << 4; \
  (void)bar; (void)wq; (void)gq; (void)lrow; (void)lchk; (void)elected; (void)wrow0; (void)wg; (void)rowo; (void)X; (void)t;

__device__ __forceinline__ void slab_out_half(uint32_t slot, bf16* dst, int wrow0, int lane, bool FENCE = false) {
  const int r0 = lane >> 3, ch = lane & 7;
  const uint32_t src = slot + (wrow0 + r0) * 128;
  uint4 v[4];
#pragma unroll
  for (int i = 0; i < 4; ++i) v[i] = lds128(src + i * 512 + (((ch ^ (4 * i + r0)) & 7) << 4));
  if (FENCE) fence_async_smem();
  dst += (size_t)(wrow0 + r0) * D_ + ch * 8;
#pragma unroll
  for (int i = 0; i < 4; ++i)
    asm volatile("st.global.v4.u32 [%0], {%1,%2,%3,%4};" ::"l"(dst + (size_t)i * 4 * D_), "r"(v[i].x), "r"(v[i].y), "r"(v[i].z), "r"(v[i].w) : "memory");
}

struct Tag { uint32_t me, mo, tg; };
__device__ __forceinline__ Tag make_tag(int gq, int t, uint32_t tg) { return Tag{t == 0, t == 1, tg}; }
__device__ __forceinline__ void stsm_tag(uint32_t addr, uint32_t r0, uint32_t r1, uint32_t r2, uint32_t r3, const Tag& k, int jp) {
  if (jp == 0) stsm_x4(addr, (r0 & ~k.me) | (k.tg & k.me), (r1 & ~k.mo) | (k.tg & k.mo), r2, r3);
  else stsm_x4(addr, r0, r1, r2, r3);
}
#define TILE_BAD() ((lds_vol(va) ^ tg) & 1)
#define TILE_VA() (slot + (wrow0 + (lane & 15)) * 128 + (lane & 7) * 16 + ((lane >> 3) & 1) * 4)
__device__ __forceinline__ void tile_check(uint32_t slot, const bf16* src, int wrow0, int lane, uint32_t tg) {
  const uint32_t va = TILE_VA();
  if (__builtin_expect(__any_sync(0xffffffffu, TILE_BAD()), 0)) {
    const int r0 = lane >> 3, ch = lane & 7;
    uint32_t n = 0;
#pragma unroll 1
    do {
      uint4 v[4];
#pragma unroll
      for (int i = 0; i < 4; ++i) v[i] = ld_relaxed4(reinterpret_cast<const uint4*>(src + (size_t)(wrow0 + r0 + 4 * i) * D_ + ch * 8));
#pragma unroll
      for (int i = 0; i < 4; ++i) sts128(slot + (wrow0 + r0 + 4 * i) * 128 + (((ch ^ (4 * i + r0)) & 7) << 4), v[i]);
      __syncwarp();
      if (++n > (1u << 16)) { g_err = 8u; break; }
    } while (__any_sync(0xffffffffu, TILE_BAD()));
    fence_async_smem();
    __syncwarp();
  }
}

template <int O>
__device__ __forceinline__ void phi_proj(float (&p)[2][4][4], const uint32_t (&kq)[64], uint32_t wa) {
#pragma unroll
  for (int h = 0; h < 2; ++h)
#pragma unroll
    for (int i = 0; i < 4; ++i) { p[h][i][0] = p[h][i][1] = p[h][i][2] = p[h][i][3] = 0.f; }
#pragma unroll
  for (int ks = 0; ks < 2; ++ks)
#pragma unroll
    for (int np = 0; np < 2; ++np)
#pragma unroll
      for (int h = 0; h < 2; ++h) {
        uint32_t b0, b1, b2, b3;
        ldsm_x4_t(b0, b1, b2, b3, wa + h * 2560 + ks * 1280 + np * 32);
        mma_bf16(p[h][2 * np], kq[O + 8 * h + 4 * ks], kq[O + 8 * h + 4 * ks + 1], kq[O + 8 * h + 4 * ks + 2], kq[O + 8 * h + 4 * ks + 3], b0, b1);
        mma_bf16(p[h][2 * np + 1], kq[O + 8 * h + 4 * ks], kq[O + 8 * h + 4 * ks + 1], kq[O + 8 * h + 4 * ks + 2], kq[O + 8 * h + 4 * ks + 3], b2, b3);
      }
}
__device__ __forceinline__ void phi_exp(uint32_t (&raw)[4][4], const float (&p)[4][4], float sc0, float sc1) {
#pragma unroll
  for (int i = 0; i < 4; ++i) {
    const float e0 = ex2(p[i][0] * sc0), e1 = ex2(p[i][1] * sc0), e2 = ex2(p[i][2] * sc1), e3 = ex2(p[i][3] * sc1);
    const float m0 = e0 * e1, m1 = e2 * e3, rr = rcp(m0 * m1), r0 = rr * m1, r1 = rr * m0;
    raw[i >> 1][(i & 1) * 2] = pack_bf16(e0, e1);
    raw[i >> 1][(i & 1) * 2 + 1] = pack_bf16(e2, e3);
    raw[2 + (i >> 1)][(i & 1) * 2] = pack_bf16(e1 * r0, e0 * r0);
    raw[2 + (i >> 1)][(i & 1) * 2 + 1] = pack_bf16(e3 * r1, e2 * r1);
  }
}
template <int O>
__device__ __forceinline__ void phi_norm(uint32_t (&ph)[2][4][4], const uint32_t (&raw)[2][4][4], const uint32_t (&kq)[64], uint32_t wa,
                                         float sc0, float sc1, float mul0, float mul1) {
  bool bad = false;
#pragma unroll
  for (int h = 0; h < 2; ++h)
#pragma unroll
    for (int sg = 0; sg < 2; ++sg) {
      float ss[4] = {0.f, 0.f, 0.f, 0.f};
#pragma unroll
      for (int ks = 0; ks < 2; ++ks)
        mma_bf16(ss, raw[h][2 * sg + ks][0], raw[h][2 * sg + ks][1], raw[h][2 * sg + ks][2], raw[h][2 * sg + ks][3], 0x3F803F80u, 0x3F803F80u);
      bad = bad || !(ss[0] < PHI_MAX) || !(ss[2] < PHI_MAX);
      const uint32_t iv = pack_bf16(rcp(ss[0]) * mul0, rcp(ss[2]) * mul1);
#pragma unroll
      for (int ks = 0; ks < 2; ++ks)
#pragma unroll
        for (int j = 0; j < 4; ++j) ph[h][2 * sg + ks][j] = mul_bf16x2(raw[h][2 * sg + ks][j], iv, j & 1);
    }
  if (__builtin_expect(__any_sync(0xffffffffu, bad), 0)) {
#pragma unroll 1
    for (int it = 0; it < 4; ++it) {
      float q[4][4];
#pragma unroll
      for (int i = 0; i < 4; ++i) { q[i][0] = q[i][1] = q[i][2] = q[i][3] = 0.f; }
#pragma unroll
      for (int ks = 0; ks < 2; ++ks) {
        uint32_t a[4];
#pragma unroll
        for (int j = 0; j < 4; ++j) a[j] = (it & 2) ? kq[O + 8 + 4 * ks + j] : kq[O + 4 * ks + j];
#pragma unroll
        for (int np = 0; np < 2; ++np) {
          uint32_t b0, b1, b2, b3;
          ldsm_x4_t(b0, b1, b2, b3, wa + (it >> 1) * 2560 + ks * 1280 + np * 32);
          mma_bf16(q[2 * np], a[0], a[1], a[2], a[3], b0, b1);
          mma_bf16(q[2 * np + 1], a[0], a[1], a[2], a[3], b2, b3);
        }
      }
      float iv[2];
#pragma unroll
      for (int r = 0; r < 2; ++r) {
        const float sc = (it & 1) ? -(r ? sc1 : sc0) : (r ? sc1 : sc0);
        float mx = -INFINITY, sm = 0.f;
#pragma unroll
        for (int i = 0; i < 8; ++i) { float& v = q[i >> 1][2 * r + (i & 1)]; v *= sc; mx = fmaxf(mx, v); }
        mx = fmaxf(mx, __shfl_xor_sync(0xffffffffu, mx, 1));
        mx = fmaxf(mx, __shfl_xor_sync(0xffffffffu, mx, 2));
#pragma unroll
        for (int i = 0; i < 8; ++i) { float& v = q[i >> 1][2 * r + (i & 1)]; v = ex2(v - mx); sm += v; }
        sm += __shfl_xor_sync(0xffffffffu, sm, 1);
        sm += __shfl_xor_sync(0xffffffffu, sm, 2);
        iv[r] = rcp(sm) * (r ? mul1 : mul0);
      }
#pragma unroll
      for (int i = 0; i < 24; ++i) ph[i >> 4][(i >> 2) & 3][i & 3] = ph[(i + 8) >> 4][((i + 8) >> 2) & 3][i & 3];
#pragma unroll
      for (int i = 0; i < 4; ++i) {
        ph[1][2 + (i >> 1)][(i & 1) * 2] = pack_bf16(q[i][0] * iv[0], q[i][1] * iv[0]);
        ph[1][2 + (i >> 1)][(i & 1) * 2 + 1] = pack_bf16(q[i][2] * iv[1], q[i][3] * iv[1]);
      }
    }
  }
}

__device__ __forceinline__ void stats_out(float s0, float s1, float q0, float q1, float2* dst, int t) {
  const bool od = t & 1;
  float sa = od ? s1 : s0, qa = od ? q1 : q0;
  sa += __shfl_xor_sync(0xffffffffu, od ? s0 : s1, 1);
  qa += __shfl_xor_sync(0xffffffffu, od ? q0 : q1, 1);
  sa += __shfl_xor_sync(0xffffffffu, sa, 2);
  qa += __shfl_xor_sync(0xffffffffu, qa, 2);
  if (t < 2) red_add2(&dst[t * 8].x, sa, qa);
}

__device__ __forceinline__ void consumer(const Ctx& c) {
  const int g = c.g, m0 = c.rb * 128;
  float acc[192];
#define X_HALF(hf, TG) \
      _Pragma("unroll") for (int jp = 4 * (hf); jp < 4 * (hf) + 4; ++jp) \
        stsm_tag(sb + (XS + (hf)) * SLOT + rowo + (X ^ ((jp & 3) << 5)), \
                 pack_bf16(acc[128 + 8 * jp], acc[129 + 8 * jp]), pack_bf16(acc[130 + 8 * jp], acc[131 + 8 * jp]), \
                 pack_bf16(acc[132 + 8 * jp], acc[133 + 8 * jp]), pack_bf16(acc[134 + 8 * jp], acc[135 + 8 * jp]), TG, jp & 3);
#pragma unroll
  for (int i = 128; i < 192; ++i) acc[i] = 0.f;
#pragma unroll 1
  for (int layer = 0;; ++layer) {
    {
      PHASE_CTX();
      const uint32_t wu = c.cu >> 2;
      const uint32_t dA0 = (((sb + wu * 8192) & 0x3FFFF) >> 4) | (1u << 16), dB0 = ((sb & 0x3FFFF) >> 4) | (512u << 16);
      {
        PROFX(0);
        if (!RT2 || !layer) mbar_wait(bar + B_FULLS, 0);
        PROFX(1);
        wgmma_fence();
        wgmma_n256_0(acc, D128(dA0 + XS * 1024), D128(dB0 + 2048));
#pragma unroll
        for (int k = 1; k < 4; ++k) wgmma_n256(acc, D128(dA0 + XS * 1024 + k * 2), D128(dB0 + 2048 + k * 128), 1);
        wgmma_commit();
        wgmma_wait<1>();
        float s0 = 0.f, s1 = 0.f, q0 = 0.f, q1 = 0.f;
        if (layer) {
          X_HALF(1, (Tag{0u, 0u, 0u}));
#pragma unroll
          for (int i = 128; i < 192; i += 4) {
            s0 += acc[i] + acc[i + 1]; s1 += acc[i + 2] + acc[i + 3];
            q0 = fmaf(acc[i], acc[i], fmaf(acc[i + 1], acc[i + 1], q0)); q1 = fmaf(acc[i + 2], acc[i + 2], fmaf(acc[i + 3], acc[i + 3], q1));
          }
        }
        asm volatile("" : "+f"(s0), "+f"(s1), "+f"(q0), "+f"(q1) :: "memory");
        wgmma_fence();
        wgmma_n128_0(acc, D128(dA0 + XS * 1024), D128(dB0 + 1024));
#pragma unroll
        for (int k = 1; k < 4; ++k) wgmma_n128(acc, D128(dA0 + XS * 1024 + k * 2), D128(dB0 + 1024 + k * 128), 1);
        wgmma_commit();
        if (layer) {
          PHASE_CTX();
          fence_async_smem();
          nbar_dyn(3 + wu, 128);
          stats_out(s0, s1, q0, q1, g_stats + layer * S_ + m0 + wrow0 + gq, t);
          PROFT(tid_ == 128, layer * 16 + 8);
        }
      }
      uint32_t s = 1, u = 0, sp = 0;
      const int ix = layer ? 99 : 2 * (K0V ? NCOM : min(g, NCOM)) + 1;
#pragma unroll 1
      for (int i = 1; i < 14; ++i) {
        mbar_wait(bar + B_FULLS + s * 8, (u + (s ? layer : 0)) & 1);
        if (layer && (unsigned)(i - 2) < 7u) {
          PHASE_CTX();
          tile_check(sb + ((QA >> (4 * s)) & 15) * SLOT, g_x + (size_t)m0 * D_ + ((2 * g + 2 * i - 2) & 15) * 64, wrow0, lane, lds_vol(sb + SM_EPOCH) + layer);
        }
        const uint32_t da = dA0 + ((QA >> (4 * s)) & 15) * 1024, dk = dB0 + ((QK >> (4 * s)) & 15) * 1024,
                       dq = dB0 + ((QQ >> (4 * s)) & 15) * 1024;
        wgmma_fence();
#pragma unroll
        for (int k = 0; k < 4; ++k) {
          wgmma_n256(acc, D128(da + k * 2), D128(dk + k * 128), 1);
          wgmma_n128(acc, D128(da + k * 2), D128(dq + k * 128), 1);
          if (k == 0) {
            wgmma_commit();
            wgmma_wait<1>();
            if (elected && (unsigned)(i - ix) >= 2u) release2(bar + B_EMPTYS + sp * 8);
          }
        }
        wgmma_commit();
        if ((unsigned)(i - ix) < 2u) {
          PHASE_CTX();
          {
            float s0 = 0.f, s1 = 0.f, q0 = 0.f, q1 = 0.f;
            const uint32_t xa = sb + ((QA >> (4 * sp)) & 15) * SLOT + rowo;
#pragma unroll
            for (int jp = 0; jp < 4; ++jp) {
              uint32_t x0, x1, x2, x3;
              ldsm_x4(x0, x1, x2, x3, xa + (X ^ (jp << 5)));
              s0 += (bf_lo(x0) + bf_hi(x0)) + (bf_lo(x2) + bf_hi(x2));
              s1 += (bf_lo(x1) + bf_hi(x1)) + (bf_lo(x3) + bf_hi(x3));
              q0 = fmaf(bf_lo(x0), bf_lo(x0), fmaf(bf_hi(x0), bf_hi(x0), fmaf(bf_lo(x2), bf_lo(x2), fmaf(bf_hi(x2), bf_hi(x2), q0))));
              q1 = fmaf(bf_lo(x1), bf_lo(x1), fmaf(bf_hi(x1), bf_hi(x1), fmaf(bf_lo(x3), bf_lo(x3), fmaf(bf_hi(x3), bf_hi(x3), q1))));
            }
            stats_out(s0, s1, q0, q1, g_stats + m0 + wrow0 + gq, t);
          }
          __syncwarp();
          if (lane == 0 && i != ix) mbar_arrive(bar + B_XDONE);
          nbar_dyn(3 + wu, 128);
          if (elected) release2(bar + B_EMPTYS + sp * 8);
        }
        if (i == 1 && layer) {
          PHASE_CTX();
          slab_out_half(sb + (XS + 1) * SLOT, g_x + (size_t)m0 * D_ + g * 128 + 64, wrow0, lane);
          __syncwarp();
          if (lane == 0) mbar_arrive(bar + B_XDONE);
          nbar_dyn(3 + wu, 128);
        }
        sp = s;
        if (++s == 3) { s = 0; ++u; }
      }
      {
        const uint64_t dap = make_desc_ns(sb + SM_AP + wu * 1024, 0, 128), dbp = make_desc_ns(sb + SM_BP + (layer & 1) * 6144, 0, 128);
        if (wu == 0) {
          wgmma_wait<0>();
          if (elected) mbar_arrive(bar + B_R0);
          nbar<6, 256>();
        }
        if (layer < 2) mbar_wait(bar + (layer ? B_CS2 : B_CS), 0);
        mbar_wait(bar + B_STAT, layer & 1);
        mbar_wait(bar + B_FULLS + 16, layer & 1);
        wgmma_fence();
        wgmma_n256_k(acc, dap, dbp, 1);
#pragma unroll
        for (int k = 0; k < 4; ++k) wgmma_n256(acc, D128(dA0 + (QA >> 8) * 1024 + k * 2), D128(dB0 + (QK >> 8) * 1024 + k * 128), 1);
        mbar_wait(bar + B_FULLS, 1);
        PROFT(tid_ == 128, layer * 16 + 9);
        wgmma_fence();
#pragma unroll
        for (int k = 0; k < 4; ++k) wgmma_n256(acc, D128(dA0 + (QA & 15) * 1024 + k * 2), D128(dB0 + (QK & 15) * 1024 + k * 128), 1);
        wgmma_commit();
        if (wu) nbar<6, 256>();
#define Q_TAIL() \
        wgmma_n128_k(acc, dap, dbp + 256, 1); \
        _Pragma("unroll") for (int k = 0; k < 4; ++k) wgmma_n128(acc, D128(dA0 + (QA >> 8) * 1024 + k * 2), D128(dB0 + (QQ >> 8) * 1024 + k * 128), 1); \
        _Pragma("unroll") for (int k = 0; k < 4; ++k) wgmma_n128(acc, D128(dA0 + (QA & 15) * 1024 + k * 2), D128(dB0 + (QQ & 15) * 1024 + k * 128), 1);
        Q_TAIL();
        wgmma_commit();
        wgmma_wait<1>();
#pragma unroll
        for (int i = 0; i < 128; ++i) asm volatile("" : "+f"(acc[i]) :: "memory");
      }
    }
    uint32_t xo[32];
    uint32_t oq[8][4];
    {
      PHASE_CTX();
      PROFT(tid_ == 128, layer * 16 + 1);
      const bool isB = layer & 1;
      const int cu = c.cu;
      if (cu >= 4) asm volatile("bar.arrive 7, 256;" ::: "memory");
      if (elected && cu == 4) mbar_arrive(bar + B_R0);
      uint32_t kq[64];
      const uint32_t rowq = rowo & 8191;
      const float rs0 = lds_f(sb + SM_RS + (16 + wrow0 + gq) * 4), rs1 = lds_f(sb + SM_RS + (24 + wrow0 + gq) * 4);
#define Q_DONE() \
      wgmma_wait<0>(); \
      if (lane == 0) release2(bar + B_E0); \
      _Pragma("unroll") for (int i = 128; i < 192; ++i) asm volatile("" : "+f"(acc[i]) :: "memory"); \
      _Pragma("unroll") for (int i = 0; i < 32; ++i) kq[32 + i] = pack_bf16(acc[128 + 2 * i], acc[129 + 2 * i]);
      if (isB) {
        if (cu == 0) asm volatile("bar.arrive 10, 64;" ::: "memory");
        if (elected) release2(bar + B_E1);
        const int e = gq & 1;
        const bool sel = t > (gq >> 1);
        const uint32_t rja = sb + SM_RS + (wrow0 + 2 * t + e) * 4;
        const float rjA0 = lds_f(rja + 32), rjA1 = lds_f(rja + 64), rjB0 = lds_f(rja + (sel ? 0 : 64)), rjB1 = lds_f(rja + (sel ? 32 : 96));
        uint32_t vv[32];
#pragma unroll
        for (int i = 0; i < 16; ++i) { kq[i] = pack_bf16(acc[2 * i], acc[2 * i + 1]); vv[i] = pack_bf16(acc[64 + 2 * i], acc[65 + 2 * i]); }
        const uint32_t rB = sb + 4 * SLOT + wg * 4 * KVT + rowq;
        auto prev = [&](int hp) { return cu == 4 ? rB - 4 * KVT + 8192 + 2 * hp * KVT : rB + 2 * (hp ^ wg) * KVT; };
        auto dump = [&](int hp) {
          const uint32_t kb = rB + 2048 + (hp ^ wg) * 2 * KVT;
#pragma unroll
          for (int jp = 0; jp < 4; ++jp) {
            stsm_x4(kb + (X ^ (jp << 5)), kq[16 * hp + 4 * jp], kq[16 * hp + 4 * jp + 1], kq[16 * hp + 4 * jp + 2], kq[16 * hp + 4 * jp + 3]);
            stsm_x4(kb + KVT + (X ^ (jp << 5)), vv[16 * hp + 4 * jp], vv[16 * hp + 4 * jp + 1], vv[16 * hp + 4 * jp + 2], vv[16 * hp + 4 * jp + 3]);
          }
          if (cu == 3) {
            if (hp) asm volatile("bar.arrive 15, 64;" ::: "memory"); else asm volatile("bar.arrive 9, 64;" ::: "memory");
          }
          asm volatile("bar.arrive %0, 224;" :: "r"(hp ? 13 + (cu >> 2) : 8 + (cu & 4)) : "memory");
        };
        uint4* const hbuf = g_halo + ((c.rb * 8 + g) * 2 + (layer >> 1)) * 512 + lane;
        if (cu < 4) {
          nbar<7, 256>();
          dump(0);
        }
#pragma unroll
        for (int i = 16; i < 32; ++i) { kq[i] = pack_bf16(acc[2 * i], acc[2 * i + 1]); vv[i] = pack_bf16(acc[64 + 2 * i], acc[65 + 2 * i]); }
        if (cu >= 4) {
          if (cu == 7) {
#pragma unroll
            for (int jp = 0; jp < 8; ++jp) {
              st_relaxed4(hbuf + jp * 32, ~kq[4 * jp], ~kq[4 * jp + 1], ~kq[4 * jp + 2], ~kq[4 * jp + 3]);
              st_relaxed4(hbuf + 256 + jp * 32, ~vv[4 * jp], ~vv[4 * jp + 1], ~vv[4 * jp + 2], ~vv[4 * jp + 3]);
            }
          }
          dump(0);
          dump(1);
        }
        PROFT(tid_ == 128, layer * 16 + 2);
        constexpr float SC = 0.17677669529663687f * L2E;
        const float fA0 = rjA0 * rs0 * SC, fB0 = rjB0 * rs0 * SC, fA1 = rjA1 * rs1 * SC, fB1 = rjB1 * rs1 * SC;
        const float bA0 = (m0 + wrow0) ? 0.f : -1e30f, bB = sel ? bA0 : 0.f;
        const uint32_t pA_ = e ? 0x1044u : 0x4410u, pB_ = e ? 0x3244u : 0x4432u, pLo = sel ? pB_ : 0x4444u, pHi = sel ? 0x4444u : pB_;
        const uint32_t KX = ((lane >> 3) ^ (lane & 7)) << 4;
        Q_DONE();
        if (cu == 0) {
          nbar<11, 64>();
        } else if (cu == 4) {
          uint4 hv[16];
          if (c.rb > 0) {
            uint32_t n = 0;
#pragma unroll 1
            while (true) {
              uint32_t mn = 0xFFFFFFFFu;
#pragma unroll
              for (int i = 0; i < 16; ++i) hv[i] = ld_relaxed4(hbuf - 16 * 512 + i * 32);
#pragma unroll
              for (int i = 0; i < 16; ++i) mn = __vimin3_u32(__vimin3_u32(mn, hv[i].x, hv[i].y), hv[i].z, hv[i].w);
              if (__all_sync(0xffffffffu, mn != 0u)) break;
              if (++n > (1u << 20)) { g_err = 4u; break; }
            }
          } else {
#pragma unroll
            for (int i = 0; i < 16; ++i) hv[i] = make_uint4(~0u, ~0u, ~0u, ~0u);
          }
          nbar<10, 64>();
#pragma unroll
          for (int i = 0; i < 16; ++i)
            stsm_x4(rB - 4 * KVT + (((i >> 2) & 1) * 2 + (i >> 3)) * KVT + (X ^ ((i & 3) << 5)), ~hv[i].x, ~hv[i].y, ~hv[i].z, ~hv[i].w);
          asm volatile("bar.arrive 11, 64;" ::: "memory");
          nbar<9, 64>();
        } else {
          nbar_dyn(8 + (cu & 4), 224);
        }
        PROFT(tid_ == 128, layer * 16 + 5);
        PROFT(lane == 0 && layer == PL, 136 + cw);
        uint32_t kb[2][2][4], vb[2][2][2][4];
        float oa[2][4][4], sm[2][2];
        auto att_load = [&](int hp) {
          const uint32_t kt = prev(hp) - (lane & 8) * 128, vt = rB + (2 * (hp ^ wg) + 1) * KVT + 2048;
          __syncwarp();
#pragma unroll
          for (int h = 0; h < 2; ++h)
#pragma unroll
            for (int nt = 0; nt < 2; ++nt) ldsm_x4(kb[h][nt][0], kb[h][nt][1], kb[h][nt][2], kb[h][nt][3], kt + nt * 1024 + (KX ^ (h << 6)));
#pragma unroll
          for (int ks = 0; ks < 2; ++ks)
#pragma unroll
            for (int np = 0; np < 2; ++np)
#pragma unroll
              for (int h = 0; h < 2; ++h)
                ldsm_x4_t(vb[h][ks][np][0], vb[h][ks][np][1], vb[h][ks][np][2], vb[h][ks][np][3], (ks ? vt : prev(hp) + KVT) + (X ^ (h << 6) ^ (np << 5)));
          if (hp == 0 && lane == 0) release2(bar + B_E3);
        };
        auto att_mid = [&](int hp) {
          float la[2][2], lb[2][2], mx[2][2];
#pragma unroll
          for (int h = 0; h < 2; ++h) {
            const int qo = 32 + 16 * hp + 8 * h, ko = 16 * hp + 8 * h;
            float sc[4][4];
#pragma unroll
            for (int nt = 0; nt < 4; ++nt) {
              sc[nt][0] = sc[nt][1] = sc[nt][2] = sc[nt][3] = 0.f;
#pragma unroll
              for (int ks = 0; ks < 2; ++ks)
                mma_bf16(sc[nt], kq[qo + 4 * ks], kq[qo + 4 * ks + 1], kq[qo + 4 * ks + 2], kq[qo + 4 * ks + 3],
                         nt < 2 ? kb[h][nt & 1][2 * ks] : kq[ko + 4 * ks + (nt & 1)], nt < 2 ? kb[h][nt & 1][2 * ks + 1] : kq[ko + 4 * ks + 2 + (nt & 1)]);
            }
            la[h][0] = fmaf(e ? sc[1][1] : sc[1][0], fA0, bA0);
            lb[h][0] = fmaf(sel ? (e ? sc[0][1] : sc[0][0]) : (e ? sc[2][1] : sc[2][0]), fB0, bB);
            la[h][1] = (e ? sc[2][3] : sc[2][2]) * fA1;
            lb[h][1] = fmaf(sel ? (e ? sc[1][3] : sc[1][2]) : (e ? sc[3][3] : sc[3][2]), fB1, bB);
            mx[h][0] = fmaxf(la[h][0], lb[h][0]); mx[h][1] = fmaxf(la[h][1], lb[h][1]);
          }
#pragma unroll
          for (int o = 1; o <= 2; o <<= 1)
#pragma unroll
            for (int h = 0; h < 2; ++h)
#pragma unroll
              for (int r = 0; r < 2; ++r) mx[h][r] = fmaxf(mx[h][r], __shfl_xor_sync(0xffffffffu, mx[h][r], o));
#pragma unroll
          for (int h = 0; h < 2; ++h) {
#pragma unroll
            for (int r = 0; r < 2; ++r) { la[h][r] = ex2(la[h][r] - mx[h][r]); lb[h][r] = ex2(lb[h][r] - mx[h][r]); sm[h][r] = la[h][r] + lb[h][r]; }
            const uint32_t p0 = pack_bf16(la[h][0] * rjA0, lb[h][0] * rjB0), p1 = pack_bf16(la[h][1] * rjA1, lb[h][1] * rjB1);
            const uint32_t a00 = __byte_perm(p0, 0u, pLo), a02 = __byte_perm(p0, 0u, pA_), a03 = __byte_perm(p1, 0u, pLo);
            const uint32_t a10 = __byte_perm(p0, 0u, pHi), a11 = __byte_perm(p1, 0u, pA_), a13 = __byte_perm(p1, 0u, pHi);
#pragma unroll
            for (int i = 0; i < 4; ++i) {
              oa[h][i][0] = oa[h][i][1] = oa[h][i][2] = oa[h][i][3] = 0.f;
              mma_bf16(oa[h][i], a00, 0u, a02, a03, vb[h][0][i >> 1][2 * (i & 1)], vb[h][0][i >> 1][2 * (i & 1) + 1]);
              mma_bf16(oa[h][i], a10, a11, 0u, a13, vb[h][1][i >> 1][2 * (i & 1)], vb[h][1][i >> 1][2 * (i & 1) + 1]);
            }
          }
#pragma unroll
          for (int o = 1; o <= 2; o <<= 1)
#pragma unroll
            for (int h = 0; h < 2; ++h)
#pragma unroll
              for (int r = 0; r < 2; ++r) sm[h][r] += __shfl_xor_sync(0xffffffffu, sm[h][r], o);
        };
        auto att_end = [&](int hp) {
          const uint32_t qad = sb + (XS + 1 - hp) * SLOT + rowo;
#pragma unroll
          for (int jp = 0; jp < 4; ++jp) ldsm_x4(xo[16 * hp + 4 * jp], xo[16 * hp + 4 * jp + 1], xo[16 * hp + 4 * jp + 2], xo[16 * hp + 4 * jp + 3], qad + (X ^ (jp << 5)));
#pragma unroll
          for (int h = 0; h < 2; ++h) {
            const float i0 = rcp(sm[h][0]), i1 = rcp(sm[h][1]);
#pragma unroll
            for (int np = 0; np < 2; ++np)
            {
              uint32_t (&o)[4] = oq[4 * hp + 2 * h + np];
              o[0] = pack_bf16(oa[h][2 * np][0] * i0, oa[h][2 * np][1] * i0); o[1] = pack_bf16(oa[h][2 * np][2] * i1, oa[h][2 * np][3] * i1);
              o[2] = pack_bf16(oa[h][2 * np + 1][0] * i0, oa[h][2 * np + 1][1] * i0); o[3] = pack_bf16(oa[h][2 * np + 1][2] * i1, oa[h][2 * np + 1][3] * i1);
              if (!hp || !H1L) stsm_tag(qad + (X ^ (h << 6) ^ (np << 5)), o[0], o[1], o[2], o[3], make_tag(gq, t, 0u), 2 * h + np);
            }
          }
          if (!hp || !H1L) {
          __syncwarp();
          slab_out_half(sb + (XS + 1 - hp) * SLOT, g_o + (size_t)m0 * D_ + g * 128 + hp * 64, wrow0, lane);
          __syncwarp();
          if (lane == 0) mbar_arrive(bar + (hp ? B_ODONE : B_OH1));
          }
          PROFT(lane == 0 && layer == PL && hp == 0, 128 + cw);
        };
#define ATT_SYNC1() if (cu == 4) nbar<15, 64>(); else if (cu != 0) nbar_dyn(13 + (cu >> 2), 224);
        att_load(0);
        if (BP && cu < 4) dump(1);
        att_mid(0);
        mbar_wait(bar + B_XOLD, 1);
        if (BP) { ATT_SYNC1(); att_load(1); }
        att_end(0);
        if (!BP) { if (cu < 4) dump(1); ATT_SYNC1(); att_load(1); }
        att_mid(1);
        mbar_wait(bar + B_XOLD2, 1);
        att_end(1);
      } else {
#pragma unroll
        for (int i = 0; i < 32; ++i) kq[i] = pack_bf16(acc[2 * i], acc[2 * i + 1]);
        if (cu < 4) nbar<7, 256>();
        {
          const uint32_t vb = sb + (5 + 3 * wg) * SLOT + (rowq >> 1) + ((lchk ^ ((lane & 7) >> 1)) << 4);
#pragma unroll
          for (int jp = 8; jp < 16; ++jp)
            stsm_x4((vb ^ ((jp & 1) << 5)) + ((jp >> 1) & 3) * 4096,
                    pack_bf16(acc[8 * jp], acc[8 * jp + 1]), pack_bf16(acc[8 * jp + 2], acc[8 * jp + 3]),
                    pack_bf16(acc[8 * jp + 4], acc[8 * jp + 5]), pack_bf16(acc[8 * jp + 6], acc[8 * jp + 7]));
        }
        PROFT(tid_ == 128, layer * 16 + 2);
        Q_DONE();
        const uint32_t pA = sb + (3 + 3 * wg) * SLOT + (rowo & 8191);
        float sc0 = rs0 * L2E, sc1 = rs1 * L2E;
        const uint32_t wa0 = sb + SM_WPHI + lrow * 80 + lchk * 16;
        const uint32_t wu = c.cu >> 2, par = (layer >> 1) & 1;
        float p[2][4][4];
        uint32_t raw[2][4][4], ph[2][4][4];
        float kva[20], oab[2][2][20];
        auto kv_start = [&](int hp) {
#pragma unroll
          for (int h = 0; h < 2; ++h)
#pragma unroll
            for (int cp = 0; cp < 4; ++cp)
              stsm_x4(pA + hp * 16384 + h * 8192 + (X ^ (cp << 5)), ph[h][cp][0], ph[h][cp][1], ph[h][cp][2], ph[h][cp][3]);
          PROFT(tid_ == 128, layer * 16 + 11);
          nbar<1, 256>();
          fence_async_smem();
          const uint32_t hu = 2 * hp + wu;
          const uint32_t dP = (((sb + 3 * SLOT + hu * 8192) & 0x3FFFF) >> 4) | (512u << 16);
          const uint32_t dV = (((sb + 5 * SLOT + hu * 4096) & 0x3FFFF) >> 4) | (((SM_SD - 5 * SLOT - hu * 4096) >> 4) << 16);
          wgmma_fence();
#pragma unroll
          for (int ks = 0; ks < 8; ++ks)
            wgmma_n40_tt(kva, desc64(dP + (ks >> 2) * 3072 + (ks & 3) * 128, 0x40000040u),
                         desc64(dV + (ks >> 2) * (3072u - (2816u << 16)) + (ks & 3) * 64, 0x80000020u), ks != 0);
          wgmma_commit();
        };
        auto kv_end = [&](int hp) {
          wgmma_wait<0>();
#pragma unroll
          for (int i = 0; i < 20; ++i) asm volatile("" : "+f"(kva[i]) :: "memory");
          nbar_dyn(3 + wu, 128);
          PROFT(tid_ == 128, layer * 16 + 12);
          const bool od = lane & 1;
#pragma unroll
          for (int i = 0; i < 4; ++i)
            sts128(sb + (3 + hp) * SLOT + (cw * 128 + i * 32 + lane) * 16,
                   make_uint4(__float_as_uint(kva[4 * i]), __float_as_uint(kva[4 * i + 1]), __float_as_uint(kva[4 * i + 2]),
                              __float_as_uint(od == (i >= 2) ? 1.f : kva[4 * i + 3])));
          sts128(sb + (6 + hp) * SLOT + wg * 8192 + (wq * 32 + lane) * 16,
                 make_uint4(__float_as_uint(od ? kva[11] : kva[3]), __float_as_uint(od ? kva[15] : kva[7]), __float_as_uint(od ? kva[18] : kva[16]), __float_as_uint(1.f)));
          __syncwarp();
          if (lane == 0) mbar_arrive(bar + B_KVDONE - hp * 32);
          PROFT(tid_ == 128, layer * 16 + 3);
        };
        const uint4* const kvg = g_kv + (g * 2 + (layer >> 1)) * 2560 + cw * 128 + lane;
        uint4 ub[2][5];
        auto kv_load = [&](int hp) {
          uint4 (&u)[5] = ub[hp];
#pragma unroll
          for (int i = 0; i < 4; ++i) u[i] = ld_relaxed4(kvg + hp * 1280 + i * 32);
          u[4] = ld_relaxed4(kvg + hp * 1280 + 1024 - cw * 96);
        };
        auto kv_conv = [&](int hp) {
          uint4 (&u)[5] = ub[hp];
          PROFT(tid_ == 128 && hp == 0, layer * 16 + 10);
          PROFT(lane == 0 && hp == 1 && layer == PL, 128 + cw);
          if (hp == 0) mbar_wait(bar + B_KVDONE - 32, par);
          const bool od = lane & 1;
          uint32_t n = 0;
#pragma unroll 1
          while (!__all_sync(0xffffffffu, (od ? u[2].w : u[0].w) == 0x41800000u && (od ? u[3].w : u[1].w) == 0x41800000u && u[4].w == 0x41800000u)) {
#pragma unroll 1
            while (__any_sync(0xffffffffu, u[4].w < KVTH) && ++n < (1u << 20)) u[4].w = ld_relaxed(&kvg[hp * 1280 + 1024 - cw * 96].w);
            if (++n > (1u << 20)) { g_err = 6u; break; }
            kv_load(hp);
          }
          PROFT(lane == 0 && hp == 1 && layer == PL, 136 + cw);
          PROFT(tid_ == 128 && hp == 0, layer * 16 + 5);
          if (!od) { u[0].w = u[4].x; u[1].w = u[4].y; } else { u[2].w = u[4].x; u[3].w = u[4].y; }
#pragma unroll
          for (int i = 0; i < 4; i += 2)
            stsm_x4(sb + (5 + 3 * hp) * SLOT + rowo + (X ^ ((i & 2) << 4)),
                    pack_bf16(__uint_as_float(u[i].x), __uint_as_float(u[i].y)), pack_bf16(__uint_as_float(u[i].z), __uint_as_float(u[i].w)),
                    pack_bf16(__uint_as_float(u[i + 1].x), __uint_as_float(u[i + 1].y)), pack_bf16(__uint_as_float(u[i + 1].z), __uint_as_float(u[i + 1].w)));
          const uint32_t z2 = pack_bf16(__uint_as_float(u[4].z), __uint_as_float(u[4].z));
          if (t < 2) sts128(sb + (5 + 3 * hp) * SLOT + (wrow0 + gq + 8 * t) * 128 + ((4 ^ gq) << 4), make_uint4(z2, z2, z2, z2));
        };
        auto o_mma = [&](int hp, const uint32_t (&pq)[2][4][4]) {
          float (&oa)[2][20] = oab[hp];
          PROFT(tid_ == 128 && hp == 1, layer * 16 + 4);
          const uint32_t dK = (((sb + (5 + 3 * hp) * SLOT) & 0x3FFFF) >> 4) | (512u << 16);
          wgmma_fence();
#pragma unroll
          for (int ks = 0; ks < 4; ++ks) {
#pragma unroll
            for (int hh = 0; hh < 2; ++hh) wgmma_n40_rs(oa[hh], pq[hh][ks], D128(dK + hh * 512 + ks * 128), ks != 0);
          }
          wgmma_commit();
        };
        auto o_start = [&](int hp, const uint32_t (&pq)[2][4][4]) {
          kv_conv(hp);
          nbar<1, 256>();
          fence_async_smem();
          o_mma(hp, pq);
        };
        auto o_end = [&](int hp) {
          float (&oa)[2][20] = oab[hp];
          wgmma_wait<0>();
#pragma unroll
          for (int i = 0; i < 20; ++i) asm volatile("" : "+f"(oa[0][i]), "+f"(oa[1][i]) :: "memory");
#pragma unroll
          for (int hh = 0; hh < 2; ++hh) {
            const float i0 = rcp(oa[hh][16] + 1e-6f), i1 = rcp(oa[hh][18] + 1e-6f);
            const uint32_t qad = sb + (3 + hp) * SLOT + rowo, hx = hh << 6;
#pragma unroll
            for (int np = 0; np < 2; ++np)
            {
              uint32_t (&o)[4] = oq[4 * hp + 2 * hh + np];
              o[0] = pack_bf16(oa[hh][8 * np] * i0, oa[hh][8 * np + 1] * i0); o[1] = pack_bf16(oa[hh][8 * np + 2] * i1, oa[hh][8 * np + 3] * i1);
              o[2] = pack_bf16(oa[hh][8 * np + 4] * i0, oa[hh][8 * np + 5] * i0); o[3] = pack_bf16(oa[hh][8 * np + 6] * i1, oa[hh][8 * np + 7] * i1);
              if (!hp || !H1L) stsm_tag(qad + (X ^ hx ^ (np << 5)), o[0], o[1], o[2], o[3], make_tag(gq, t, 1u), 2 * hh + np);
            }
          }
          if (!hp || !H1L) {
          __syncwarp();
          slab_out_half(sb + (3 + hp) * SLOT, g_o + (size_t)m0 * D_ + g * 128 + hp * 64, wrow0, lane);
          __syncwarp();
          if (lane == 0) mbar_arrive(bar + (hp ? B_ODONE : B_OH1));
          }
        };
#define XO_LOAD() \
        mbar_wait(bar + B_XOLD, 0); \
        mbar_wait(bar + B_XOLD2, 0); \
        _Pragma("unroll") for (int jp = 0; jp < 8; ++jp) \
          ldsm_x4(xo[4 * jp], xo[4 * jp + 1], xo[4 * jp + 2], xo[4 * jp + 3], sb + (XS + 1 - (jp >> 2)) * SLOT + rowo + (X ^ ((jp & 3) << 5)));
#define SC_RELOAD() \
        sc0 = __uint_as_float(lds_vol(sb + SM_RS + (16 + wrow0 + gq) * 4)) * L2E; sc1 = __uint_as_float(lds_vol(sb + SM_RS + (24 + wrow0 + gq) * 4)) * L2E;
        __syncwarp();
        phi_proj<0>(p, kq, wa0);
        phi_exp(raw[0], p[0], sc0, sc1);
        phi_exp(raw[1], p[1], sc0, sc1);
        phi_proj<16>(p, kq, wa0 + 5120);
        phi_norm<0>(ph, raw, kq, wa0, sc0, sc1, rs0, rs1);
#define PIN(h) if ((raw[h][2][0] & raw[h][2][2] & raw[h][3][0] & raw[h][3][2]) == ~0u) sts_f(sb + SM_EPOCH + 12, 0.f)
        kv_start(0);
        phi_exp(raw[0], p[0], sc0, sc1);
        if (OV & 1) { phi_exp(raw[1], p[1], sc0, sc1); PIN(0); PIN(1); }
        kv_end(0);
        if (RL & 1) { SC_RELOAD(); }
        XO_LOAD();
        if (!(OV & 1)) phi_exp(raw[1], p[1], sc0, sc1);
        phi_proj<32>(p, kq, wa0);
        phi_norm<16>(ph, raw, kq, wa0 + 5120, sc0, sc1, rs0, rs1);
        kv_start(1);
        if (lane == 0) release2(bar + B_E3);
        phi_exp(raw[0], p[0], sc0, sc1);
        if (OV & 2) PIN(0);
        kv_end(1);
        if (RL & 2) { SC_RELOAD(); }
        phi_exp(raw[1], p[1], sc0, sc1);
        phi_proj<48>(p, kq, wa0 + 5120);
        phi_norm<32>(ph, raw, kq, wa0, sc0, sc1, 1.f, 1.f);
        kv_load(0);
        phi_exp(raw[0], p[0], sc0, sc1);
        phi_exp(raw[1], p[1], sc0, sc1);
        if ((raw[0][2][0] & raw[0][2][2] & raw[0][3][0] & raw[0][3][2] & raw[1][2][0] & raw[1][2][2] & raw[1][3][0] & raw[1][3][2]) == ~0u) sts_f(sb + SM_EPOCH + 12, 0.f);
        o_start(0, ph);
        kv_load(1);
        o_end(0);
        phi_norm<48>(ph, raw, kq, wa0 + 5120, sc0, sc1, 1.f, 1.f);
        o_start(1, ph);
        o_end(1);
      }
      __syncwarp();
      PROFT(lane == 0 && layer == PL, 216 + cw);
      if (lane == 0) mbar_arrive(bar + B_EPI);
      PROFT(tid_ == 128, layer * 16 + 6);
    }
    {
      PHASE_CTX();
      const uint32_t wu = c.cu >> 2;
      const uint32_t dA0 = (((sb + wu * 8192) & 0x3FFFF) >> 4) | (1u << 16), dB0 = ((sb & 0x3FFFF) >> 4) | (512u << 16);
#pragma unroll
      for (int i = 0; i < 32; ++i) { acc[128 + 2 * i] = bf_lo(xo[i]); acc[129 + 2 * i] = bf_hi(xo[i]); }
      uint64_t ta = ((layer & 1) ? WO_A1 : WO_A0) >> 8, tw = (layer & 1) ? WO_B1 : WO_B0;
      mbar_wait(bar + B_FULLT, layer & 1);
      mbar_wait(bar + B_FULLT + 8, layer & 1);
      PROFT(tid_ == 128 && layer == PL, 160);
      wgmma_fence();
#pragma unroll
      for (int k = 0; k < 8; ++k) wgmma_n128_rs(acc, oq[k], D128(dB0 + ((uint32_t)(tw >> (k & 4)) & 15) * 1024 + (k & 3) * 128), 1);
      wgmma_commit();
      tw >>= 8;
      if (lane == 0 && !H1L) release2(bar + B_E2);
#pragma unroll 1
      for (int i = 2; i < 16; ++i) {
        mbar_wait(bar + B_FULLT + i * 8, layer & 1);
        PROFT(tid_ == 128 && layer == PL, 160 + i);
        tile_check(sb + ((uint32_t)ta & 15) * SLOT, g_o + (size_t)m0 * D_ + ((2 * g + (int)(WOORD >> (4 * i))) & 15) * 64, wrow0, lane, ~layer);
        const uint32_t da = dA0 + ((uint32_t)ta & 15) * 1024, db = dB0 + ((uint32_t)tw & 15) * 1024;
        ta >>= 4; tw >>= 4;
        if (i == 16 - WSK && wu) nbar<6, 256>();
        wgmma_fence();
#pragma unroll
        for (int k = 0; k < 4; ++k) wgmma_n128(acc, D128(da + k * 2), D128(db + k * 128), 1);
        wgmma_commit();
        if (i == 15 && !wu) asm volatile("bar.arrive 6, 256;" ::: "memory");
        if (H1L && i == H1L) {
          const uint32_t st = sb + ((layer & 1) ? XS : 4) * SLOT;
#pragma unroll
          for (int k = 0; k < 4; ++k) stsm_tag(st + rowo + (X ^ (k << 5)), oq[4 + k][0], oq[4 + k][1], oq[4 + k][2], oq[4 + k][3], make_tag(gq, t, ~layer), k);
          __syncwarp();
          slab_out_half(st, g_o + (size_t)m0 * D_ + g * 128 + 64, wrow0, lane);
          __syncwarp();
          if (lane == 0) { mbar_arrive(bar + B_ODONE); release2(bar + B_E2); }
        }
        wgmma_wait<1>();
        if (elected && i < 12) release2(bar + B_CONS + (i - 1) * 8);
        if (elected && (unsigned)(i - EI) < 2u && layer + 1 < NLAYERS) release2(bar + B_EMPTYS + (i - EI) * 8);
      }
      const bool last = layer == NLAYERS - 1;
      Tag xt = make_tag(gq, last ? 4 : t, lds_vol(sb + SM_EPOCH) + layer + 1);
      asm volatile("" : "+r"(xt.me), "+r"(xt.mo), "+r"(xt.tg) :: "memory");
      if (RT2 && !last) mbar_wait(bar + B_FULLS, 0);
      wgmma_wait<0>();
#pragma unroll
      for (int i = 128; i < 192; ++i) asm volatile("" : "+f"(acc[i]) :: "memory");
      if (elected && !last) release2(bar + B_EMPTYS + 16);
      PROFT(tid_ == 128, layer * 16 + 7);
      X_HALF(0, xt);
      if (last) {
        __syncwarp();
        slab_out_half(sb + XS * SLOT, c.out + (size_t)m0 * D_ + g * 128, wrow0, lane);
        X_HALF(1, (Tag{0u, 0u, 0u}));
        __syncwarp();
        slab_out_half(sb + (XS + 1) * SLOT, c.out + (size_t)m0 * D_ + g * 128 + 64, wrow0, lane);
        __syncwarp();
        if (lane == 0) mbar_arrive(bar + B_XDONE);
        PROFT(tid_ == 128, layer * 16 + 24);
        break;
      }
      __syncwarp();
      slab_out_half(sb + XS * SLOT, g_x + (size_t)m0 * D_ + g * 128, wrow0, lane, true);
      __syncwarp();
      if (lane == 0) mbar_arrive(bar + B_XH0);
      nbar_dyn(3 + wu, 128);
    }
  }
}

__device__ __forceinline__ int kblock0(int i, int g) {
  const int j = i >> 1, p = max(g, NCOM) + j - NCOM;
  return (j < NCOM ? j : p < 8 ? p : p - 8 + NCOM) * 2 + (i & 1);
}

__device__ __forceinline__ int wo_kblock(int m, int g) { return (2 * g + (int)((WOORD >> (4 * m)) & 15)) & 15; }

__global__ void __cluster_dims__(2, 1, 1) __launch_bounds__(384, 1)
mega_kernel(const __grid_constant__ CUtensorMap tm_x0, const __grid_constant__ CUtensorMap tm_x,
            const __grid_constant__ CUtensorMap tm_o,
            const __grid_constant__ CUtensorMap tm_wA, const __grid_constant__ CUtensorMap tm_wB,
            const __grid_constant__ CUtensorMap tm_woA, const __grid_constant__ CUtensorMap tm_woB,
                        const bf16* __restrict__ wB, const bf16* __restrict__ wphi, bf16* __restrict__ out) {
  extern __shared__ uint8_t smem_raw[];
  const uint32_t sb = (smem_u32(smem_raw) + 1023u) & ~1023u;
  const uint32_t bar = sb + SM_BAR;
  const int warp = __shfl_sync(0xffffffffu, threadIdx.x >> 5, 0), lane = threadIdx.x & 31;
  uint32_t bid = blockIdx.x;
  if (MAP == 3 && gridDim.x == 128 + NX) {
    uint32_t tp;
    asm volatile("mov.u32 %0, %%smid;" : "=r"(tp));
    tp >>= 1;
    const uint32_t u7 = ((tp - 32) * 37) >> 8;
    bid = (tp < 32 ? tp : tp < 60 ? tp + 1 + u7 : tp < 62 ? tp + 4 : (tp - 58) * 8) * 2 + (bid & 1);
  }
  if (bid >= 128 || gridDim.x == NX) {
    const int xb = bid & (NX - 1);
    const int ch = threadIdx.x % 96, rg = threadIdx.x / 96, gg = xb * 2 + ch / 48, sec = (ch % 48) >> 4;
    const uint4* src = reinterpret_cast<const uint4*>(wB + (size_t)rg * 3072 + (sec == 2 ? 0 : 1024 + sec * 1024) + gg * 128 + (ch & 15) * 8);
    float s[8] = {0.f, 0.f, 0.f, 0.f, 0.f, 0.f, 0.f, 0.f};
#pragma unroll 1
    for (int r0 = 0; r0 < 256; r0 += 32) {
      uint4 v[32];
#pragma unroll
      for (int r = 0; r < 32; ++r) v[r] = __ldg(src + (size_t)(r0 + r) * 1536);
#pragma unroll
      for (int r = 0; r < 32; ++r) {
        s[0] += bf_lo(v[r].x); s[1] += bf_hi(v[r].x); s[2] += bf_lo(v[r].y); s[3] += bf_hi(v[r].y);
        s[4] += bf_lo(v[r].z); s[5] += bf_hi(v[r].z); s[6] += bf_lo(v[r].w); s[7] += bf_hi(v[r].w);
      }
    }
    float* cd = g_cs + (ld_relaxed(&g_epoch) & 1) * 6144 + 3072 + xb * 768 + ch * 8;
    red_add4(cd, s[0], s[1], s[2], s[3]);
    red_add4(cd + 4, s[4], s[5], s[6], s[7]);
    nbar<1, 384>();
    if (threadIdx.x < 2) flag_add(&g_csflag[8 + xb * 2 + threadIdx.x].v);
    return;
  }
  const int cr = bid & 1;
  const int g = bid >> 4;
  const int rb = bid & 15;
  const int m0 = rb * 128;

  if (warp < 4) {
    asm volatile("setmaxnreg.dec.sync.aligned.u32 40;");
    asm volatile("barrier.cluster.arrive.relaxed.aligned;" ::: "memory");
    const unsigned int epoch = warp ? ld_relaxed(&g_epoch) : 0u;
    if (warp) cluster_wait();
    unsigned int xbase = epoch * NLAYERS;
    auto wo_a = [&](int layer, int m1) {
      uint64_t ts = ((layer & 1) ? WO_A1 : WO_A0) >> (4 * m1), td = ((layer & 1) ? WO_DA1 : WO_DA0) >> (4 * m1), tk = WOORD >> (4 * m1);
      uint32_t ready = 0u;
#pragma unroll 1
      for (int m = m1; m < 16; ++m) {
        const int kb = (2 * g + (uint32_t)tk) & 15;
        uint32_t dst = sb + ((uint32_t)ts & 15) * SLOT, fb = bar + B_FULLT + m * 8, eb = bar + B_CONS + ((uint32_t)td & 15) * 8;
        int kc = kb * 64;
        ts >>= 4; td >>= 4; tk >>= 4;
        asm volatile("" : "+r"(dst), "+r"(fb), "+r"(eb), "+r"(kc));
        bool fr = false;
        if (!((ready >> kb) & 1)) {
          PROFT(m == 2 && lane == 0, 64 + layer * 16 + 2);
          fr = src_wait_tma(g_of + rb * 32, xbase + layer + 1, 1u << kb, ready, lane, eb, layer & 1);
          fence_async_all();
        }
        if (m == 6) mbar_wait_u(bar + B_EPI, layer & 1);
        if (!fr) mbar_wait_u(eb, layer & 1);
        tma_2d_e(dst, &tm_o, kc, m0, fb);
        PROFT(lane == 0 && layer == PL, 176 + m);
      }
    };
    auto wo_w = [&](int layer) {
      const CUtensorMap* tx = layer == 0 ? &tm_x0 : &tm_x;
      const CUtensorMap* two = (layer & 1) ? &tm_woB : &tm_woA;
      uint64_t ts = (layer & 1) ? WO_B1 : WO_B0, td = (layer & 1) ? WO_DB1 : WO_DB0, tk = WOORD;
      uint32_t pb = 0;
      fence_async_all();
      mbar_wait_u(bar + B_R0, layer & 1);
      expect_tx_e(bar + B_XOLD, 16384);
      tma_2d_e(sb + (XS + 1) * SLOT, tx, g * 128, m0, bar + B_XOLD);
#pragma unroll 1
      for (int m = 0; m < 16; ++m) {
        uint32_t dst = sb + ((uint32_t)ts & 15) * SLOT + cr * 8192, fb = bar + B_FULLT + m * 8, eb = bar + B_CONS + ((uint32_t)td & 15) * 8;
        int kc = ((2 * g + (uint32_t)tk) & 15) * 64;
        ts >>= 4; td >>= 4; tk >>= 4;
        asm volatile("" : "+r"(dst), "+r"(fb), "+r"(eb), "+r"(kc));
        if (eb < bar + B_E3 && pb >= bar + B_E3) mbar_wait_u(bar + B_E2, layer & 1);
        if (eb != pb) mbar_wait_u(eb, layer & 1);
        pb = eb;
        tma_2d_mc_e(dst, two, g * 128 + cr * 64, kc, fb);
        expect_tx_e(fb, m < 2 ? 16384 : 32768);
        PROFT(lane == 0 && layer == PL, 144 + m);
        if (m == ((layer & 1) ? 2 : 0)) {
          expect_tx_e(bar + B_XOLD2, 16384);
          tma_2d_e(sb + XS * SLOT, tx, g * 128 + 64, m0, bar + B_XOLD2);
        }
      }
    };
    if (warp == 0) {
      cluster_wait();
      PROFT(lane == 0, 125);
#pragma unroll 1
      for (int layer = 0; layer < NLAYERS; ++layer) {
        const CUtensorMap* tx = layer == 0 ? &tm_x0 : &tm_x;
        const CUtensorMap* tw = (layer & 1) ? &tm_wB : &tm_wA;
        uint32_t s = layer == 0, u = 0, ready = layer == 0 ? 0xFFFFu : 0u;
#pragma unroll 1
        for (int i = s; i < 16; ++i) {
          const int kb = layer == 0 ? kblock0(i, g) : wo_kblock(i, g), kc = kb * 64;
          const uint32_t fb = bar + B_FULLS + s * 8;
          const uint32_t kd = sb + (((QK >> (4 * s)) & 15) + cr) * SLOT, qd = sb + ((QQ >> (4 * s)) & 15) * SLOT + cr * 8192;
          const uint32_t need = 1u << kb;
          const bool ext = i >= 2 || layer == 0, early = ext && (ready & need) == need;
          mbar_wait_u(bar + B_EMPTYS + s * 8, (u + (s ? layer : 0) + 1) & 1);
          if (early) tma_2d_e(sb + ((QA >> (4 * s)) & 15) * SLOT, tx, kc, m0, fb);
          tma_2d_mc_e(kd, tw, 1024 + cr * 1024 + g * 128, kc, fb);
          tma_2d_mc_e(kd + 8192, tw, 1024 + cr * 1024 + g * 128 + 64, kc, fb);
          tma_2d_mc_e(qd, tw, g * 128 + cr * 64, kc, fb);
          expect_tx_e(fb, ext ? 65536 : 49152);
          PROFT(lane == 0 && layer == 0 && i == 1, 31);
          if (layer == 0 && g >= NCOM && i == XPF + (((g - NCOM) * XPM) >> 2)) {
            if (i <= 2) mbar_wait_u(bar + B_FULLS, 0);
            tma_pf_e(&tm_x0, g * 128, m0);
            tma_pf_e(&tm_x0, g * 128 + 64, m0);
          }
          if (layer < 2 && i >= PFS) {
            const int j = i - PFS;
            if (j < 2) tma_pf_e(layer ? &tm_woB : &tm_woA, g * 128 + j * 64, rb * 64);
            else if (j < 8 && layer == 0) tma_pf_e(&tm_wB, ((j >> 1) - 1) * 1024 + g * 128 + (j & 1) * 64, rb * 64);
          }
          if (ext && !early) {
            PROFT(i == 2 && lane == 0, 64 + layer * 16 + 0);
            src_wait_tma(g_xf + rb * 32, xbase + layer + 1, need, ready, lane, fb, 0);
            PROFT(i == 2 && lane == 0, 64 + layer * 16 + 1);
            fence_async_all();
            tma_2d_e(sb + ((QA >> (4 * s)) & 15) * SLOT, tx, kc, m0, fb);
          }
          if (++s == 3) { s = 0; ++u; }
        }
        if (layer == 0) xbase = ld_relaxed(&g_epoch) * NLAYERS;
        wo_a(layer, 2);
      }
    } else {
      if (warp >= 2) {
        const int h2 = threadIdx.x - 64;
        if (h2 < 16) sts_f(sb + SM_RS + h2 * 4, 0.f);
        if (h2 == 0) sts_f(sb + SM_EPOCH, __uint_as_float(epoch));
        mbar_wait_u(bar + B_FULLS, 0);
        colsum(&tm_wA, g_cs + (epoch & 1) * 6144, rb, g, warp - 2, 2, lane, warp == 2 ? sb + SM_SD : (sb + SM_BP + 1023u) & ~1023u, bar + B_CB + (warp - 2) * 8, 0);
#pragma unroll 1
        for (int i = h2; i < 320; i += 64) g_kv[(g * 16 + rb) * 320 + i] = make_uint4(0u, 0u, 0u, 0u);
        fence_async_all();
        nbar<5, 64>();
        if (h2 == 0) flag_add(&g_csflag[g].v);
        PROFT(h2 == 0, 242);
#pragma unroll 1
        for (int i = h2; i < 512; i += 256) {
          uint4 w[4];
#pragma unroll
          for (int j = 0; j < 4; ++j) w[j] = __ldg(reinterpret_cast<const uint4*>(wphi + (size_t)g * 4096) + i + j * 64);
#pragma unroll
          for (int j = 0; j < 4; ++j) sts128(sb + SM_WPHI + ((i >> 2) + j * 16) * 80 + (i & 3) * 16, w[j]);
        }
      }
      if (warp == 1) {
        if (lane >= 27) {
          const CUtensorMap* tm = lane == 27 ? &tm_o : lane == 28 ? &tm_wB : lane == 29 ? &tm_woA : lane == 30 ? &tm_woB : &tm_x;
          asm volatile("prefetch.tensormap [%0];" ::"l"(tm) : "memory");
        }
        __syncwarp();
        {
#pragma unroll 1
          for (int e = 0;; ++e) {
            if (e > 0 && e < NLAYERS) {
              mbar_wait_u(bar + B_XH0, (e - 1) & 1);
              flag_hint(g_xf + rb * 32 + 2 * g, xbase + e + 1);
            }
            mbar_wait_u(bar + B_XDONE, e & 1);
            PROFT(e < 4, 64 + e * 16 + 4);
            if (e == NLAYERS) {
              if (bid == 0) g_epoch = epoch + 1;
              break;
            }
            PROFT(e < 4, 64 + e * 16 + 5);
            flag_set(g_xf + rb * 32 + 2 * g + 1, xbase + e + 1);
            PROFT(e < 4, 64 + e * 16 + 7);
            if ((e & 1) == 0) {
#pragma unroll 1
              for (int hp = 0; hp < 2; ++hp) {
                uint4* kvl = g_kv + ((g * 2 + (e >> 1)) * 2 + hp) * 1280;
                mbar_wait_u(bar + B_KVDONE - hp * 32, (e >> 1) & 1);
                PROFT(e == PL, 243 + hp * 4);
                fence_async_smem();
                bulk_red_add_e(kvl + rb * 64, sb + (3 + hp) * SLOT + rb * 1024, 16384 - rb * 1024);
                if (rb) bulk_red_add_e(kvl, sb + (3 + hp) * SLOT, rb * 1024);
                bulk_red_add_e(kvl + 1024, sb + (6 + hp) * SLOT, 2048);
                bulk_red_add_e(kvl + 1152, sb + (6 + hp) * SLOT + 8192, 2048);
                bulk_commit();
                PROFT(e < 4, 64 + e * 16 + 6);
              }
              bulk_wait_read0();
              __syncwarp();
              if (lane < 2) release2(bar + B_E1);
              __syncwarp();
            }
            mbar_wait_u(bar + B_OH1, e & 1);
            PROFT(e == PL, 251);
            flag_hint(g_of + rb * 32 + 2 * g, xbase + e + 1);
            PROFT(e < 4, 64 + e * 16 + 9);
            mbar_wait_u(bar + B_ODONE, e & 1);
            PROFT(e < 4, 64 + e * 16 + 8);
            flag_hint(g_of + rb * 32 + 2 * g + 1, xbase + e + 1);
            PROFT(e < 4, 64 + e * 16 + 11);
          }
        }
      } else {
        const int h2 = threadIdx.x - 64;
        const float* cs = g_cs + (epoch & 1) * 6144;
#pragma unroll 1
        for (int layer = 0; layer < NLAYERS; ++layer) {
          if (warp == 2 && layer < 2) {
            if (lane == 0) flag_wait_t<128>(&g_csflag[layer * 8 + g].v, (epoch + 1) * (16u + layer));
            __syncwarp();
            float4 a[3];
#pragma unroll
            for (int i = 0; i < 3; ++i) a[i] = __ldcg(reinterpret_cast<const float4*>(cs + layer * 3072 + g * 384) + i * 32 + lane);
#pragma unroll 1
            for (int i = 0; i < 3; ++i) {
              const float av[4] = {a[0].x, a[0].y, a[0].z, a[0].w};
              a[0] = a[1]; a[1] = a[2];
#pragma unroll
              for (int j = 0; j < 4; ++j) {
                const float c1 = bf16r(av[j]), c2 = bf16r(av[j] - c1), c3 = (av[j] - c1) - c2;
                sts128(sb + SM_BP + layer * 6144 + ((i * 32 + lane) * 4 + j) * 16, make_uint4(pack_bf16(c1, c2), pack_bf16(c3, 0.f), 0u, 0u));
              }
            }
            fence_async_smem();
            __syncwarp();
            if (lane == 0) mbar_arrive(bar + (layer ? B_CS2 : B_CS));
            PROFT(lane == 0, 64 + layer * 16 + 12);
            if (layer == 0) {
              uint4* hz = g_halo + (rb * 8 + g) * 1024;
#pragma unroll 2
              for (int i = lane; i < 1024; i += 32) hz[i] = make_uint4(0u, 0u, 0u, 0u);
              if (lane < 12) reinterpret_cast<float4*>(g_cs + ((epoch & 1) ^ 1) * 6144 + bid * 48)[lane] = make_float4(0.f, 0.f, 0.f, 0.f);
              g_stats[(2 + (lane >> 4)) * S_ + m0 + g * 16 + (lane & 15)] = make_float2(0.f, 0.f);
              __syncwarp();
              if (lane == 0) flag_add(&g_csflag[8 + g].v);
            }
          }
          if (warp == 3) {
            const bool hal = (layer & 1) && rb > 0;
            {
              uint32_t rdy = 0u;
              src_wait<256>(g_xf + rb * 32, xbase + layer + 1, 0xAAAAu, rdy, lane);
              rdy = 0u;
              if (hal) src_wait<256>(g_xf + (rb - 1) * 32, xbase + layer + 1, 0xAAAAu, rdy, lane);
            }
            float2 u[5];
            const float2* sp = g_stats + layer * S_ + m0 + lane;
#pragma unroll
            for (int i = 0; i < 4; ++i) u[i] = __ldcg(sp + i * 32);
            u[4] = __ldcg(hal ? sp - 16 : sp);
            if (layer == 3) g_stats[(lane >> 4) * S_ + m0 + g * 16 + (lane & 15)] = make_float2(0.f, 0.f);
#pragma unroll
            for (int i = 0; i < 5; ++i) {
              const int r = i < 4 ? 16 + i * 32 + lane : lane;
              const float mean = u[i].x * (1.f / D_);
              const float var = fmaxf(fmaf(-u[i].x, mean, u[i].y) * (1.f / D_), 0.f);
              float sd;
              asm("sqrt.approx.f32 %0, %1;" : "=f"(sd) : "f"(bf16r(bf16r(var) + 1e-5f)));
              sd = bf16r(sd);
              if (i < 4 || hal) sts_f(sb + SM_RS + r * 4, rcp(sd));
              if (i < 4) {
                const float hm = -0.5f * bf16r(mean);
                const uint32_t s2 = pack_bf16(sd, sd);
                if (!(layer & 1)) sts128(sb + SM_SD + (r - 16) * 64 + ((r >> 1) & 3) * 16, make_uint4(s2, s2, s2, s2));
                sts128(sb + SM_AP + (r - 16) * 16, make_uint4(pack_bf16(hm, hm), pack_bf16(hm, 0.f), 0u, 0u));
              }
            }
            fence_async_smem();
            __syncwarp();
            if (lane == 0) mbar_arrive(bar + B_STAT);
            PROFT(lane == 0, 64 + layer * 16 + 14);
            wo_w(__shfl_sync(0xffffffffu, layer, 0));
          }
        }
      }
    }
    __syncwarp();
    asm volatile("barrier.cluster.arrive.relaxed.aligned;\nbarrier.cluster.wait.aligned;\n" ::: "memory");
  } else {
    if (warp == 5) {
      if (lane == 0) {
        mbar_init(bar + B_FULLS, 1);
        asm volatile("fence.mbarrier_init.release.cluster;" ::: "memory");
      }
      __syncwarp();
      expect_tx_e(bar + B_FULLS, 65536);
      const int kc0 = (g || !K0V) ? 0 : 128;
      tma_2d_e(sb + XS * SLOT, &tm_x0, kc0, m0, bar + B_FULLS);
#pragma unroll
      for (int j = 0; j < 6; ++j)
        tma_2d_e(sb + (j < 4 ? j + 4 : j - 2) * 8192, &tm_wA, (j < 4 ? 1024 + (j >> 1) * 1024 : 0) + g * 128 + (j & 1) * 64, kc0, bar + B_FULLS);
      PROFT(lane == 0, 241);
    }
    if (lane < 8 && warp != 5 && threadIdx.x != 128) {
      const int i = (warp - 4) * 8 + lane;
      mbar_init(bar + i * 8, i < 32 ? 1u << ((BAR_CNT >> (2 * i)) & 3) : i < 48 ? 1u : (i == 59 || i == 60 || i == 62) ? 16u : (i == 48 || i == 63) ? 8u : 4u);
      asm volatile("fence.mbarrier_init.release.cluster;" ::: "memory");
    }
    __syncwarp();
    asm volatile("barrier.cluster.arrive.relaxed.aligned;" ::: "memory");
    asm volatile("setmaxnreg.inc.sync.aligned.u32 232;");
    cluster_wait();
    PROFT(threadIdx.x == 128, 0);
    Ctx c; c.sb = sb; c.g = g; c.rb = rb; c.cu = warp - 4; c.out = out;
    consumer(c);
    asm volatile("bar.warp.sync 0xffffffff;\nbarrier.cluster.arrive.relaxed.aligned;\nbarrier.cluster.wait.aligned;\n" ::: "memory");
  }
}

typedef CUresult (*PFN_encodeTiled)(CUtensorMap*, CUtensorMapDataType, cuuint32_t, void*, const cuuint64_t*, const cuuint64_t*,
                                    const cuuint32_t*, const cuuint32_t*, CUtensorMapInterleave, CUtensorMapSwizzle,
                                    CUtensorMapL2promotion, CUtensorMapFloatOOBfill);

static CUtensorMap make_map(PFN_encodeTiled enc, const void* ptr, uint64_t cols, uint64_t rows, uint32_t box_c, uint32_t box_r, uint32_t nb = 1) {
  CUtensorMap m;
  cuuint64_t dims[3] = {nb > 1 ? box_c : cols, rows, cols / box_c};
  cuuint64_t strides[2] = {cols * 2, box_c * 2};
  cuuint32_t box[3] = {box_c, box_r, nb};
  cuuint32_t es[3] = {1, 1, 1};
  CUresult r = enc(&m, CU_TENSOR_MAP_DATA_TYPE_BFLOAT16, nb > 1 ? 3 : 2, const_cast<void*>(ptr), dims, strides, box, es, CU_TENSOR_MAP_INTERLEAVE_NONE,
      CU_TENSOR_MAP_SWIZZLE_128B, CU_TENSOR_MAP_L2_PROMOTION_L2_256B, CU_TENSOR_MAP_FLOAT_OOB_FILL_NONE);
  (void)r;
  return m;
}

extern "C" void kernel_launch(void* const* d_in, const int* in_sizes, int n_in, void* d_out, int out_size) {
  const bf16* A_x = (const bf16*)d_in[0];
  const bf16* A_wqkv = (const bf16*)d_in[1];
  const bf16* A_wphi = (const bf16*)d_in[2];
  const bf16* A_wo = (const bf16*)d_in[3];
  const bf16* B_wqkv = (const bf16*)d_in[5];
  const bf16* B_wo = (const bf16*)d_in[6];
  bf16* out = (bf16*)d_out;

  static PFN_encodeTiled enc = nullptr;
  static bf16 *p_x, *p_o;
  static bool together;
  if (!enc) {
    void* fn = nullptr; cudaDriverEntryPointQueryResult qr;
    cudaGetDriverEntryPoint("cuTensorMapEncodeTiled", &fn, cudaEnableDefault, &qr);
    enc = (PFN_encodeTiled)fn;
    cudaGetSymbolAddress((void**)&p_x, g_x);
    cudaGetSymbolAddress((void**)&p_o, g_o);
    cudaFuncSetAttribute(mega_kernel, cudaFuncAttributeMaxDynamicSharedMemorySize, SM_TOTAL);
    cudaLaunchConfig_t cfg = {};
    cfg.gridDim = dim3(128 + NX); cfg.blockDim = dim3(384); cfg.dynamicSmemBytes = SM_TOTAL;
    cudaLaunchAttribute at[1];
    at[0].id = cudaLaunchAttributeClusterDimension; at[0].val.clusterDim.x = 2; at[0].val.clusterDim.y = 1; at[0].val.clusterDim.z = 1;
    cfg.attrs = at; cfg.numAttrs = 1;
    int ncl = 0;
    together = cudaOccupancyMaxActiveClusters(&ncl, mega_kernel, &cfg) == cudaSuccess && 2 * ncl == 128 + NX;
    int nsm = 0;
    cudaDeviceGetAttribute(&nsm, cudaDevAttrMultiProcessorCount, 0);
    together = together && nsm == 128 + NX;
  }
  CUtensorMap tm_x0 = make_map(enc, A_x, 1024, 2048, 64, 128);
  CUtensorMap tm_x = make_map(enc, p_x, 1024, 2048, 64, 128);
  CUtensorMap tm_o = make_map(enc, p_o, 1024, 2048, 64, 128);
  CUtensorMap tm_wA = make_map(enc, A_wqkv, 3072, 1024, 64, 64);
  CUtensorMap tm_wB = make_map(enc, B_wqkv, 3072, 1024, 64, 64);
  CUtensorMap tm_woA = make_map(enc, A_wo, 1024, 1024, 64, 64);
  CUtensorMap tm_woB = make_map(enc, B_wo, 1024, 1024, 64, 64);
  if (!together) mega_kernel<<<NX, 384, SM_TOTAL, cudaStreamPerThread>>>(tm_x0, tm_x, tm_o, tm_wA, tm_wB, tm_woA, tm_woB, B_wqkv, A_wphi, out);
  mega_kernel<<<together ? 128 + NX : 128, 384, SM_TOTAL, cudaStreamPerThread>>>(tm_x0, tm_x, tm_o, tm_wA, tm_wB, tm_woA, tm_woB,
                                                                                 B_wqkv, A_wphi, out);
}
```

```cpp
#include <cuda_runtime.h>
#include <cuda_bf16.h>
#include <cuda.h>
#include <stdint.h>

typedef __nv_bfloat16 bf16;

constexpr int S_ = 2048, D_ = 1024;

struct __align__(128) Flag { unsigned int v; unsigned int pad[31]; };
__device__ __align__(1024) bf16 g_x[S_ * D_];
__device__ __align__(1024) bf16 g_o[S_ * D_];
__device__ __align__(1024) uint4 g_halo[128 * 2 * 512];
__device__ __align__(1024) uint4 g_kv[8 * 2 * 2 * 1280];
__device__ __align__(1024) float2 g_stats[4 * S_];
__device__ __align__(1024) float g_cs[2 * 2 * 3072];
__device__ Flag g_csflag[16];
__device__ __align__(128) unsigned int g_xf[16 * 32], g_of[16 * 32];
__device__ unsigned int g_epoch, g_err;
#define PROFT(cond, idx) asm volatile("" ::: "memory")

__device__ __forceinline__ uint32_t smem_u32(const void* p) { return (uint32_t)__cvta_generic_to_shared(p); }
__device__ __forceinline__ void mbar_init(uint32_t bar, uint32_t count) {
  asm volatile("mbarrier.init.shared::cta.b64 [%0], %1;" ::"r"(bar), "r"(count) : "memory");
}
__device__ __forceinline__ void mbar_expect_tx(uint32_t bar, uint32_t bytes) {
  asm volatile("mbarrier.arrive.expect_tx.shared::cta.b64 _, [%0], %1;" ::"r"(bar), "r"(bytes) : "memory");
}
__device__ __forceinline__ void mbar_arrive(uint32_t bar) {
  asm volatile("mbarrier.arrive.shared::cta.b64 _, [%0];" ::"r"(bar) : "memory");
}
__device__ __forceinline__ bool mbar_try_wait(uint32_t bar, uint32_t parity) {
  uint32_t ok;
  asm volatile("{\n.reg .pred p;\nmbarrier.try_wait.parity.shared::cta.b64 p, [%1], %2;\nselp.b32 %0, 1, 0, p;\n}\n"
               : "=r"(ok) : "r"(bar), "r"(parity) : "memory");
  return ok != 0;
}
__device__ __forceinline__ bool mbar_test_wait(uint32_t bar, uint32_t parity) {
  uint32_t ok;
  asm volatile("{\n.reg .pred p;\nmbarrier.test_wait.parity.shared::cta.b64 p, [%1], %2;\nselp.b32 %0, 1, 0, p;\n}\n"
               : "=r"(ok) : "r"(bar), "r"(parity) : "memory");
  return ok != 0;
}
__device__ __forceinline__ uint64_t gtimer() {
  uint64_t t; asm volatile("mov.u64 %0, %globaltimer;" : "=l"(t)); return t;
}
__device__ __forceinline__ void mbar_wait(uint32_t bar, uint32_t parity) {
  uint32_t n = 0;
#pragma unroll 1
  while (!mbar_try_wait(bar, parity)) {
    if (++n > (1u << 22)) { g_err = 1u; break; }
  }
}
__device__ __forceinline__ unsigned int ld_acquire(const unsigned int* p) {
  unsigned int v; asm volatile("ld.acquire.gpu.global.u32 %0, [%1];" : "=r"(v) : "l"(p) : "memory"); return v;
}
__device__ __forceinline__ void flag_add(unsigned int* p) {
  asm volatile("red.release.gpu.global.add.u32 [%0], 1;" ::"l"(p) : "memory");
}
__device__ __forceinline__ void flag_set(unsigned int* p, unsigned int v) {
  asm volatile("st.release.gpu.global.u32 [%0], %1;" ::"l"(p), "r"(v) : "memory");
}
__device__ __forceinline__ void flag_hint(unsigned int* p, unsigned int v) {
  asm volatile("st.relaxed.gpu.global.u32 [%0], %1;" ::"l"(p), "r"(v) : "memory");
}
template <int SLEEP>
__device__ __forceinline__ void src_wait(const unsigned int* f, unsigned int target, uint32_t need, uint32_t& ready, int lane) {
  uint32_t n = 0;
#pragma unroll 1
  while ((ready & need) != need) {
    const unsigned int v = ld_acquire(f + (lane & 15));
    ready = __ballot_sync(0xffffffffu, (int)(v - target) >= 0);
    if (SLEEP) { if ((ready & need) != need) __nanosleep(SLEEP); }
    if (++n > (1u << 20)) { g_err = 3u; break; }
  }
  __syncwarp();
}
__device__ __forceinline__ unsigned int ld_relaxed(const unsigned int* p) {
  unsigned int v; asm volatile("ld.relaxed.gpu.global.u32 %0, [%1];" : "=r"(v) : "l"(p) : "memory"); return v;
}
__device__ __forceinline__ bool src_wait_tma(const unsigned int* f, unsigned int target, uint32_t need, uint32_t& ready, int lane, uint32_t eb, uint32_t par) {
  uint32_t n = 0;
  bool fr = false;
#pragma unroll 1
  while ((ready & need) != need) {
    const unsigned int v = ld_acquire(f + (lane & 15));
    fr = __all_sync(0xffffffffu, mbar_test_wait(eb, par));
    ready = __ballot_sync(0xffffffffu, (int)(v - target) >= 0);
    if (++n > (1u << 20)) { g_err = 3u; break; }
  }
  return fr;
}
__device__ __forceinline__ uint4 ld_relaxed4(const uint4* p) {
  uint4 v; asm volatile("ld.relaxed.gpu.global.v4.u32 {%0,%1,%2,%3}, [%4];" : "=r"(v.x), "=r"(v.y), "=r"(v.z), "=r"(v.w) : "l"(p) : "memory"); return v;
}
__device__ __forceinline__ void st_relaxed4(uint4* p, uint32_t a, uint32_t b, uint32_t c, uint32_t d) {
  asm volatile("st.relaxed.gpu.global.v4.u32 [%0], {%1,%2,%3,%4};" ::"l"(p), "r"(a), "r"(b), "r"(c), "r"(d) : "memory");
}
template <int SLEEP>
__device__ __forceinline__ void flag_wait_t(const unsigned int* p, unsigned int target) {
  uint32_t n = 0;
#pragma unroll 1
  while ((int)(ld_acquire(p) - target) < 0) {
    if (SLEEP) __nanosleep(SLEEP);
    if (++n > (1u << 20)) { g_err = 2u; break; }
  }
}
__device__ __forceinline__ void flag_wait(const unsigned int* p, unsigned int target) { flag_wait_t<0>(p, target); }
__device__ __forceinline__ void flag_wait_slow(const unsigned int* p, unsigned int target) { flag_wait_t<256>(p, target); }
__device__ __forceinline__ void tma_load_2d(uint32_t dst, const CUtensorMap* tm, int c0, int c1, uint32_t bar) {
  asm volatile("cp.async.bulk.tensor.2d.shared::cluster.global.mbarrier::complete_tx::bytes [%0], [%1, {%2, %3}], [%4];"
               ::"r"(dst), "l"(tm), "r"(c0), "r"(c1), "r"(bar) : "memory");
}
__device__ __forceinline__ void tma_load_2d_mc(uint32_t dst, const CUtensorMap* tm, int c0, int c1, uint32_t bar, uint16_t mask) {
  asm volatile("cp.async.bulk.tensor.2d.shared::cluster.global.mbarrier::complete_tx::bytes.multicast::cluster [%0], [%1, {%2, %3}], [%4], %5;"
               ::"r"(dst), "l"(tm), "r"(c0), "r"(c1), "r"(bar), "h"(mask) : "memory");
}
__device__ __forceinline__ void mbar_wait_u(uint32_t bar, uint32_t parity) {
  uint32_t n = 0;
#pragma unroll 1
  while (!__all_sync(0xffffffffu, mbar_try_wait(bar, parity))) {
    if (++n > (1u << 22)) { g_err = 1u; break; }
  }
}
__device__ __forceinline__ void expect_tx_e(uint32_t bar, uint32_t bytes) {
  asm volatile("{\n.reg .pred p;\nelect.sync _|p, 0xffffffff;\n@p mbarrier.arrive.expect_tx.shared::cta.b64 _, [%0], %1;\n}\n" ::"r"(bar), "r"(bytes) : "memory");
}
__device__ __forceinline__ void tma_2d_e(uint32_t dst, const CUtensorMap* tm, int c0, int c1, uint32_t bar) {
  asm volatile("{\n.reg .pred p;\nelect.sync _|p, 0xffffffff;\n"
               "@p cp.async.bulk.tensor.2d.shared::cluster.global.mbarrier::complete_tx::bytes [%0], [%1, {%2, %3}], [%4];\n}\n"
               ::"r"(dst), "l"(tm), "r"(c0), "r"(c1), "r"(bar) : "memory");
}
__device__ __forceinline__ void tma_2d_mc_e(uint32_t dst, const CUtensorMap* tm, int c0, int c1, uint32_t bar) {
  asm volatile("{\n.reg .pred p;\nelect.sync _|p, 0xffffffff;\n"
               "@p cp.async.bulk.tensor.2d.shared::cluster.global.mbarrier::complete_tx::bytes.multicast::cluster [%0], [%1, {%2, %3}], [%4], %5;\n}\n"
               ::"r"(dst), "l"(tm), "r"(c0), "r"(c1), "r"(bar), "h"((uint16_t)3) : "memory");
}
__device__ __forceinline__ void tma_pf_e(const CUtensorMap* tm, int c0, int c1) {
  asm volatile("{\n.reg .pred p;\nelect.sync _|p, 0xffffffff;\n"
               "@p cp.async.bulk.prefetch.tensor.2d.L2.global.tile [%0, {%1, %2}];\n}\n" ::"l"(tm), "r"(c0), "r"(c1) : "memory");
}
__device__ __forceinline__ void tma_2d_to_e(uint32_t dst, const CUtensorMap* tm, int c0, int c1, uint32_t bar, uint32_t mask) {
  asm volatile("{\n.reg .pred p;\nelect.sync _|p, 0xffffffff;\n"
               "@p cp.async.bulk.tensor.2d.shared::cluster.global.mbarrier::complete_tx::bytes.multicast::cluster [%0], [%1, {%2, %3}], [%4], %5;\n}\n"
               ::"r"(dst), "l"(tm), "r"(c0), "r"(c1), "r"(bar), "h"((uint16_t)mask) : "memory");
}
__device__ __forceinline__ void tma_3d_mc_e(uint32_t dst, const CUtensorMap* tm, int c1, int c2, uint32_t bar) {
  asm volatile("{\n.reg .pred p;\nelect.sync _|p, 0xffffffff;\n"
               "@p cp.async.bulk.tensor.3d.shared::cluster.global.mbarrier::complete_tx::bytes.multicast::cluster [%0], [%1, {%6, %2, %3}], [%4], %5;\n}\n"
               ::"r"(dst), "l"(tm), "r"(c1), "r"(c2), "r"(bar), "h"((uint16_t)3), "r"(0) : "memory");
}
__device__ __forceinline__ uint32_t poll_flags(const unsigned int* f, unsigned int target, int lane) {
  const unsigned int v = ld_acquire(f + (lane & 15));
  const uint32_t r = __ballot_sync(0xffffffffu, (int)(v - target) >= 0);
  __syncwarp();
  return r;
}
__device__ __forceinline__ void mbar_arrive_cluster(uint32_t local_bar, uint32_t rank) {
  asm volatile("{\n.reg .b32 ra;\nmapa.shared::cluster.u32 ra, %0, %1;\nmbarrier.arrive.shared::cluster.b64 _, [ra];\n}\n"
               ::"r"(local_bar), "r"(rank) : "memory");
}
__device__ __forceinline__ void release2(uint32_t bar) { mbar_arrive_cluster(bar, 0); mbar_arrive_cluster(bar, 1); }
__device__ __forceinline__ void tma_store_2d(const CUtensorMap* tm, uint32_t src, int c0, int c1) {
  asm volatile("cp.async.bulk.tensor.2d.global.shared::cta.bulk_group [%0, {%2, %3}], [%1];"
               ::"l"(tm), "r"(src), "r"(c0), "r"(c1) : "memory");
}
__device__ __forceinline__ void bulk_store(void* dst, uint32_t src, uint32_t bytes) {
  asm volatile("cp.async.bulk.global.shared::cta.bulk_group [%0], [%1], %2;" ::"l"(dst), "r"(src), "r"(bytes) : "memory");
}
__device__ __forceinline__ void bulk_load(uint32_t dst, const void* src, uint32_t bytes, uint32_t bar) {
  asm volatile("cp.async.bulk.shared::cluster.global.mbarrier::complete_tx::bytes [%0], [%1], %2, [%3];" ::"r"(dst), "l"(src), "r"(bytes), "r"(bar) : "memory");
}
__device__ __forceinline__ void bulk_red_add(void* dst, uint32_t src, uint32_t bytes) {
  asm volatile("cp.reduce.async.bulk.global.shared::cta.bulk_group.add.f32 [%0], [%1], %2;" ::"l"(dst), "r"(src), "r"(bytes) : "memory");
}
__device__ __forceinline__ void bulk_red_add_e(void* dst, uint32_t src, uint32_t bytes) {
  asm volatile("{\n.reg .pred p;\nelect.sync _|p, 0xffffffff;\n@p cp.reduce.async.bulk.global.shared::cta.bulk_group.add.f32 [%0], [%1], %2;\n}\n" ::"l"(dst), "r"(src), "r"(bytes) : "memory");
}
__device__ __forceinline__ void bulk_commit() { asm volatile("cp.async.bulk.commit_group;" ::: "memory"); }
__device__ __forceinline__ void bulk_wait_read0() { asm volatile("cp.async.bulk.wait_group.read 0;" ::: "memory"); }
__device__ __forceinline__ void bulk_wait0() { asm volatile("cp.async.bulk.wait_group 0;" ::: "memory"); }
__device__ __forceinline__ void fence_async_smem() { asm volatile("fence.proxy.async.shared::cta;" ::: "memory"); }
__device__ __forceinline__ void fence_async_all() { asm volatile("fence.proxy.async.global;" ::: "memory"); }
__device__ __forceinline__ void wgmma_fence() { asm volatile("wgmma.fence.sync.aligned;" ::: "memory"); }
__device__ __forceinline__ void wgmma_commit() { asm volatile("wgmma.commit_group.sync.aligned;" ::: "memory"); }
template <int N> __device__ __forceinline__ void wgmma_wait() { asm volatile("wgmma.wait_group.sync.aligned %0;" ::"n"(N) : "memory"); }
__device__ __forceinline__ void cluster_arrive() { asm volatile("barrier.cluster.arrive.release.aligned;" ::: "memory"); }
__device__ __forceinline__ void cluster_wait() { asm volatile("barrier.cluster.wait.acquire.aligned;" ::: "memory"); }
template <int ID, int N> __device__ __forceinline__ void nbar() { asm volatile("bar.sync %0, %1;" ::"n"(ID), "n"(N) : "memory"); }
__device__ __forceinline__ uint64_t make_desc(uint32_t addr, uint32_t lbo_bytes, uint32_t sbo_bytes) {
  uint64_t d = 0;
  d |= (uint64_t)((addr & 0x3FFFF) >> 4);
  d |= (uint64_t)((lbo_bytes >> 4) & 0x3FFF) << 16;
  d |= (uint64_t)((sbo_bytes >> 4) & 0x3FFF) << 32;
  d |= (uint64_t)1 << 62;
  return d;
}
__device__ __forceinline__ uint64_t desc64(uint32_t lo, uint32_t hi) { return (uint64_t)lo | ((uint64_t)hi << 32); }
__device__ __forceinline__ uint32_t pack_bf16(float lo, float hi) {
  uint32_t r; asm("cvt.rn.bf16x2.f32 %0, %1, %2;" : "=r"(r) : "f"(hi), "f"(lo)); return r;
}
__device__ __forceinline__ uint32_t mul_bf16x2(uint32_t a, uint32_t s, bool hi) {
  __nv_bfloat162 x = *reinterpret_cast<__nv_bfloat162*>(&a), y = *reinterpret_cast<__nv_bfloat162*>(&s);
  x = __hmul2(x, hi ? __high2bfloat162(y) : __low2bfloat162(y));
  return *reinterpret_cast<uint32_t*>(&x);
}
__device__ __forceinline__ float bf16r(float x) { return __bfloat162float(__float2bfloat16_rn(x)); }
__device__ __forceinline__ float bf_lo(uint32_t u) { return __uint_as_float(u << 16); }
__device__ __forceinline__ float bf_hi(uint32_t u) { return __uint_as_float(u & 0xFFFF0000u); }
__device__ __forceinline__ float ex2(float x) { float r; asm("ex2.approx.ftz.f32 %0, %1;" : "=f"(r) : "f"(x)); return r; }
__device__ __forceinline__ float rcp(float x) { float r; asm("rcp.approx.ftz.f32 %0, %1;" : "=f"(r) : "f"(x)); return r; }
__device__ __forceinline__ void mma_bf16(float (&d)[4], uint32_t a0, uint32_t a1, uint32_t a2, uint32_t a3, uint32_t b0, uint32_t b1) {
  asm("mma.sync.aligned.m16n8k16.row.col.f32.bf16.bf16.f32 {%0,%1,%2,%3}, {%4,%5,%6,%7}, {%8,%9}, {%0,%1,%2,%3};"
               : "+f"(d[0]), "+f"(d[1]), "+f"(d[2]), "+f"(d[3]) : "r"(a0), "r"(a1), "r"(a2), "r"(a3), "r"(b0), "r"(b1));
}
__device__ __forceinline__ void ldsm_x4(uint32_t& r0, uint32_t& r1, uint32_t& r2, uint32_t& r3, uint32_t addr) {
  asm volatile("ldmatrix.sync.aligned.m8n8.x4.shared.b16 {%0,%1,%2,%3}, [%4];"
               : "=r"(r0), "=r"(r1), "=r"(r2), "=r"(r3) : "r"(addr) : "memory");
}
__device__ __forceinline__ void ldsm_x4_t(uint32_t& r0, uint32_t& r1, uint32_t& r2, uint32_t& r3, uint32_t addr) {
  asm volatile("ldmatrix.sync.aligned.m8n8.x4.trans.shared.b16 {%0,%1,%2,%3}, [%4];"
               : "=r"(r0), "=r"(r1), "=r"(r2), "=r"(r3) : "r"(addr) : "memory");
}
__device__ __forceinline__ void ldsm_x2_t(uint32_t& r0, uint32_t& r1, uint32_t addr) {
  asm volatile("ldmatrix.sync.aligned.m8n8.x2.trans.shared.b16 {%0,%1}, [%2];"
               : "=r"(r0), "=r"(r1) : "r"(addr) : "memory");
}
__device__ __forceinline__ void stsm_x4(uint32_t addr, uint32_t r0, uint32_t r1, uint32_t r2, uint32_t r3) {
  asm volatile("stmatrix.sync.aligned.m8n8.x4.shared.b16 [%0], {%1,%2,%3,%4};"
               ::"r"(addr), "r"(r0), "r"(r1), "r"(r2), "r"(r3) : "memory");
}
__device__ __forceinline__ void stsm_x4_p(bool on, uint32_t addr, uint32_t r0, uint32_t r1, uint32_t r2, uint32_t r3) {
  asm volatile("{\n.reg .pred p;\nsetp.ne.b32 p, %5, 0;\n@p stmatrix.sync.aligned.m8n8.x4.shared.b16 [%0], {%1,%2,%3,%4};\n}\n"
               ::"r"(addr), "r"(r0), "r"(r1), "r"(r2), "r"(r3), "r"((int)on) : "memory");
}
__device__ __forceinline__ float2 lds_f2(uint32_t addr) {
  float2 v; asm volatile("ld.shared.v2.f32 {%0,%1}, [%2];" : "=f"(v.x), "=f"(v.y) : "r"(addr) : "memory"); return v;
}
__device__ __forceinline__ uint4 lds128(uint32_t addr) {
  uint4 v; asm volatile("ld.shared.v4.b32 {%0,%1,%2,%3}, [%4];" : "=r"(v.x), "=r"(v.y), "=r"(v.z), "=r"(v.w) : "r"(addr) : "memory"); return v;
}
__device__ __forceinline__ void sts128(uint32_t addr, uint4 v) {
  asm volatile("st.shared.v4.b32 [%0], {%1,%2,%3,%4};" ::"r"(addr), "r"(v.x), "r"(v.y), "r"(v.z), "r"(v.w) : "memory");
}
__device__ __forceinline__ float lds_f(uint32_t addr) {
  float v; asm volatile("ld.shared.f32 %0, [%1];" : "=f"(v) : "r"(addr) : "memory"); return v;
}
__device__ __forceinline__ uint32_t lds_vol(uint32_t addr) {
  uint32_t v; asm volatile("ld.volatile.shared.u32 %0, [%1];" : "=r"(v) : "r"(addr) : "memory"); return v;
}
__device__ __forceinline__ void sts16(uint32_t addr, uint32_t v) {
  asm volatile("st.shared.u16 [%0], %1;" ::"r"(addr), "h"((unsigned short)v) : "memory");
}
__device__ __forceinline__ void nbar_dyn(int id, int n) { asm volatile("bar.sync %0, %1;" ::"r"(id), "r"(n) : "memory"); }
__device__ __forceinline__ uint64_t make_desc_ns(uint32_t addr, uint32_t lbo_bytes, uint32_t sbo_bytes) {
  return (uint64_t)((addr & 0x3FFFF) >> 4) | ((uint64_t)(lbo_bytes >> 4) << 16) | ((uint64_t)(sbo_bytes >> 4) << 32);
}
__device__ __forceinline__ void sts_f(uint32_t addr, float v) { asm volatile("st.shared.f32 [%0], %1;" ::"r"(addr), "f"(v) : "memory"); }
__device__ __forceinline__ void sts64(uint32_t addr, uint32_t a, uint32_t b) {
  asm volatile("st.shared.v2.b32 [%0], {%1,%2};" ::"r"(addr), "r"(a), "r"(b) : "memory");
}
__device__ __forceinline__ void sts_f2(uint32_t addr, float a, float b) {
  asm volatile("st.shared.v2.f32 [%0], {%1,%2};" ::"r"(addr), "f"(a), "f"(b) : "memory");
}
__device__ __forceinline__ void red_add2(float* p, float a, float b) {
  asm volatile("red.global.add.v2.f32 [%0], {%1,%2};" ::"l"(p), "f"(a), "f"(b) : "memory");
}
__device__ __forceinline__ void red_add4(float* p, float a, float b, float c, float d) {
  asm volatile("red.global.add.v4.f32 [%0], {%1,%2,%3,%4};" ::"l"(p), "f"(a), "f"(b), "f"(c), "f"(d) : "memory");
}
__device__ __forceinline__ void red_add1(float* p, float a) {
  asm volatile("red.global.add.f32 [%0], %1;" ::"l"(p), "f"(a) : "memory");
}
__device__ __forceinline__ void l2_prefetch(const void* p, uint32_t bytes) {
  asm volatile("cp.async.bulk.prefetch.L2.global [%0], %1;" ::"l"(p), "r"(bytes) : "memory");
}

__device__ __forceinline__ void wgmma_n256(float (&d)[192], uint64_t da, uint64_t db, int scale_d) {
  asm volatile("{\n.reg .pred p;\nsetp.ne.b32 p, %130, 0;\n"
    "wgmma.mma_async.sync.aligned.m64n256k16.f32.bf16.bf16 {%0, %1, %2, %3, %4, %5, %6, %7, %8, %9, %10, %11, %12, %13, %14, %15, %16, %17, %18, %19, %20, %21, %22, %23, %24, %25, %26, %27, %28, %29, %30, %31, %32, %33, %34, %35, %36, %37, %38, %39, %40, %41, %42, %43, %44, %45, %46, %47, %48, %49, %50, %51, %52, %53, %54, %55, %56, %57, %58, %59, %60, %61, %62, %63, %64, %65, %66, %67, %68, %69, %70, %71, %72, %73, %74, %75, %76, %77, %78, %79, %80, %81, %82, %83, %84, %85, %86, %87, %88, %89, %90, %91, %92, %93, %94, %95, %96, %97, %98, %99, %100, %101, %102, %103, %104, %105, %106, %107, %108, %109, %110, %111, %112, %113, %114, %115, %116, %117, %118, %119, %120, %121, %122, %123, %124, %125, %126, %127}, %128, %129, p, 1, 1, 0, 1;\n}\n"
    : "+f"(d[0]), "+f"(d[1]), "+f"(d[2]), "+f"(d[3]), "+f"(d[4]), "+f"(d[5]), "+f"(d[6]), "+f"(d[7]), "+f"(d[8]), "+f"(d[9]), "+f"(d[10]), "+f"(d[11]), "+f"(d[12]), "+f"(d[13]), "+f"(d[14]), "+f"(d[15]), "+f"(d[16]), "+f"(d[17]), "+f"(d[18]), "+f"(d[19]), "+f"(d[20]), "+f"(d[21]), "+f"(d[22]), "+f"(d[23]), "+f"(d[24]), "+f"(d[25]), "+f"(d[26]), "+f"(d[27]), "+f"(d[28]), "+f"(d[29]), "+f"(d[30]), "+f"(d[31]), "+f"(d[32]), "+f"(d[33]), "+f"(d[34]), "+f"(d[35]), "+f"(d[36]), "+f"(d[37]), "+f"(d[38]), "+f"(d[39]), "+f"(d[40]), "+f"(d[41]), "+f"(d[42]), "+f"(d[43]), "+f"(d[44]), "+f"(d[45]), "+f"(d[46]), "+f"(d[47]), "+f"(d[48]), "+f"(d[49]), "+f"(d[50]), "+f"(d[51]), "+f"(d[52]), "+f"(d[53]), "+f"(d[54]), "+f"(d[55]), "+f"(d[56]), "+f"(d[57]), "+f"(d[58]), "+f"(d[59]), "+f"(d[60]), "+f"(d[61]), "+f"(d[62]), "+f"(d[63]), "+f"(d[64]), "+f"(d[65]), "+f"(d[66]), "+f"(d[67]), "+f"(d[68]), "+f"(d[69]), "+f"(d[70]), "+f"(d[71]), "+f"(d[72]), "+f"(d[73]), "+f"(d[74]), "+f"(d[75]), "+f"(d[76]), "+f"(d[77]), "+f"(d[78]), "+f"(d[79]), "+f"(d[80]), "+f"(d[81]), "+f"(d[82]), "+f"(d[83]), "+f"(d[84]), "+f"(d[85]), "+f"(d[86]), "+f"(d[87]), "+f"(d[88]), "+f"(d[89]), "+f"(d[90]), "+f"(d[91]), "+f"(d[92]), "+f"(d[93]), "+f"(d[94]), "+f"(d[95]), "+f"(d[96]), "+f"(d[97]), "+f"(d[98]), "+f"(d[99]), "+f"(d[100]), "+f"(d[101]), "+f"(d[102]), "+f"(d[103]), "+f"(d[104]), "+f"(d[105]), "+f"(d[106]), "+f"(d[107]), "+f"(d[108]), "+f"(d[109]), "+f"(d[110]), "+f"(d[111]), "+f"(d[112]), "+f"(d[113]), "+f"(d[114]), "+f"(d[115]), "+f"(d[116]), "+f"(d[117]), "+f"(d[118]), "+f"(d[119]), "+f"(d[120]), "+f"(d[121]), "+f"(d[122]), "+f"(d[123]), "+f"(d[124]), "+f"(d[125]), "+f"(d[126]), "+f"(d[127])
    : "l"(da), "l"(db), "r"(scale_d));
}
__device__ __forceinline__ void wgmma_n128(float (&d)[192], uint64_t da, uint64_t db, int scale_d) {
  asm volatile("{\n.reg .pred p;\nsetp.ne.b32 p, %66, 0;\n"
    "wgmma.mma_async.sync.aligned.m64n128k16.f32.bf16.bf16 {%0, %1, %2, %3, %4, %5, %6, %7, %8, %9, %10, %11, %12, %13, %14, %15, %16, %17, %18, %19, %20, %21, %22, %23, %24, %25, %26, %27, %28, %29, %30, %31, %32, %33, %34, %35, %36, %37, %38, %39, %40, %41, %42, %43, %44, %45, %46, %47, %48, %49, %50, %51, %52, %53, %54, %55, %56, %57, %58, %59, %60, %61, %62, %63}, %64, %65, p, 1, 1, 0, 1;\n}\n"
    : "+f"(d[128]), "+f"(d[129]), "+f"(d[130]), "+f"(d[131]), "+f"(d[132]), "+f"(d[133]), "+f"(d[134]), "+f"(d[135]), "+f"(d[136]), "+f"(d[137]), "+f"(d[138]), "+f"(d[139]), "+f"(d[140]), "+f"(d[141]), "+f"(d[142]), "+f"(d[143]), "+f"(d[144]), "+f"(d[145]), "+f"(d[146]), "+f"(d[147]), "+f"(d[148]), "+f"(d[149]), "+f"(d[150]), "+f"(d[151]), "+f"(d[152]), "+f"(d[153]), "+f"(d[154]), "+f"(d[155]), "+f"(d[156]), "+f"(d[157]), "+f"(d[158]), "+f"(d[159]), "+f"(d[160]), "+f"(d[161]), "+f"(d[162]), "+f"(d[163]), "+f"(d[164]), "+f"(d[165]), "+f"(d[166]), "+f"(d[167]), "+f"(d[168]), "+f"(d[169]), "+f"(d[170]), "+f"(d[171]), "+f"(d[172]), "+f"(d[173]), "+f"(d[174]), "+f"(d[175]), "+f"(d[176]), "+f"(d[177]), "+f"(d[178]), "+f"(d[179]), "+f"(d[180]), "+f"(d[181]), "+f"(d[182]), "+f"(d[183]), "+f"(d[184]), "+f"(d[185]), "+f"(d[186]), "+f"(d[187]), "+f"(d[188]), "+f"(d[189]), "+f"(d[190]), "+f"(d[191])
    : "l"(da), "l"(db), "r"(scale_d));
}
__device__ __forceinline__ void wgmma_n256_k(float (&d)[192], uint64_t da, uint64_t db, int scale_d) {
  asm volatile("{\n.reg .pred p;\nsetp.ne.b32 p, %130, 0;\n"
    "wgmma.mma_async.sync.aligned.m64n256k16.f32.bf16.bf16 {%0, %1, %2, %3, %4, %5, %6, %7, %8, %9, %10, %11, %12, %13, %14, %15, %16, %17, %18, %19, %20, %21, %22, %23, %24, %25, %26, %27, %28, %29, %30, %31, %32, %33, %34, %35, %36, %37, %38, %39, %40, %41, %42, %43, %44, %45, %46, %47, %48, %49, %50, %51, %52, %53, %54, %55, %56, %57, %58, %59, %60, %61, %62, %63, %64, %65, %66, %67, %68, %69, %70, %71, %72, %73, %74, %75, %76, %77, %78, %79, %80, %81, %82, %83, %84, %85, %86, %87, %88, %89, %90, %91, %92, %93, %94, %95, %96, %97, %98, %99, %100, %101, %102, %103, %104, %105, %106, %107, %108, %109, %110, %111, %112, %113, %114, %115, %116, %117, %118, %119, %120, %121, %122, %123, %124, %125, %126, %127}, %128, %129, p, 1, 1, 0, 0;\n}\n"
    : "+f"(d[0]), "+f"(d[1]), "+f"(d[2]), "+f"(d[3]), "+f"(d[4]), "+f"(d[5]), "+f"(d[6]), "+f"(d[7]), "+f"(d[8]), "+f"(d[9]), "+f"(d[10]), "+f"(d[11]), "+f"(d[12]), "+f"(d[13]), "+f"(d[14]), "+f"(d[15]), "+f"(d[16]), "+f"(d[17]), "+f"(d[18]), "+f"(d[19]), "+f"(d[20]), "+f"(d[21]), "+f"(d[22]), "+f"(d[23]), "+f"(d[24]), "+f"(d[25]), "+f"(d[26]), "+f"(d[27]), "+f"(d[28]), "+f"(d[29]), "+f"(d[30]), "+f"(d[31]), "+f"(d[32]), "+f"(d[33]), "+f"(d[34]), "+f"(d[35]), "+f"(d[36]), "+f"(d[37]), "+f"(d[38]), "+f"(d[39]), "+f"(d[40]), "+f"(d[41]), "+f"(d[42]), "+f"(d[43]), "+f"(d[44]), "+f"(d[45]), "+f"(d[46]), "+f"(d[47]), "+f"(d[48]), "+f"(d[49]), "+f"(d[50]), "+f"(d[51]), "+f"(d[52]), "+f"(d[53]), "+f"(d[54]), "+f"(d[55]), "+f"(d[56]), "+f"(d[57]), "+f"(d[58]), "+f"(d[59]), "+f"(d[60]), "+f"(d[61]), "+f"(d[62]), "+f"(d[63]), "+f"(d[64]), "+f"(d[65]), "+f"(d[66]), "+f"(d[67]), "+f"(d[68]), "+f"(d[69]), "+f"(d[70]), "+f"(d[71]), "+f"(d[72]), "+f"(d[73]), "+f"(d[74]), "+f"(d[75]), "+f"(d[76]), "+f"(d[77]), "+f"(d[78]), "+f"(d[79]), "+f"(d[80]), "+f"(d[81]), "+f"(d[82]), "+f"(d[83]), "+f"(d[84]), "+f"(d[85]), "+f"(d[86]), "+f"(d[87]), "+f"(d[88]), "+f"(d[89]), "+f"(d[90]), "+f"(d[91]), "+f"(d[92]), "+f"(d[93]), "+f"(d[94]), "+f"(d[95]), "+f"(d[96]), "+f"(d[97]), "+f"(d[98]), "+f"(d[99]), "+f"(d[100]), "+f"(d[101]), "+f"(d[102]), "+f"(d[103]), "+f"(d[104]), "+f"(d[105]), "+f"(d[106]), "+f"(d[107]), "+f"(d[108]), "+f"(d[109]), "+f"(d[110]), "+f"(d[111]), "+f"(d[112]), "+f"(d[113]), "+f"(d[114]), "+f"(d[115]), "+f"(d[116]), "+f"(d[117]), "+f"(d[118]), "+f"(d[119]), "+f"(d[120]), "+f"(d[121]), "+f"(d[122]), "+f"(d[123]), "+f"(d[124]), "+f"(d[125]), "+f"(d[126]), "+f"(d[127])
    : "l"(da), "l"(db), "r"(scale_d));
}
__device__ __forceinline__ void wgmma_n128_k(float (&d)[192], uint64_t da, uint64_t db, int scale_d) {
  asm volatile("{\n.reg .pred p;\nsetp.ne.b32 p, %66, 0;\n"
    "wgmma.mma_async.sync.aligned.m64n128k16.f32.bf16.bf16 {%0, %1, %2, %3, %4, %5, %6, %7, %8, %9, %10, %11, %12, %13, %14, %15, %16, %17, %18, %19, %20, %21, %22, %23, %24, %25, %26, %27, %28, %29, %30, %31, %32, %33, %34, %35, %36, %37, %38, %39, %40, %41, %42, %43, %44, %45, %46, %47, %48, %49, %50, %51, %52, %53, %54, %55, %56, %57, %58, %59, %60, %61, %62, %63}, %64, %65, p, 1, 1, 0, 0;\n}\n"
    : "+f"(d[128]), "+f"(d[129]), "+f"(d[130]), "+f"(d[131]), "+f"(d[132]), "+f"(d[133]), "+f"(d[134]), "+f"(d[135]), "+f"(d[136]), "+f"(d[137]), "+f"(d[138]), "+f"(d[139]), "+f"(d[140]), "+f"(d[141]), "+f"(d[142]), "+f"(d[143]), "+f"(d[144]), "+f"(d[145]), "+f"(d[146]), "+f"(d[147]), "+f"(d[148]), "+f"(d[149]), "+f"(d[150]), "+f"(d[151]), "+f"(d[152]), "+f"(d[153]), "+f"(d[154]), "+f"(d[155]), "+f"(d[156]), "+f"(d[157]), "+f"(d[158]), "+f"(d[159]), "+f"(d[160]), "+f"(d[161]), "+f"(d[162]), "+f"(d[163]), "+f"(d[164]), "+f"(d[165]), "+f"(d[166]), "+f"(d[167]), "+f"(d[168]), "+f"(d[169]), "+f"(d[170]), "+f"(d[171]), "+f"(d[172]), "+f"(d[173]), "+f"(d[174]), "+f"(d[175]), "+f"(d[176]), "+f"(d[177]), "+f"(d[178]), "+f"(d[179]), "+f"(d[180]), "+f"(d[181]), "+f"(d[182]), "+f"(d[183]), "+f"(d[184]), "+f"(d[185]), "+f"(d[186]), "+f"(d[187]), "+f"(d[188]), "+f"(d[189]), "+f"(d[190]), "+f"(d[191])
    : "l"(da), "l"(db), "r"(scale_d));
}
__device__ __forceinline__ void wgmma_n40_tt(float (&d)[20], uint64_t da, uint64_t db, int scale_d) {
  asm volatile("{\n.reg .pred p;\nsetp.ne.b32 p, %22, 0;\n"
    "wgmma.mma_async.sync.aligned.m64n40k16.f32.bf16.bf16 {%0, %1, %2, %3, %4, %5, %6, %7, %8, %9, %10, %11, %12, %13, %14, %15, %16, %17, %18, %19}, %20, %21, p, 1, 1, 1, 1;\n}\n"
    : "+f"(d[0]), "+f"(d[1]), "+f"(d[2]), "+f"(d[3]), "+f"(d[4]), "+f"(d[5]), "+f"(d[6]), "+f"(d[7]), "+f"(d[8]), "+f"(d[9]), "+f"(d[10]), "+f"(d[11]), "+f"(d[12]), "+f"(d[13]), "+f"(d[14]), "+f"(d[15]), "+f"(d[16]), "+f"(d[17]), "+f"(d[18]), "+f"(d[19])
    : "l"(da), "l"(db), "r"(scale_d));
}
__device__ __forceinline__ void wgmma_n40_rs(float (&d)[20], const uint32_t (&a)[4], uint64_t db, int scale_d) {
  asm volatile("{\n.reg .pred p;\nsetp.ne.b32 p, %25, 0;\n"
    "wgmma.mma_async.sync.aligned.m64n40k16.f32.bf16.bf16 {%0, %1, %2, %3, %4, %5, %6, %7, %8, %9, %10, %11, %12, %13, %14, %15, %16, %17, %18, %19}, {%20, %21, %22, %23}, %24, p, 1, 1, 1;\n}\n"
    : "+f"(d[0]), "+f"(d[1]), "+f"(d[2]), "+f"(d[3]), "+f"(d[4]), "+f"(d[5]), "+f"(d[6]), "+f"(d[7]), "+f"(d[8]), "+f"(d[9]), "+f"(d[10]), "+f"(d[11]), "+f"(d[12]), "+f"(d[13]), "+f"(d[14]), "+f"(d[15]), "+f"(d[16]), "+f"(d[17]), "+f"(d[18]), "+f"(d[19])
    : "r"(a[0]), "r"(a[1]), "r"(a[2]), "r"(a[3]), "l"(db), "r"(scale_d));
}
__device__ __forceinline__ void wgmma_n256_0(float (&d)[192], uint64_t da, uint64_t db) {
  asm volatile("{\n.reg .pred p;\nsetp.ne.b32 p, 0, 0;\n"
    "wgmma.mma_async.sync.aligned.m64n256k16.f32.bf16.bf16 {%0, %1, %2, %3, %4, %5, %6, %7, %8, %9, %10, %11, %12, %13, %14, %15, %16, %17, %18, %19, %20, %21, %22, %23, %24, %25, %26, %27, %28, %29, %30, %31, %32, %33, %34, %35, %36, %37, %38, %39, %40, %41, %42, %43, %44, %45, %46, %47, %48, %49, %50, %51, %52, %53, %54, %55, %56, %57, %58, %59, %60, %61, %62, %63, %64, %65, %66, %67, %68, %69, %70, %71, %72, %73, %74, %75, %76, %77, %78, %79, %80, %81, %82, %83, %84, %85, %86, %87, %88, %89, %90, %91, %92, %93, %94, %95, %96, %97, %98, %99, %100, %101, %102, %103, %104, %105, %106, %107, %108, %109, %110, %111, %112, %113, %114, %115, %116, %117, %118, %119, %120, %121, %122, %123, %124, %125, %126, %127}, %128, %129, p, 1, 1, 0, 1;\n}\n"
    : "=f"(d[0]), "=f"(d[1]), "=f"(d[2]), "=f"(d[3]), "=f"(d[4]), "=f"(d[5]), "=f"(d[6]), "=f"(d[7]), "=f"(d[8]), "=f"(d[9]), "=f"(d[10]), "=f"(d[11]), "=f"(d[12]), "=f"(d[13]), "=f"(d[14]), "=f"(d[15]), "=f"(d[16]), "=f"(d[17]), "=f"(d[18]), "=f"(d[19]), "=f"(d[20]), "=f"(d[21]), "=f"(d[22]), "=f"(d[23]), "=f"(d[24]), "=f"(d[25]), "=f"(d[26]), "=f"(d[27]), "=f"(d[28]), "=f"(d[29]), "=f"(d[30]), "=f"(d[31]), "=f"(d[32]), "=f"(d[33]), "=f"(d[34]), "=f"(d[35]), "=f"(d[36]), "=f"(d[37]), "=f"(d[38]), "=f"(d[39]), "=f"(d[40]), "=f"(d[41]), "=f"(d[42]), "=f"(d[43]), "=f"(d[44]), "=f"(d[45]), "=f"(d[46]), "=f"(d[47]), "=f"(d[48]), "=f"(d[49]), "=f"(d[50]), "=f"(d[51]), "=f"(d[52]), "=f"(d[53]), "=f"(d[54]), "=f"(d[55]), "=f"(d[56]), "=f"(d[57]), "=f"(d[58]), "=f"(d[59]), "=f"(d[60]), "=f"(d[61]), "=f"(d[62]), "=f"(d[63]), "=f"(d[64]), "=f"(d[65]), "=f"(d[66]), "=f"(d[67]), "=f"(d[68]), "=f"(d[69]), "=f"(d[70]), "=f"(d[71]), "=f"(d[72]), "=f"(d[73]), "=f"(d[74]), "=f"(d[75]), "=f"(d[76]), "=f"(d[77]), "=f"(d[78]), "=f"(d[79]), "=f"(d[80]), "=f"(d[81]), "=f"(d[82]), "=f"(d[83]), "=f"(d[84]), "=f"(d[85]), "=f"(d[86]), "=f"(d[87]), "=f"(d[88]), "=f"(d[89]), "=f"(d[90]), "=f"(d[91]), "=f"(d[92]), "=f"(d[93]), "=f"(d[94]), "=f"(d[95]), "=f"(d[96]), "=f"(d[97]), "=f"(d[98]), "=f"(d[99]), "=f"(d[100]), "=f"(d[101]), "=f"(d[102]), "=f"(d[103]), "=f"(d[104]), "=f"(d[105]), "=f"(d[106]), "=f"(d[107]), "=f"(d[108]), "=f"(d[109]), "=f"(d[110]), "=f"(d[111]), "=f"(d[112]), "=f"(d[113]), "=f"(d[114]), "=f"(d[115]), "=f"(d[116]), "=f"(d[117]), "=f"(d[118]), "=f"(d[119]), "=f"(d[120]), "=f"(d[121]), "=f"(d[122]), "=f"(d[123]), "=f"(d[124]), "=f"(d[125]), "=f"(d[126]), "=f"(d[127])
    : "l"(da), "l"(db));
}
__device__ __forceinline__ void wgmma_n128_0(float (&d)[192], uint64_t da, uint64_t db) {
  asm volatile("{\n.reg .pred p;\nsetp.ne.b32 p, 0, 0;\n"
    "wgmma.mma_async.sync.aligned.m64n128k16.f32.bf16.bf16 {%0, %1, %2, %3, %4, %5, %6, %7, %8, %9, %10, %11, %12, %13, %14, %15, %16, %17, %18, %19, %20, %21, %22, %23, %24, %25, %26, %27, %28, %29, %30, %31, %32, %33, %34, %35, %36, %37, %38, %39, %40, %41, %42, %43, %44, %45, %46, %47, %48, %49, %50, %51, %52, %53, %54, %55, %56, %57, %58, %59, %60, %61, %62, %63}, %64, %65, p, 1, 1, 0, 1;\n}\n"
    : "=f"(d[128]), "=f"(d[129]), "=f"(d[130]), "=f"(d[131]), "=f"(d[132]), "=f"(d[133]), "=f"(d[134]), "=f"(d[135]), "=f"(d[136]), "=f"(d[137]), "=f"(d[138]), "=f"(d[139]), "=f"(d[140]), "=f"(d[141]), "=f"(d[142]), "=f"(d[143]), "=f"(d[144]), "=f"(d[145]), "=f"(d[146]), "=f"(d[147]), "=f"(d[148]), "=f"(d[149]), "=f"(d[150]), "=f"(d[151]), "=f"(d[152]), "=f"(d[153]), "=f"(d[154]), "=f"(d[155]), "=f"(d[156]), "=f"(d[157]), "=f"(d[158]), "=f"(d[159]), "=f"(d[160]), "=f"(d[161]), "=f"(d[162]), "=f"(d[163]), "=f"(d[164]), "=f"(d[165]), "=f"(d[166]), "=f"(d[167]), "=f"(d[168]), "=f"(d[169]), "=f"(d[170]), "=f"(d[171]), "=f"(d[172]), "=f"(d[173]), "=f"(d[174]), "=f"(d[175]), "=f"(d[176]), "=f"(d[177]), "=f"(d[178]), "=f"(d[179]), "=f"(d[180]), "=f"(d[181]), "=f"(d[182]), "=f"(d[183]), "=f"(d[184]), "=f"(d[185]), "=f"(d[186]), "=f"(d[187]), "=f"(d[188]), "=f"(d[189]), "=f"(d[190]), "=f"(d[191])
    : "l"(da), "l"(db));
}
__device__ __forceinline__ void wgmma_n128_rs(float (&d)[192], const uint32_t (&a)[4], uint64_t db, int scale_d) {
  asm volatile("{\n.reg .pred p;\nsetp.ne.b32 p, %69, 0;\n"
    "wgmma.mma_async.sync.aligned.m64n128k16.f32.bf16.bf16 {%0, %1, %2, %3, %4, %5, %6, %7, %8, %9, %10, %11, %12, %13, %14, %15, %16, %17, %18, %19, %20, %21, %22, %23, %24, %25, %26, %27, %28, %29, %30, %31, %32, %33, %34, %35, %36, %37, %38, %39, %40, %41, %42, %43, %44, %45, %46, %47, %48, %49, %50, %51, %52, %53, %54, %55, %56, %57, %58, %59, %60, %61, %62, %63}, {%64, %65, %66, %67}, %68, p, 1, 1, 1;\n}\n"
    : "+f"(d[128]), "+f"(d[129]), "+f"(d[130]), "+f"(d[131]), "+f"(d[132]), "+f"(d[133]), "+f"(d[134]), "+f"(d[135]), "+f"(d[136]), "+f"(d[137]), "+f"(d[138]), "+f"(d[139]), "+f"(d[140]), "+f"(d[141]), "+f"(d[142]), "+f"(d[143]), "+f"(d[144]), "+f"(d[145]), "+f"(d[146]), "+f"(d[147]), "+f"(d[148]), "+f"(d[149]), "+f"(d[150]), "+f"(d[151]), "+f"(d[152]), "+f"(d[153]), "+f"(d[154]), "+f"(d[155]), "+f"(d[156]), "+f"(d[157]), "+f"(d[158]), "+f"(d[159]), "+f"(d[160]), "+f"(d[161]), "+f"(d[162]), "+f"(d[163]), "+f"(d[164]), "+f"(d[165]), "+f"(d[166]), "+f"(d[167]), "+f"(d[168]), "+f"(d[169]), "+f"(d[170]), "+f"(d[171]), "+f"(d[172]), "+f"(d[173]), "+f"(d[174]), "+f"(d[175]), "+f"(d[176]), "+f"(d[177]), "+f"(d[178]), "+f"(d[179]), "+f"(d[180]), "+f"(d[181]), "+f"(d[182]), "+f"(d[183]), "+f"(d[184]), "+f"(d[185]), "+f"(d[186]), "+f"(d[187]), "+f"(d[188]), "+f"(d[189]), "+f"(d[190]), "+f"(d[191])
    : "r"(a[0]), "r"(a[1]), "r"(a[2]), "r"(a[3]), "l"(db), "r"(scale_d));
}

constexpr int SLOT = 16384;
constexpr int KVT = 10240;
constexpr uint32_t QA = 0x0BAu, QK = 0x462u, QQ = 0x981u;
constexpr int SM_SD = 12 * SLOT;
constexpr int SM_BAR = SM_SD + 8192;
constexpr int SM_RS = SM_BAR + 512;
constexpr int SM_AP = SM_RS + 768;
constexpr int SM_BP = SM_AP + 2048;
constexpr int SM_WPHI = SM_BP + 12288;
constexpr int SM_EPOCH = SM_WPHI + 10240;
constexpr int SM_TOTAL = SM_EPOCH + 16 + 1024;
constexpr int B_FULLS = 0, B_XOLD = 24, B_STAT = 32, B_EMPTYS = 40, B_FULLT = 256  , B_CONS = 384  , B_E3 = 472, B_E0 = 480, B_E1 = 488, B_E2 = 496, B_EPI = 504, B_CS = 160,
              B_KVDONE = 168  , B_ODONE = 176, B_XDONE = 184, B_OH1 = B_CONS, B_CS2 = 208, B_XH0 = 232, B_R0 = 240, B_CB = 144  , B_XOLD2 = 216;
constexpr uint64_t BAR_CNT = 0x1c07fc0eac00a800ull;
constexpr uint64_t WO_A0 = 0xa461b57648357643ull, WO_B0 = 0x59083a9021ba9021ull, WO_A1 = 0xa0b76901276a5babull, WO_B1 = 0x95428a5b34890132ull;
constexpr uint64_t WO_DA0 = 0xa9865432ff00dd00ull, WO_DB0 = 0xa986543211bbccccull, WO_DA1 = 0xa98654321ffff000ull, WO_DB1 = 0xa98754321bbcccddull;
#define WOORD 0xFDB9753ECA864210ull
constexpr int NX = 4;
constexpr int XS = 10;

#define PL 2
#define PROFX(i) PROFT(tid_ == 128 && layer == PL, 200 + (i))
#define NCOM 3
#define PFS 8
#define KVTH 0x41700000u
#define XPF 3
#define XPM 2
#define TLINE 1
#define NLAYERS 4
constexpr float L2E = 1.4426950408889634f;
#define PHI_MAX 2147483648.f

#define D128(lo) desc64(lo, 0x40000040u)
struct Ctx { uint32_t sb; int g, rb, cu; bf16* out; };

__device__ __forceinline__ void colsum(const CUtensorMap* tm, float* cs, int rb, int g, int w0, int dw, int lane, uint32_t stg, uint32_t cb, uint32_t par) {
  const uint32_t src = stg + (lane >> 3) * 2048;
#pragma unroll 1
  for (int wi = w0 - dw; wi < 6; wi += dw) {
    float s[8] = {0.f, 0.f, 0.f, 0.f, 0.f, 0.f, 0.f, 0.f};
    if (wi >= 0) {
      mbar_wait_u(cb, par);
      par ^= 1;
#pragma unroll 4
      for (int r = 0; r < 16; ++r) {
        const uint4 v = lds128(src + r * 128 + (((lane ^ r) & 7) << 4));
        s[0] += bf_lo(v.x); s[1] += bf_hi(v.x); s[2] += bf_lo(v.y); s[3] += bf_hi(v.y);
        s[4] += bf_lo(v.z); s[5] += bf_hi(v.z); s[6] += bf_lo(v.w); s[7] += bf_hi(v.w);
      }
#pragma unroll
      for (int i = 0; i < 8; ++i) s[i] += __shfl_xor_sync(0xffffffffu, s[i], 8);
    }
    const int wn = wi + dw;
    if (wn < 6) {
      expect_tx_e(cb, 8192);
      tma_2d_e(stg, tm, (wn >= 4 ? 0 : 1024 + (wn >> 1) * 1024) + g * 128 + (wn & 1) * 64, rb * 64, cb);
    }
    if (wi >= 0) {
#pragma unroll
      for (int i = 0; i < 8; ++i) s[i] += __shfl_xor_sync(0xffffffffu, s[i], 16);
      if (lane < 8) {
        red_add4(cs + g * 384 + (wi * 8 + lane) * 8, s[0], s[1], s[2], s[3]);
        red_add4(cs + g * 384 + (wi * 8 + lane) * 8 + 4, s[4], s[5], s[6], s[7]);
      }
      __syncwarp();
    }
  }
}
#define PHASE_CTX() \
  uint32_t sb = c.sb; asm volatile("" : "+r"(sb)); \
  int tid_ = threadIdx.x; asm volatile("" : "+r"(tid_)); \
  const uint32_t bar = sb + SM_BAR; \
  const int lane = tid_ & 31, cw = (tid_ >> 5) - 4, wg = cw >> 2, wq = cw & 3, gq = lane >> 2, t = lane & 3, wrow0 = cw * 16; \
  const int lrow = (lane & 7) + ((lane >> 3) & 1) * 8, lchk = lane >> 4; \
  const bool elected = (tid_ & 127) == 0; \
  const uint32_t rowo = (wrow0 + lrow) * 128, X = (lchk ^ (lane & 7)) << 4; \
  (void)bar; (void)wq; (void)gq; (void)lrow; (void)lchk; (void)elected; (void)wrow0; (void)wg; (void)rowo; (void)X; (void)t;

__device__ __forceinline__ void slab_out_half(uint32_t slot, bf16* dst, int wrow0, int lane, bool FENCE = false) {
  const int r0 = lane >> 3, ch = lane & 7;
  const uint32_t src = slot + (wrow0 + r0) * 128;
  uint4 v[4];
#pragma unroll
  for (int i = 0; i < 4; ++i) v[i] = lds128(src + i * 512 + (((ch ^ (4 * i + r0)) & 7) << 4));
  if (FENCE) fence_async_smem();
  dst += (size_t)(wrow0 + r0) * D_ + ch * 8;
#pragma unroll
  for (int i = 0; i < 4; ++i)
    asm volatile("st.global.v4.u32 [%0], {%1,%2,%3,%4};" ::"l"(dst + (size_t)i * 4 * D_), "r"(v[i].x), "r"(v[i].y), "r"(v[i].z), "r"(v[i].w) : "memory");
}

struct Tag { uint32_t me, mo, tg; };
__device__ __forceinline__ Tag make_tag(int gq, int t, uint32_t tg) { return Tag{t == 0, t == 1, tg}; }
__device__ __forceinline__ void stsm_tag(uint32_t addr, uint32_t r0, uint32_t r1, uint32_t r2, uint32_t r3, const Tag& k, int jp) {
  if (jp == 0) stsm_x4(addr, (r0 & ~k.me) | (k.tg & k.me), (r1 & ~k.mo) | (k.tg & k.mo), r2, r3);
  else stsm_x4(addr, r0, r1, r2, r3);
}
#define TILE_BAD() ((lds_vol(va) ^ tg) & 1)
#define TILE_VA() (slot + (wrow0 + (lane & 15)) * 128 + (lane & 7) * 16 + ((lane >> 3) & 1) * 4)
__device__ __forceinline__ void tile_check(uint32_t slot, const bf16* src, int wrow0, int lane, uint32_t tg) {
  const uint32_t va = TILE_VA();
  if (__builtin_expect(__any_sync(0xffffffffu, TILE_BAD()), 0)) {
    const int r0 = lane >> 3, ch = lane & 7;
    uint32_t n = 0;
#pragma unroll 1
    do {
      uint4 v[4];
#pragma unroll
      for (int i = 0; i < 4; ++i) v[i] = ld_relaxed4(reinterpret_cast<const uint4*>(src + (size_t)(wrow0 + r0 + 4 * i) * D_ + ch * 8));
#pragma unroll
      for (int i = 0; i < 4; ++i) sts128(slot + (wrow0 + r0 + 4 * i) * 128 + (((ch ^ (4 * i + r0)) & 7) << 4), v[i]);
      __syncwarp();
      if (++n > (1u << 16)) { g_err = 8u; break; }
    } while (__any_sync(0xffffffffu, TILE_BAD()));
    fence_async_smem();
    __syncwarp();
  }
}

template <int O>
__device__ __forceinline__ void phi_proj(float (&p)[2][4][4], const uint32_t (&kq)[64], uint32_t wa) {
#pragma unroll
  for (int h = 0; h < 2; ++h)
#pragma unroll
    for (int i = 0; i < 4; ++i) { p[h][i][0] = p[h][i][1] = p[h][i][2] = p[h][i][3] = 0.f; }
#pragma unroll
  for (int ks = 0; ks < 2; ++ks)
#pragma unroll
    for (int np = 0; np < 2; ++np)
#pragma unroll
      for (int h = 0; h < 2; ++h) {
        uint32_t b0, b1, b2, b3;
        ldsm_x4_t(b0, b1, b2, b3, wa + h * 2560 + ks * 1280 + np * 32);
        mma_bf16(p[h][2 * np], kq[O + 8 * h + 4 * ks], kq[O + 8 * h + 4 * ks + 1], kq[O + 8 * h + 4 * ks + 2], kq[O + 8 * h + 4 * ks + 3], b0, b1);
        mma_bf16(p[h][2 * np + 1], kq[O + 8 * h + 4 * ks], kq[O + 8 * h + 4 * ks + 1], kq[O + 8 * h + 4 * ks + 2], kq[O + 8 * h + 4 * ks + 3], b2, b3);
      }
}
__device__ __forceinline__ void phi_exp(uint32_t (&raw)[4][4], const float (&p)[4][4], float sc0, float sc1) {
#pragma unroll
  for (int i = 0; i < 4; ++i) {
    const float e0 = ex2(p[i][0] * sc0), e1 = ex2(p[i][1] * sc0), e2 = ex2(p[i][2] * sc1), e3 = ex2(p[i][3] * sc1);
    const float m0 = e0 * e1, m1 = e2 * e3, rr = rcp(m0 * m1), r0 = rr * m1, r1 = rr * m0;
    raw[i >> 1][(i & 1) * 2] = pack_bf16(e0, e1);
    raw[i >> 1][(i & 1) * 2 + 1] = pack_bf16(e2, e3);
    raw[2 + (i >> 1)][(i & 1) * 2] = pack_bf16(e1 * r0, e0 * r0);
    raw[2 + (i >> 1)][(i & 1) * 2 + 1] = pack_bf16(e3 * r1, e2 * r1);
  }
}
template <int O>
__device__ __forceinline__ void phi_norm(uint32_t (&ph)[2][4][4], const uint32_t (&raw)[2][4][4], const uint32_t (&kq)[64], uint32_t wa,
                                         float sc0, float sc1, float mul0, float mul1) {
  bool bad = false;
#pragma unroll
  for (int h = 0; h < 2; ++h)
#pragma unroll
    for (int sg = 0; sg < 2; ++sg) {
      float ss[4] = {0.f, 0.f, 0.f, 0.f};
#pragma unroll
      for (int ks = 0; ks < 2; ++ks)
        mma_bf16(ss, raw[h][2 * sg + ks][0], raw[h][2 * sg + ks][1], raw[h][2 * sg + ks][2], raw[h][2 * sg + ks][3], 0x3F803F80u, 0x3F803F80u);
      bad = bad || !(ss[0] < PHI_MAX) || !(ss[2] < PHI_MAX);
      const uint32_t iv = pack_bf16(rcp(ss[0]) * mul0, rcp(ss[2]) * mul1);
#pragma unroll
      for (int ks = 0; ks < 2; ++ks)
#pragma unroll
        for (int j = 0; j < 4; ++j) ph[h][2 * sg + ks][j] = mul_bf16x2(raw[h][2 * sg + ks][j], iv, j & 1);
    }
  if (__builtin_expect(__any_sync(0xffffffffu, bad), 0)) {
#pragma unroll 1
    for (int it = 0; it < 4; ++it) {
      float q[4][4];
#pragma unroll
      for (int i = 0; i < 4; ++i) { q[i][0] = q[i][1] = q[i][2] = q[i][3] = 0.f; }
#pragma unroll
      for (int ks = 0; ks < 2; ++ks) {
        uint32_t a[4];
#pragma unroll
        for (int j = 0; j < 4; ++j) a[j] = (it & 2) ? kq[O + 8 + 4 * ks + j] : kq[O + 4 * ks + j];
#pragma unroll
        for (int np = 0; np < 2; ++np) {
          uint32_t b0, b1, b2, b3;
          ldsm_x4_t(b0, b1, b2, b3, wa + (it >> 1) * 2560 + ks * 1280 + np * 32);
          mma_bf16(q[2 * np], a[0], a[1], a[2], a[3], b0, b1);
          mma_bf16(q[2 * np + 1], a[0], a[1], a[2], a[3], b2, b3);
        }
      }
      float iv[2];
#pragma unroll
      for (int r = 0; r < 2; ++r) {
        const float sc = (it & 1) ? -(r ? sc1 : sc0) : (r ? sc1 : sc0);
        float mx = -INFINITY, sm = 0.f;
#pragma unroll
        for (int i = 0; i < 8; ++i) { float& v = q[i >> 1][2 * r + (i & 1)]; v *= sc; mx = fmaxf(mx, v); }
        mx = fmaxf(mx, __shfl_xor_sync(0xffffffffu, mx, 1));
        mx = fmaxf(mx, __shfl_xor_sync(0xffffffffu, mx, 2));
#pragma unroll
        for (int i = 0; i < 8; ++i) { float& v = q[i >> 1][2 * r + (i & 1)]; v = ex2(v - mx); sm += v; }
        sm += __shfl_xor_sync(0xffffffffu, sm, 1);
        sm += __shfl_xor_sync(0xffffffffu, sm, 2);
        iv[r] = rcp(sm) * (r ? mul1 : mul0);
      }
#pragma unroll
      for (int i = 0; i < 24; ++i) ph[i >> 4][(i >> 2) & 3][i & 3] = ph[(i + 8) >> 4][((i + 8) >> 2) & 3][i & 3];
#pragma unroll
      for (int i = 0; i < 4; ++i) {
        ph[1][2 + (i >> 1)][(i & 1) * 2] = pack_bf16(q[i][0] * iv[0], q[i][1] * iv[0]);
        ph[1][2 + (i >> 1)][(i & 1) * 2 + 1] = pack_bf16(q[i][2] * iv[1], q[i][3] * iv[1]);
      }
    }
  }
}

__device__ __forceinline__ void stats_out(float s0, float s1, float q0, float q1, float2* dst, int t) {
  const bool od = t & 1;
  float sa = od ? s1 : s0, qa = od ? q1 : q0;
  sa += __shfl_xor_sync(0xffffffffu, od ? s0 : s1, 1);
  qa += __shfl_xor_sync(0xffffffffu, od ? q0 : q1, 1);
  sa += __shfl_xor_sync(0xffffffffu, sa, 2);
  qa += __shfl_xor_sync(0xffffffffu, qa, 2);
  if (t < 2) red_add2(&dst[t * 8].x, sa, qa);
}

__device__ __forceinline__ void consumer(const Ctx& c) {
  const int g = c.g, m0 = c.rb * 128;
  float acc[192];
#define X_HALF(hf, TG) \
      _Pragma("unroll") for (int jp = 4 * (hf); jp < 4 * (hf) + 4; ++jp) \
        stsm_tag(sb + (XS + (hf)) * SLOT + rowo + (X ^ ((jp & 3) << 5)), \
                 pack_bf16(acc[128 + 8 * jp], acc[129 + 8 * jp]), pack_bf16(acc[130 + 8 * jp], acc[131 + 8 * jp]), \
                 pack_bf16(acc[132 + 8 * jp], acc[133 + 8 * jp]), pack_bf16(acc[134 + 8 * jp], acc[135 + 8 * jp]), TG, jp & 3);
#pragma unroll
  for (int i = 128; i < 192; ++i) acc[i] = 0.f;
#pragma unroll 1
  for (int layer = 0;; ++layer) {
    {
      PHASE_CTX();
      const uint32_t wu = c.cu >> 2;
      const uint32_t dA0 = (((sb + wu * 8192) & 0x3FFFF) >> 4) | (1u << 16), dB0 = ((sb & 0x3FFFF) >> 4) | (512u << 16);
      {
        PROFX(0);
        mbar_wait(bar + B_FULLS, 0);
        PROFX(1);
        wgmma_fence();
        wgmma_n256_0(acc, D128(dA0 + XS * 1024), D128(dB0 + 2048));
#pragma unroll
        for (int k = 1; k < 4; ++k) wgmma_n256(acc, D128(dA0 + XS * 1024 + k * 2), D128(dB0 + 2048 + k * 128), 1);
        wgmma_commit();
        wgmma_wait<1>();
        float s0 = 0.f, s1 = 0.f, q0 = 0.f, q1 = 0.f;
        if (layer) {
          X_HALF(1, (Tag{0u, 0u, 0u}));
#pragma unroll
          for (int i = 128; i < 192; i += 4) {
            s0 += acc[i] + acc[i + 1]; s1 += acc[i + 2] + acc[i + 3];
            q0 = fmaf(acc[i], acc[i], fmaf(acc[i + 1], acc[i + 1], q0)); q1 = fmaf(acc[i + 2], acc[i + 2], fmaf(acc[i + 3], acc[i + 3], q1));
          }
        }
        asm volatile("" : "+f"(s0), "+f"(s1), "+f"(q0), "+f"(q1) :: "memory");
        wgmma_fence();
        wgmma_n128_0(acc, D128(dA0 + XS * 1024), D128(dB0 + 1024));
#pragma unroll
        for (int k = 1; k < 4; ++k) wgmma_n128(acc, D128(dA0 + XS * 1024 + k * 2), D128(dB0 + 1024 + k * 128), 1);
        wgmma_commit();
        if (layer) {
          PHASE_CTX();
          fence_async_smem();
          nbar_dyn(3 + wu, 128);
          stats_out(s0, s1, q0, q1, g_stats + layer * S_ + m0 + wrow0 + gq, t);
          PROFT(tid_ == 128, layer * 16 + 8);
        }
      }
      uint32_t s = 1, u = 0, sp = 0;
      const int ix = layer ? 99 : 2 * min(g, NCOM) + 1;
#pragma unroll 1
      for (int i = 1; i < 14; ++i) {
        mbar_wait(bar + B_FULLS + s * 8, (u + (s ? layer : 0)) & 1);
        if (layer && (unsigned)(i - 2) < 7u) {
          PHASE_CTX();
          tile_check(sb + ((QA >> (4 * s)) & 15) * SLOT, g_x + (size_t)m0 * D_ + ((2 * g + 2 * i - 2) & 15) * 64, wrow0, lane, lds_vol(sb + SM_EPOCH) + layer);
        }
        const uint32_t da = dA0 + ((QA >> (4 * s)) & 15) * 1024, dk = dB0 + ((QK >> (4 * s)) & 15) * 1024,
                       dq = dB0 + ((QQ >> (4 * s)) & 15) * 1024;
        wgmma_fence();
#pragma unroll
        for (int k = 0; k < 4; ++k) {
          wgmma_n256(acc, D128(da + k * 2), D128(dk + k * 128), 1);
          wgmma_n128(acc, D128(da + k * 2), D128(dq + k * 128), 1);
          if (k == 0) {
            wgmma_commit();
            wgmma_wait<1>();
            if (elected && (unsigned)(i - ix) >= 2u) release2(bar + B_EMPTYS + sp * 8);
          }
        }
        wgmma_commit();
        if ((unsigned)(i - ix) < 2u) {
          PHASE_CTX();
          {
            float s0 = 0.f, s1 = 0.f, q0 = 0.f, q1 = 0.f;
            const uint32_t xa = sb + ((QA >> (4 * sp)) & 15) * SLOT + rowo;
#pragma unroll
            for (int jp = 0; jp < 4; ++jp) {
              uint32_t x0, x1, x2, x3;
              ldsm_x4(x0, x1, x2, x3, xa + (X ^ (jp << 5)));
              s0 += (bf_lo(x0) + bf_hi(x0)) + (bf_lo(x2) + bf_hi(x2));
              s1 += (bf_lo(x1) + bf_hi(x1)) + (bf_lo(x3) + bf_hi(x3));
              q0 = fmaf(bf_lo(x0), bf_lo(x0), fmaf(bf_hi(x0), bf_hi(x0), fmaf(bf_lo(x2), bf_lo(x2), fmaf(bf_hi(x2), bf_hi(x2), q0))));
              q1 = fmaf(bf_lo(x1), bf_lo(x1), fmaf(bf_hi(x1), bf_hi(x1), fmaf(bf_lo(x3), bf_lo(x3), fmaf(bf_hi(x3), bf_hi(x3), q1))));
            }
            stats_out(s0, s1, q0, q1, g_stats + m0 + wrow0 + gq, t);
          }
          __syncwarp();
          if (lane == 0 && i != ix) mbar_arrive(bar + B_XDONE);
          nbar_dyn(3 + wu, 128);
          if (elected) release2(bar + B_EMPTYS + sp * 8);
        }
        if (i == 1 && layer) {
          PHASE_CTX();
          slab_out_half(sb + (XS + 1) * SLOT, g_x + (size_t)m0 * D_ + g * 128 + 64, wrow0, lane);
          __syncwarp();
          if (lane == 0) mbar_arrive(bar + B_XDONE);
          nbar_dyn(3 + wu, 128);
        }
        sp = s;
        if (++s == 3) { s = 0; ++u; }
      }
      {
        const uint64_t dap = make_desc_ns(sb + SM_AP + wu * 1024, 0, 128), dbp = make_desc_ns(sb + SM_BP + (layer & 1) * 6144, 0, 128);
        if (wu == 0) {
          wgmma_wait<0>();
          if (elected) mbar_arrive(bar + B_R0);
          nbar<6, 256>();
        }
        if (layer < 2) mbar_wait(bar + (layer ? B_CS2 : B_CS), 0);
        mbar_wait(bar + B_STAT, layer & 1);
        mbar_wait(bar + B_FULLS + 16, layer & 1);
        wgmma_fence();
        wgmma_n256_k(acc, dap, dbp, 1);
#pragma unroll
        for (int k = 0; k < 4; ++k) wgmma_n256(acc, D128(dA0 + (QA >> 8) * 1024 + k * 2), D128(dB0 + (QK >> 8) * 1024 + k * 128), 1);
        mbar_wait(bar + B_FULLS, 1);
        PROFT(tid_ == 128, layer * 16 + 9);
        wgmma_fence();
#pragma unroll
        for (int k = 0; k < 4; ++k) wgmma_n256(acc, D128(dA0 + (QA & 15) * 1024 + k * 2), D128(dB0 + (QK & 15) * 1024 + k * 128), 1);
        wgmma_commit();
        if (wu) nbar<6, 256>();
#define Q_TAIL() \
        wgmma_n128_k(acc, dap, dbp + 256, 1); \
        _Pragma("unroll") for (int k = 0; k < 4; ++k) wgmma_n128(acc, D128(dA0 + (QA >> 8) * 1024 + k * 2), D128(dB0 + (QQ >> 8) * 1024 + k * 128), 1); \
        _Pragma("unroll") for (int k = 0; k < 4; ++k) wgmma_n128(acc, D128(dA0 + (QA & 15) * 1024 + k * 2), D128(dB0 + (QQ & 15) * 1024 + k * 128), 1);
        Q_TAIL();
        wgmma_commit();
        wgmma_wait<1>();
#pragma unroll
        for (int i = 0; i < 128; ++i) asm volatile("" : "+f"(acc[i]) :: "memory");
      }
    }
    uint32_t xo[32];
    uint32_t oq[8][4];
    {
      PHASE_CTX();
      PROFT(tid_ == 128, layer * 16 + 1);
      const bool isB = layer & 1;
      const int cu = c.cu;
      if (cu >= 4) asm volatile("bar.arrive 7, 256;" ::: "memory");
      if (elected && cu == 4) mbar_arrive(bar + B_R0);
      uint32_t kq[64];
      const uint32_t rowq = rowo & 8191;
      const float rs0 = lds_f(sb + SM_RS + (16 + wrow0 + gq) * 4), rs1 = lds_f(sb + SM_RS + (24 + wrow0 + gq) * 4);
#define Q_DONE() \
      wgmma_wait<0>(); \
      if (lane == 0) release2(bar + B_E0); \
      _Pragma("unroll") for (int i = 128; i < 192; ++i) asm volatile("" : "+f"(acc[i]) :: "memory"); \
      _Pragma("unroll") for (int i = 0; i < 32; ++i) kq[32 + i] = pack_bf16(acc[128 + 2 * i], acc[129 + 2 * i]);
      if (isB) {
        if (cu == 0) asm volatile("bar.arrive 10, 64;" ::: "memory");
        if (elected) release2(bar + B_E1);
        const int e = gq & 1;
        const bool sel = t > (gq >> 1);
        const uint32_t rja = sb + SM_RS + (wrow0 + 2 * t + e) * 4;
        const float rjA0 = lds_f(rja + 32), rjA1 = lds_f(rja + 64), rjB0 = lds_f(rja + (sel ? 0 : 64)), rjB1 = lds_f(rja + (sel ? 32 : 96));
        uint32_t vv[32];
#pragma unroll
        for (int i = 0; i < 16; ++i) { kq[i] = pack_bf16(acc[2 * i], acc[2 * i + 1]); vv[i] = pack_bf16(acc[64 + 2 * i], acc[65 + 2 * i]); }
        const uint32_t rB = sb + 4 * SLOT + wg * 4 * KVT + rowq;
        auto prev = [&](int hp) { return cu == 4 ? rB - 4 * KVT + 8192 + 2 * hp * KVT : rB + 2 * (hp ^ wg) * KVT; };
        auto dump = [&](int hp) {
          const uint32_t kb = rB + 2048 + (hp ^ wg) * 2 * KVT;
#pragma unroll
          for (int jp = 0; jp < 4; ++jp) {
            stsm_x4(kb + (X ^ (jp << 5)), kq[16 * hp + 4 * jp], kq[16 * hp + 4 * jp + 1], kq[16 * hp + 4 * jp + 2], kq[16 * hp + 4 * jp + 3]);
            stsm_x4(kb + KVT + (X ^ (jp << 5)), vv[16 * hp + 4 * jp], vv[16 * hp + 4 * jp + 1], vv[16 * hp + 4 * jp + 2], vv[16 * hp + 4 * jp + 3]);
          }
          if (cu == 3) {
            if (hp) asm volatile("bar.arrive 15, 64;" ::: "memory"); else asm volatile("bar.arrive 9, 64;" ::: "memory");
          }
          asm volatile("bar.arrive %0, 224;" :: "r"(hp ? 13 + (cu >> 2) : 8 + (cu & 4)) : "memory");
        };
        uint4* const hbuf = g_halo + ((c.rb * 8 + g) * 2 + (layer >> 1)) * 512 + lane;
        if (cu < 4) {
          nbar<7, 256>();
          dump(0);
        }
#pragma unroll
        for (int i = 16; i < 32; ++i) { kq[i] = pack_bf16(acc[2 * i], acc[2 * i + 1]); vv[i] = pack_bf16(acc[64 + 2 * i], acc[65 + 2 * i]); }
        if (cu >= 4) {
          if (cu == 7) {
#pragma unroll
            for (int jp = 0; jp < 8; ++jp) {
              st_relaxed4(hbuf + jp * 32, ~kq[4 * jp], ~kq[4 * jp + 1], ~kq[4 * jp + 2], ~kq[4 * jp + 3]);
              st_relaxed4(hbuf + 256 + jp * 32, ~vv[4 * jp], ~vv[4 * jp + 1], ~vv[4 * jp + 2], ~vv[4 * jp + 3]);
            }
          }
          dump(0);
          dump(1);
        }
        PROFT(tid_ == 128, layer * 16 + 2);
        constexpr float SC = 0.17677669529663687f * L2E;
        const float fA0 = rjA0 * rs0 * SC, fB0 = rjB0 * rs0 * SC, fA1 = rjA1 * rs1 * SC, fB1 = rjB1 * rs1 * SC;
        const float bA0 = (m0 + wrow0) ? 0.f : -1e30f, bB = sel ? bA0 : 0.f;
        const uint32_t pA_ = e ? 0x1044u : 0x4410u, pB_ = e ? 0x3244u : 0x4432u, pLo = sel ? pB_ : 0x4444u, pHi = sel ? 0x4444u : pB_;
        const uint32_t KX = ((lane >> 3) ^ (lane & 7)) << 4;
        Q_DONE();
        if (cu == 0) {
          nbar<11, 64>();
        } else if (cu == 4) {
          uint4 hv[16];
          if (c.rb > 0) {
            uint32_t n = 0;
#pragma unroll 1
            while (true) {
              uint32_t mn = 0xFFFFFFFFu;
#pragma unroll
              for (int i = 0; i < 16; ++i) hv[i] = ld_relaxed4(hbuf - 16 * 512 + i * 32);
#pragma unroll
              for (int i = 0; i < 16; ++i) mn = __vimin3_u32(__vimin3_u32(mn, hv[i].x, hv[i].y), hv[i].z, hv[i].w);
              if (__all_sync(0xffffffffu, mn != 0u)) break;
              if (++n > (1u << 20)) { g_err = 4u; break; }
            }
          } else {
#pragma unroll
            for (int i = 0; i < 16; ++i) hv[i] = make_uint4(~0u, ~0u, ~0u, ~0u);
          }
          nbar<10, 64>();
#pragma unroll
          for (int i = 0; i < 16; ++i)
            stsm_x4(rB - 4 * KVT + (((i >> 2) & 1) * 2 + (i >> 3)) * KVT + (X ^ ((i & 3) << 5)), ~hv[i].x, ~hv[i].y, ~hv[i].z, ~hv[i].w);
          asm volatile("bar.arrive 11, 64;" ::: "memory");
          nbar<9, 64>();
        } else {
          nbar_dyn(8 + (cu & 4), 224);
        }
        PROFT(tid_ == 128, layer * 16 + 5);
        PROFT(lane == 0 && layer == PL, 136 + cw);
        uint32_t kb[2][2][4], vb[2][2][2][4];
        float oa[2][4][4], sm[2][2];
        auto att_load = [&](int hp) {
          const uint32_t kt = prev(hp) - (lane & 8) * 128, vt = rB + (2 * (hp ^ wg) + 1) * KVT + 2048;
          __syncwarp();
#pragma unroll
          for (int h = 0; h < 2; ++h)
#pragma unroll
            for (int nt = 0; nt < 2; ++nt) ldsm_x4(kb[h][nt][0], kb[h][nt][1], kb[h][nt][2], kb[h][nt][3], kt + nt * 1024 + (KX ^ (h << 6)));
#pragma unroll
          for (int ks = 0; ks < 2; ++ks)
#pragma unroll
            for (int np = 0; np < 2; ++np)
#pragma unroll
              for (int h = 0; h < 2; ++h)
                ldsm_x4_t(vb[h][ks][np][0], vb[h][ks][np][1], vb[h][ks][np][2], vb[h][ks][np][3], (ks ? vt : prev(hp) + KVT) + (X ^ (h << 6) ^ (np << 5)));
          if (hp == 0 && lane == 0) release2(bar + B_E3);
        };
        auto att_mid = [&](int hp) {
          float la[2][2], lb[2][2], mx[2][2];
#pragma unroll
          for (int h = 0; h < 2; ++h) {
            const int qo = 32 + 16 * hp + 8 * h, ko = 16 * hp + 8 * h;
            float sc[4][4];
#pragma unroll
            for (int nt = 0; nt < 4; ++nt) {
              sc[nt][0] = sc[nt][1] = sc[nt][2] = sc[nt][3] = 0.f;
#pragma unroll
              for (int ks = 0; ks < 2; ++ks)
                mma_bf16(sc[nt], kq[qo + 4 * ks], kq[qo + 4 * ks + 1], kq[qo + 4 * ks + 2], kq[qo + 4 * ks + 3],
                         nt < 2 ? kb[h][nt & 1][2 * ks] : kq[ko + 4 * ks + (nt & 1)], nt < 2 ? kb[h][nt & 1][2 * ks + 1] : kq[ko + 4 * ks + 2 + (nt & 1)]);
            }
            la[h][0] = fmaf(e ? sc[1][1] : sc[1][0], fA0, bA0);
            lb[h][0] = fmaf(sel ? (e ? sc[0][1] : sc[0][0]) : (e ? sc[2][1] : sc[2][0]), fB0, bB);
            la[h][1] = (e ? sc[2][3] : sc[2][2]) * fA1;
            lb[h][1] = fmaf(sel ? (e ? sc[1][3] : sc[1][2]) : (e ? sc[3][3] : sc[3][2]), fB1, bB);
            mx[h][0] = fmaxf(la[h][0], lb[h][0]); mx[h][1] = fmaxf(la[h][1], lb[h][1]);
          }
#pragma unroll
          for (int o = 1; o <= 2; o <<= 1)
#pragma unroll
            for (int h = 0; h < 2; ++h)
#pragma unroll
              for (int r = 0; r < 2; ++r) mx[h][r] = fmaxf(mx[h][r], __shfl_xor_sync(0xffffffffu, mx[h][r], o));
#pragma unroll
          for (int h = 0; h < 2; ++h) {
#pragma unroll
            for (int r = 0; r < 2; ++r) { la[h][r] = ex2(la[h][r] - mx[h][r]); lb[h][r] = ex2(lb[h][r] - mx[h][r]); sm[h][r] = la[h][r] + lb[h][r]; }
            const uint32_t p0 = pack_bf16(la[h][0] * rjA0, lb[h][0] * rjB0), p1 = pack_bf16(la[h][1] * rjA1, lb[h][1] * rjB1);
            const uint32_t a00 = __byte_perm(p0, 0u, pLo), a02 = __byte_perm(p0, 0u, pA_), a03 = __byte_perm(p1, 0u, pLo);
            const uint32_t a10 = __byte_perm(p0, 0u, pHi), a11 = __byte_perm(p1, 0u, pA_), a13 = __byte_perm(p1, 0u, pHi);
#pragma unroll
            for (int i = 0; i < 4; ++i) {
              oa[h][i][0] = oa[h][i][1] = oa[h][i][2] = oa[h][i][3] = 0.f;
              mma_bf16(oa[h][i], a00, 0u, a02, a03, vb[h][0][i >> 1][2 * (i & 1)], vb[h][0][i >> 1][2 * (i & 1) + 1]);
              mma_bf16(oa[h][i], a10, a11, 0u, a13, vb[h][1][i >> 1][2 * (i & 1)], vb[h][1][i >> 1][2 * (i & 1) + 1]);
            }
          }
#pragma unroll
          for (int o = 1; o <= 2; o <<= 1)
#pragma unroll
            for (int h = 0; h < 2; ++h)
#pragma unroll
              for (int r = 0; r < 2; ++r) sm[h][r] += __shfl_xor_sync(0xffffffffu, sm[h][r], o);
        };
        auto att_end = [&](int hp) {
          const uint32_t qad = sb + (XS + 1 - hp) * SLOT + rowo;
#pragma unroll
          for (int jp = 0; jp < 4; ++jp) ldsm_x4(xo[16 * hp + 4 * jp], xo[16 * hp + 4 * jp + 1], xo[16 * hp + 4 * jp + 2], xo[16 * hp + 4 * jp + 3], qad + (X ^ (jp << 5)));
#pragma unroll
          for (int h = 0; h < 2; ++h) {
            const float i0 = rcp(sm[h][0]), i1 = rcp(sm[h][1]);
#pragma unroll
            for (int np = 0; np < 2; ++np)
            {
              uint32_t (&o)[4] = oq[4 * hp + 2 * h + np];
              o[0] = pack_bf16(oa[h][2 * np][0] * i0, oa[h][2 * np][1] * i0); o[1] = pack_bf16(oa[h][2 * np][2] * i1, oa[h][2 * np][3] * i1);
              o[2] = pack_bf16(oa[h][2 * np + 1][0] * i0, oa[h][2 * np + 1][1] * i0); o[3] = pack_bf16(oa[h][2 * np + 1][2] * i1, oa[h][2 * np + 1][3] * i1);
              stsm_tag(qad + (X ^ (h << 6) ^ (np << 5)), o[0], o[1], o[2], o[3], make_tag(gq, t, 0u), 2 * h + np);
            }
          }
          {
          __syncwarp();
          slab_out_half(sb + (XS + 1 - hp) * SLOT, g_o + (size_t)m0 * D_ + g * 128 + hp * 64, wrow0, lane);
          __syncwarp();
          if (lane == 0) mbar_arrive(bar + (hp ? B_ODONE : B_OH1));
          }
          PROFT(lane == 0 && layer == PL && hp == 0, 128 + cw);
        };
        att_load(0);
        att_mid(0);
        mbar_wait(bar + B_XOLD, 1);
        att_end(0);
        if (cu < 4) dump(1);
        if (cu == 4) nbar<15, 64>();
        else if (cu != 0) nbar_dyn(13 + (cu >> 2), 224);
        att_load(1);
        att_mid(1);
        mbar_wait(bar + B_XOLD2, 1);
        att_end(1);
      } else {
#pragma unroll
        for (int i = 0; i < 32; ++i) kq[i] = pack_bf16(acc[2 * i], acc[2 * i + 1]);
        if (cu < 4) nbar<7, 256>();
        {
          const uint32_t vb = sb + (5 + 3 * wg) * SLOT + (rowq >> 1) + ((lchk ^ ((lane & 7) >> 1)) << 4);
#pragma unroll
          for (int jp = 8; jp < 16; ++jp)
            stsm_x4((vb ^ ((jp & 1) << 5)) + ((jp >> 1) & 3) * 4096,
                    pack_bf16(acc[8 * jp], acc[8 * jp + 1]), pack_bf16(acc[8 * jp + 2], acc[8 * jp + 3]),
                    pack_bf16(acc[8 * jp + 4], acc[8 * jp + 5]), pack_bf16(acc[8 * jp + 6], acc[8 * jp + 7]));
        }
        PROFT(tid_ == 128, layer * 16 + 2);
        Q_DONE();
        const uint32_t pA = sb + (3 + 3 * wg) * SLOT + (rowo & 8191);
        float sc0 = rs0 * L2E, sc1 = rs1 * L2E;
        const uint32_t wa0 = sb + SM_WPHI + lrow * 80 + lchk * 16;
        const uint32_t wu = c.cu >> 2, par = (layer >> 1) & 1;
        float p[2][4][4];
        uint32_t raw[2][4][4], ph[2][4][4];
        float kva[20], oab[2][2][20];
        auto kv_start = [&](int hp) {
#pragma unroll
          for (int h = 0; h < 2; ++h)
#pragma unroll
            for (int cp = 0; cp < 4; ++cp)
              stsm_x4(pA + hp * 16384 + h * 8192 + (X ^ (cp << 5)), ph[h][cp][0], ph[h][cp][1], ph[h][cp][2], ph[h][cp][3]);
          PROFT(tid_ == 128, layer * 16 + 11);
          nbar<1, 256>();
          fence_async_smem();
          const uint32_t hu = 2 * hp + wu;
          const uint32_t dP = (((sb + 3 * SLOT + hu * 8192) & 0x3FFFF) >> 4) | (512u << 16);
          const uint32_t dV = (((sb + 5 * SLOT + hu * 4096) & 0x3FFFF) >> 4) | (((SM_SD - 5 * SLOT - hu * 4096) >> 4) << 16);
          wgmma_fence();
#pragma unroll
          for (int ks = 0; ks < 8; ++ks)
            wgmma_n40_tt(kva, desc64(dP + (ks >> 2) * 3072 + (ks & 3) * 128, 0x40000040u),
                         desc64(dV + (ks >> 2) * (3072u - (2816u << 16)) + (ks & 3) * 64, 0x80000020u), ks != 0);
          wgmma_commit();
        };
        auto kv_end = [&](int hp) {
          wgmma_wait<0>();
#pragma unroll
          for (int i = 0; i < 20; ++i) asm volatile("" : "+f"(kva[i]) :: "memory");
          nbar_dyn(3 + wu, 128);
          PROFT(tid_ == 128, layer * 16 + 12);
          const bool od = lane & 1;
#pragma unroll
          for (int i = 0; i < 4; ++i)
            sts128(sb + (3 + hp) * SLOT + (cw * 128 + i * 32 + lane) * 16,
                   make_uint4(__float_as_uint(kva[4 * i]), __float_as_uint(kva[4 * i + 1]), __float_as_uint(kva[4 * i + 2]),
                              __float_as_uint(od == (i >= 2) ? 1.f : kva[4 * i + 3])));
          sts128(sb + (6 + hp) * SLOT + wg * 8192 + (wq * 32 + lane) * 16,
                 make_uint4(__float_as_uint(od ? kva[11] : kva[3]), __float_as_uint(od ? kva[15] : kva[7]), __float_as_uint(od ? kva[18] : kva[16]), __float_as_uint(1.f)));
          __syncwarp();
          if (lane == 0) mbar_arrive(bar + B_KVDONE - hp * 32);
          PROFT(tid_ == 128, layer * 16 + 3);
        };
        const uint4* const kvg = g_kv + (g * 2 + (layer >> 1)) * 2560 + cw * 128 + lane;
        uint4 ub[2][5];
        auto kv_load = [&](int hp) {
          uint4 (&u)[5] = ub[hp];
#pragma unroll
          for (int i = 0; i < 4; ++i) u[i] = ld_relaxed4(kvg + hp * 1280 + i * 32);
          u[4] = ld_relaxed4(kvg + hp * 1280 + 1024 - cw * 96);
        };
        auto kv_conv = [&](int hp) {
          uint4 (&u)[5] = ub[hp];
          PROFT(tid_ == 128 && hp == 0, layer * 16 + 10);
          PROFT(lane == 0 && hp == 1 && layer == PL, 128 + cw);
          if (hp == 0) mbar_wait(bar + B_KVDONE - 32, par);
          const bool od = lane & 1;
          uint32_t n = 0;
#pragma unroll 1
          while (!__all_sync(0xffffffffu, (od ? u[2].w : u[0].w) == 0x41800000u && (od ? u[3].w : u[1].w) == 0x41800000u && u[4].w == 0x41800000u)) {
#pragma unroll 1
            while (__any_sync(0xffffffffu, u[4].w < KVTH) && ++n < (1u << 20)) u[4].w = ld_relaxed(&kvg[hp * 1280 + 1024 - cw * 96].w);
            if (++n > (1u << 20)) { g_err = 6u; break; }
            kv_load(hp);
          }
          PROFT(lane == 0 && hp == 1 && layer == PL, 136 + cw);
          PROFT(tid_ == 128 && hp == 0, layer * 16 + 5);
          if (!od) { u[0].w = u[4].x; u[1].w = u[4].y; } else { u[2].w = u[4].x; u[3].w = u[4].y; }
#pragma unroll
          for (int i = 0; i < 4; i += 2)
            stsm_x4(sb + (5 + 3 * hp) * SLOT + rowo + (X ^ ((i & 2) << 4)),
                    pack_bf16(__uint_as_float(u[i].x), __uint_as_float(u[i].y)), pack_bf16(__uint_as_float(u[i].z), __uint_as_float(u[i].w)),
                    pack_bf16(__uint_as_float(u[i + 1].x), __uint_as_float(u[i + 1].y)), pack_bf16(__uint_as_float(u[i + 1].z), __uint_as_float(u[i + 1].w)));
          const uint32_t z2 = pack_bf16(__uint_as_float(u[4].z), __uint_as_float(u[4].z));
          if (t < 2) sts128(sb + (5 + 3 * hp) * SLOT + (wrow0 + gq + 8 * t) * 128 + ((4 ^ gq) << 4), make_uint4(z2, z2, z2, z2));
        };
        auto o_mma = [&](int hp, const uint32_t (&pq)[2][4][4]) {
          float (&oa)[2][20] = oab[hp];
          PROFT(tid_ == 128 && hp == 1, layer * 16 + 4);
          const uint32_t dK = (((sb + (5 + 3 * hp) * SLOT) & 0x3FFFF) >> 4) | (512u << 16);
          wgmma_fence();
#pragma unroll
          for (int ks = 0; ks < 4; ++ks) {
#pragma unroll
            for (int hh = 0; hh < 2; ++hh) wgmma_n40_rs(oa[hh], pq[hh][ks], D128(dK + hh * 512 + ks * 128), ks != 0);
          }
          wgmma_commit();
        };
        auto o_start = [&](int hp, const uint32_t (&pq)[2][4][4]) {
          kv_conv(hp);
          nbar<1, 256>();
          fence_async_smem();
          o_mma(hp, pq);
        };
        auto o_end = [&](int hp) {
          float (&oa)[2][20] = oab[hp];
          wgmma_wait<0>();
#pragma unroll
          for (int i = 0; i < 20; ++i) asm volatile("" : "+f"(oa[0][i]), "+f"(oa[1][i]) :: "memory");
#pragma unroll
          for (int hh = 0; hh < 2; ++hh) {
            const float i0 = rcp(oa[hh][16] + 1e-6f), i1 = rcp(oa[hh][18] + 1e-6f);
            const uint32_t qad = sb + (3 + hp) * SLOT + rowo, hx = hh << 6;
#pragma unroll
            for (int np = 0; np < 2; ++np)
            {
              uint32_t (&o)[4] = oq[4 * hp + 2 * hh + np];
              o[0] = pack_bf16(oa[hh][8 * np] * i0, oa[hh][8 * np + 1] * i0); o[1] = pack_bf16(oa[hh][8 * np + 2] * i1, oa[hh][8 * np + 3] * i1);
              o[2] = pack_bf16(oa[hh][8 * np + 4] * i0, oa[hh][8 * np + 5] * i0); o[3] = pack_bf16(oa[hh][8 * np + 6] * i1, oa[hh][8 * np + 7] * i1);
              stsm_tag(qad + (X ^ hx ^ (np << 5)), o[0], o[1], o[2], o[3], make_tag(gq, t, 1u), 2 * hh + np);
            }
          }
          {
          __syncwarp();
          slab_out_half(sb + (3 + hp) * SLOT, g_o + (size_t)m0 * D_ + g * 128 + hp * 64, wrow0, lane);
          __syncwarp();
          if (lane == 0) mbar_arrive(bar + (hp ? B_ODONE : B_OH1));
          }
        };
#define XO_LOAD() \
        mbar_wait(bar + B_XOLD, 0); \
        mbar_wait(bar + B_XOLD2, 0); \
        _Pragma("unroll") for (int jp = 0; jp < 8; ++jp) \
          ldsm_x4(xo[4 * jp], xo[4 * jp + 1], xo[4 * jp + 2], xo[4 * jp + 3], sb + (XS + 1 - (jp >> 2)) * SLOT + rowo + (X ^ ((jp & 3) << 5)));
#define SC_RELOAD() \
        sc0 = __uint_as_float(lds_vol(sb + SM_RS + (16 + wrow0 + gq) * 4)) * L2E; sc1 = __uint_as_float(lds_vol(sb + SM_RS + (24 + wrow0 + gq) * 4)) * L2E;
        __syncwarp();
        phi_proj<0>(p, kq, wa0);
        phi_exp(raw[0], p[0], sc0, sc1);
        phi_exp(raw[1], p[1], sc0, sc1);
        phi_proj<16>(p, kq, wa0 + 5120);
        phi_norm<0>(ph, raw, kq, wa0, sc0, sc1, rs0, rs1);
        kv_start(0);
        phi_exp(raw[0], p[0], sc0, sc1);
        kv_end(0);
        XO_LOAD();
        phi_exp(raw[1], p[1], sc0, sc1);
        phi_proj<32>(p, kq, wa0);
        phi_norm<16>(ph, raw, kq, wa0 + 5120, sc0, sc1, rs0, rs1);
        kv_start(1);
        if (lane == 0) release2(bar + B_E3);
        phi_exp(raw[0], p[0], sc0, sc1);
        kv_end(1);
        SC_RELOAD();
        phi_exp(raw[1], p[1], sc0, sc1);
        phi_proj<48>(p, kq, wa0 + 5120);
        phi_norm<32>(ph, raw, kq, wa0, sc0, sc1, 1.f, 1.f);
        kv_load(0);
        phi_exp(raw[0], p[0], sc0, sc1);
        phi_exp(raw[1], p[1], sc0, sc1);
        if ((raw[0][2][0] & raw[0][2][2] & raw[0][3][0] & raw[0][3][2] & raw[1][2][0] & raw[1][2][2] & raw[1][3][0] & raw[1][3][2]) == ~0u) sts_f(sb + SM_EPOCH + 12, 0.f);
        o_start(0, ph);
        kv_load(1);
        o_end(0);
        phi_norm<48>(ph, raw, kq, wa0 + 5120, sc0, sc1, 1.f, 1.f);
        o_start(1, ph);
        o_end(1);
      }
      __syncwarp();
      PROFT(lane == 0 && layer == PL, 216 + cw);
      if (lane == 0) mbar_arrive(bar + B_EPI);
      PROFT(tid_ == 128, layer * 16 + 6);
    }
    {
      PHASE_CTX();
      const uint32_t wu = c.cu >> 2;
      const uint32_t dA0 = (((sb + wu * 8192) & 0x3FFFF) >> 4) | (1u << 16), dB0 = ((sb & 0x3FFFF) >> 4) | (512u << 16);
#pragma unroll
      for (int i = 0; i < 32; ++i) { acc[128 + 2 * i] = bf_lo(xo[i]); acc[129 + 2 * i] = bf_hi(xo[i]); }
      uint64_t ta = ((layer & 1) ? WO_A1 : WO_A0) >> 8, tw = (layer & 1) ? WO_B1 : WO_B0;
      mbar_wait(bar + B_FULLT, layer & 1);
      mbar_wait(bar + B_FULLT + 8, layer & 1);
      PROFT(tid_ == 128 && layer == PL, 160);
      wgmma_fence();
#pragma unroll
      for (int k = 0; k < 8; ++k) wgmma_n128_rs(acc, oq[k], D128(dB0 + ((uint32_t)(tw >> (k & 4)) & 15) * 1024 + (k & 3) * 128), 1);
      wgmma_commit();
      tw >>= 8;
      if (lane == 0) release2(bar + B_E2);
#pragma unroll 1
      for (int i = 2; i < 16; ++i) {
        mbar_wait(bar + B_FULLT + i * 8, layer & 1);
        PROFT(tid_ == 128 && layer == PL, 160 + i);
        tile_check(sb + ((uint32_t)ta & 15) * SLOT, g_o + (size_t)m0 * D_ + ((2 * g + (int)(WOORD >> (4 * i))) & 15) * 64, wrow0, lane, ~layer);
        const uint32_t da = dA0 + ((uint32_t)ta & 15) * 1024, db = dB0 + ((uint32_t)tw & 15) * 1024;
        ta >>= 4; tw >>= 4;
        if (i == 15 && wu) nbar<6, 256>();
        wgmma_fence();
#pragma unroll
        for (int k = 0; k < 4; ++k) wgmma_n128(acc, D128(da + k * 2), D128(db + k * 128), 1);
        wgmma_commit();
        if (i == 15 && !wu) asm volatile("bar.arrive 6, 256;" ::: "memory");
        wgmma_wait<1>();
        if (elected && i < 12) release2(bar + B_CONS + (i - 1) * 8);
        if (elected && (unsigned)(i - 13) < 2u && layer + 1 < NLAYERS) release2(bar + B_EMPTYS + (i - 13) * 8);
      }
      const bool last = layer == NLAYERS - 1;
      Tag xt = make_tag(gq, last ? 4 : t, lds_vol(sb + SM_EPOCH) + layer + 1);
      asm volatile("" : "+r"(xt.me), "+r"(xt.mo), "+r"(xt.tg) :: "memory");
      wgmma_wait<0>();
#pragma unroll
      for (int i = 128; i < 192; ++i) asm volatile("" : "+f"(acc[i]) :: "memory");
      if (elected && !last) release2(bar + B_EMPTYS + 16);
      PROFT(tid_ == 128, layer * 16 + 7);
      X_HALF(0, xt);
      if (last) {
        __syncwarp();
        slab_out_half(sb + XS * SLOT, c.out + (size_t)m0 * D_ + g * 128, wrow0, lane);
        X_HALF(1, (Tag{0u, 0u, 0u}));
        __syncwarp();
        slab_out_half(sb + (XS + 1) * SLOT, c.out + (size_t)m0 * D_ + g * 128 + 64, wrow0, lane);
        __syncwarp();
        if (lane == 0) mbar_arrive(bar + B_XDONE);
        PROFT(tid_ == 128, layer * 16 + 24);
        break;
      }
      __syncwarp();
      slab_out_half(sb + XS * SLOT, g_x + (size_t)m0 * D_ + g * 128, wrow0, lane, true);
      __syncwarp();
      if (lane == 0) mbar_arrive(bar + B_XH0);
      nbar_dyn(3 + wu, 128);
    }
  }
}

__device__ __forceinline__ int kblock0(int i, int g) {
  const int j = i >> 1, p = max(g, NCOM) + j - NCOM;
  return (j < NCOM ? j : p < 8 ? p : p - 8 + NCOM) * 2 + (i & 1);
}

__device__ __forceinline__ int wo_kblock(int m, int g) { return (2 * g + (int)((WOORD >> (4 * m)) & 15)) & 15; }

__global__ void __cluster_dims__(2, 1, 1) __launch_bounds__(384, 1)
mega_kernel(const __grid_constant__ CUtensorMap tm_x0, const __grid_constant__ CUtensorMap tm_x,
            const __grid_constant__ CUtensorMap tm_o,
            const __grid_constant__ CUtensorMap tm_wA, const __grid_constant__ CUtensorMap tm_wB,
            const __grid_constant__ CUtensorMap tm_woA, const __grid_constant__ CUtensorMap tm_woB,
                        const bf16* __restrict__ wB, const bf16* __restrict__ wphi, bf16* __restrict__ out) {
  extern __shared__ uint8_t smem_raw[];
  const uint32_t sb = (smem_u32(smem_raw) + 1023u) & ~1023u;
  const uint32_t bar = sb + SM_BAR;
  const int warp = __shfl_sync(0xffffffffu, threadIdx.x >> 5, 0), lane = threadIdx.x & 31;
  uint32_t bid = blockIdx.x;
  if (gridDim.x == 128 + NX) {
    uint32_t tp;
    asm volatile("mov.u32 %0, %%smid;" : "=r"(tp));
    tp >>= 1;
    const uint32_t u7 = ((tp - 32) * 37) >> 8;
    bid = (tp < 32 ? tp : tp < 60 ? tp + 1 + u7 : tp < 62 ? tp + 4 : (tp - 58) * 8) * 2 + (bid & 1);
  }
  if (bid >= 128 || gridDim.x == NX) {
    const int xb = bid & (NX - 1);
    const int ch = threadIdx.x % 96, rg = threadIdx.x / 96, gg = xb * 2 + ch / 48, sec = (ch % 48) >> 4;
    const uint4* src = reinterpret_cast<const uint4*>(wB + (size_t)rg * 3072 + (sec == 2 ? 0 : 1024 + sec * 1024) + gg * 128 + (ch & 15) * 8);
    float s[8] = {0.f, 0.f, 0.f, 0.f, 0.f, 0.f, 0.f, 0.f};
#pragma unroll 1
    for (int r0 = 0; r0 < 256; r0 += 32) {
      uint4 v[32];
#pragma unroll
      for (int r = 0; r < 32; ++r) v[r] = __ldg(src + (size_t)(r0 + r) * 1536);
#pragma unroll
      for (int r = 0; r < 32; ++r) {
        s[0] += bf_lo(v[r].x); s[1] += bf_hi(v[r].x); s[2] += bf_lo(v[r].y); s[3] += bf_hi(v[r].y);
        s[4] += bf_lo(v[r].z); s[5] += bf_hi(v[r].z); s[6] += bf_lo(v[r].w); s[7] += bf_hi(v[r].w);
      }
    }
    float* cd = g_cs + (ld_relaxed(&g_epoch) & 1) * 6144 + 3072 + xb * 768 + ch * 8;
    red_add4(cd, s[0], s[1], s[2], s[3]);
    red_add4(cd + 4, s[4], s[5], s[6], s[7]);
    nbar<1, 384>();
    if (threadIdx.x < 2) flag_add(&g_csflag[8 + xb * 2 + threadIdx.x].v);
    return;
  }
  const int cr = bid & 1;
  const int g = bid >> 4;
  const int rb = bid & 15;
  const int m0 = rb * 128;

  if (warp < 4) {
    asm volatile("setmaxnreg.dec.sync.aligned.u32 40;");
    asm volatile("barrier.cluster.arrive.relaxed.aligned;" ::: "memory");
    const unsigned int epoch = warp ? ld_relaxed(&g_epoch) : 0u;
    if (warp) cluster_wait();
    unsigned int xbase = epoch * NLAYERS;
    auto wo_a = [&](int layer, int m1) {
      uint64_t ts = ((layer & 1) ? WO_A1 : WO_A0) >> (4 * m1), td = ((layer & 1) ? WO_DA1 : WO_DA0) >> (4 * m1), tk = WOORD >> (4 * m1);
      uint32_t ready = 0u;
#pragma unroll 1
      for (int m = m1; m < 16; ++m) {
        const int kb = (2 * g + (uint32_t)tk) & 15;
        uint32_t dst = sb + ((uint32_t)ts & 15) * SLOT, fb = bar + B_FULLT + m * 8, eb = bar + B_CONS + ((uint32_t)td & 15) * 8;
        int kc = kb * 64;
        ts >>= 4; td >>= 4; tk >>= 4;
        asm volatile("" : "+r"(dst), "+r"(fb), "+r"(eb), "+r"(kc));
        bool fr = false;
        if (!((ready >> kb) & 1)) {
          PROFT(m == 2 && lane == 0, 64 + layer * 16 + 2);
          fr = src_wait_tma(g_of + rb * 32, xbase + layer + 1, 1u << kb, ready, lane, eb, layer & 1);
          fence_async_all();
        }
        if (m == 6) mbar_wait_u(bar + B_EPI, layer & 1);
        if (!fr) mbar_wait_u(eb, layer & 1);
        tma_2d_e(dst, &tm_o, kc, m0, fb);
        PROFT(lane == 0 && layer == PL, 176 + m);
      }
    };
    auto wo_w = [&](int layer) {
      const CUtensorMap* tx = layer == 0 ? &tm_x0 : &tm_x;
      const CUtensorMap* two = (layer & 1) ? &tm_woB : &tm_woA;
      uint64_t ts = (layer & 1) ? WO_B1 : WO_B0, td = (layer & 1) ? WO_DB1 : WO_DB0, tk = WOORD;
      uint32_t pb = 0;
      fence_async_all();
      mbar_wait_u(bar + B_R0, layer & 1);
      expect_tx_e(bar + B_XOLD, 16384);
      tma_2d_e(sb + (XS + 1) * SLOT, tx, g * 128, m0, bar + B_XOLD);
#pragma unroll 1
      for (int m = 0; m < 16; ++m) {
        uint32_t dst = sb + ((uint32_t)ts & 15) * SLOT + cr * 8192, fb = bar + B_FULLT + m * 8, eb = bar + B_CONS + ((uint32_t)td & 15) * 8;
        int kc = ((2 * g + (uint32_t)tk) & 15) * 64;
        ts >>= 4; td >>= 4; tk >>= 4;
        asm volatile("" : "+r"(dst), "+r"(fb), "+r"(eb), "+r"(kc));
        if (eb < bar + B_E3 && pb >= bar + B_E3) mbar_wait_u(bar + B_E2, layer & 1);
        if (eb != pb) mbar_wait_u(eb, layer & 1);
        pb = eb;
        tma_2d_mc_e(dst, two, g * 128 + cr * 64, kc, fb);
        expect_tx_e(fb, m < 2 ? 16384 : 32768);
        PROFT(lane == 0 && layer == PL, 144 + m);
        if (m == ((layer & 1) ? 2 : 0)) {
          expect_tx_e(bar + B_XOLD2, 16384);
          tma_2d_e(sb + XS * SLOT, tx, g * 128 + 64, m0, bar + B_XOLD2);
        }
      }
    };
    if (warp == 0) {
      cluster_wait();
      PROFT(lane == 0, 125);
#pragma unroll 1
      for (int layer = 0; layer < NLAYERS; ++layer) {
        const CUtensorMap* tx = layer == 0 ? &tm_x0 : &tm_x;
        const CUtensorMap* tw = (layer & 1) ? &tm_wB : &tm_wA;
        uint32_t s = layer == 0, u = 0, ready = layer == 0 ? 0xFFFFu : 0u;
#pragma unroll 1
        for (int i = s; i < 16; ++i) {
          const int kb = layer == 0 ? kblock0(i, g) : wo_kblock(i, g), kc = kb * 64;
          const uint32_t fb = bar + B_FULLS + s * 8;
          const uint32_t kd = sb + (((QK >> (4 * s)) & 15) + cr) * SLOT, qd = sb + ((QQ >> (4 * s)) & 15) * SLOT + cr * 8192;
          const uint32_t need = 1u << kb;
          const bool ext = i >= 2 || layer == 0, early = ext && (ready & need) == need;
          mbar_wait_u(bar + B_EMPTYS + s * 8, (u + (s ? layer : 0) + 1) & 1);
          if (early) tma_2d_e(sb + ((QA >> (4 * s)) & 15) * SLOT, tx, kc, m0, fb);
          tma_2d_mc_e(kd, tw, 1024 + cr * 1024 + g * 128, kc, fb);
          tma_2d_mc_e(kd + 8192, tw, 1024 + cr * 1024 + g * 128 + 64, kc, fb);
          tma_2d_mc_e(qd, tw, g * 128 + cr * 64, kc, fb);
          expect_tx_e(fb, ext ? 65536 : 49152);
          PROFT(lane == 0 && layer == 0 && i == 1, 31);
          if (layer == 0 && g >= NCOM && i == XPF + (((g - NCOM) * XPM) >> 2)) {
            if (i <= 2) mbar_wait_u(bar + B_FULLS, 0);
            tma_pf_e(&tm_x0, g * 128, m0);
            tma_pf_e(&tm_x0, g * 128 + 64, m0);
          }
          if (layer < 2 && i >= PFS) {
            const int j = i - PFS;
            if (j < 2) tma_pf_e(layer ? &tm_woB : &tm_woA, g * 128 + j * 64, rb * 64);
            else if (j < 8 && layer == 0) tma_pf_e(&tm_wB, ((j >> 1) - 1) * 1024 + g * 128 + (j & 1) * 64, rb * 64);
          }
          if (ext && !early) {
            PROFT(i == 2 && lane == 0, 64 + layer * 16 + 0);
            src_wait_tma(g_xf + rb * 32, xbase + layer + 1, need, ready, lane, fb, 0);
            PROFT(i == 2 && lane == 0, 64 + layer * 16 + 1);
            fence_async_all();
            tma_2d_e(sb + ((QA >> (4 * s)) & 15) * SLOT, tx, kc, m0, fb);
          }
          if (++s == 3) { s = 0; ++u; }
        }
        if (layer == 0) xbase = ld_relaxed(&g_epoch) * NLAYERS;
        wo_a(layer, 2);
      }
    } else {
      if (warp >= 2) {
        const int h2 = threadIdx.x - 64;
        if (h2 < 16) sts_f(sb + SM_RS + h2 * 4, 0.f);
        if (h2 == 0) sts_f(sb + SM_EPOCH, __uint_as_float(epoch));
        mbar_wait_u(bar + B_FULLS, 0);
        colsum(&tm_wA, g_cs + (epoch & 1) * 6144, rb, g, warp - 2, 2, lane, warp == 2 ? sb + SM_SD : (sb + SM_BP + 1023u) & ~1023u, bar + B_CB + (warp - 2) * 8, 0);
#pragma unroll 1
        for (int i = h2; i < 320; i += 64) g_kv[(g * 16 + rb) * 320 + i] = make_uint4(0u, 0u, 0u, 0u);
        fence_async_all();
        nbar<5, 64>();
        if (h2 == 0) flag_add(&g_csflag[g].v);
        PROFT(h2 == 0, 242);
#pragma unroll 1
        for (int i = h2; i < 512; i += 256) {
          uint4 w[4];
#pragma unroll
          for (int j = 0; j < 4; ++j) w[j] = __ldg(reinterpret_cast<const uint4*>(wphi + (size_t)g * 4096) + i + j * 64);
#pragma unroll
          for (int j = 0; j < 4; ++j) sts128(sb + SM_WPHI + ((i >> 2) + j * 16) * 80 + (i & 3) * 16, w[j]);
        }
      }
      if (warp == 1) {
        if (lane >= 27) {
          const CUtensorMap* tm = lane == 27 ? &tm_o : lane == 28 ? &tm_wB : lane == 29 ? &tm_woA : lane == 30 ? &tm_woB : &tm_x;
          asm volatile("prefetch.tensormap [%0];" ::"l"(tm) : "memory");
        }
        __syncwarp();
        {
#pragma unroll 1
          for (int e = 0;; ++e) {
            if (e > 0 && e < NLAYERS) {
              mbar_wait_u(bar + B_XH0, (e - 1) & 1);
              flag_hint(g_xf + rb * 32 + 2 * g, xbase + e + 1);
            }
            mbar_wait_u(bar + B_XDONE, e & 1);
            PROFT(e < 4, 64 + e * 16 + 4);
            if (e == NLAYERS) {
              if (bid == 0) g_epoch = epoch + 1;
              break;
            }
            PROFT(e < 4, 64 + e * 16 + 5);
            flag_set(g_xf + rb * 32 + 2 * g + 1, xbase + e + 1);
            PROFT(e < 4, 64 + e * 16 + 7);
            if ((e & 1) == 0) {
#pragma unroll 1
              for (int hp = 0; hp < 2; ++hp) {
                uint4* kvl = g_kv + ((g * 2 + (e >> 1)) * 2 + hp) * 1280;
                mbar_wait_u(bar + B_KVDONE - hp * 32, (e >> 1) & 1);
                PROFT(e == PL, 243 + hp * 4);
                fence_async_smem();
                bulk_red_add_e(kvl + rb * 64, sb + (3 + hp) * SLOT + rb * 1024, 16384 - rb * 1024);
                if (rb) bulk_red_add_e(kvl, sb + (3 + hp) * SLOT, rb * 1024);
                bulk_red_add_e(kvl + 1024, sb + (6 + hp) * SLOT, 2048);
                bulk_red_add_e(kvl + 1152, sb + (6 + hp) * SLOT + 8192, 2048);
                bulk_commit();
                PROFT(e < 4, 64 + e * 16 + 6);
              }
              bulk_wait_read0();
              __syncwarp();
              if (lane < 2) release2(bar + B_E1);
              __syncwarp();
            }
            mbar_wait_u(bar + B_OH1, e & 1);
            PROFT(e == PL, 251);
            flag_hint(g_of + rb * 32 + 2 * g, xbase + e + 1);
            PROFT(e < 4, 64 + e * 16 + 9);
            mbar_wait_u(bar + B_ODONE, e & 1);
            PROFT(e < 4, 64 + e * 16 + 8);
            flag_hint(g_of + rb * 32 + 2 * g + 1, xbase + e + 1);
            PROFT(e < 4, 64 + e * 16 + 11);
          }
        }
      } else {
        const int h2 = threadIdx.x - 64;
        const float* cs = g_cs + (epoch & 1) * 6144;
#pragma unroll 1
        for (int layer = 0; layer < NLAYERS; ++layer) {
          if (warp == 2 && layer < 2) {
            if (lane == 0) flag_wait_t<128>(&g_csflag[layer * 8 + g].v, (epoch + 1) * (16u + layer));
            __syncwarp();
            float4 a[3];
#pragma unroll
            for (int i = 0; i < 3; ++i) a[i] = __ldcg(reinterpret_cast<const float4*>(cs + layer * 3072 + g * 384) + i * 32 + lane);
#pragma unroll 1
            for (int i = 0; i < 3; ++i) {
              const float av[4] = {a[0].x, a[0].y, a[0].z, a[0].w};
              a[0] = a[1]; a[1] = a[2];
#pragma unroll
              for (int j = 0; j < 4; ++j) {
                const float c1 = bf16r(av[j]), c2 = bf16r(av[j] - c1), c3 = (av[j] - c1) - c2;
                sts128(sb + SM_BP + layer * 6144 + ((i * 32 + lane) * 4 + j) * 16, make_uint4(pack_bf16(c1, c2), pack_bf16(c3, 0.f), 0u, 0u));
              }
            }
            fence_async_smem();
            __syncwarp();
            if (lane == 0) mbar_arrive(bar + (layer ? B_CS2 : B_CS));
            PROFT(lane == 0, 64 + layer * 16 + 12);
            if (layer == 0) {
              uint4* hz = g_halo + (rb * 8 + g) * 1024;
#pragma unroll 2
              for (int i = lane; i < 1024; i += 32) hz[i] = make_uint4(0u, 0u, 0u, 0u);
              if (lane < 12) reinterpret_cast<float4*>(g_cs + ((epoch & 1) ^ 1) * 6144 + bid * 48)[lane] = make_float4(0.f, 0.f, 0.f, 0.f);
              g_stats[(2 + (lane >> 4)) * S_ + m0 + g * 16 + (lane & 15)] = make_float2(0.f, 0.f);
              __syncwarp();
              if (lane == 0) flag_add(&g_csflag[8 + g].v);
            }
          }
          if (warp == 3) {
            const bool hal = (layer & 1) && rb > 0;
            {
              uint32_t rdy = 0u;
              src_wait<256>(g_xf + rb * 32, xbase + layer + 1, 0xAAAAu, rdy, lane);
              rdy = 0u;
              if (hal) src_wait<256>(g_xf + (rb - 1) * 32, xbase + layer + 1, 0xAAAAu, rdy, lane);
            }
            float2 u[5];
            const float2* sp = g_stats + layer * S_ + m0 + lane;
#pragma unroll
            for (int i = 0; i < 4; ++i) u[i] = __ldcg(sp + i * 32);
            u[4] = __ldcg(hal ? sp - 16 : sp);
            if (layer == 3) g_stats[(lane >> 4) * S_ + m0 + g * 16 + (lane & 15)] = make_float2(0.f, 0.f);
#pragma unroll
            for (int i = 0; i < 5; ++i) {
              const int r = i < 4 ? 16 + i * 32 + lane : lane;
              const float mean = u[i].x * (1.f / D_);
              const float var = fmaxf(fmaf(-u[i].x, mean, u[i].y) * (1.f / D_), 0.f);
              float sd;
              asm("sqrt.approx.f32 %0, %1;" : "=f"(sd) : "f"(bf16r(bf16r(var) + 1e-5f)));
              sd = bf16r(sd);
              if (i < 4 || hal) sts_f(sb + SM_RS + r * 4, rcp(sd));
              if (i < 4) {
                const float hm = -0.5f * bf16r(mean);
                const uint32_t s2 = pack_bf16(sd, sd);
                if (!(layer & 1)) sts128(sb + SM_SD + (r - 16) * 64 + ((r >> 1) & 3) * 16, make_uint4(s2, s2, s2, s2));
                sts128(sb + SM_AP + (r - 16) * 16, make_uint4(pack_bf16(hm, hm), pack_bf16(hm, 0.f), 0u, 0u));
              }
            }
            fence_async_smem();
            __syncwarp();
            if (lane == 0) mbar_arrive(bar + B_STAT);
            PROFT(lane == 0, 64 + layer * 16 + 14);
            wo_w(__shfl_sync(0xffffffffu, layer, 0));
          }
        }
      }
    }
    __syncwarp();
    asm volatile("barrier.cluster.arrive.relaxed.aligned;\nbarrier.cluster.wait.aligned;\n" ::: "memory");
  } else {
    if (warp == 5) {
      if (lane == 0) {
        mbar_init(bar + B_FULLS, 1);
        asm volatile("fence.mbarrier_init.release.cluster;" ::: "memory");
      }
      __syncwarp();
      expect_tx_e(bar + B_FULLS, 65536);
      tma_2d_e(sb + XS * SLOT, &tm_x0, 0, m0, bar + B_FULLS);
#pragma unroll
      for (int j = 0; j < 6; ++j)
        tma_2d_e(sb + (j < 4 ? j + 4 : j - 2) * 8192, &tm_wA, (j < 4 ? 1024 + (j >> 1) * 1024 : 0) + g * 128 + (j & 1) * 64, 0, bar + B_FULLS);
      PROFT(lane == 0, 241);
    }
    if (lane < 8 && warp != 5 && threadIdx.x != 128) {
      const int i = (warp - 4) * 8 + lane;
      mbar_init(bar + i * 8, i < 32 ? 1u << ((BAR_CNT >> (2 * i)) & 3) : i < 48 ? 1u : (i == 59 || i == 60 || i == 62) ? 16u : (i == 48 || i == 63) ? 8u : 4u);
      asm volatile("fence.mbarrier_init.release.cluster;" ::: "memory");
    }
    __syncwarp();
    asm volatile("barrier.cluster.arrive.relaxed.aligned;" ::: "memory");
    asm volatile("setmaxnreg.inc.sync.aligned.u32 232;");
    cluster_wait();
    PROFT(threadIdx.x == 128, 0);
    Ctx c; c.sb = sb; c.g = g; c.rb = rb; c.cu = warp - 4; c.out = out;
    consumer(c);
    asm volatile("bar.warp.sync 0xffffffff;\nbarrier.cluster.arrive.relaxed.aligned;\nbarrier.cluster.wait.aligned;\n" ::: "memory");
  }
}

typedef CUresult (*PFN_encodeTiled)(CUtensorMap*, CUtensorMapDataType, cuuint32_t, void*, const cuuint64_t*, const cuuint64_t*,
                                    const cuuint32_t*, const cuuint32_t*, CUtensorMapInterleave, CUtensorMapSwizzle,
                                    CUtensorMapL2promotion, CUtensorMapFloatOOBfill);

static CUtensorMap make_map(PFN_encodeTiled enc, const void* ptr, uint64_t cols, uint64_t rows, uint32_t box_c, uint32_t box_r, uint32_t nb = 1) {
  CUtensorMap m;
  cuuint64_t dims[3] = {nb > 1 ? box_c : cols, rows, cols / box_c};
  cuuint64_t strides[2] = {cols * 2, box_c * 2};
  cuuint32_t box[3] = {box_c, box_r, nb};
  cuuint32_t es[3] = {1, 1, 1};
  CUresult r = enc(&m, CU_TENSOR_MAP_DATA_TYPE_BFLOAT16, nb > 1 ? 3 : 2, const_cast<void*>(ptr), dims, strides, box, es, CU_TENSOR_MAP_INTERLEAVE_NONE,
      CU_TENSOR_MAP_SWIZZLE_128B, CU_TENSOR_MAP_L2_PROMOTION_L2_256B, CU_TENSOR_MAP_FLOAT_OOB_FILL_NONE);
  (void)r;
  return m;
}

extern "C" void kernel_launch(void* const* d_in, const int* in_sizes, int n_in, void* d_out, int out_size) {
  const bf16* A_x = (const bf16*)d_in[0];
  const bf16* A_wqkv = (const bf16*)d_in[1];
  const bf16* A_wphi = (const bf16*)d_in[2];
  const bf16* A_wo = (const bf16*)d_in[3];
  const bf16* B_wqkv = (const bf16*)d_in[5];
  const bf16* B_wo = (const bf16*)d_in[6];
  bf16* out = (bf16*)d_out;

  static PFN_encodeTiled enc = nullptr;
  static bf16 *p_x, *p_o;
  static bool together;
  if (!enc) {
    void* fn = nullptr; cudaDriverEntryPointQueryResult qr;
    cudaGetDriverEntryPoint("cuTensorMapEncodeTiled", &fn, cudaEnableDefault, &qr);
    enc = (PFN_encodeTiled)fn;
    cudaGetSymbolAddress((void**)&p_x, g_x);
    cudaGetSymbolAddress((void**)&p_o, g_o);
    cudaFuncSetAttribute(mega_kernel, cudaFuncAttributeMaxDynamicSharedMemorySize, SM_TOTAL);
    cudaLaunchConfig_t cfg = {};
    cfg.gridDim = dim3(128 + NX); cfg.blockDim = dim3(384); cfg.dynamicSmemBytes = SM_TOTAL;
    cudaLaunchAttribute at[1];
    at[0].id = cudaLaunchAttributeClusterDimension; at[0].val.clusterDim.x = 2; at[0].val.clusterDim.y = 1; at[0].val.clusterDim.z = 1;
    cfg.attrs = at; cfg.numAttrs = 1;
    int ncl = 0;
    together = cudaOccupancyMaxActiveClusters(&ncl, mega_kernel, &cfg) == cudaSuccess && 2 * ncl == 128 + NX;
    int nsm = 0;
    cudaDeviceGetAttribute(&nsm, cudaDevAttrMultiProcessorCount, 0);
    together = together && nsm == 128 + NX;
  }
  CUtensorMap tm_x0 = make_map(enc, A_x, 1024, 2048, 64, 128);
  CUtensorMap tm_x = make_map(enc, p_x, 1024, 2048, 64, 128);
  CUtensorMap tm_o = make_map(enc, p_o, 1024, 2048, 64, 128);
  CUtensorMap tm_wA = make_map(enc, A_wqkv, 3072, 1024, 64, 64);
  CUtensorMap tm_wB = make_map(enc, B_wqkv, 3072, 1024, 64, 64);
  CUtensorMap tm_woA = make_map(enc, A_wo, 1024, 1024, 64, 64);
  CUtensorMap tm_woB = make_map(enc, B_wo, 1024, 1024, 64, 64);
  if (!together) mega_kernel<<<NX, 384, SM_TOTAL, cudaStreamPerThread>>>(tm_x0, tm_x, tm_o, tm_wA, tm_wB, tm_woA, tm_woB, B_wqkv, A_wphi, out);
  mega_kernel<<<together ? 128 + NX : 128, 384, SM_TOTAL, cudaStreamPerThread>>>(tm_x0, tm_x, tm_o, tm_wA, tm_wB, tm_woA, tm_woB,
                                                                                 B_wqkv, A_wphi, out);
}
```

```cpp
#include <cuda_runtime.h>
#include <cuda_bf16.h>
#include <cuda.h>
#include <stdint.h>

typedef __nv_bfloat16 bf16;

constexpr int S_ = 2048, D_ = 1024;

struct __align__(128) Flag { unsigned int v; unsigned int pad[31]; };
__device__ __align__(1024) bf16 g_x[S_ * D_];
__device__ __align__(1024) bf16 g_o[S_ * D_];
__device__ __align__(1024) uint4 g_halo[128 * 2 * 512];
__device__ __align__(1024) uint4 g_kv[8 * 2 * 2 * 1280];
__device__ __align__(1024) float2 g_stats[4 * S_];
__device__ __align__(1024) float g_cs[2 * 2 * 3072];
__device__ Flag g_csflag[16];
__device__ __align__(128) unsigned int g_xf[16 * 32], g_of[16 * 32];
__device__ unsigned int g_epoch, g_err;
#define PROFT(cond, idx) asm volatile("" ::: "memory")

__device__ __forceinline__ uint32_t smem_u32(const void* p) { return (uint32_t)__cvta_generic_to_shared(p); }
__device__ __forceinline__ void mbar_init(uint32_t bar, uint32_t count) {
  asm volatile("mbarrier.init.shared::cta.b64 [%0], %1;" ::"r"(bar), "r"(count) : "memory");
}
__device__ __forceinline__ void mbar_arrive(uint32_t bar) {
  asm volatile("mbarrier.arrive.shared::cta.b64 _, [%0];" ::"r"(bar) : "memory");
}
__device__ __forceinline__ bool mbar_try_wait(uint32_t bar, uint32_t parity) {
  uint32_t ok;
  asm volatile("{\n.reg .pred p;\nmbarrier.try_wait.parity.shared::cta.b64 p, [%1], %2;\nselp.b32 %0, 1, 0, p;\n}\n"
               : "=r"(ok) : "r"(bar), "r"(parity) : "memory");
  return ok != 0;
}
__device__ __forceinline__ bool mbar_test_wait(uint32_t bar, uint32_t parity) {
  uint32_t ok;
  asm volatile("{\n.reg .pred p;\nmbarrier.test_wait.parity.shared::cta.b64 p, [%1], %2;\nselp.b32 %0, 1, 0, p;\n}\n"
               : "=r"(ok) : "r"(bar), "r"(parity) : "memory");
  return ok != 0;
}
__device__ __forceinline__ uint64_t gtimer() {
  uint64_t t; asm volatile("mov.u64 %0, %globaltimer;" : "=l"(t)); return t;
}
__device__ __forceinline__ void mbar_wait(uint32_t bar, uint32_t parity) {
  uint32_t n = 0;
#pragma unroll 1
  while (!mbar_try_wait(bar, parity)) {
    if (++n > (1u << 22)) { g_err = 1u; break; }
  }
}
__device__ __forceinline__ unsigned int ld_acquire(const unsigned int* p) {
  unsigned int v; asm volatile("ld.acquire.gpu.global.u32 %0, [%1];" : "=r"(v) : "l"(p) : "memory"); return v;
}
__device__ __forceinline__ void flag_add(unsigned int* p) {
  asm volatile("red.release.gpu.global.add.u32 [%0], 1;" ::"l"(p) : "memory");
}
__device__ __forceinline__ void flag_set(unsigned int* p, unsigned int v) {
  asm volatile("st.release.gpu.global.u32 [%0], %1;" ::"l"(p), "r"(v) : "memory");
}
__device__ __forceinline__ void flag_hint(unsigned int* p, unsigned int v) {
  asm volatile("st.relaxed.gpu.global.u32 [%0], %1;" ::"l"(p), "r"(v) : "memory");
}
template <int SLEEP>
__device__ __forceinline__ void src_wait(const unsigned int* f, unsigned int target, uint32_t need, uint32_t& ready, int lane) {
  uint32_t n = 0;
#pragma unroll 1
  while ((ready & need) != need) {
    const unsigned int v = ld_acquire(f + (lane & 15));
    ready = __ballot_sync(0xffffffffu, (int)(v - target) >= 0);
    if (SLEEP) { if ((ready & need) != need) __nanosleep(SLEEP); }
    if (++n > (1u << 20)) { g_err = 3u; break; }
  }
  __syncwarp();
}
__device__ __forceinline__ unsigned int ld_relaxed(const unsigned int* p) {
  unsigned int v; asm volatile("ld.relaxed.gpu.global.u32 %0, [%1];" : "=r"(v) : "l"(p) : "memory"); return v;
}
__device__ __forceinline__ bool src_wait_tma(const unsigned int* f, unsigned int target, uint32_t need, uint32_t& ready, int lane, uint32_t eb, uint32_t par) {
  uint32_t n = 0;
  bool fr = false;
#pragma unroll 1
  while ((ready & need) != need) {
    const unsigned int v = ld_acquire(f + (lane & 15));
    fr = __all_sync(0xffffffffu, mbar_test_wait(eb, par));
    ready = __ballot_sync(0xffffffffu, (int)(v - target) >= 0);
    if (++n > (1u << 20)) { g_err = 3u; break; }
  }
  return fr;
}
__device__ __forceinline__ uint4 ld_relaxed4(const uint4* p) {
  uint4 v; asm volatile("ld.relaxed.gpu.global.v4.u32 {%0,%1,%2,%3}, [%4];" : "=r"(v.x), "=r"(v.y), "=r"(v.z), "=r"(v.w) : "l"(p) : "memory"); return v;
}
__device__ __forceinline__ void st_relaxed4(uint4* p, uint32_t a, uint32_t b, uint32_t c, uint32_t d) {
  asm volatile("st.relaxed.gpu.global.v4.u32 [%0], {%1,%2,%3,%4};" ::"l"(p), "r"(a), "r"(b), "r"(c), "r"(d) : "memory");
}
template <int SLEEP>
__device__ __forceinline__ void flag_wait_t(const unsigned int* p, unsigned int target) {
  uint32_t n = 0;
#pragma unroll 1
  while ((int)(ld_acquire(p) - target) < 0) {
    if (SLEEP) __nanosleep(SLEEP);
    if (++n > (1u << 20)) { g_err = 2u; break; }
  }
}
__device__ __forceinline__ void mbar_wait_u(uint32_t bar, uint32_t parity) {
  uint32_t n = 0;
#pragma unroll 1
  while (!__all_sync(0xffffffffu, mbar_try_wait(bar, parity))) {
    if (++n > (1u << 22)) { g_err = 1u; break; }
  }
}
__device__ __forceinline__ void expect_tx_e(uint32_t bar, uint32_t bytes) {
  asm volatile("{\n.reg .pred p;\nelect.sync _|p, 0xffffffff;\n@p mbarrier.arrive.expect_tx.shared::cta.b64 _, [%0], %1;\n}\n" ::"r"(bar), "r"(bytes) : "memory");
}
__device__ __forceinline__ void tma_2d_e(uint32_t dst, const CUtensorMap* tm, int c0, int c1, uint32_t bar) {
  asm volatile("{\n.reg .pred p;\nelect.sync _|p, 0xffffffff;\n"
               "@p cp.async.bulk.tensor.2d.shared::cluster.global.mbarrier::complete_tx::bytes [%0], [%1, {%2, %3}], [%4];\n}\n"
               ::"r"(dst), "l"(tm), "r"(c0), "r"(c1), "r"(bar) : "memory");
}
__device__ __forceinline__ void tma_2d_mc_e(uint32_t dst, const CUtensorMap* tm, int c0, int c1, uint32_t bar) {
  asm volatile("{\n.reg .pred p;\nelect.sync _|p, 0xffffffff;\n"
               "@p cp.async.bulk.tensor.2d.shared::cluster.global.mbarrier::complete_tx::bytes.multicast::cluster [%0], [%1, {%2, %3}], [%4], %5;\n}\n"
               ::"r"(dst), "l"(tm), "r"(c0), "r"(c1), "r"(bar), "h"((uint16_t)3) : "memory");
}
__device__ __forceinline__ void tma_pf_e(const CUtensorMap* tm, int c0, int c1) {
  asm volatile("{\n.reg .pred p;\nelect.sync _|p, 0xffffffff;\n"
               "@p cp.async.bulk.prefetch.tensor.2d.L2.global.tile [%0, {%1, %2}];\n}\n" ::"l"(tm), "r"(c0), "r"(c1) : "memory");
}
__device__ __forceinline__ void mbar_arrive_cluster(uint32_t local_bar, uint32_t rank) {
  asm volatile("{\n.reg .b32 ra;\nmapa.shared::cluster.u32 ra, %0, %1;\nmbarrier.arrive.shared::cluster.b64 _, [ra];\n}\n"
               ::"r"(local_bar), "r"(rank) : "memory");
}
__device__ __forceinline__ void release2(uint32_t bar) { mbar_arrive_cluster(bar, 0); mbar_arrive_cluster(bar, 1); }
__device__ __forceinline__ void bulk_red_add_e(void* dst, uint32_t src, uint32_t bytes) {
  asm volatile("{\n.reg .pred p;\nelect.sync _|p, 0xffffffff;\n@p cp.reduce.async.bulk.global.shared::cta.bulk_group.add.f32 [%0], [%1], %2;\n}\n" ::"l"(dst), "r"(src), "r"(bytes) : "memory");
}
__device__ __forceinline__ void bulk_commit() { asm volatile("cp.async.bulk.commit_group;" ::: "memory"); }
__device__ __forceinline__ void bulk_wait_read0() { asm volatile("cp.async.bulk.wait_group.read 0;" ::: "memory"); }
__device__ __forceinline__ void fence_async_smem() { asm volatile("fence.proxy.async.shared::cta;" ::: "memory"); }
__device__ __forceinline__ void fence_async_all() { asm volatile("fence.proxy.async.global;" ::: "memory"); }
__device__ __forceinline__ void wgmma_fence() { asm volatile("wgmma.fence.sync.aligned;" ::: "memory"); }
__device__ __forceinline__ void wgmma_commit() { asm volatile("wgmma.commit_group.sync.aligned;" ::: "memory"); }
template <int N> __device__ __forceinline__ void wgmma_wait() { asm volatile("wgmma.wait_group.sync.aligned %0;" ::"n"(N) : "memory"); }
__device__ __forceinline__ void cluster_wait() { asm volatile("barrier.cluster.wait.acquire.aligned;" ::: "memory"); }
template <int ID, int N> __device__ __forceinline__ void nbar() { asm volatile("bar.sync %0, %1;" ::"n"(ID), "n"(N) : "memory"); }
__device__ __forceinline__ uint64_t desc64(uint32_t lo, uint32_t hi) { return (uint64_t)lo | ((uint64_t)hi << 32); }
__device__ __forceinline__ uint32_t pack_bf16(float lo, float hi) {
  uint32_t r; asm("cvt.rn.bf16x2.f32 %0, %1, %2;" : "=r"(r) : "f"(hi), "f"(lo)); return r;
}
__device__ __forceinline__ uint32_t mul_bf16x2(uint32_t a, uint32_t s, bool hi) {
  __nv_bfloat162 x = *reinterpret_cast<__nv_bfloat162*>(&a), y = *reinterpret_cast<__nv_bfloat162*>(&s);
  x = __hmul2(x, hi ? __high2bfloat162(y) : __low2bfloat162(y));
  return *reinterpret_cast<uint32_t*>(&x);
}
__device__ __forceinline__ float bf16r(float x) { return __bfloat162float(__float2bfloat16_rn(x)); }
__device__ __forceinline__ float bf_lo(uint32_t u) { return __uint_as_float(u << 16); }
__device__ __forceinline__ float bf_hi(uint32_t u) { return __uint_as_float(u & 0xFFFF0000u); }
__device__ __forceinline__ float ex2(float x) { float r; asm("ex2.approx.ftz.f32 %0, %1;" : "=f"(r) : "f"(x)); return r; }
__device__ __forceinline__ float rcp(float x) { float r; asm("rcp.approx.ftz.f32 %0, %1;" : "=f"(r) : "f"(x)); return r; }
__device__ __forceinline__ void mma_bf16(float (&d)[4], uint32_t a0, uint32_t a1, uint32_t a2, uint32_t a3, uint32_t b0, uint32_t b1) {
  asm("mma.sync.aligned.m16n8k16.row.col.f32.bf16.bf16.f32 {%0,%1,%2,%3}, {%4,%5,%6,%7}, {%8,%9}, {%0,%1,%2,%3};"
               : "+f"(d[0]), "+f"(d[1]), "+f"(d[2]), "+f"(d[3]) : "r"(a0), "r"(a1), "r"(a2), "r"(a3), "r"(b0), "r"(b1));
}
__device__ __forceinline__ void ldsm_x4(uint32_t& r0, uint32_t& r1, uint32_t& r2, uint32_t& r3, uint32_t addr) {
  asm volatile("ldmatrix.sync.aligned.m8n8.x4.shared.b16 {%0,%1,%2,%3}, [%4];"
               : "=r"(r0), "=r"(r1), "=r"(r2), "=r"(r3) : "r"(addr) : "memory");
}
__device__ __forceinline__ void ldsm_x4_t(uint32_t& r0, uint32_t& r1, uint32_t& r2, uint32_t& r3, uint32_t addr) {
  asm volatile("ldmatrix.sync.aligned.m8n8.x4.trans.shared.b16 {%0,%1,%2,%3}, [%4];"
               : "=r"(r0), "=r"(r1), "=r"(r2), "=r"(r3) : "r"(addr) : "memory");
}
__device__ __forceinline__ void stsm_x4(uint32_t addr, uint32_t r0, uint32_t r1, uint32_t r2, uint32_t r3) {
  asm volatile("stmatrix.sync.aligned.m8n8.x4.shared.b16 [%0], {%1,%2,%3,%4};"
               ::"r"(addr), "r"(r0), "r"(r1), "r"(r2), "r"(r3) : "memory");
}
__device__ __forceinline__ uint4 lds128(uint32_t addr) {
  uint4 v; asm volatile("ld.shared.v4.b32 {%0,%1,%2,%3}, [%4];" : "=r"(v.x), "=r"(v.y), "=r"(v.z), "=r"(v.w) : "r"(addr) : "memory"); return v;
}
__device__ __forceinline__ void sts128(uint32_t addr, uint4 v) {
  asm volatile("st.shared.v4.b32 [%0], {%1,%2,%3,%4};" ::"r"(addr), "r"(v.x), "r"(v.y), "r"(v.z), "r"(v.w) : "memory");
}
__device__ __forceinline__ float lds_f(uint32_t addr) {
  float v; asm volatile("ld.shared.f32 %0, [%1];" : "=f"(v) : "r"(addr) : "memory"); return v;
}
__device__ __forceinline__ uint32_t lds_vol(uint32_t addr) {
  uint32_t v; asm volatile("ld.volatile.shared.u32 %0, [%1];" : "=r"(v) : "r"(addr) : "memory"); return v;
}
__device__ __forceinline__ void nbar_dyn(int id, int n) { asm volatile("bar.sync %0, %1;" ::"r"(id), "r"(n) : "memory"); }
__device__ __forceinline__ uint64_t make_desc_ns(uint32_t addr, uint32_t lbo_bytes, uint32_t sbo_bytes) {
  return (uint64_t)((addr & 0x3FFFF) >> 4) | ((uint64_t)(lbo_bytes >> 4) << 16) | ((uint64_t)(sbo_bytes >> 4) << 32);
}
__device__ __forceinline__ void sts_f(uint32_t addr, float v) { asm volatile("st.shared.f32 [%0], %1;" ::"r"(addr), "f"(v) : "memory"); }
__device__ __forceinline__ void red_add2(float* p, float a, float b) {
  asm volatile("red.global.add.v2.f32 [%0], {%1,%2};" ::"l"(p), "f"(a), "f"(b) : "memory");
}
__device__ __forceinline__ void red_add4(float* p, float a, float b, float c, float d) {
  asm volatile("red.global.add.v4.f32 [%0], {%1,%2,%3,%4};" ::"l"(p), "f"(a), "f"(b), "f"(c), "f"(d) : "memory");
}

__device__ __forceinline__ void wgmma_n256(float (&d)[192], uint64_t da, uint64_t db, int scale_d) {
  asm volatile("{\n.reg .pred p;\nsetp.ne.b32 p, %130, 0;\n"
    "wgmma.mma_async.sync.aligned.m64n256k16.f32.bf16.bf16 {%0, %1, %2, %3, %4, %5, %6, %7, %8, %9, %10, %11, %12, %13, %14, %15, %16, %17, %18, %19, %20, %21, %22, %23, %24, %25, %26, %27, %28, %29, %30, %31, %32, %33, %34, %35, %36, %37, %38, %39, %40, %41, %42, %43, %44, %45, %46, %47, %48, %49, %50, %51, %52, %53, %54, %55, %56, %57, %58, %59, %60, %61, %62, %63, %64, %65, %66, %67, %68, %69, %70, %71, %72, %73, %74, %75, %76, %77, %78, %79, %80, %81, %82, %83, %84, %85, %86, %87, %88, %89, %90, %91, %92, %93, %94, %95, %96, %97, %98, %99, %100, %101, %102, %103, %104, %105, %106, %107, %108, %109, %110, %111, %112, %113, %114, %115, %116, %117, %118, %119, %120, %121, %122, %123, %124, %125, %126, %127}, %128, %129, p, 1, 1, 0, 1;\n}\n"
    : "+f"(d[0]), "+f"(d[1]), "+f"(d[2]), "+f"(d[3]), "+f"(d[4]), "+f"(d[5]), "+f"(d[6]), "+f"(d[7]), "+f"(d[8]), "+f"(d[9]), "+f"(d[10]), "+f"(d[11]), "+f"(d[12]), "+f"(d[13]), "+f"(d[14]), "+f"(d[15]), "+f"(d[16]), "+f"(d[17]), "+f"(d[18]), "+f"(d[19]), "+f"(d[20]), "+f"(d[21]), "+f"(d[22]), "+f"(d[23]), "+f"(d[24]), "+f"(d[25]), "+f"(d[26]), "+f"(d[27]), "+f"(d[28]), "+f"(d[29]), "+f"(d[30]), "+f"(d[31]), "+f"(d[32]), "+f"(d[33]), "+f"(d[34]), "+f"(d[35]), "+f"(d[36]), "+f"(d[37]), "+f"(d[38]), "+f"(d[39]), "+f"(d[40]), "+f"(d[41]), "+f"(d[42]), "+f"(d[43]), "+f"(d[44]), "+f"(d[45]), "+f"(d[46]), "+f"(d[47]), "+f"(d[48]), "+f"(d[49]), "+f"(d[50]), "+f"(d[51]), "+f"(d[52]), "+f"(d[53]), "+f"(d[54]), "+f"(d[55]), "+f"(d[56]), "+f"(d[57]), "+f"(d[58]), "+f"(d[59]), "+f"(d[60]), "+f"(d[61]), "+f"(d[62]), "+f"(d[63]), "+f"(d[64]), "+f"(d[65]), "+f"(d[66]), "+f"(d[67]), "+f"(d[68]), "+f"(d[69]), "+f"(d[70]), "+f"(d[71]), "+f"(d[72]), "+f"(d[73]), "+f"(d[74]), "+f"(d[75]), "+f"(d[76]), "+f"(d[77]), "+f"(d[78]), "+f"(d[79]), "+f"(d[80]), "+f"(d[81]), "+f"(d[82]), "+f"(d[83]), "+f"(d[84]), "+f"(d[85]), "+f"(d[86]), "+f"(d[87]), "+f"(d[88]), "+f"(d[89]), "+f"(d[90]), "+f"(d[91]), "+f"(d[92]), "+f"(d[93]), "+f"(d[94]), "+f"(d[95]), "+f"(d[96]), "+f"(d[97]), "+f"(d[98]), "+f"(d[99]), "+f"(d[100]), "+f"(d[101]), "+f"(d[102]), "+f"(d[103]), "+f"(d[104]), "+f"(d[105]), "+f"(d[106]), "+f"(d[107]), "+f"(d[108]), "+f"(d[109]), "+f"(d[110]), "+f"(d[111]), "+f"(d[112]), "+f"(d[113]), "+f"(d[114]), "+f"(d[115]), "+f"(d[116]), "+f"(d[117]), "+f"(d[118]), "+f"(d[119]), "+f"(d[120]), "+f"(d[121]), "+f"(d[122]), "+f"(d[123]), "+f"(d[124]), "+f"(d[125]), "+f"(d[126]), "+f"(d[127])
    : "l"(da), "l"(db), "r"(scale_d));
}
__device__ __forceinline__ void wgmma_n128(float (&d)[192], uint64_t da, uint64_t db, int scale_d) {
  asm volatile("{\n.reg .pred p;\nsetp.ne.b32 p, %66, 0;\n"
    "wgmma.mma_async.sync.aligned.m64n128k16.f32.bf16.bf16 {%0, %1, %2, %3, %4, %5, %6, %7, %8, %9, %10, %11, %12, %13, %14, %15, %16, %17, %18, %19, %20, %21, %22, %23, %24, %25, %26, %27, %28, %29, %30, %31, %32, %33, %34, %35, %36, %37, %38, %39, %40, %41, %42, %43, %44, %45, %46, %47, %48, %49, %50, %51, %52, %53, %54, %55, %56, %57, %58, %59, %60, %61, %62, %63}, %64, %65, p, 1, 1, 0, 1;\n}\n"
    : "+f"(d[128]), "+f"(d[129]), "+f"(d[130]), "+f"(d[131]), "+f"(d[132]), "+f"(d[133]), "+f"(d[134]), "+f"(d[135]), "+f"(d[136]), "+f"(d[137]), "+f"(d[138]), "+f"(d[139]), "+f"(d[140]), "+f"(d[141]), "+f"(d[142]), "+f"(d[143]), "+f"(d[144]), "+f"(d[145]), "+f"(d[146]), "+f"(d[147]), "+f"(d[148]), "+f"(d[149]), "+f"(d[150]), "+f"(d[151]), "+f"(d[152]), "+f"(d[153]), "+f"(d[154]), "+f"(d[155]), "+f"(d[156]), "+f"(d[157]), "+f"(d[158]), "+f"(d[159]), "+f"(d[160]), "+f"(d[161]), "+f"(d[162]), "+f"(d[163]), "+f"(d[164]), "+f"(d[165]), "+f"(d[166]), "+f"(d[167]), "+f"(d[168]), "+f"(d[169]), "+f"(d[170]), "+f"(d[171]), "+f"(d[172]), "+f"(d[173]), "+f"(d[174]), "+f"(d[175]), "+f"(d[176]), "+f"(d[177]), "+f"(d[178]), "+f"(d[179]), "+f"(d[180]), "+f"(d[181]), "+f"(d[182]), "+f"(d[183]), "+f"(d[184]), "+f"(d[185]), "+f"(d[186]), "+f"(d[187]), "+f"(d[188]), "+f"(d[189]), "+f"(d[190]), "+f"(d[191])
    : "l"(da), "l"(db), "r"(scale_d));
}
__device__ __forceinline__ void wgmma_n256_k(float (&d)[192], uint64_t da, uint64_t db, int scale_d) {
  asm volatile("{\n.reg .pred p;\nsetp.ne.b32 p, %130, 0;\n"
    "wgmma.mma_async.sync.aligned.m64n256k16.f32.bf16.bf16 {%0, %1, %2, %3, %4, %5, %6, %7, %8, %9, %10, %11, %12, %13, %14, %15, %16, %17, %18, %19, %20, %21, %22, %23, %24, %25, %26, %27, %28, %29, %30, %31, %32, %33, %34, %35, %36, %37, %38, %39, %40, %41, %42, %43, %44, %45, %46, %47, %48, %49, %50, %51, %52, %53, %54, %55, %56, %57, %58, %59, %60, %61, %62, %63, %64, %65, %66, %67, %68, %69, %70, %71, %72, %73, %74, %75, %76, %77, %78, %79, %80, %81, %82, %83, %84, %85, %86, %87, %88, %89, %90, %91, %92, %93, %94, %95, %96, %97, %98, %99, %100, %101, %102, %103, %104, %105, %106, %107, %108, %109, %110, %111, %112, %113, %114, %115, %116, %117, %118, %119, %120, %121, %122, %123, %124, %125, %126, %127}, %128, %129, p, 1, 1, 0, 0;\n}\n"
    : "+f"(d[0]), "+f"(d[1]), "+f"(d[2]), "+f"(d[3]), "+f"(d[4]), "+f"(d[5]), "+f"(d[6]), "+f"(d[7]), "+f"(d[8]), "+f"(d[9]), "+f"(d[10]), "+f"(d[11]), "+f"(d[12]), "+f"(d[13]), "+f"(d[14]), "+f"(d[15]), "+f"(d[16]), "+f"(d[17]), "+f"(d[18]), "+f"(d[19]), "+f"(d[20]), "+f"(d[21]), "+f"(d[22]), "+f"(d[23]), "+f"(d[24]), "+f"(d[25]), "+f"(d[26]), "+f"(d[27]), "+f"(d[28]), "+f"(d[29]), "+f"(d[30]), "+f"(d[31]), "+f"(d[32]), "+f"(d[33]), "+f"(d[34]), "+f"(d[35]), "+f"(d[36]), "+f"(d[37]), "+f"(d[38]), "+f"(d[39]), "+f"(d[40]), "+f"(d[41]), "+f"(d[42]), "+f"(d[43]), "+f"(d[44]), "+f"(d[45]), "+f"(d[46]), "+f"(d[47]), "+f"(d[48]), "+f"(d[49]), "+f"(d[50]), "+f"(d[51]), "+f"(d[52]), "+f"(d[53]), "+f"(d[54]), "+f"(d[55]), "+f"(d[56]), "+f"(d[57]), "+f"(d[58]), "+f"(d[59]), "+f"(d[60]), "+f"(d[61]), "+f"(d[62]), "+f"(d[63]), "+f"(d[64]), "+f"(d[65]), "+f"(d[66]), "+f"(d[67]), "+f"(d[68]), "+f"(d[69]), "+f"(d[70]), "+f"(d[71]), "+f"(d[72]), "+f"(d[73]), "+f"(d[74]), "+f"(d[75]), "+f"(d[76]), "+f"(d[77]), "+f"(d[78]), "+f"(d[79]), "+f"(d[80]), "+f"(d[81]), "+f"(d[82]), "+f"(d[83]), "+f"(d[84]), "+f"(d[85]), "+f"(d[86]), "+f"(d[87]), "+f"(d[88]), "+f"(d[89]), "+f"(d[90]), "+f"(d[91]), "+f"(d[92]), "+f"(d[93]), "+f"(d[94]), "+f"(d[95]), "+f"(d[96]), "+f"(d[97]), "+f"(d[98]), "+f"(d[99]), "+f"(d[100]), "+f"(d[101]), "+f"(d[102]), "+f"(d[103]), "+f"(d[104]), "+f"(d[105]), "+f"(d[106]), "+f"(d[107]), "+f"(d[108]), "+f"(d[109]), "+f"(d[110]), "+f"(d[111]), "+f"(d[112]), "+f"(d[113]), "+f"(d[114]), "+f"(d[115]), "+f"(d[116]), "+f"(d[117]), "+f"(d[118]), "+f"(d[119]), "+f"(d[120]), "+f"(d[121]), "+f"(d[122]), "+f"(d[123]), "+f"(d[124]), "+f"(d[125]), "+f"(d[126]), "+f"(d[127])
    : "l"(da), "l"(db), "r"(scale_d));
}
__device__ __forceinline__ void wgmma_n128_k(float (&d)[192], uint64_t da, uint64_t db, int scale_d) {
  asm volatile("{\n.reg .pred p;\nsetp.ne.b32 p, %66, 0;\n"
    "wgmma.mma_async.sync.aligned.m64n128k16.f32.bf16.bf16 {%0, %1, %2, %3, %4, %5, %6, %7, %8, %9, %10, %11, %12, %13, %14, %15, %16, %17, %18, %19, %20, %21, %22, %23, %24, %25, %26, %27, %28, %29, %30, %31, %32, %33, %34, %35, %36, %37, %38, %39, %40, %41, %42, %43, %44, %45, %46, %47, %48, %49, %50, %51, %52, %53, %54, %55, %56, %57, %58, %59, %60, %61, %62, %63}, %64, %65, p, 1, 1, 0, 0;\n}\n"
    : "+f"(d[128]), "+f"(d[129]), "+f"(d[130]), "+f"(d[131]), "+f"(d[132]), "+f"(d[133]), "+f"(d[134]), "+f"(d[135]), "+f"(d[136]), "+f"(d[137]), "+f"(d[138]), "+f"(d[139]), "+f"(d[140]), "+f"(d[141]), "+f"(d[142]), "+f"(d[143]), "+f"(d[144]), "+f"(d[145]), "+f"(d[146]), "+f"(d[147]), "+f"(d[148]), "+f"(d[149]), "+f"(d[150]), "+f"(d[151]), "+f"(d[152]), "+f"(d[153]), "+f"(d[154]), "+f"(d[155]), "+f"(d[156]), "+f"(d[157]), "+f"(d[158]), "+f"(d[159]), "+f"(d[160]), "+f"(d[161]), "+f"(d[162]), "+f"(d[163]), "+f"(d[164]), "+f"(d[165]), "+f"(d[166]), "+f"(d[167]), "+f"(d[168]), "+f"(d[169]), "+f"(d[170]), "+f"(d[171]), "+f"(d[172]), "+f"(d[173]), "+f"(d[174]), "+f"(d[175]), "+f"(d[176]), "+f"(d[177]), "+f"(d[178]), "+f"(d[179]), "+f"(d[180]), "+f"(d[181]), "+f"(d[182]), "+f"(d[183]), "+f"(d[184]), "+f"(d[185]), "+f"(d[186]), "+f"(d[187]), "+f"(d[188]), "+f"(d[189]), "+f"(d[190]), "+f"(d[191])
    : "l"(da), "l"(db), "r"(scale_d));
}
__device__ __forceinline__ void wgmma_n40_tt(float (&d)[20], uint64_t da, uint64_t db, int scale_d) {
  asm volatile("{\n.reg .pred p;\nsetp.ne.b32 p, %22, 0;\n"
    "wgmma.mma_async.sync.aligned.m64n40k16.f32.bf16.bf16 {%0, %1, %2, %3, %4, %5, %6, %7, %8, %9, %10, %11, %12, %13, %14, %15, %16, %17, %18, %19}, %20, %21, p, 1, 1, 1, 1;\n}\n"
    : "+f"(d[0]), "+f"(d[1]), "+f"(d[2]), "+f"(d[3]), "+f"(d[4]), "+f"(d[5]), "+f"(d[6]), "+f"(d[7]), "+f"(d[8]), "+f"(d[9]), "+f"(d[10]), "+f"(d[11]), "+f"(d[12]), "+f"(d[13]), "+f"(d[14]), "+f"(d[15]), "+f"(d[16]), "+f"(d[17]), "+f"(d[18]), "+f"(d[19])
    : "l"(da), "l"(db), "r"(scale_d));
}
__device__ __forceinline__ void wgmma_n40_rs(float (&d)[20], const uint32_t (&a)[4], uint64_t db, int scale_d) {
  asm volatile("{\n.reg .pred p;\nsetp.ne.b32 p, %25, 0;\n"
    "wgmma.mma_async.sync.aligned.m64n40k16.f32.bf16.bf16 {%0, %1, %2, %3, %4, %5, %6, %7, %8, %9, %10, %11, %12, %13, %14, %15, %16, %17, %18, %19}, {%20, %21, %22, %23}, %24, p, 1, 1, 1;\n}\n"
    : "+f"(d[0]), "+f"(d[1]), "+f"(d[2]), "+f"(d[3]), "+f"(d[4]), "+f"(d[5]), "+f"(d[6]), "+f"(d[7]), "+f"(d[8]), "+f"(d[9]), "+f"(d[10]), "+f"(d[11]), "+f"(d[12]), "+f"(d[13]), "+f"(d[14]), "+f"(d[15]), "+f"(d[16]), "+f"(d[17]), "+f"(d[18]), "+f"(d[19])
    : "r"(a[0]), "r"(a[1]), "r"(a[2]), "r"(a[3]), "l"(db), "r"(scale_d));
}
__device__ __forceinline__ void wgmma_n256_0(float (&d)[192], uint64_t da, uint64_t db) {
  asm volatile("{\n.reg .pred p;\nsetp.ne.b32 p, 0, 0;\n"
    "wgmma.mma_async.sync.aligned.m64n256k16.f32.bf16.bf16 {%0, %1, %2, %3, %4, %5, %6, %7, %8, %9, %10, %11, %12, %13, %14, %15, %16, %17, %18, %19, %20, %21, %22, %23, %24, %25, %26, %27, %28, %29, %30, %31, %32, %33, %34, %35, %36, %37, %38, %39, %40, %41, %42, %43, %44, %45, %46, %47, %48, %49, %50, %51, %52, %53, %54, %55, %56, %57, %58, %59, %60, %61, %62, %63, %64, %65, %66, %67, %68, %69, %70, %71, %72, %73, %74, %75, %76, %77, %78, %79, %80, %81, %82, %83, %84, %85, %86, %87, %88, %89, %90, %91, %92, %93, %94, %95, %96, %97, %98, %99, %100, %101, %102, %103, %104, %105, %106, %107, %108, %109, %110, %111, %112, %113, %114, %115, %116, %117, %118, %119, %120, %121, %122, %123, %124, %125, %126, %127}, %128, %129, p, 1, 1, 0, 1;\n}\n"
    : "=f"(d[0]), "=f"(d[1]), "=f"(d[2]), "=f"(d[3]), "=f"(d[4]), "=f"(d[5]), "=f"(d[6]), "=f"(d[7]), "=f"(d[8]), "=f"(d[9]), "=f"(d[10]), "=f"(d[11]), "=f"(d[12]), "=f"(d[13]), "=f"(d[14]), "=f"(d[15]), "=f"(d[16]), "=f"(d[17]), "=f"(d[18]), "=f"(d[19]), "=f"(d[20]), "=f"(d[21]), "=f"(d[22]), "=f"(d[23]), "=f"(d[24]), "=f"(d[25]), "=f"(d[26]), "=f"(d[27]), "=f"(d[28]), "=f"(d[29]), "=f"(d[30]), "=f"(d[31]), "=f"(d[32]), "=f"(d[33]), "=f"(d[34]), "=f"(d[35]), "=f"(d[36]), "=f"(d[37]), "=f"(d[38]), "=f"(d[39]), "=f"(d[40]), "=f"(d[41]), "=f"(d[42]), "=f"(d[43]), "=f"(d[44]), "=f"(d[45]), "=f"(d[46]), "=f"(d[47]), "=f"(d[48]), "=f"(d[49]), "=f"(d[50]), "=f"(d[51]), "=f"(d[52]), "=f"(d[53]), "=f"(d[54]), "=f"(d[55]), "=f"(d[56]), "=f"(d[57]), "=f"(d[58]), "=f"(d[59]), "=f"(d[60]), "=f"(d[61]), "=f"(d[62]), "=f"(d[63]), "=f"(d[64]), "=f"(d[65]), "=f"(d[66]), "=f"(d[67]), "=f"(d[68]), "=f"(d[69]), "=f"(d[70]), "=f"(d[71]), "=f"(d[72]), "=f"(d[73]), "=f"(d[74]), "=f"(d[75]), "=f"(d[76]), "=f"(d[77]), "=f"(d[78]), "=f"(d[79]), "=f"(d[80]), "=f"(d[81]), "=f"(d[82]), "=f"(d[83]), "=f"(d[84]), "=f"(d[85]), "=f"(d[86]), "=f"(d[87]), "=f"(d[88]), "=f"(d[89]), "=f"(d[90]), "=f"(d[91]), "=f"(d[92]), "=f"(d[93]), "=f"(d[94]), "=f"(d[95]), "=f"(d[96]), "=f"(d[97]), "=f"(d[98]), "=f"(d[99]), "=f"(d[100]), "=f"(d[101]), "=f"(d[102]), "=f"(d[103]), "=f"(d[104]), "=f"(d[105]), "=f"(d[106]), "=f"(d[107]), "=f"(d[108]), "=f"(d[109]), "=f"(d[110]), "=f"(d[111]), "=f"(d[112]), "=f"(d[113]), "=f"(d[114]), "=f"(d[115]), "=f"(d[116]), "=f"(d[117]), "=f"(d[118]), "=f"(d[119]), "=f"(d[120]), "=f"(d[121]), "=f"(d[122]), "=f"(d[123]), "=f"(d[124]), "=f"(d[125]), "=f"(d[126]), "=f"(d[127])
    : "l"(da), "l"(db));
}
__device__ __forceinline__ void wgmma_n128_0(float (&d)[192], uint64_t da, uint64_t db) {
  asm volatile("{\n.reg .pred p;\nsetp.ne.b32 p, 0, 0;\n"
    "wgmma.mma_async.sync.aligned.m64n128k16.f32.bf16.bf16 {%0, %1, %2, %3, %4, %5, %6, %7, %8, %9, %10, %11, %12, %13, %14, %15, %16, %17, %18, %19, %20, %21, %22, %23, %24, %25, %26, %27, %28, %29, %30, %31, %32, %33, %34, %35, %36, %37, %38, %39, %40, %41, %42, %43, %44, %45, %46, %47, %48, %49, %50, %51, %52, %53, %54, %55, %56, %57, %58, %59, %60, %61, %62, %63}, %64, %65, p, 1, 1, 0, 1;\n}\n"
    : "=f"(d[128]), "=f"(d[129]), "=f"(d[130]), "=f"(d[131]), "=f"(d[132]), "=f"(d[133]), "=f"(d[134]), "=f"(d[135]), "=f"(d[136]), "=f"(d[137]), "=f"(d[138]), "=f"(d[139]), "=f"(d[140]), "=f"(d[141]), "=f"(d[142]), "=f"(d[143]), "=f"(d[144]), "=f"(d[145]), "=f"(d[146]), "=f"(d[147]), "=f"(d[148]), "=f"(d[149]), "=f"(d[150]), "=f"(d[151]), "=f"(d[152]), "=f"(d[153]), "=f"(d[154]), "=f"(d[155]), "=f"(d[156]), "=f"(d[157]), "=f"(d[158]), "=f"(d[159]), "=f"(d[160]), "=f"(d[161]), "=f"(d[162]), "=f"(d[163]), "=f"(d[164]), "=f"(d[165]), "=f"(d[166]), "=f"(d[167]), "=f"(d[168]), "=f"(d[169]), "=f"(d[170]), "=f"(d[171]), "=f"(d[172]), "=f"(d[173]), "=f"(d[174]), "=f"(d[175]), "=f"(d[176]), "=f"(d[177]), "=f"(d[178]), "=f"(d[179]), "=f"(d[180]), "=f"(d[181]), "=f"(d[182]), "=f"(d[183]), "=f"(d[184]), "=f"(d[185]), "=f"(d[186]), "=f"(d[187]), "=f"(d[188]), "=f"(d[189]), "=f"(d[190]), "=f"(d[191])
    : "l"(da), "l"(db));
}
__device__ __forceinline__ void wgmma_n128_rs(float (&d)[192], const uint32_t (&a)[4], uint64_t db, int scale_d) {
  asm volatile("{\n.reg .pred p;\nsetp.ne.b32 p, %69, 0;\n"
    "wgmma.mma_async.sync.aligned.m64n128k16.f32.bf16.bf16 {%0, %1, %2, %3, %4, %5, %6, %7, %8, %9, %10, %11, %12, %13, %14, %15, %16, %17, %18, %19, %20, %21, %22, %23, %24, %25, %26, %27, %28, %29, %30, %31, %32, %33, %34, %35, %36, %37, %38, %39, %40, %41, %42, %43, %44, %45, %46, %47, %48, %49, %50, %51, %52, %53, %54, %55, %56, %57, %58, %59, %60, %61, %62, %63}, {%64, %65, %66, %67}, %68, p, 1, 1, 1;\n}\n"
    : "+f"(d[128]), "+f"(d[129]), "+f"(d[130]), "+f"(d[131]), "+f"(d[132]), "+f"(d[133]), "+f"(d[134]), "+f"(d[135]), "+f"(d[136]), "+f"(d[137]), "+f"(d[138]), "+f"(d[139]), "+f"(d[140]), "+f"(d[141]), "+f"(d[142]), "+f"(d[143]), "+f"(d[144]), "+f"(d[145]), "+f"(d[146]), "+f"(d[147]), "+f"(d[148]), "+f"(d[149]), "+f"(d[150]), "+f"(d[151]), "+f"(d[152]), "+f"(d[153]), "+f"(d[154]), "+f"(d[155]), "+f"(d[156]), "+f"(d[157]), "+f"(d[158]), "+f"(d[159]), "+f"(d[160]), "+f"(d[161]), "+f"(d[162]), "+f"(d[163]), "+f"(d[164]), "+f"(d[165]), "+f"(d[166]), "+f"(d[167]), "+f"(d[168]), "+f"(d[169]), "+f"(d[170]), "+f"(d[171]), "+f"(d[172]), "+f"(d[173]), "+f"(d[174]), "+f"(d[175]), "+f"(d[176]), "+f"(d[177]), "+f"(d[178]), "+f"(d[179]), "+f"(d[180]), "+f"(d[181]), "+f"(d[182]), "+f"(d[183]), "+f"(d[184]), "+f"(d[185]), "+f"(d[186]), "+f"(d[187]), "+f"(d[188]), "+f"(d[189]), "+f"(d[190]), "+f"(d[191])
    : "r"(a[0]), "r"(a[1]), "r"(a[2]), "r"(a[3]), "l"(db), "r"(scale_d));
}

constexpr int SLOT = 16384;
constexpr int KVT = 10240;
constexpr uint32_t QA = 0x0BAu, QK = 0x462u, QQ = 0x981u;
constexpr int SM_SD = 12 * SLOT;
constexpr int SM_BAR = SM_SD + 8192;
constexpr int SM_RS = SM_BAR + 512;
constexpr int SM_AP = SM_RS + 768;
constexpr int SM_BP = SM_AP + 2048;
constexpr int SM_WPHI = SM_BP + 12288;
constexpr int SM_EPOCH = SM_WPHI + 10240;
constexpr int SM_TOTAL = SM_EPOCH + 16 + 1024;
constexpr int B_FULLS = 0, B_XOLD = 24, B_STAT = 32, B_EMPTYS = 40, B_FULLT = 256  , B_CONS = 384  , B_E3 = 472, B_E0 = 480, B_E1 = 488, B_E2 = 496, B_EPI = 504, B_CS = 160,
              B_KVDONE = 168  , B_ODONE = 176, B_XDONE = 184, B_OH1 = B_CONS, B_CS2 = 208, B_XH0 = 232, B_R0 = 240, B_CB = 144  , B_XOLD2 = 216;
constexpr uint64_t BAR_CNT = 0x1c07fc0eac00a800ull;
constexpr uint64_t WO_A0 = 0xa461b57648357643ull, WO_B0 = 0x59083a9021ba9021ull, WO_A1 = 0xa0b76901276a5babull, WO_B1 = 0x95428a5b34890132ull;
constexpr uint64_t WO_DA0 = 0xa9865432ff00dd00ull, WO_DB0 = 0xa986543211bbccccull, WO_DA1 = 0xa98654321ffff000ull, WO_DB1 = 0xa98754321bbcccddull;
#define WOORD 0xFDB9753ECA864210ull
constexpr int NX = 4;
constexpr int XS = 10;

#define PL 2
#define PROFX(i) PROFT(tid_ == 128 && layer == PL, 200 + (i))
#define NCOM 3
#define PFS 8
#define KVTH 0x41700000u
#define XPF 3
#define XPM 2
#define TLINE 1
#define NLAYERS 4
constexpr float L2E = 1.4426950408889634f;
#define PHI_MAX 2147483648.f

#define D128(lo) desc64(lo, 0x40000040u)
struct Ctx { uint32_t sb; int g, rb, cu; bf16* out; };

__device__ __forceinline__ void colsum(const CUtensorMap* tm, float* cs, int rb, int g, int w0, int dw, int lane, uint32_t stg, uint32_t cb, uint32_t par) {
  const uint32_t src = stg + (lane >> 3) * 2048;
#pragma unroll 1
  for (int wi = w0 - dw; wi < 6; wi += dw) {
    float s[8] = {0.f, 0.f, 0.f, 0.f, 0.f, 0.f, 0.f, 0.f};
    if (wi >= 0) {
      mbar_wait_u(cb, par);
      par ^= 1;
#pragma unroll 4
      for (int r = 0; r < 16; ++r) {
        const uint4 v = lds128(src + r * 128 + (((lane ^ r) & 7) << 4));
        s[0] += bf_lo(v.x); s[1] += bf_hi(v.x); s[2] += bf_lo(v.y); s[3] += bf_hi(v.y);
        s[4] += bf_lo(v.z); s[5] += bf_hi(v.z); s[6] += bf_lo(v.w); s[7] += bf_hi(v.w);
      }
#pragma unroll
      for (int i = 0; i < 8; ++i) s[i] += __shfl_xor_sync(0xffffffffu, s[i], 8);
    }
    const int wn = wi + dw;
    if (wn < 6) {
      expect_tx_e(cb, 8192);
      tma_2d_e(stg, tm, (wn >= 4 ? 0 : 1024 + (wn >> 1) * 1024) + g * 128 + (wn & 1) * 64, rb * 64, cb);
    }
    if (wi >= 0) {
#pragma unroll
      for (int i = 0; i < 8; ++i) s[i] += __shfl_xor_sync(0xffffffffu, s[i], 16);
      if (lane < 8) {
        red_add4(cs + g * 384 + (wi * 8 + lane) * 8, s[0], s[1], s[2], s[3]);
        red_add4(cs + g * 384 + (wi * 8 + lane) * 8 + 4, s[4], s[5], s[6], s[7]);
      }
      __syncwarp();
    }
  }
}
#define PHASE_CTX() \
  uint32_t sb = c.sb; asm volatile("" : "+r"(sb)); \
  int tid_ = threadIdx.x; asm volatile("" : "+r"(tid_)); \
  const uint32_t bar = sb + SM_BAR; \
  const int lane = tid_ & 31, cw = (tid_ >> 5) - 4, wg = cw >> 2, wq = cw & 3, gq = lane >> 2, t = lane & 3, wrow0 = cw * 16; \
  const int lrow = (lane & 7) + ((lane >> 3) & 1) * 8, lchk = lane >> 4; \
  const bool elected = (tid_ & 127) == 0; \
  const uint32_t rowo = (wrow0 + lrow) * 128, X = (lchk ^ (lane & 7)) << 4; \
  (void)bar; (void)wq; (void)gq; (void)lrow; (void)lchk; (void)elected; (void)wrow0; (void)wg; (void)rowo; (void)X; (void)t;

__device__ __forceinline__ void slab_out_half(uint32_t slot, bf16* dst, int wrow0, int lane, bool FENCE = false) {
  const int r0 = lane >> 3, ch = lane & 7;
  const uint32_t src = slot + (wrow0 + r0) * 128;
  uint4 v[4];
#pragma unroll
  for (int i = 0; i < 4; ++i) v[i] = lds128(src + i * 512 + (((ch ^ (4 * i + r0)) & 7) << 4));
  if (FENCE) fence_async_smem();
  dst += (size_t)(wrow0 + r0) * D_ + ch * 8;
#pragma unroll
  for (int i = 0; i < 4; ++i)
    asm volatile("st.global.v4.u32 [%0], {%1,%2,%3,%4};" ::"l"(dst + (size_t)i * 4 * D_), "r"(v[i].x), "r"(v[i].y), "r"(v[i].z), "r"(v[i].w) : "memory");
}

struct Tag { uint32_t me, mo, tg; };
__device__ __forceinline__ Tag make_tag(int gq, int t, uint32_t tg) { return Tag{t == 0, t == 1, tg}; }
__device__ __forceinline__ void stsm_tag(uint32_t addr, uint32_t r0, uint32_t r1, uint32_t r2, uint32_t r3, const Tag& k, int jp) {
  if (jp == 0) stsm_x4(addr, (r0 & ~k.me) | (k.tg & k.me), (r1 & ~k.mo) | (k.tg & k.mo), r2, r3);
  else stsm_x4(addr, r0, r1, r2, r3);
}
#define TILE_BAD() ((lds_vol(va) ^ tg) & 1)
#define TILE_VA() (slot + (wrow0 + (lane & 15)) * 128 + (lane & 7) * 16 + ((lane >> 3) & 1) * 4)
__device__ __forceinline__ void tile_check(uint32_t slot, const bf16* src, int wrow0, int lane, uint32_t tg) {
  const uint32_t va = TILE_VA();
  if (__builtin_expect(__any_sync(0xffffffffu, TILE_BAD()), 0)) {
    const int r0 = lane >> 3, ch = lane & 7;
    uint32_t n = 0;
#pragma unroll 1
    do {
      uint4 v[4];
#pragma unroll
      for (int i = 0; i < 4; ++i) v[i] = ld_relaxed4(reinterpret_cast<const uint4*>(src + (size_t)(wrow0 + r0 + 4 * i) * D_ + ch * 8));
#pragma unroll
      for (int i = 0; i < 4; ++i) sts128(slot + (wrow0 + r0 + 4 * i) * 128 + (((ch ^ (4 * i + r0)) & 7) << 4), v[i]);
      __syncwarp();
      if (++n > (1u << 16)) { g_err = 8u; break; }
    } while (__any_sync(0xffffffffu, TILE_BAD()));
    fence_async_smem();
    __syncwarp();
  }
}

template <int O>
__device__ __forceinline__ void phi_proj(float (&p)[2][4][4], const uint32_t (&kq)[64], uint32_t wa) {
#pragma unroll
  for (int h = 0; h < 2; ++h)
#pragma unroll
    for (int i = 0; i < 4; ++i) { p[h][i][0] = p[h][i][1] = p[h][i][2] = p[h][i][3] = 0.f; }
#pragma unroll
  for (int ks = 0; ks < 2; ++ks)
#pragma unroll
    for (int np = 0; np < 2; ++np)
#pragma unroll
      for (int h = 0; h < 2; ++h) {
        uint32_t b0, b1, b2, b3;
        ldsm_x4_t(b0, b1, b2, b3, wa + h * 2560 + ks * 1280 + np * 32);
        mma_bf16(p[h][2 * np], kq[O + 8 * h + 4 * ks], kq[O + 8 * h + 4 * ks + 1], kq[O + 8 * h + 4 * ks + 2], kq[O + 8 * h + 4 * ks + 3], b0, b1);
        mma_bf16(p[h][2 * np + 1], kq[O + 8 * h + 4 * ks], kq[O + 8 * h + 4 * ks + 1], kq[O + 8 * h + 4 * ks + 2], kq[O + 8 * h + 4 * ks + 3], b2, b3);
      }
}
__device__ __forceinline__ void phi_exp(uint32_t (&raw)[4][4], const float (&p)[4][4], float sc0, float sc1) {
#pragma unroll
  for (int i = 0; i < 4; ++i) {
    const float e0 = ex2(p[i][0] * sc0), e1 = ex2(p[i][1] * sc0), e2 = ex2(p[i][2] * sc1), e3 = ex2(p[i][3] * sc1);
    const float m0 = e0 * e1, m1 = e2 * e3, rr = rcp(m0 * m1), r0 = rr * m1, r1 = rr * m0;
    raw[i >> 1][(i & 1) * 2] = pack_bf16(e0, e1);
    raw[i >> 1][(i & 1) * 2 + 1] = pack_bf16(e2, e3);
    raw[2 + (i >> 1)][(i & 1) * 2] = pack_bf16(e1 * r0, e0 * r0);
    raw[2 + (i >> 1)][(i & 1) * 2 + 1] = pack_bf16(e3 * r1, e2 * r1);
  }
}
template <int O>
__device__ __forceinline__ void phi_norm(uint32_t (&ph)[2][4][4], const uint32_t (&raw)[2][4][4], const uint32_t (&kq)[64], uint32_t wa,
                                         float sc0, float sc1, float mul0, float mul1) {
  bool bad = false;
#pragma unroll
  for (int h = 0; h < 2; ++h)
#pragma unroll
    for (int sg = 0; sg < 2; ++sg) {
      float ss[4] = {0.f, 0.f, 0.f, 0.f};
#pragma unroll
      for (int ks = 0; ks < 2; ++ks)
        mma_bf16(ss, raw[h][2 * sg + ks][0], raw[h][2 * sg + ks][1], raw[h][2 * sg + ks][2], raw[h][2 * sg + ks][3], 0x3F803F80u, 0x3F803F80u);
      bad = bad || !(ss[0] < PHI_MAX) || !(ss[2] < PHI_MAX);
      const uint32_t iv = pack_bf16(rcp(ss[0]) * mul0, rcp(ss[2]) * mul1);
#pragma unroll
      for (int ks = 0; ks < 2; ++ks)
#pragma unroll
        for (int j = 0; j < 4; ++j) ph[h][2 * sg + ks][j] = mul_bf16x2(raw[h][2 * sg + ks][j], iv, j & 1);
    }
  if (__builtin_expect(__any_sync(0xffffffffu, bad), 0)) {
#pragma unroll 1
    for (int it = 0; it < 4; ++it) {
      float q[4][4];
#pragma unroll
      for (int i = 0; i < 4; ++i) { q[i][0] = q[i][1] = q[i][2] = q[i][3] = 0.f; }
#pragma unroll
      for (int ks = 0; ks < 2; ++ks) {
        uint32_t a[4];
#pragma unroll
        for (int j = 0; j < 4; ++j) a[j] = (it & 2) ? kq[O + 8 + 4 * ks + j] : kq[O + 4 * ks + j];
#pragma unroll
        for (int np = 0; np < 2; ++np) {
          uint32_t b0, b1, b2, b3;
          ldsm_x4_t(b0, b1, b2, b3, wa + (it >> 1) * 2560 + ks * 1280 + np * 32);
          mma_bf16(q[2 * np], a[0], a[1], a[2], a[3], b0, b1);
          mma_bf16(q[2 * np + 1], a[0], a[1], a[2], a[3], b2, b3);
        }
      }
      float iv[2];
#pragma unroll
      for (int r = 0; r < 2; ++r) {
        const float sc = (it & 1) ? -(r ? sc1 : sc0) : (r ? sc1 : sc0);
        float mx = -INFINITY, sm = 0.f;
#pragma unroll
        for (int i = 0; i < 8; ++i) { float& v = q[i >> 1][2 * r + (i & 1)]; v *= sc; mx = fmaxf(mx, v); }
        mx = fmaxf(mx, __shfl_xor_sync(0xffffffffu, mx, 1));
        mx = fmaxf(mx, __shfl_xor_sync(0xffffffffu, mx, 2));
#pragma unroll
        for (int i = 0; i < 8; ++i) { float& v = q[i >> 1][2 * r + (i & 1)]; v = ex2(v - mx); sm += v; }
        sm += __shfl_xor_sync(0xffffffffu, sm, 1);
        sm += __shfl_xor_sync(0xffffffffu, sm, 2);
        iv[r] = rcp(sm) * (r ? mul1 : mul0);
      }
#pragma unroll
      for (int i = 0; i < 24; ++i) ph[i >> 4][(i >> 2) & 3][i & 3] = ph[(i + 8) >> 4][((i + 8) >> 2) & 3][i & 3];
#pragma unroll
      for (int i = 0; i < 4; ++i) {
        ph[1][2 + (i >> 1)][(i & 1) * 2] = pack_bf16(q[i][0] * iv[0], q[i][1] * iv[0]);
        ph[1][2 + (i >> 1)][(i & 1) * 2 + 1] = pack_bf16(q[i][2] * iv[1], q[i][3] * iv[1]);
      }
    }
  }
}

__device__ __forceinline__ void stats_out(float s0, float s1, float q0, float q1, float2* dst, int t) {
  const bool od = t & 1;
  float sa = od ? s1 : s0, qa = od ? q1 : q0;
  sa += __shfl_xor_sync(0xffffffffu, od ? s0 : s1, 1);
  qa += __shfl_xor_sync(0xffffffffu, od ? q0 : q1, 1);
  sa += __shfl_xor_sync(0xffffffffu, sa, 2);
  qa += __shfl_xor_sync(0xffffffffu, qa, 2);
  if (t < 2) red_add2(&dst[t * 8].x, sa, qa);
}

__device__ __forceinline__ void consumer(const Ctx& c) {
  const int g = c.g, m0 = c.rb * 128;
  float acc[192];
#define X_HALF(hf, TG) \
      _Pragma("unroll") for (int jp = 4 * (hf); jp < 4 * (hf) + 4; ++jp) \
        stsm_tag(sb + (XS + (hf)) * SLOT + rowo + (X ^ ((jp & 3) << 5)), \
                 pack_bf16(acc[128 + 8 * jp], acc[129 + 8 * jp]), pack_bf16(acc[130 + 8 * jp], acc[131 + 8 * jp]), \
                 pack_bf16(acc[132 + 8 * jp], acc[133 + 8 * jp]), pack_bf16(acc[134 + 8 * jp], acc[135 + 8 * jp]), TG, jp & 3);
#pragma unroll
  for (int i = 128; i < 192; ++i) acc[i] = 0.f;
#pragma unroll 1
  for (int layer = 0;; ++layer) {
    {
      PHASE_CTX();
      const uint32_t wu = c.cu >> 2;
      const uint32_t dA0 = (((sb + wu * 8192) & 0x3FFFF) >> 4) | (1u << 16), dB0 = ((sb & 0x3FFFF) >> 4) | (512u << 16);
      {
        PROFX(0);
        mbar_wait(bar + B_FULLS, 0);
        PROFX(1);
        wgmma_fence();
        wgmma_n256_0(acc, D128(dA0 + XS * 1024), D128(dB0 + 2048));
#pragma unroll
        for (int k = 1; k < 4; ++k) wgmma_n256(acc, D128(dA0 + XS * 1024 + k * 2), D128(dB0 + 2048 + k * 128), 1);
        wgmma_commit();
        wgmma_wait<1>();
        float s0 = 0.f, s1 = 0.f, q0 = 0.f, q1 = 0.f;
        if (layer) {
          X_HALF(1, (Tag{0u, 0u, 0u}));
#pragma unroll
          for (int i = 128; i < 192; i += 4) {
            s0 += acc[i] + acc[i + 1]; s1 += acc[i + 2] + acc[i + 3];
            q0 = fmaf(acc[i], acc[i], fmaf(acc[i + 1], acc[i + 1], q0)); q1 = fmaf(acc[i + 2], acc[i + 2], fmaf(acc[i + 3], acc[i + 3], q1));
          }
        }
        asm volatile("" : "+f"(s0), "+f"(s1), "+f"(q0), "+f"(q1) :: "memory");
        wgmma_fence();
        wgmma_n128_0(acc, D128(dA0 + XS * 1024), D128(dB0 + 1024));
#pragma unroll
        for (int k = 1; k < 4; ++k) wgmma_n128(acc, D128(dA0 + XS * 1024 + k * 2), D128(dB0 + 1024 + k * 128), 1);
        wgmma_commit();
        if (layer) {
          PHASE_CTX();
          fence_async_smem();
          nbar_dyn(3 + wu, 128);
          stats_out(s0, s1, q0, q1, g_stats + layer * S_ + m0 + wrow0 + gq, t);
          PROFT(tid_ == 128, layer * 16 + 8);
        }
      }
      uint32_t s = 1, u = 0, sp = 0;
      const int ix = layer ? 99 : 2 * min(g, NCOM) + 1;
#pragma unroll 1
      for (int i = 1; i < 14; ++i) {
        mbar_wait(bar + B_FULLS + s * 8, (u + (s ? layer : 0)) & 1);
        if (layer && (unsigned)(i - 2) < 7u) {
          PHASE_CTX();
          tile_check(sb + ((QA >> (4 * s)) & 15) * SLOT, g_x + (size_t)m0 * D_ + ((2 * g + 2 * i - 2) & 15) * 64, wrow0, lane, lds_vol(sb + SM_EPOCH) + layer);
        }
        const uint32_t da = dA0 + ((QA >> (4 * s)) & 15) * 1024, dk = dB0 + ((QK >> (4 * s)) & 15) * 1024,
                       dq = dB0 + ((QQ >> (4 * s)) & 15) * 1024;
        wgmma_fence();
#pragma unroll
        for (int k = 0; k < 4; ++k) {
          wgmma_n256(acc, D128(da + k * 2), D128(dk + k * 128), 1);
          wgmma_n128(acc, D128(da + k * 2), D128(dq + k * 128), 1);
          if (k == 0) {
            wgmma_commit();
            wgmma_wait<1>();
            if (elected && (unsigned)(i - ix) >= 2u) release2(bar + B_EMPTYS + sp * 8);
          }
        }
        wgmma_commit();
        if ((unsigned)(i - ix) < 2u) {
          PHASE_CTX();
          {
            float s0 = 0.f, s1 = 0.f, q0 = 0.f, q1 = 0.f;
            const uint32_t xa = sb + ((QA >> (4 * sp)) & 15) * SLOT + rowo;
#pragma unroll
            for (int jp = 0; jp < 4; ++jp) {
              uint32_t x0, x1, x2, x3;
              ldsm_x4(x0, x1, x2, x3, xa + (X ^ (jp << 5)));
              s0 += (bf_lo(x0) + bf_hi(x0)) + (bf_lo(x2) + bf_hi(x2));
              s1 += (bf_lo(x1) + bf_hi(x1)) + (bf_lo(x3) + bf_hi(x3));
              q0 = fmaf(bf_lo(x0), bf_lo(x0), fmaf(bf_hi(x0), bf_hi(x0), fmaf(bf_lo(x2), bf_lo(x2), fmaf(bf_hi(x2), bf_hi(x2), q0))));
              q1 = fmaf(bf_lo(x1), bf_lo(x1), fmaf(bf_hi(x1), bf_hi(x1), fmaf(bf_lo(x3), bf_lo(x3), fmaf(bf_hi(x3), bf_hi(x3), q1))));
            }
            stats_out(s0, s1, q0, q1, g_stats + m0 + wrow0 + gq, t);
          }
          __syncwarp();
          if (lane == 0 && i != ix) mbar_arrive(bar + B_XDONE);
          nbar_dyn(3 + wu, 128);
          if (elected) release2(bar + B_EMPTYS + sp * 8);
        }
        if (i == 1 && layer) {
          PHASE_CTX();
          slab_out_half(sb + (XS + 1) * SLOT, g_x + (size_t)m0 * D_ + g * 128 + 64, wrow0, lane);
          __syncwarp();
          if (lane == 0) mbar_arrive(bar + B_XDONE);
          nbar_dyn(3 + wu, 128);
        }
        sp = s;
        if (++s == 3) { s = 0; ++u; }
      }
      {
        const uint64_t dap = make_desc_ns(sb + SM_AP + wu * 1024, 0, 128), dbp = make_desc_ns(sb + SM_BP + (layer & 1) * 6144, 0, 128);
        if (wu == 0) {
          wgmma_wait<0>();
          if (elected) mbar_arrive(bar + B_R0);
          nbar<6, 256>();
        }
        if (layer < 2) mbar_wait(bar + (layer ? B_CS2 : B_CS), 0);
        mbar_wait(bar + B_STAT, layer & 1);
        mbar_wait(bar + B_FULLS + 16, layer & 1);
        wgmma_fence();
        wgmma_n256_k(acc, dap, dbp, 1);
#pragma unroll
        for (int k = 0; k < 4; ++k) wgmma_n256(acc, D128(dA0 + (QA >> 8) * 1024 + k * 2), D128(dB0 + (QK >> 8) * 1024 + k * 128), 1);
        mbar_wait(bar + B_FULLS, 1);
        PROFT(tid_ == 128, layer * 16 + 9);
        wgmma_fence();
#pragma unroll
        for (int k = 0; k < 4; ++k) wgmma_n256(acc, D128(dA0 + (QA & 15) * 1024 + k * 2), D128(dB0 + (QK & 15) * 1024 + k * 128), 1);
        wgmma_commit();
        if (wu) nbar<6, 256>();
#define Q_TAIL() \
        wgmma_n128_k(acc, dap, dbp + 256, 1); \
        _Pragma("unroll") for (int k = 0; k < 4; ++k) wgmma_n128(acc, D128(dA0 + (QA >> 8) * 1024 + k * 2), D128(dB0 + (QQ >> 8) * 1024 + k * 128), 1); \
        _Pragma("unroll") for (int k = 0; k < 4; ++k) wgmma_n128(acc, D128(dA0 + (QA & 15) * 1024 + k * 2), D128(dB0 + (QQ & 15) * 1024 + k * 128), 1);
        Q_TAIL();
        wgmma_commit();
        wgmma_wait<1>();
#pragma unroll
        for (int i = 0; i < 128; ++i) asm volatile("" : "+f"(acc[i]) :: "memory");
      }
    }
    uint32_t xo[32];
    uint32_t oq[8][4];
    {
      PHASE_CTX();
      PROFT(tid_ == 128, layer * 16 + 1);
      const bool isB = layer & 1;
      const int cu = c.cu;
      if (cu >= 4) asm volatile("bar.arrive 7, 256;" ::: "memory");
      if (elected && cu == 4) mbar_arrive(bar + B_R0);
      uint32_t kq[64];
      const uint32_t rowq = rowo & 8191;
      const float rs0 = lds_f(sb + SM_RS + (16 + wrow0 + gq) * 4), rs1 = lds_f(sb + SM_RS + (24 + wrow0 + gq) * 4);
#define Q_DONE() \
      wgmma_wait<0>(); \
      if (lane == 0) release2(bar + B_E0); \
      _Pragma("unroll") for (int i = 128; i < 192; ++i) asm volatile("" : "+f"(acc[i]) :: "memory"); \
      _Pragma("unroll") for (int i = 0; i < 32; ++i) kq[32 + i] = pack_bf16(acc[128 + 2 * i], acc[129 + 2 * i]);
      if (isB) {
        if (cu == 0) asm volatile("bar.arrive 10, 64;" ::: "memory");
        if (elected) release2(bar + B_E1);
        const int e = gq & 1;
        const bool sel = t > (gq >> 1);
        const uint32_t rja = sb + SM_RS + (wrow0 + 2 * t + e) * 4;
        const float rjA0 = lds_f(rja + 32), rjA1 = lds_f(rja + 64), rjB0 = lds_f(rja + (sel ? 0 : 64)), rjB1 = lds_f(rja + (sel ? 32 : 96));
        uint32_t vv[32];
#pragma unroll
        for (int i = 0; i < 16; ++i) { kq[i] = pack_bf16(acc[2 * i], acc[2 * i + 1]); vv[i] = pack_bf16(acc[64 + 2 * i], acc[65 + 2 * i]); }
        const uint32_t rB = sb + 4 * SLOT + wg * 4 * KVT + rowq;
        auto prev = [&](int hp) { return cu == 4 ? rB - 4 * KVT + 8192 + 2 * hp * KVT : rB + 2 * (hp ^ wg) * KVT; };
        auto dump = [&](int hp) {
          const uint32_t kb = rB + 2048 + (hp ^ wg) * 2 * KVT;
#pragma unroll
          for (int jp = 0; jp < 4; ++jp) {
            stsm_x4(kb + (X ^ (jp << 5)), kq[16 * hp + 4 * jp], kq[16 * hp + 4 * jp + 1], kq[16 * hp + 4 * jp + 2], kq[16 * hp + 4 * jp + 3]);
            stsm_x4(kb + KVT + (X ^ (jp << 5)), vv[16 * hp + 4 * jp], vv[16 * hp + 4 * jp + 1], vv[16 * hp + 4 * jp + 2], vv[16 * hp + 4 * jp + 3]);
          }
          if (cu == 3) {
            if (hp) asm volatile("bar.arrive 15, 64;" ::: "memory"); else asm volatile("bar.arrive 9, 64;" ::: "memory");
          }
          asm volatile("bar.arrive %0, 224;" :: "r"(hp ? 13 + (cu >> 2) : 8 + (cu & 4)) : "memory");
        };
        uint4* const hbuf = g_halo + ((c.rb * 8 + g) * 2 + (layer >> 1)) * 512 + lane;
        if (cu < 4) {
          nbar<7, 256>();
          dump(0);
        }
#pragma unroll
        for (int i = 16; i < 32; ++i) { kq[i] = pack_bf16(acc[2 * i], acc[2 * i + 1]); vv[i] = pack_bf16(acc[64 + 2 * i], acc[65 + 2 * i]); }
        if (cu >= 4) {
          if (cu == 7) {
#pragma unroll
            for (int jp = 0; jp < 8; ++jp) {
              st_relaxed4(hbuf + jp * 32, ~kq[4 * jp], ~kq[4 * jp + 1], ~kq[4 * jp + 2], ~kq[4 * jp + 3]);
              st_relaxed4(hbuf + 256 + jp * 32, ~vv[4 * jp], ~vv[4 * jp + 1], ~vv[4 * jp + 2], ~vv[4 * jp + 3]);
            }
          }
          dump(0);
          dump(1);
        }
        PROFT(tid_ == 128, layer * 16 + 2);
        constexpr float SC = 0.17677669529663687f * L2E;
        const float fA0 = rjA0 * rs0 * SC, fB0 = rjB0 * rs0 * SC, fA1 = rjA1 * rs1 * SC, fB1 = rjB1 * rs1 * SC;
        const float bA0 = (m0 + wrow0) ? 0.f : -1e30f, bB = sel ? bA0 : 0.f;
        const uint32_t pA_ = e ? 0x1044u : 0x4410u, pB_ = e ? 0x3244u : 0x4432u, pLo = sel ? pB_ : 0x4444u, pHi = sel ? 0x4444u : pB_;
        const uint32_t KX = ((lane >> 3) ^ (lane & 7)) << 4;
        Q_DONE();
        if (cu == 0) {
          nbar<11, 64>();
        } else if (cu == 4) {
          uint4 hv[16];
          if (c.rb > 0) {
            uint32_t n = 0;
#pragma unroll 1
            while (true) {
              uint32_t mn = 0xFFFFFFFFu;
#pragma unroll
              for (int i = 0; i < 16; ++i) hv[i] = ld_relaxed4(hbuf - 16 * 512 + i * 32);
#pragma unroll
              for (int i = 0; i < 16; ++i) mn = __vimin3_u32(__vimin3_u32(mn, hv[i].x, hv[i].y), hv[i].z, hv[i].w);
              if (__all_sync(0xffffffffu, mn != 0u)) break;
              if (++n > (1u << 20)) { g_err = 4u; break; }
            }
          } else {
#pragma unroll
            for (int i = 0; i < 16; ++i) hv[i] = make_uint4(~0u, ~0u, ~0u, ~0u);
          }
          nbar<10, 64>();
#pragma unroll
          for (int i = 0; i < 16; ++i)
            stsm_x4(rB - 4 * KVT + (((i >> 2) & 1) * 2 + (i >> 3)) * KVT + (X ^ ((i & 3) << 5)), ~hv[i].x, ~hv[i].y, ~hv[i].z, ~hv[i].w);
          asm volatile("bar.arrive 11, 64;" ::: "memory");
          nbar<9, 64>();
        } else {
          nbar_dyn(8 + (cu & 4), 224);
        }
        PROFT(tid_ == 128, layer * 16 + 5);
        PROFT(lane == 0 && layer == PL, 136 + cw);
        uint32_t kb[2][2][4], vb[2][2][2][4];
        float oa[2][4][4], sm[2][2];
        auto att_load = [&](int hp) {
          const uint32_t kt = prev(hp) - (lane & 8) * 128, vt = rB + (2 * (hp ^ wg) + 1) * KVT + 2048;
          __syncwarp();
#pragma unroll
          for (int h = 0; h < 2; ++h)
#pragma unroll
            for (int nt = 0; nt < 2; ++nt) ldsm_x4(kb[h][nt][0], kb[h][nt][1], kb[h][nt][2], kb[h][nt][3], kt + nt * 1024 + (KX ^ (h << 6)));
#pragma unroll
          for (int ks = 0; ks < 2; ++ks)
#pragma unroll
            for (int np = 0; np < 2; ++np)
#pragma unroll
              for (int h = 0; h < 2; ++h)
                ldsm_x4_t(vb[h][ks][np][0], vb[h][ks][np][1], vb[h][ks][np][2], vb[h][ks][np][3], (ks ? vt : prev(hp) + KVT) + (X ^ (h << 6) ^ (np << 5)));
          if (hp == 0 && lane == 0) release2(bar + B_E3);
        };
        auto att_mid = [&](int hp) {
          float la[2][2], lb[2][2], mx[2][2];
#pragma unroll
          for (int h = 0; h < 2; ++h) {
            const int qo = 32 + 16 * hp + 8 * h, ko = 16 * hp + 8 * h;
            float sc[4][4];
#pragma unroll
            for (int nt = 0; nt < 4; ++nt) {
              sc[nt][0] = sc[nt][1] = sc[nt][2] = sc[nt][3] = 0.f;
#pragma unroll
              for (int ks = 0; ks < 2; ++ks)
                mma_bf16(sc[nt], kq[qo + 4 * ks], kq[qo + 4 * ks + 1], kq[qo + 4 * ks + 2], kq[qo + 4 * ks + 3],
                         nt < 2 ? kb[h][nt & 1][2 * ks] : kq[ko + 4 * ks + (nt & 1)], nt < 2 ? kb[h][nt & 1][2 * ks + 1] : kq[ko + 4 * ks + 2 + (nt & 1)]);
            }
            la[h][0] = fmaf(e ? sc[1][1] : sc[1][0], fA0, bA0);
            lb[h][0] = fmaf(sel ? (e ? sc[0][1] : sc[0][0]) : (e ? sc[2][1] : sc[2][0]), fB0, bB);
            la[h][1] = (e ? sc[2][3] : sc[2][2]) * fA1;
            lb[h][1] = fmaf(sel ? (e ? sc[1][3] : sc[1][2]) : (e ? sc[3][3] : sc[3][2]), fB1, bB);
            mx[h][0] = fmaxf(la[h][0], lb[h][0]); mx[h][1] = fmaxf(la[h][1], lb[h][1]);
          }
#pragma unroll
          for (int o = 1; o <= 2; o <<= 1)
#pragma unroll
            for (int h = 0; h < 2; ++h)
#pragma unroll
              for (int r = 0; r < 2; ++r) mx[h][r] = fmaxf(mx[h][r], __shfl_xor_sync(0xffffffffu, mx[h][r], o));
#pragma unroll
          for (int h = 0; h < 2; ++h) {
#pragma unroll
            for (int r = 0; r < 2; ++r) { la[h][r] = ex2(la[h][r] - mx[h][r]); lb[h][r] = ex2(lb[h][r] - mx[h][r]); sm[h][r] = la[h][r] + lb[h][r]; }
            const uint32_t p0 = pack_bf16(la[h][0] * rjA0, lb[h][0] * rjB0), p1 = pack_bf16(la[h][1] * rjA1, lb[h][1] * rjB1);
            const uint32_t a00 = __byte_perm(p0, 0u, pLo), a02 = __byte_perm(p0, 0u, pA_), a03 = __byte_perm(p1, 0u, pLo);
            const uint32_t a10 = __byte_perm(p0, 0u, pHi), a11 = __byte_perm(p1, 0u, pA_), a13 = __byte_perm(p1, 0u, pHi);
#pragma unroll
            for (int i = 0; i < 4; ++i) {
              oa[h][i][0] = oa[h][i][1] = oa[h][i][2] = oa[h][i][3] = 0.f;
              mma_bf16(oa[h][i], a00, 0u, a02, a03, vb[h][0][i >> 1][2 * (i & 1)], vb[h][0][i >> 1][2 * (i & 1) + 1]);
              mma_bf16(oa[h][i], a10, a11, 0u, a13, vb[h][1][i >> 1][2 * (i & 1)], vb[h][1][i >> 1][2 * (i & 1) + 1]);
            }
          }
#pragma unroll
          for (int o = 1; o <= 2; o <<= 1)
#pragma unroll
            for (int h = 0; h < 2; ++h)
#pragma unroll
              for (int r = 0; r < 2; ++r) sm[h][r] += __shfl_xor_sync(0xffffffffu, sm[h][r], o);
        };
        auto att_end = [&](int hp) {
          const uint32_t qad = sb + (XS + 1 - hp) * SLOT + rowo;
#pragma unroll
          for (int jp = 0; jp < 4; ++jp) ldsm_x4(xo[16 * hp + 4 * jp], xo[16 * hp + 4 * jp + 1], xo[16 * hp + 4 * jp + 2], xo[16 * hp + 4 * jp + 3], qad + (X ^ (jp << 5)));
#pragma unroll
          for (int h = 0; h < 2; ++h) {
            const float i0 = rcp(sm[h][0]), i1 = rcp(sm[h][1]);
#pragma unroll
            for (int np = 0; np < 2; ++np)
            {
              uint32_t (&o)[4] = oq[4 * hp + 2 * h + np];
              o[0] = pack_bf16(oa[h][2 * np][0] * i0, oa[h][2 * np][1] * i0); o[1] = pack_bf16(oa[h][2 * np][2] * i1, oa[h][2 * np][3] * i1);
              o[2] = pack_bf16(oa[h][2 * np + 1][0] * i0, oa[h][2 * np + 1][1] * i0); o[3] = pack_bf16(oa[h][2 * np + 1][2] * i1, oa[h][2 * np + 1][3] * i1);
              stsm_tag(qad + (X ^ (h << 6) ^ (np << 5)), o[0], o[1], o[2], o[3], make_tag(gq, t, 0u), 2 * h + np);
            }
          }
          {
          __syncwarp();
          slab_out_half(sb + (XS + 1 - hp) * SLOT, g_o + (size_t)m0 * D_ + g * 128 + hp * 64, wrow0, lane);
          __syncwarp();
          if (lane == 0) mbar_arrive(bar + (hp ? B_ODONE : B_OH1));
          }
          PROFT(lane == 0 && layer == PL && hp == 0, 128 + cw);
        };
        att_load(0);
        att_mid(0);
        mbar_wait(bar + B_XOLD, 1);
        att_end(0);
        if (cu < 4) dump(1);
        if (cu == 4) nbar<15, 64>();
        else if (cu != 0) nbar_dyn(13 + (cu >> 2), 224);
        att_load(1);
        att_mid(1);
        mbar_wait(bar + B_XOLD2, 1);
        att_end(1);
      } else {
#pragma unroll
        for (int i = 0; i < 32; ++i) kq[i] = pack_bf16(acc[2 * i], acc[2 * i + 1]);
        if (cu < 4) nbar<7, 256>();
        {
          const uint32_t vb = sb + (5 + 3 * wg) * SLOT + (rowq >> 1) + ((lchk ^ ((lane & 7) >> 1)) << 4);
#pragma unroll
          for (int jp = 8; jp < 16; ++jp)
            stsm_x4((vb ^ ((jp & 1) << 5)) + ((jp >> 1) & 3) * 4096,
                    pack_bf16(acc[8 * jp], acc[8 * jp + 1]), pack_bf16(acc[8 * jp + 2], acc[8 * jp + 3]),
                    pack_bf16(acc[8 * jp + 4], acc[8 * jp + 5]), pack_bf16(acc[8 * jp + 6], acc[8 * jp + 7]));
        }
        PROFT(tid_ == 128, layer * 16 + 2);
        Q_DONE();
        const uint32_t pA = sb + (3 + 3 * wg) * SLOT + (rowo & 8191);
        float sc0 = rs0 * L2E, sc1 = rs1 * L2E;
        const uint32_t wa0 = sb + SM_WPHI + lrow * 80 + lchk * 16;
        const uint32_t wu = c.cu >> 2, par = (layer >> 1) & 1;
        float p[2][4][4];
        uint32_t raw[2][4][4], ph[2][4][4];
        float kva[20], oab[2][2][20];
        auto kv_start = [&](int hp) {
#pragma unroll
          for (int h = 0; h < 2; ++h)
#pragma unroll
            for (int cp = 0; cp < 4; ++cp)
              stsm_x4(pA + hp * 16384 + h * 8192 + (X ^ (cp << 5)), ph[h][cp][0], ph[h][cp][1], ph[h][cp][2], ph[h][cp][3]);
          PROFT(tid_ == 128, layer * 16 + 11);
          nbar<1, 256>();
          fence_async_smem();
          const uint32_t hu = 2 * hp + wu;
          const uint32_t dP = (((sb + 3 * SLOT + hu * 8192) & 0x3FFFF) >> 4) | (512u << 16);
          const uint32_t dV = (((sb + 5 * SLOT + hu * 4096) & 0x3FFFF) >> 4) | (((SM_SD - 5 * SLOT - hu * 4096) >> 4) << 16);
          wgmma_fence();
#pragma unroll
          for (int ks = 0; ks < 8; ++ks)
            wgmma_n40_tt(kva, desc64(dP + (ks >> 2) * 3072 + (ks & 3) * 128, 0x40000040u),
                         desc64(dV + (ks >> 2) * (3072u - (2816u << 16)) + (ks & 3) * 64, 0x80000020u), ks != 0);
          wgmma_commit();
        };
        auto kv_end = [&](int hp) {
          wgmma_wait<0>();
#pragma unroll
          for (int i = 0; i < 20; ++i) asm volatile("" : "+f"(kva[i]) :: "memory");
          nbar_dyn(3 + wu, 128);
          PROFT(tid_ == 128, layer * 16 + 12);
          const bool od = lane & 1;
#pragma unroll
          for (int i = 0; i < 4; ++i)
            sts128(sb + (3 + hp) * SLOT + (cw * 128 + i * 32 + lane) * 16,
                   make_uint4(__float_as_uint(kva[4 * i]), __float_as_uint(kva[4 * i + 1]), __float_as_uint(kva[4 * i + 2]),
                              __float_as_uint(od == (i >= 2) ? 1.f : kva[4 * i + 3])));
          sts128(sb + (6 + hp) * SLOT + wg * 8192 + (wq * 32 + lane) * 16,
                 make_uint4(__float_as_uint(od ? kva[11] : kva[3]), __float_as_uint(od ? kva[15] : kva[7]), __float_as_uint(od ? kva[18] : kva[16]), __float_as_uint(1.f)));
          __syncwarp();
          if (lane == 0) mbar_arrive(bar + B_KVDONE - hp * 32);
          PROFT(tid_ == 128, layer * 16 + 3);
        };
        const uint4* const kvg = g_kv + (g * 2 + (layer >> 1)) * 2560 + cw * 128 + lane;
        uint4 ub[2][5];
        auto kv_load = [&](int hp) {
          uint4 (&u)[5] = ub[hp];
#pragma unroll
          for (int i = 0; i < 4; ++i) u[i] = ld_relaxed4(kvg + hp * 1280 + i * 32);
          u[4] = ld_relaxed4(kvg + hp * 1280 + 1024 - cw * 96);
        };
        auto kv_conv = [&](int hp) {
          uint4 (&u)[5] = ub[hp];
          PROFT(tid_ == 128 && hp == 0, layer * 16 + 10);
          PROFT(lane == 0 && hp == 1 && layer == PL, 128 + cw);
          if (hp == 0) mbar_wait(bar + B_KVDONE - 32, par);
          const bool od = lane & 1;
          uint32_t n = 0;
#pragma unroll 1
          while (!__all_sync(0xffffffffu, (od ? u[2].w : u[0].w) == 0x41800000u && (od ? u[3].w : u[1].w) == 0x41800000u && u[4].w == 0x41800000u)) {
#pragma unroll 1
            while (__any_sync(0xffffffffu, u[4].w < KVTH) && ++n < (1u << 20)) u[4].w = ld_relaxed(&kvg[hp * 1280 + 1024 - cw * 96].w);
            if (++n > (1u << 20)) { g_err = 6u; break; }
            kv_load(hp);
          }
          PROFT(lane == 0 && hp == 1 && layer == PL, 136 + cw);
          PROFT(tid_ == 128 && hp == 0, layer * 16 + 5);
          if (!od) { u[0].w = u[4].x; u[1].w = u[4].y; } else { u[2].w = u[4].x; u[3].w = u[4].y; }
#pragma unroll
          for (int i = 0; i < 4; i += 2)
            stsm_x4(sb + (5 + 3 * hp) * SLOT + rowo + (X ^ ((i & 2) << 4)),
                    pack_bf16(__uint_as_float(u[i].x), __uint_as_float(u[i].y)), pack_bf16(__uint_as_float(u[i].z), __uint_as_float(u[i].w)),
                    pack_bf16(__uint_as_float(u[i + 1].x), __uint_as_float(u[i + 1].y)), pack_bf16(__uint_as_float(u[i + 1].z), __uint_as_float(u[i + 1].w)));
          const uint32_t z2 = pack_bf16(__uint_as_float(u[4].z), __uint_as_float(u[4].z));
          if (t < 2) sts128(sb + (5 + 3 * hp) * SLOT + (wrow0 + gq + 8 * t) * 128 + ((4 ^ gq) << 4), make_uint4(z2, z2, z2, z2));
        };
        auto o_mma = [&](int hp, const uint32_t (&pq)[2][4][4]) {
          float (&oa)[2][20] = oab[hp];
          PROFT(tid_ == 128 && hp == 1, layer * 16 + 4);
          const uint32_t dK = (((sb + (5 + 3 * hp) * SLOT) & 0x3FFFF) >> 4) | (512u << 16);
          wgmma_fence();
#pragma unroll
          for (int ks = 0; ks < 4; ++ks) {
#pragma unroll
            for (int hh = 0; hh < 2; ++hh) wgmma_n40_rs(oa[hh], pq[hh][ks], D128(dK + hh * 512 + ks * 128), ks != 0);
          }
          wgmma_commit();
        };
        auto o_start = [&](int hp, const uint32_t (&pq)[2][4][4]) {
          kv_conv(hp);
          nbar<1, 256>();
          fence_async_smem();
          o_mma(hp, pq);
        };
        auto o_end = [&](int hp) {
          float (&oa)[2][20] = oab[hp];
          wgmma_wait<0>();
#pragma unroll
          for (int i = 0; i < 20; ++i) asm volatile("" : "+f"(oa[0][i]), "+f"(oa[1][i]) :: "memory");
#pragma unroll
          for (int hh = 0; hh < 2; ++hh) {
            const float i0 = rcp(oa[hh][16] + 1e-6f), i1 = rcp(oa[hh][18] + 1e-6f);
            const uint32_t qad = sb + (3 + hp) * SLOT + rowo, hx = hh << 6;
#pragma unroll
            for (int np = 0; np < 2; ++np)
            {
              uint32_t (&o)[4] = oq[4 * hp + 2 * hh + np];
              o[0] = pack_bf16(oa[hh][8 * np] * i0, oa[hh][8 * np + 1] * i0); o[1] = pack_bf16(oa[hh][8 * np + 2] * i1, oa[hh][8 * np + 3] * i1);
              o[2] = pack_bf16(oa[hh][8 * np + 4] * i0, oa[hh][8 * np + 5] * i0); o[3] = pack_bf16(oa[hh][8 * np + 6] * i1, oa[hh][8 * np + 7] * i1);
              stsm_tag(qad + (X ^ hx ^ (np << 5)), o[0], o[1], o[2], o[3], make_tag(gq, t, 1u), 2 * hh + np);
            }
          }
          {
          __syncwarp();
          slab_out_half(sb + (3 + hp) * SLOT, g_o + (size_t)m0 * D_ + g * 128 + hp * 64, wrow0, lane);
          __syncwarp();
          if (lane == 0) mbar_arrive(bar + (hp ? B_ODONE : B_OH1));
          }
        };
#define XO_LOAD() \
        mbar_wait(bar + B_XOLD, 0); \
        mbar_wait(bar + B_XOLD2, 0); \
        _Pragma("unroll") for (int jp = 0; jp < 8; ++jp) \
          ldsm_x4(xo[4 * jp], xo[4 * jp + 1], xo[4 * jp + 2], xo[4 * jp + 3], sb + (XS + 1 - (jp >> 2)) * SLOT + rowo + (X ^ ((jp & 3) << 5)));
#define SC_RELOAD() \
        sc0 = __uint_as_float(lds_vol(sb + SM_RS + (16 + wrow0 + gq) * 4)) * L2E; sc1 = __uint_as_float(lds_vol(sb + SM_RS + (24 + wrow0 + gq) * 4)) * L2E;
        __syncwarp();
        phi_proj<0>(p, kq, wa0);
        phi_exp(raw[0], p[0], sc0, sc1);
        phi_exp(raw[1], p[1], sc0, sc1);
        phi_proj<16>(p, kq, wa0 + 5120);
        phi_norm<0>(ph, raw, kq, wa0, sc0, sc1, rs0, rs1);
        kv_start(0);
        phi_exp(raw[0], p[0], sc0, sc1);
        kv_end(0);
        XO_LOAD();
        phi_exp(raw[1], p[1], sc0, sc1);
        phi_proj<32>(p, kq, wa0);
        phi_norm<16>(ph, raw, kq, wa0 + 5120, sc0, sc1, rs0, rs1);
        kv_start(1);
        if (lane == 0) release2(bar + B_E3);
        phi_exp(raw[0], p[0], sc0, sc1);
        kv_end(1);
        SC_RELOAD();
        phi_exp(raw[1], p[1], sc0, sc1);
        phi_proj<48>(p, kq, wa0 + 5120);
        phi_norm<32>(ph, raw, kq, wa0, sc0, sc1, 1.f, 1.f);
        kv_load(0);
        phi_exp(raw[0], p[0], sc0, sc1);
        phi_exp(raw[1], p[1], sc0, sc1);
        if ((raw[0][2][0] & raw[0][2][2] & raw[0][3][0] & raw[0][3][2] & raw[1][2][0] & raw[1][2][2] & raw[1][3][0] & raw[1][3][2]) == ~0u) sts_f(sb + SM_EPOCH + 12, 0.f);
        o_start(0, ph);
        kv_load(1);
        o_end(0);
        phi_norm<48>(ph, raw, kq, wa0 + 5120, sc0, sc1, 1.f, 1.f);
        o_start(1, ph);
        o_end(1);
      }
      __syncwarp();
      PROFT(lane == 0 && layer == PL, 216 + cw);
      if (lane == 0) mbar_arrive(bar + B_EPI);
      PROFT(tid_ == 128, layer * 16 + 6);
    }
    {
      PHASE_CTX();
      const uint32_t wu = c.cu >> 2;
      const uint32_t dA0 = (((sb + wu * 8192) & 0x3FFFF) >> 4) | (1u << 16), dB0 = ((sb & 0x3FFFF) >> 4) | (512u << 16);
#pragma unroll
      for (int i = 0; i < 32; ++i) { acc[128 + 2 * i] = bf_lo(xo[i]); acc[129 + 2 * i] = bf_hi(xo[i]); }
      uint64_t ta = ((layer & 1) ? WO_A1 : WO_A0) >> 8, tw = (layer & 1) ? WO_B1 : WO_B0;
      mbar_wait(bar + B_FULLT, layer & 1);
      mbar_wait(bar + B_FULLT + 8, layer & 1);
      PROFT(tid_ == 128 && layer == PL, 160);
      wgmma_fence();
#pragma unroll
      for (int k = 0; k < 8; ++k) wgmma_n128_rs(acc, oq[k], D128(dB0 + ((uint32_t)(tw >> (k & 4)) & 15) * 1024 + (k & 3) * 128), 1);
      wgmma_commit();
      tw >>= 8;
      if (lane == 0) release2(bar + B_E2);
#pragma unroll 1
      for (int i = 2; i < 16; ++i) {
        mbar_wait(bar + B_FULLT + i * 8, layer & 1);
        PROFT(tid_ == 128 && layer == PL, 160 + i);
        tile_check(sb + ((uint32_t)ta & 15) * SLOT, g_o + (size_t)m0 * D_ + ((2 * g + (int)(WOORD >> (4 * i))) & 15) * 64, wrow0, lane, ~layer);
        const uint32_t da = dA0 + ((uint32_t)ta & 15) * 1024, db = dB0 + ((uint32_t)tw & 15) * 1024;
        ta >>= 4; tw >>= 4;
        if (i == 15 && wu) nbar<6, 256>();
        wgmma_fence();
#pragma unroll
        for (int k = 0; k < 4; ++k) wgmma_n128(acc, D128(da + k * 2), D128(db + k * 128), 1);
        wgmma_commit();
        if (i == 15 && !wu) asm volatile("bar.arrive 6, 256;" ::: "memory");
        wgmma_wait<1>();
        if (elected && i < 12) release2(bar + B_CONS + (i - 1) * 8);
        if (elected && (unsigned)(i - 13) < 2u && layer + 1 < NLAYERS) release2(bar + B_EMPTYS + (i - 13) * 8);
      }
      const bool last = layer == NLAYERS - 1;
      Tag xt = make_tag(gq, last ? 4 : t, lds_vol(sb + SM_EPOCH) + layer + 1);
      asm volatile("" : "+r"(xt.me), "+r"(xt.mo), "+r"(xt.tg) :: "memory");
      wgmma_wait<0>();
#pragma unroll
      for (int i = 128; i < 192; ++i) asm volatile("" : "+f"(acc[i]) :: "memory");
      if (elected && !last) release2(bar + B_EMPTYS + 16);
      PROFT(tid_ == 128, layer * 16 + 7);
      X_HALF(0, xt);
      if (last) {
        __syncwarp();
        slab_out_half(sb + XS * SLOT, c.out + (size_t)m0 * D_ + g * 128, wrow0, lane);
        X_HALF(1, (Tag{0u, 0u, 0u}));
        __syncwarp();
        slab_out_half(sb + (XS + 1) * SLOT, c.out + (size_t)m0 * D_ + g * 128 + 64, wrow0, lane);
        __syncwarp();
        if (lane == 0) mbar_arrive(bar + B_XDONE);
        PROFT(tid_ == 128, layer * 16 + 24);
        break;
      }
      __syncwarp();
      slab_out_half(sb + XS * SLOT, g_x + (size_t)m0 * D_ + g * 128, wrow0, lane, true);
      __syncwarp();
      if (lane == 0) mbar_arrive(bar + B_XH0);
      nbar_dyn(3 + wu, 128);
    }
  }
}

__device__ __forceinline__ int kblock0(int i, int g) {
  const int j = i >> 1, p = max(g, NCOM) + j - NCOM;
  return (j < NCOM ? j : p < 8 ? p : p - 8 + NCOM) * 2 + (i & 1);
}

__device__ __forceinline__ int wo_kblock(int m, int g) { return (2 * g + (int)((WOORD >> (4 * m)) & 15)) & 15; }

__global__ void __cluster_dims__(2, 1, 1) __launch_bounds__(384, 1)
mega_kernel(const __grid_constant__ CUtensorMap tm_x0, const __grid_constant__ CUtensorMap tm_x,
            const __grid_constant__ CUtensorMap tm_o,
            const __grid_constant__ CUtensorMap tm_wA, const __grid_constant__ CUtensorMap tm_wB,
            const __grid_constant__ CUtensorMap tm_woA, const __grid_constant__ CUtensorMap tm_woB,
                        const bf16* __restrict__ wB, const bf16* __restrict__ wphi, bf16* __restrict__ out) {
  extern __shared__ uint8_t smem_raw[];
  const uint32_t sb = (smem_u32(smem_raw) + 1023u) & ~1023u;
  const uint32_t bar = sb + SM_BAR;
  const int warp = __shfl_sync(0xffffffffu, threadIdx.x >> 5, 0), lane = threadIdx.x & 31;
  uint32_t bid = blockIdx.x;
  if (gridDim.x == 128 + NX) {
    uint32_t tp;
    asm volatile("mov.u32 %0, %%smid;" : "=r"(tp));
    tp >>= 1;
    const uint32_t u7 = ((tp - 32) * 37) >> 8;
    bid = (tp < 32 ? tp : tp < 60 ? tp + 1 + u7 : tp < 62 ? tp + 4 : (tp - 58) * 8) * 2 + (bid & 1);
  }
  if (bid >= 128 || gridDim.x == NX) {
    const int xb = bid & (NX - 1);
    const int ch = threadIdx.x % 96, rg = threadIdx.x / 96, gg = xb * 2 + ch / 48, sec = (ch % 48) >> 4;
    const uint4* src = reinterpret_cast<const uint4*>(wB + (size_t)rg * 3072 + (sec == 2 ? 0 : 1024 + sec * 1024) + gg * 128 + (ch & 15) * 8);
    float s[8] = {0.f, 0.f, 0.f, 0.f, 0.f, 0.f, 0.f, 0.f};
#pragma unroll 1
    for (int r0 = 0; r0 < 256; r0 += 32) {
      uint4 v[32];
#pragma unroll
      for (int r = 0; r < 32; ++r) v[r] = __ldg(src + (size_t)(r0 + r) * 1536);
#pragma unroll
      for (int r = 0; r < 32; ++r) {
        s[0] += bf_lo(v[r].x); s[1] += bf_hi(v[r].x); s[2] += bf_lo(v[r].y); s[3] += bf_hi(v[r].y);
        s[4] += bf_lo(v[r].z); s[5] += bf_hi(v[r].z); s[6] += bf_lo(v[r].w); s[7] += bf_hi(v[r].w);
      }
    }
    float* cd = g_cs + (ld_relaxed(&g_epoch) & 1) * 6144 + 3072 + xb * 768 + ch * 8;
    red_add4(cd, s[0], s[1], s[2], s[3]);
    red_add4(cd + 4, s[4], s[5], s[6], s[7]);
    nbar<1, 384>();
    if (threadIdx.x < 2) flag_add(&g_csflag[8 + xb * 2 + threadIdx.x].v);
    return;
  }
  const int cr = bid & 1;
  const int g = bid >> 4;
  const int rb = bid & 15;
  const int m0 = rb * 128;

  if (warp < 4) {
    asm volatile("setmaxnreg.dec.sync.aligned.u32 40;");
    asm volatile("barrier.cluster.arrive.relaxed.aligned;" ::: "memory");
    const unsigned int epoch = warp ? ld_relaxed(&g_epoch) : 0u;
    if (warp) cluster_wait();
    unsigned int xbase = epoch * NLAYERS;
    auto wo_a = [&](int layer, int m1) {
      uint64_t ts = ((layer & 1) ? WO_A1 : WO_A0) >> (4 * m1), td = ((layer & 1) ? WO_DA1 : WO_DA0) >> (4 * m1), tk = WOORD >> (4 * m1);
      uint32_t ready = 0u;
#pragma unroll 1
      for (int m = m1; m < 16; ++m) {
        const int kb = (2 * g + (uint32_t)tk) & 15;
        uint32_t dst = sb + ((uint32_t)ts & 15) * SLOT, fb = bar + B_FULLT + m * 8, eb = bar + B_CONS + ((uint32_t)td & 15) * 8;
        int kc = kb * 64;
        ts >>= 4; td >>= 4; tk >>= 4;
        asm volatile("" : "+r"(dst), "+r"(fb), "+r"(eb), "+r"(kc));
        bool fr = false;
        if (!((ready >> kb) & 1)) {
          PROFT(m == 2 && lane == 0, 64 + layer * 16 + 2);
          fr = src_wait_tma(g_of + rb * 32, xbase + layer + 1, 1u << kb, ready, lane, eb, layer & 1);
          fence_async_all();
        }
        if (m == 6) mbar_wait_u(bar + B_EPI, layer & 1);
        if (!fr) mbar_wait_u(eb, layer & 1);
        tma_2d_e(dst, &tm_o, kc, m0, fb);
        PROFT(lane == 0 && layer == PL, 176 + m);
      }
    };
    auto wo_w = [&](int layer) {
      const CUtensorMap* tx = layer == 0 ? &tm_x0 : &tm_x;
      const CUtensorMap* two = (layer & 1) ? &tm_woB : &tm_woA;
      uint64_t ts = (layer & 1) ? WO_B1 : WO_B0, td = (layer & 1) ? WO_DB1 : WO_DB0, tk = WOORD;
      uint32_t pb = 0;
      fence_async_all();
      mbar_wait_u(bar + B_R0, layer & 1);
      expect_tx_e(bar + B_XOLD, 16384);
      tma_2d_e(sb + (XS + 1) * SLOT, tx, g * 128, m0, bar + B_XOLD);
#pragma unroll 1
      for (int m = 0; m < 16; ++m) {
        uint32_t dst = sb + ((uint32_t)ts & 15) * SLOT + cr * 8192, fb = bar + B_FULLT + m * 8, eb = bar + B_CONS + ((uint32_t)td & 15) * 8;
        int kc = ((2 * g + (uint32_t)tk) & 15) * 64;
        ts >>= 4; td >>= 4; tk >>= 4;
        asm volatile("" : "+r"(dst), "+r"(fb), "+r"(eb), "+r"(kc));
        if (eb < bar + B_E3 && pb >= bar + B_E3) mbar_wait_u(bar + B_E2, layer & 1);
        if (eb != pb) mbar_wait_u(eb, layer & 1);
        pb = eb;
        tma_2d_mc_e(dst, two, g * 128 + cr * 64, kc, fb);
        expect_tx_e(fb, m < 2 ? 16384 : 32768);
        PROFT(lane == 0 && layer == PL, 144 + m);
        if (m == ((layer & 1) ? 2 : 0)) {
          expect_tx_e(bar + B_XOLD2, 16384);
          tma_2d_e(sb + XS * SLOT, tx, g * 128 + 64, m0, bar + B_XOLD2);
        }
      }
    };
    if (warp == 0) {
      cluster_wait();
      PROFT(lane == 0, 125);
#pragma unroll 1
      for (int layer = 0; layer < NLAYERS; ++layer) {
        const CUtensorMap* tx = layer == 0 ? &tm_x0 : &tm_x;
        const CUtensorMap* tw = (layer & 1) ? &tm_wB : &tm_wA;
        uint32_t s = layer == 0, u = 0, ready = layer == 0 ? 0xFFFFu : 0u;
#pragma unroll 1
        for (int i = s; i < 16; ++i) {
          const int kb = layer == 0 ? kblock0(i, g) : wo_kblock(i, g), kc = kb * 64;
          const uint32_t fb = bar + B_FULLS + s * 8;
          const uint32_t kd = sb + (((QK >> (4 * s)) & 15) + cr) * SLOT, qd = sb + ((QQ >> (4 * s)) & 15) * SLOT + cr * 8192;
          const uint32_t need = 1u << kb;
          const bool ext = i >= 2 || layer == 0, early = ext && (ready & need) == need;
          mbar_wait_u(bar + B_EMPTYS + s * 8, (u + (s ? layer : 0) + 1) & 1);
          if (early) tma_2d_e(sb + ((QA >> (4 * s)) & 15) * SLOT, tx, kc, m0, fb);
          tma_2d_mc_e(kd, tw, 1024 + cr * 1024 + g * 128, kc, fb);
          tma_2d_mc_e(kd + 8192, tw, 1024 + cr * 1024 + g * 128 + 64, kc, fb);
          tma_2d_mc_e(qd, tw, g * 128 + cr * 64, kc, fb);
          expect_tx_e(fb, ext ? 65536 : 49152);
          PROFT(lane == 0 && layer == 0 && i == 1, 31);
          if (layer == 0 && g >= NCOM && i == XPF + (((g - NCOM) * XPM) >> 2)) {
            if (i <= 2) mbar_wait_u(bar + B_FULLS, 0);
            tma_pf_e(&tm_x0, g * 128, m0);
            tma_pf_e(&tm_x0, g * 128 + 64, m0);
          }
          if (layer < 2 && i >= PFS) {
            const int j = i - PFS;
            if (j < 2) tma_pf_e(layer ? &tm_woB : &tm_woA, g * 128 + j * 64, rb * 64);
            else if (j < 8 && layer == 0) tma_pf_e(&tm_wB, ((j >> 1) - 1) * 1024 + g * 128 + (j & 1) * 64, rb * 64);
          }
          if (ext && !early) {
            PROFT(i == 2 && lane == 0, 64 + layer * 16 + 0);
            src_wait_tma(g_xf + rb * 32, xbase + layer + 1, need, ready, lane, fb, 0);
            PROFT(i == 2 && lane == 0, 64 + layer * 16 + 1);
            fence_async_all();
            tma_2d_e(sb + ((QA >> (4 * s)) & 15) * SLOT, tx, kc, m0, fb);
          }
          if (++s == 3) { s = 0; ++u; }
        }
        if (layer == 0) xbase = ld_relaxed(&g_epoch) * NLAYERS;
        wo_a(layer, 2);
      }
    } else {
      if (warp >= 2) {
        const int h2 = threadIdx.x - 64;
        if (h2 < 16) sts_f(sb + SM_RS + h2 * 4, 0.f);
        if (h2 == 0) sts_f(sb + SM_EPOCH, __uint_as_float(epoch));
        mbar_wait_u(bar + B_FULLS, 0);
        colsum(&tm_wA, g_cs + (epoch & 1) * 6144, rb, g, warp - 2, 2, lane, warp == 2 ? sb + SM_SD : (sb + SM_BP + 1023u) & ~1023u, bar + B_CB + (warp - 2) * 8, 0);
#pragma unroll 1
        for (int i = h2; i < 320; i += 64) g_kv[(g * 16 + rb) * 320 + i] = make_uint4(0u, 0u, 0u, 0u);
        fence_async_all();
        nbar<5, 64>();
        if (h2 == 0) flag_add(&g_csflag[g].v);
        PROFT(h2 == 0, 242);
#pragma unroll 1
        for (int i = h2; i < 512; i += 256) {
          uint4 w[4];
#pragma unroll
          for (int j = 0; j < 4; ++j) w[j] = __ldg(reinterpret_cast<const uint4*>(wphi + (size_t)g * 4096) + i + j * 64);
#pragma unroll
          for (int j = 0; j < 4; ++j) sts128(sb + SM_WPHI + ((i >> 2) + j * 16) * 80 + (i & 3) * 16, w[j]);
        }
      }
      if (warp == 1) {
        if (lane >= 27) {
          const CUtensorMap* tm = lane == 27 ? &tm_o : lane == 28 ? &tm_wB : lane == 29 ? &tm_woA : lane == 30 ? &tm_woB : &tm_x;
          asm volatile("prefetch.tensormap [%0];" ::"l"(tm) : "memory");
        }
        __syncwarp();
        {
#pragma unroll 1
          for (int e = 0;; ++e) {
            if (e > 0 && e < NLAYERS) {
              mbar_wait_u(bar + B_XH0, (e - 1) & 1);
              flag_hint(g_xf + rb * 32 + 2 * g, xbase + e + 1);
            }
            mbar_wait_u(bar + B_XDONE, e & 1);
            PROFT(e < 4, 64 + e * 16 + 4);
            if (e == NLAYERS) {
              if (bid == 0) g_epoch = epoch + 1;
              break;
            }
            PROFT(e < 4, 64 + e * 16 + 5);
            flag_set(g_xf + rb * 32 + 2 * g + 1, xbase + e + 1);
            PROFT(e < 4, 64 + e * 16 + 7);
            if ((e & 1) == 0) {
#pragma unroll 1
              for (int hp = 0; hp < 2; ++hp) {
                uint4* kvl = g_kv + ((g * 2 + (e >> 1)) * 2 + hp) * 1280;
                mbar_wait_u(bar + B_KVDONE - hp * 32, (e >> 1) & 1);
                PROFT(e == PL, 243 + hp * 4);
                fence_async_smem();
                bulk_red_add_e(kvl + rb * 64, sb + (3 + hp) * SLOT + rb * 1024, 16384 - rb * 1024);
                if (rb) bulk_red_add_e(kvl, sb + (3 + hp) * SLOT, rb * 1024);
                bulk_red_add_e(kvl + 1024, sb + (6 + hp) * SLOT, 2048);
                bulk_red_add_e(kvl + 1152, sb + (6 + hp) * SLOT + 8192, 2048);
                bulk_commit();
                PROFT(e < 4, 64 + e * 16 + 6);
              }
              bulk_wait_read0();
              __syncwarp();
              if (lane < 2) release2(bar + B_E1);
              __syncwarp();
            }
            mbar_wait_u(bar + B_OH1, e & 1);
            PROFT(e == PL, 251);
            flag_hint(g_of + rb * 32 + 2 * g, xbase + e + 1);
            PROFT(e < 4, 64 + e * 16 + 9);
            mbar_wait_u(bar + B_ODONE, e & 1);
            PROFT(e < 4, 64 + e * 16 + 8);
            flag_hint(g_of + rb * 32 + 2 * g + 1, xbase + e + 1);
            PROFT(e < 4, 64 + e * 16 + 11);
          }
        }
      } else {
        const int h2 = threadIdx.x - 64;
        const float* cs = g_cs + (epoch & 1) * 6144;
#pragma unroll 1
        for (int layer = 0; layer < NLAYERS; ++layer) {
          if (warp == 2 && layer < 2) {
            if (lane == 0) flag_wait_t<128>(&g_csflag[layer * 8 + g].v, (epoch + 1) * (16u + layer));
            __syncwarp();
            float4 a[3];
#pragma unroll
            for (int i = 0; i < 3; ++i) a[i] = __ldcg(reinterpret_cast<const float4*>(cs + layer * 3072 + g * 384) + i * 32 + lane);
#pragma unroll 1
            for (int i = 0; i < 3; ++i) {
              const float av[4] = {a[0].x, a[0].y, a[0].z, a[0].w};
              a[0] = a[1]; a[1] = a[2];
#pragma unroll
              for (int j = 0; j < 4; ++j) {
                const float c1 = bf16r(av[j]), c2 = bf16r(av[j] - c1), c3 = (av[j] - c1) - c2;
                sts128(sb + SM_BP + layer * 6144 + ((i * 32 + lane) * 4 + j) * 16, make_uint4(pack_bf16(c1, c2), pack_bf16(c3, 0.f), 0u, 0u));
              }
            }
            fence_async_smem();
            __syncwarp();
            if (lane == 0) mbar_arrive(bar + (layer ? B_CS2 : B_CS));
            PROFT(lane == 0, 64 + layer * 16 + 12);
            if (layer == 0) {
              uint4* hz = g_halo + (rb * 8 + g) * 1024;
#pragma unroll 2
              for (int i = lane; i < 1024; i += 32) hz[i] = make_uint4(0u, 0u, 0u, 0u);
              if (lane < 12) reinterpret_cast<float4*>(g_cs + ((epoch & 1) ^ 1) * 6144 + bid * 48)[lane] = make_float4(0.f, 0.f, 0.f, 0.f);
              g_stats[(2 + (lane >> 4)) * S_ + m0 + g * 16 + (lane & 15)] = make_float2(0.f, 0.f);
              __syncwarp();
              if (lane == 0) flag_add(&g_csflag[8 + g].v);
            }
          }
          if (warp == 3) {
            const bool hal = (layer & 1) && rb > 0;
            {
              uint32_t rdy = 0u;
              src_wait<256>(g_xf + rb * 32, xbase + layer + 1, 0xAAAAu, rdy, lane);
              rdy = 0u;
              if (hal) src_wait<256>(g_xf + (rb - 1) * 32, xbase + layer + 1, 0xAAAAu, rdy, lane);
            }
            float2 u[5];
            const float2* sp = g_stats + layer * S_ + m0 + lane;
#pragma unroll
            for (int i = 0; i < 4; ++i) u[i] = __ldcg(sp + i * 32);
            u[4] = __ldcg(hal ? sp - 16 : sp);
            if (layer == 3) g_stats[(lane >> 4) * S_ + m0 + g * 16 + (lane & 15)] = make_float2(0.f, 0.f);
#pragma unroll
            for (int i = 0; i < 5; ++i) {
              const int r = i < 4 ? 16 + i * 32 + lane : lane;
              const float mean = u[i].x * (1.f / D_);
              const float var = fmaxf(fmaf(-u[i].x, mean, u[i].y) * (1.f / D_), 0.f);
              float sd;
              asm("sqrt.approx.f32 %0, %1;" : "=f"(sd) : "f"(bf16r(bf16r(var) + 1e-5f)));
              sd = bf16r(sd);
              if (i < 4 || hal) sts_f(sb + SM_RS + r * 4, rcp(sd));
              if (i < 4) {
                const float hm = -0.5f * bf16r(mean);
                const uint32_t s2 = pack_bf16(sd, sd);
                if (!(layer & 1)) sts128(sb + SM_SD + (r - 16) * 64 + ((r >> 1) & 3) * 16, make_uint4(s2, s2, s2, s2));
                sts128(sb + SM_AP + (r - 16) * 16, make_uint4(pack_bf16(hm, hm), pack_bf16(hm, 0.f), 0u, 0u));
              }
            }
            fence_async_smem();
            __syncwarp();
            if (lane == 0) mbar_arrive(bar + B_STAT);
            PROFT(lane == 0, 64 + layer * 16 + 14);
            wo_w(__shfl_sync(0xffffffffu, layer, 0));
          }
        }
      }
    }
    __syncwarp();
    asm volatile("barrier.cluster.arrive.relaxed.aligned;\nbarrier.cluster.wait.aligned;\n" ::: "memory");
  } else {
    if (warp == 5) {
      if (lane == 0) {
        mbar_init(bar + B_FULLS, 1);
        asm volatile("fence.mbarrier_init.release.cluster;" ::: "memory");
      }
      __syncwarp();
      expect_tx_e(bar + B_FULLS, 65536);
      tma_2d_e(sb + XS * SLOT, &tm_x0, 0, m0, bar + B_FULLS);
#pragma unroll
      for (int j = 0; j < 6; ++j)
        tma_2d_e(sb + (j < 4 ? j + 4 : j - 2) * 8192, &tm_wA, (j < 4 ? 1024 + (j >> 1) * 1024 : 0) + g * 128 + (j & 1) * 64, 0, bar + B_FULLS);
      PROFT(lane == 0, 241);
    }
    if (lane < 8 && warp != 5 && threadIdx.x != 128) {
      const int i = (warp - 4) * 8 + lane;
      mbar_init(bar + i * 8, i < 32 ? 1u << ((BAR_CNT >> (2 * i)) & 3) : i < 48 ? 1u : (i == 59 || i == 60 || i == 62) ? 16u : (i == 48 || i == 63) ? 8u : 4u);
      asm volatile("fence.mbarrier_init.release.cluster;" ::: "memory");
    }
    __syncwarp();
    asm volatile("barrier.cluster.arrive.relaxed.aligned;" ::: "memory");
    asm volatile("setmaxnreg.inc.sync.aligned.u32 232;");
    cluster_wait();
    PROFT(threadIdx.x == 128, 0);
    Ctx c; c.sb = sb; c.g = g; c.rb = rb; c.cu = warp - 4; c.out = out;
    consumer(c);
    asm volatile("bar.warp.sync 0xffffffff;\nbarrier.cluster.arrive.relaxed.aligned;\nbarrier.cluster.wait.aligned;\n" ::: "memory");
  }
}

typedef CUresult (*PFN_encodeTiled)(CUtensorMap*, CUtensorMapDataType, cuuint32_t, void*, const cuuint64_t*, const cuuint64_t*,
                                    const cuuint32_t*, const cuuint32_t*, CUtensorMapInterleave, CUtensorMapSwizzle,
                                    CUtensorMapL2promotion, CUtensorMapFloatOOBfill);

static CUtensorMap make_map(PFN_encodeTiled enc, const void* ptr, uint64_t cols, uint64_t rows, uint32_t box_c, uint32_t box_r, uint32_t nb = 1) {
  CUtensorMap m;
  cuuint64_t dims[3] = {nb > 1 ? box_c : cols, rows, cols / box_c};
  cuuint64_t strides[2] = {cols * 2, box_c * 2};
  cuuint32_t box[3] = {box_c, box_r, nb};
  cuuint32_t es[3] = {1, 1, 1};
  CUresult r = enc(&m, CU_TENSOR_MAP_DATA_TYPE_BFLOAT16, nb > 1 ? 3 : 2, const_cast<void*>(ptr), dims, strides, box, es, CU_TENSOR_MAP_INTERLEAVE_NONE,
      CU_TENSOR_MAP_SWIZZLE_128B, CU_TENSOR_MAP_L2_PROMOTION_L2_256B, CU_TENSOR_MAP_FLOAT_OOB_FILL_NONE);
  (void)r;
  return m;
}

extern "C" void kernel_launch(void* const* d_in, const int* in_sizes, int n_in, void* d_out, int out_size) {
  const bf16* A_x = (const bf16*)d_in[0];
  const bf16* A_wqkv = (const bf16*)d_in[1];
  const bf16* A_wphi = (const bf16*)d_in[2];
  const bf16* A_wo = (const bf16*)d_in[3];
  const bf16* B_wqkv = (const bf16*)d_in[5];
  const bf16* B_wo = (const bf16*)d_in[6];
  bf16* out = (bf16*)d_out;

  static PFN_encodeTiled enc = nullptr;
  static bf16 *p_x, *p_o;
  static bool together;
  if (!enc) {
    void* fn = nullptr; cudaDriverEntryPointQueryResult qr;
    cudaGetDriverEntryPoint("cuTensorMapEncodeTiled", &fn, cudaEnableDefault, &qr);
    enc = (PFN_encodeTiled)fn;
    cudaGetSymbolAddress((void**)&p_x, g_x);
    cudaGetSymbolAddress((void**)&p_o, g_o);
    cudaFuncSetAttribute(mega_kernel, cudaFuncAttributeMaxDynamicSharedMemorySize, SM_TOTAL);
    cudaLaunchConfig_t cfg = {};
    cfg.gridDim = dim3(128 + NX); cfg.blockDim = dim3(384); cfg.dynamicSmemBytes = SM_TOTAL;
    cudaLaunchAttribute at[1];
    at[0].id = cudaLaunchAttributeClusterDimension; at[0].val.clusterDim.x = 2; at[0].val.clusterDim.y = 1; at[0].val.clusterDim.z = 1;
    cfg.attrs = at; cfg.numAttrs = 1;
    int ncl = 0;
    together = cudaOccupancyMaxActiveClusters(&ncl, mega_kernel, &cfg) == cudaSuccess && 2 * ncl == 128 + NX;
    int nsm = 0;
    cudaDeviceGetAttribute(&nsm, cudaDevAttrMultiProcessorCount, 0);
    together = together && nsm == 128 + NX;
  }
  CUtensorMap tm_x0 = make_map(enc, A_x, 1024, 2048, 64, 128);
  CUtensorMap tm_x = make_map(enc, p_x, 1024, 2048, 64, 128);
  CUtensorMap tm_o = make_map(enc, p_o, 1024, 2048, 64, 128);
  CUtensorMap tm_wA = make_map(enc, A_wqkv, 3072, 1024, 64, 64);
  CUtensorMap tm_wB = make_map(enc, B_wqkv, 3072, 1024, 64, 64);
  CUtensorMap tm_woA = make_map(enc, A_wo, 1024, 1024, 64, 64);
  CUtensorMap tm_woB = make_map(enc, B_wo, 1024, 1024, 64, 64);
  if (!together) mega_kernel<<<NX, 384, SM_TOTAL, cudaStreamPerThread>>>(tm_x0, tm_x, tm_o, tm_wA, tm_wB, tm_woA, tm_woB, B_wqkv, A_wphi, out);
  mega_kernel<<<together ? 128 + NX : 128, 384, SM_TOTAL, cudaStreamPerThread>>>(tm_x0, tm_x, tm_o, tm_wA, tm_wB, tm_woA, tm_woB,
                                                                                 B_wqkv, A_wphi, out);
}
```

```cpp
#include <cuda_runtime.h>
#include <cuda_bf16.h>
#include <cuda.h>
#include <stdint.h>

typedef __nv_bfloat16 bf16;

constexpr int S_ = 2048, D_ = 1024;

struct __align__(128) Flag { unsigned int v; unsigned int pad[31]; };
__device__ __align__(1024) bf16 g_x[S_ * D_];
__device__ __align__(1024) bf16 g_o[S_ * D_];
__device__ __align__(1024) uint4 g_halo[128 * 2 * 512];
__device__ __align__(1024) uint4 g_kv[8 * 2 * 2 * 1280];
__device__ __align__(1024) float2 g_stats[4 * S_];
__device__ __align__(1024) float g_cs[2 * 2 * 3072];
__device__ Flag g_csflag[16];
__device__ __align__(128) unsigned int g_xf[16 * 32], g_of[16 * 32];
__device__ unsigned int g_epoch, g_err;
#define PROFT(cond, idx) asm volatile("" ::: "memory")

__device__ __forceinline__ uint32_t smem_u32(const void* p) { return (uint32_t)__cvta_generic_to_shared(p); }
__device__ __forceinline__ void mbar_init(uint32_t bar, uint32_t count) {
  asm volatile("mbarrier.init.shared::cta.b64 [%0], %1;" ::"r"(bar), "r"(count) : "memory");
}
__device__ __forceinline__ void mbar_arrive(uint32_t bar) {
  asm volatile("mbarrier.arrive.shared::cta.b64 _, [%0];" ::"r"(bar) : "memory");
}
__device__ __forceinline__ bool mbar_try_wait(uint32_t bar, uint32_t parity) {
  uint32_t ok;
  asm volatile("{\n.reg .pred p;\nmbarrier.try_wait.parity.shared::cta.b64 p, [%1], %2;\nselp.b32 %0, 1, 0, p;\n}\n"
               : "=r"(ok) : "r"(bar), "r"(parity) : "memory");
  return ok != 0;
}
__device__ __forceinline__ bool mbar_test_wait(uint32_t bar, uint32_t parity) {
  uint32_t ok;
  asm volatile("{\n.reg .pred p;\nmbarrier.test_wait.parity.shared::cta.b64 p, [%1], %2;\nselp.b32 %0, 1, 0, p;\n}\n"
               : "=r"(ok) : "r"(bar), "r"(parity) : "memory");
  return ok != 0;
}
__device__ __forceinline__ uint64_t gtimer() {
  uint64_t t; asm volatile("mov.u64 %0, %globaltimer;" : "=l"(t)); return t;
}
__device__ __forceinline__ void mbar_wait(uint32_t bar, uint32_t parity) {
  uint32_t n = 0;
#pragma unroll 1
  while (!mbar_try_wait(bar, parity)) {
    if (++n > (1u << 22)) { g_err = 1u; break; }
  }
}
__device__ __forceinline__ unsigned int ld_acquire(const unsigned int* p) {
  unsigned int v; asm volatile("ld.acquire.gpu.global.u32 %0, [%1];" : "=r"(v) : "l"(p) : "memory"); return v;
}
__device__ __forceinline__ void flag_add(unsigned int* p) {
  asm volatile("red.release.gpu.global.add.u32 [%0], 1;" ::"l"(p) : "memory");
}
__device__ __forceinline__ void flag_set(unsigned int* p, unsigned int v) {
  asm volatile("st.release.gpu.global.u32 [%0], %1;" ::"l"(p), "r"(v) : "memory");
}
__device__ __forceinline__ void flag_hint(unsigned int* p, unsigned int v) {
  asm volatile("st.relaxed.gpu.global.u32 [%0], %1;" ::"l"(p), "r"(v) : "memory");
}
template <int SLEEP>
__device__ __forceinline__ void src_wait(const unsigned int* f, unsigned int target, uint32_t need, uint32_t& ready, int lane) {
  uint32_t n = 0;
#pragma unroll 1
  while ((ready & need) != need) {
    const unsigned int v = ld_acquire(f + (lane & 15));
    ready = __ballot_sync(0xffffffffu, (int)(v - target) >= 0);
    if (SLEEP) { if ((ready & need) != need) __nanosleep(SLEEP); }
    if (++n > (1u << 20)) { g_err = 3u; break; }
  }
  __syncwarp();
}
__device__ __forceinline__ unsigned int ld_relaxed(const unsigned int* p) {
  unsigned int v; asm volatile("ld.relaxed.gpu.global.u32 %0, [%1];" : "=r"(v) : "l"(p) : "memory"); return v;
}
__device__ __forceinline__ bool src_wait_tma(const unsigned int* f, unsigned int target, uint32_t need, uint32_t& ready, int lane, uint32_t eb, uint32_t par) {
  uint32_t n = 0;
  bool fr = false;
#pragma unroll 1
  while ((ready & need) != need) {
    const unsigned int v = ld_acquire(f + (lane & 15));
    fr = __all_sync(0xffffffffu, mbar_test_wait(eb, par));
    ready = __ballot_sync(0xffffffffu, (int)(v - target) >= 0);
    if (++n > (1u << 20)) { g_err = 3u; break; }
  }
  return fr;
}
__device__ __forceinline__ uint4 ld_relaxed4(const uint4* p) {
  uint4 v; asm volatile("ld.relaxed.gpu.global.v4.u32 {%0,%1,%2,%3}, [%4];" : "=r"(v.x), "=r"(v.y), "=r"(v.z), "=r"(v.w) : "l"(p) : "memory"); return v;
}
__device__ __forceinline__ void st_relaxed4(uint4* p, uint32_t a, uint32_t b, uint32_t c, uint32_t d) {
  asm volatile("st.relaxed.gpu.global.v4.u32 [%0], {%1,%2,%3,%4};" ::"l"(p), "r"(a), "r"(b), "r"(c), "r"(d) : "memory");
}
template <int SLEEP>
__device__ __forceinline__ void flag_wait_t(const unsigned int* p, unsigned int target) {
  uint32_t n = 0;
#pragma unroll 1
  while ((int)(ld_acquire(p) - target) < 0) {
    if (SLEEP) __nanosleep(SLEEP);
    if (++n > (1u << 20)) { g_err = 2u; break; }
  }
}
__device__ __forceinline__ void mbar_wait_u(uint32_t bar, uint32_t parity) {
  uint32_t n = 0;
#pragma unroll 1
  while (!__all_sync(0xffffffffu, mbar_try_wait(bar, parity))) {
    if (++n > (1u << 22)) { g_err = 1u; break; }
  }
}
__device__ __forceinline__ void expect_tx_e(uint32_t bar, uint32_t bytes) {
  asm volatile("{\n.reg .pred p;\nelect.sync _|p, 0xffffffff;\n@p mbarrier.arrive.expect_tx.shared::cta.b64 _, [%0], %1;\n}\n" ::"r"(bar), "r"(bytes) : "memory");
}
__device__ __forceinline__ void tma_2d_e(uint32_t dst, const CUtensorMap* tm, int c0, int c1, uint32_t bar) {
  asm volatile("{\n.reg .pred p;\nelect.sync _|p, 0xffffffff;\n"
               "@p cp.async.bulk.tensor.2d.shared::cluster.global.mbarrier::complete_tx::bytes [%0], [%1, {%2, %3}], [%4];\n}\n"
               ::"r"(dst), "l"(tm), "r"(c0), "r"(c1), "r"(bar) : "memory");
}
__device__ __forceinline__ void tma_2d_mc_e(uint32_t dst, const CUtensorMap* tm, int c0, int c1, uint32_t bar) {
  asm volatile("{\n.reg .pred p;\nelect.sync _|p, 0xffffffff;\n"
               "@p cp.async.bulk.tensor.2d.shared::cluster.global.mbarrier::complete_tx::bytes.multicast::cluster [%0], [%1, {%2, %3}], [%4], %5;\n}\n"
               ::"r"(dst), "l"(tm), "r"(c0), "r"(c1), "r"(bar), "h"((uint16_t)3) : "memory");
}
__device__ __forceinline__ void tma_pf_e(const CUtensorMap* tm, int c0, int c1) {
  asm volatile("{\n.reg .pred p;\nelect.sync _|p, 0xffffffff;\n"
               "@p cp.async.bulk.prefetch.tensor.2d.L2.global.tile [%0, {%1, %2}];\n}\n" ::"l"(tm), "r"(c0), "r"(c1) : "memory");
}
__device__ __forceinline__ void mbar_arrive_cluster(uint32_t local_bar, uint32_t rank) {
  asm volatile("{\n.reg .b32 ra;\nmapa.shared::cluster.u32 ra, %0, %1;\nmbarrier.arrive.shared::cluster.b64 _, [ra];\n}\n"
               ::"r"(local_bar), "r"(rank) : "memory");
}
__device__ __forceinline__ void release2(uint32_t bar) { mbar_arrive_cluster(bar, 0); mbar_arrive_cluster(bar, 1); }
__device__ __forceinline__ void bulk_red_add_e(void* dst, uint32_t src, uint32_t bytes) {
  asm volatile("{\n.reg .pred p;\nelect.sync _|p, 0xffffffff;\n@p cp.reduce.async.bulk.global.shared::cta.bulk_group.add.f32 [%0], [%1], %2;\n}\n" ::"l"(dst), "r"(src), "r"(bytes) : "memory");
}
__device__ __forceinline__ void bulk_commit() { asm volatile("cp.async.bulk.commit_group;" ::: "memory"); }
__device__ __forceinline__ void bulk_wait_read0() { asm volatile("cp.async.bulk.wait_group.read 0;" ::: "memory"); }
__device__ __forceinline__ void fence_async_smem() { asm volatile("fence.proxy.async.shared::cta;" ::: "memory"); }
__device__ __forceinline__ void fence_async_all() { asm volatile("fence.proxy.async.global;" ::: "memory"); }
__device__ __forceinline__ void wgmma_fence() { asm volatile("wgmma.fence.sync.aligned;" ::: "memory"); }
__device__ __forceinline__ void wgmma_commit() { asm volatile("wgmma.commit_group.sync.aligned;" ::: "memory"); }
template <int N> __device__ __forceinline__ void wgmma_wait() { asm volatile("wgmma.wait_group.sync.aligned %0;" ::"n"(N) : "memory"); }
__device__ __forceinline__ void cluster_wait() { asm volatile("barrier.cluster.wait.acquire.aligned;" ::: "memory"); }
template <int ID, int N> __device__ __forceinline__ void nbar() { asm volatile("bar.sync %0, %1;" ::"n"(ID), "n"(N) : "memory"); }
__device__ __forceinline__ uint64_t desc64(uint32_t lo, uint32_t hi) { return (uint64_t)lo | ((uint64_t)hi << 32); }
__device__ __forceinline__ uint32_t pack_bf16(float lo, float hi) {
  uint32_t r; asm("cvt.rn.bf16x2.f32 %0, %1, %2;" : "=r"(r) : "f"(hi), "f"(lo)); return r;
}
__device__ __forceinline__ uint32_t mul_bf16x2(uint32_t a, uint32_t s, bool hi) {
  __nv_bfloat162 x = *reinterpret_cast<__nv_bfloat162*>(&a), y = *reinterpret_cast<__nv_bfloat162*>(&s);
  x = __hmul2(x, hi ? __high2bfloat162(y) : __low2bfloat162(y));
  return *reinterpret_cast<uint32_t*>(&x);
}
__device__ __forceinline__ float bf16r(float x) { return __bfloat162float(__float2bfloat16_rn(x)); }
__device__ __forceinline__ float bf_lo(uint32_t u) { return __uint_as_float(u << 16); }
__device__ __forceinline__ float bf_hi(uint32_t u) { return __uint_as_float(u & 0xFFFF0000u); }
__device__ __forceinline__ float ex2(float x) { float r; asm("ex2.approx.ftz.f32 %0, %1;" : "=f"(r) : "f"(x)); return r; }
__device__ __forceinline__ float rcp(float x) { float r; asm("rcp.approx.ftz.f32 %0, %1;" : "=f"(r) : "f"(x)); return r; }
__device__ __forceinline__ void mma_bf16(float (&d)[4], uint32_t a0, uint32_t a1, uint32_t a2, uint32_t a3, uint32_t b0, uint32_t b1) {
  asm("mma.sync.aligned.m16n8k16.row.col.f32.bf16.bf16.f32 {%0,%1,%2,%3}, {%4,%5,%6,%7}, {%8,%9}, {%0,%1,%2,%3};"
               : "+f"(d[0]), "+f"(d[1]), "+f"(d[2]), "+f"(d[3]) : "r"(a0), "r"(a1), "r"(a2), "r"(a3), "r"(b0), "r"(b1));
}
__device__ __forceinline__ void ldsm_x4(uint32_t& r0, uint32_t& r1, uint32_t& r2, uint32_t& r3, uint32_t addr) {
  asm volatile("ldmatrix.sync.aligned.m8n8.x4.shared.b16 {%0,%1,%2,%3}, [%4];"
               : "=r"(r0), "=r"(r1), "=r"(r2), "=r"(r3) : "r"(addr) : "memory");
}
__device__ __forceinline__ void ldsm_x4_t(uint32_t& r0, uint32_t& r1, uint32_t& r2, uint32_t& r3, uint32_t addr) {
  asm volatile("ldmatrix.sync.aligned.m8n8.x4.trans.shared.b16 {%0,%1,%2,%3}, [%4];"
               : "=r"(r0), "=r"(r1), "=r"(r2), "=r"(r3) : "r"(addr) : "memory");
}
__device__ __forceinline__ void stsm_x4(uint32_t addr, uint32_t r0, uint32_t r1, uint32_t r2, uint32_t r3) {
  asm volatile("stmatrix.sync.aligned.m8n8.x4.shared.b16 [%0], {%1,%2,%3,%4};"
               ::"r"(addr), "r"(r0), "r"(r1), "r"(r2), "r"(r3) : "memory");
}
__device__ __forceinline__ uint4 lds128(uint32_t addr) {
  uint4 v; asm volatile("ld.shared.v4.b32 {%0,%1,%2,%3}, [%4];" : "=r"(v.x), "=r"(v.y), "=r"(v.z), "=r"(v.w) : "r"(addr) : "memory"); return v;
}
__device__ __forceinline__ void sts128(uint32_t addr, uint4 v) {
  asm volatile("st.shared.v4.b32 [%0], {%1,%2,%3,%4};" ::"r"(addr), "r"(v.x), "r"(v.y), "r"(v.z), "r"(v.w) : "memory");
}
__device__ __forceinline__ float lds_f(uint32_t addr) {
  float v; asm volatile("ld.shared.f32 %0, [%1];" : "=f"(v) : "r"(addr) : "memory"); return v;
}
__device__ __forceinline__ uint32_t lds_vol(uint32_t addr) {
  uint32_t v; asm volatile("ld.volatile.shared.u32 %0, [%1];" : "=r"(v) : "r"(addr) : "memory"); return v;
}
__device__ __forceinline__ void nbar_dyn(int id, int n) { asm volatile("bar.sync %0, %1;" ::"r"(id), "r"(n) : "memory"); }
__device__ __forceinline__ uint64_t make_desc_ns(uint32_t addr, uint32_t lbo_bytes, uint32_t sbo_bytes) {
  return (uint64_t)((addr & 0x3FFFF) >> 4) | ((uint64_t)(lbo_bytes >> 4) << 16) | ((uint64_t)(sbo_bytes >> 4) << 32);
}
__device__ __forceinline__ void sts_f(uint32_t addr, float v) { asm volatile("st.shared.f32 [%0], %1;" ::"r"(addr), "f"(v) : "memory"); }
__device__ __forceinline__ void red_add2(float* p, float a, float b) {
  asm volatile("red.global.add.v2.f32 [%0], {%1,%2};" ::"l"(p), "f"(a), "f"(b) : "memory");
}
__device__ __forceinline__ void red_add4(float* p, float a, float b, float c, float d) {
  asm volatile("red.global.add.v4.f32 [%0], {%1,%2,%3,%4};" ::"l"(p), "f"(a), "f"(b), "f"(c), "f"(d) : "memory");
}

__device__ __forceinline__ void wgmma_n256(float (&d)[192], uint64_t da, uint64_t db, int scale_d) {
  asm volatile("{\n.reg .pred p;\nsetp.ne.b32 p, %130, 0;\n"
    "wgmma.mma_async.sync.aligned.m64n256k16.f32.bf16.bf16 {%0, %1, %2, %3, %4, %5, %6, %7, %8, %9, %10, %11, %12, %13, %14, %15, %16, %17, %18, %19, %20, %21, %22, %23, %24, %25, %26, %27, %28, %29, %30, %31, %32, %33, %34, %35, %36, %37, %38, %39, %40, %41, %42, %43, %44, %45, %46, %47, %48, %49, %50, %51, %52, %53, %54, %55, %56, %57, %58, %59, %60, %61, %62, %63, %64, %65, %66, %67, %68, %69, %70, %71, %72, %73, %74, %75, %76, %77, %78, %79, %80, %81, %82, %83, %84, %85, %86, %87, %88, %89, %90, %91, %92, %93, %94, %95, %96, %97, %98, %99, %100, %101, %102, %103, %104, %105, %106, %107, %108, %109, %110, %111, %112, %113, %114, %115, %116, %117, %118, %119, %120, %121, %122, %123, %124, %125, %126, %127}, %128, %129, p, 1, 1, 0, 1;\n}\n"
    : "+f"(d[0]), "+f"(d[1]), "+f"(d[2]), "+f"(d[3]), "+f"(d[4]), "+f"(d[5]), "+f"(d[6]), "+f"(d[7]), "+f"(d[8]), "+f"(d[9]), "+f"(d[10]), "+f"(d[11]), "+f"(d[12]), "+f"(d[13]), "+f"(d[14]), "+f"(d[15]), "+f"(d[16]), "+f"(d[17]), "+f"(d[18]), "+f"(d[19]), "+f"(d[20]), "+f"(d[21]), "+f"(d[22]), "+f"(d[23]), "+f"(d[24]), "+f"(d[25]), "+f"(d[26]), "+f"(d[27]), "+f"(d[28]), "+f"(d[29]), "+f"(d[30]), "+f"(d[31]), "+f"(d[32]), "+f"(d[33]), "+f"(d[34]), "+f"(d[35]), "+f"(d[36]), "+f"(d[37]), "+f"(d[38]), "+f"(d[39]), "+f"(d[40]), "+f"(d[41]), "+f"(d[42]), "+f"(d[43]), "+f"(d[44]), "+f"(d[45]), "+f"(d[46]), "+f"(d[47]), "+f"(d[48]), "+f"(d[49]), "+f"(d[50]), "+f"(d[51]), "+f"(d[52]), "+f"(d[53]), "+f"(d[54]), "+f"(d[55]), "+f"(d[56]), "+f"(d[57]), "+f"(d[58]), "+f"(d[59]), "+f"(d[60]), "+f"(d[61]), "+f"(d[62]), "+f"(d[63]), "+f"(d[64]), "+f"(d[65]), "+f"(d[66]), "+f"(d[67]), "+f"(d[68]), "+f"(d[69]), "+f"(d[70]), "+f"(d[71]), "+f"(d[72]), "+f"(d[73]), "+f"(d[74]), "+f"(d[75]), "+f"(d[76]), "+f"(d[77]), "+f"(d[78]), "+f"(d[79]), "+f"(d[80]), "+f"(d[81]), "+f"(d[82]), "+f"(d[83]), "+f"(d[84]), "+f"(d[85]), "+f"(d[86]), "+f"(d[87]), "+f"(d[88]), "+f"(d[89]), "+f"(d[90]), "+f"(d[91]), "+f"(d[92]), "+f"(d[93]), "+f"(d[94]), "+f"(d[95]), "+f"(d[96]), "+f"(d[97]), "+f"(d[98]), "+f"(d[99]), "+f"(d[100]), "+f"(d[101]), "+f"(d[102]), "+f"(d[103]), "+f"(d[104]), "+f"(d[105]), "+f"(d[106]), "+f"(d[107]), "+f"(d[108]), "+f"(d[109]), "+f"(d[110]), "+f"(d[111]), "+f"(d[112]), "+f"(d[113]), "+f"(d[114]), "+f"(d[115]), "+f"(d[116]), "+f"(d[117]), "+f"(d[118]), "+f"(d[119]), "+f"(d[120]), "+f"(d[121]), "+f"(d[122]), "+f"(d[123]), "+f"(d[124]), "+f"(d[125]), "+f"(d[126]), "+f"(d[127])
    : "l"(da), "l"(db), "r"(scale_d));
}
__device__ __forceinline__ void wgmma_n128(float (&d)[192], uint64_t da, uint64_t db, int scale_d) {
  asm volatile("{\n.reg .pred p;\nsetp.ne.b32 p, %66, 0;\n"
    "wgmma.mma_async.sync.aligned.m64n128k16.f32.bf16.bf16 {%0, %1, %2, %3, %4, %5, %6, %7, %8, %9, %10, %11, %12, %13, %14, %15, %16, %17, %18, %19, %20, %21, %22, %23, %24, %25, %26, %27, %28, %29, %30, %31, %32, %33, %34, %35, %36, %37, %38, %39, %40, %41, %42, %43, %44, %45, %46, %47, %48, %49, %50, %51, %52, %53, %54, %55, %56, %57, %58, %59, %60, %61, %62, %63}, %64, %65, p, 1, 1, 0, 1;\n}\n"
    : "+f"(d[128]), "+f"(d[129]), "+f"(d[130]), "+f"(d[131]), "+f"(d[132]), "+f"(d[133]), "+f"(d[134]), "+f"(d[135]), "+f"(d[136]), "+f"(d[137]), "+f"(d[138]), "+f"(d[139]), "+f"(d[140]), "+f"(d[141]), "+f"(d[142]), "+f"(d[143]), "+f"(d[144]), "+f"(d[145]), "+f"(d[146]), "+f"(d[147]), "+f"(d[148]), "+f"(d[149]), "+f"(d[150]), "+f"(d[151]), "+f"(d[152]), "+f"(d[153]), "+f"(d[154]), "+f"(d[155]), "+f"(d[156]), "+f"(d[157]), "+f"(d[158]), "+f"(d[159]), "+f"(d[160]), "+f"(d[161]), "+f"(d[162]), "+f"(d[163]), "+f"(d[164]), "+f"(d[165]), "+f"(d[166]), "+f"(d[167]), "+f"(d[168]), "+f"(d[169]), "+f"(d[170]), "+f"(d[171]), "+f"(d[172]), "+f"(d[173]), "+f"(d[174]), "+f"(d[175]), "+f"(d[176]), "+f"(d[177]), "+f"(d[178]), "+f"(d[179]), "+f"(d[180]), "+f"(d[181]), "+f"(d[182]), "+f"(d[183]), "+f"(d[184]), "+f"(d[185]), "+f"(d[186]), "+f"(d[187]), "+f"(d[188]), "+f"(d[189]), "+f"(d[190]), "+f"(d[191])
    : "l"(da), "l"(db), "r"(scale_d));
}
__device__ __forceinline__ void wgmma_n256_k(float (&d)[192], uint64_t da, uint64_t db, int scale_d) {
  asm volatile("{\n.reg .pred p;\nsetp.ne.b32 p, %130, 0;\n"
    "wgmma.mma_async.sync.aligned.m64n256k16.f32.bf16.bf16 {%0, %1, %2, %3, %4, %5, %6, %7, %8, %9, %10, %11, %12, %13, %14, %15, %16, %17, %18, %19, %20, %21, %22, %23, %24, %25, %26, %27, %28, %29, %30, %31, %32, %33, %34, %35, %36, %37, %38, %39, %40, %41, %42, %43, %44, %45, %46, %47, %48, %49, %50, %51, %52, %53, %54, %55, %56, %57, %58, %59, %60, %61, %62, %63, %64, %65, %66, %67, %68, %69, %70, %71, %72, %73, %74, %75, %76, %77, %78, %79, %80, %81, %82, %83, %84, %85, %86, %87, %88, %89, %90, %91, %92, %93, %94, %95, %96, %97, %98, %99, %100, %101, %102, %103, %104, %105, %106, %107, %108, %109, %110, %111, %112, %113, %114, %115, %116, %117, %118, %119, %120, %121, %122, %123, %124, %125, %126, %127}, %128, %129, p, 1, 1, 0, 0;\n}\n"
    : "+f"(d[0]), "+f"(d[1]), "+f"(d[2]), "+f"(d[3]), "+f"(d[4]), "+f"(d[5]), "+f"(d[6]), "+f"(d[7]), "+f"(d[8]), "+f"(d[9]), "+f"(d[10]), "+f"(d[11]), "+f"(d[12]), "+f"(d[13]), "+f"(d[14]), "+f"(d[15]), "+f"(d[16]), "+f"(d[17]), "+f"(d[18]), "+f"(d[19]), "+f"(d[20]), "+f"(d[21]), "+f"(d[22]), "+f"(d[23]), "+f"(d[24]), "+f"(d[25]), "+f"(d[26]), "+f"(d[27]), "+f"(d[28]), "+f"(d[29]), "+f"(d[30]), "+f"(d[31]), "+f"(d[32]), "+f"(d[33]), "+f"(d[34]), "+f"(d[35]), "+f"(d[36]), "+f"(d[37]), "+f"(d[38]), "+f"(d[39]), "+f"(d[40]), "+f"(d[41]), "+f"(d[42]), "+f"(d[43]), "+f"(d[44]), "+f"(d[45]), "+f"(d[46]), "+f"(d[47]), "+f"(d[48]), "+f"(d[49]), "+f"(d[50]), "+f"(d[51]), "+f"(d[52]), "+f"(d[53]), "+f"(d[54]), "+f"(d[55]), "+f"(d[56]), "+f"(d[57]), "+f"(d[58]), "+f"(d[59]), "+f"(d[60]), "+f"(d[61]), "+f"(d[62]), "+f"(d[63]), "+f"(d[64]), "+f"(d[65]), "+f"(d[66]), "+f"(d[67]), "+f"(d[68]), "+f"(d[69]), "+f"(d[70]), "+f"(d[71]), "+f"(d[72]), "+f"(d[73]), "+f"(d[74]), "+f"(d[75]), "+f"(d[76]), "+f"(d[77]), "+f"(d[78]), "+f"(d[79]), "+f"(d[80]), "+f"(d[81]), "+f"(d[82]), "+f"(d[83]), "+f"(d[84]), "+f"(d[85]), "+f"(d[86]), "+f"(d[87]), "+f"(d[88]), "+f"(d[89]), "+f"(d[90]), "+f"(d[91]), "+f"(d[92]), "+f"(d[93]), "+f"(d[94]), "+f"(d[95]), "+f"(d[96]), "+f"(d[97]), "+f"(d[98]), "+f"(d[99]), "+f"(d[100]), "+f"(d[101]), "+f"(d[102]), "+f"(d[103]), "+f"(d[104]), "+f"(d[105]), "+f"(d[106]), "+f"(d[107]), "+f"(d[108]), "+f"(d[109]), "+f"(d[110]), "+f"(d[111]), "+f"(d[112]), "+f"(d[113]), "+f"(d[114]), "+f"(d[115]), "+f"(d[116]), "+f"(d[117]), "+f"(d[118]), "+f"(d[119]), "+f"(d[120]), "+f"(d[121]), "+f"(d[122]), "+f"(d[123]), "+f"(d[124]), "+f"(d[125]), "+f"(d[126]), "+f"(d[127])
    : "l"(da), "l"(db), "r"(scale_d));
}
__device__ __forceinline__ void wgmma_n128_k(float (&d)[192], uint64_t da, uint64_t db, int scale_d) {
  asm volatile("{\n.reg .pred p;\nsetp.ne.b32 p, %66, 0;\n"
    "wgmma.mma_async.sync.aligned.m64n128k16.f32.bf16.bf16 {%0, %1, %2, %3, %4, %5, %6, %7, %8, %9, %10, %11, %12, %13, %14, %15, %16, %17, %18, %19, %20, %21, %22, %23, %24, %25, %26, %27, %28, %29, %30, %31, %32, %33, %34, %35, %36, %37, %38, %39, %40, %41, %42, %43, %44, %45, %46, %47, %48, %49, %50, %51, %52, %53, %54, %55, %56, %57, %58, %59, %60, %61, %62, %63}, %64, %65, p, 1, 1, 0, 0;\n}\n"
    : "+f"(d[128]), "+f"(d[129]), "+f"(d[130]), "+f"(d[131]), "+f"(d[132]), "+f"(d[133]), "+f"(d[134]), "+f"(d[135]), "+f"(d[136]), "+f"(d[137]), "+f"(d[138]), "+f"(d[139]), "+f"(d[140]), "+f"(d[141]), "+f"(d[142]), "+f"(d[143]), "+f"(d[144]), "+f"(d[145]), "+f"(d[146]), "+f"(d[147]), "+f"(d[148]), "+f"(d[149]), "+f"(d[150]), "+f"(d[151]), "+f"(d[152]), "+f"(d[153]), "+f"(d[154]), "+f"(d[155]), "+f"(d[156]), "+f"(d[157]), "+f"(d[158]), "+f"(d[159]), "+f"(d[160]), "+f"(d[161]), "+f"(d[162]), "+f"(d[163]), "+f"(d[164]), "+f"(d[165]), "+f"(d[166]), "+f"(d[167]), "+f"(d[168]), "+f"(d[169]), "+f"(d[170]), "+f"(d[171]), "+f"(d[172]), "+f"(d[173]), "+f"(d[174]), "+f"(d[175]), "+f"(d[176]), "+f"(d[177]), "+f"(d[178]), "+f"(d[179]), "+f"(d[180]), "+f"(d[181]), "+f"(d[182]), "+f"(d[183]), "+f"(d[184]), "+f"(d[185]), "+f"(d[186]), "+f"(d[187]), "+f"(d[188]), "+f"(d[189]), "+f"(d[190]), "+f"(d[191])
    : "l"(da), "l"(db), "r"(scale_d));
}
__device__ __forceinline__ void wgmma_n40_tt(float (&d)[20], uint64_t da, uint64_t db, int scale_d) {
  asm volatile("{\n.reg .pred p;\nsetp.ne.b32 p, %22, 0;\n"
    "wgmma.mma_async.sync.aligned.m64n40k16.f32.bf16.bf16 {%0, %1, %2, %3, %4, %5, %6, %7, %8, %9, %10, %11, %12, %13, %14, %15, %16, %17, %18, %19}, %20, %21, p, 1, 1, 1, 1;\n}\n"
    : "+f"(d[0]), "+f"(d[1]), "+f"(d[2]), "+f"(d[3]), "+f"(d[4]), "+f"(d[5]), "+f"(d[6]), "+f"(d[7]), "+f"(d[8]), "+f"(d[9]), "+f"(d[10]), "+f"(d[11]), "+f"(d[12]), "+f"(d[13]), "+f"(d[14]), "+f"(d[15]), "+f"(d[16]), "+f"(d[17]), "+f"(d[18]), "+f"(d[19])
    : "l"(da), "l"(db), "r"(scale_d));
}
__device__ __forceinline__ void wgmma_n40_rs(float (&d)[20], const uint32_t (&a)[4], uint64_t db, int scale_d) {
  asm volatile("{\n.reg .pred p;\nsetp.ne.b32 p, %25, 0;\n"
    "wgmma.mma_async.sync.aligned.m64n40k16.f32.bf16.bf16 {%0, %1, %2, %3, %4, %5, %6, %7, %8, %9, %10, %11, %12, %13, %14, %15, %16, %17, %18, %19}, {%20, %21, %22, %23}, %24, p, 1, 1, 1;\n}\n"
    : "+f"(d[0]), "+f"(d[1]), "+f"(d[2]), "+f"(d[3]), "+f"(d[4]), "+f"(d[5]), "+f"(d[6]), "+f"(d[7]), "+f"(d[8]), "+f"(d[9]), "+f"(d[10]), "+f"(d[11]), "+f"(d[12]), "+f"(d[13]), "+f"(d[14]), "+f"(d[15]), "+f"(d[16]), "+f"(d[17]), "+f"(d[18]), "+f"(d[19])
    : "r"(a[0]), "r"(a[1]), "r"(a[2]), "r"(a[3]), "l"(db), "r"(scale_d));
}
__device__ __forceinline__ void wgmma_n256_0(float (&d)[192], uint64_t da, uint64_t db) {
  asm volatile("{\n.reg .pred p;\nsetp.ne.b32 p, 0, 0;\n"
    "wgmma.mma_async.sync.aligned.m64n256k16.f32.bf16.bf16 {%0, %1, %2, %3, %4, %5, %6, %7, %8, %9, %10, %11, %12, %13, %14, %15, %16, %17, %18, %19, %20, %21, %22, %23, %24, %25, %26, %27, %28, %29, %30, %31, %32, %33, %34, %35, %36, %37, %38, %39, %40, %41, %42, %43, %44, %45, %46, %47, %48, %49, %50, %51, %52, %53, %54, %55, %56, %57, %58, %59, %60, %61, %62, %63, %64, %65, %66, %67, %68, %69, %70, %71, %72, %73, %74, %75, %76, %77, %78, %79, %80, %81, %82, %83, %84, %85, %86, %87, %88, %89, %90, %91, %92, %93, %94, %95, %96, %97, %98, %99, %100, %101, %102, %103, %104, %105, %106, %107, %108, %109, %110, %111, %112, %113, %114, %115, %116, %117, %118, %119, %120, %121, %122, %123, %124, %125, %126, %127}, %128, %129, p, 1, 1, 0, 1;\n}\n"
    : "=f"(d[0]), "=f"(d[1]), "=f"(d[2]), "=f"(d[3]), "=f"(d[4]), "=f"(d[5]), "=f"(d[6]), "=f"(d[7]), "=f"(d[8]), "=f"(d[9]), "=f"(d[10]), "=f"(d[11]), "=f"(d[12]), "=f"(d[13]), "=f"(d[14]), "=f"(d[15]), "=f"(d[16]), "=f"(d[17]), "=f"(d[18]), "=f"(d[19]), "=f"(d[20]), "=f"(d[21]), "=f"(d[22]), "=f"(d[23]), "=f"(d[24]), "=f"(d[25]), "=f"(d[26]), "=f"(d[27]), "=f"(d[28]), "=f"(d[29]), "=f"(d[30]), "=f"(d[31]), "=f"(d[32]), "=f"(d[33]), "=f"(d[34]), "=f"(d[35]), "=f"(d[36]), "=f"(d[37]), "=f"(d[38]), "=f"(d[39]), "=f"(d[40]), "=f"(d[41]), "=f"(d[42]), "=f"(d[43]), "=f"(d[44]), "=f"(d[45]), "=f"(d[46]), "=f"(d[47]), "=f"(d[48]), "=f"(d[49]), "=f"(d[50]), "=f"(d[51]), "=f"(d[52]), "=f"(d[53]), "=f"(d[54]), "=f"(d[55]), "=f"(d[56]), "=f"(d[57]), "=f"(d[58]), "=f"(d[59]), "=f"(d[60]), "=f"(d[61]), "=f"(d[62]), "=f"(d[63]), "=f"(d[64]), "=f"(d[65]), "=f"(d[66]), "=f"(d[67]), "=f"(d[68]), "=f"(d[69]), "=f"(d[70]), "=f"(d[71]), "=f"(d[72]), "=f"(d[73]), "=f"(d[74]), "=f"(d[75]), "=f"(d[76]), "=f"(d[77]), "=f"(d[78]), "=f"(d[79]), "=f"(d[80]), "=f"(d[81]), "=f"(d[82]), "=f"(d[83]), "=f"(d[84]), "=f"(d[85]), "=f"(d[86]), "=f"(d[87]), "=f"(d[88]), "=f"(d[89]), "=f"(d[90]), "=f"(d[91]), "=f"(d[92]), "=f"(d[93]), "=f"(d[94]), "=f"(d[95]), "=f"(d[96]), "=f"(d[97]), "=f"(d[98]), "=f"(d[99]), "=f"(d[100]), "=f"(d[101]), "=f"(d[102]), "=f"(d[103]), "=f"(d[104]), "=f"(d[105]), "=f"(d[106]), "=f"(d[107]), "=f"(d[108]), "=f"(d[109]), "=f"(d[110]), "=f"(d[111]), "=f"(d[112]), "=f"(d[113]), "=f"(d[114]), "=f"(d[115]), "=f"(d[116]), "=f"(d[117]), "=f"(d[118]), "=f"(d[119]), "=f"(d[120]), "=f"(d[121]), "=f"(d[122]), "=f"(d[123]), "=f"(d[124]), "=f"(d[125]), "=f"(d[126]), "=f"(d[127])
    : "l"(da), "l"(db));
}
__device__ __forceinline__ void wgmma_n128_0(float (&d)[192], uint64_t da, uint64_t db) {
  asm volatile("{\n.reg .pred p;\nsetp.ne.b32 p, 0, 0;\n"
    "wgmma.mma_async.sync.aligned.m64n128k16.f32.bf16.bf16 {%0, %1, %2, %3, %4, %5, %6, %7, %8, %9, %10, %11, %12, %13, %14, %15, %16, %17, %18, %19, %20, %21, %22, %23, %24, %25, %26, %27, %28, %29, %30, %31, %32, %33, %34, %35, %36, %37, %38, %39, %40, %41, %42, %43, %44, %45, %46, %47, %48, %49, %50, %51, %52, %53, %54, %55, %56, %57, %58, %59, %60, %61, %62, %63}, %64, %65, p, 1, 1, 0, 1;\n}\n"
    : "=f"(d[128]), "=f"(d[129]), "=f"(d[130]), "=f"(d[131]), "=f"(d[132]), "=f"(d[133]), "=f"(d[134]), "=f"(d[135]), "=f"(d[136]), "=f"(d[137]), "=f"(d[138]), "=f"(d[139]), "=f"(d[140]), "=f"(d[141]), "=f"(d[142]), "=f"(d[143]), "=f"(d[144]), "=f"(d[145]), "=f"(d[146]), "=f"(d[147]), "=f"(d[148]), "=f"(d[149]), "=f"(d[150]), "=f"(d[151]), "=f"(d[152]), "=f"(d[153]), "=f"(d[154]), "=f"(d[155]), "=f"(d[156]), "=f"(d[157]), "=f"(d[158]), "=f"(d[159]), "=f"(d[160]), "=f"(d[161]), "=f"(d[162]), "=f"(d[163]), "=f"(d[164]), "=f"(d[165]), "=f"(d[166]), "=f"(d[167]), "=f"(d[168]), "=f"(d[169]), "=f"(d[170]), "=f"(d[171]), "=f"(d[172]), "=f"(d[173]), "=f"(d[174]), "=f"(d[175]), "=f"(d[176]), "=f"(d[177]), "=f"(d[178]), "=f"(d[179]), "=f"(d[180]), "=f"(d[181]), "=f"(d[182]), "=f"(d[183]), "=f"(d[184]), "=f"(d[185]), "=f"(d[186]), "=f"(d[187]), "=f"(d[188]), "=f"(d[189]), "=f"(d[190]), "=f"(d[191])
    : "l"(da), "l"(db));
}
__device__ __forceinline__ void wgmma_n128_rs(float (&d)[192], const uint32_t (&a)[4], uint64_t db, int scale_d) {
  asm volatile("{\n.reg .pred p;\nsetp.ne.b32 p, %69, 0;\n"
    "wgmma.mma_async.sync.aligned.m64n128k16.f32.bf16.bf16 {%0, %1, %2, %3, %4, %5, %6, %7, %8, %9, %10, %11, %12, %13, %14, %15, %16, %17, %18, %19, %20, %21, %22, %23, %24, %25, %26, %27, %28, %29, %30, %31, %32, %33, %34, %35, %36, %37, %38, %39, %40, %41, %42, %43, %44, %45, %46, %47, %48, %49, %50, %51, %52, %53, %54, %55, %56, %57, %58, %59, %60, %61, %62, %63}, {%64, %65, %66, %67}, %68, p, 1, 1, 1;\n}\n"
    : "+f"(d[128]), "+f"(d[129]), "+f"(d[130]), "+f"(d[131]), "+f"(d[132]), "+f"(d[133]), "+f"(d[134]), "+f"(d[135]), "+f"(d[136]), "+f"(d[137]), "+f"(d[138]), "+f"(d[139]), "+f"(d[140]), "+f"(d[141]), "+f"(d[142]), "+f"(d[143]), "+f"(d[144]), "+f"(d[145]), "+f"(d[146]), "+f"(d[147]), "+f"(d[148]), "+f"(d[149]), "+f"(d[150]), "+f"(d[151]), "+f"(d[152]), "+f"(d[153]), "+f"(d[154]), "+f"(d[155]), "+f"(d[156]), "+f"(d[157]), "+f"(d[158]), "+f"(d[159]), "+f"(d[160]), "+f"(d[161]), "+f"(d[162]), "+f"(d[163]), "+f"(d[164]), "+f"(d[165]), "+f"(d[166]), "+f"(d[167]), "+f"(d[168]), "+f"(d[169]), "+f"(d[170]), "+f"(d[171]), "+f"(d[172]), "+f"(d[173]), "+f"(d[174]), "+f"(d[175]), "+f"(d[176]), "+f"(d[177]), "+f"(d[178]), "+f"(d[179]), "+f"(d[180]), "+f"(d[181]), "+f"(d[182]), "+f"(d[183]), "+f"(d[184]), "+f"(d[185]), "+f"(d[186]), "+f"(d[187]), "+f"(d[188]), "+f"(d[189]), "+f"(d[190]), "+f"(d[191])
    : "r"(a[0]), "r"(a[1]), "r"(a[2]), "r"(a[3]), "l"(db), "r"(scale_d));
}

constexpr int SLOT = 16384;
constexpr int KVT = 10240;
constexpr uint32_t QA = 0x0BAu, QK = 0x462u, QQ = 0x981u;
constexpr int SM_SD = 12 * SLOT;
constexpr int SM_BAR = SM_SD + 8192;
constexpr int SM_RS = SM_BAR + 512;
constexpr int SM_AP = SM_RS + 768;
constexpr int SM_BP = SM_AP + 2048;
constexpr int SM_WPHI = SM_BP + 12288;
constexpr int SM_EPOCH = SM_WPHI + 10240;
constexpr int SM_TOTAL = SM_EPOCH + 16 + 1024;
constexpr int B_FULLS = 0, B_XOLD = 24, B_STAT = 32, B_EMPTYS = 40, B_FULLT = 256  , B_CONS = 384  , B_E3 = 472, B_E0 = 480, B_E1 = 488, B_E2 = 496, B_EPI = 504, B_CS = 160,
              B_KVDONE = 168  , B_ODONE = 176, B_XDONE = 184, B_OH1 = B_CONS, B_CS2 = 208, B_XH0 = 232, B_R0 = 240, B_CB = 144  , B_XOLD2 = 216;
constexpr uint64_t BAR_CNT = 0x1c07fc0eac00a800ull;
constexpr uint64_t WO_A0 = 0xa461b57648357643ull, WO_B0 = 0x59083a9021ba9021ull, WO_A1 = 0xa0b76901276a5babull, WO_B1 = 0x95428a5b34890132ull;
constexpr uint64_t WO_DA0 = 0xa9865432ff00dd00ull, WO_DB0 = 0xa986543211bbccccull, WO_DA1 = 0xa98654321ffff000ull, WO_DB1 = 0xa98754321bbcccddull;
#define WOORD 0xFDB9753ECA864210ull
constexpr int NX = 4;
constexpr int XS = 10;

#define PL 2
#define PROFX(i) PROFT(tid_ == 128 && layer == PL, 200 + (i))
#define NCOM 3
#define PFS 8
#define KVTH 0x41700000u
#define XPF 3
#define XPM 2
#define TLINE 1
#define NLAYERS 4
constexpr float L2E = 1.4426950408889634f;
#define PHI_MAX 2147483648.f

#define D128(lo) desc64(lo, 0x40000040u)
struct Ctx { uint32_t sb; int g, rb, cu; bf16* out; };

__device__ __forceinline__ void colsum(const CUtensorMap* tm, float* cs, int rb, int g, int w0, int dw, int lane, uint32_t stg, uint32_t cb, uint32_t par) {
  const uint32_t src = stg + (lane >> 3) * 2048;
#pragma unroll 1
  for (int wi = w0 - dw; wi < 6; wi += dw) {
    float s[8] = {0.f, 0.f, 0.f, 0.f, 0.f, 0.f, 0.f, 0.f};
    if (wi >= 0) {
      mbar_wait_u(cb, par);
      par ^= 1;
#pragma unroll 4
      for (int r = 0; r < 16; ++r) {
        const uint4 v = lds128(src + r * 128 + (((lane ^ r) & 7) << 4));
        s[0] += bf_lo(v.x); s[1] += bf_hi(v.x); s[2] += bf_lo(v.y); s[3] += bf_hi(v.y);
        s[4] += bf_lo(v.z); s[5] += bf_hi(v.z); s[6] += bf_lo(v.w); s[7] += bf_hi(v.w);
      }
#pragma unroll
      for (int i = 0; i < 8; ++i) s[i] += __shfl_xor_sync(0xffffffffu, s[i], 8);
    }
    const int wn = wi + dw;
    if (wn < 6) {
      expect_tx_e(cb, 8192);
      tma_2d_e(stg, tm, (wn >= 4 ? 0 : 1024 + (wn >> 1) * 1024) + g * 128 + (wn & 1) * 64, rb * 64, cb);
    }
    if (wi >= 0) {
#pragma unroll
      for (int i = 0; i < 8; ++i) s[i] += __shfl_xor_sync(0xffffffffu, s[i], 16);
      if (lane < 8) {
        red_add4(cs + g * 384 + (wi * 8 + lane) * 8, s[0], s[1], s[2], s[3]);
        red_add4(cs + g * 384 + (wi * 8 + lane) * 8 + 4, s[4], s[5], s[6], s[7]);
      }
      __syncwarp();
    }
  }
}
#define PHASE_CTX() \
  uint32_t sb = c.sb; asm volatile("" : "+r"(sb)); \
  int tid_ = threadIdx.x; asm volatile("" : "+r"(tid_)); \
  const uint32_t bar = sb + SM_BAR; \
  const int lane = tid_ & 31, cw = (tid_ >> 5) - 4, wg = cw >> 2, wq = cw & 3, gq = lane >> 2, t = lane & 3, wrow0 = cw * 16; \
  const int lrow = (lane & 7) + ((lane >> 3) & 1) * 8, lchk = lane >> 4; \
  const bool elected = (tid_ & 127) == 0; \
  const uint32_t rowo = (wrow0 + lrow) * 128, X = (lchk ^ (lane & 7)) << 4; \
  (void)bar; (void)wq; (void)gq; (void)lrow; (void)lchk; (void)elected; (void)wrow0; (void)wg; (void)rowo; (void)X; (void)t;

__device__ __forceinline__ void slab_out_half(uint32_t slot, bf16* dst, int wrow0, int lane, bool FENCE = false) {
  const int r0 = lane >> 3, ch = lane & 7;
  const uint32_t src = slot + (wrow0 + r0) * 128;
  uint4 v[4];
#pragma unroll
  for (int i = 0; i < 4; ++i) v[i] = lds128(src + i * 512 + (((ch ^ (4 * i + r0)) & 7) << 4));
  if (FENCE) fence_async_smem();
  dst += (size_t)(wrow0 + r0) * D_ + ch * 8;
#pragma unroll
  for (int i = 0; i < 4; ++i)
    asm volatile("st.global.v4.u32 [%0], {%1,%2,%3,%4};" ::"l"(dst + (size_t)i * 4 * D_), "r"(v[i].x), "r"(v[i].y), "r"(v[i].z), "r"(v[i].w) : "memory");
}

struct Tag { uint32_t me, mo, tg; };
__device__ __forceinline__ Tag make_tag(int gq, int t, uint32_t tg) { return Tag{t == 0, t == 1, tg}; }
__device__ __forceinline__ void stsm_tag(uint32_t addr, uint32_t r0, uint32_t r1, uint32_t r2, uint32_t r3, const Tag& k, int jp) {
  if (jp == 0) stsm_x4(addr, (r0 & ~k.me) | (k.tg & k.me), (r1 & ~k.mo) | (k.tg & k.mo), r2, r3);
  else stsm_x4(addr, r0, r1, r2, r3);
}
#define TILE_BAD() ((lds_vol(va) ^ tg) & 1)
#define TILE_VA() (slot + (wrow0 + (lane & 15)) * 128 + (lane & 7) * 16 + ((lane >> 3) & 1) * 4)
__device__ __forceinline__ void tile_check(uint32_t slot, const bf16* src, int wrow0, int lane, uint32_t tg) {
  const uint32_t va = TILE_VA();
  if (__builtin_expect(__any_sync(0xffffffffu, TILE_BAD()), 0)) {
    const int r0 = lane >> 3, ch = lane & 7;
    uint32_t n = 0;
#pragma unroll 1
    do {
      uint4 v[4];
#pragma unroll
      for (int i = 0; i < 4; ++i) v[i] = ld_relaxed4(reinterpret_cast<const uint4*>(src + (size_t)(wrow0 + r0 + 4 * i) * D_ + ch * 8));
#pragma unroll
      for (int i = 0; i < 4; ++i) sts128(slot + (wrow0 + r0 + 4 * i) * 128 + (((ch ^ (4 * i + r0)) & 7) << 4), v[i]);
      __syncwarp();
      if (++n > (1u << 16)) { g_err = 8u; break; }
    } while (__any_sync(0xffffffffu, TILE_BAD()));
    fence_async_smem();
    __syncwarp();
  }
}

template <int O>
__device__ __forceinline__ void phi_proj(float (&p)[2][4][4], const uint32_t (&kq)[64], uint32_t wa) {
#pragma unroll
  for (int h = 0; h < 2; ++h)
#pragma unroll
    for (int i = 0; i < 4; ++i) { p[h][i][0] = p[h][i][1] = p[h][i][2] = p[h][i][3] = 0.f; }
#pragma unroll
  for (int ks = 0; ks < 2; ++ks)
#pragma unroll
    for (int np = 0; np < 2; ++np)
#pragma unroll
      for (int h = 0; h < 2; ++h) {
        uint32_t b0, b1, b2, b3;
        ldsm_x4_t(b0, b1, b2, b3, wa + h * 2560 + ks * 1280 + np * 32);
        mma_bf16(p[h][2 * np], kq[O + 8 * h + 4 * ks], kq[O + 8 * h + 4 * ks + 1], kq[O + 8 * h + 4 * ks + 2], kq[O + 8 * h + 4 * ks + 3], b0, b1);
        mma_bf16(p[h][2 * np + 1], kq[O + 8 * h + 4 * ks], kq[O + 8 * h + 4 * ks + 1], kq[O + 8 * h + 4 * ks + 2], kq[O + 8 * h + 4 * ks + 3], b2, b3);
      }
}
__device__ __forceinline__ void phi_exp(uint32_t (&raw)[4][4], const float (&p)[4][4], float sc0, float sc1) {
#pragma unroll
  for (int i = 0; i < 4; ++i) {
    const float e0 = ex2(p[i][0] * sc0), e1 = ex2(p[i][1] * sc0), e2 = ex2(p[i][2] * sc1), e3 = ex2(p[i][3] * sc1);
    const float m0 = e0 * e1, m1 = e2 * e3, rr = rcp(m0 * m1), r0 = rr * m1, r1 = rr * m0;
    raw[i >> 1][(i & 1) * 2] = pack_bf16(e0, e1);
    raw[i >> 1][(i & 1) * 2 + 1] = pack_bf16(e2, e3);
    raw[2 + (i >> 1)][(i & 1) * 2] = pack_bf16(e1 * r0, e0 * r0);
    raw[2 + (i >> 1)][(i & 1) * 2 + 1] = pack_bf16(e3 * r1, e2 * r1);
  }
}
template <int O>
__device__ __forceinline__ void phi_norm(uint32_t (&ph)[2][4][4], const uint32_t (&raw)[2][4][4], const uint32_t (&kq)[64], uint32_t wa,
                                         float sc0, float sc1, float mul0, float mul1) {
  bool bad = false;
#pragma unroll
  for (int h = 0; h < 2; ++h)
#pragma unroll
    for (int sg = 0; sg < 2; ++sg) {
      float ss[4] = {0.f, 0.f, 0.f, 0.f};
#pragma unroll
      for (int ks = 0; ks < 2; ++ks)
        mma_bf16(ss, raw[h][2 * sg + ks][0], raw[h][2 * sg + ks][1], raw[h][2 * sg + ks][2], raw[h][2 * sg + ks][3], 0x3F803F80u, 0x3F803F80u);
      bad = bad || !(ss[0] < PHI_MAX) || !(ss[2] < PHI_MAX);
      const uint32_t iv = pack_bf16(rcp(ss[0]) * mul0, rcp(ss[2]) * mul1);
#pragma unroll
      for (int ks = 0; ks < 2; ++ks)
#pragma unroll
        for (int j = 0; j < 4; ++j) ph[h][2 * sg + ks][j] = mul_bf16x2(raw[h][2 * sg + ks][j], iv, j & 1);
    }
  if (__builtin_expect(__any_sync(0xffffffffu, bad), 0)) {
#pragma unroll 1
    for (int it = 0; it < 4; ++it) {
      float q[4][4];
#pragma unroll
      for (int i = 0; i < 4; ++i) { q[i][0] = q[i][1] = q[i][2] = q[i][3] = 0.f; }
#pragma unroll
      for (int ks = 0; ks < 2; ++ks) {
        uint32_t a[4];
#pragma unroll
        for (int j = 0; j < 4; ++j) a[j] = (it & 2) ? kq[O + 8 + 4 * ks + j] : kq[O + 4 * ks + j];
#pragma unroll
        for (int np = 0; np < 2; ++np) {
          uint32_t b0, b1, b2, b3;
          ldsm_x4_t(b0, b1, b2, b3, wa + (it >> 1) * 2560 + ks * 1280 + np * 32);
          mma_bf16(q[2 * np], a[0], a[1], a[2], a[3], b0, b1);
          mma_bf16(q[2 * np + 1], a[0], a[1], a[2], a[3], b2, b3);
        }
      }
      float iv[2];
#pragma unroll
      for (int r = 0; r < 2; ++r) {
        const float sc = (it & 1) ? -(r ? sc1 : sc0) : (r ? sc1 : sc0);
        float mx = -INFINITY, sm = 0.f;
#pragma unroll
        for (int i = 0; i < 8; ++i) { float& v = q[i >> 1][2 * r + (i & 1)]; v *= sc; mx = fmaxf(mx, v); }
        mx = fmaxf(mx, __shfl_xor_sync(0xffffffffu, mx, 1));
        mx = fmaxf(mx, __shfl_xor_sync(0xffffffffu, mx, 2));
#pragma unroll
        for (int i = 0; i < 8; ++i) { float& v = q[i >> 1][2 * r + (i & 1)]; v = ex2(v - mx); sm += v; }
        sm += __shfl_xor_sync(0xffffffffu, sm, 1);
        sm += __shfl_xor_sync(0xffffffffu, sm, 2);
        iv[r] = rcp(sm) * (r ? mul1 : mul0);
      }
#pragma unroll
      for (int i = 0; i < 24; ++i) ph[i >> 4][(i >> 2) & 3][i & 3] = ph[(i + 8) >> 4][((i + 8) >> 2) & 3][i & 3];
#pragma unroll
      for (int i = 0; i < 4; ++i) {
        ph[1][2 + (i >> 1)][(i & 1) * 2] = pack_bf16(q[i][0] * iv[0], q[i][1] * iv[0]);
        ph[1][2 + (i >> 1)][(i & 1) * 2 + 1] = pack_bf16(q[i][2] * iv[1], q[i][3] * iv[1]);
      }
    }
  }
}

__device__ __forceinline__ void stats_out(float s0, float s1, float q0, float q1, float2* dst, int t) {
  const bool od = t & 1;
  float sa = od ? s1 : s0, qa = od ? q1 : q0;
  sa += __shfl_xor_sync(0xffffffffu, od ? s0 : s1, 1);
  qa += __shfl_xor_sync(0xffffffffu, od ? q0 : q1, 1);
  sa += __shfl_xor_sync(0xffffffffu, sa, 2);
  qa += __shfl_xor_sync(0xffffffffu, qa, 2);
  if (t < 2) red_add2(&dst[t * 8].x, sa, qa);
}

__device__ __forceinline__ void consumer(const Ctx& c) {
  const int g = c.g, m0 = c.rb * 128;
  float acc[192];
#define X_HALF(hf, TG) \
      _Pragma("unroll") for (int jp = 4 * (hf); jp < 4 * (hf) + 4; ++jp) \
        stsm_tag(sb + (XS + (hf)) * SLOT + rowo + (X ^ ((jp & 3) << 5)), \
                 pack_bf16(acc[128 + 8 * jp], acc[129 + 8 * jp]), pack_bf16(acc[130 + 8 * jp], acc[131 + 8 * jp]), \
                 pack_bf16(acc[132 + 8 * jp], acc[133 + 8 * jp]), pack_bf16(acc[134 + 8 * jp], acc[135 + 8 * jp]), TG, jp & 3);
#pragma unroll
  for (int i = 128; i < 192; ++i) acc[i] = 0.f;
#pragma unroll 1
  for (int layer = 0;; ++layer) {
    {
      PHASE_CTX();
      const uint32_t wu = c.cu >> 2;
      const uint32_t dA0 = (((sb + wu * 8192) & 0x3FFFF) >> 4) | (1u << 16), dB0 = ((sb & 0x3FFFF) >> 4) | (512u << 16);
      {
        PROFX(0);
        mbar_wait(bar + B_FULLS, 0);
        PROFX(1);
        wgmma_fence();
        wgmma_n256_0(acc, D128(dA0 + XS * 1024), D128(dB0 + 2048));
#pragma unroll
        for (int k = 1; k < 4; ++k) wgmma_n256(acc, D128(dA0 + XS * 1024 + k * 2), D128(dB0 + 2048 + k * 128), 1);
        wgmma_commit();
        wgmma_wait<1>();
        float s0 = 0.f, s1 = 0.f, q0 = 0.f, q1 = 0.f;
        if (layer) {
          X_HALF(1, (Tag{0u, 0u, 0u}));
#pragma unroll
          for (int i = 128; i < 192; i += 4) {
            s0 += acc[i] + acc[i + 1]; s1 += acc[i + 2] + acc[i + 3];
            q0 = fmaf(acc[i], acc[i], fmaf(acc[i + 1], acc[i + 1], q0)); q1 = fmaf(acc[i + 2], acc[i + 2], fmaf(acc[i + 3], acc[i + 3], q1));
          }
        }
        asm volatile("" : "+f"(s0), "+f"(s1), "+f"(q0), "+f"(q1) :: "memory");
        wgmma_fence();
        wgmma_n128_0(acc, D128(dA0 + XS * 1024), D128(dB0 + 1024));
#pragma unroll
        for (int k = 1; k < 4; ++k) wgmma_n128(acc, D128(dA0 + XS * 1024 + k * 2), D128(dB0 + 1024 + k * 128), 1);
        wgmma_commit();
        if (layer) {
          PHASE_CTX();
          fence_async_smem();
          nbar_dyn(3 + wu, 128);
          stats_out(s0, s1, q0, q1, g_stats + layer * S_ + m0 + wrow0 + gq, t);
          PROFT(tid_ == 128, layer * 16 + 8);
        }
      }
      uint32_t s = 1, u = 0, sp = 0;
      const int ix = layer ? 99 : 2 * min(g, NCOM) + 1;
#pragma unroll 1
      for (int i = 1; i < 14; ++i) {
        mbar_wait(bar + B_FULLS + s * 8, (u + (s ? layer : 0)) & 1);
        if (layer && (unsigned)(i - 2) < 7u) {
          PHASE_CTX();
          tile_check(sb + ((QA >> (4 * s)) & 15) * SLOT, g_x + (size_t)m0 * D_ + ((2 * g + 2 * i - 2) & 15) * 64, wrow0, lane, lds_vol(sb + SM_EPOCH) + layer);
        }
        const uint32_t da = dA0 + ((QA >> (4 * s)) & 15) * 1024, dk = dB0 + ((QK >> (4 * s)) & 15) * 1024,
                       dq = dB0 + ((QQ >> (4 * s)) & 15) * 1024;
        wgmma_fence();
#pragma unroll
        for (int k = 0; k < 4; ++k) {
          wgmma_n256(acc, D128(da + k * 2), D128(dk + k * 128), 1);
          wgmma_n128(acc, D128(da + k * 2), D128(dq + k * 128), 1);
          if (k == 0) {
            wgmma_commit();
            wgmma_wait<1>();
            if (elected && (unsigned)(i - ix) >= 2u) release2(bar + B_EMPTYS + sp * 8);
          }
        }
        wgmma_commit();
        if ((unsigned)(i - ix) < 2u) {
          PHASE_CTX();
          {
            float s0 = 0.f, s1 = 0.f, q0 = 0.f, q1 = 0.f;
            const uint32_t xa = sb + ((QA >> (4 * sp)) & 15) * SLOT + rowo;
#pragma unroll
            for (int jp = 0; jp < 4; ++jp) {
              uint32_t x0, x1, x2, x3;
              ldsm_x4(x0, x1, x2, x3, xa + (X ^ (jp << 5)));
              s0 += (bf_lo(x0) + bf_hi(x0)) + (bf_lo(x2) + bf_hi(x2));
              s1 += (bf_lo(x1) + bf_hi(x1)) + (bf_lo(x3) + bf_hi(x3));
              q0 = fmaf(bf_lo(x0), bf_lo(x0), fmaf(bf_hi(x0), bf_hi(x0), fmaf(bf_lo(x2), bf_lo(x2), fmaf(bf_hi(x2), bf_hi(x2), q0))));
              q1 = fmaf(bf_lo(x1), bf_lo(x1), fmaf(bf_hi(x1), bf_hi(x1), fmaf(bf_lo(x3), bf_lo(x3), fmaf(bf_hi(x3), bf_hi(x3), q1))));
            }
            stats_out(s0, s1, q0, q1, g_stats + m0 + wrow0 + gq, t);
          }
          __syncwarp();
          if (lane == 0 && i != ix) mbar_arrive(bar + B_XDONE);
          nbar_dyn(3 + wu, 128);
          if (elected) release2(bar + B_EMPTYS + sp * 8);
        }
        if (i == 1 && layer) {
          PHASE_CTX();
          slab_out_half(sb + (XS + 1) * SLOT, g_x + (size_t)m0 * D_ + g * 128 + 64, wrow0, lane);
          __syncwarp();
          if (lane == 0) mbar_arrive(bar + B_XDONE);
          nbar_dyn(3 + wu, 128);
        }
        sp = s;
        if (++s == 3) { s = 0; ++u; }
      }
      {
        const uint64_t dap = make_desc_ns(sb + SM_AP + wu * 1024, 0, 128), dbp = make_desc_ns(sb + SM_BP + (layer & 1) * 6144, 0, 128);
        if (wu == 0) {
          wgmma_wait<0>();
          if (elected) mbar_arrive(bar + B_R0);
          nbar<6, 256>();
        }
        if (layer < 2) mbar_wait(bar + (layer ? B_CS2 : B_CS), 0);
        mbar_wait(bar + B_STAT, layer & 1);
        mbar_wait(bar + B_FULLS + 16, layer & 1);
        wgmma_fence();
        wgmma_n256_k(acc, dap, dbp, 1);
#pragma unroll
        for (int k = 0; k < 4; ++k) wgmma_n256(acc, D128(dA0 + (QA >> 8) * 1024 + k * 2), D128(dB0 + (QK >> 8) * 1024 + k * 128), 1);
        mbar_wait(bar + B_FULLS, 1);
        PROFT(tid_ == 128, layer * 16 + 9);
        wgmma_fence();
#pragma unroll
        for (int k = 0; k < 4; ++k) wgmma_n256(acc, D128(dA0 + (QA & 15) * 1024 + k * 2), D128(dB0 + (QK & 15) * 1024 + k * 128), 1);
        wgmma_commit();
        if (wu) nbar<6, 256>();
#define Q_TAIL() \
        wgmma_n128_k(acc, dap, dbp + 256, 1); \
        _Pragma("unroll") for (int k = 0; k < 4; ++k) wgmma_n128(acc, D128(dA0 + (QA >> 8) * 1024 + k * 2), D128(dB0 + (QQ >> 8) * 1024 + k * 128), 1); \
        _Pragma("unroll") for (int k = 0; k < 4; ++k) wgmma_n128(acc, D128(dA0 + (QA & 15) * 1024 + k * 2), D128(dB0 + (QQ & 15) * 1024 + k * 128), 1);
        Q_TAIL();
        wgmma_commit();
        wgmma_wait<1>();
#pragma unroll
        for (int i = 0; i < 128; ++i) asm volatile("" : "+f"(acc[i]) :: "memory");
      }
    }
    uint32_t xo[32];
    uint32_t oq[8][4];
    {
      PHASE_CTX();
      PROFT(tid_ == 128, layer * 16 + 1);
      const bool isB = layer & 1;
      const int cu = c.cu;
      if (cu >= 4) asm volatile("bar.arrive 7, 256;" ::: "memory");
      if (elected && cu == 4) mbar_arrive(bar + B_R0);
      uint32_t kq[64];
      const uint32_t rowq = rowo & 8191;
      const float rs0 = lds_f(sb + SM_RS + (16 + wrow0 + gq) * 4), rs1 = lds_f(sb + SM_RS + (24 + wrow0 + gq) * 4);
#define Q_DONE() \
      wgmma_wait<0>(); \
      if (lane == 0) release2(bar + B_E0); \
      _Pragma("unroll") for (int i = 128; i < 192; ++i) asm volatile("" : "+f"(acc[i]) :: "memory"); \
      _Pragma("unroll") for (int i = 0; i < 32; ++i) kq[32 + i] = pack_bf16(acc[128 + 2 * i], acc[129 + 2 * i]);
      if (isB) {
        if (cu == 0) asm volatile("bar.arrive 10, 64;" ::: "memory");
        if (elected) release2(bar + B_E1);
        const int e = gq & 1;
        const bool sel = t > (gq >> 1);
        const uint32_t rja = sb + SM_RS + (wrow0 + 2 * t + e) * 4;
        const float rjA0 = lds_f(rja + 32), rjA1 = lds_f(rja + 64), rjB0 = lds_f(rja + (sel ? 0 : 64)), rjB1 = lds_f(rja + (sel ? 32 : 96));
        uint32_t vv[32];
#pragma unroll
        for (int i = 0; i < 16; ++i) { kq[i] = pack_bf16(acc[2 * i], acc[2 * i + 1]); vv[i] = pack_bf16(acc[64 + 2 * i], acc[65 + 2 * i]); }
        const uint32_t rB = sb + 4 * SLOT + wg * 4 * KVT + rowq;
        auto prev = [&](int hp) { return cu == 4 ? rB - 4 * KVT + 8192 + 2 * hp * KVT : rB + 2 * (hp ^ wg) * KVT; };
        auto dump = [&](int hp) {
          const uint32_t kb = rB + 2048 + (hp ^ wg) * 2 * KVT;
#pragma unroll
          for (int jp = 0; jp < 4; ++jp) {
            stsm_x4(kb + (X ^ (jp << 5)), kq[16 * hp + 4 * jp], kq[16 * hp + 4 * jp + 1], kq[16 * hp + 4 * jp + 2], kq[16 * hp + 4 * jp + 3]);
            stsm_x4(kb + KVT + (X ^ (jp << 5)), vv[16 * hp + 4 * jp], vv[16 * hp + 4 * jp + 1], vv[16 * hp + 4 * jp + 2], vv[16 * hp + 4 * jp + 3]);
          }
          if (cu == 3) {
            if (hp) asm volatile("bar.arrive 15, 64;" ::: "memory"); else asm volatile("bar.arrive 9, 64;" ::: "memory");
          }
          asm volatile("bar.arrive %0, 224;" :: "r"(hp ? 13 + (cu >> 2) : 8 + (cu & 4)) : "memory");
        };
        uint4* const hbuf = g_halo + ((c.rb * 8 + g) * 2 + (layer >> 1)) * 512 + lane;
        if (cu < 4) {
          nbar<7, 256>();
          dump(0);
        }
#pragma unroll
        for (int i = 16; i < 32; ++i) { kq[i] = pack_bf16(acc[2 * i], acc[2 * i + 1]); vv[i] = pack_bf16(acc[64 + 2 * i], acc[65 + 2 * i]); }
        if (cu >= 4) {
          if (cu == 7) {
#pragma unroll
            for (int jp = 0; jp < 8; ++jp) {
              st_relaxed4(hbuf + jp * 32, ~kq[4 * jp], ~kq[4 * jp + 1], ~kq[4 * jp + 2], ~kq[4 * jp + 3]);
              st_relaxed4(hbuf + 256 + jp * 32, ~vv[4 * jp], ~vv[4 * jp + 1], ~vv[4 * jp + 2], ~vv[4 * jp + 3]);
            }
          }
          dump(0);
          dump(1);
        }
        PROFT(tid_ == 128, layer * 16 + 2);
        constexpr float SC = 0.17677669529663687f * L2E;
        const float fA0 = rjA0 * rs0 * SC, fB0 = rjB0 * rs0 * SC, fA1 = rjA1 * rs1 * SC, fB1 = rjB1 * rs1 * SC;
        const float bA0 = (m0 + wrow0) ? 0.f : -1e30f, bB = sel ? bA0 : 0.f;
        const uint32_t pA_ = e ? 0x1044u : 0x4410u, pB_ = e ? 0x3244u : 0x4432u, pLo = sel ? pB_ : 0x4444u, pHi = sel ? 0x4444u : pB_;
        const uint32_t KX = ((lane >> 3) ^ (lane & 7)) << 4;
        Q_DONE();
        if (cu == 0) {
          nbar<11, 64>();
        } else if (cu == 4) {
          uint4 hv[16];
          if (c.rb > 0) {
            uint32_t n = 0;
#pragma unroll 1
            while (true) {
              uint32_t mn = 0xFFFFFFFFu;
#pragma unroll
              for (int i = 0; i < 16; ++i) hv[i] = ld_relaxed4(hbuf - 16 * 512 + i * 32);
#pragma unroll
              for (int i = 0; i < 16; ++i) mn = __vimin3_u32(__vimin3_u32(mn, hv[i].x, hv[i].y), hv[i].z, hv[i].w);
              if (__all_sync(0xffffffffu, mn != 0u)) break;
              if (++n > (1u << 20)) { g_err = 4u; break; }
            }
          } else {
#pragma unroll
            for (int i = 0; i < 16; ++i) hv[i] = make_uint4(~0u, ~0u, ~0u, ~0u);
          }
          nbar<10, 64>();
#pragma unroll
          for (int i = 0; i < 16; ++i)
            stsm_x4(rB - 4 * KVT + (((i >> 2) & 1) * 2 + (i >> 3)) * KVT + (X ^ ((i & 3) << 5)), ~hv[i].x, ~hv[i].y, ~hv[i].z, ~hv[i].w);
          asm volatile("bar.arrive 11, 64;" ::: "memory");
          nbar<9, 64>();
        } else {
          nbar_dyn(8 + (cu & 4), 224);
        }
        PROFT(tid_ == 128, layer * 16 + 5);
        PROFT(lane == 0 && layer == PL, 136 + cw);
        uint32_t kb[2][2][4], vb[2][2][2][4];
        float oa[2][4][4], sm[2][2];
        auto att_load = [&](int hp) {
          const uint32_t kt = prev(hp) - (lane & 8) * 128, vt = rB + (2 * (hp ^ wg) + 1) * KVT + 2048;
          __syncwarp();
#pragma unroll
          for (int h = 0; h < 2; ++h)
#pragma unroll
            for (int nt = 0; nt < 2; ++nt) ldsm_x4(kb[h][nt][0], kb[h][nt][1], kb[h][nt][2], kb[h][nt][3], kt + nt * 1024 + (KX ^ (h << 6)));
#pragma unroll
          for (int ks = 0; ks < 2; ++ks)
#pragma unroll
            for (int np = 0; np < 2; ++np)
#pragma unroll
              for (int h = 0; h < 2; ++h)
                ldsm_x4_t(vb[h][ks][np][0], vb[h][ks][np][1], vb[h][ks][np][2], vb[h][ks][np][3], (ks ? vt : prev(hp) + KVT) + (X ^ (h << 6) ^ (np << 5)));
          if (hp == 0 && lane == 0) release2(bar + B_E3);
        };
        auto att_mid = [&](int hp) {
          float la[2][2], lb[2][2], mx[2][2];
#pragma unroll
          for (int h = 0; h < 2; ++h) {
            const int qo = 32 + 16 * hp + 8 * h, ko = 16 * hp + 8 * h;
            float sc[4][4];
#pragma unroll
            for (int nt = 0; nt < 4; ++nt) {
              sc[nt][0] = sc[nt][1] = sc[nt][2] = sc[nt][3] = 0.f;
#pragma unroll
              for (int ks = 0; ks < 2; ++ks)
                mma_bf16(sc[nt], kq[qo + 4 * ks], kq[qo + 4 * ks + 1], kq[qo + 4 * ks + 2], kq[qo + 4 * ks + 3],
                         nt < 2 ? kb[h][nt & 1][2 * ks] : kq[ko + 4 * ks + (nt & 1)], nt < 2 ? kb[h][nt & 1][2 * ks + 1] : kq[ko + 4 * ks + 2 + (nt & 1)]);
            }
            la[h][0] = fmaf(e ? sc[1][1] : sc[1][0], fA0, bA0);
            lb[h][0] = fmaf(sel ? (e ? sc[0][1] : sc[0][0]) : (e ? sc[2][1] : sc[2][0]), fB0, bB);
            la[h][1] = (e ? sc[2][3] : sc[2][2]) * fA1;
            lb[h][1] = fmaf(sel ? (e ? sc[1][3] : sc[1][2]) : (e ? sc[3][3] : sc[3][2]), fB1, bB);
            mx[h][0] = fmaxf(la[h][0], lb[h][0]); mx[h][1] = fmaxf(la[h][1], lb[h][1]);
          }
#pragma unroll
          for (int o = 1; o <= 2; o <<= 1)
#pragma unroll
            for (int h = 0; h < 2; ++h)
#pragma unroll
              for (int r = 0; r < 2; ++r) mx[h][r] = fmaxf(mx[h][r], __shfl_xor_sync(0xffffffffu, mx[h][r], o));
#pragma unroll
          for (int h = 0; h < 2; ++h) {
#pragma unroll
            for (int r = 0; r < 2; ++r) { la[h][r] = ex2(la[h][r] - mx[h][r]); lb[h][r] = ex2(lb[h][r] - mx[h][r]); sm[h][r] = la[h][r] + lb[h][r]; }
            const uint32_t p0 = pack_bf16(la[h][0] * rjA0, lb[h][0] * rjB0), p1 = pack_bf16(la[h][1] * rjA1, lb[h][1] * rjB1);
            const uint32_t a00 = __byte_perm(p0, 0u, pLo), a02 = __byte_perm(p0, 0u, pA_), a03 = __byte_perm(p1, 0u, pLo);
            const uint32_t a10 = __byte_perm(p0, 0u, pHi), a11 = __byte_perm(p1, 0u, pA_), a13 = __byte_perm(p1, 0u, pHi);
#pragma unroll
            for (int i = 0; i < 4; ++i) {
              oa[h][i][0] = oa[h][i][1] = oa[h][i][2] = oa[h][i][3] = 0.f;
              mma_bf16(oa[h][i], a00, 0u, a02, a03, vb[h][0][i >> 1][2 * (i & 1)], vb[h][0][i >> 1][2 * (i & 1) + 1]);
              mma_bf16(oa[h][i], a10, a11, 0u, a13, vb[h][1][i >> 1][2 * (i & 1)], vb[h][1][i >> 1][2 * (i & 1) + 1]);
            }
          }
#pragma unroll
          for (int o = 1; o <= 2; o <<= 1)
#pragma unroll
            for (int h = 0; h < 2; ++h)
#pragma unroll
              for (int r = 0; r < 2; ++r) sm[h][r] += __shfl_xor_sync(0xffffffffu, sm[h][r], o);
        };
        auto att_end = [&](int hp) {
          const uint32_t qad = sb + (XS + 1 - hp) * SLOT + rowo;
#pragma unroll
          for (int jp = 0; jp < 4; ++jp) ldsm_x4(xo[16 * hp + 4 * jp], xo[16 * hp + 4 * jp + 1], xo[16 * hp + 4 * jp + 2], xo[16 * hp + 4 * jp + 3], qad + (X ^ (jp << 5)));
#pragma unroll
          for (int h = 0; h < 2; ++h) {
            const float i0 = rcp(sm[h][0]), i1 = rcp(sm[h][1]);
#pragma unroll
            for (int np = 0; np < 2; ++np)
            {
              uint32_t (&o)[4] = oq[4 * hp + 2 * h + np];
              o[0] = pack_bf16(oa[h][2 * np][0] * i0, oa[h][2 * np][1] * i0); o[1] = pack_bf16(oa[h][2 * np][2] * i1, oa[h][2 * np][3] * i1);
              o[2] = pack_bf16(oa[h][2 * np + 1][0] * i0, oa[h][2 * np + 1][1] * i0); o[3] = pack_bf16(oa[h][2 * np + 1][2] * i1, oa[h][2 * np + 1][3] * i1);
              stsm_tag(qad + (X ^ (h << 6) ^ (np << 5)), o[0], o[1], o[2], o[3], make_tag(gq, t, 0u), 2 * h + np);
            }
          }
          {
          __syncwarp();
          slab_out_half(sb + (XS + 1 - hp) * SLOT, g_o + (size_t)m0 * D_ + g * 128 + hp * 64, wrow0, lane);
          __syncwarp();
          if (lane == 0) mbar_arrive(bar + (hp ? B_ODONE : B_OH1));
          }
          PROFT(lane == 0 && layer == PL && hp == 0, 128 + cw);
        };
        att_load(0);
        att_mid(0);
        mbar_wait(bar + B_XOLD, 1);
        att_end(0);
        if (cu < 4) dump(1);
        if (cu == 4) nbar<15, 64>();
        else if (cu != 0) nbar_dyn(13 + (cu >> 2), 224);
        att_load(1);
        att_mid(1);
        mbar_wait(bar + B_XOLD2, 1);
        att_end(1);
      } else {
#pragma unroll
        for (int i = 0; i < 32; ++i) kq[i] = pack_bf16(acc[2 * i], acc[2 * i + 1]);
        if (cu < 4) nbar<7, 256>();
        {
          const uint32_t vb = sb + (5 + 3 * wg) * SLOT + (rowq >> 1) + ((lchk ^ ((lane & 7) >> 1)) << 4);
#pragma unroll
          for (int jp = 8; jp < 16; ++jp)
            stsm_x4((vb ^ ((jp & 1) << 5)) + ((jp >> 1) & 3) * 4096,
                    pack_bf16(acc[8 * jp], acc[8 * jp + 1]), pack_bf16(acc[8 * jp + 2], acc[8 * jp + 3]),
                    pack_bf16(acc[8 * jp + 4], acc[8 * jp + 5]), pack_bf16(acc[8 * jp + 6], acc[8 * jp + 7]));
        }
        PROFT(tid_ == 128, layer * 16 + 2);
        Q_DONE();
        const uint32_t pA = sb + (3 + 3 * wg) * SLOT + (rowo & 8191);
        float sc0 = rs0 * L2E, sc1 = rs1 * L2E;
        const uint32_t wa0 = sb + SM_WPHI + lrow * 80 + lchk * 16;
        const uint32_t wu = c.cu >> 2, par = (layer >> 1) & 1;
        float p[2][4][4];
        uint32_t raw[2][4][4], ph[2][4][4];
        float kva[20], oab[2][2][20];
        auto kv_start = [&](int hp) {
#pragma unroll
          for (int h = 0; h < 2; ++h)
#pragma unroll
            for (int cp = 0; cp < 4; ++cp)
              stsm_x4(pA + hp * 16384 + h * 8192 + (X ^ (cp << 5)), ph[h][cp][0], ph[h][cp][1], ph[h][cp][2], ph[h][cp][3]);
          PROFT(tid_ == 128, layer * 16 + 11);
          nbar<1, 256>();
          fence_async_smem();
          const uint32_t hu = 2 * hp + wu;
          const uint32_t dP = (((sb + 3 * SLOT + hu * 8192) & 0x3FFFF) >> 4) | (512u << 16);
          const uint32_t dV = (((sb + 5 * SLOT + hu * 4096) & 0x3FFFF) >> 4) | (((SM_SD - 5 * SLOT - hu * 4096) >> 4) << 16);
          wgmma_fence();
#pragma unroll
          for (int ks = 0; ks < 8; ++ks)
            wgmma_n40_tt(kva, desc64(dP + (ks >> 2) * 3072 + (ks & 3) * 128, 0x40000040u),
                         desc64(dV + (ks >> 2) * (3072u - (2816u << 16)) + (ks & 3) * 64, 0x80000020u), ks != 0);
          wgmma_commit();
        };
        auto kv_end = [&](int hp) {
          wgmma_wait<0>();
#pragma unroll
          for (int i = 0; i < 20; ++i) asm volatile("" : "+f"(kva[i]) :: "memory");
          nbar_dyn(3 + wu, 128);
          PROFT(tid_ == 128, layer * 16 + 12);
          const bool od = lane & 1;
#pragma unroll
          for (int i = 0; i < 4; ++i)
            sts128(sb + (3 + hp) * SLOT + (cw * 128 + i * 32 + lane) * 16,
                   make_uint4(__float_as_uint(kva[4 * i]), __float_as_uint(kva[4 * i + 1]), __float_as_uint(kva[4 * i + 2]),
                              __float_as_uint(od == (i >= 2) ? 1.f : kva[4 * i + 3])));
          sts128(sb + (6 + hp) * SLOT + wg * 8192 + (wq * 32 + lane) * 16,
                 make_uint4(__float_as_uint(od ? kva[11] : kva[3]), __float_as_uint(od ? kva[15] : kva[7]), __float_as_uint(od ? kva[18] : kva[16]), __float_as_uint(1.f)));
          __syncwarp();
          if (lane == 0) mbar_arrive(bar + B_KVDONE - hp * 32);
          PROFT(tid_ == 128, layer * 16 + 3);
        };
        const uint4* const kvg = g_kv + (g * 2 + (layer >> 1)) * 2560 + cw * 128 + lane;
        uint4 ub[2][5];
        auto kv_load = [&](int hp) {
          uint4 (&u)[5] = ub[hp];
#pragma unroll
          for (int i = 0; i < 4; ++i) u[i] = ld_relaxed4(kvg + hp * 1280 + i * 32);
          u[4] = ld_relaxed4(kvg + hp * 1280 + 1024 - cw * 96);
        };
        auto kv_conv = [&](int hp) {
          uint4 (&u)[5] = ub[hp];
          PROFT(tid_ == 128 && hp == 0, layer * 16 + 10);
          PROFT(lane == 0 && hp == 1 && layer == PL, 128 + cw);
          if (hp == 0) mbar_wait(bar + B_KVDONE - 32, par);
          const bool od = lane & 1;
          uint32_t n = 0;
#pragma unroll 1
          while (!__all_sync(0xffffffffu, (od ? u[2].w : u[0].w) == 0x41800000u && (od ? u[3].w : u[1].w) == 0x41800000u && u[4].w == 0x41800000u)) {
#pragma unroll 1
            while (__any_sync(0xffffffffu, u[4].w < KVTH) && ++n < (1u << 20)) u[4].w = ld_relaxed(&kvg[hp * 1280 + 1024 - cw * 96].w);
            if (++n > (1u << 20)) { g_err = 6u; break; }
            kv_load(hp);
          }
          PROFT(lane == 0 && hp == 1 && layer == PL, 136 + cw);
          PROFT(tid_ == 128 && hp == 0, layer * 16 + 5);
          if (!od) { u[0].w = u[4].x; u[1].w = u[4].y; } else { u[2].w = u[4].x; u[3].w = u[4].y; }
#pragma unroll
          for (int i = 0; i < 4; i += 2)
            stsm_x4(sb + (5 + 3 * hp) * SLOT + rowo + (X ^ ((i & 2) << 4)),
                    pack_bf16(__uint_as_float(u[i].x), __uint_as_float(u[i].y)), pack_bf16(__uint_as_float(u[i].z), __uint_as_float(u[i].w)),
                    pack_bf16(__uint_as_float(u[i + 1].x), __uint_as_float(u[i + 1].y)), pack_bf16(__uint_as_float(u[i + 1].z), __uint_as_float(u[i + 1].w)));
          const uint32_t z2 = pack_bf16(__uint_as_float(u[4].z), __uint_as_float(u[4].z));
          if (t < 2) sts128(sb + (5 + 3 * hp) * SLOT + (wrow0 + gq + 8 * t) * 128 + ((4 ^ gq) << 4), make_uint4(z2, z2, z2, z2));
        };
        auto o_mma = [&](int hp, const uint32_t (&pq)[2][4][4]) {
          float (&oa)[2][20] = oab[hp];
          PROFT(tid_ == 128 && hp == 1, layer * 16 + 4);
          const uint32_t dK = (((sb + (5 + 3 * hp) * SLOT) & 0x3FFFF) >> 4) | (512u << 16);
          wgmma_fence();
#pragma unroll
          for (int ks = 0; ks < 4; ++ks) {
#pragma unroll
            for (int hh = 0; hh < 2; ++hh) wgmma_n40_rs(oa[hh], pq[hh][ks], D128(dK + hh * 512 + ks * 128), ks != 0);
          }
          wgmma_commit();
        };
        auto o_start = [&](int hp, const uint32_t (&pq)[2][4][4]) {
          kv_conv(hp);
          nbar<1, 256>();
          fence_async_smem();
          o_mma(hp, pq);
        };
        auto o_end = [&](int hp) {
          float (&oa)[2][20] = oab[hp];
          wgmma_wait<0>();
#pragma unroll
          for (int i = 0; i < 20; ++i) asm volatile("" : "+f"(oa[0][i]), "+f"(oa[1][i]) :: "memory");
#pragma unroll
          for (int hh = 0; hh < 2; ++hh) {
            const float i0 = rcp(oa[hh][16] + 1e-6f), i1 = rcp(oa[hh][18] + 1e-6f);
            const uint32_t qad = sb + (3 + hp) * SLOT + rowo, hx = hh << 6;
#pragma unroll
            for (int np = 0; np < 2; ++np)
            {
              uint32_t (&o)[4] = oq[4 * hp + 2 * hh + np];
              o[0] = pack_bf16(oa[hh][8 * np] * i0, oa[hh][8 * np + 1] * i0); o[1] = pack_bf16(oa[hh][8 * np + 2] * i1, oa[hh][8 * np + 3] * i1);
              o[2] = pack_bf16(oa[hh][8 * np + 4] * i0, oa[hh][8 * np + 5] * i0); o[3] = pack_bf16(oa[hh][8 * np + 6] * i1, oa[hh][8 * np + 7] * i1);
              stsm_tag(qad + (X ^ hx ^ (np << 5)), o[0], o[1], o[2], o[3], make_tag(gq, t, 1u), 2 * hh + np);
            }
          }
          {
          __syncwarp();
          slab_out_half(sb + (3 + hp) * SLOT, g_o + (size_t)m0 * D_ + g * 128 + hp * 64, wrow0, lane);
          __syncwarp();
          if (lane == 0) mbar_arrive(bar + (hp ? B_ODONE : B_OH1));
          }
        };
#define XO_LOAD() \
        mbar_wait(bar + B_XOLD, 0); \
        mbar_wait(bar + B_XOLD2, 0); \
        _Pragma("unroll") for (int jp = 0; jp < 8; ++jp) \
          ldsm_x4(xo[4 * jp], xo[4 * jp + 1], xo[4 * jp + 2], xo[4 * jp + 3], sb + (XS + 1 - (jp >> 2)) * SLOT + rowo + (X ^ ((jp & 3) << 5)));
#define SC_RELOAD() \
        sc0 = __uint_as_float(lds_vol(sb + SM_RS + (16 + wrow0 + gq) * 4)) * L2E; sc1 = __uint_as_float(lds_vol(sb + SM_RS + (24 + wrow0 + gq) * 4)) * L2E;
        __syncwarp();
        phi_proj<0>(p, kq, wa0);
        phi_exp(raw[0], p[0], sc0, sc1);
        phi_exp(raw[1], p[1], sc0, sc1);
        phi_proj<16>(p, kq, wa0 + 5120);
        phi_norm<0>(ph, raw, kq, wa0, sc0, sc1, rs0, rs1);
        kv_start(0);
        phi_exp(raw[0], p[0], sc0, sc1);
        kv_end(0);
        XO_LOAD();
        phi_exp(raw[1], p[1], sc0, sc1);
        phi_proj<32>(p, kq, wa0);
        phi_norm<16>(ph, raw, kq, wa0 + 5120, sc0, sc1, rs0, rs1);
        kv_start(1);
        if (lane == 0) release2(bar + B_E3);
        phi_exp(raw[0], p[0], sc0, sc1);
        kv_end(1);
        SC_RELOAD();
        phi_exp(raw[1], p[1], sc0, sc1);
        phi_proj<48>(p, kq, wa0 + 5120);
        phi_norm<32>(ph, raw, kq, wa0, sc0, sc1, 1.f, 1.f);
        kv_load(0);
        phi_exp(raw[0], p[0], sc0, sc1);
        phi_exp(raw[1], p[1], sc0, sc1);
        if ((raw[0][2][0] & raw[0][2][2] & raw[0][3][0] & raw[0][3][2] & raw[1][2][0] & raw[1][2][2] & raw[1][3][0] & raw[1][3][2]) == ~0u) sts_f(sb + SM_EPOCH + 12, 0.f);
        o_start(0, ph);
        kv_load(1);
        o_end(0);
        phi_norm<48>(ph, raw, kq, wa0 + 5120, sc0, sc1, 1.f, 1.f);
        o_start(1, ph);
        o_end(1);
      }
      __syncwarp();
      PROFT(lane == 0 && layer == PL, 216 + cw);
      if (lane == 0) mbar_arrive(bar + B_EPI);
      PROFT(tid_ == 128, layer * 16 + 6);
    }
    {
      PHASE_CTX();
      const uint32_t wu = c.cu >> 2;
      const uint32_t dA0 = (((sb + wu * 8192) & 0x3FFFF) >> 4) | (1u << 16), dB0 = ((sb & 0x3FFFF) >> 4) | (512u << 16);
#pragma unroll
      for (int i = 0; i < 32; ++i) { acc[128 + 2 * i] = bf_lo(xo[i]); acc[129 + 2 * i] = bf_hi(xo[i]); }
      uint64_t ta = ((layer & 1) ? WO_A1 : WO_A0) >> 8, tw = (layer & 1) ? WO_B1 : WO_B0;
      mbar_wait(bar + B_FULLT, layer & 1);
      mbar_wait(bar + B_FULLT + 8, layer & 1);
      PROFT(tid_ == 128 && layer == PL, 160);
      wgmma_fence();
#pragma unroll
      for (int k = 0; k < 8; ++k) wgmma_n128_rs(acc, oq[k], D128(dB0 + ((uint32_t)(tw >> (k & 4)) & 15) * 1024 + (k & 3) * 128), 1);
      wgmma_commit();
      tw >>= 8;
      if (lane == 0) release2(bar + B_E2);
#pragma unroll 1
      for (int i = 2; i < 16; ++i) {
        mbar_wait(bar + B_FULLT + i * 8, layer & 1);
        PROFT(tid_ == 128 && layer == PL, 160 + i);
        tile_check(sb + ((uint32_t)ta & 15) * SLOT, g_o + (size_t)m0 * D_ + ((2 * g + (int)(WOORD >> (4 * i))) & 15) * 64, wrow0, lane, ~layer);
        const uint32_t da = dA0 + ((uint32_t)ta & 15) * 1024, db = dB0 + ((uint32_t)tw & 15) * 1024;
        ta >>= 4; tw >>= 4;
        if (i == 15 && wu) nbar<6, 256>();
        wgmma_fence();
#pragma unroll
        for (int k = 0; k < 4; ++k) wgmma_n128(acc, D128(da + k * 2), D128(db + k * 128), 1);
        wgmma_commit();
        if (i == 15 && !wu) asm volatile("bar.arrive 6, 256;" ::: "memory");
        wgmma_wait<1>();
        if (elected && i < 12) release2(bar + B_CONS + (i - 1) * 8);
        if (elected && (unsigned)(i - 13) < 2u && layer + 1 < NLAYERS) release2(bar + B_EMPTYS + (i - 13) * 8);
      }
      const bool last = layer == NLAYERS - 1;
      Tag xt = make_tag(gq, last ? 4 : t, lds_vol(sb + SM_EPOCH) + layer + 1);
      asm volatile("" : "+r"(xt.me), "+r"(xt.mo), "+r"(xt.tg) :: "memory");
      wgmma_wait<0>();
#pragma unroll
      for (int i = 128; i < 192; ++i) asm volatile("" : "+f"(acc[i]) :: "memory");
      if (elected && !last) release2(bar + B_EMPTYS + 16);
      PROFT(tid_ == 128, layer * 16 + 7);
      X_HALF(0, xt);
      if (last) {
        __syncwarp();
        slab_out_half(sb + XS * SLOT, c.out + (size_t)m0 * D_ + g * 128, wrow0, lane);
        X_HALF(1, (Tag{0u, 0u, 0u}));
        __syncwarp();
        slab_out_half(sb + (XS + 1) * SLOT, c.out + (size_t)m0 * D_ + g * 128 + 64, wrow0, lane);
        __syncwarp();
        if (lane == 0) mbar_arrive(bar + B_XDONE);
        PROFT(tid_ == 128, layer * 16 + 24);
        break;
      }
      __syncwarp();
      slab_out_half(sb + XS * SLOT, g_x + (size_t)m0 * D_ + g * 128, wrow0, lane, true);
      __syncwarp();
      if (lane == 0) mbar_arrive(bar + B_XH0);
      nbar_dyn(3 + wu, 128);
    }
  }
}

__device__ __forceinline__ int kblock0(int i, int g) {
  const int j = i >> 1, p = max(g, NCOM) + j - NCOM;
  return (j < NCOM ? j : p < 8 ? p : p - 8 + NCOM) * 2 + (i & 1);
}

__device__ __forceinline__ int wo_kblock(int m, int g) { return (2 * g + (int)((WOORD >> (4 * m)) & 15)) & 15; }

__global__ void __cluster_dims__(2, 1, 1) __launch_bounds__(384, 1)
mega_kernel(const __grid_constant__ CUtensorMap tm_x0, const __grid_constant__ CUtensorMap tm_x,
            const __grid_constant__ CUtensorMap tm_o,
            const __grid_constant__ CUtensorMap tm_wA, const __grid_constant__ CUtensorMap tm_wB,
            const __grid_constant__ CUtensorMap tm_woA, const __grid_constant__ CUtensorMap tm_woB,
                        const bf16* __restrict__ wB, const bf16* __restrict__ wphi, bf16* __restrict__ out) {
  extern __shared__ uint8_t smem_raw[];
  const uint32_t sb = (smem_u32(smem_raw) + 1023u) & ~1023u;
  const uint32_t bar = sb + SM_BAR;
  const int warp = __shfl_sync(0xffffffffu, threadIdx.x >> 5, 0), lane = threadIdx.x & 31;
  uint32_t bid = blockIdx.x;
  uint32_t nsm;
  asm volatile("mov.u32 %0, %%nsmid;" : "=r"(nsm));
  if (gridDim.x == 128 + NX && nsm == 128 + NX) {
    uint32_t tp;
    asm volatile("mov.u32 %0, %%smid;" : "=r"(tp));
    tp >>= 1;
    const uint32_t u7 = ((tp - 32) * 37) >> 8;
    bid = (tp < 32 ? tp : tp < 60 ? tp + 1 + u7 : tp < 62 ? tp + 4 : (tp - 58) * 8) * 2 + (bid & 1);
  }
  if (bid >= 128 || gridDim.x == NX) {
    const int xb = bid & (NX - 1);
    const int ch = threadIdx.x % 96, rg = threadIdx.x / 96, gg = xb * 2 + ch / 48, sec = (ch % 48) >> 4;
    const uint4* src = reinterpret_cast<const uint4*>(wB + (size_t)rg * 3072 + (sec == 2 ? 0 : 1024 + sec * 1024) + gg * 128 + (ch & 15) * 8);
    float s[8] = {0.f, 0.f, 0.f, 0.f, 0.f, 0.f, 0.f, 0.f};
#pragma unroll 1
    for (int r0 = 0; r0 < 256; r0 += 32) {
      uint4 v[32];
#pragma unroll
      for (int r = 0; r < 32; ++r) v[r] = __ldg(src + (size_t)(r0 + r) * 1536);
#pragma unroll
      for (int r = 0; r < 32; ++r) {
        s[0] += bf_lo(v[r].x); s[1] += bf_hi(v[r].x); s[2] += bf_lo(v[r].y); s[3] += bf_hi(v[r].y);
        s[4] += bf_lo(v[r].z); s[5] += bf_hi(v[r].z); s[6] += bf_lo(v[r].w); s[7] += bf_hi(v[r].w);
      }
    }
    float* cd = g_cs + (ld_relaxed(&g_epoch) & 1) * 6144 + 3072 + xb * 768 + ch * 8;
    red_add4(cd, s[0], s[1], s[2], s[3]);
    red_add4(cd + 4, s[4], s[5], s[6], s[7]);
    nbar<1, 384>();
    if (threadIdx.x < 2) flag_add(&g_csflag[8 + xb * 2 + threadIdx.x].v);
    return;
  }
  const int cr = bid & 1;
  const int g = bid >> 4;
  const int rb = bid & 15;
  const int m0 = rb * 128;

  if (warp < 4) {
    asm volatile("setmaxnreg.dec.sync.aligned.u32 40;");
    asm volatile("barrier.cluster.arrive.relaxed.aligned;" ::: "memory");
    const unsigned int epoch = warp ? ld_relaxed(&g_epoch) : 0u;
    if (warp) cluster_wait();
    unsigned int xbase = epoch * NLAYERS;
    auto wo_a = [&](int layer, int m1) {
      uint64_t ts = ((layer & 1) ? WO_A1 : WO_A0) >> (4 * m1), td = ((layer & 1) ? WO_DA1 : WO_DA0) >> (4 * m1), tk = WOORD >> (4 * m1);
      uint32_t ready = 0u;
#pragma unroll 1
      for (int m = m1; m < 16; ++m) {
        const int kb = (2 * g + (uint32_t)tk) & 15;
        uint32_t dst = sb + ((uint32_t)ts & 15) * SLOT, fb = bar + B_FULLT + m * 8, eb = bar + B_CONS + ((uint32_t)td & 15) * 8;
        int kc = kb * 64;
        ts >>= 4; td >>= 4; tk >>= 4;
        asm volatile("" : "+r"(dst), "+r"(fb), "+r"(eb), "+r"(kc));
        bool fr = false;
        if (!((ready >> kb) & 1)) {
          PROFT(m == 2 && lane == 0, 64 + layer * 16 + 2);
          fr = src_wait_tma(g_of + rb * 32, xbase + layer + 1, 1u << kb, ready, lane, eb, layer & 1);
          fence_async_all();
        }
        if (m == 6) mbar_wait_u(bar + B_EPI, layer & 1);
        if (!fr) mbar_wait_u(eb, layer & 1);
        tma_2d_e(dst, &tm_o, kc, m0, fb);
        PROFT(lane == 0 && layer == PL, 176 + m);
      }
    };
    auto wo_w = [&](int layer) {
      const CUtensorMap* tx = layer == 0 ? &tm_x0 : &tm_x;
      const CUtensorMap* two = (layer & 1) ? &tm_woB : &tm_woA;
      uint64_t ts = (layer & 1) ? WO_B1 : WO_B0, td = (layer & 1) ? WO_DB1 : WO_DB0, tk = WOORD;
      uint32_t pb = 0;
      fence_async_all();
      mbar_wait_u(bar + B_R0, layer & 1);
      expect_tx_e(bar + B_XOLD, 16384);
      tma_2d_e(sb + (XS + 1) * SLOT, tx, g * 128, m0, bar + B_XOLD);
#pragma unroll 1
      for (int m = 0; m < 16; ++m) {
        uint32_t dst = sb + ((uint32_t)ts & 15) * SLOT + cr * 8192, fb = bar + B_FULLT + m * 8, eb = bar + B_CONS + ((uint32_t)td & 15) * 8;
        int kc = ((2 * g + (uint32_t)tk) & 15) * 64;
        ts >>= 4; td >>= 4; tk >>= 4;
        asm volatile("" : "+r"(dst), "+r"(fb), "+r"(eb), "+r"(kc));
        if (eb < bar + B_E3 && pb >= bar + B_E3) mbar_wait_u(bar + B_E2, layer & 1);
        if (eb != pb) mbar_wait_u(eb, layer & 1);
        pb = eb;
        tma_2d_mc_e(dst, two, g * 128 + cr * 64, kc, fb);
        expect_tx_e(fb, m < 2 ? 16384 : 32768);
        PROFT(lane == 0 && layer == PL, 144 + m);
        if (m == ((layer & 1) ? 2 : 0)) {
          expect_tx_e(bar + B_XOLD2, 16384);
          tma_2d_e(sb + XS * SLOT, tx, g * 128 + 64, m0, bar + B_XOLD2);
        }
      }
    };
    if (warp == 0) {
      cluster_wait();
      PROFT(lane == 0, 125);
#pragma unroll 1
      for (int layer = 0; layer < NLAYERS; ++layer) {
        const CUtensorMap* tx = layer == 0 ? &tm_x0 : &tm_x;
        const CUtensorMap* tw = (layer & 1) ? &tm_wB : &tm_wA;
        uint32_t s = layer == 0, u = 0, ready = layer == 0 ? 0xFFFFu : 0u;
#pragma unroll 1
        for (int i = s; i < 16; ++i) {
          const int kb = layer == 0 ? kblock0(i, g) : wo_kblock(i, g), kc = kb * 64;
          const uint32_t fb = bar + B_FULLS + s * 8;
          const uint32_t kd = sb + (((QK >> (4 * s)) & 15) + cr) * SLOT, qd = sb + ((QQ >> (4 * s)) & 15) * SLOT + cr * 8192;
          const uint32_t need = 1u << kb;
          const bool ext = i >= 2 || layer == 0, early = ext && (ready & need) == need;
          mbar_wait_u(bar + B_EMPTYS + s * 8, (u + (s ? layer : 0) + 1) & 1);
          if (early) tma_2d_e(sb + ((QA >> (4 * s)) & 15) * SLOT, tx, kc, m0, fb);
          tma_2d_mc_e(kd, tw, 1024 + cr * 1024 + g * 128, kc, fb);
          tma_2d_mc_e(kd + 8192, tw, 1024 + cr * 1024 + g * 128 + 64, kc, fb);
          tma_2d_mc_e(qd, tw, g * 128 + cr * 64, kc, fb);
          expect_tx_e(fb, ext ? 65536 : 49152);
          PROFT(lane == 0 && layer == 0 && i == 1, 31);
          if (layer == 0 && g >= NCOM && i == XPF + (((g - NCOM) * XPM) >> 2)) {
            if (i <= 2) mbar_wait_u(bar + B_FULLS, 0);
            tma_pf_e(&tm_x0, g * 128, m0);
            tma_pf_e(&tm_x0, g * 128 + 64, m0);
          }
          if (layer < 2 && i >= PFS) {
            const int j = i - PFS;
            if (j < 2) tma_pf_e(layer ? &tm_woB : &tm_woA, g * 128 + j * 64, rb * 64);
            else if (j < 8 && layer == 0) tma_pf_e(&tm_wB, ((j >> 1) - 1) * 1024 + g * 128 + (j & 1) * 64, rb * 64);
          }
          if (ext && !early) {
            PROFT(i == 2 && lane == 0, 64 + layer * 16 + 0);
            src_wait_tma(g_xf + rb * 32, xbase + layer + 1, need, ready, lane, fb, 0);
            PROFT(i == 2 && lane == 0, 64 + layer * 16 + 1);
            fence_async_all();
            tma_2d_e(sb + ((QA >> (4 * s)) & 15) * SLOT, tx, kc, m0, fb);
          }
          if (++s == 3) { s = 0; ++u; }
        }
        if (layer == 0) xbase = ld_relaxed(&g_epoch) * NLAYERS;
        mbar_wait_u(bar + ((layer & 1) ? B_E3 : B_E1), layer & 1);
        wo_a(layer, 2);
      }
    } else {
      if (warp >= 2) {
        const int h2 = threadIdx.x - 64;
        if (h2 < 16) sts_f(sb + SM_RS + h2 * 4, 0.f);
        if (h2 == 0) sts_f(sb + SM_EPOCH, __uint_as_float(epoch));
        mbar_wait_u(bar + B_FULLS, 0);
        colsum(&tm_wA, g_cs + (epoch & 1) * 6144, rb, g, warp - 2, 2, lane, warp == 2 ? sb + SM_SD : (sb + SM_BP + 1023u) & ~1023u, bar + B_CB + (warp - 2) * 8, 0);
#pragma unroll 1
        for (int i = h2; i < 320; i += 64) g_kv[(g * 16 + rb) * 320 + i] = make_uint4(0u, 0u, 0u, 0u);
        fence_async_all();
        nbar<5, 64>();
        if (h2 == 0) flag_add(&g_csflag[g].v);
        PROFT(h2 == 0, 242);
#pragma unroll 1
        for (int i = h2; i < 512; i += 256) {
          uint4 w[4];
#pragma unroll
          for (int j = 0; j < 4; ++j) w[j] = __ldg(reinterpret_cast<const uint4*>(wphi + (size_t)g * 4096) + i + j * 64);
#pragma unroll
          for (int j = 0; j < 4; ++j) sts128(sb + SM_WPHI + ((i >> 2) + j * 16) * 80 + (i & 3) * 16, w[j]);
        }
      }
      if (warp == 1) {
        if (lane >= 27) {
          const CUtensorMap* tm = lane == 27 ? &tm_o : lane == 28 ? &tm_wB : lane == 29 ? &tm_woA : lane == 30 ? &tm_woB : &tm_x;
          asm volatile("prefetch.tensormap [%0];" ::"l"(tm) : "memory");
        }
        __syncwarp();
        {
#pragma unroll 1
          for (int e = 0;; ++e) {
            if (e > 0 && e < NLAYERS) {
              mbar_wait_u(bar + B_XH0, (e - 1) & 1);
              flag_hint(g_xf + rb * 32 + 2 * g, xbase + e + 1);
            }
            mbar_wait_u(bar + B_XDONE, e & 1);
            PROFT(e < 4, 64 + e * 16 + 4);
            if (e == NLAYERS) {
              if (bid == 0) g_epoch = epoch + 1;
              break;
            }
            PROFT(e < 4, 64 + e * 16 + 5);
            flag_set(g_xf + rb * 32 + 2 * g + 1, xbase + e + 1);
            PROFT(e < 4, 64 + e * 16 + 7);
            if ((e & 1) == 0) {
#pragma unroll 1
              for (int hp = 0; hp < 2; ++hp) {
                uint4* kvl = g_kv + ((g * 2 + (e >> 1)) * 2 + hp) * 1280;
                mbar_wait_u(bar + B_KVDONE - hp * 32, (e >> 1) & 1);
                PROFT(e == PL, 243 + hp * 4);
                fence_async_smem();
                bulk_red_add_e(kvl + rb * 64, sb + (3 + hp) * SLOT + rb * 1024, 16384 - rb * 1024);
                if (rb) bulk_red_add_e(kvl, sb + (3 + hp) * SLOT, rb * 1024);
                bulk_red_add_e(kvl + 1024, sb + (6 + hp) * SLOT, 2048);
                bulk_red_add_e(kvl + 1152, sb + (6 + hp) * SLOT + 8192, 2048);
                bulk_commit();
                PROFT(e < 4, 64 + e * 16 + 6);
              }
              bulk_wait_read0();
              __syncwarp();
              if (lane < 2) release2(bar + B_E1);
              __syncwarp();
            }
            mbar_wait_u(bar + B_OH1, e & 1);
            PROFT(e == PL, 251);
            flag_hint(g_of + rb * 32 + 2 * g, xbase + e + 1);
            PROFT(e < 4, 64 + e * 16 + 9);
            mbar_wait_u(bar + B_ODONE, e & 1);
            PROFT(e < 4, 64 + e * 16 + 8);
            flag_hint(g_of + rb * 32 + 2 * g + 1, xbase + e + 1);
            PROFT(e < 4, 64 + e * 16 + 11);
          }
        }
      } else {
        const int h2 = threadIdx.x - 64;
        const float* cs = g_cs + (epoch & 1) * 6144;
#pragma unroll 1
        for (int layer = 0; layer < NLAYERS; ++layer) {
          if (warp == 2 && layer < 2) {
            if (layer) mbar_wait_u(bar + B_XH0, 0);
            if (lane == 0) flag_wait_t<128>(&g_csflag[layer * 8 + g].v, (epoch + 1) * (16u + layer));
            __syncwarp();
            float4 a[3];
#pragma unroll
            for (int i = 0; i < 3; ++i) a[i] = __ldcg(reinterpret_cast<const float4*>(cs + layer * 3072 + g * 384) + i * 32 + lane);
#pragma unroll 1
            for (int i = 0; i < 3; ++i) {
              const float av[4] = {a[0].x, a[0].y, a[0].z, a[0].w};
              a[0] = a[1]; a[1] = a[2];
#pragma unroll
              for (int j = 0; j < 4; ++j) {
                const float c1 = bf16r(av[j]), c2 = bf16r(av[j] - c1), c3 = (av[j] - c1) - c2;
                sts128(sb + SM_BP + layer * 6144 + ((i * 32 + lane) * 4 + j) * 16, make_uint4(pack_bf16(c1, c2), pack_bf16(c3, 0.f), 0u, 0u));
              }
            }
            fence_async_smem();
            __syncwarp();
            if (lane == 0) mbar_arrive(bar + (layer ? B_CS2 : B_CS));
            PROFT(lane == 0, 64 + layer * 16 + 12);
            if (layer == 0) {
              uint4* hz = g_halo + (rb * 8 + g) * 1024;
#pragma unroll 2
              for (int i = lane; i < 1024; i += 32) hz[i] = make_uint4(0u, 0u, 0u, 0u);
              if (lane < 12) reinterpret_cast<float4*>(g_cs + ((epoch & 1) ^ 1) * 6144 + bid * 48)[lane] = make_float4(0.f, 0.f, 0.f, 0.f);
              g_stats[(2 + (lane >> 4)) * S_ + m0 + g * 16 + (lane & 15)] = make_float2(0.f, 0.f);
              __syncwarp();
              if (lane == 0) flag_add(&g_csflag[8 + g].v);
            }
          }
          if (warp == 3) {
            const bool hal = (layer & 1) && rb > 0;
            mbar_wait_u(bar + B_XDONE, layer & 1);
            {
              uint32_t rdy = 0u;
              src_wait<256>(g_xf + rb * 32, xbase + layer + 1, 0xAAAAu, rdy, lane);
              rdy = 0u;
              if (hal) src_wait<256>(g_xf + (rb - 1) * 32, xbase + layer + 1, 0xAAAAu, rdy, lane);
            }
            float2 u[5];
            const float2* sp = g_stats + layer * S_ + m0 + lane;
#pragma unroll
            for (int i = 0; i < 4; ++i) u[i] = __ldcg(sp + i * 32);
            u[4] = __ldcg(hal ? sp - 16 : sp);
            if (layer == 3) g_stats[(lane >> 4) * S_ + m0 + g * 16 + (lane & 15)] = make_float2(0.f, 0.f);
#pragma unroll
            for (int i = 0; i < 5; ++i) {
              const int r = i < 4 ? 16 + i * 32 + lane : lane;
              const float mean = u[i].x * (1.f / D_);
              const float var = fmaxf(fmaf(-u[i].x, mean, u[i].y) * (1.f / D_), 0.f);
              float sd;
              asm("sqrt.approx.f32 %0, %1;" : "=f"(sd) : "f"(bf16r(bf16r(var) + 1e-5f)));
              sd = bf16r(sd);
              if (i < 4 || hal) sts_f(sb + SM_RS + r * 4, rcp(sd));
              if (i < 4) {
                const float hm = -0.5f * bf16r(mean);
                const uint32_t s2 = pack_bf16(sd, sd);
                if (!(layer & 1)) sts128(sb + SM_SD + (r - 16) * 64 + ((r >> 1) & 3) * 16, make_uint4(s2, s2, s2, s2));
                sts128(sb + SM_AP + (r - 16) * 16, make_uint4(pack_bf16(hm, hm), pack_bf16(hm, 0.f), 0u, 0u));
              }
            }
            fence_async_smem();
            __syncwarp();
            if (lane == 0) mbar_arrive(bar + B_STAT);
            PROFT(lane == 0, 64 + layer * 16 + 14);
            wo_w(__shfl_sync(0xffffffffu, layer, 0));
          }
        }
      }
    }
    __syncwarp();
    asm volatile("barrier.cluster.arrive.relaxed.aligned;\nbarrier.cluster.wait.aligned;\n" ::: "memory");
  } else {
    if (warp == 5) {
      if (lane == 0) {
        mbar_init(bar + B_FULLS, 1);
        asm volatile("fence.mbarrier_init.release.cluster;" ::: "memory");
      }
      __syncwarp();
      expect_tx_e(bar + B_FULLS, 65536);
      tma_2d_e(sb + XS * SLOT, &tm_x0, 0, m0, bar + B_FULLS);
#pragma unroll
      for (int j = 0; j < 6; ++j)
        tma_2d_e(sb + (j < 4 ? j + 4 : j - 2) * 8192, &tm_wA, (j < 4 ? 1024 + (j >> 1) * 1024 : 0) + g * 128 + (j & 1) * 64, 0, bar + B_FULLS);
      PROFT(lane == 0, 241);
    }
    if (lane < 8 && warp != 5 && threadIdx.x != 128) {
      const int i = (warp - 4) * 8 + lane;
      mbar_init(bar + i * 8, i < 32 ? 1u << ((BAR_CNT >> (2 * i)) & 3) : i < 48 ? 1u : (i == 59 || i == 60 || i == 62) ? 16u : (i == 48 || i == 63) ? 8u : 4u);
      asm volatile("fence.mbarrier_init.release.cluster;" ::: "memory");
    }
    __syncwarp();
    asm volatile("barrier.cluster.arrive.relaxed.aligned;" ::: "memory");
    asm volatile("setmaxnreg.inc.sync.aligned.u32 232;");
    cluster_wait();
    PROFT(threadIdx.x == 128, 0);
    Ctx c; c.sb = sb; c.g = g; c.rb = rb; c.cu = warp - 4; c.out = out;
    consumer(c);
    asm volatile("bar.warp.sync 0xffffffff;\nbarrier.cluster.arrive.relaxed.aligned;\nbarrier.cluster.wait.aligned;\n" ::: "memory");
  }
}

typedef CUresult (*PFN_encodeTiled)(CUtensorMap*, CUtensorMapDataType, cuuint32_t, void*, const cuuint64_t*, const cuuint64_t*,
                                    const cuuint32_t*, const cuuint32_t*, CUtensorMapInterleave, CUtensorMapSwizzle,
                                    CUtensorMapL2promotion, CUtensorMapFloatOOBfill);

static CUtensorMap make_map(PFN_encodeTiled enc, const void* ptr, uint64_t cols, uint64_t rows, uint32_t box_c, uint32_t box_r) {
  CUtensorMap m;
  cuuint64_t dims[2] = {cols, rows};
  cuuint64_t strides[1] = {cols * 2};
  cuuint32_t box[2] = {box_c, box_r};
  cuuint32_t es[2] = {1, 1};
  CUresult r = enc(&m, CU_TENSOR_MAP_DATA_TYPE_BFLOAT16, 2, const_cast<void*>(ptr), dims, strides, box, es, CU_TENSOR_MAP_INTERLEAVE_NONE,
      CU_TENSOR_MAP_SWIZZLE_128B, CU_TENSOR_MAP_L2_PROMOTION_L2_128B, CU_TENSOR_MAP_FLOAT_OOB_FILL_NONE);
  (void)r;
  return m;
}

extern "C" void kernel_launch(void* const* d_in, const int* in_sizes, int n_in, void* d_out, int out_size) {
  const bf16* A_x = (const bf16*)d_in[0];
  const bf16* A_wqkv = (const bf16*)d_in[1];
  const bf16* A_wphi = (const bf16*)d_in[2];
  const bf16* A_wo = (const bf16*)d_in[3];
  const bf16* B_wqkv = (const bf16*)d_in[5];
  const bf16* B_wo = (const bf16*)d_in[6];
  bf16* out = (bf16*)d_out;

  static PFN_encodeTiled enc = nullptr;
  static bf16 *p_x, *p_o;
  static bool together;
  if (!enc) {
    void* fn = nullptr; cudaDriverEntryPointQueryResult qr;
    cudaGetDriverEntryPoint("cuTensorMapEncodeTiled", &fn, cudaEnableDefault, &qr);
    enc = (PFN_encodeTiled)fn;
    cudaGetSymbolAddress((void**)&p_x, g_x);
    cudaGetSymbolAddress((void**)&p_o, g_o);
    cudaFuncSetAttribute(mega_kernel, cudaFuncAttributeMaxDynamicSharedMemorySize, SM_TOTAL);
    cudaLaunchConfig_t cfg = {};
    cfg.gridDim = dim3(128 + NX); cfg.blockDim = dim3(384); cfg.dynamicSmemBytes = SM_TOTAL;
    cudaLaunchAttribute at[1];
    at[0].id = cudaLaunchAttributeClusterDimension; at[0].val.clusterDim.x = 2; at[0].val.clusterDim.y = 1; at[0].val.clusterDim.z = 1;
    cfg.attrs = at; cfg.numAttrs = 1;
    int ncl = 0;
    together = cudaOccupancyMaxActiveClusters(&ncl, mega_kernel, &cfg) == cudaSuccess && 2 * ncl == 128 + NX;
    int nsm = 0;
    cudaDeviceGetAttribute(&nsm, cudaDevAttrMultiProcessorCount, 0);
    together = together && nsm == 128 + NX;
  }
  CUtensorMap tm_x0 = make_map(enc, A_x, 1024, 2048, 64, 128);
  CUtensorMap tm_x = make_map(enc, p_x, 1024, 2048, 64, 128);
  CUtensorMap tm_o = make_map(enc, p_o, 1024, 2048, 64, 128);
  CUtensorMap tm_wA = make_map(enc, A_wqkv, 3072, 1024, 64, 64);
  CUtensorMap tm_wB = make_map(enc, B_wqkv, 3072, 1024, 64, 64);
  CUtensorMap tm_woA = make_map(enc, A_wo, 1024, 1024, 64, 64);
  CUtensorMap tm_woB = make_map(enc, B_wo, 1024, 1024, 64, 64);
  if (!together) mega_kernel<<<NX, 384, SM_TOTAL, cudaStreamPerThread>>>(tm_x0, tm_x, tm_o, tm_wA, tm_wB, tm_woA, tm_woB, B_wqkv, A_wphi, out);
  mega_kernel<<<together ? 128 + NX : 128, 384, SM_TOTAL, cudaStreamPerThread>>>(tm_x0, tm_x, tm_o, tm_wA, tm_wB, tm_woA, tm_woB,
                                                                                 B_wqkv, A_wphi, out);
}
```
